```python
import torch

def _softmax(x, axis=-1):
    return torch.softmax(x, dim=axis)
def _gelu(x):
    return torch.nn.functional.gelu(x, approximate="tanh")
def _silu(x):
    return torch.nn.functional.silu(x)
def _sigmoid(x):
    return torch.sigmoid(x)
def _layernorm(x, axis=-1, eps=1e-5):
    m = x.mean(dim=axis, keepdim=True)
    v = x.var(dim=axis, keepdim=True, unbiased=False)
    return (x - m) / torch.sqrt(v + eps)
def _scatter_add(tgt, idx, src, axis=0):
    return tgt.clone().index_add_(axis, idx, src)
def _segment_sum(src, seg, n):
    out = torch.zeros((n,) + src.shape[1:], dtype=src.dtype)
    return out.index_add_(0, seg, src)
def _pad(x, pw):
    flat = tuple(v for pair in reversed(pw) for v in pair)
    return torch.nn.functional.pad(x, flat)

kernel_name = 'gated_mix__compressed_kv_cla__sliding_local_dilated__prompt'

def setup_inputs():

    _w = (lambda a: (lambda t: t.to(torch.bfloat16) if t.is_floating_point() else t)(torch.as_tensor(a)))
    def _A_setup():
        B, H, Sq, Sk, D, M = 1, 32, 2048, 2048, 128, 1024
        Dc = 4 * D
        return {
            "x": _w((lambda *s: torch.randn(*s, dtype=torch.bfloat16) * 0.05)(B, Sq, M)),
            "c_kv": _w((lambda *s: torch.randn(*s, dtype=torch.bfloat16) * 1.6)(B, Sk, Dc)),
            "w_q": _w((lambda *s: torch.randn(*s, dtype=torch.bfloat16) * 6.4)(M, H, D) * (M ** -0.5)),
            "w_uk": _w((lambda *s: torch.randn(*s, dtype=torch.bfloat16) * 6.4)(Dc, H, D) * (Dc ** -0.5)),
            "w_uv": _w((lambda *s: torch.randn(*s, dtype=torch.bfloat16) * 1.6)(Dc, H, D) * (Dc ** -0.5)),
            "w_o": _w((lambda *s: torch.randn(*s, dtype=torch.bfloat16) * 1.6)(H, D, M) * ((H * D) ** -0.5)),
        }
    _A_in = _A_setup()

    def _B_setup():
        B, S, D = 1, 2048, 1024
        return {
            "x": _w((lambda *s: torch.randn(*s, dtype=torch.bfloat16) * 0.05)(B, S, D)),
            "wqkv": _w((lambda *s: torch.randn(*s, dtype=torch.bfloat16) * 0.8)(D, 3 * D)),
            "wo": _w((lambda *s: torch.randn(*s, dtype=torch.bfloat16) * 0.05)(D, D)),
        }
    _B_in = _B_setup()

    return {
        "A_x": _A_in["x"],
        "A_c_kv": _A_in["c_kv"],
        "A_w_q": _A_in["w_q"],
        "A_w_uk": _A_in["w_uk"],
        "A_w_uv": _A_in["w_uv"],
        "A_w_o": _A_in["w_o"],
        "B_x": _B_in["x"],
        "B_wqkv": _B_in["wqkv"],
        "B_wo": _B_in["wo"],
        "gate_w": _w((lambda *s: torch.randn(*s, dtype=torch.bfloat16) * 0.05)(1024) * 16.0),
    }

def reference(A_x, A_c_kv, A_w_q, A_w_uk, A_w_uv, A_w_o, B_x, B_wqkv, B_wo, gate_w):
    def _A_ref(x, c_kv, w_q, w_uk, w_uv, w_o):
        B, Sq, M = x.shape[0], x.shape[1], x.shape[2]
        Sk = c_kv.shape[1]
        H, D = w_q.shape[1], w_q.shape[2]
        q = torch.einsum("bqm,mhd->bhqd", x, w_q)
        k = torch.einsum("bkc,chd->bhkd", c_kv, w_uk)
        v = torch.einsum("bkc,chd->bhkd", c_kv, w_uv)
        scores = torch.einsum("bhqd,bhkd->bhqk", q, k) * (D ** -0.5)
        off = Sk - Sq
        qi = torch.arange(Sq)[:, None]
        kj = torch.arange(Sk)[None, :]
        cmask = kj <= (qi + off)
        scores = torch.where(cmask[None, None], scores, -1e9)
        p = _softmax(scores, axis=-1)
        ctx = torch.einsum("bhqk,bhkd->bhqd", p, v)
        return torch.einsum("bhqd,hdm->bqm", ctx, w_o)

    def _B_ref(x, wqkv, wo):
        B, S, D = x.shape
        H = 32; Dh = D // H
        W, dil = 8, 2
        qkv = (lambda x, *d: x.permute(*d))((x @ wqkv).reshape(B, S, 3, H, Dh), 2, 0, 3, 1, 4)
        q, k, v = qkv[0], qkv[1], qkv[2]
        scale = Dh ** -0.5
        pos = torch.arange(S)
        off = torch.arange(W) * dil
        idx = pos[:, None] - off[None, :]
        mask = idx >= 0
        idx_c = torch.where(mask, idx, 0).reshape(-1)
        kg = k[:, :, idx_c, :].reshape(B, H, S, W, Dh)
        vg = v[:, :, idx_c, :].reshape(B, H, S, W, Dh)
        logits = torch.einsum("bhsd,bhswd->bhsw", q, kg) * scale
        logits = torch.where(mask[None, None, :, :], logits, -1e9)
        attn = _softmax(logits, axis=-1)
        o = torch.einsum("bhsw,bhswd->bhsd", attn, vg)
        return (lambda x, *d: x.permute(*d))(o, 0, 2, 1, 3).reshape(B, S, D) @ wo

    x = A_x
    g = _sigmoid((x * gate_w).sum(-1, keepdims=True))
    a = _A_ref(x, A_c_kv, A_w_q, A_w_uk, A_w_uv, A_w_o)
    b = _B_ref(x, B_wqkv, B_wo)
    return g * a + (1 - g) * b
```

```cpp
#include <cuda_runtime.h>
#include <cuda_bf16.h>
#include <cuda.h>
#include <stdint.h>
#include <type_traits>

namespace {

constexpr int SEQ = 2048;
constexpr int G_Q = 0, G_K = 32, G_V = 64, G_B = 96, G_CTX = G_Q, G_LOC = G_B, G_PART = 120, G_TOTAL = 128;

__device__ __align__(1024) __nv_bfloat16 g_scr[(size_t)G_TOTAL * SEQ * 128];
__device__ __align__(128) float g_gate[SEQ];

__device__ __forceinline__ uint32_t smem_u32(const void* p) { return (uint32_t)__cvta_generic_to_shared(p); }
__device__ __forceinline__ bool elect_one() {
    uint32_t p;
    asm volatile("{\n.reg .pred P;\nelect.sync _|P, 0xffffffff;\nselp.u32 %0, 1, 0, P;\n}\n" : "=r"(p));
    return p != 0;
}
__device__ __forceinline__ void mbar_init(uint32_t bar, uint32_t count) {
    asm volatile("mbarrier.init.shared::cta.b64 [%0], %1;" :: "r"(bar), "r"(count) : "memory");
}
__device__ __forceinline__ void mbar_expect_tx(uint32_t bar, uint32_t bytes) {
    asm volatile("mbarrier.arrive.expect_tx.shared::cta.b64 _, [%0], %1;" :: "r"(bar), "r"(bytes) : "memory");
}
__device__ __forceinline__ uint32_t cluster_rank() { uint32_t r; asm("mov.u32 %0, %%cluster_ctarank;" : "=r"(r)); return r; }
__device__ __forceinline__ uint32_t map_cta(uint32_t addr, uint32_t cta) {
    uint32_t r; asm("mapa.shared::cluster.u32 %0, %1, %2;" : "=r"(r) : "r"(addr), "r"(cta)); return r;
}
__device__ __forceinline__ void mbar_arrive_cluster_if(bool pred, uint32_t cluster_bar) {
    asm volatile("{\n.reg .pred P;\nsetp.ne.u32 P, %1, 0;\n@P mbarrier.arrive.shared::cluster.b64 _, [%0];\n}\n"
                 :: "r"(cluster_bar), "r"((uint32_t)pred) : "memory");
}
__device__ __forceinline__ void mbar_arrive_cluster_n_if(bool pred, uint32_t cluster_bar, uint32_t count) {
    asm volatile("{\n.reg .pred P;\nsetp.ne.u32 P, %1, 0;\n@P mbarrier.arrive.shared::cluster.b64 _, [%0], %2;\n}\n"
                 :: "r"(cluster_bar), "r"((uint32_t)pred), "r"(count) : "memory");
}
__device__ __forceinline__ void mbar_arrive_if(bool pred, uint32_t bar) {
    asm volatile("{\n.reg .pred P;\nsetp.ne.u32 P, %1, 0;\n@P mbarrier.arrive.shared::cta.b64 _, [%0];\n}\n"
                 :: "r"(bar), "r"((uint32_t)pred) : "memory");
}
__device__ __forceinline__ bool mbar_test(uint32_t bar, uint32_t parity) {
    uint32_t ok;
    asm volatile("{\n.reg .pred P;\nmbarrier.test_wait.parity.shared::cta.b64 P, [%1], %2;\nselp.u32 %0, 1, 0, P;\n}\n"
                 : "=r"(ok) : "r"(bar), "r"(parity) : "memory");
    return ok != 0;
}
__device__ __forceinline__ void mbar_wait(uint32_t bar, uint32_t parity) {
    asm volatile("{\n.reg .pred P;\n.reg .u32 c;\n"
                 "mbarrier.try_wait.parity.shared::cta.b64 P, [%0], %1;\n"
                 "@P bra DONE;\n"
                 "mov.u32 c, 0;\n"
                 "SPIN:\n"
                 "mbarrier.try_wait.parity.shared::cta.b64 P, [%0], %1;\n"
                 "@P bra DONE;\n"
                 "add.u32 c, c, 1;\n"
                 "setp.lt.u32 P, c, 4194304;\n"
                 "@P bra SPIN;\n"
                 "trap;\n"
                 "DONE:\n}\n" :: "r"(bar), "r"(parity) : "memory");
}
__device__ __forceinline__ void mbar_spin(uint32_t bar, uint32_t parity) {
    asm volatile("{\n.reg .pred P;\n"
                 "SPIN:\n"
                 "mbarrier.try_wait.parity.shared::cta.b64 P, [%0], %1;\n"
                 "@!P bra SPIN;\n}\n" :: "r"(bar), "r"(parity) : "memory");
}
__device__ __forceinline__ void bar_sync(int id, int n) { asm volatile("bar.sync %0, %1;" :: "r"(id), "r"(n) : "memory"); }
__device__ __forceinline__ void bar_arrive(int id, int n) { asm volatile("bar.arrive %0, %1;" :: "r"(id), "r"(n) : "memory"); }
__device__ __forceinline__ void fence_proxy_async_smem() { asm volatile("fence.proxy.async.shared::cta;" ::: "memory"); }
__device__ __forceinline__ void tma_load_3d(uint32_t dst, const CUtensorMap* map, uint32_t bar, int c0, int c1, int c2) {
    asm volatile("cp.async.bulk.tensor.3d.shared::cluster.global.mbarrier::complete_tx::bytes [%0], [%1, {%3, %4, %5}], [%2];"
                 :: "r"(dst), "l"(map), "r"(bar), "r"(c0), "r"(c1), "r"(c2) : "memory");
}
__device__ __forceinline__ void warp_expect_tx(uint32_t bar, uint32_t bytes) {
    asm volatile("{\n.reg .pred P;\nelect.sync _|P, 0xffffffff;\n@P mbarrier.arrive.expect_tx.shared::cta.b64 _, [%0], %1;\n}\n"
                 :: "r"(bar), "r"(bytes) : "memory");
}
__device__ __forceinline__ void warp_tma_load(uint32_t dst, const CUtensorMap* map, uint32_t bar, int c0, int c1, int c2) {
    asm volatile("{\n.reg .pred P;\nelect.sync _|P, 0xffffffff;\n"
                 "@P cp.async.bulk.tensor.3d.shared::cluster.global.mbarrier::complete_tx::bytes [%0], [%1, {%3, %4, %5}], [%2];\n}\n"
                 :: "r"(dst), "l"(map), "r"(bar), "r"(c0), "r"(c1), "r"(c2) : "memory");
}
__device__ __forceinline__ void warp_tma_load_pair(uint32_t dst, const CUtensorMap* map, uint32_t bar, int c0, int c1, int c2) {
    asm volatile("{\n.reg .pred P;\nelect.sync _|P, 0xffffffff;\n"
                 "@P cp.async.bulk.tensor.3d.shared::cluster.global.mbarrier::complete_tx::bytes.multicast::cluster"
                 " [%0], [%1, {%3, %4, %5}], [%2], %6;\n}\n"
                 :: "r"(dst), "l"(map), "r"(bar), "r"(c0), "r"(c1), "r"(c2), "h"((uint16_t)3) : "memory");
}
__device__ __forceinline__ void warp_bulk_load(uint32_t dst, const void* src, uint32_t bytes, uint32_t bar) {
    asm volatile("{\n.reg .pred P;\nelect.sync _|P, 0xffffffff;\n"
                 "@P cp.async.bulk.shared::cluster.global.mbarrier::complete_tx::bytes [%0], [%1], %2, [%3];\n}\n"
                 :: "r"(dst), "l"(src), "r"(bytes), "r"(bar) : "memory");
}
__device__ __forceinline__ void warp_tma_store(const CUtensorMap* map, uint32_t src, int c0, int c1, int c2) {
    asm volatile("{\n.reg .pred P;\nelect.sync _|P, 0xffffffff;\n"
                 "@P cp.async.bulk.tensor.3d.global.shared::cta.bulk_group [%0, {%2, %3, %4}], [%1];\n}\n"
                 :: "l"(map), "r"(src), "r"(c0), "r"(c1), "r"(c2) : "memory");
}
__device__ __forceinline__ void prefetch_l2(const void* src, uint32_t bytes) {
    asm volatile("cp.async.bulk.prefetch.L2.global [%0], %1;" :: "l"(src), "r"(bytes) : "memory");
}
__device__ __forceinline__ void warp_prefetch(const void* src, uint32_t bytes) {
    asm volatile("{\n.reg .pred P;\nelect.sync _|P, 0xffffffff;\n@P cp.async.bulk.prefetch.L2.global [%0], %1;\n}\n" :: "l"(src), "r"(bytes) : "memory");
}
__device__ __forceinline__ void bulk_commit() { asm volatile("cp.async.bulk.commit_group;" ::: "memory"); }
template <int N> __device__ __forceinline__ void bulk_wait_read() { asm volatile("cp.async.bulk.wait_group.read %0;" :: "n"(N) : "memory"); }
template <int N> __device__ __forceinline__ void bulk_wait() { asm volatile("cp.async.bulk.wait_group %0;" :: "n"(N) : "memory"); }
__device__ __forceinline__ void wgmma_fence() { asm volatile("wgmma.fence.sync.aligned;" ::: "memory"); }
__device__ __forceinline__ void wgmma_commit() { asm volatile("wgmma.commit_group.sync.aligned;" ::: "memory"); }
template <int N> __device__ __forceinline__ void wgmma_wait() { asm volatile("wgmma.wait_group.sync.aligned %0;" :: "n"(N) : "memory"); }
template <int N> __device__ __forceinline__ void fence_regs(float (&d)[N]) {
#pragma unroll
    for (int i = 0; i < N; i++) asm volatile("" : "+f"(d[i]) :: "memory");
}
template <int N> __device__ __forceinline__ void fence_regs(uint32_t (&d)[N]) {
#pragma unroll
    for (int i = 0; i < N; i++) asm volatile("" : "+r"(d[i]) :: "memory");
}
template <int N> __device__ __forceinline__ void reg_dec() { asm volatile("setmaxnreg.dec.sync.aligned.u32 %0;" :: "n"(N)); }
template <int N> __device__ __forceinline__ void reg_inc() { asm volatile("setmaxnreg.inc.sync.aligned.u32 %0;" :: "n"(N)); }
__device__ __forceinline__ uint32_t pack_bf16(float lo, float hi) {
    uint32_t r; asm("cvt.rn.bf16x2.f32 %0, %1, %2;" : "=r"(r) : "f"(hi), "f"(lo)); return r;
}
__device__ __forceinline__ void stmatrix_x4(uint32_t addr, uint32_t r0, uint32_t r1, uint32_t r2, uint32_t r3) {
    asm volatile("stmatrix.sync.aligned.m8n8.x4.shared.b16 [%0], {%1, %2, %3, %4};"
                 :: "r"(addr), "r"(r0), "r"(r1), "r"(r2), "r"(r3) : "memory");
}
__device__ __forceinline__ float ex2(float x) { float y; asm("ex2.approx.ftz.f32 %0, %1;" : "=f"(y) : "f"(x)); return y; }

constexpr uint32_t DESC_HI = (1024 >> 4) | (1u << 30);
__device__ __forceinline__ uint32_t make_desc(uint32_t addr, uint32_t lbo) {
    uint32_t lo = ((addr & 0x3FFFF) >> 4) | ((lbo >> 4) << 16);
    asm volatile("" : "+r"(lo));
    return lo;
}
__device__ __forceinline__ uint64_t full_desc(uint32_t lo) {
    uint64_t d; asm("mov.b64 %0, {%1, %2};" : "=l"(d) : "r"(lo), "r"(DESC_HI)); return d;
}

__device__ __forceinline__ void wgmma_ss_n256_tb_init(float (&d)[128], uint64_t da, uint64_t db) {
    asm volatile("{\n.reg .pred p;\n"
        "setp.ne.b32 p, 0, 0;\n"
        "wgmma.mma_async.sync.aligned.m64n256k16.f32.bf16.bf16 "
        "{%0, %1, %2, %3, %4, %5, %6, %7, %8, %9, %10, %11, %12, %13, %14, %15, %16, %17, %18, %19, %20, "
        "%21, %22, %23, %24, %25, %26, %27, %28, %29, %30, %31, %32, %33, %34, %35, %36, %37, %38, %39, %40, "
        "%41, %42, %43, %44, %45, %46, %47, %48, %49, %50, %51, %52, %53, %54, %55, %56, %57, %58, %59, %60, "
        "%61, %62, %63, %64, %65, %66, %67, %68, %69, %70, %71, %72, %73, %74, %75, %76, %77, %78, %79, %80, "
        "%81, %82, %83, %84, %85, %86, %87, %88, %89, %90, %91, %92, %93, %94, %95, %96, %97, %98, %99, "
        "%100, %101, %102, %103, %104, %105, %106, %107, %108, %109, %110, %111, %112, %113, %114, %115, "
        "%116, %117, %118, %119, %120, %121, %122, %123, %124, %125, %126, %127},"
        " %128, %129, p, 1, 1, 0, 1;\n}\n"
        : "=f"(d[0]), "=f"(d[1]), "=f"(d[2]), "=f"(d[3]), "=f"(d[4]), "=f"(d[5]), "=f"(d[6]), "=f"(d[7]),
        "=f"(d[8]), "=f"(d[9]), "=f"(d[10]), "=f"(d[11]), "=f"(d[12]), "=f"(d[13]), "=f"(d[14]), "=f"(d[15]),
        "=f"(d[16]), "=f"(d[17]), "=f"(d[18]), "=f"(d[19]), "=f"(d[20]), "=f"(d[21]), "=f"(d[22]),
        "=f"(d[23]), "=f"(d[24]), "=f"(d[25]), "=f"(d[26]), "=f"(d[27]), "=f"(d[28]), "=f"(d[29]),
        "=f"(d[30]), "=f"(d[31]), "=f"(d[32]), "=f"(d[33]), "=f"(d[34]), "=f"(d[35]), "=f"(d[36]),
        "=f"(d[37]), "=f"(d[38]), "=f"(d[39]), "=f"(d[40]), "=f"(d[41]), "=f"(d[42]), "=f"(d[43]),
        "=f"(d[44]), "=f"(d[45]), "=f"(d[46]), "=f"(d[47]), "=f"(d[48]), "=f"(d[49]), "=f"(d[50]),
        "=f"(d[51]), "=f"(d[52]), "=f"(d[53]), "=f"(d[54]), "=f"(d[55]), "=f"(d[56]), "=f"(d[57]),
        "=f"(d[58]), "=f"(d[59]), "=f"(d[60]), "=f"(d[61]), "=f"(d[62]), "=f"(d[63]), "=f"(d[64]),
        "=f"(d[65]), "=f"(d[66]), "=f"(d[67]), "=f"(d[68]), "=f"(d[69]), "=f"(d[70]), "=f"(d[71]),
        "=f"(d[72]), "=f"(d[73]), "=f"(d[74]), "=f"(d[75]), "=f"(d[76]), "=f"(d[77]), "=f"(d[78]),
        "=f"(d[79]), "=f"(d[80]), "=f"(d[81]), "=f"(d[82]), "=f"(d[83]), "=f"(d[84]), "=f"(d[85]),
        "=f"(d[86]), "=f"(d[87]), "=f"(d[88]), "=f"(d[89]), "=f"(d[90]), "=f"(d[91]), "=f"(d[92]),
        "=f"(d[93]), "=f"(d[94]), "=f"(d[95]), "=f"(d[96]), "=f"(d[97]), "=f"(d[98]), "=f"(d[99]),
        "=f"(d[100]), "=f"(d[101]), "=f"(d[102]), "=f"(d[103]), "=f"(d[104]), "=f"(d[105]), "=f"(d[106]),
        "=f"(d[107]), "=f"(d[108]), "=f"(d[109]), "=f"(d[110]), "=f"(d[111]), "=f"(d[112]), "=f"(d[113]),
        "=f"(d[114]), "=f"(d[115]), "=f"(d[116]), "=f"(d[117]), "=f"(d[118]), "=f"(d[119]), "=f"(d[120]),
        "=f"(d[121]), "=f"(d[122]), "=f"(d[123]), "=f"(d[124]), "=f"(d[125]), "=f"(d[126]), "=f"(d[127])
        : "l"(da), "l"(db));
}
__device__ __forceinline__ void wgmma_ss_n256_tb(float (&d)[128], uint64_t da, uint64_t db, int scale_d) {
    asm volatile("{\n.reg .pred p;\n"
        "setp.ne.b32 p, %130, 0;\n"
        "wgmma.mma_async.sync.aligned.m64n256k16.f32.bf16.bf16 "
        "{%0, %1, %2, %3, %4, %5, %6, %7, %8, %9, %10, %11, %12, %13, %14, %15, %16, %17, %18, %19, %20, "
        "%21, %22, %23, %24, %25, %26, %27, %28, %29, %30, %31, %32, %33, %34, %35, %36, %37, %38, %39, %40, "
        "%41, %42, %43, %44, %45, %46, %47, %48, %49, %50, %51, %52, %53, %54, %55, %56, %57, %58, %59, %60, "
        "%61, %62, %63, %64, %65, %66, %67, %68, %69, %70, %71, %72, %73, %74, %75, %76, %77, %78, %79, %80, "
        "%81, %82, %83, %84, %85, %86, %87, %88, %89, %90, %91, %92, %93, %94, %95, %96, %97, %98, %99, "
        "%100, %101, %102, %103, %104, %105, %106, %107, %108, %109, %110, %111, %112, %113, %114, %115, "
        "%116, %117, %118, %119, %120, %121, %122, %123, %124, %125, %126, %127},"
        " %128, %129, p, 1, 1, 0, 1;\n}\n"
        : "+f"(d[0]), "+f"(d[1]), "+f"(d[2]), "+f"(d[3]), "+f"(d[4]), "+f"(d[5]), "+f"(d[6]), "+f"(d[7]),
        "+f"(d[8]), "+f"(d[9]), "+f"(d[10]), "+f"(d[11]), "+f"(d[12]), "+f"(d[13]), "+f"(d[14]), "+f"(d[15]),
        "+f"(d[16]), "+f"(d[17]), "+f"(d[18]), "+f"(d[19]), "+f"(d[20]), "+f"(d[21]), "+f"(d[22]),
        "+f"(d[23]), "+f"(d[24]), "+f"(d[25]), "+f"(d[26]), "+f"(d[27]), "+f"(d[28]), "+f"(d[29]),
        "+f"(d[30]), "+f"(d[31]), "+f"(d[32]), "+f"(d[33]), "+f"(d[34]), "+f"(d[35]), "+f"(d[36]),
        "+f"(d[37]), "+f"(d[38]), "+f"(d[39]), "+f"(d[40]), "+f"(d[41]), "+f"(d[42]), "+f"(d[43]),
        "+f"(d[44]), "+f"(d[45]), "+f"(d[46]), "+f"(d[47]), "+f"(d[48]), "+f"(d[49]), "+f"(d[50]),
        "+f"(d[51]), "+f"(d[52]), "+f"(d[53]), "+f"(d[54]), "+f"(d[55]), "+f"(d[56]), "+f"(d[57]),
        "+f"(d[58]), "+f"(d[59]), "+f"(d[60]), "+f"(d[61]), "+f"(d[62]), "+f"(d[63]), "+f"(d[64]),
        "+f"(d[65]), "+f"(d[66]), "+f"(d[67]), "+f"(d[68]), "+f"(d[69]), "+f"(d[70]), "+f"(d[71]),
        "+f"(d[72]), "+f"(d[73]), "+f"(d[74]), "+f"(d[75]), "+f"(d[76]), "+f"(d[77]), "+f"(d[78]),
        "+f"(d[79]), "+f"(d[80]), "+f"(d[81]), "+f"(d[82]), "+f"(d[83]), "+f"(d[84]), "+f"(d[85]),
        "+f"(d[86]), "+f"(d[87]), "+f"(d[88]), "+f"(d[89]), "+f"(d[90]), "+f"(d[91]), "+f"(d[92]),
        "+f"(d[93]), "+f"(d[94]), "+f"(d[95]), "+f"(d[96]), "+f"(d[97]), "+f"(d[98]), "+f"(d[99]),
        "+f"(d[100]), "+f"(d[101]), "+f"(d[102]), "+f"(d[103]), "+f"(d[104]), "+f"(d[105]), "+f"(d[106]),
        "+f"(d[107]), "+f"(d[108]), "+f"(d[109]), "+f"(d[110]), "+f"(d[111]), "+f"(d[112]), "+f"(d[113]),
        "+f"(d[114]), "+f"(d[115]), "+f"(d[116]), "+f"(d[117]), "+f"(d[118]), "+f"(d[119]), "+f"(d[120]),
        "+f"(d[121]), "+f"(d[122]), "+f"(d[123]), "+f"(d[124]), "+f"(d[125]), "+f"(d[126]), "+f"(d[127])
        : "l"(da), "l"(db), "r"(scale_d));
}
__device__ __forceinline__ void wgmma_ss_n128(float (&d)[64], uint64_t da, uint64_t db, int scale_d) {
    asm volatile("{\n.reg .pred p;\n"
        "setp.ne.b32 p, %66, 0;\n"
        "wgmma.mma_async.sync.aligned.m64n128k16.f32.bf16.bf16 "
        "{%0, %1, %2, %3, %4, %5, %6, %7, %8, %9, %10, %11, %12, %13, %14, %15, %16, %17, %18, %19, %20, "
        "%21, %22, %23, %24, %25, %26, %27, %28, %29, %30, %31, %32, %33, %34, %35, %36, %37, %38, %39, %40, "
        "%41, %42, %43, %44, %45, %46, %47, %48, %49, %50, %51, %52, %53, %54, %55, %56, %57, %58, %59, %60, "
        "%61, %62, %63},"
        " %64, %65, p, 1, 1, 0, 0;\n}\n"
        : "+f"(d[0]), "+f"(d[1]), "+f"(d[2]), "+f"(d[3]), "+f"(d[4]), "+f"(d[5]), "+f"(d[6]), "+f"(d[7]),
        "+f"(d[8]), "+f"(d[9]), "+f"(d[10]), "+f"(d[11]), "+f"(d[12]), "+f"(d[13]), "+f"(d[14]), "+f"(d[15]),
        "+f"(d[16]), "+f"(d[17]), "+f"(d[18]), "+f"(d[19]), "+f"(d[20]), "+f"(d[21]), "+f"(d[22]),
        "+f"(d[23]), "+f"(d[24]), "+f"(d[25]), "+f"(d[26]), "+f"(d[27]), "+f"(d[28]), "+f"(d[29]),
        "+f"(d[30]), "+f"(d[31]), "+f"(d[32]), "+f"(d[33]), "+f"(d[34]), "+f"(d[35]), "+f"(d[36]),
        "+f"(d[37]), "+f"(d[38]), "+f"(d[39]), "+f"(d[40]), "+f"(d[41]), "+f"(d[42]), "+f"(d[43]),
        "+f"(d[44]), "+f"(d[45]), "+f"(d[46]), "+f"(d[47]), "+f"(d[48]), "+f"(d[49]), "+f"(d[50]),
        "+f"(d[51]), "+f"(d[52]), "+f"(d[53]), "+f"(d[54]), "+f"(d[55]), "+f"(d[56]), "+f"(d[57]),
        "+f"(d[58]), "+f"(d[59]), "+f"(d[60]), "+f"(d[61]), "+f"(d[62]), "+f"(d[63])
        : "l"(da), "l"(db), "r"(scale_d));
}
__device__ __forceinline__ void wgmma_rs_n128_tb(float (&d)[64], uint32_t a0, uint32_t a1, uint32_t a2, uint32_t a3, uint64_t db, int scale_d) {
    asm volatile("{\n.reg .pred p;\n"
        "setp.ne.b32 p, %69, 0;\n"
        "wgmma.mma_async.sync.aligned.m64n128k16.f32.bf16.bf16 "
        "{%0, %1, %2, %3, %4, %5, %6, %7, %8, %9, %10, %11, %12, %13, %14, %15, %16, %17, %18, %19, %20, "
        "%21, %22, %23, %24, %25, %26, %27, %28, %29, %30, %31, %32, %33, %34, %35, %36, %37, %38, %39, %40, "
        "%41, %42, %43, %44, %45, %46, %47, %48, %49, %50, %51, %52, %53, %54, %55, %56, %57, %58, %59, %60, "
        "%61, %62, %63},"
        " {%64, %65, %66, %67}, %68, p, 1, 1, 1;\n}\n"
        : "+f"(d[0]), "+f"(d[1]), "+f"(d[2]), "+f"(d[3]), "+f"(d[4]), "+f"(d[5]), "+f"(d[6]), "+f"(d[7]),
        "+f"(d[8]), "+f"(d[9]), "+f"(d[10]), "+f"(d[11]), "+f"(d[12]), "+f"(d[13]), "+f"(d[14]), "+f"(d[15]),
        "+f"(d[16]), "+f"(d[17]), "+f"(d[18]), "+f"(d[19]), "+f"(d[20]), "+f"(d[21]), "+f"(d[22]),
        "+f"(d[23]), "+f"(d[24]), "+f"(d[25]), "+f"(d[26]), "+f"(d[27]), "+f"(d[28]), "+f"(d[29]),
        "+f"(d[30]), "+f"(d[31]), "+f"(d[32]), "+f"(d[33]), "+f"(d[34]), "+f"(d[35]), "+f"(d[36]),
        "+f"(d[37]), "+f"(d[38]), "+f"(d[39]), "+f"(d[40]), "+f"(d[41]), "+f"(d[42]), "+f"(d[43]),
        "+f"(d[44]), "+f"(d[45]), "+f"(d[46]), "+f"(d[47]), "+f"(d[48]), "+f"(d[49]), "+f"(d[50]),
        "+f"(d[51]), "+f"(d[52]), "+f"(d[53]), "+f"(d[54]), "+f"(d[55]), "+f"(d[56]), "+f"(d[57]),
        "+f"(d[58]), "+f"(d[59]), "+f"(d[60]), "+f"(d[61]), "+f"(d[62]), "+f"(d[63])
        : "r"(a0), "r"(a1), "r"(a2), "r"(a3), "l"(db), "r"(scale_d));
}
__device__ __forceinline__ void wgmma_ss_n128_lo_tb(float (&d)[128], uint64_t da, uint64_t db, int scale_d) {
    asm volatile("{\n.reg .pred p;\n"
        "setp.ne.b32 p, %66, 0;\n"
        "wgmma.mma_async.sync.aligned.m64n128k16.f32.bf16.bf16 "
        "{%0, %1, %2, %3, %4, %5, %6, %7, %8, %9, %10, %11, %12, %13, %14, %15, %16, %17, %18, %19, %20, "
        "%21, %22, %23, %24, %25, %26, %27, %28, %29, %30, %31, %32, %33, %34, %35, %36, %37, %38, %39, %40, "
        "%41, %42, %43, %44, %45, %46, %47, %48, %49, %50, %51, %52, %53, %54, %55, %56, %57, %58, %59, %60, "
        "%61, %62, %63},"
        " %64, %65, p, 1, 1, 0, 1;\n}\n"
        : "+f"(d[0]), "+f"(d[1]), "+f"(d[2]), "+f"(d[3]), "+f"(d[4]), "+f"(d[5]), "+f"(d[6]), "+f"(d[7]),
        "+f"(d[8]), "+f"(d[9]), "+f"(d[10]), "+f"(d[11]), "+f"(d[12]), "+f"(d[13]), "+f"(d[14]), "+f"(d[15]),
        "+f"(d[16]), "+f"(d[17]), "+f"(d[18]), "+f"(d[19]), "+f"(d[20]), "+f"(d[21]), "+f"(d[22]),
        "+f"(d[23]), "+f"(d[24]), "+f"(d[25]), "+f"(d[26]), "+f"(d[27]), "+f"(d[28]), "+f"(d[29]),
        "+f"(d[30]), "+f"(d[31]), "+f"(d[32]), "+f"(d[33]), "+f"(d[34]), "+f"(d[35]), "+f"(d[36]),
        "+f"(d[37]), "+f"(d[38]), "+f"(d[39]), "+f"(d[40]), "+f"(d[41]), "+f"(d[42]), "+f"(d[43]),
        "+f"(d[44]), "+f"(d[45]), "+f"(d[46]), "+f"(d[47]), "+f"(d[48]), "+f"(d[49]), "+f"(d[50]),
        "+f"(d[51]), "+f"(d[52]), "+f"(d[53]), "+f"(d[54]), "+f"(d[55]), "+f"(d[56]), "+f"(d[57]),
        "+f"(d[58]), "+f"(d[59]), "+f"(d[60]), "+f"(d[61]), "+f"(d[62]), "+f"(d[63])
        : "l"(da), "l"(db), "r"(scale_d));
}

enum { M_X = 0, M_C, M_WQ, M_WQKV, M_WUK, M_WUV, M_WO, M_WOB, M_SCR_LD, M_SCR_LOC, M_SCR_LOQ, M_SCR_ST, M_OUT, M_COUNT };
enum { T_Q = 0, T_K, T_V, T_B, T_OUT, T_LOCAL, T_ATTN, T_END };
constexpr int NCTA = 132, NPAIR = NCTA / 2;
constexpr int NITEMS = 480 + 64 + 256 + 64;
struct Params {
    CUtensorMap m[M_COUNT];
    const __nv_bfloat16* x;
    const __nv_bfloat16* gate_w;
    const char* wo[2];
    uint32_t pfd;
    uint32_t zero;
    uint16_t items[NITEMS];
    uint8_t oseq[2][22];
};
__device__ __forceinline__ int item_type(int it) { return it >> 13; }
__device__ __forceinline__ int item_row(int it) { return it & 15; }
__device__ __forceinline__ int item_col(int it) { return (it >> 4) & 31; }
__device__ __forceinline__ int item_asc(int it) { return (it >> 9) & 1; }
constexpr int ITEM_READY = 1 << 10;

struct __align__(128) Sync {
    unsigned long long count[4];
    unsigned loc[16];
    __align__(128) unsigned long long ctx[16];
    unsigned next, done;
};
__device__ Sync g_sync;
__device__ __align__(8) unsigned g_pflag[128][2];

constexpr uint32_t GST_BYTES = 49152, SM_KV = 65536, SM_STAGING = 196608, SM_BARS = SM_STAGING + 32768;
constexpr uint32_t B_GFULL = 0, B_GEMPTY = 32, B_AFULL = 64, B_AEMPTY = 112, B_SFULL = 160, B_SEMPTY = 192,
                   B_IFULL = 224, B_IEMPTY = 288, B_XFREE = 352, B_WANT = 384, B_PRECV = 392, B_WIDE = 408, B_HALF = 416,
                   SM_ORDY = 448, SM_QUEUE = 456, B_ALT = 488, B_QFREE = 504, SM_GATE = 512, SM_TOTAL = SM_BARS + 1536;
constexpr int QDEPTH = 8;
constexpr uint32_t LOC_PLANE = 72 * 128;
constexpr float SM_SCALE = 0.08838834764831845f * 1.4426950408889634f;
constexpr float LOC_SCALE = 0.17677669529663687f * 1.4426950408889634f;
constexpr float SUM_LIMIT = 1152921504606846976.f;

__device__ __forceinline__ unsigned ld_acquire(const unsigned* p) {
    unsigned v; asm volatile("ld.acquire.gpu.global.u32 %0, [%1];" : "=r"(v) : "l"(p) : "memory"); return v;
}
__device__ __forceinline__ unsigned long long ld_acquire(const unsigned long long* p) {
    unsigned long long v; asm volatile("ld.acquire.gpu.global.u64 %0, [%1];" : "=l"(v) : "l"(p) : "memory"); return v;
}
__device__ __forceinline__ void spin_guard(unsigned& n) {
    asm volatile("{\n.reg .pred P;\nadd.u32 %0, %0, 1;\nsetp.gt.u32 P, %0, 16777216;\n@P trap;\n}\n" : "+r"(n));
    if (n > 1) __nanosleep(100);
}
__device__ __forceinline__ void red_add(unsigned long long* p, unsigned long long v) {
    asm volatile("red.release.gpu.global.add.u64 [%0], %1;" :: "l"(p), "l"(v) : "memory");
}
__device__ __forceinline__ float rcp(float x) { float y; asm("rcp.approx.ftz.f32 %0, %1;" : "=f"(y) : "f"(x)); return y; }
__device__ __forceinline__ float lds_f32(uint32_t addr) {
    float v; asm volatile("ld.shared.f32 %0, [%1];" : "=f"(v) : "r"(addr) : "memory"); return v;
}
__device__ __forceinline__ void ldsm_x4(uint32_t (&r)[4], uint32_t addr) {
    asm volatile("ldmatrix.sync.aligned.m8n8.x4.shared.b16 {%0, %1, %2, %3}, [%4];"
                 : "=r"(r[0]), "=r"(r[1]), "=r"(r[2]), "=r"(r[3]) : "r"(addr) : "memory");
}
__device__ __forceinline__ void ldsm_x4_t(uint32_t (&r)[4], uint32_t addr) {
    asm volatile("ldmatrix.sync.aligned.m8n8.x4.trans.shared.b16 {%0, %1, %2, %3}, [%4];"
                 : "=r"(r[0]), "=r"(r[1]), "=r"(r[2]), "=r"(r[3]) : "r"(addr) : "memory");
}
__device__ __forceinline__ void mma_k16(float (&d)[4], const uint32_t (&a)[4], uint32_t b0, uint32_t b1) {
    asm("mma.sync.aligned.m16n8k16.row.col.f32.bf16.bf16.f32 {%0,%1,%2,%3}, {%4,%5,%6,%7}, {%8,%9}, {%0,%1,%2,%3};"
        : "+f"(d[0]), "+f"(d[1]), "+f"(d[2]), "+f"(d[3]) : "r"(a[0]), "r"(a[1]), "r"(a[2]), "r"(a[3]), "r"(b0), "r"(b1));
}
__device__ __forceinline__ void mma_k16_init(float (&d)[4], const uint32_t (&a)[4], uint32_t b0, uint32_t b1) {
    asm("{\n.reg .f32 z;\nmov.f32 z, 0f00000000;\n"
        "mma.sync.aligned.m16n8k16.row.col.f32.bf16.bf16.f32 {%0,%1,%2,%3}, {%4,%5,%6,%7}, {%8,%9}, {z,z,z,z};\n}\n"
        : "=f"(d[0]), "=f"(d[1]), "=f"(d[2]), "=f"(d[3]) : "r"(a[0]), "r"(a[1]), "r"(a[2]), "r"(a[3]), "r"(b0), "r"(b1));
}
__device__ __forceinline__ void mma_k8(float (&d)[4], uint32_t a0, uint32_t a1, uint32_t b0) {
    asm("mma.sync.aligned.m16n8k8.row.col.f32.bf16.bf16.f32 {%0,%1,%2,%3}, {%4,%5}, {%6}, {%0,%1,%2,%3};"
        : "+f"(d[0]), "+f"(d[1]), "+f"(d[2]), "+f"(d[3]) : "r"(a0), "r"(a1), "r"(b0));
}
template <typename T, int N> __device__ __forceinline__ void zero_regs(T (&d)[N]) {
#pragma unroll
    for (int i = 0; i < N; i++) d[i] = 0;
}
__device__ __forceinline__ float quad_max(float v) {
    v = fmaxf(v, __shfl_xor_sync(0xffffffffu, v, 1));
    return fmaxf(v, __shfl_xor_sync(0xffffffffu, v, 2));
}
__device__ __forceinline__ float quad_sum(float v) {
    v += __shfl_xor_sync(0xffffffffu, v, 1);
    return v + __shfl_xor_sync(0xffffffffu, v, 2);
}

__device__ __forceinline__ void qk_gemm(float (&s)[64], uint32_t q_lo, uint32_t k_lo) {
    const uint64_t dq = full_desc(q_lo), dk = full_desc(k_lo);
    fence_regs(s);
    wgmma_fence();
#pragma unroll
    for (int kk = 0; kk < 8; kk++) {
        const uint32_t o = (kk >> 2) * 1024 + (kk & 3) * 2;
        wgmma_ss_n128(s, dq + o, dk + o, kk != 0);
    }
    wgmma_commit();
}
__device__ __forceinline__ void pv_gemm(float (&o)[64], uint32_t (&p)[32], uint32_t v_lo, int accumulate) {
    const uint64_t dv = full_desc(v_lo);
    fence_regs(o);
    fence_regs(p);
    wgmma_fence();
#pragma unroll
    for (int kk = 0; kk < 8; kk++)
        wgmma_rs_n128_tb(o, p[4 * kk], p[4 * kk + 1], p[4 * kk + 2], p[4 * kk + 3], dv + kk * 128, kk != 0 || accumulate);
    wgmma_commit();
}
template <int NJ>
__device__ __forceinline__ void row_max(const float (&s)[64], float& x0, float& x1) {
    float z0 = fmaxf(s[0], s[1]), z1 = fmaxf(s[2], s[3]);
    x0 = fmaxf(s[4], s[5]); x1 = fmaxf(s[6], s[7]);
#pragma unroll
    for (int j = 2; j < NJ; j += 2) {
        z0 = fmaxf(z0, fmaxf(s[4 * j], s[4 * j + 1]));
        z1 = fmaxf(z1, fmaxf(s[4 * j + 2], s[4 * j + 3]));
        x0 = fmaxf(x0, fmaxf(s[4 * j + 4], s[4 * j + 5]));
        x1 = fmaxf(x1, fmaxf(s[4 * j + 6], s[4 * j + 7]));
    }
    x0 = quad_max(fmaxf(x0, z0)); x1 = quad_max(fmaxf(x1, z1));
}
__device__ __forceinline__ void exp_pack(uint32_t (&p)[32], const float (&s)[64], float n0, float n1, float& r0, float& r1) {
#pragma unroll
    for (int j = 0; j < 16; j++) {
        const float e0 = ex2(fmaf(s[4 * j], SM_SCALE, n0)), e1 = ex2(fmaf(s[4 * j + 1], SM_SCALE, n0));
        const float e2 = ex2(fmaf(s[4 * j + 2], SM_SCALE, n1)), e3 = ex2(fmaf(s[4 * j + 3], SM_SCALE, n1));
        if (j == 0) { r0 = e0 + e1; r1 = e2 + e3; }
        else { r0 += e0; r0 += e1; r1 += e2; r1 += e3; }
        p[2 * j] = pack_bf16(e0, e1);
        p[2 * j + 1] = pack_bf16(e2, e3);
    }
}
template <int J0>
__device__ __forceinline__ void mask_triangle(float (&s)[64], int thr) {
#pragma unroll
    for (int j = 0; j < 8; j++) {
        if (8 * j > thr) s[4 * (J0 + j)] = -INFINITY;
        if (8 * j + 1 > thr) s[4 * (J0 + j) + 1] = -INFINITY;
        if (j > 0 && 8 * j - 8 > thr) s[4 * (J0 + j) + 2] = -INFINITY;
        if (j > 0 && 8 * j - 7 > thr) s[4 * (J0 + j) + 3] = -INFINITY;
    }
}
__device__ __forceinline__ void causal_mask(float (&s)[64], int thr, int wg) {
    asm volatile("" : "+r"(thr));
    if (wg == 0) {
        mask_triangle<0>(s, thr);
#pragma unroll
        for (int j = 32; j < 64; j++) s[j] = -INFINITY;
    } else {
        mask_triangle<8>(s, thr - 64);
    }
}

__global__ void __cluster_dims__(2, 1, 1) __launch_bounds__(384, 1) fused_kernel(const __grid_constant__ Params prm) {
    extern __shared__ __align__(1024) uint8_t smem[];
    const uint32_t sb = smem_u32(smem), bars = sb + SM_BARS;
    const int warp = __shfl_sync(0xffffffffu, threadIdx.x >> 5, 0), lane = threadIdx.x & 31;

    const uint32_t rank = cluster_rank();
    const uint32_t bars0 = map_cta(bars, 0), bars_peer = map_cta(bars, rank ^ 1);

    auto first_item = [&]() -> int {
        uint32_t pair = blockIdx.x >> 1;
        asm volatile("" : "+r"(pair));
        return prm.items[pair] + item_row(prm.items[pair]) + rank;
    };
    if (threadIdx.x == 256) {
        for (int k = 0; k < 4; k++) mbar_init(bars + B_GFULL + 8 * k, 1);
        asm volatile("fence.mbarrier_init.release.cluster;" ::: "memory");
        fence_proxy_async_smem();
    }
    if (threadIdx.x == 128) {
        for (int i = 0; i < 4; i++) { mbar_init(bars + B_GEMPTY + 8 * i, 16); mbar_init(bars + B_XFREE + 8 * i, 1); }
        for (int i = 0; i < 6; i++) { mbar_init(bars + B_AFULL + 8 * i, 1); mbar_init(bars + B_AEMPTY + 8 * i, i < 2 ? 8 : 16); }
        for (int i = 0; i < 4; i++) { mbar_init(bars + B_SFULL + 8 * i, 4); mbar_init(bars + B_SEMPTY + 8 * i, 1); }
        for (int i = 0; i < QDEPTH; i++) { mbar_init(bars + B_IFULL + 8 * i, 1); mbar_init(bars + B_IEMPTY + 8 * i, 23); }
        mbar_init(bars + B_WANT, 2); mbar_init(bars + B_PRECV, 1); mbar_init(bars + B_PRECV + 8, 1); mbar_init(bars + B_WIDE, 8);
        for (int i = 0; i < 4; i++) mbar_init(bars + B_HALF + 8 * i, 1);
        mbar_init(bars + B_ALT, 4); mbar_init(bars + B_ALT + 8, 4); mbar_init(bars + B_QFREE, 2);
        asm volatile("st.shared.u32 [%0], 0;" :: "r"(bars + SM_ORDY) : "memory");
        asm volatile("fence.mbarrier_init.release.cluster;\nfence.acq_rel.cta;" ::: "memory");
    }
    __syncwarp();
    asm volatile("barrier.cluster.arrive.relaxed.aligned;" ::: "memory");
    if (threadIdx.x == 256) {
        const int first_it = first_item();
        for (int k = 0; k < 4; k++) {
            const uint32_t dst = sb + k * GST_BYTES, fb = bars + B_GFULL + 8 * k;
            mbar_expect_tx(fb, GST_BYTES);
            tma_load_3d(dst, &prm.m[M_X], fb, k * 64, item_row(first_it) * 128, 0);
            tma_load_3d(dst + 16384, &prm.m[M_WQKV], fb, 0, k * 64, item_col(first_it) * 4);
            tma_load_3d(dst + 32768, &prm.m[M_WQKV], fb, 0, k * 64, item_col(first_it) * 4 + 2);
        }
    }
    __syncwarp();
    asm volatile("barrier.cluster.wait.acquire.aligned;" ::: "memory");

    uint32_t qn = 0;
    auto next_item = [&](bool releaser, bool bounded = true) -> int {
        const uint32_t slot = qn % QDEPTH;
        if (bounded) mbar_wait(bars + B_IFULL + 8 * slot, (qn / QDEPTH) & 1);
        else mbar_spin(bars + B_IFULL + 8 * slot, (qn / QDEPTH) & 1);
        uint32_t it;
        asm volatile("ld.shared.u32 %0, [%1];" : "=r"(it) : "r"(bars + SM_QUEUE + 4 * slot) : "memory");
        mbar_arrive_cluster_if(releaser, bars0 + B_IEMPTY + 8 * slot);
        qn++;
        return it;
    };

    if (warp < 4) {
        reg_dec<40>();
        if (warp == 0) {
            {
                uint32_t gph = 0;
                const uint32_t prank = __shfl_sync(0xffffffffu, rank, 0);
                int k0 = 4;
                uint32_t kv = 0, kvph = 1;
                uint32_t qc = 0;
                uint32_t oneed = 0, ordy = 0;
                uint32_t xph = 0;
                uint32_t need_g = 0, need_a = 0;
                auto a_parity = [&](uint32_t b) { return b < 2 ? (((qc + 1 - b) >> 1) & 1) ^ 1 : kvph ^ (b - 2 < kv); };
                int held_type = T_END;
                uint32_t borrowed = 0, fph = 0;
                auto reclaim_q = [&]() { if (borrowed) { mbar_wait(bars + B_QFREE, fph); fph ^= 1; borrowed = 0; } };
                auto acquire_g = [&](uint32_t st, bool shared) {
                    mbar_wait(bars + B_GEMPTY + 8 * st, gph);
                    if (need_a) {
                        reclaim_q();
                        const uint32_t b = (3 * st) >> 1;
                        mbar_wait(bars + B_AEMPTY + 8 * b, a_parity(b));
                        mbar_wait(bars + B_AEMPTY + 8 * (b + 1), a_parity(b + 1));
                        if (shared) {
                            mbar_arrive_cluster_if(lane == 0, bars_peer + B_XFREE + 8 * st);
                            mbar_wait(bars + B_XFREE + 8 * st, xph);
                        }
                        if (st == 3) { need_a = 0; xph ^= shared; }
                    }
                };
                auto leave_gemm = [&](uint32_t b) {
                    if (need_g >> b & 1) {
                        mbar_wait(bars + B_GEMPTY + 8 * ((2 * b) / 3), gph);
                        mbar_wait(bars + B_GEMPTY + 8 * ((2 * b + 1) / 3), gph);
                        need_g &= ~(1u << b);
                    }
                };
                const CUtensorMap* tile_map = &prm.m[M_SCR_LD];
                asm volatile("" : "+l"(tile_map));
                auto load_q = [&](int grp, int row) {
                    const uint32_t b = qc & 1, dst = sb + b * 32768, fb = bars + B_AFULL + 8 * b;
                    mbar_wait(bars + B_AEMPTY + 8 * b, a_parity(b));
                    leave_gemm(b);
                    reclaim_q();
                    borrowed = held_type != T_END;
                    held_type = T_END;
                    warp_expect_tx(fb, 32768 + 512);
                    warp_tma_load(dst, tile_map, fb, 0, row, grp);
                    warp_tma_load(dst + 16384, tile_map, fb, 64, row, grp);
                    warp_bulk_load(bars + SM_GATE + b * 512, &g_gate[row], 512, fb);
                    qc++;
                };
                auto load_kv = [&](int grp, int row, bool shared) {
                    uint32_t fb = bars + B_AFULL + 16 + 8 * kv, mine = sb + SM_KV + kv * 32768 + prank * 16384;
                    int c_mine = prank * 64;
                    asm volatile("" : "+r"(mine), "+r"(fb), "+r"(row), "+r"(grp), "+r"(c_mine));
                    if (need_g) leave_gemm(2 + kv);
                    mbar_wait(fb + B_AEMPTY - B_AFULL, kvph);
                    warp_expect_tx(fb, grp < 0 ? 0 : 32768);
                    if (shared) {
                        warp_tma_load_pair(mine, tile_map, fb, c_mine, row, grp);
                    } else if (grp >= 0) {
                        warp_tma_load(mine, tile_map, fb, c_mine, row, grp);
                        warp_tma_load(mine + 16384 - prank * 32768, tile_map, fb, 64 - c_mine, row, grp);
                    } else {
                        mbar_arrive_cluster_n_if(lane < 2, map_cta(fb, lane & 1) + B_AEMPTY - B_AFULL, 8);
                    }
                    if (++kv == 4) { kv = 0; kvph ^= 1; }
                };
                auto request = [&]() { mbar_arrive_cluster_if(lane == 0, bars0 + B_WANT); };
                int pv_grp = -1, pv_row = 0;
                bool pv_shared = false, peer_longer = false;
                auto wait_inputs = [&]() {
                    if (++oneed <= ordy) return;
                    unsigned n = 0;
                    do {
                        asm volatile("ld.acquire.cta.shared.u32 %0, [%1];" : "=r"(ordy) : "r"(bars + SM_ORDY) : "memory");
                        ordy = __shfl_sync(0xffffffffu, ordy, 0);
                        spin_guard(n);
                    } while (oneed > ordy);
                };
                auto fetch = [&]() -> int {
                    const int nx = __shfl_sync(0xffffffffu, next_item(lane == 0), 0);
                    if ((item_type(nx) == T_ATTN || item_type(nx) == T_LOCAL) && !(nx & ITEM_READY)) wait_inputs();
                    if (item_type(nx) == T_ATTN) load_q(G_Q + item_col(nx), item_row(nx) * 128);
                    return nx;
                };
                int nxt = first_item();
                while (true) {
                    const int it = nxt >= 0 ? nxt : fetch();
                    nxt = -1;
                    const int type = item_type(it), m = item_row(it), c = item_col(it);
                    const int asc = item_asc(it), nu = type == T_ATTN ? 2 * m + 2 : 0;
                    const int uend = nu + ((type == T_ATTN ? m < 2 : pv_grp >= 0) ? 3 : 0), ureq = 2 * max(m - 2 - (asc & m), 0);
#pragma unroll 1
                    for (int u = 0; u < uend; u++) {
                        int grp = pv_grp, row = pv_row;
                        bool shared = pv_shared;
                        if (u >= nu) {
                            if (u == nu + 1) pv_grp = -1;
                            else if (peer_longer) { grp = -1; shared = false; }
                            else continue;
                        } else {
                            const int j = asc ? u >> 1 : m - (u >> 1);
                            if (u & 1) {
                                pv_grp = G_V + c; pv_row = j * 128; pv_shared = j != (m | 1);
                                peer_longer = asc & ~m & 1;
                                if (grp < 0) continue;
                            } else {
                                if (u == ureq) request();
                                if (u == 2 * m && m > 0) nxt = fetch();
                                grp = G_K + c; row = j * 128; shared = j != (m | 1);
                            }
                        }
                        load_kv(grp, row, shared);
                    }
                    if (type == T_END) break;
                    if (type == T_ATTN) {
                        need_a = 1;
                    } else if (type == T_LOCAL) {
                        if (held_type == T_B) held_type = T_END;
                        request();
#pragma unroll 1
                        for (uint32_t st = 0; st < 4; st++) {
                            acquire_g(st, false);
                            const uint32_t dst = sb + st * GST_BYTES, fb = bars + B_GFULL + 8 * st;
                            warp_expect_tx(fb, st == 0 ? 32768 + 512 : st == 3 ? 0 : 4 * LOC_PLANE);
                            if (st == 3) break;
                            if (st == 0) warp_bulk_load(dst + 4 * LOC_PLANE, &g_gate[m * 128], 512, fb);
#pragma unroll 1
                            for (int i = 0; i < 4; i++)
                                warp_tma_load(dst + i * LOC_PLANE, &prm.m[st ? M_SCR_LOC : M_SCR_LOQ], fb, i * 64, m * 64 - (st ? 8 : 0), G_B + 8 * st + c);
                        }
                        gph ^= 1;
                        need_g = 63;
                    } else {
                        const bool is_out = type == T_OUT;
                        const int nk = is_out ? 44 : (type == T_K || type == T_V) ? 8 : 16;
                        const CUtensorMap* ma = &prm.m[is_out ? M_SCR_LD : nk == 8 ? M_C : M_X];
                        const CUtensorMap* mb = &prm.m[type == T_Q ? M_WQ : type == T_K ? M_WUK : type == T_V ? M_WUV : M_WQKV];
                        const int half = is_out ? c & 1 : 0, nb = is_out ? (c >> 1) * 4 : c * 4;
                        for (int k = k0; k < nk; k++) {
                            if (k == nk - 3) request();
                            int a0 = k * 64, a2 = 0, b1 = k * 64;
                            if (is_out) {
                                const int g = prm.oseq[half][k >> 1];
                                if (!(k & 1)) wait_inputs();
                                a0 = (k & 1) * 64; a2 = g < 32 ? G_CTX + g : G_LOC - 32 + g;
                                mb = &prm.m[g >= 32 ? M_WOB : M_WO];
                                b1 = (g & 31) * 128 + a0;
                            }
                            const uint32_t st = k & 3;
                            const bool narrow = k >= 36;
                            const uint32_t part = narrow ? 0 : prank;
                            uint32_t dst = sb + st * GST_BYTES, fb = bars + B_GFULL + 8 * st, bytes = narrow ? 32768 : GST_BYTES;
                            uint32_t dstb = dst + 16384 + part * 16384, skipb = narrow && (k & 1) != prank;
                            int a1 = m * 128, b2 = nb + 2 * (half ^ part);
                            asm volatile("" : "+r"(dst), "+r"(fb), "+r"(bytes), "+r"(dstb), "+r"(skipb), "+r"(a0), "+r"(a1), "+r"(a2), "+r"(b1), "+r"(b2), "+l"(ma), "+l"(mb));
                            acquire_g(st, true);
                            warp_expect_tx(fb, bytes);
                            warp_tma_load(dst, ma, fb, a0, a1, a2);
                            if (!skipb) warp_tma_load_pair(dstb, mb, fb, 0, b1, b2);
                            if (is_out && (k & 1) && (k >> 1) + prm.pfd < 20) {
                                const int g = prm.oseq[half][(k >> 1) + prm.pfd];
                                warp_prefetch((const char*)g_scr + (size_t)(g < 32 ? G_CTX + g : G_LOC - 32 + g) * (SEQ * 256) + m * 32768 + (c >> 1) * 8192, 8192);
                                warp_prefetch(prm.wo[g >> 5] + (g & 31) * 262144 + (m * 4 + (c >> 1)) * 4096, 4096);
                            }
                            if (st == 3) gph ^= 1;
                        }
                        need_g = 63;
                        held_type = is_out ? T_END : type;
                        k0 = 0;
                    }
                }
                for (uint32_t st = 0; st < 4; st++) { mbar_wait(bars + B_GEMPTY + 8 * st, gph); mbar_wait(bars + B_AEMPTY + 16 + 8 * st, a_parity(2 + st)); }
                if (lane == 0 && atomicAdd(&g_sync.done, 1u) == NCTA - 1) {
                    g_sync.next = 0; g_sync.done = 0;
                    for (int i = 0; i < 4; i++) g_sync.count[i] = 0;
                    for (int i = 0; i < 16; i++) { g_sync.loc[i] = 0; g_sync.ctx[i] = 0; }
                }
            }
        } else if (warp <= 2) {
            for (int r = 2 * blockIdx.x + warp - 1; r < SEQ; r += 2 * NCTA) {
                float z = 0.f;
#pragma unroll
                for (int q = 0; q < 4; q++) {
                    const uint4 xv = __ldg((const uint4*)(prm.x + (size_t)r * 1024) + q * 32 + lane);
                    const uint4 wv = __ldg((const uint4*)prm.gate_w + q * 32 + lane);
                    const uint32_t xs[4] = {xv.x, xv.y, xv.z, xv.w}, ws[4] = {wv.x, wv.y, wv.z, wv.w};
#pragma unroll
                    for (int e = 0; e < 4; e++) {
                        z = fmaf(__uint_as_float(xs[e] << 16), __uint_as_float(ws[e] << 16), z);
                        z = fmaf(__uint_as_float(xs[e] & 0xffff0000u), __uint_as_float(ws[e] & 0xffff0000u), z);
                    }
                }
#pragma unroll
                for (int o = 16; o > 0; o >>= 1) z += __shfl_xor_sync(0xffffffffu, z, o);
                if (lane == 0) g_gate[r] = 1.f / (1.f + __expf(-z));
            }
            if (lane == 0) {
                asm volatile("fence.proxy.async;" ::: "memory");
                red_add(&g_sync.count[3], 1);
            }
            __syncwarp();
            {
                const int w = warp - 1;
                uint32_t sph = 0, oph = 0, aph = 0, nann = 0, nattn = 0;
                int unsent = -1;
                auto join_halves = [&]() -> bool {
                    bulk_wait<0>();
                    __syncwarp();
                    const uint32_t hb = bars + B_HALF + 8 * (nann & 3);
                    if (w == 0) mbar_arrive_if(lane == 0, hb);
                    else mbar_wait(hb, (nann >> 2) & 1);
                    nann++;
                    return w == 1;
                };
                auto announce = [&]() {
                    if (unsent < 0 || item_type(unsent) == T_OUT) return;
                    if (join_halves() && lane == 0) {
                        const int type = item_type(unsent), m = item_row(unsent), c = item_col(unsent);
                        if (type < T_B) red_add(&g_sync.count[c >> 3], 1ull << (8 * (c & 7)));
                        else if (type == T_B) red_add(&g_sync.count[2], 1ull << (4 * m));
                        else if (type == T_LOCAL) asm volatile("red.release.gpu.global.or.b32 [%0], %1;" :: "l"(&g_sync.loc[m]), "r"(3u << (2 * c)) : "memory");
                        else asm volatile("red.release.gpu.global.or.b64 [%0], %1;" :: "l"(&g_sync.ctx[m]), "l"(3ull << (2 * c)) : "memory");
                    }
                    __syncwarp();
                    unsent = -1;
                };
                auto store_item = [&](int it, bool borrow) {
                    const int type = item_type(it), m = item_row(it), c = item_col(it);
                    const int npair = type <= T_OUT ? 2 : 1;
                    const bool local = type == T_LOCAL;
                    const int grp = type == T_Q ? G_Q + 2 * c : type == T_K ? G_K + 2 * c : type == T_V ? G_V + 2 * c : type == T_B ? G_B + 2 * c
                                  : type == T_OUT ? G_PART + c : type == T_ATTN ? G_CTX + c : G_LOC + c;
                    for (int pr = 0; pr < npair; pr++) {
                        const bool final_out = type == T_OUT && pr;
                        if (final_out) {
                            announce();
                            if (join_halves() && lane == 0)
                                asm volatile("st.release.gpu.global.u64 [%0], %1;" :: "l"(&g_pflag[it & 127][0]), "l"(0x100000001ull) : "memory");
                            unsigned* flag = &g_pflag[(it & 127) ^ 16][w];
                            for (unsigned n = 0; !__all_sync(0xffffffffu, ld_acquire(flag) == 1);) spin_guard(n);
                            *flag = 0;
                            mbar_wait(bars + B_WIDE, oph);
                            oph ^= 1;
                            warp_expect_tx(bars + B_PRECV + 8 * w, 16384);
                            for (int b = 0; b < 2; b++)
                                warp_tma_load(sb + w * GST_BYTES + 32768 + b * 8192, &prm.m[M_SCR_ST], bars + B_PRECV + 8 * w, b * 64, m * 128 + w * 64, G_PART + (c ^ 1));
                        }
                        if (borrow && pr) {
                            mbar_wait(bars + B_ALT + 8 * w, aph);
                            aph ^= 1;
                            for (int b = 0; b < 2; b++)
                                warp_tma_store(&prm.m[M_SCR_ST], sb + ((nattn & 1) ^ 1) * 32768 + w * 16384 + b * 8192, b * 64, m * 128 + w * 64, grp + 1);
                            bulk_commit();
                            bulk_wait_read<0>();
                            __syncwarp();
                            mbar_arrive_if(lane == 0, bars + B_QFREE);
                            break;
                        }
                        for (int b = 0; b < 2; b++) {
                            if (!__all_sync(0xffffffffu, mbar_test(bars + B_SFULL + 16 * w + 8 * b, sph))) announce();
                            mbar_wait(bars + B_SFULL + 16 * w + 8 * b, sph);
                            warp_tma_store(&prm.m[final_out ? M_OUT : local ? M_SCR_LOQ : M_SCR_ST], sb + SM_STAGING + w * 16384 + b * 8192,
                                         local ? b * 128 + w * 64 : (final_out ? c * 128 : 0) + b * 64, local ? m * 64 : m * 128 + w * 64, final_out ? 0 : grp + pr);
                            bulk_commit();
                            bulk_wait_read<0>();
                            __syncwarp();
                            mbar_arrive_if(lane == 0, bars + B_SEMPTY + 16 * w + 8 * b);
                        }
                        sph ^= 1;
                    }
                    announce();
                    unsent = it;
                };
                int held = first_item();
                while (true) {
                    if (!__all_sync(0xffffffffu, mbar_test(bars + B_IFULL + 8 * (qn % QDEPTH), (qn / QDEPTH) & 1))) announce();
                    const int it = __shfl_sync(0xffffffffu, next_item(lane == 0), 0), type = item_type(it);
                    const bool keep_held = type == T_LOCAL && item_type(held) != T_B;
                    for (int pass = held < 0 || keep_held; pass < 2; pass++) {
                        if (pass && (type < T_OUT || type == T_END)) break;
                        store_item(pass ? it : held, !pass && type == T_ATTN);
                    }
                    if (type == T_END) break;
                    nattn += type == T_ATTN;
                    if (!keep_held) held = type < T_OUT ? it : -1;
                }
                announce();
            }
        } else {
            if (elect_one()) {
                uint32_t ordy = 0;
                unsigned long long cnt_lo = 0, cnt_hi = 0;
                int late = 0;
                auto refresh = [&]() {
                    if (!late && cnt_lo == 0xccccccccccccccccull && cnt_hi == 2 * NCTA) late = 1;
                    asm volatile("ld.acquire.gpu.global.v2.u64 {%0, %1}, [%2];" : "=l"(cnt_lo), "=l"(cnt_hi) : "l"(&g_sync.count[2 - 2 * late]) : "memory");
                };
                auto inputs_ready = [&](int it) -> bool {
                    const int m = item_row(it), c = item_col(it);
                    if (item_type(it) == T_ATTN) return late && ((c < 16 ? cnt_lo : cnt_hi) >> (4 * (c & 14)) & 255) == 48;
                    return late || (cnt_hi == 2 * NCTA && (cnt_lo >> (4 * m) & 15) == 12 && (cnt_lo >> (4 * max(m - 1, 0)) & 15) == 12);
                };
                int asc = 1;
                while (true) {
                    int it;
                    if (rank == 0) {
                        mbar_wait(bars + B_WANT, qn & 1);
                        unsigned i;
                        asm volatile("atom.relaxed.gpu.global.add.u32 %0, [%1], 1;" : "=r"(i) : "l"(&g_sync.next) : "memory");
                        if (cnt_lo != 0x3030303030303030ull || cnt_hi != cnt_lo) refresh();
                        i += NPAIR;
                        const int pit = i < NITEMS ? prm.items[i] : T_END << 13, type = item_type(pit);
                        int step = type == T_LOCAL ? 16 : 1;
                        it = pit + (pit & (step == 1 ? 15 : 0x1f0));
                        if (type == T_ATTN) {
                            if (!asc) { it += 1; step = -1; }
                            it |= asc << 9;
                        }
                        asc = type != T_ATTN || item_row(pit) == 0 || !asc;
                        if (inputs_ready(it)) it |= ITEM_READY;
                        const uint32_t slot = qn % QDEPTH;
                        mbar_wait(bars + B_IEMPTY + 8 * slot, ((qn / QDEPTH) & 1) ^ 1);
                        for (uint32_t r = 0; r < 2; r++) {
                            const uint32_t rb = map_cta(bars, r);
                            asm volatile("mbarrier.arrive.expect_tx.shared::cluster.b64 _, [%0], 4;" :: "r"(rb + B_IFULL + 8 * slot) : "memory");
                            asm volatile("st.async.shared::cluster.mbarrier::complete_tx::bytes.u32 [%0], %1, [%2];"
                                         :: "r"(rb + SM_QUEUE + 4 * slot), "r"(it + r * step), "r"(rb + B_IFULL + 8 * slot) : "memory");
                        }
                        qn++;
                    } else {
                        it = next_item(true);
                    }
                    if (item_type(it) == T_END) {
                        if (rank == 0) for (uint32_t n = qn; n < qn + QDEPTH; n++) mbar_wait(bars + B_IEMPTY + 8 * (n % QDEPTH), ((n / QDEPTH) & 1) ^ 1);
                        break;
                    }
                    const int type = item_type(it), m = item_row(it), c = item_col(it);
                    unsigned n = 0;
                    if (type == T_OUT) {
                        if (prm.pfd < 20) for (int i = 0; i < prm.pfd; i++) {
                            const int g = prm.oseq[c & 1][i];
                            prefetch_l2((const char*)g_scr + (size_t)(g < 32 ? G_CTX + g : G_LOC - 32 + g) * (SEQ * 256) + m * 32768, 32768);
                            prefetch_l2(prm.wo[g >> 5] + (g & 31) * 262144 + (((m & 3) * 4 + (c >> 1)) & 15) * 16384, 16384);
                        }
                        for (int i = 0; i < 22;) {
                            const unsigned long long rc = ld_acquire(&g_sync.ctx[m]);
                            const unsigned rl = ld_acquire(&g_sync.loc[m]);
                            for (; i < 22; i++, ordy++) {
                                const int g = prm.oseq[c & 1][i];
                                if (((g >= 32 ? rl >> (2 * g - 64) : rc >> (2 * g)) & 3) != 3) break;
                            }
                            asm volatile("st.release.cta.shared.u32 [%0], %1;" :: "r"(bars + SM_ORDY), "r"(ordy) : "memory");
                            spin_guard(n);
                        }
                    } else if (type > T_OUT && !(it & ITEM_READY)) {
                        while (!inputs_ready(it)) { refresh(); spin_guard(n); }
                        asm volatile("st.release.cta.shared.u32 [%0], %1;" :: "r"(bars + SM_ORDY), "r"(++ordy) : "memory");
                    }
                }
            }
        }
    } else {
        reg_inc<232>();
        const int wg = (warp >> 2) - 1, wq = warp & 3;
        uint32_t gph = 0;
        uint32_t kvn = 0;
        const uint32_t dA = make_desc(sb + wg * 8192, 16);
        uint32_t ti = 0;
        uint32_t oph = 0;
        uint32_t sph = 1;
        const uint32_t stg = sb + SM_STAGING + wg * 16384;
        const uint32_t stg_row = stg + (wq * 16 + (lane & 15)) * 128;
        auto release = [&](uint32_t bar) { mbar_arrive_if(lane == 0, bars + bar); };
        const uint32_t bars_lane = map_cta(bars, lane & 1);
        auto release_stage = [&](uint32_t st) { mbar_arrive_cluster_if(lane < 2, bars_lane + B_GEMPTY + 8 * st); };
        auto take_item = [&]() -> int {
            return __shfl_sync(0xffffffffu, next_item(lane == 0, false), 0);
        };
        auto stage_acquire = [&](int b) { mbar_spin(bars + B_SEMPTY + 16 * wg + 8 * b, sph); };
        auto stage_publish = [&](int b) {
            fence_proxy_async_smem();
            __syncwarp();
            release(B_SFULL + 16 * wg + 8 * b);
        };
        auto stage_chunk = [&](int b, const uint32_t* v) {
            stage_acquire(b);
#pragma unroll
            for (int j = 0; j < 4; j++)
                stmatrix_x4(stg_row + b * 8192 + (((j * 2 + (lane >> 4)) ^ (lane & 7)) << 4), v[4 * j], v[4 * j + 1], v[4 * j + 2], v[4 * j + 3]);
            stage_publish(b);
            if (b) sph ^= 1;
        };
        auto stage_pair = [&](const uint32_t* v) {
            stage_acquire(0); stage_acquire(1);
#pragma unroll
            for (int j = 0; j < 8; j++)
                stmatrix_x4(stg_row + (j >> 2) * 8192 + ((((j & 3) * 2 + (lane >> 4)) ^ (lane & 7)) << 4), v[4 * j], v[4 * j + 1], v[4 * j + 2], v[4 * j + 3]);
            fence_proxy_async_smem();
            __syncwarp();
            mbar_arrive_if(lane < 2, bars + B_SFULL + 16 * wg + 8 * lane);
            sph ^= 1;
        };
        if (wg == 1) bar_arrive(1, 256);
        int it = first_item();
        while (item_type(it) != T_END) {
            if (item_type(it) <= T_LOCAL) {
                float acc[128];
                uint32_t pk[64];
                bool pending = false;
                bool final_out = false;
                zero_regs(pk);
                const uint32_t dB = make_desc(sb + 16384, 8192);
                do {
                    const int type = item_type(it);
                    if (type == T_LOCAL) {
                        int ln = lane;
                        asm volatile("" : "+r"(ln));
                        const int g = ln >> 2, t = ln & 3, par = wq & 1;
                        const uint32_t hc = (wq >> 1) * 4, pl = sb + (par * 2 + wg) * LOC_PLANE;
                        const uint32_t a16 = (ln & 15) * 128 + (((hc + (ln >> 4)) ^ (ln & 7)) << 4), a8 = (ln & 7) * 128 + (((hc + (ln >> 3)) ^ (ln & 7)) << 4);
                        const bool first0 = 2 * t > g, first1 = 2 * t + 1 > g;
                        const uint32_t fmask = (first0 ? 0xffffu : 0u) | (first1 ? 0xffff0000u : 0u);
                        const bool edge = item_row(it) == 0;
                        uint32_t q[4][2][4], kf[9][4], vf[9][4];
                        float w[8];
                        mbar_spin(bars + B_GFULL, gph);
#pragma unroll
                        for (int u = 0; u < 4; u++) { ldsm_x4(q[u][0], pl + u * 2048 + a16); ldsm_x4(q[u][1], pl + u * 2048 + (a16 ^ 32)); }
#pragma unroll
                        for (int j = 0; j < 8; j++) w[j] = lds_f32(sb + 4 * LOC_PLANE + 4 * (2 * g + par) + 64 * j);
                        __syncwarp();
                        release_stage(0);
                        mbar_spin(bars + B_GFULL + 8, gph);
#pragma unroll
                        for (int n = 0; n < 9; n++) ldsm_x4(kf[n], pl + GST_BYTES + n * 1024 + a8);
                        __syncwarp();
                        release_stage(1);
                        float s[8][2];
#pragma unroll
                        for (int u = 0; u < 4; u++) {
                            float d[3][4];
#pragma unroll
                            for (int nt = 0; nt < 3; nt++) {
                                mma_k16_init(d[nt], q[u][0], kf[2 * u + nt][0], kf[2 * u + nt][1]);
                                mma_k16(d[nt], q[u][1], kf[2 * u + nt][2], kf[2 * u + nt][3]);
                            }
                            if (u == 0 && edge) { d[0][0] = -INFINITY; d[0][1] = -INFINITY; }
                            s[2 * u][0] = first0 ? d[0][0] : d[1][0]; s[2 * u][1] = first1 ? d[0][1] : d[1][1];
                            s[2 * u + 1][0] = first0 ? d[1][2] : d[2][2]; s[2 * u + 1][1] = first1 ? d[1][3] : d[2][3];
                        }
                        mbar_spin(bars + B_GFULL + 16, gph);
#pragma unroll
                        for (int u = 0; u < 4; u++) { ldsm_x4_t(vf[2 * u], pl + 2 * GST_BYTES + u * 2048 + a16); ldsm_x4_t(vf[2 * u + 1], pl + 2 * GST_BYTES + u * 2048 + (a16 ^ 32)); }
                        ldsm_x4_t(vf[8], pl + 2 * GST_BYTES + 8192 + a8);
                        __syncwarp();
                        release_stage(2);
                        float x[8];
#pragma unroll
                        for (int j = 0; j < 8; j++) x[j] = fmaxf(s[j][0], s[j][1]);
#pragma unroll
                        for (int o = 1; o < 4; o *= 2)
#pragma unroll
                            for (int j = 0; j < 8; j++) x[j] = fmaxf(x[j], __shfl_xor_sync(0xffffffffu, x[j], o));
#pragma unroll
                        for (int j = 0; j < 8; j++) {
                            const float n = x[j] * -LOC_SCALE;
                            s[j][0] = ex2(fmaf(s[j][0], LOC_SCALE, n)); s[j][1] = ex2(fmaf(s[j][1], LOC_SCALE, n));
                            x[j] = s[j][0] + s[j][1];
                        }
#pragma unroll
                        for (int o = 1; o < 4; o *= 2)
#pragma unroll
                            for (int j = 0; j < 8; j++) x[j] += __shfl_xor_sync(0xffffffffu, x[j], o);
                        mbar_spin(bars + B_GFULL + 24, gph);
                        release_stage(3);
                        it = take_item();
                        uint32_t ob[4][8];
#pragma unroll
                        for (int u = 0; u < 4; u++) {
                            const float r0 = rcp(x[2 * u]), r1 = rcp(x[2 * u + 1]), f0 = fmaf(-w[2 * u], r0, r0), f1 = fmaf(-w[2 * u + 1], r1, r1);
                            const uint32_t p0 = pack_bf16(s[2 * u][0] * f0, s[2 * u][1] * f0), p1 = pack_bf16(s[2 * u + 1][0] * f1, s[2 * u + 1][1] * f1);
                            const uint32_t pa[4] = {p0 & fmask, 0, p0 & ~fmask, p1 & fmask};
#pragma unroll
                            for (int c = 0; c < 4; c++) {
                                float ol[4];
                                mma_k16_init(ol, pa, vf[2 * u + (c >> 1)][2 * (c & 1)], vf[2 * u + (c >> 1)][2 * (c & 1) + 1]);
                                mma_k8(ol, 0, p1 & ~fmask, u < 3 ? vf[2 * u + 2 + (c >> 1)][2 * (c & 1)] : vf[8][c]);
                                ob[u][2 * c] = pack_bf16(ol[0], ol[1]);
                                ob[u][2 * c + 1] = pack_bf16(ol[2], ol[3]);
                            }
                        }
                        stage_acquire(0); stage_acquire(1);
#pragma unroll
                        for (int u = 0; u < 4; u++) {
                            stmatrix_x4(stg + par * 8192 + u * 2048 + a16, ob[u][0], ob[u][1], ob[u][2], ob[u][3]);
                            stmatrix_x4(stg + par * 8192 + u * 2048 + (a16 ^ 32), ob[u][4], ob[u][5], ob[u][6], ob[u][7]);
                        }
                        fence_proxy_async_smem();
                        __syncwarp();
                        mbar_arrive_if(lane < 2, bars + B_SFULL + 16 * wg + 8 * lane);
                        bar_sync(4, 256);
                        sph ^= 1; gph ^= 1;
                        continue;
                    }
                    const int nk = type == T_OUT ? 36 : (type == T_K || type == T_V) ? 8 : 16;
                    mbar_spin(bars + B_GFULL, gph);
                    wgmma_fence();
                    wgmma_ss_n256_tb_init(acc, full_desc(dA), full_desc(dB));
#pragma unroll
                    for (int kk = 1; kk < 4; kk++) wgmma_ss_n256_tb(acc, full_desc(dA) + 2 * kk, full_desc(dB) + 128 * kk, 1);
                    wgmma_commit();
                    for (int k = 1; k < nk; k++) {
                        const uint32_t st = k & 3;
                        if (pending) {
                            const int kf = k - 1 - wg;
                            if (kf == 0) stage_chunk(0, pk);
                            else if (kf == 1) stage_chunk(1, pk + 16);
                            else if (kf == 3) stage_chunk(0, pk + 32);
                            else if (kf == 4) stage_chunk(1, pk + 48);
                        }
                        const bool lag = wg == 1 && k == nk - 2 && type != T_OUT;
                        asm volatile("{\n.reg .pred P;\nsetp.ne.u32 P, %0, 0;\n@P wgmma.wait_group.sync.aligned 0;\n}\n" :: "r"((uint32_t)lag) : "memory");
                        mbar_arrive_cluster_if(lane < 2 && lag, bars_lane + B_GEMPTY + 8);
                        if (lag) bar_sync(3, 256);
                        mbar_wait(bars + B_GFULL + 8 * st, gph);
                        const uint64_t da = full_desc(dA + st * (GST_BYTES >> 4)), db = full_desc(dB + st * (GST_BYTES >> 4));
                        fence_regs(acc);
                        wgmma_fence();
#pragma unroll
                        for (int kk = 0; kk < 4; kk++) wgmma_ss_n256_tb(acc, da + 2 * kk, db + 128 * kk, 1);
                        wgmma_commit();
                        if (wg == 0 && k == nk - 1 && type != T_OUT) bar_arrive(3, 256);
                        wgmma_wait<1>();
                        mbar_arrive_cluster_if(lane < 2 && !lag, bars_lane + B_GEMPTY + 8 * ((k - 1) & 3));
                        if (st == 3) gph ^= 1;
                    }
                    wgmma_wait<0>();
                    fence_regs(acc);
                    release_stage(3);
                    if (type == T_OUT) {
                        release(B_WIDE);
                        for (int k = 0; k < 8; k++) {
                            const uint32_t st = k & 3;
                            mbar_spin(bars + B_GFULL + 8 * st, gph);
                            const uint64_t da = full_desc(dA + st * (GST_BYTES >> 4)), db = full_desc(dB + st * (GST_BYTES >> 4));
                            wgmma_fence();
#pragma unroll
                            for (int kk = 0; kk < 4; kk++) wgmma_ss_n128_lo_tb(acc, da + 2 * kk, db + 128 * kk, 1);
                            wgmma_commit();
                            if (k > 0) {
                                wgmma_wait<1>();
                                release_stage((k - 1) & 3);
                            }
                            if (k == 0) {
#pragma unroll
                                for (int j = 0; j < 32; j++) pk[j] = pack_bf16(acc[64 + 2 * j], acc[65 + 2 * j]);
                                stage_chunk(0, pk);
                                stage_chunk(1, pk + 16);
                            }
                            if (st == 3) gph ^= 1;
                        }
                        it = take_item();
                        mbar_spin(bars + B_PRECV + 8 * wg, oph);
                        oph ^= 1;
                        uint32_t v[8][4];
#pragma unroll
                        for (int j = 0; j < 8; j++)
                            ldsm_x4(v[j], stg_row - stg + sb + wg * GST_BYTES + 32768 + (j >> 2) * 8192 + ((((j & 3) * 2 + (lane >> 4)) ^ (lane & 7)) << 4));
                        wgmma_wait<0>();
                        fence_regs(acc);
                        __syncwarp();
                        release_stage(3);
#pragma unroll
                        for (int j = 0; j < 32; j++)
                            pk[j] = pack_bf16(acc[2 * j] + __uint_as_float(v[j >> 2][j & 3] << 16), acc[2 * j + 1] + __uint_as_float(v[j >> 2][j & 3] & 0xffff0000u));
                        pending = false; final_out = true;
                        break;
                    }
#pragma unroll
                    for (int j = 0; j < 64; j++) pk[j] = pack_bf16(acc[2 * j], acc[2 * j + 1]);
                    pending = true;
                    it = take_item();
                    if (type == T_B && item_type(it) == T_LOCAL) break;
                } while (item_type(it) <= T_LOCAL);
                if (pending || final_out) { stage_chunk(0, pk); stage_chunk(1, pk + 16); }
                if (pending && item_type(it) == T_ATTN) {
                    mbar_spin(bars + B_GEMPTY, gph ^ 1); mbar_spin(bars + B_GEMPTY + 8, gph ^ 1);
                    const uint32_t base = stg_row - stg + sb + ((ti & 1) ^ 1) * 32768 + wg * 16384;
#pragma unroll
                    for (int j = 0; j < 8; j++)
                        stmatrix_x4(base + (j >> 2) * 8192 + ((((j & 3) * 2 + (lane >> 4)) ^ (lane & 7)) << 4), pk[32 + 4 * j], pk[33 + 4 * j], pk[34 + 4 * j], pk[35 + 4 * j]);
                    fence_proxy_async_smem();
                    __syncwarp();
                    release(B_ALT + 8 * wg);
                } else if (pending) {
                    stage_chunk(0, pk + 32); stage_chunk(1, pk + 48);
                }
            } else {
                float o[64], s[64];
                uint32_t pa[32], pb[32];
                zero_regs(o); zero_regs(s); zero_regs(pa);
                float n0 = 0.f, n1 = 0.f;
                float l0 = 1.f, l1 = 1.f, f0 = 0.f, f1 = 0.f, g0 = 0.f, g1 = 0.f;
                uint32_t has_pv = 0;
                int first = 0;
                int pending = 0;
                const uint32_t dK = make_desc(sb + SM_KV, 16), dV = make_desc(sb + SM_KV, 16384);
                const uint32_t lane_off = bars_lane - bars + B_AEMPTY - B_AFULL;
                int cur = 0;
                uint32_t qoff = 0;
                const int row = wg * 64 + wq * 16 + (lane >> 2), thr = row - (lane & 3) * 2;
                auto kv_wait = [&](uint32_t n) { mbar_spin(bars + B_AFULL + 16 + 8 * (n & 3), (n >> 2) & 1); };
                auto kv_release = [&](uint32_t n) { mbar_arrive_cluster_if(lane < 2, bars_lane + B_AEMPTY + 16 + 8 * (n & 3)); };
                struct Slot { uint32_t bar, par, off; } slot[4];
                auto align = [&]() {
#pragma unroll
                    for (uint32_t i = 0; i < 4; i++) {
                        const uint32_t n = kvn + (i == 1 ? has_pv : i);
                        slot[i].bar = bars + B_AFULL + 16 + 8 * (n & 3); slot[i].par = (n >> 2) & 1; slot[i].off = (n & 3) * 2048;
                    }
                };
                align();
                auto pack_o = [&](uint32_t (&v)[32]) {
#pragma unroll
                    for (int j = 0; j < 16; j++) {
                        v[2 * j] = pack_bf16(o[4 * j] * f0, o[4 * j + 1] * f0);
                        v[2 * j + 1] = pack_bf16(o[4 * j + 2] * f1, o[4 * j + 3] * f1);
                    }
                };
                auto scales = [&]() { f0 = g0 * rcp(quad_sum(l0)); f1 = g1 * rcp(quad_sum(l1)); };
                auto step = [&](auto even, uint32_t (&pin)[32], uint32_t (&pout)[32], bool fresh, bool diag) {
                    constexpr bool EVEN = decltype(even)::value;
                    Slot& sk = slot[EVEN ? 0 : 2];
                    Slot& sv = slot[EVEN ? 1 : 3];
                    kvn += EVEN ? 1 + has_pv : 2;
                    mbar_spin(sk.bar, sk.par);
                    bar_sync(1 + wg, 256);
                    qk_gemm(s, dA + qoff, dK + sk.off);
                    if (EVEN && fresh) scales();
                    if (!EVEN && pending) { pack_o(pout); stage_pair(pout); }
                    mbar_spin(sv.bar, sv.par);
                    pv_gemm(o, pin, dV + sv.off, EVEN || !first);
                    bar_arrive(2 - wg, 256);
                    sk.par ^= 1; sv.par ^= 1;
                    wgmma_wait<1>();
                    fence_regs(s);
                    mbar_arrive_cluster_if(lane < 2 && (!EVEN || has_pv), sk.bar + lane_off);
                    if (diag) causal_mask(s, thr, wg);
                    if (EVEN && fresh) {
                        row_max<2>(s, n0, n1);
                        n0 *= -SM_SCALE; n1 *= -SM_SCALE;
                        l0 = 0.f; l1 = 0.f;
                    }
                    float r0, r1;
                    exp_pack(pout, s, n0, n1, r0, r1);
                    if (__any_sync(0xffffffffu, fmaxf(r0, r1) >= SUM_LIMIT)) {
                        float x0, x1;
                        row_max<16>(s, x0, x1);
                        x0 = fminf(x0 * -SM_SCALE, n0); x1 = fminf(x1 * -SM_SCALE, n1);
                        float a0 = ex2(x0 - n0), a1 = ex2(x1 - n1);
                        n0 = x0; n1 = x1;
                        l0 *= a0; l1 *= a1;
                        if (EVEN && fresh) { a0 = 1.f; a1 = 1.f; }
                        wgmma_wait<0>();
                        fence_regs(o);
#pragma unroll
                        for (int q = 0; q < 16; q++) { o[4 * q] *= a0; o[4 * q + 1] *= a0; o[4 * q + 2] *= a1; o[4 * q + 3] *= a1; }
                        exp_pack(pout, s, n0, n1, r0, r1);
                    }
                    l0 += r0; l1 += r1;
                    wgmma_wait<0>();
                    fence_regs(o);
                    fence_regs(pin);
                    mbar_arrive_cluster_if(lane < 2, sv.bar + lane_off);
                };
                auto copy_p = [&]() {
#pragma unroll
                    for (int j = 0; j < 32; j++) pa[j] = pb[j] ^ prm.zero;
                };
                int rem = 0;
                while (true) {
                    const bool fresh = rem == 0;
                    if (fresh) {
                        if (has_pv) {
                            release(B_AEMPTY + 8 * ((ti - 1) & 1));
                            it = take_item();
                            if (item_row(cur) < 2 || item_type(it) != T_ATTN) break;
                        }
                        cur = it;
                        qoff = (ti & 1) * 2048;
                        mbar_spin(bars + B_AFULL + 8 * (ti & 1), (ti >> 1) & 1);
                    }
                    step(std::true_type(), pa, pb, fresh, fresh ? !item_asc(cur) || item_row(cur) == 0 : item_asc(cur) && rem == 1);
                    first = fresh;
                    if (fresh) {
                        pending = has_pv; has_pv = 1;
                        if (!pending) { kvn -= 2; align(); kvn += 2; slot[0].par ^= 1; slot[1].par ^= 1; }
                        rem = item_row(cur);
                        g0 = lds_f32(bars + SM_GATE + (ti & 1) * 512 + 4 * row); g1 = lds_f32(bars + SM_GATE + (ti & 1) * 512 + 4 * row + 32);
                        ti++;
                        if (rem == 0) {
                            copy_p();
                            continue;
                        }
                    } else if (--rem == 0) {
                        copy_p();
                        align();
                        continue;
                    }
                    step(std::false_type(), pb, pa, false, item_asc(cur) && rem == 1);
                    pending = 0; first = 0;
                    rem--;
                }
                const uint32_t skip = item_asc(cur) & ~item_row(cur) & 1;
                kvn += skip;
#pragma unroll 1
                for (int pass = pending ? 0 : 1; pass < 2; pass++) {
                    if (pass) {
                        kv_wait(kvn);
                        pv_gemm(o, pa, dV + (kvn & 3) * 2048, !first);
                        scales();
                        wgmma_wait<0>();
                        fence_regs(o);
                        kv_release(kvn);
                        kvn += 1 + skip;
                    }
                    pack_o(pb);
                    stage_pair(pb);
                }
            }
        }
    }
}

typedef CUresult (*EncodeFn)(CUtensorMap*, CUtensorMapDataType, cuuint32_t, void*, const cuuint64_t*, const cuuint64_t*,
                             const cuuint32_t*, const cuuint32_t*, CUtensorMapInterleave, CUtensorMapSwizzle,
                             CUtensorMapL2promotion, CUtensorMapFloatOOBfill);

void encode3(EncodeFn fn, CUtensorMap* m, const void* ptr, uint64_t d0, uint64_t d1, uint64_t d2, uint64_t s1, uint64_t s2,
             uint32_t b0, uint32_t b1, uint32_t b2) {
    cuuint64_t dims[3] = {d0, d1, d2};
    cuuint64_t strides[2] = {s1, s2};
    cuuint32_t box[3] = {b0, b1, b2};
    cuuint32_t es[3] = {1, 1, 1};
    fn(m, CU_TENSOR_MAP_DATA_TYPE_BFLOAT16, 3, const_cast<void*>(ptr), dims, strides, box, es, CU_TENSOR_MAP_INTERLEAVE_NONE,
       CU_TENSOR_MAP_SWIZZLE_128B, CU_TENSOR_MAP_L2_PROMOTION_NONE, CU_TENSOR_MAP_FLOAT_OOB_FILL_NONE);
}
void map_act(EncodeFn fn, CUtensorMap* m, const void* p, int rows, int cols, int box_rows) {
    encode3(fn, m, p, cols, rows, 1, (uint64_t)cols * 2, (uint64_t)cols * rows * 2, 64, box_rows, 1);
}
void map_wgt(EncodeFn fn, CUtensorMap* m, const void* p, int K, int N) {
    encode3(fn, m, p, 64, K, N / 64, (uint64_t)N * 2, 128, 64, 64, 2);
}

void build_schedule(Params& p) {
    int n = 0;
    auto add = [&](int type, int col, int row) { p.items[n++] = (uint16_t)(type << 13 | col << 4 | row); };
    auto add_qkv = [&](int c) {
        for (int m = 0; m < 8; m++) add(T_Q, c, m);
        for (int m = 0; m < 8; m++) add(T_K, c, m);
        for (int m = 0; m < 8; m++) add(T_V, c, m);
    };
    int ldist = 170, ldist2 = 250, lstep = 16, beta = 26, tail = 32, late = 6;
    int order[16] = {6, 7, 8, 9, 10, 11, 12, 13, 14, 15, 5, 4, 3, 2, 1, 0};
    uint16_t proj[480];
    for (int m = 0; m < 8; m++) for (int c = 0; c < 12; c++) add(T_B, c, m);
    for (int c = 0; c < 16; c++) add_qkv(c);
    for (int i = 0; i < 480; i++) proj[i] = p.items[i];
    n = 0;
    for (int i = 0, l = 0; i < 480; i++) {
        p.items[n++] = proj[i];
        for (; l < 64 && i >= (l < 40 ? ldist + lstep * l / 8 : ldist2 + lstep * (l - 40) / 8); l++) add(T_LOCAL, l & 3, l >> 2);
    }
    const int a0 = n;
    for (int key = 0; key < 4000; key++)
        for (int r = 0; r < 32; r++)
            for (int j = 7; j >= 0; j--)
                if ((j ? (7 - j) * 40 + r * beta : 3999) == key) add(T_ATTN, 2 * order[r >> 1] + (r & 1), j);
    int t0 = n;
    for (int work = 0; work < 32 * 136 * tail / 100;) work += 4 * (p.items[--t0] & 15) + 3;
    for (int i = t0 + 1; i < n; i++)
        for (int j = i; j > t0 && (p.items[j] & 15) > (p.items[j - 1] & 15); j--) { const uint16_t t = p.items[j]; p.items[j] = p.items[j - 1]; p.items[j - 1] = t; }
    for (int moved = 0; moved < 2 && late >= 0; moved++)
        for (int i = a0; i < n; i++)
            if (p.items[i] == (T_ATTN << 13 | (2 * order[15] + moved) << 4 | late)) {
                for (int j = i; j + 1 < n; j++) p.items[j] = p.items[j + 1];
                p.items[n - 1] = (uint16_t)(T_ATTN << 13 | (2 * order[15] + moved) << 4 | late);
                break;
            }
    for (int m = 7; m >= 0; m--) for (int c = 0; c < 8; c++) add(T_OUT, c, m);
    for (int half = 0; half < 2; half++) {
        for (int i = 0; i < 20; i++) p.oseq[half][i] = (uint8_t)(i < 4 ? 32 + 4 * half + i : 2 * order[i - 4] + half);
        for (int i = 0; i < 2; i++) p.oseq[half][20 + i] = (uint8_t)(2 * order[14 + i] + 1 - half);
    }
}

void build_params(Params& p, void* const* d_in, void* d_out) {
    void* fnp = nullptr;
    cudaDriverEntryPointQueryResult qr;
    cudaGetDriverEntryPoint("cuTensorMapEncodeTiled", &fnp, cudaEnableDefault, &qr);
    EncodeFn fn = (EncodeFn)fnp;
    void* scr = nullptr;
    cudaGetSymbolAddress(&scr, g_scr);
    map_act(fn, &p.m[M_X], d_in[0], SEQ, 1024, 128);
    map_act(fn, &p.m[M_C], d_in[1], SEQ, 512, 128);
    map_wgt(fn, &p.m[M_WQ], d_in[2], 1024, 4096);
    map_wgt(fn, &p.m[M_WUK], d_in[3], 512, 4096);
    map_wgt(fn, &p.m[M_WUV], d_in[4], 512, 4096);
    map_wgt(fn, &p.m[M_WO], d_in[5], 4096, 1024);
    map_wgt(fn, &p.m[M_WQKV], d_in[7], 1024, 3072);
    map_wgt(fn, &p.m[M_WOB], d_in[8], 1024, 1024);
    encode3(fn, &p.m[M_SCR_LD], scr, 128, SEQ, G_TOTAL, 256, (uint64_t)SEQ * 256, 64, 128, 1);
    encode3(fn, &p.m[M_SCR_LOC], scr, 256, SEQ / 2, G_TOTAL, 512, (uint64_t)SEQ * 256, 64, 72, 1);
    encode3(fn, &p.m[M_SCR_LOQ], scr, 256, SEQ / 2, G_TOTAL, 512, (uint64_t)SEQ * 256, 64, 64, 1);
    encode3(fn, &p.m[M_SCR_ST], scr, 128, SEQ, G_TOTAL, 256, (uint64_t)SEQ * 256, 64, 64, 1);
    map_act(fn, &p.m[M_OUT], d_out, SEQ, 1024, 64);
    p.x = (const __nv_bfloat16*)d_in[0];
    p.gate_w = (const __nv_bfloat16*)d_in[9];
    p.zero = 0;
    p.wo[0] = (const char*)d_in[5]; p.wo[1] = (const char*)d_in[8]; p.pfd = 99;
    build_schedule(p);
}

}

extern "C" void kernel_launch(void* const* d_in, const int* in_sizes, int n_in, void* d_out, int out_size) {
    (void)in_sizes; (void)n_in; (void)out_size;
    Params p;
    build_params(p, d_in, d_out);
    cudaFuncSetAttribute(fused_kernel, cudaFuncAttributeMaxDynamicSharedMemorySize, SM_TOTAL);
    fused_kernel<<<NCTA, 384, SM_TOTAL>>>(p);
}
```

```cpp
#include <cuda_runtime.h>
#include <cuda_bf16.h>
#include <cuda.h>
#include <stdint.h>
#include <type_traits>

namespace {

constexpr int SEQ = 2048;
constexpr int G_Q = 0, G_K = 32, G_V = 64, G_B = 96, G_CTX = G_Q, G_LOC = G_B, G_PART = 120, G_TOTAL = 128;

__device__ __align__(1024) __nv_bfloat16 g_scr[(size_t)G_TOTAL * SEQ * 128];
__device__ __align__(128) float g_gate[SEQ];

__device__ __forceinline__ uint32_t smem_u32(const void* p) { return (uint32_t)__cvta_generic_to_shared(p); }
__device__ __forceinline__ bool elect_one() {
    uint32_t p;
    asm volatile("{\n.reg .pred P;\nelect.sync _|P, 0xffffffff;\nselp.u32 %0, 1, 0, P;\n}\n" : "=r"(p));
    return p != 0;
}
__device__ __forceinline__ void mbar_init(uint32_t bar, uint32_t count) {
    asm volatile("mbarrier.init.shared::cta.b64 [%0], %1;" :: "r"(bar), "r"(count) : "memory");
}
__device__ __forceinline__ void mbar_expect_tx(uint32_t bar, uint32_t bytes) {
    asm volatile("mbarrier.arrive.expect_tx.shared::cta.b64 _, [%0], %1;" :: "r"(bar), "r"(bytes) : "memory");
}
__device__ __forceinline__ uint32_t cluster_rank() { uint32_t r; asm("mov.u32 %0, %%cluster_ctarank;" : "=r"(r)); return r; }
__device__ __forceinline__ uint32_t map_cta(uint32_t addr, uint32_t cta) {
    uint32_t r; asm("mapa.shared::cluster.u32 %0, %1, %2;" : "=r"(r) : "r"(addr), "r"(cta)); return r;
}
__device__ __forceinline__ void mbar_arrive_cluster_if(bool pred, uint32_t cluster_bar) {
    asm volatile("{\n.reg .pred P;\nsetp.ne.u32 P, %1, 0;\n@P mbarrier.arrive.shared::cluster.b64 _, [%0];\n}\n"
                 :: "r"(cluster_bar), "r"((uint32_t)pred) : "memory");
}
__device__ __forceinline__ void mbar_arrive_cluster_n_if(bool pred, uint32_t cluster_bar, uint32_t count) {
    asm volatile("{\n.reg .pred P;\nsetp.ne.u32 P, %1, 0;\n@P mbarrier.arrive.shared::cluster.b64 _, [%0], %2;\n}\n"
                 :: "r"(cluster_bar), "r"((uint32_t)pred), "r"(count) : "memory");
}
__device__ __forceinline__ void mbar_arrive_if(bool pred, uint32_t bar) {
    asm volatile("{\n.reg .pred P;\nsetp.ne.u32 P, %1, 0;\n@P mbarrier.arrive.shared::cta.b64 _, [%0];\n}\n"
                 :: "r"(bar), "r"((uint32_t)pred) : "memory");
}
__device__ __forceinline__ bool mbar_test(uint32_t bar, uint32_t parity) {
    uint32_t ok;
    asm volatile("{\n.reg .pred P;\nmbarrier.test_wait.parity.shared::cta.b64 P, [%1], %2;\nselp.u32 %0, 1, 0, P;\n}\n"
                 : "=r"(ok) : "r"(bar), "r"(parity) : "memory");
    return ok != 0;
}
__device__ __forceinline__ void mbar_wait(uint32_t bar, uint32_t parity) {
    asm volatile("{\n.reg .pred P;\n.reg .u32 c;\n"
                 "mbarrier.try_wait.parity.shared::cta.b64 P, [%0], %1;\n"
                 "@P bra DONE;\n"
                 "mov.u32 c, 0;\n"
                 "SPIN:\n"
                 "mbarrier.try_wait.parity.shared::cta.b64 P, [%0], %1;\n"
                 "@P bra DONE;\n"
                 "add.u32 c, c, 1;\n"
                 "setp.lt.u32 P, c, 4194304;\n"
                 "@P bra SPIN;\n"
                 "trap;\n"
                 "DONE:\n}\n" :: "r"(bar), "r"(parity) : "memory");
}
__device__ __forceinline__ void mbar_spin(uint32_t bar, uint32_t parity) {
    asm volatile("{\n.reg .pred P;\n"
                 "SPIN:\n"
                 "mbarrier.try_wait.parity.shared::cta.b64 P, [%0], %1;\n"
                 "@!P bra SPIN;\n}\n" :: "r"(bar), "r"(parity) : "memory");
}
__device__ __forceinline__ void bar_sync(int id, int n) { asm volatile("bar.sync %0, %1;" :: "r"(id), "r"(n) : "memory"); }
__device__ __forceinline__ void bar_arrive(int id, int n) { asm volatile("bar.arrive %0, %1;" :: "r"(id), "r"(n) : "memory"); }
__device__ __forceinline__ void fence_proxy_async_smem() { asm volatile("fence.proxy.async.shared::cta;" ::: "memory"); }
__device__ __forceinline__ void tma_load_3d(uint32_t dst, const CUtensorMap* map, uint32_t bar, int c0, int c1, int c2) {
    asm volatile("cp.async.bulk.tensor.3d.shared::cluster.global.mbarrier::complete_tx::bytes [%0], [%1, {%3, %4, %5}], [%2];"
                 :: "r"(dst), "l"(map), "r"(bar), "r"(c0), "r"(c1), "r"(c2) : "memory");
}
__device__ __forceinline__ void warp_expect_tx(uint32_t bar, uint32_t bytes) {
    asm volatile("{\n.reg .pred P;\nelect.sync _|P, 0xffffffff;\n@P mbarrier.arrive.expect_tx.shared::cta.b64 _, [%0], %1;\n}\n"
                 :: "r"(bar), "r"(bytes) : "memory");
}
__device__ __forceinline__ void warp_tma_load(uint32_t dst, const CUtensorMap* map, uint32_t bar, int c0, int c1, int c2) {
    asm volatile("{\n.reg .pred P;\nelect.sync _|P, 0xffffffff;\n"
                 "@P cp.async.bulk.tensor.3d.shared::cluster.global.mbarrier::complete_tx::bytes [%0], [%1, {%3, %4, %5}], [%2];\n}\n"
                 :: "r"(dst), "l"(map), "r"(bar), "r"(c0), "r"(c1), "r"(c2) : "memory");
}
__device__ __forceinline__ void warp_tma_load_pair(uint32_t dst, const CUtensorMap* map, uint32_t bar, int c0, int c1, int c2) {
    asm volatile("{\n.reg .pred P;\nelect.sync _|P, 0xffffffff;\n"
                 "@P cp.async.bulk.tensor.3d.shared::cluster.global.mbarrier::complete_tx::bytes.multicast::cluster"
                 " [%0], [%1, {%3, %4, %5}], [%2], %6;\n}\n"
                 :: "r"(dst), "l"(map), "r"(bar), "r"(c0), "r"(c1), "r"(c2), "h"((uint16_t)3) : "memory");
}
__device__ __forceinline__ void warp_bulk_load(uint32_t dst, const void* src, uint32_t bytes, uint32_t bar) {
    asm volatile("{\n.reg .pred P;\nelect.sync _|P, 0xffffffff;\n"
                 "@P cp.async.bulk.shared::cluster.global.mbarrier::complete_tx::bytes [%0], [%1], %2, [%3];\n}\n"
                 :: "r"(dst), "l"(src), "r"(bytes), "r"(bar) : "memory");
}
__device__ __forceinline__ void warp_tma_store(const CUtensorMap* map, uint32_t src, int c0, int c1, int c2) {
    asm volatile("{\n.reg .pred P;\nelect.sync _|P, 0xffffffff;\n"
                 "@P cp.async.bulk.tensor.3d.global.shared::cta.bulk_group [%0, {%2, %3, %4}], [%1];\n}\n"
                 :: "l"(map), "r"(src), "r"(c0), "r"(c1), "r"(c2) : "memory");
}
__device__ __forceinline__ void warp_bulk_store(void* dst, uint32_t src, uint32_t bytes) {
    asm volatile("{\n.reg .pred P;\nelect.sync _|P, 0xffffffff;\n"
                 "@P cp.async.bulk.global.shared::cta.bulk_group [%0], [%1], %2;\n}\n" :: "l"(dst), "r"(src), "r"(bytes) : "memory");
}
__device__ __forceinline__ void prefetch_l2(const void* src, uint32_t bytes) {
    asm volatile("cp.async.bulk.prefetch.L2.global [%0], %1;" :: "l"(src), "r"(bytes) : "memory");
}
__device__ __forceinline__ void warp_prefetch(const void* src, uint32_t bytes) {
    asm volatile("{\n.reg .pred P;\nelect.sync _|P, 0xffffffff;\n@P cp.async.bulk.prefetch.L2.global [%0], %1;\n}\n" :: "l"(src), "r"(bytes) : "memory");
}
__device__ __forceinline__ void bulk_commit() { asm volatile("cp.async.bulk.commit_group;" ::: "memory"); }
template <int N> __device__ __forceinline__ void bulk_wait_read() { asm volatile("cp.async.bulk.wait_group.read %0;" :: "n"(N) : "memory"); }
template <int N> __device__ __forceinline__ void bulk_wait() { asm volatile("cp.async.bulk.wait_group %0;" :: "n"(N) : "memory"); }
__device__ __forceinline__ void wgmma_fence() { asm volatile("wgmma.fence.sync.aligned;" ::: "memory"); }
__device__ __forceinline__ void wgmma_commit() { asm volatile("wgmma.commit_group.sync.aligned;" ::: "memory"); }
template <int N> __device__ __forceinline__ void wgmma_wait() { asm volatile("wgmma.wait_group.sync.aligned %0;" :: "n"(N) : "memory"); }
template <int N> __device__ __forceinline__ void fence_regs(float (&d)[N]) {
#pragma unroll
    for (int i = 0; i < N; i++) asm volatile("" : "+f"(d[i]) :: "memory");
}
template <int N> __device__ __forceinline__ void fence_regs(uint32_t (&d)[N]) {
#pragma unroll
    for (int i = 0; i < N; i++) asm volatile("" : "+r"(d[i]) :: "memory");
}
template <int N> __device__ __forceinline__ void reg_dec() { asm volatile("setmaxnreg.dec.sync.aligned.u32 %0;" :: "n"(N)); }
template <int N> __device__ __forceinline__ void reg_inc() { asm volatile("setmaxnreg.inc.sync.aligned.u32 %0;" :: "n"(N)); }
__device__ __forceinline__ uint32_t pack_bf16(float lo, float hi) {
    uint32_t r; asm("cvt.rn.bf16x2.f32 %0, %1, %2;" : "=r"(r) : "f"(hi), "f"(lo)); return r;
}
__device__ __forceinline__ void stmatrix_x4(uint32_t addr, uint32_t r0, uint32_t r1, uint32_t r2, uint32_t r3) {
    asm volatile("stmatrix.sync.aligned.m8n8.x4.shared.b16 [%0], {%1, %2, %3, %4};"
                 :: "r"(addr), "r"(r0), "r"(r1), "r"(r2), "r"(r3) : "memory");
}
__device__ __forceinline__ float ex2(float x) { float y; asm("ex2.approx.ftz.f32 %0, %1;" : "=f"(y) : "f"(x)); return y; }

constexpr uint32_t DESC_HI = (1024 >> 4) | (1u << 30);
__device__ __forceinline__ uint32_t make_desc(uint32_t addr, uint32_t lbo) {
    uint32_t lo = ((addr & 0x3FFFF) >> 4) | ((lbo >> 4) << 16);
    asm volatile("" : "+r"(lo));
    return lo;
}
__device__ __forceinline__ uint64_t full_desc(uint32_t lo) {
    uint64_t d; asm("mov.b64 %0, {%1, %2};" : "=l"(d) : "r"(lo), "r"(DESC_HI)); return d;
}

__device__ __forceinline__ void wgmma_ss_n256_tb_init(float (&d)[128], uint64_t da, uint64_t db) {
    asm volatile("{\n.reg .pred p;\n"
        "setp.ne.b32 p, 0, 0;\n"
        "wgmma.mma_async.sync.aligned.m64n256k16.f32.bf16.bf16 "
        "{%0, %1, %2, %3, %4, %5, %6, %7, %8, %9, %10, %11, %12, %13, %14, %15, %16, %17, %18, %19, %20, "
        "%21, %22, %23, %24, %25, %26, %27, %28, %29, %30, %31, %32, %33, %34, %35, %36, %37, %38, %39, %40, "
        "%41, %42, %43, %44, %45, %46, %47, %48, %49, %50, %51, %52, %53, %54, %55, %56, %57, %58, %59, %60, "
        "%61, %62, %63, %64, %65, %66, %67, %68, %69, %70, %71, %72, %73, %74, %75, %76, %77, %78, %79, %80, "
        "%81, %82, %83, %84, %85, %86, %87, %88, %89, %90, %91, %92, %93, %94, %95, %96, %97, %98, %99, "
        "%100, %101, %102, %103, %104, %105, %106, %107, %108, %109, %110, %111, %112, %113, %114, %115, "
        "%116, %117, %118, %119, %120, %121, %122, %123, %124, %125, %126, %127},"
        " %128, %129, p, 1, 1, 0, 1;\n}\n"
        : "=f"(d[0]), "=f"(d[1]), "=f"(d[2]), "=f"(d[3]), "=f"(d[4]), "=f"(d[5]), "=f"(d[6]), "=f"(d[7]),
        "=f"(d[8]), "=f"(d[9]), "=f"(d[10]), "=f"(d[11]), "=f"(d[12]), "=f"(d[13]), "=f"(d[14]), "=f"(d[15]),
        "=f"(d[16]), "=f"(d[17]), "=f"(d[18]), "=f"(d[19]), "=f"(d[20]), "=f"(d[21]), "=f"(d[22]),
        "=f"(d[23]), "=f"(d[24]), "=f"(d[25]), "=f"(d[26]), "=f"(d[27]), "=f"(d[28]), "=f"(d[29]),
        "=f"(d[30]), "=f"(d[31]), "=f"(d[32]), "=f"(d[33]), "=f"(d[34]), "=f"(d[35]), "=f"(d[36]),
        "=f"(d[37]), "=f"(d[38]), "=f"(d[39]), "=f"(d[40]), "=f"(d[41]), "=f"(d[42]), "=f"(d[43]),
        "=f"(d[44]), "=f"(d[45]), "=f"(d[46]), "=f"(d[47]), "=f"(d[48]), "=f"(d[49]), "=f"(d[50]),
        "=f"(d[51]), "=f"(d[52]), "=f"(d[53]), "=f"(d[54]), "=f"(d[55]), "=f"(d[56]), "=f"(d[57]),
        "=f"(d[58]), "=f"(d[59]), "=f"(d[60]), "=f"(d[61]), "=f"(d[62]), "=f"(d[63]), "=f"(d[64]),
        "=f"(d[65]), "=f"(d[66]), "=f"(d[67]), "=f"(d[68]), "=f"(d[69]), "=f"(d[70]), "=f"(d[71]),
        "=f"(d[72]), "=f"(d[73]), "=f"(d[74]), "=f"(d[75]), "=f"(d[76]), "=f"(d[77]), "=f"(d[78]),
        "=f"(d[79]), "=f"(d[80]), "=f"(d[81]), "=f"(d[82]), "=f"(d[83]), "=f"(d[84]), "=f"(d[85]),
        "=f"(d[86]), "=f"(d[87]), "=f"(d[88]), "=f"(d[89]), "=f"(d[90]), "=f"(d[91]), "=f"(d[92]),
        "=f"(d[93]), "=f"(d[94]), "=f"(d[95]), "=f"(d[96]), "=f"(d[97]), "=f"(d[98]), "=f"(d[99]),
        "=f"(d[100]), "=f"(d[101]), "=f"(d[102]), "=f"(d[103]), "=f"(d[104]), "=f"(d[105]), "=f"(d[106]),
        "=f"(d[107]), "=f"(d[108]), "=f"(d[109]), "=f"(d[110]), "=f"(d[111]), "=f"(d[112]), "=f"(d[113]),
        "=f"(d[114]), "=f"(d[115]), "=f"(d[116]), "=f"(d[117]), "=f"(d[118]), "=f"(d[119]), "=f"(d[120]),
        "=f"(d[121]), "=f"(d[122]), "=f"(d[123]), "=f"(d[124]), "=f"(d[125]), "=f"(d[126]), "=f"(d[127])
        : "l"(da), "l"(db));
}
__device__ __forceinline__ void wgmma_ss_n256_tb(float (&d)[128], uint64_t da, uint64_t db, int scale_d) {
    asm volatile("{\n.reg .pred p;\n"
        "setp.ne.b32 p, %130, 0;\n"
        "wgmma.mma_async.sync.aligned.m64n256k16.f32.bf16.bf16 "
        "{%0, %1, %2, %3, %4, %5, %6, %7, %8, %9, %10, %11, %12, %13, %14, %15, %16, %17, %18, %19, %20, "
        "%21, %22, %23, %24, %25, %26, %27, %28, %29, %30, %31, %32, %33, %34, %35, %36, %37, %38, %39, %40, "
        "%41, %42, %43, %44, %45, %46, %47, %48, %49, %50, %51, %52, %53, %54, %55, %56, %57, %58, %59, %60, "
        "%61, %62, %63, %64, %65, %66, %67, %68, %69, %70, %71, %72, %73, %74, %75, %76, %77, %78, %79, %80, "
        "%81, %82, %83, %84, %85, %86, %87, %88, %89, %90, %91, %92, %93, %94, %95, %96, %97, %98, %99, "
        "%100, %101, %102, %103, %104, %105, %106, %107, %108, %109, %110, %111, %112, %113, %114, %115, "
        "%116, %117, %118, %119, %120, %121, %122, %123, %124, %125, %126, %127},"
        " %128, %129, p, 1, 1, 0, 1;\n}\n"
        : "+f"(d[0]), "+f"(d[1]), "+f"(d[2]), "+f"(d[3]), "+f"(d[4]), "+f"(d[5]), "+f"(d[6]), "+f"(d[7]),
        "+f"(d[8]), "+f"(d[9]), "+f"(d[10]), "+f"(d[11]), "+f"(d[12]), "+f"(d[13]), "+f"(d[14]), "+f"(d[15]),
        "+f"(d[16]), "+f"(d[17]), "+f"(d[18]), "+f"(d[19]), "+f"(d[20]), "+f"(d[21]), "+f"(d[22]),
        "+f"(d[23]), "+f"(d[24]), "+f"(d[25]), "+f"(d[26]), "+f"(d[27]), "+f"(d[28]), "+f"(d[29]),
        "+f"(d[30]), "+f"(d[31]), "+f"(d[32]), "+f"(d[33]), "+f"(d[34]), "+f"(d[35]), "+f"(d[36]),
        "+f"(d[37]), "+f"(d[38]), "+f"(d[39]), "+f"(d[40]), "+f"(d[41]), "+f"(d[42]), "+f"(d[43]),
        "+f"(d[44]), "+f"(d[45]), "+f"(d[46]), "+f"(d[47]), "+f"(d[48]), "+f"(d[49]), "+f"(d[50]),
        "+f"(d[51]), "+f"(d[52]), "+f"(d[53]), "+f"(d[54]), "+f"(d[55]), "+f"(d[56]), "+f"(d[57]),
        "+f"(d[58]), "+f"(d[59]), "+f"(d[60]), "+f"(d[61]), "+f"(d[62]), "+f"(d[63]), "+f"(d[64]),
        "+f"(d[65]), "+f"(d[66]), "+f"(d[67]), "+f"(d[68]), "+f"(d[69]), "+f"(d[70]), "+f"(d[71]),
        "+f"(d[72]), "+f"(d[73]), "+f"(d[74]), "+f"(d[75]), "+f"(d[76]), "+f"(d[77]), "+f"(d[78]),
        "+f"(d[79]), "+f"(d[80]), "+f"(d[81]), "+f"(d[82]), "+f"(d[83]), "+f"(d[84]), "+f"(d[85]),
        "+f"(d[86]), "+f"(d[87]), "+f"(d[88]), "+f"(d[89]), "+f"(d[90]), "+f"(d[91]), "+f"(d[92]),
        "+f"(d[93]), "+f"(d[94]), "+f"(d[95]), "+f"(d[96]), "+f"(d[97]), "+f"(d[98]), "+f"(d[99]),
        "+f"(d[100]), "+f"(d[101]), "+f"(d[102]), "+f"(d[103]), "+f"(d[104]), "+f"(d[105]), "+f"(d[106]),
        "+f"(d[107]), "+f"(d[108]), "+f"(d[109]), "+f"(d[110]), "+f"(d[111]), "+f"(d[112]), "+f"(d[113]),
        "+f"(d[114]), "+f"(d[115]), "+f"(d[116]), "+f"(d[117]), "+f"(d[118]), "+f"(d[119]), "+f"(d[120]),
        "+f"(d[121]), "+f"(d[122]), "+f"(d[123]), "+f"(d[124]), "+f"(d[125]), "+f"(d[126]), "+f"(d[127])
        : "l"(da), "l"(db), "r"(scale_d));
}
__device__ __forceinline__ void wgmma_ss_n128(float (&d)[64], uint64_t da, uint64_t db, int scale_d) {
    asm volatile("{\n.reg .pred p;\n"
        "setp.ne.b32 p, %66, 0;\n"
        "wgmma.mma_async.sync.aligned.m64n128k16.f32.bf16.bf16 "
        "{%0, %1, %2, %3, %4, %5, %6, %7, %8, %9, %10, %11, %12, %13, %14, %15, %16, %17, %18, %19, %20, "
        "%21, %22, %23, %24, %25, %26, %27, %28, %29, %30, %31, %32, %33, %34, %35, %36, %37, %38, %39, %40, "
        "%41, %42, %43, %44, %45, %46, %47, %48, %49, %50, %51, %52, %53, %54, %55, %56, %57, %58, %59, %60, "
        "%61, %62, %63},"
        " %64, %65, p, 1, 1, 0, 0;\n}\n"
        : "+f"(d[0]), "+f"(d[1]), "+f"(d[2]), "+f"(d[3]), "+f"(d[4]), "+f"(d[5]), "+f"(d[6]), "+f"(d[7]),
        "+f"(d[8]), "+f"(d[9]), "+f"(d[10]), "+f"(d[11]), "+f"(d[12]), "+f"(d[13]), "+f"(d[14]), "+f"(d[15]),
        "+f"(d[16]), "+f"(d[17]), "+f"(d[18]), "+f"(d[19]), "+f"(d[20]), "+f"(d[21]), "+f"(d[22]),
        "+f"(d[23]), "+f"(d[24]), "+f"(d[25]), "+f"(d[26]), "+f"(d[27]), "+f"(d[28]), "+f"(d[29]),
        "+f"(d[30]), "+f"(d[31]), "+f"(d[32]), "+f"(d[33]), "+f"(d[34]), "+f"(d[35]), "+f"(d[36]),
        "+f"(d[37]), "+f"(d[38]), "+f"(d[39]), "+f"(d[40]), "+f"(d[41]), "+f"(d[42]), "+f"(d[43]),
        "+f"(d[44]), "+f"(d[45]), "+f"(d[46]), "+f"(d[47]), "+f"(d[48]), "+f"(d[49]), "+f"(d[50]),
        "+f"(d[51]), "+f"(d[52]), "+f"(d[53]), "+f"(d[54]), "+f"(d[55]), "+f"(d[56]), "+f"(d[57]),
        "+f"(d[58]), "+f"(d[59]), "+f"(d[60]), "+f"(d[61]), "+f"(d[62]), "+f"(d[63])
        : "l"(da), "l"(db), "r"(scale_d));
}
__device__ __forceinline__ void wgmma_rs_n128_tb(float (&d)[64], uint32_t a0, uint32_t a1, uint32_t a2, uint32_t a3, uint64_t db, int scale_d) {
    asm volatile("{\n.reg .pred p;\n"
        "setp.ne.b32 p, %69, 0;\n"
        "wgmma.mma_async.sync.aligned.m64n128k16.f32.bf16.bf16 "
        "{%0, %1, %2, %3, %4, %5, %6, %7, %8, %9, %10, %11, %12, %13, %14, %15, %16, %17, %18, %19, %20, "
        "%21, %22, %23, %24, %25, %26, %27, %28, %29, %30, %31, %32, %33, %34, %35, %36, %37, %38, %39, %40, "
        "%41, %42, %43, %44, %45, %46, %47, %48, %49, %50, %51, %52, %53, %54, %55, %56, %57, %58, %59, %60, "
        "%61, %62, %63},"
        " {%64, %65, %66, %67}, %68, p, 1, 1, 1;\n}\n"
        : "+f"(d[0]), "+f"(d[1]), "+f"(d[2]), "+f"(d[3]), "+f"(d[4]), "+f"(d[5]), "+f"(d[6]), "+f"(d[7]),
        "+f"(d[8]), "+f"(d[9]), "+f"(d[10]), "+f"(d[11]), "+f"(d[12]), "+f"(d[13]), "+f"(d[14]), "+f"(d[15]),
        "+f"(d[16]), "+f"(d[17]), "+f"(d[18]), "+f"(d[19]), "+f"(d[20]), "+f"(d[21]), "+f"(d[22]),
        "+f"(d[23]), "+f"(d[24]), "+f"(d[25]), "+f"(d[26]), "+f"(d[27]), "+f"(d[28]), "+f"(d[29]),
        "+f"(d[30]), "+f"(d[31]), "+f"(d[32]), "+f"(d[33]), "+f"(d[34]), "+f"(d[35]), "+f"(d[36]),
        "+f"(d[37]), "+f"(d[38]), "+f"(d[39]), "+f"(d[40]), "+f"(d[41]), "+f"(d[42]), "+f"(d[43]),
        "+f"(d[44]), "+f"(d[45]), "+f"(d[46]), "+f"(d[47]), "+f"(d[48]), "+f"(d[49]), "+f"(d[50]),
        "+f"(d[51]), "+f"(d[52]), "+f"(d[53]), "+f"(d[54]), "+f"(d[55]), "+f"(d[56]), "+f"(d[57]),
        "+f"(d[58]), "+f"(d[59]), "+f"(d[60]), "+f"(d[61]), "+f"(d[62]), "+f"(d[63])
        : "r"(a0), "r"(a1), "r"(a2), "r"(a3), "l"(db), "r"(scale_d));
}
__device__ __forceinline__ void wgmma_ss_n128_lo_tb(float (&d)[128], uint64_t da, uint64_t db, int scale_d) {
    asm volatile("{\n.reg .pred p;\n"
        "setp.ne.b32 p, %66, 0;\n"
        "wgmma.mma_async.sync.aligned.m64n128k16.f32.bf16.bf16 "
        "{%0, %1, %2, %3, %4, %5, %6, %7, %8, %9, %10, %11, %12, %13, %14, %15, %16, %17, %18, %19, %20, "
        "%21, %22, %23, %24, %25, %26, %27, %28, %29, %30, %31, %32, %33, %34, %35, %36, %37, %38, %39, %40, "
        "%41, %42, %43, %44, %45, %46, %47, %48, %49, %50, %51, %52, %53, %54, %55, %56, %57, %58, %59, %60, "
        "%61, %62, %63},"
        " %64, %65, p, 1, 1, 0, 1;\n}\n"
        : "+f"(d[0]), "+f"(d[1]), "+f"(d[2]), "+f"(d[3]), "+f"(d[4]), "+f"(d[5]), "+f"(d[6]), "+f"(d[7]),
        "+f"(d[8]), "+f"(d[9]), "+f"(d[10]), "+f"(d[11]), "+f"(d[12]), "+f"(d[13]), "+f"(d[14]), "+f"(d[15]),
        "+f"(d[16]), "+f"(d[17]), "+f"(d[18]), "+f"(d[19]), "+f"(d[20]), "+f"(d[21]), "+f"(d[22]),
        "+f"(d[23]), "+f"(d[24]), "+f"(d[25]), "+f"(d[26]), "+f"(d[27]), "+f"(d[28]), "+f"(d[29]),
        "+f"(d[30]), "+f"(d[31]), "+f"(d[32]), "+f"(d[33]), "+f"(d[34]), "+f"(d[35]), "+f"(d[36]),
        "+f"(d[37]), "+f"(d[38]), "+f"(d[39]), "+f"(d[40]), "+f"(d[41]), "+f"(d[42]), "+f"(d[43]),
        "+f"(d[44]), "+f"(d[45]), "+f"(d[46]), "+f"(d[47]), "+f"(d[48]), "+f"(d[49]), "+f"(d[50]),
        "+f"(d[51]), "+f"(d[52]), "+f"(d[53]), "+f"(d[54]), "+f"(d[55]), "+f"(d[56]), "+f"(d[57]),
        "+f"(d[58]), "+f"(d[59]), "+f"(d[60]), "+f"(d[61]), "+f"(d[62]), "+f"(d[63])
        : "l"(da), "l"(db), "r"(scale_d));
}

enum { M_X = 0, M_C, M_WQ, M_WQKV, M_WUK, M_WUV, M_WO, M_WOB, M_SCR_LD, M_SCR_LOC, M_SCR_LOQ, M_SCR_ST, M_OUT, M_COUNT };
enum { T_Q = 0, T_K, T_V, T_B, T_OUT, T_LOCAL, T_ATTN, T_END };
constexpr int NCTA = 132, NPAIR = NCTA / 2;
constexpr int NITEMS = 480 + 64 + 256 + 64;
struct Params {
    CUtensorMap m[M_COUNT];
    const __nv_bfloat16* x;
    const __nv_bfloat16* gate_w;
    const char* wo[2];
    uint32_t pfd;
    uint32_t zero;
    uint16_t items[NITEMS];
    uint8_t oseq[2][22];
};
__device__ __forceinline__ int item_type(int it) { return it >> 13; }
__device__ __forceinline__ int item_row(int it) { return it & 15; }
__device__ __forceinline__ int item_col(int it) { return (it >> 4) & 31; }
__device__ __forceinline__ int item_asc(int it) { return (it >> 9) & 1; }
constexpr int ITEM_READY = 1 << 10;

struct __align__(128) Sync {
    unsigned long long count[4];
    unsigned loc[16];
    __align__(128) unsigned long long ctx[16];
    unsigned next, done;
};
__device__ Sync g_sync;
__device__ __align__(8) unsigned g_pflag[128][2];

constexpr uint32_t GST_BYTES = 49152, SM_KV = 65536, SM_STAGING = 196608, SM_BARS = SM_STAGING + 32768;
constexpr uint32_t B_GFULL = 0, B_GEMPTY = 32, B_AFULL = 64, B_AEMPTY = 112, B_SFULL = 160, B_SEMPTY = 192,
                   B_IFULL = 224, B_IEMPTY = 288, B_XFREE = 352, B_WANT = 384, B_PRECV = 392, B_WIDE = 408, B_HALF = 416,
                   SM_ORDY = 448, SM_QUEUE = 456, B_ALT = 488, B_QFREE = 504, SM_GATE = 512, SM_TOTAL = SM_BARS + 1536;
constexpr int QDEPTH = 8;
#define KF2 3
constexpr uint32_t LOC_PLANE = 72 * 128;
constexpr float SM_SCALE = 0.08838834764831845f * 1.4426950408889634f;
constexpr float LOC_SCALE = 0.17677669529663687f * 1.4426950408889634f;
constexpr float SUM_LIMIT = 1152921504606846976.f;

__device__ __forceinline__ unsigned ld_acquire(const unsigned* p) {
    unsigned v; asm volatile("ld.acquire.gpu.global.u32 %0, [%1];" : "=r"(v) : "l"(p) : "memory"); return v;
}
__device__ __forceinline__ unsigned long long ld_acquire(const unsigned long long* p) {
    unsigned long long v; asm volatile("ld.acquire.gpu.global.u64 %0, [%1];" : "=l"(v) : "l"(p) : "memory"); return v;
}
__device__ __forceinline__ void spin_guard(unsigned& n) {
    asm volatile("{\n.reg .pred P;\nadd.u32 %0, %0, 1;\nsetp.gt.u32 P, %0, 16777216;\n@P trap;\n}\n" : "+r"(n));
    if (n > 1) __nanosleep(100);
}
__device__ __forceinline__ void red_add(unsigned long long* p, unsigned long long v) {
    asm volatile("red.release.gpu.global.add.u64 [%0], %1;" :: "l"(p), "l"(v) : "memory");
}
__device__ __forceinline__ float rcp(float x) { float y; asm("rcp.approx.ftz.f32 %0, %1;" : "=f"(y) : "f"(x)); return y; }
__device__ __forceinline__ float lds_f32(uint32_t addr) {
    float v; asm volatile("ld.shared.f32 %0, [%1];" : "=f"(v) : "r"(addr) : "memory"); return v;
}
__device__ __forceinline__ void ldsm_x4(uint32_t (&r)[4], uint32_t addr) {
    asm volatile("ldmatrix.sync.aligned.m8n8.x4.shared.b16 {%0, %1, %2, %3}, [%4];"
                 : "=r"(r[0]), "=r"(r[1]), "=r"(r[2]), "=r"(r[3]) : "r"(addr) : "memory");
}
__device__ __forceinline__ void ldsm_x4_t(uint32_t (&r)[4], uint32_t addr) {
    asm volatile("ldmatrix.sync.aligned.m8n8.x4.trans.shared.b16 {%0, %1, %2, %3}, [%4];"
                 : "=r"(r[0]), "=r"(r[1]), "=r"(r[2]), "=r"(r[3]) : "r"(addr) : "memory");
}
__device__ __forceinline__ void mma_k16(float (&d)[4], const uint32_t (&a)[4], uint32_t b0, uint32_t b1) {
    asm("mma.sync.aligned.m16n8k16.row.col.f32.bf16.bf16.f32 {%0,%1,%2,%3}, {%4,%5,%6,%7}, {%8,%9}, {%0,%1,%2,%3};"
        : "+f"(d[0]), "+f"(d[1]), "+f"(d[2]), "+f"(d[3]) : "r"(a[0]), "r"(a[1]), "r"(a[2]), "r"(a[3]), "r"(b0), "r"(b1));
}
__device__ __forceinline__ void mma_k16_init(float (&d)[4], const uint32_t (&a)[4], uint32_t b0, uint32_t b1) {
    asm("{\n.reg .f32 z;\nmov.f32 z, 0f00000000;\n"
        "mma.sync.aligned.m16n8k16.row.col.f32.bf16.bf16.f32 {%0,%1,%2,%3}, {%4,%5,%6,%7}, {%8,%9}, {z,z,z,z};\n}\n"
        : "=f"(d[0]), "=f"(d[1]), "=f"(d[2]), "=f"(d[3]) : "r"(a[0]), "r"(a[1]), "r"(a[2]), "r"(a[3]), "r"(b0), "r"(b1));
}
__device__ __forceinline__ void mma_k8(float (&d)[4], uint32_t a0, uint32_t a1, uint32_t b0) {
    asm("mma.sync.aligned.m16n8k8.row.col.f32.bf16.bf16.f32 {%0,%1,%2,%3}, {%4,%5}, {%6}, {%0,%1,%2,%3};"
        : "+f"(d[0]), "+f"(d[1]), "+f"(d[2]), "+f"(d[3]) : "r"(a0), "r"(a1), "r"(b0));
}
template <typename T, int N> __device__ __forceinline__ void zero_regs(T (&d)[N]) {
#pragma unroll
    for (int i = 0; i < N; i++) d[i] = 0;
}
__device__ __forceinline__ float quad_max(float v) {
    v = fmaxf(v, __shfl_xor_sync(0xffffffffu, v, 1));
    return fmaxf(v, __shfl_xor_sync(0xffffffffu, v, 2));
}
__device__ __forceinline__ float quad_sum(float v) {
    v += __shfl_xor_sync(0xffffffffu, v, 1);
    return v + __shfl_xor_sync(0xffffffffu, v, 2);
}

__device__ __forceinline__ void qk_gemm(float (&s)[64], uint32_t q_lo, uint32_t k_lo) {
    const uint64_t dq = full_desc(q_lo), dk = full_desc(k_lo);
    fence_regs(s);
    wgmma_fence();
#pragma unroll
    for (int kk = 0; kk < 8; kk++) {
        const uint32_t o = (kk >> 2) * 1024 + (kk & 3) * 2;
        wgmma_ss_n128(s, dq + o, dk + o, kk != 0);
    }
    wgmma_commit();
}
__device__ __forceinline__ void pv_gemm(float (&o)[64], uint32_t (&p)[32], uint32_t v_lo, int accumulate) {
    const uint64_t dv = full_desc(v_lo);
    fence_regs(o);
    fence_regs(p);
    wgmma_fence();
#pragma unroll
    for (int kk = 0; kk < 8; kk++)
        wgmma_rs_n128_tb(o, p[4 * kk], p[4 * kk + 1], p[4 * kk + 2], p[4 * kk + 3], dv + kk * 128, kk != 0 || accumulate);
    wgmma_commit();
}
template <int NJ>
__device__ __forceinline__ void row_max(const float (&s)[64], float& x0, float& x1) {
    float z0 = fmaxf(s[0], s[1]), z1 = fmaxf(s[2], s[3]);
    x0 = fmaxf(s[4], s[5]); x1 = fmaxf(s[6], s[7]);
#pragma unroll
    for (int j = 2; j < NJ; j += 2) {
        z0 = fmaxf(z0, fmaxf(s[4 * j], s[4 * j + 1]));
        z1 = fmaxf(z1, fmaxf(s[4 * j + 2], s[4 * j + 3]));
        x0 = fmaxf(x0, fmaxf(s[4 * j + 4], s[4 * j + 5]));
        x1 = fmaxf(x1, fmaxf(s[4 * j + 6], s[4 * j + 7]));
    }
    x0 = quad_max(fmaxf(x0, z0)); x1 = quad_max(fmaxf(x1, z1));
}
__device__ __forceinline__ void exp_pack(uint32_t (&p)[32], const float (&s)[64], float n0, float n1, float& r0, float& r1) {
#pragma unroll
    for (int j = 0; j < 16; j++) {
        const float e0 = ex2(fmaf(s[4 * j], SM_SCALE, n0)), e1 = ex2(fmaf(s[4 * j + 1], SM_SCALE, n0));
        const float e2 = ex2(fmaf(s[4 * j + 2], SM_SCALE, n1)), e3 = ex2(fmaf(s[4 * j + 3], SM_SCALE, n1));
        if (j == 0) { r0 = e0 + e1; r1 = e2 + e3; }
        else { r0 += e0; r0 += e1; r1 += e2; r1 += e3; }
        p[2 * j] = pack_bf16(e0, e1);
        p[2 * j + 1] = pack_bf16(e2, e3);
    }
}
template <int J0>
__device__ __forceinline__ void mask_triangle(float (&s)[64], int thr) {
#pragma unroll
    for (int j = 0; j < 8; j++) {
        if (8 * j > thr) s[4 * (J0 + j)] = -INFINITY;
        if (8 * j + 1 > thr) s[4 * (J0 + j) + 1] = -INFINITY;
        if (j > 0 && 8 * j - 8 > thr) s[4 * (J0 + j) + 2] = -INFINITY;
        if (j > 0 && 8 * j - 7 > thr) s[4 * (J0 + j) + 3] = -INFINITY;
    }
}
__device__ __forceinline__ void causal_mask(float (&s)[64], int thr, int wg) {
    asm volatile("" : "+r"(thr));
    if (wg == 0) {
        mask_triangle<0>(s, thr);
#pragma unroll
        for (int j = 32; j < 64; j++) s[j] = -INFINITY;
    } else {
        mask_triangle<8>(s, thr - 64);
    }
}

__global__ void __cluster_dims__(2, 1, 1) __launch_bounds__(384, 1) fused_kernel(const __grid_constant__ Params prm) {
    extern __shared__ __align__(1024) uint8_t smem[];
    const uint32_t sb = smem_u32(smem), bars = sb + SM_BARS;
    const int warp = __shfl_sync(0xffffffffu, threadIdx.x >> 5, 0), lane = threadIdx.x & 31;

    const uint32_t rank = cluster_rank();
    const uint32_t bars0 = map_cta(bars, 0), bars_peer = map_cta(bars, rank ^ 1);

    auto first_item = [&]() -> int {
        uint32_t pair = blockIdx.x >> 1;
        asm volatile("" : "+r"(pair));
        return prm.items[pair] + item_row(prm.items[pair]) + rank;
    };
    if (threadIdx.x == 256) {
        for (int k = 0; k < 4; k++) mbar_init(bars + B_GFULL + 8 * k, 1);
        asm volatile("fence.mbarrier_init.release.cluster;" ::: "memory");
        fence_proxy_async_smem();
    }
    if (threadIdx.x == 128) {
        for (int i = 0; i < 4; i++) { mbar_init(bars + B_GEMPTY + 8 * i, 16); mbar_init(bars + B_XFREE + 8 * i, 1); }
        for (int i = 0; i < 6; i++) { mbar_init(bars + B_AFULL + 8 * i, 1); mbar_init(bars + B_AEMPTY + 8 * i, i < 2 ? 8 : 16); }
        for (int i = 0; i < 4; i++) { mbar_init(bars + B_SFULL + 8 * i, 4); mbar_init(bars + B_SEMPTY + 8 * i, 1); }
        for (int i = 0; i < QDEPTH; i++) { mbar_init(bars + B_IFULL + 8 * i, 1); mbar_init(bars + B_IEMPTY + 8 * i, 23); }
        mbar_init(bars + B_WANT, 2); mbar_init(bars + B_PRECV, 1); mbar_init(bars + B_PRECV + 8, 1); mbar_init(bars + B_WIDE, 8);
        for (int i = 0; i < 4; i++) mbar_init(bars + B_HALF + 8 * i, 1);
        mbar_init(bars + B_ALT, 4); mbar_init(bars + B_ALT + 8, 4); mbar_init(bars + B_QFREE, 2);
        asm volatile("st.shared.u32 [%0], 0;" :: "r"(bars + SM_ORDY) : "memory");
        asm volatile("fence.mbarrier_init.release.cluster;\nfence.acq_rel.cta;" ::: "memory");
    }
    __syncwarp();
    asm volatile("barrier.cluster.arrive.relaxed.aligned;" ::: "memory");
    if (threadIdx.x == 256) {
        const int first_it = first_item();
        for (int k = 0; k < 4; k++) {
            const uint32_t dst = sb + k * GST_BYTES, fb = bars + B_GFULL + 8 * k;
            mbar_expect_tx(fb, GST_BYTES);
            tma_load_3d(dst, &prm.m[M_X], fb, k * 64, item_row(first_it) * 128, 0);
            tma_load_3d(dst + 16384, &prm.m[M_WQKV], fb, 0, k * 64, item_col(first_it) * 4);
            tma_load_3d(dst + 32768, &prm.m[M_WQKV], fb, 0, k * 64, item_col(first_it) * 4 + 2);
        }
    }
    __syncwarp();
    asm volatile("barrier.cluster.wait.acquire.aligned;" ::: "memory");

    uint32_t qn = 0;
    auto next_item = [&](bool releaser, bool bounded = true) -> int {
        const uint32_t slot = qn % QDEPTH;
        if (bounded) mbar_wait(bars + B_IFULL + 8 * slot, (qn / QDEPTH) & 1);
        else mbar_spin(bars + B_IFULL + 8 * slot, (qn / QDEPTH) & 1);
        uint32_t it;
        asm volatile("ld.shared.u32 %0, [%1];" : "=r"(it) : "r"(bars + SM_QUEUE + 4 * slot) : "memory");
        mbar_arrive_cluster_if(releaser, bars0 + B_IEMPTY + 8 * slot);
        qn++;
        return it;
    };

    if (warp < 4) {
        reg_dec<40>();
        if (warp == 0) {
            {
                uint32_t gph = 0;
                const uint32_t prank = __shfl_sync(0xffffffffu, rank, 0);
                int k0 = 4;
                uint32_t kv = 0, kvph = 1;
                uint32_t qc = 0;
                uint32_t oneed = 0, ordy = 0;
                uint32_t xph = 0;
                uint32_t need_g = 0, need_a = 0;
                auto a_parity = [&](uint32_t b) { return b < 2 ? (((qc + 1 - b) >> 1) & 1) ^ 1 : kvph ^ (b - 2 < kv); };
                int held_type = T_END;
                uint32_t borrowed = 0, fph = 0;
                auto reclaim_q = [&]() { if (borrowed) { mbar_wait(bars + B_QFREE, fph); fph ^= 1; borrowed = 0; } };
                auto acquire_g = [&](uint32_t st, bool shared) {
                    mbar_wait(bars + B_GEMPTY + 8 * st, gph);
                    if (need_a) {
                        reclaim_q();
                        const uint32_t b = (3 * st) >> 1;
                        mbar_wait(bars + B_AEMPTY + 8 * b, a_parity(b));
                        mbar_wait(bars + B_AEMPTY + 8 * (b + 1), a_parity(b + 1));
                        if (shared) {
                            mbar_arrive_cluster_if(lane == 0, bars_peer + B_XFREE + 8 * st);
                            mbar_wait(bars + B_XFREE + 8 * st, xph);
                        }
                        if (st == 3) { need_a = 0; xph ^= shared; }
                    }
                };
                auto leave_gemm = [&](uint32_t b) {
                    if (need_g >> b & 1) {
                        mbar_wait(bars + B_GEMPTY + 8 * ((2 * b) / 3), gph);
                        mbar_wait(bars + B_GEMPTY + 8 * ((2 * b + 1) / 3), gph);
                        need_g &= ~(1u << b);
                    }
                };
                const CUtensorMap* tile_map = &prm.m[M_SCR_LD];
                asm volatile("" : "+l"(tile_map));
                auto load_q = [&](int grp, int row) {
                    const uint32_t b = qc & 1, dst = sb + b * 32768, fb = bars + B_AFULL + 8 * b;
                    mbar_wait(bars + B_AEMPTY + 8 * b, a_parity(b));
                    leave_gemm(b);
                    reclaim_q();
                    borrowed = held_type != T_END;
                    held_type = T_END;
                    warp_expect_tx(fb, 32768 + 512);
                    warp_tma_load(dst, tile_map, fb, 0, row, grp);
                    warp_tma_load(dst + 16384, tile_map, fb, 64, row, grp);
                    warp_bulk_load(bars + SM_GATE + b * 512, &g_gate[row], 512, fb);
                    qc++;
                };
                auto load_kv = [&](int grp, int row, bool shared) {
                    uint32_t fb = bars + B_AFULL + 16 + 8 * kv, mine = sb + SM_KV + kv * 32768 + prank * 16384;
                    int c_mine = prank * 64;
                    asm volatile("" : "+r"(mine), "+r"(fb), "+r"(row), "+r"(grp), "+r"(c_mine));
                    if (need_g) leave_gemm(2 + kv);
                    mbar_wait(fb + B_AEMPTY - B_AFULL, kvph);
                    warp_expect_tx(fb, grp < 0 ? 0 : 32768);
                    if (shared) {
                        warp_tma_load_pair(mine, tile_map, fb, c_mine, row, grp);
                    } else if (grp >= 0) {
                        warp_tma_load(mine, tile_map, fb, c_mine, row, grp);
                        warp_tma_load(mine + 16384 - prank * 32768, tile_map, fb, 64 - c_mine, row, grp);
                    } else {
                        mbar_arrive_cluster_n_if(lane < 2, map_cta(fb, lane & 1) + B_AEMPTY - B_AFULL, 8);
                    }
                    if (++kv == 4) { kv = 0; kvph ^= 1; }
                };
                auto request = [&]() { mbar_arrive_cluster_if(lane == 0, bars0 + B_WANT); };
                int pv_grp = -1, pv_row = 0;
                bool pv_shared = false, peer_longer = false;
                auto wait_inputs = [&]() {
                    if (++oneed <= ordy) return;
                    unsigned n = 0;
                    do {
                        asm volatile("ld.acquire.cta.shared.u32 %0, [%1];" : "=r"(ordy) : "r"(bars + SM_ORDY) : "memory");
                        ordy = __shfl_sync(0xffffffffu, ordy, 0);
                        spin_guard(n);
                    } while (oneed > ordy);
                };
                auto fetch = [&]() -> int {
                    const int nx = __shfl_sync(0xffffffffu, next_item(lane == 0), 0);
                    if ((item_type(nx) == T_ATTN || item_type(nx) == T_LOCAL) && !(nx & ITEM_READY)) wait_inputs();
                    if (item_type(nx) == T_ATTN) load_q(G_Q + item_col(nx), item_row(nx) * 128);
                    return nx;
                };
                int nxt = first_item();
                while (true) {
                    const int it = nxt >= 0 ? nxt : fetch();
                    nxt = -1;
                    const int type = item_type(it), m = item_row(it), c = item_col(it);
                    const int asc = item_asc(it), nu = type == T_ATTN ? 2 * m + 2 : 0;
                    const int uend = nu + ((type == T_ATTN ? m < 2 : pv_grp >= 0) ? 3 : 0), ureq = 2 * max(m - 2 - (asc & m), 0);
#pragma unroll 1
                    for (int u = 0; u < uend; u++) {
                        int grp = pv_grp, row = pv_row;
                        bool shared = pv_shared;
                        if (u >= nu) {
                            if (u == nu + 1) pv_grp = -1;
                            else if (peer_longer) { grp = -1; shared = false; }
                            else continue;
                        } else {
                            const int j = asc ? u >> 1 : m - (u >> 1);
                            if (u & 1) {
                                pv_grp = G_V + c; pv_row = j * 128; pv_shared = j != (m | 1);
                                peer_longer = asc & ~m & 1;
                                if (grp < 0) continue;
                            } else {
                                if (u == ureq) request();
                                if (u == 2 * m && m > 0) nxt = fetch();
                                grp = G_K + c; row = j * 128; shared = j != (m | 1);
                            }
                        }
                        load_kv(grp, row, shared);
                    }
                    if (type == T_END) break;
                    if (type == T_ATTN) {
                        need_a = 1;
                    } else if (type == T_LOCAL) {
                        if (held_type == T_B && !(it & ITEM_READY)) held_type = T_END;
                        request();
#pragma unroll 1
                        for (uint32_t st = 0; st < 4; st++) {
                            acquire_g(st, false);
                            const uint32_t dst = sb + st * GST_BYTES, fb = bars + B_GFULL + 8 * st;
                            warp_expect_tx(fb, st == 0 ? 32768 + 512 : st == 3 ? 0 : 4 * LOC_PLANE);
                            if (st == 3) break;
                            if (st == 0) warp_bulk_load(dst + 4 * LOC_PLANE, &g_gate[m * 128], 512, fb);
#pragma unroll 1
                            for (int i = 0; i < 4; i++)
                                warp_tma_load(dst + i * LOC_PLANE, &prm.m[st ? M_SCR_LOC : M_SCR_LOQ], fb, i * 64, m * 64 - (st ? 8 : 0), G_B + 8 * st + c);
                        }
                        gph ^= 1;
                        need_g = 63;
                    } else {
                        const bool is_out = type == T_OUT;
                        const int nk = is_out ? 44 : (type == T_K || type == T_V) ? 8 : 16;
                        const CUtensorMap* ma = &prm.m[is_out ? M_SCR_LD : nk == 8 ? M_C : M_X];
                        const CUtensorMap* mb = &prm.m[type == T_Q ? M_WQ : type == T_K ? M_WUK : type == T_V ? M_WUV : M_WQKV];
                        const int half = is_out ? c & 1 : 0, nb = is_out ? (c >> 1) * 4 : c * 4;
                        for (int k = k0; k < nk; k++) {
                            if (k == nk - 3) request();
                            int a0 = k * 64, a2 = 0, b1 = k * 64;
                            if (is_out) {
                                const int g = prm.oseq[half][k >> 1];
                                if (!(k & 1)) wait_inputs();
                                a0 = (k & 1) * 64; a2 = g < 32 ? G_CTX + g : G_LOC - 32 + g;
                                mb = &prm.m[g >= 32 ? M_WOB : M_WO];
                                b1 = (g & 31) * 128 + a0;
                            }
                            const uint32_t st = k & 3;
                            const bool narrow = k >= 36;
                            const uint32_t part = narrow ? 0 : prank;
                            uint32_t dst = sb + st * GST_BYTES, fb = bars + B_GFULL + 8 * st, bytes = narrow ? 32768 : GST_BYTES;
                            uint32_t dstb = dst + 16384 + part * 16384, skipb = narrow && (k & 1) != prank;
                            int a1 = m * 128, b2 = nb + 2 * (half ^ part);
                            asm volatile("" : "+r"(dst), "+r"(fb), "+r"(bytes), "+r"(dstb), "+r"(skipb), "+r"(a0), "+r"(a1), "+r"(a2), "+r"(b1), "+r"(b2), "+l"(ma), "+l"(mb));
                            acquire_g(st, true);
                            warp_expect_tx(fb, bytes);
                            warp_tma_load(dst, ma, fb, a0, a1, a2);
                            if (!skipb) warp_tma_load_pair(dstb, mb, fb, 0, b1, b2);
                            if (st == 3) gph ^= 1;
                        }
                        need_g = 63;
                        held_type = is_out ? T_END : type;
                        k0 = 0;
                    }
                }
                for (uint32_t st = 0; st < 4; st++) { mbar_wait(bars + B_GEMPTY + 8 * st, gph); mbar_wait(bars + B_AEMPTY + 16 + 8 * st, a_parity(2 + st)); }
                if (lane == 0 && atomicAdd(&g_sync.done, 1u) == NCTA - 1) {
                    g_sync.next = 0; g_sync.done = 0;
                    for (int i = 0; i < 4; i++) g_sync.count[i] = 0;
                    for (int i = 0; i < 16; i++) { g_sync.loc[i] = 0; g_sync.ctx[i] = 0; }
                }
            }
        } else if (warp <= 2) {
            for (int r = 2 * blockIdx.x + warp - 1; r < SEQ; r += 2 * NCTA) {
                float z = 0.f;
#pragma unroll
                for (int q = 0; q < 4; q++) {
                    const uint4 xv = __ldg((const uint4*)(prm.x + (size_t)r * 1024) + q * 32 + lane);
                    const uint4 wv = __ldg((const uint4*)prm.gate_w + q * 32 + lane);
                    const uint32_t xs[4] = {xv.x, xv.y, xv.z, xv.w}, ws[4] = {wv.x, wv.y, wv.z, wv.w};
#pragma unroll
                    for (int e = 0; e < 4; e++) {
                        z = fmaf(__uint_as_float(xs[e] << 16), __uint_as_float(ws[e] << 16), z);
                        z = fmaf(__uint_as_float(xs[e] & 0xffff0000u), __uint_as_float(ws[e] & 0xffff0000u), z);
                    }
                }
#pragma unroll
                for (int o = 16; o > 0; o >>= 1) z += __shfl_xor_sync(0xffffffffu, z, o);
                if (lane == 0) g_gate[r] = 1.f / (1.f + __expf(-z));
            }
            if (lane == 0) {
                asm volatile("fence.proxy.async;" ::: "memory");
                red_add(&g_sync.count[3], 1);
            }
            __syncwarp();
            {
                const int w = warp - 1;
                uint32_t sph = 0, oph = 0, aph = 0, nann = 0, nattn = 0;
                int unsent = -1;
                auto join_halves = [&]() -> bool {
                    bulk_wait<0>();
                    __syncwarp();
                    const uint32_t hb = bars + B_HALF + 8 * (nann & 3);
                    if (w == 0) mbar_arrive_if(lane == 0, hb);
                    else mbar_wait(hb, (nann >> 2) & 1);
                    nann++;
                    return w == 1;
                };
                auto announce = [&]() {
                    if (unsent < 0 || item_type(unsent) == T_OUT) return;
                    if (join_halves() && lane == 0) {
                        const int type = item_type(unsent), m = item_row(unsent), c = item_col(unsent);
                        if (type < T_B) red_add(&g_sync.count[c >> 3], 1ull << (8 * (c & 7)));
                        else if (type == T_B) red_add(&g_sync.count[2], 1ull << (4 * m));
                        else if (type == T_LOCAL) asm volatile("red.release.gpu.global.or.b32 [%0], %1;" :: "l"(&g_sync.loc[m]), "r"(3u << (2 * c)) : "memory");
                        else asm volatile("red.release.gpu.global.or.b64 [%0], %1;" :: "l"(&g_sync.ctx[m]), "l"(3ull << (2 * c)) : "memory");
                    }
                    __syncwarp();
                    unsent = -1;
                };
                auto store_item = [&](int it, bool borrow) {
                    const int type = item_type(it), m = item_row(it), c = item_col(it);
                    const int npair = type <= T_OUT ? 2 : 1;
                    const bool local = type == T_LOCAL;
                    const int grp = type == T_Q ? G_Q + 2 * c : type == T_K ? G_K + 2 * c : type == T_V ? G_V + 2 * c : type == T_B ? G_B + 2 * c
                                  : type == T_OUT ? G_PART + c : type == T_ATTN ? G_CTX + c : G_LOC + c;
                    for (int pr = 0; pr < npair; pr++) {
                        const bool final_out = type == T_OUT && pr;
                        if (final_out) {
                            announce();
                            if (join_halves() && lane == 0)
                                asm volatile("st.release.gpu.global.u64 [%0], %1;" :: "l"(&g_pflag[it & 127][0]), "l"(0x100000001ull) : "memory");
                            unsigned* flag = &g_pflag[(it & 127) ^ 16][w];
                            for (unsigned n = 0; !__all_sync(0xffffffffu, ld_acquire(flag) == 1);) spin_guard(n);
                            *flag = 0;
                            mbar_wait(bars + B_WIDE, oph);
                            oph ^= 1;
                            warp_expect_tx(bars + B_PRECV + 8 * w, 16384);
                            for (int b = 0; b < 2; b++)
                                warp_tma_load(sb + w * GST_BYTES + 32768 + b * 8192, &prm.m[M_SCR_ST], bars + B_PRECV + 8 * w, b * 64, m * 128 + w * 64, G_PART + (c ^ 1));
                        }
                        if (borrow && pr) {
                            mbar_wait(bars + B_ALT + 8 * w, aph);
                            aph ^= 1;
                            for (int b = 0; b < 2; b++)
                                warp_tma_store(&prm.m[M_SCR_ST], sb + ((nattn & 1) ^ 1) * 32768 + w * 16384 + b * 8192, b * 64, m * 128 + w * 64, grp + 1);
                            bulk_commit();
                            bulk_wait_read<0>();
                            __syncwarp();
                            mbar_arrive_if(lane == 0, bars + B_QFREE);
                            break;
                        }
                        for (int b = 0; b < 2; b++) {
                            if (!__all_sync(0xffffffffu, mbar_test(bars + B_SFULL + 16 * w + 8 * b, sph))) announce();
                            mbar_wait(bars + B_SFULL + 16 * w + 8 * b, sph);
                            warp_tma_store(&prm.m[final_out ? M_OUT : local ? M_SCR_LOQ : M_SCR_ST], sb + SM_STAGING + w * 16384 + b * 8192,
                                         local ? b * 128 + w * 64 : (final_out ? c * 128 : 0) + b * 64, local ? m * 64 : m * 128 + w * 64, final_out ? 0 : grp + pr);
                            bulk_commit();
                            bulk_wait_read<0>();
                            __syncwarp();
                            mbar_arrive_if(lane == 0, bars + B_SEMPTY + 16 * w + 8 * b);
                        }
                        sph ^= 1;
                    }
                    announce();
                    unsent = it;
                };
                int held = first_item();
                while (true) {
                    if (!__all_sync(0xffffffffu, mbar_test(bars + B_IFULL + 8 * (qn % QDEPTH), (qn / QDEPTH) & 1))) announce();
                    const int it = __shfl_sync(0xffffffffu, next_item(lane == 0), 0), type = item_type(it);
                    const bool keep_held = type == T_LOCAL && (item_type(held) != T_B || (it & ITEM_READY));
                    for (int pass = held < 0 || keep_held; pass < 2; pass++) {
                        if (pass && (type < T_OUT || type == T_END)) break;
                        store_item(pass ? it : held, !pass && type == T_ATTN);
                    }
                    if (type == T_END) break;
                    nattn += type == T_ATTN;
                    if (!keep_held) held = type < T_OUT ? it : -1;
                }
                announce();
            }
        } else {
            if (elect_one()) {
                uint32_t ordy = 0;
                unsigned long long cnt_lo = 0, cnt_hi = 0;
                int late = 0;
                auto refresh = [&]() {
                    if (!late && cnt_lo == 0xccccccccccccccccull && cnt_hi == 2 * NCTA) late = 1;
                    asm volatile("ld.acquire.gpu.global.v2.u64 {%0, %1}, [%2];" : "=l"(cnt_lo), "=l"(cnt_hi) : "l"(&g_sync.count[2 - 2 * late]) : "memory");
                };
                auto inputs_ready = [&](int it) -> bool {
                    const int m = item_row(it), c = item_col(it);
                    if (item_type(it) == T_ATTN) return late && ((c < 16 ? cnt_lo : cnt_hi) >> (4 * (c & 14)) & 255) == 48;
                    return late || (cnt_hi == 2 * NCTA && (cnt_lo >> (4 * m) & 15) == 12 && (cnt_lo >> (4 * max(m - 1, 0)) & 15) == 12);
                };
                int asc = 1;
                while (true) {
                    int it;
                    if (rank == 0) {
                        mbar_wait(bars + B_WANT, qn & 1);
                        unsigned i;
                        asm volatile("atom.relaxed.gpu.global.add.u32 %0, [%1], 1;" : "=r"(i) : "l"(&g_sync.next) : "memory");
                        if (cnt_lo != 0x3030303030303030ull || cnt_hi != cnt_lo) refresh();
                        i += NPAIR;
                        const int pit = i < NITEMS ? prm.items[i] : T_END << 13, type = item_type(pit);
                        int step = type == T_LOCAL ? 16 : 1;
                        it = pit + (pit & (step == 1 ? 15 : 0x1f0));
                        if (type == T_ATTN) {
                            if (!asc) { it += 1; step = -1; }
                            it |= asc << 9;
                        }
                        asc = type != T_ATTN || item_row(pit) == 0 || !asc;
                        if (inputs_ready(it)) it |= ITEM_READY;
                        const uint32_t slot = qn % QDEPTH;
                        mbar_wait(bars + B_IEMPTY + 8 * slot, ((qn / QDEPTH) & 1) ^ 1);
                        for (uint32_t r = 0; r < 2; r++) {
                            const uint32_t rb = map_cta(bars, r);
                            asm volatile("mbarrier.arrive.expect_tx.shared::cluster.b64 _, [%0], 4;" :: "r"(rb + B_IFULL + 8 * slot) : "memory");
                            asm volatile("st.async.shared::cluster.mbarrier::complete_tx::bytes.u32 [%0], %1, [%2];"
                                         :: "r"(rb + SM_QUEUE + 4 * slot), "r"(it + r * step), "r"(rb + B_IFULL + 8 * slot) : "memory");
                        }
                        qn++;
                    } else {
                        it = next_item(true);
                    }
                    if (item_type(it) == T_END) {
                        if (rank == 0) for (uint32_t n = qn; n < qn + QDEPTH; n++) mbar_wait(bars + B_IEMPTY + 8 * (n % QDEPTH), ((n / QDEPTH) & 1) ^ 1);
                        break;
                    }
                    const int type = item_type(it), m = item_row(it), c = item_col(it);
                    unsigned n = 0;
                    if (type == T_OUT) {
                        for (int i = 0; i < 22;) {
                            const unsigned long long rc = ld_acquire(&g_sync.ctx[m]);
                            const unsigned rl = ld_acquire(&g_sync.loc[m]);
                            for (; i < 22; i++, ordy++) {
                                const int g = prm.oseq[c & 1][i];
                                if (((g >= 32 ? rl >> (2 * g - 64) : rc >> (2 * g)) & 3) != 3) break;
                            }
                            asm volatile("st.release.cta.shared.u32 [%0], %1;" :: "r"(bars + SM_ORDY), "r"(ordy) : "memory");
                            spin_guard(n);
                        }
                    } else if (type > T_OUT && !(it & ITEM_READY)) {
                        while (!inputs_ready(it)) { refresh(); spin_guard(n); }
                        asm volatile("st.release.cta.shared.u32 [%0], %1;" :: "r"(bars + SM_ORDY), "r"(++ordy) : "memory");
                    }
                }
            }
        }
    } else {
        reg_inc<232>();
        const int wg = (warp >> 2) - 1, wq = warp & 3;
        uint32_t gph = 0;
        uint32_t kvn = 0;
        const uint32_t dA = make_desc(sb + wg * 8192, 16);
        uint32_t ti = 0;
        uint32_t oph = 0;
        uint32_t sph = 1;
        const uint32_t stg = sb + SM_STAGING + wg * 16384;
        const uint32_t stg_row = stg + (wq * 16 + (lane & 15)) * 128;
        auto release = [&](uint32_t bar) { mbar_arrive_if(lane == 0, bars + bar); };
        const uint32_t bars_lane = map_cta(bars, lane & 1);
        auto release_stage = [&](uint32_t st) { mbar_arrive_cluster_if(lane < 2, bars_lane + B_GEMPTY + 8 * st); };
        auto take_item = [&]() -> int {
            return __shfl_sync(0xffffffffu, next_item(lane == 0, false), 0);
        };
        auto stage_acquire = [&](int b) { mbar_spin(bars + B_SEMPTY + 16 * wg + 8 * b, sph); };
        auto stage_publish = [&](int b) {
            fence_proxy_async_smem();
            __syncwarp();
            release(B_SFULL + 16 * wg + 8 * b);
        };
        auto stage_chunk = [&](int b, const uint32_t* v) {
            stage_acquire(b);
#pragma unroll
            for (int j = 0; j < 4; j++)
                stmatrix_x4(stg_row + b * 8192 + (((j * 2 + (lane >> 4)) ^ (lane & 7)) << 4), v[4 * j], v[4 * j + 1], v[4 * j + 2], v[4 * j + 3]);
            stage_publish(b);
            if (b) sph ^= 1;
        };
        auto stage_pair = [&](const uint32_t* v) {
            stage_acquire(0); stage_acquire(1);
#pragma unroll
            for (int j = 0; j < 8; j++)
                stmatrix_x4(stg_row + (j >> 2) * 8192 + ((((j & 3) * 2 + (lane >> 4)) ^ (lane & 7)) << 4), v[4 * j], v[4 * j + 1], v[4 * j + 2], v[4 * j + 3]);
            fence_proxy_async_smem();
            __syncwarp();
            mbar_arrive_if(lane < 2, bars + B_SFULL + 16 * wg + 8 * lane);
            sph ^= 1;
        };
        if (wg == 1) bar_arrive(1, 256);
        int it = first_item();
        while (item_type(it) != T_END) {
            if (item_type(it) <= T_LOCAL) {
                float acc[128];
                uint32_t pk[64];
                bool pending = false;
                bool held_b = false;
                bool final_out = false;
                zero_regs(pk);
                const uint32_t dB = make_desc(sb + 16384, 8192);
                do {
                    const int type = item_type(it);
                    if (type == T_LOCAL) {
                        int ln = lane;
                        asm volatile("" : "+r"(ln));
                        const int g = ln >> 2, t = ln & 3, par = wq & 1;
                        const uint32_t hc = (wq >> 1) * 4, pl = sb + (par * 2 + wg) * LOC_PLANE;
                        const uint32_t a16 = (ln & 15) * 128 + (((hc + (ln >> 4)) ^ (ln & 7)) << 4), a8 = (ln & 7) * 128 + (((hc + (ln >> 3)) ^ (ln & 7)) << 4);
                        const bool first0 = 2 * t > g, first1 = 2 * t + 1 > g;
                        const uint32_t fmask = (first0 ? 0xffffu : 0u) | (first1 ? 0xffff0000u : 0u);
                        const bool edge = item_row(it) == 0;
                        uint32_t q[4][2][4], kf[9][4], vf[9][4];
                        float w[8];
                        mbar_spin(bars + B_GFULL, gph);
#pragma unroll
                        for (int u = 0; u < 4; u++) { ldsm_x4(q[u][0], pl + u * 2048 + a16); ldsm_x4(q[u][1], pl + u * 2048 + (a16 ^ 32)); }
#pragma unroll
                        for (int j = 0; j < 8; j++) w[j] = lds_f32(sb + 4 * LOC_PLANE + 4 * (2 * g + par) + 64 * j);
                        __syncwarp();
                        release_stage(0);
                        mbar_spin(bars + B_GFULL + 8, gph);
#pragma unroll
                        for (int n = 0; n < 9; n++) ldsm_x4(kf[n], pl + GST_BYTES + n * 1024 + a8);
                        __syncwarp();
                        release_stage(1);
                        float s[8][2];
#pragma unroll
                        for (int u = 0; u < 4; u++) {
                            float d[3][4];
#pragma unroll
                            for (int nt = 0; nt < 3; nt++) {
                                mma_k16_init(d[nt], q[u][0], kf[2 * u + nt][0], kf[2 * u + nt][1]);
                                mma_k16(d[nt], q[u][1], kf[2 * u + nt][2], kf[2 * u + nt][3]);
                            }
                            if (u == 0 && edge) { d[0][0] = -INFINITY; d[0][1] = -INFINITY; }
                            s[2 * u][0] = first0 ? d[0][0] : d[1][0]; s[2 * u][1] = first1 ? d[0][1] : d[1][1];
                            s[2 * u + 1][0] = first0 ? d[1][2] : d[2][2]; s[2 * u + 1][1] = first1 ? d[1][3] : d[2][3];
                        }
                        mbar_spin(bars + B_GFULL + 16, gph);
#pragma unroll
                        for (int u = 0; u < 4; u++) { ldsm_x4_t(vf[2 * u], pl + 2 * GST_BYTES + u * 2048 + a16); ldsm_x4_t(vf[2 * u + 1], pl + 2 * GST_BYTES + u * 2048 + (a16 ^ 32)); }
                        ldsm_x4_t(vf[8], pl + 2 * GST_BYTES + 8192 + a8);
                        __syncwarp();
                        release_stage(2);
                        float x[8];
#pragma unroll
                        for (int j = 0; j < 8; j++) x[j] = fmaxf(s[j][0], s[j][1]);
#pragma unroll
                        for (int o = 1; o < 4; o *= 2)
#pragma unroll
                            for (int j = 0; j < 8; j++) x[j] = fmaxf(x[j], __shfl_xor_sync(0xffffffffu, x[j], o));
#pragma unroll
                        for (int j = 0; j < 8; j++) {
                            const float n = x[j] * -LOC_SCALE;
                            s[j][0] = ex2(fmaf(s[j][0], LOC_SCALE, n)); s[j][1] = ex2(fmaf(s[j][1], LOC_SCALE, n));
                            x[j] = s[j][0] + s[j][1];
                        }
#pragma unroll
                        for (int o = 1; o < 4; o *= 2)
#pragma unroll
                            for (int j = 0; j < 8; j++) x[j] += __shfl_xor_sync(0xffffffffu, x[j], o);
                        mbar_spin(bars + B_GFULL + 24, gph);
                        release_stage(3);
                        it = take_item();
                        uint32_t ob[4][8];
#pragma unroll
                        for (int u = 0; u < 4; u++) {
                            const float r0 = rcp(x[2 * u]), r1 = rcp(x[2 * u + 1]), f0 = fmaf(-w[2 * u], r0, r0), f1 = fmaf(-w[2 * u + 1], r1, r1);
                            const uint32_t p0 = pack_bf16(s[2 * u][0] * f0, s[2 * u][1] * f0), p1 = pack_bf16(s[2 * u + 1][0] * f1, s[2 * u + 1][1] * f1);
                            const uint32_t pa[4] = {p0 & fmask, 0, p0 & ~fmask, p1 & fmask};
#pragma unroll
                            for (int c = 0; c < 4; c++) {
                                float ol[4];
                                mma_k16_init(ol, pa, vf[2 * u + (c >> 1)][2 * (c & 1)], vf[2 * u + (c >> 1)][2 * (c & 1) + 1]);
                                mma_k8(ol, 0, p1 & ~fmask, u < 3 ? vf[2 * u + 2 + (c >> 1)][2 * (c & 1)] : vf[8][c]);
                                ob[u][2 * c] = pack_bf16(ol[0], ol[1]);
                                ob[u][2 * c + 1] = pack_bf16(ol[2], ol[3]);
                            }
                        }
                        stage_acquire(0); stage_acquire(1);
#pragma unroll
                        for (int u = 0; u < 4; u++) {
                            stmatrix_x4(stg + par * 8192 + u * 2048 + a16, ob[u][0], ob[u][1], ob[u][2], ob[u][3]);
                            stmatrix_x4(stg + par * 8192 + u * 2048 + (a16 ^ 32), ob[u][4], ob[u][5], ob[u][6], ob[u][7]);
                        }
                        fence_proxy_async_smem();
                        __syncwarp();
                        mbar_arrive_if(lane < 2, bars + B_SFULL + 16 * wg + 8 * lane);
                        bar_sync(4, 256);
                        sph ^= 1; gph ^= 1;
                        continue;
                    }
                    const int nk = type == T_OUT ? 36 : (type == T_K || type == T_V) ? 8 : 16;
                    mbar_spin(bars + B_GFULL, gph);
                    wgmma_fence();
                    wgmma_ss_n256_tb_init(acc, full_desc(dA), full_desc(dB));
#pragma unroll
                    for (int kk = 1; kk < 4; kk++) wgmma_ss_n256_tb(acc, full_desc(dA) + 2 * kk, full_desc(dB) + 128 * kk, 1);
                    wgmma_commit();
                    for (int k = 1; k < nk; k++) {
                        const uint32_t st = k & 3;
                        if (pending) {
                            const int kf = k - 1 - wg;
                            if (kf == 0) stage_chunk(0, pk);
                            else if (kf == 1) stage_chunk(1, pk + 16);
                            else if (kf == KF2) stage_chunk(0, pk + 32);
                            else if (kf == KF2 + 1) stage_chunk(1, pk + 48);
                        }
                        const bool lag = wg == 1 && k == nk - 2 && type != T_OUT;
                        if (lag) { wgmma_fence(); wgmma_commit(); }
                        wgmma_wait<1>();
                        mbar_arrive_cluster_if(lane < 2 && lag, bars_lane + B_GEMPTY + 8);
                        if (lag) bar_sync(3, 256);
                        mbar_wait(bars + B_GFULL + 8 * st, gph);
                        const uint64_t da = full_desc(dA + st * (GST_BYTES >> 4)), db = full_desc(dB + st * (GST_BYTES >> 4));
                        fence_regs(acc);
                        wgmma_fence();
#pragma unroll
                        for (int kk = 0; kk < 4; kk++) wgmma_ss_n256_tb(acc, da + 2 * kk, db + 128 * kk, 1);
                        wgmma_commit();
                        if (wg == 0 && k == nk - 1 && type != T_OUT) bar_arrive(3, 256);
                        wgmma_wait<1>();
                        mbar_arrive_cluster_if(lane < 2 && !lag, bars_lane + B_GEMPTY + 8 * ((k - 1) & 3));
                        if (st == 3) gph ^= 1;
                    }
                    wgmma_wait<0>();
                    fence_regs(acc);
                    release_stage(3);
                    if (type == T_OUT) {
                        release(B_WIDE);
                        for (int k = 0; k < 8; k++) {
                            const uint32_t st = k & 3;
                            mbar_spin(bars + B_GFULL + 8 * st, gph);
                            const uint64_t da = full_desc(dA + st * (GST_BYTES >> 4)), db = full_desc(dB + st * (GST_BYTES >> 4));
                            wgmma_fence();
#pragma unroll
                            for (int kk = 0; kk < 4; kk++) wgmma_ss_n128_lo_tb(acc, da + 2 * kk, db + 128 * kk, 1);
                            wgmma_commit();
                            if (k > 0) {
                                wgmma_wait<1>();
                                release_stage((k - 1) & 3);
                            }
                            if (k == 0) {
#pragma unroll
                                for (int j = 0; j < 32; j++) pk[j] = pack_bf16(acc[64 + 2 * j], acc[65 + 2 * j]);
                                stage_chunk(0, pk);
                                stage_chunk(1, pk + 16);
                            }
                            if (st == 3) gph ^= 1;
                        }
                        it = take_item();
                        mbar_spin(bars + B_PRECV + 8 * wg, oph);
                        oph ^= 1;
                        uint32_t v[8][4];
#pragma unroll
                        for (int j = 0; j < 8; j++)
                            ldsm_x4(v[j], stg_row - stg + sb + wg * GST_BYTES + 32768 + (j >> 2) * 8192 + ((((j & 3) * 2 + (lane >> 4)) ^ (lane & 7)) << 4));
                        wgmma_wait<0>();
                        fence_regs(acc);
                        __syncwarp();
                        release_stage(3);
#pragma unroll
                        for (int j = 0; j < 32; j++)
                            pk[j] = pack_bf16(acc[2 * j] + __uint_as_float(v[j >> 2][j & 3] << 16), acc[2 * j + 1] + __uint_as_float(v[j >> 2][j & 3] & 0xffff0000u));
                        pending = false; final_out = true;
                        break;
                    }
#pragma unroll
                    for (int j = 0; j < 64; j++) pk[j] = pack_bf16(acc[2 * j], acc[2 * j + 1]);
                    pending = true;
                    it = take_item();
                    held_b = type == T_B;
                } while (item_type(it) < T_LOCAL || (item_type(it) == T_LOCAL && (!held_b || (it & ITEM_READY))));
                if (pending || final_out) { stage_chunk(0, pk); stage_chunk(1, pk + 16); }
                if (pending && item_type(it) == T_ATTN) {
                    mbar_spin(bars + B_GEMPTY, gph ^ 1); mbar_spin(bars + B_GEMPTY + 8, gph ^ 1);
                    const uint32_t base = stg_row - stg + sb + ((ti & 1) ^ 1) * 32768 + wg * 16384;
#pragma unroll
                    for (int j = 0; j < 8; j++)
                        stmatrix_x4(base + (j >> 2) * 8192 + ((((j & 3) * 2 + (lane >> 4)) ^ (lane & 7)) << 4), pk[32 + 4 * j], pk[33 + 4 * j], pk[34 + 4 * j], pk[35 + 4 * j]);
                    fence_proxy_async_smem();
                    __syncwarp();
                    release(B_ALT + 8 * wg);
                } else if (pending) {
                    stage_chunk(0, pk + 32); stage_chunk(1, pk + 48);
                }
            } else {
                float o[64], s[64];
                uint32_t pa[32], pb[32];
                zero_regs(o); zero_regs(s); zero_regs(pa);
                float n0 = 0.f, n1 = 0.f;
                float l0 = 1.f, l1 = 1.f, f0 = 0.f, f1 = 0.f, g0 = 0.f, g1 = 0.f;
                uint32_t has_pv = 0;
                int first = 0;
                int pending = 0;
                const uint32_t dK = make_desc(sb + SM_KV, 16), dV = make_desc(sb + SM_KV, 16384);
                const uint32_t lane_off = bars_lane - bars + B_AEMPTY - B_AFULL;
                int cur = 0;
                uint32_t qoff = 0;
                const int row = wg * 64 + wq * 16 + (lane >> 2), thr = row - (lane & 3) * 2;
                auto kv_wait = [&](uint32_t n) { mbar_spin(bars + B_AFULL + 16 + 8 * (n & 3), (n >> 2) & 1); };
                auto kv_release = [&](uint32_t n) { mbar_arrive_cluster_if(lane < 2, bars_lane + B_AEMPTY + 16 + 8 * (n & 3)); };
                struct Slot { uint32_t bar, par, off; } slot[4];
                auto align = [&]() {
#pragma unroll
                    for (uint32_t i = 0; i < 4; i++) {
                        const uint32_t n = kvn + (i == 1 ? has_pv : i);
                        slot[i].bar = bars + B_AFULL + 16 + 8 * (n & 3); slot[i].par = (n >> 2) & 1; slot[i].off = (n & 3) * 2048;
                    }
                };
                align();
                auto pack_o = [&](uint32_t (&v)[32]) {
#pragma unroll
                    for (int j = 0; j < 16; j++) {
                        v[2 * j] = pack_bf16(o[4 * j] * f0, o[4 * j + 1] * f0);
                        v[2 * j + 1] = pack_bf16(o[4 * j + 2] * f1, o[4 * j + 3] * f1);
                    }
                };
                auto scales = [&]() { f0 = g0 * rcp(quad_sum(l0)); f1 = g1 * rcp(quad_sum(l1)); };
                auto step = [&](auto even, uint32_t (&pin)[32], uint32_t (&pout)[32], bool fresh, bool diag) {
                    constexpr bool EVEN = decltype(even)::value;
                    Slot& sk = slot[EVEN ? 0 : 2];
                    Slot& sv = slot[EVEN ? 1 : 3];
                    kvn += EVEN ? 1 + has_pv : 2;
                    mbar_spin(sk.bar, sk.par);
                    bar_sync(1 + wg, 256);
                    qk_gemm(s, dA + qoff, dK + sk.off);
                    if (EVEN && fresh) scales();
                    if (!EVEN && pending) { pack_o(pout); stage_pair(pout); }
                    mbar_spin(sv.bar, sv.par);
                    pv_gemm(o, pin, dV + sv.off, EVEN || !first);
                    bar_arrive(2 - wg, 256);
                    sk.par ^= 1; sv.par ^= 1;
                    wgmma_wait<1>();
                    fence_regs(s);
                    mbar_arrive_cluster_if(lane < 2 && (!EVEN || has_pv), sk.bar + lane_off);
                    if (diag) causal_mask(s, thr, wg);
                    if (EVEN && fresh) {
                        row_max<2>(s, n0, n1);
                        n0 *= -SM_SCALE; n1 *= -SM_SCALE;
                        l0 = 0.f; l1 = 0.f;
                    }
                    float r0, r1;
                    exp_pack(pout, s, n0, n1, r0, r1);
                    if (__any_sync(0xffffffffu, fmaxf(r0, r1) >= SUM_LIMIT)) {
                        float x0, x1;
                        row_max<16>(s, x0, x1);
                        x0 = fminf(x0 * -SM_SCALE, n0); x1 = fminf(x1 * -SM_SCALE, n1);
                        float a0 = ex2(x0 - n0), a1 = ex2(x1 - n1);
                        n0 = x0; n1 = x1;
                        l0 *= a0; l1 *= a1;
                        if (EVEN && fresh) { a0 = 1.f; a1 = 1.f; }
                        wgmma_wait<0>();
                        fence_regs(o);
#pragma unroll
                        for (int q = 0; q < 16; q++) { o[4 * q] *= a0; o[4 * q + 1] *= a0; o[4 * q + 2] *= a1; o[4 * q + 3] *= a1; }
                        exp_pack(pout, s, n0, n1, r0, r1);
                    }
                    l0 += r0; l1 += r1;
                    wgmma_wait<0>();
                    fence_regs(o);
                    fence_regs(pin);
                    mbar_arrive_cluster_if(lane < 2, sv.bar + lane_off);
                };
                auto copy_p = [&]() {
#pragma unroll
                    for (int j = 0; j < 32; j++) pa[j] = pb[j] ^ prm.zero;
                };
                int rem = 0;
                while (true) {
                    const bool fresh = rem == 0;
                    if (fresh) {
                        if (has_pv) {
                            release(B_AEMPTY + 8 * ((ti - 1) & 1));
                            it = take_item();
                            if (item_row(cur) < 2 || item_type(it) != T_ATTN) break;
                        }
                        cur = it;
                        qoff = (ti & 1) * 2048;
                        mbar_spin(bars + B_AFULL + 8 * (ti & 1), (ti >> 1) & 1);
                    }
                    step(std::true_type(), pa, pb, fresh, fresh ? !item_asc(cur) || item_row(cur) == 0 : item_asc(cur) && rem == 1);
                    first = fresh;
                    if (fresh) {
                        pending = has_pv; has_pv = 1;
                        if (!pending) { kvn -= 2; align(); kvn += 2; slot[0].par ^= 1; slot[1].par ^= 1; }
                        rem = item_row(cur);
                        g0 = lds_f32(bars + SM_GATE + (ti & 1) * 512 + 4 * row); g1 = lds_f32(bars + SM_GATE + (ti & 1) * 512 + 4 * row + 32);
                        ti++;
                        if (rem == 0) {
                            copy_p();
                            continue;
                        }
                    } else if (--rem == 0) {
                        copy_p();
                        align();
                        continue;
                    }
                    step(std::false_type(), pb, pa, false, item_asc(cur) && rem == 1);
                    pending = 0; first = 0;
                    rem--;
                }
                const uint32_t skip = item_asc(cur) & ~item_row(cur) & 1;
                kvn += skip;
#pragma unroll 1
                for (int pass = pending ? 0 : 1; pass < 2; pass++) {
                    if (pass) {
                        kv_wait(kvn);
                        pv_gemm(o, pa, dV + (kvn & 3) * 2048, !first);
                        scales();
                        wgmma_wait<0>();
                        fence_regs(o);
                        kv_release(kvn);
                        kvn += 1 + skip;
                    }
                    pack_o(pb);
                    stage_pair(pb);
                }
            }
        }
    }
}

typedef CUresult (*EncodeFn)(CUtensorMap*, CUtensorMapDataType, cuuint32_t, void*, const cuuint64_t*, const cuuint64_t*,
                             const cuuint32_t*, const cuuint32_t*, CUtensorMapInterleave, CUtensorMapSwizzle,
                             CUtensorMapL2promotion, CUtensorMapFloatOOBfill);

void encode3(EncodeFn fn, CUtensorMap* m, const void* ptr, uint64_t d0, uint64_t d1, uint64_t d2, uint64_t s1, uint64_t s2,
             uint32_t b0, uint32_t b1, uint32_t b2) {
    cuuint64_t dims[3] = {d0, d1, d2};
    cuuint64_t strides[2] = {s1, s2};
    cuuint32_t box[3] = {b0, b1, b2};
    cuuint32_t es[3] = {1, 1, 1};
    fn(m, CU_TENSOR_MAP_DATA_TYPE_BFLOAT16, 3, const_cast<void*>(ptr), dims, strides, box, es, CU_TENSOR_MAP_INTERLEAVE_NONE,
       CU_TENSOR_MAP_SWIZZLE_128B, CU_TENSOR_MAP_L2_PROMOTION_NONE, CU_TENSOR_MAP_FLOAT_OOB_FILL_NONE);
}
void map_act(EncodeFn fn, CUtensorMap* m, const void* p, int rows, int cols, int box_rows) {
    encode3(fn, m, p, cols, rows, 1, (uint64_t)cols * 2, (uint64_t)cols * rows * 2, 64, box_rows, 1);
}
void map_wgt(EncodeFn fn, CUtensorMap* m, const void* p, int K, int N) {
    encode3(fn, m, p, 64, K, N / 64, (uint64_t)N * 2, 128, 64, 64, 2);
}

void build_schedule(Params& p) {
    int n = 0;
    auto add = [&](int type, int col, int row) { p.items[n++] = (uint16_t)(type << 13 | col << 4 | row); };
    auto add_qkv = [&](int c) {
        for (int m = 0; m < 8; m++) add(T_Q, c, m);
        for (int m = 0; m < 8; m++) add(T_K, c, m);
        for (int m = 0; m < 8; m++) add(T_V, c, m);
    };
    int ldist = 170, ldist2 = 250, lstep = 16, beta = 26, tail = 32, late = 6;
    int order[16] = {6, 7, 8, 9, 10, 11, 12, 13, 14, 15, 5, 4, 3, 2, 1, 0};
    uint16_t proj[480];
    for (int m = 0; m < 8; m++) for (int c = 0; c < 12; c++) add(T_B, c, m);
    for (int c = 0; c < 16; c++) add_qkv(c);
    for (int i = 0; i < 480; i++) proj[i] = p.items[i];
    n = 0;
    for (int i = 0, l = 0; i < 480; i++) {
        p.items[n++] = proj[i];
        for (; l < 64 && i >= (l < 40 ? ldist + lstep * l / 8 : ldist2 + lstep * (l - 40) / 8); l++) add(T_LOCAL, l & 3, l >> 2);
    }
    const int a0 = n;
    for (int key = 0; key < 4000; key++)
        for (int r = 0; r < 32; r++)
            for (int j = 7; j >= 0; j--)
                if ((j ? (7 - j) * 40 + r * beta : 3999) == key) add(T_ATTN, 2 * order[r >> 1] + (r & 1), j);
    int t0 = n;
    for (int work = 0; work < 32 * 136 * tail / 100;) work += 4 * (p.items[--t0] & 15) + 3;
    for (int i = t0 + 1; i < n; i++)
        for (int j = i; j > t0 && (p.items[j] & 15) > (p.items[j - 1] & 15); j--) { const uint16_t t = p.items[j]; p.items[j] = p.items[j - 1]; p.items[j - 1] = t; }
    for (int moved = 0; moved < 2 && late >= 0; moved++)
        for (int i = a0; i < n; i++)
            if (p.items[i] == (T_ATTN << 13 | (2 * order[15] + moved) << 4 | late)) {
                for (int j = i; j + 1 < n; j++) p.items[j] = p.items[j + 1];
                p.items[n - 1] = (uint16_t)(T_ATTN << 13 | (2 * order[15] + moved) << 4 | late);
                break;
            }
    for (int m = 7; m >= 0; m--) for (int c = 0; c < 8; c++) add(T_OUT, c, m);
    for (int half = 0; half < 2; half++) {
        for (int i = 0; i < 20; i++) p.oseq[half][i] = (uint8_t)(i < 4 ? 32 + 4 * half + i : 2 * order[i - 4] + half);
        for (int i = 0; i < 2; i++) p.oseq[half][20 + i] = (uint8_t)(2 * order[14 + i] + 1 - half);
    }
}

void build_params(Params& p, void* const* d_in, void* d_out) {
    void* fnp = nullptr;
    cudaDriverEntryPointQueryResult qr;
    cudaGetDriverEntryPoint("cuTensorMapEncodeTiled", &fnp, cudaEnableDefault, &qr);
    EncodeFn fn = (EncodeFn)fnp;
    void* scr = nullptr;
    cudaGetSymbolAddress(&scr, g_scr);
    map_act(fn, &p.m[M_X], d_in[0], SEQ, 1024, 128);
    map_act(fn, &p.m[M_C], d_in[1], SEQ, 512, 128);
    map_wgt(fn, &p.m[M_WQ], d_in[2], 1024, 4096);
    map_wgt(fn, &p.m[M_WUK], d_in[3], 512, 4096);
    map_wgt(fn, &p.m[M_WUV], d_in[4], 512, 4096);
    map_wgt(fn, &p.m[M_WO], d_in[5], 4096, 1024);
    map_wgt(fn, &p.m[M_WQKV], d_in[7], 1024, 3072);
    map_wgt(fn, &p.m[M_WOB], d_in[8], 1024, 1024);
    encode3(fn, &p.m[M_SCR_LD], scr, 128, SEQ, G_TOTAL, 256, (uint64_t)SEQ * 256, 64, 128, 1);
    encode3(fn, &p.m[M_SCR_LOC], scr, 256, SEQ / 2, G_TOTAL, 512, (uint64_t)SEQ * 256, 64, 72, 1);
    encode3(fn, &p.m[M_SCR_LOQ], scr, 256, SEQ / 2, G_TOTAL, 512, (uint64_t)SEQ * 256, 64, 64, 1);
    encode3(fn, &p.m[M_SCR_ST], scr, 128, SEQ, G_TOTAL, 256, (uint64_t)SEQ * 256, 64, 64, 1);
    map_act(fn, &p.m[M_OUT], d_out, SEQ, 1024, 64);
    p.x = (const __nv_bfloat16*)d_in[0];
    p.gate_w = (const __nv_bfloat16*)d_in[9];
    p.zero = 0;
    p.wo[0] = (const char*)d_in[5]; p.wo[1] = (const char*)d_in[8]; p.pfd = 99;
    build_schedule(p);
}

}

extern "C" void kernel_launch(void* const* d_in, const int* in_sizes, int n_in, void* d_out, int out_size) {
    (void)in_sizes; (void)n_in; (void)out_size;
    Params p;
    build_params(p, d_in, d_out);
    cudaFuncSetAttribute(fused_kernel, cudaFuncAttributeMaxDynamicSharedMemorySize, SM_TOTAL);
    fused_kernel<<<NCTA, 384, SM_TOTAL>>>(p);
}
```

```cpp
#include <cuda_runtime.h>
#include <cuda_bf16.h>
#include <cuda.h>
#include <stddef.h>
#include <stdint.h>
#include <type_traits>

namespace {

constexpr int SEQ = 2048;
constexpr int G_Q = 0, G_K = 32, G_V = 64, G_B = 96, G_CTX = G_Q, G_LOC = G_B, G_TOTAL = 120;

__device__ __align__(1024) __nv_bfloat16 g_scr[(size_t)G_TOTAL * SEQ * 128];
__device__ __align__(128) float g_gate[SEQ];

__device__ __forceinline__ uint32_t smem_u32(const void* p) { return (uint32_t)__cvta_generic_to_shared(p); }
__device__ __forceinline__ bool elect_one() {
    uint32_t p;
    asm volatile("{\n.reg .pred P;\nelect.sync _|P, 0xffffffff;\nselp.u32 %0, 1, 0, P;\n}\n" : "=r"(p));
    return p != 0;
}
__device__ __forceinline__ void mbar_init(uint32_t bar, uint32_t count) {
    asm volatile("mbarrier.init.shared::cta.b64 [%0], %1;" :: "r"(bar), "r"(count) : "memory");
}
__device__ __forceinline__ void mbar_expect_tx(uint32_t bar, uint32_t bytes) {
    asm volatile("mbarrier.arrive.expect_tx.shared::cta.b64 _, [%0], %1;" :: "r"(bar), "r"(bytes) : "memory");
}
__device__ __forceinline__ uint32_t cluster_rank() { uint32_t r; asm("mov.u32 %0, %%cluster_ctarank;" : "=r"(r)); return r; }
__device__ __forceinline__ uint32_t map_cta(uint32_t addr, uint32_t cta) {
    uint32_t r; asm("mapa.shared::cluster.u32 %0, %1, %2;" : "=r"(r) : "r"(addr), "r"(cta)); return r;
}
__device__ __forceinline__ void mbar_arrive_cluster_if(bool pred, uint32_t cluster_bar) {
    asm volatile("{\n.reg .pred P;\nsetp.ne.u32 P, %1, 0;\n@P mbarrier.arrive.shared::cluster.b64 _, [%0];\n}\n"
                 :: "r"(cluster_bar), "r"((uint32_t)pred) : "memory");
}
__device__ __forceinline__ void mbar_arrive_cluster_n_if(bool pred, uint32_t cluster_bar, uint32_t count) {
    asm volatile("{\n.reg .pred P;\nsetp.ne.u32 P, %1, 0;\n@P mbarrier.arrive.shared::cluster.b64 _, [%0], %2;\n}\n"
                 :: "r"(cluster_bar), "r"((uint32_t)pred), "r"(count) : "memory");
}
__device__ __forceinline__ void mbar_arrive_if(bool pred, uint32_t bar) {
    asm volatile("{\n.reg .pred P;\nsetp.ne.u32 P, %1, 0;\n@P mbarrier.arrive.shared::cta.b64 _, [%0];\n}\n"
                 :: "r"(bar), "r"((uint32_t)pred) : "memory");
}
__device__ __forceinline__ bool mbar_test(uint32_t bar, uint32_t parity) {
    uint32_t ok;
    asm volatile("{\n.reg .pred P;\nmbarrier.test_wait.parity.shared::cta.b64 P, [%1], %2;\nselp.u32 %0, 1, 0, P;\n}\n"
                 : "=r"(ok) : "r"(bar), "r"(parity) : "memory");
    return ok != 0;
}
__device__ __forceinline__ void mbar_wait(uint32_t bar, uint32_t parity) {
    asm volatile("{\n.reg .pred P;\n.reg .u32 c;\n"
                 "mbarrier.try_wait.parity.shared::cta.b64 P, [%0], %1;\n"
                 "@P bra DONE;\n"
                 "mov.u32 c, 0;\n"
                 "SPIN:\n"
                 "mbarrier.try_wait.parity.shared::cta.b64 P, [%0], %1;\n"
                 "@P bra DONE;\n"
                 "add.u32 c, c, 1;\n"
                 "setp.lt.u32 P, c, 4194304;\n"
                 "@P bra SPIN;\n"
                 "trap;\n"
                 "DONE:\n}\n" :: "r"(bar), "r"(parity) : "memory");
}
__device__ __forceinline__ void mbar_spin(uint32_t bar, uint32_t parity) {
    asm volatile("{\n.reg .pred P;\n"
                 "SPIN:\n"
                 "mbarrier.try_wait.parity.shared::cta.b64 P, [%0], %1;\n"
                 "@!P bra SPIN;\n}\n" :: "r"(bar), "r"(parity) : "memory");
}
__device__ __forceinline__ void bar_sync(int id, int n) { asm volatile("bar.sync %0, %1;" :: "r"(id), "r"(n) : "memory"); }
__device__ __forceinline__ void bar_arrive(int id, int n) { asm volatile("bar.arrive %0, %1;" :: "r"(id), "r"(n) : "memory"); }
__device__ __forceinline__ void fence_proxy_async_smem() { asm volatile("fence.proxy.async.shared::cta;" ::: "memory"); }
__device__ __forceinline__ void tma_load_3d(uint32_t dst, const CUtensorMap* map, uint32_t bar, int c0, int c1, int c2) {
    asm volatile("cp.async.bulk.tensor.3d.shared::cluster.global.mbarrier::complete_tx::bytes [%0], [%1, {%3, %4, %5}], [%2];"
                 :: "r"(dst), "l"(map), "r"(bar), "r"(c0), "r"(c1), "r"(c2) : "memory");
}
__device__ __forceinline__ void warp_expect_tx(uint32_t bar, uint32_t bytes) {
    asm volatile("{\n.reg .pred P;\nelect.sync _|P, 0xffffffff;\n@P mbarrier.arrive.expect_tx.shared::cta.b64 _, [%0], %1;\n}\n"
                 :: "r"(bar), "r"(bytes) : "memory");
}
__device__ __forceinline__ void warp_tma_load(uint32_t dst, const CUtensorMap* map, uint32_t bar, int c0, int c1, int c2) {
    asm volatile("{\n.reg .pred P;\nelect.sync _|P, 0xffffffff;\n"
                 "@P cp.async.bulk.tensor.3d.shared::cluster.global.mbarrier::complete_tx::bytes [%0], [%1, {%3, %4, %5}], [%2];\n}\n"
                 :: "r"(dst), "l"(map), "r"(bar), "r"(c0), "r"(c1), "r"(c2) : "memory");
}
__device__ __forceinline__ void warp_tma_load_pair(uint32_t dst, const CUtensorMap* map, uint32_t bar, int c0, int c1, int c2) {
    asm volatile("{\n.reg .pred P;\nelect.sync _|P, 0xffffffff;\n"
                 "@P cp.async.bulk.tensor.3d.shared::cluster.global.mbarrier::complete_tx::bytes.multicast::cluster"
                 " [%0], [%1, {%3, %4, %5}], [%2], %6;\n}\n"
                 :: "r"(dst), "l"(map), "r"(bar), "r"(c0), "r"(c1), "r"(c2), "h"((uint16_t)3) : "memory");
}
__device__ __forceinline__ void warp_bulk_load(uint32_t dst, const void* src, uint32_t bytes, uint32_t bar) {
    asm volatile("{\n.reg .pred P;\nelect.sync _|P, 0xffffffff;\n"
                 "@P cp.async.bulk.shared::cluster.global.mbarrier::complete_tx::bytes [%0], [%1], %2, [%3];\n}\n"
                 :: "r"(dst), "l"(src), "r"(bytes), "r"(bar) : "memory");
}
__device__ __forceinline__ void warp_tma_store(const CUtensorMap* map, uint32_t src, int c0, int c1, int c2) {
    asm volatile("{\n.reg .pred P;\nelect.sync _|P, 0xffffffff;\n"
                 "@P cp.async.bulk.tensor.3d.global.shared::cta.bulk_group [%0, {%2, %3, %4}], [%1];\n}\n"
                 :: "l"(map), "r"(src), "r"(c0), "r"(c1), "r"(c2) : "memory");
}
__device__ __forceinline__ void warp_bulk_store(void* dst, uint32_t src, uint32_t bytes) {
    asm volatile("{\n.reg .pred P;\nelect.sync _|P, 0xffffffff;\n"
                 "@P cp.async.bulk.global.shared::cta.bulk_group [%0], [%1], %2;\n}\n" :: "l"(dst), "r"(src), "r"(bytes) : "memory");
}
__device__ __forceinline__ void prefetch_l2(const void* src, uint32_t bytes) {
    asm volatile("cp.async.bulk.prefetch.L2.global [%0], %1;" :: "l"(src), "r"(bytes) : "memory");
}
__device__ __forceinline__ void warp_prefetch(const void* src, uint32_t bytes) {
    asm volatile("{\n.reg .pred P;\nelect.sync _|P, 0xffffffff;\n@P cp.async.bulk.prefetch.L2.global [%0], %1;\n}\n" :: "l"(src), "r"(bytes) : "memory");
}
__device__ __forceinline__ void bulk_commit() { asm volatile("cp.async.bulk.commit_group;" ::: "memory"); }
template <int N> __device__ __forceinline__ void bulk_wait_read() { asm volatile("cp.async.bulk.wait_group.read %0;" :: "n"(N) : "memory"); }
template <int N> __device__ __forceinline__ void bulk_wait() { asm volatile("cp.async.bulk.wait_group %0;" :: "n"(N) : "memory"); }
__device__ __forceinline__ void wgmma_fence() { asm volatile("wgmma.fence.sync.aligned;" ::: "memory"); }
__device__ __forceinline__ void wgmma_commit() { asm volatile("wgmma.commit_group.sync.aligned;" ::: "memory"); }
template <int N> __device__ __forceinline__ void wgmma_wait() { asm volatile("wgmma.wait_group.sync.aligned %0;" :: "n"(N) : "memory"); }
template <int N> __device__ __forceinline__ void fence_regs(float (&d)[N]) {
#pragma unroll
    for (int i = 0; i < N; i++) asm volatile("" : "+f"(d[i]) :: "memory");
}
template <int N> __device__ __forceinline__ void fence_regs(uint32_t (&d)[N]) {
#pragma unroll
    for (int i = 0; i < N; i++) asm volatile("" : "+r"(d[i]) :: "memory");
}
template <int N> __device__ __forceinline__ void reg_dec() { asm volatile("setmaxnreg.dec.sync.aligned.u32 %0;" :: "n"(N)); }
template <int N> __device__ __forceinline__ void reg_inc() { asm volatile("setmaxnreg.inc.sync.aligned.u32 %0;" :: "n"(N)); }
__device__ __forceinline__ uint32_t pack_bf16(float lo, float hi) {
    uint32_t r; asm("cvt.rn.bf16x2.f32 %0, %1, %2;" : "=r"(r) : "f"(hi), "f"(lo)); return r;
}
__device__ __forceinline__ void stmatrix_x4(uint32_t addr, uint32_t r0, uint32_t r1, uint32_t r2, uint32_t r3) {
    asm volatile("stmatrix.sync.aligned.m8n8.x4.shared.b16 [%0], {%1, %2, %3, %4};"
                 :: "r"(addr), "r"(r0), "r"(r1), "r"(r2), "r"(r3) : "memory");
}
__device__ __forceinline__ float ex2(float x) { float y; asm("ex2.approx.ftz.f32 %0, %1;" : "=f"(y) : "f"(x)); return y; }

constexpr uint32_t DESC_HI = (1024 >> 4) | (1u << 30);
__device__ __forceinline__ uint32_t make_desc(uint32_t addr, uint32_t lbo) {
    uint32_t lo = ((addr & 0x3FFFF) >> 4) | ((lbo >> 4) << 16);
    asm volatile("" : "+r"(lo));
    return lo;
}
__device__ __forceinline__ uint64_t full_desc(uint32_t lo) {
    uint64_t d; asm("mov.b64 %0, {%1, %2};" : "=l"(d) : "r"(lo), "r"(DESC_HI)); return d;
}

__device__ __forceinline__ void wgmma_ss_n256_tb_init(float (&d)[128], uint64_t da, uint64_t db) {
    asm volatile("{\n.reg .pred p;\n"
        "setp.ne.b32 p, 0, 0;\n"
        "wgmma.mma_async.sync.aligned.m64n256k16.f32.bf16.bf16 "
        "{%0, %1, %2, %3, %4, %5, %6, %7, %8, %9, %10, %11, %12, %13, %14, %15, %16, %17, %18, %19, %20, "
        "%21, %22, %23, %24, %25, %26, %27, %28, %29, %30, %31, %32, %33, %34, %35, %36, %37, %38, %39, %40, "
        "%41, %42, %43, %44, %45, %46, %47, %48, %49, %50, %51, %52, %53, %54, %55, %56, %57, %58, %59, %60, "
        "%61, %62, %63, %64, %65, %66, %67, %68, %69, %70, %71, %72, %73, %74, %75, %76, %77, %78, %79, %80, "
        "%81, %82, %83, %84, %85, %86, %87, %88, %89, %90, %91, %92, %93, %94, %95, %96, %97, %98, %99, "
        "%100, %101, %102, %103, %104, %105, %106, %107, %108, %109, %110, %111, %112, %113, %114, %115, "
        "%116, %117, %118, %119, %120, %121, %122, %123, %124, %125, %126, %127},"
        " %128, %129, p, 1, 1, 0, 1;\n}\n"
        : "=f"(d[0]), "=f"(d[1]), "=f"(d[2]), "=f"(d[3]), "=f"(d[4]), "=f"(d[5]), "=f"(d[6]), "=f"(d[7]),
        "=f"(d[8]), "=f"(d[9]), "=f"(d[10]), "=f"(d[11]), "=f"(d[12]), "=f"(d[13]), "=f"(d[14]), "=f"(d[15]),
        "=f"(d[16]), "=f"(d[17]), "=f"(d[18]), "=f"(d[19]), "=f"(d[20]), "=f"(d[21]), "=f"(d[22]),
        "=f"(d[23]), "=f"(d[24]), "=f"(d[25]), "=f"(d[26]), "=f"(d[27]), "=f"(d[28]), "=f"(d[29]),
        "=f"(d[30]), "=f"(d[31]), "=f"(d[32]), "=f"(d[33]), "=f"(d[34]), "=f"(d[35]), "=f"(d[36]),
        "=f"(d[37]), "=f"(d[38]), "=f"(d[39]), "=f"(d[40]), "=f"(d[41]), "=f"(d[42]), "=f"(d[43]),
        "=f"(d[44]), "=f"(d[45]), "=f"(d[46]), "=f"(d[47]), "=f"(d[48]), "=f"(d[49]), "=f"(d[50]),
        "=f"(d[51]), "=f"(d[52]), "=f"(d[53]), "=f"(d[54]), "=f"(d[55]), "=f"(d[56]), "=f"(d[57]),
        "=f"(d[58]), "=f"(d[59]), "=f"(d[60]), "=f"(d[61]), "=f"(d[62]), "=f"(d[63]), "=f"(d[64]),
        "=f"(d[65]), "=f"(d[66]), "=f"(d[67]), "=f"(d[68]), "=f"(d[69]), "=f"(d[70]), "=f"(d[71]),
        "=f"(d[72]), "=f"(d[73]), "=f"(d[74]), "=f"(d[75]), "=f"(d[76]), "=f"(d[77]), "=f"(d[78]),
        "=f"(d[79]), "=f"(d[80]), "=f"(d[81]), "=f"(d[82]), "=f"(d[83]), "=f"(d[84]), "=f"(d[85]),
        "=f"(d[86]), "=f"(d[87]), "=f"(d[88]), "=f"(d[89]), "=f"(d[90]), "=f"(d[91]), "=f"(d[92]),
        "=f"(d[93]), "=f"(d[94]), "=f"(d[95]), "=f"(d[96]), "=f"(d[97]), "=f"(d[98]), "=f"(d[99]),
        "=f"(d[100]), "=f"(d[101]), "=f"(d[102]), "=f"(d[103]), "=f"(d[104]), "=f"(d[105]), "=f"(d[106]),
        "=f"(d[107]), "=f"(d[108]), "=f"(d[109]), "=f"(d[110]), "=f"(d[111]), "=f"(d[112]), "=f"(d[113]),
        "=f"(d[114]), "=f"(d[115]), "=f"(d[116]), "=f"(d[117]), "=f"(d[118]), "=f"(d[119]), "=f"(d[120]),
        "=f"(d[121]), "=f"(d[122]), "=f"(d[123]), "=f"(d[124]), "=f"(d[125]), "=f"(d[126]), "=f"(d[127])
        : "l"(da), "l"(db));
}
__device__ __forceinline__ void wgmma_ss_n256_tb(float (&d)[128], uint64_t da, uint64_t db, int scale_d) {
    asm volatile("{\n.reg .pred p;\n"
        "setp.ne.b32 p, %130, 0;\n"
        "wgmma.mma_async.sync.aligned.m64n256k16.f32.bf16.bf16 "
        "{%0, %1, %2, %3, %4, %5, %6, %7, %8, %9, %10, %11, %12, %13, %14, %15, %16, %17, %18, %19, %20, "
        "%21, %22, %23, %24, %25, %26, %27, %28, %29, %30, %31, %32, %33, %34, %35, %36, %37, %38, %39, %40, "
        "%41, %42, %43, %44, %45, %46, %47, %48, %49, %50, %51, %52, %53, %54, %55, %56, %57, %58, %59, %60, "
        "%61, %62, %63, %64, %65, %66, %67, %68, %69, %70, %71, %72, %73, %74, %75, %76, %77, %78, %79, %80, "
        "%81, %82, %83, %84, %85, %86, %87, %88, %89, %90, %91, %92, %93, %94, %95, %96, %97, %98, %99, "
        "%100, %101, %102, %103, %104, %105, %106, %107, %108, %109, %110, %111, %112, %113, %114, %115, "
        "%116, %117, %118, %119, %120, %121, %122, %123, %124, %125, %126, %127},"
        " %128, %129, p, 1, 1, 0, 1;\n}\n"
        : "+f"(d[0]), "+f"(d[1]), "+f"(d[2]), "+f"(d[3]), "+f"(d[4]), "+f"(d[5]), "+f"(d[6]), "+f"(d[7]),
        "+f"(d[8]), "+f"(d[9]), "+f"(d[10]), "+f"(d[11]), "+f"(d[12]), "+f"(d[13]), "+f"(d[14]), "+f"(d[15]),
        "+f"(d[16]), "+f"(d[17]), "+f"(d[18]), "+f"(d[19]), "+f"(d[20]), "+f"(d[21]), "+f"(d[22]),
        "+f"(d[23]), "+f"(d[24]), "+f"(d[25]), "+f"(d[26]), "+f"(d[27]), "+f"(d[28]), "+f"(d[29]),
        "+f"(d[30]), "+f"(d[31]), "+f"(d[32]), "+f"(d[33]), "+f"(d[34]), "+f"(d[35]), "+f"(d[36]),
        "+f"(d[37]), "+f"(d[38]), "+f"(d[39]), "+f"(d[40]), "+f"(d[41]), "+f"(d[42]), "+f"(d[43]),
        "+f"(d[44]), "+f"(d[45]), "+f"(d[46]), "+f"(d[47]), "+f"(d[48]), "+f"(d[49]), "+f"(d[50]),
        "+f"(d[51]), "+f"(d[52]), "+f"(d[53]), "+f"(d[54]), "+f"(d[55]), "+f"(d[56]), "+f"(d[57]),
        "+f"(d[58]), "+f"(d[59]), "+f"(d[60]), "+f"(d[61]), "+f"(d[62]), "+f"(d[63]), "+f"(d[64]),
        "+f"(d[65]), "+f"(d[66]), "+f"(d[67]), "+f"(d[68]), "+f"(d[69]), "+f"(d[70]), "+f"(d[71]),
        "+f"(d[72]), "+f"(d[73]), "+f"(d[74]), "+f"(d[75]), "+f"(d[76]), "+f"(d[77]), "+f"(d[78]),
        "+f"(d[79]), "+f"(d[80]), "+f"(d[81]), "+f"(d[82]), "+f"(d[83]), "+f"(d[84]), "+f"(d[85]),
        "+f"(d[86]), "+f"(d[87]), "+f"(d[88]), "+f"(d[89]), "+f"(d[90]), "+f"(d[91]), "+f"(d[92]),
        "+f"(d[93]), "+f"(d[94]), "+f"(d[95]), "+f"(d[96]), "+f"(d[97]), "+f"(d[98]), "+f"(d[99]),
        "+f"(d[100]), "+f"(d[101]), "+f"(d[102]), "+f"(d[103]), "+f"(d[104]), "+f"(d[105]), "+f"(d[106]),
        "+f"(d[107]), "+f"(d[108]), "+f"(d[109]), "+f"(d[110]), "+f"(d[111]), "+f"(d[112]), "+f"(d[113]),
        "+f"(d[114]), "+f"(d[115]), "+f"(d[116]), "+f"(d[117]), "+f"(d[118]), "+f"(d[119]), "+f"(d[120]),
        "+f"(d[121]), "+f"(d[122]), "+f"(d[123]), "+f"(d[124]), "+f"(d[125]), "+f"(d[126]), "+f"(d[127])
        : "l"(da), "l"(db), "r"(scale_d));
}
__device__ __forceinline__ void wgmma_ss_n128(float (&d)[64], uint64_t da, uint64_t db, int scale_d) {
    asm volatile("{\n.reg .pred p;\n"
        "setp.ne.b32 p, %66, 0;\n"
        "wgmma.mma_async.sync.aligned.m64n128k16.f32.bf16.bf16 "
        "{%0, %1, %2, %3, %4, %5, %6, %7, %8, %9, %10, %11, %12, %13, %14, %15, %16, %17, %18, %19, %20, "
        "%21, %22, %23, %24, %25, %26, %27, %28, %29, %30, %31, %32, %33, %34, %35, %36, %37, %38, %39, %40, "
        "%41, %42, %43, %44, %45, %46, %47, %48, %49, %50, %51, %52, %53, %54, %55, %56, %57, %58, %59, %60, "
        "%61, %62, %63},"
        " %64, %65, p, 1, 1, 0, 0;\n}\n"
        : "+f"(d[0]), "+f"(d[1]), "+f"(d[2]), "+f"(d[3]), "+f"(d[4]), "+f"(d[5]), "+f"(d[6]), "+f"(d[7]),
        "+f"(d[8]), "+f"(d[9]), "+f"(d[10]), "+f"(d[11]), "+f"(d[12]), "+f"(d[13]), "+f"(d[14]), "+f"(d[15]),
        "+f"(d[16]), "+f"(d[17]), "+f"(d[18]), "+f"(d[19]), "+f"(d[20]), "+f"(d[21]), "+f"(d[22]),
        "+f"(d[23]), "+f"(d[24]), "+f"(d[25]), "+f"(d[26]), "+f"(d[27]), "+f"(d[28]), "+f"(d[29]),
        "+f"(d[30]), "+f"(d[31]), "+f"(d[32]), "+f"(d[33]), "+f"(d[34]), "+f"(d[35]), "+f"(d[36]),
        "+f"(d[37]), "+f"(d[38]), "+f"(d[39]), "+f"(d[40]), "+f"(d[41]), "+f"(d[42]), "+f"(d[43]),
        "+f"(d[44]), "+f"(d[45]), "+f"(d[46]), "+f"(d[47]), "+f"(d[48]), "+f"(d[49]), "+f"(d[50]),
        "+f"(d[51]), "+f"(d[52]), "+f"(d[53]), "+f"(d[54]), "+f"(d[55]), "+f"(d[56]), "+f"(d[57]),
        "+f"(d[58]), "+f"(d[59]), "+f"(d[60]), "+f"(d[61]), "+f"(d[62]), "+f"(d[63])
        : "l"(da), "l"(db), "r"(scale_d));
}
__device__ __forceinline__ void wgmma_rs_n128_tb(float (&d)[64], uint32_t a0, uint32_t a1, uint32_t a2, uint32_t a3, uint64_t db, int scale_d) {
    asm volatile("{\n.reg .pred p;\n"
        "setp.ne.b32 p, %69, 0;\n"
        "wgmma.mma_async.sync.aligned.m64n128k16.f32.bf16.bf16 "
        "{%0, %1, %2, %3, %4, %5, %6, %7, %8, %9, %10, %11, %12, %13, %14, %15, %16, %17, %18, %19, %20, "
        "%21, %22, %23, %24, %25, %26, %27, %28, %29, %30, %31, %32, %33, %34, %35, %36, %37, %38, %39, %40, "
        "%41, %42, %43, %44, %45, %46, %47, %48, %49, %50, %51, %52, %53, %54, %55, %56, %57, %58, %59, %60, "
        "%61, %62, %63},"
        " {%64, %65, %66, %67}, %68, p, 1, 1, 1;\n}\n"
        : "+f"(d[0]), "+f"(d[1]), "+f"(d[2]), "+f"(d[3]), "+f"(d[4]), "+f"(d[5]), "+f"(d[6]), "+f"(d[7]),
        "+f"(d[8]), "+f"(d[9]), "+f"(d[10]), "+f"(d[11]), "+f"(d[12]), "+f"(d[13]), "+f"(d[14]), "+f"(d[15]),
        "+f"(d[16]), "+f"(d[17]), "+f"(d[18]), "+f"(d[19]), "+f"(d[20]), "+f"(d[21]), "+f"(d[22]),
        "+f"(d[23]), "+f"(d[24]), "+f"(d[25]), "+f"(d[26]), "+f"(d[27]), "+f"(d[28]), "+f"(d[29]),
        "+f"(d[30]), "+f"(d[31]), "+f"(d[32]), "+f"(d[33]), "+f"(d[34]), "+f"(d[35]), "+f"(d[36]),
        "+f"(d[37]), "+f"(d[38]), "+f"(d[39]), "+f"(d[40]), "+f"(d[41]), "+f"(d[42]), "+f"(d[43]),
        "+f"(d[44]), "+f"(d[45]), "+f"(d[46]), "+f"(d[47]), "+f"(d[48]), "+f"(d[49]), "+f"(d[50]),
        "+f"(d[51]), "+f"(d[52]), "+f"(d[53]), "+f"(d[54]), "+f"(d[55]), "+f"(d[56]), "+f"(d[57]),
        "+f"(d[58]), "+f"(d[59]), "+f"(d[60]), "+f"(d[61]), "+f"(d[62]), "+f"(d[63])
        : "r"(a0), "r"(a1), "r"(a2), "r"(a3), "l"(db), "r"(scale_d));
}
__device__ __forceinline__ void wgmma_ss_n128_lo_tb(float (&d)[128], uint64_t da, uint64_t db, int scale_d) {
    asm volatile("{\n.reg .pred p;\n"
        "setp.ne.b32 p, %66, 0;\n"
        "wgmma.mma_async.sync.aligned.m64n128k16.f32.bf16.bf16 "
        "{%0, %1, %2, %3, %4, %5, %6, %7, %8, %9, %10, %11, %12, %13, %14, %15, %16, %17, %18, %19, %20, "
        "%21, %22, %23, %24, %25, %26, %27, %28, %29, %30, %31, %32, %33, %34, %35, %36, %37, %38, %39, %40, "
        "%41, %42, %43, %44, %45, %46, %47, %48, %49, %50, %51, %52, %53, %54, %55, %56, %57, %58, %59, %60, "
        "%61, %62, %63},"
        " %64, %65, p, 1, 1, 0, 1;\n}\n"
        : "+f"(d[0]), "+f"(d[1]), "+f"(d[2]), "+f"(d[3]), "+f"(d[4]), "+f"(d[5]), "+f"(d[6]), "+f"(d[7]),
        "+f"(d[8]), "+f"(d[9]), "+f"(d[10]), "+f"(d[11]), "+f"(d[12]), "+f"(d[13]), "+f"(d[14]), "+f"(d[15]),
        "+f"(d[16]), "+f"(d[17]), "+f"(d[18]), "+f"(d[19]), "+f"(d[20]), "+f"(d[21]), "+f"(d[22]),
        "+f"(d[23]), "+f"(d[24]), "+f"(d[25]), "+f"(d[26]), "+f"(d[27]), "+f"(d[28]), "+f"(d[29]),
        "+f"(d[30]), "+f"(d[31]), "+f"(d[32]), "+f"(d[33]), "+f"(d[34]), "+f"(d[35]), "+f"(d[36]),
        "+f"(d[37]), "+f"(d[38]), "+f"(d[39]), "+f"(d[40]), "+f"(d[41]), "+f"(d[42]), "+f"(d[43]),
        "+f"(d[44]), "+f"(d[45]), "+f"(d[46]), "+f"(d[47]), "+f"(d[48]), "+f"(d[49]), "+f"(d[50]),
        "+f"(d[51]), "+f"(d[52]), "+f"(d[53]), "+f"(d[54]), "+f"(d[55]), "+f"(d[56]), "+f"(d[57]),
        "+f"(d[58]), "+f"(d[59]), "+f"(d[60]), "+f"(d[61]), "+f"(d[62]), "+f"(d[63])
        : "l"(da), "l"(db), "r"(scale_d));
}

enum { M_X = 0, M_C, M_WQ, M_WQKV, M_WUK, M_WUV, M_WO, M_WOB, M_SCR_LD, M_SCR_LOC, M_SCR_LOQ, M_SCR_ST, M_COUNT };
enum { T_Q = 0, T_K, T_V, T_B, T_OUT, T_LOCAL, T_ATTN, T_END };
constexpr int NCTA = 132, NPAIR = NCTA / 2;
constexpr int NITEMS = 480 + 64 + 256;
#define NTRI 3
constexpr int TRIPLES = NTRI, WIDE = 80 - 3 * TRIPLES;
struct Params {
    CUtensorMap m[M_COUNT];
    const __nv_bfloat16* x;
    const __nv_bfloat16* gate_w;
    const char* wo;
    const char* wob;
    __nv_bfloat16* out;
    uint32_t zero;
    uint16_t items[NITEMS];
    uint8_t ostep[80];
};
__device__ __forceinline__ int item_type(int it) { return it >> 13; }
__device__ __forceinline__ int item_row(int it) { return it & 15; }
__device__ __forceinline__ int item_col(int it) { return (it >> 4) & 31; }
__device__ __forceinline__ int item_asc(int it) { return (it >> 9) & 1; }
constexpr int ITEM_READY = 1 << 10;

struct __align__(128) Sync {
    unsigned long long count[4];
    __align__(128) unsigned long long ctx[16];
    unsigned next, next_out, done;
    __align__(128) unsigned step[32][2];
    unsigned split[32];
};
__device__ Sync g_sync;
__device__ uint4 g_part[128][8][256];

constexpr uint32_t GST_BYTES = 49152, SM_KV = 65536, SM_STAGING = 196608, SM_BARS = SM_STAGING + 32768;
constexpr uint32_t B_GFULL = 0, B_GEMPTY = 32, B_AFULL = 64, B_AEMPTY = 112, B_SFULL = 160, B_SEMPTY = 192,
                   B_IFULL = 224, B_IEMPTY = 288, B_XFREE = 352, B_WANT = 384, B_HALF = 416,
                   SM_ORDY = 448, SM_QUEUE = 456, B_ALT = 488, B_QFREE = 504, SM_GATE = 512, SM_TOTAL = SM_BARS + 1536;
constexpr int QDEPTH = 8;
#define PF_NAR 20
#define SPREAD 4
#define PACE 0
#define PF_LOC 1
#define KMEET 14
constexpr int K_MEET = KMEET, K_SPLIT = KMEET + 12;
#define KF2 3
constexpr uint32_t LOC_PLANE = 72 * 128;
constexpr float SM_SCALE = 0.08838834764831845f * 1.4426950408889634f;
constexpr float LOC_SCALE = 0.17677669529663687f * 1.4426950408889634f;
constexpr float SUM_LIMIT = 1152921504606846976.f;

__device__ __forceinline__ unsigned ld_acquire(const unsigned* p) {
    unsigned v; asm volatile("ld.acquire.gpu.global.u32 %0, [%1];" : "=r"(v) : "l"(p) : "memory"); return v;
}
__device__ __forceinline__ unsigned long long ld_acquire(const unsigned long long* p) {
    unsigned long long v; asm volatile("ld.acquire.gpu.global.u64 %0, [%1];" : "=l"(v) : "l"(p) : "memory"); return v;
}
__device__ __forceinline__ void st_b128(void* p, uint32_t a, uint32_t b, uint32_t c, uint32_t d) {
    asm volatile("{\n.reg .b128 v;\n.reg .b64 lo, hi;\nmov.b64 lo, {%1, %2};\nmov.b64 hi, {%3, %4};\nmov.b128 v, {lo, hi};\n"
                 "st.relaxed.gpu.global.b128 [%0], v;\n}\n" :: "l"(p), "r"(a), "r"(b), "r"(c), "r"(d) : "memory");
}
__device__ __forceinline__ void ld_b128(const void* p, uint32_t& a, uint32_t& b, uint32_t& c, uint32_t& d) {
    asm volatile("{\n.reg .b128 v;\n.reg .b64 lo, hi;\nld.relaxed.gpu.global.b128 v, [%4];\nmov.b128 {lo, hi}, v;\n"
                 "mov.b64 {%0, %1}, lo;\nmov.b64 {%2, %3}, hi;\n}\n" : "=r"(a), "=r"(b), "=r"(c), "=r"(d) : "l"(p) : "memory");
}
__device__ __forceinline__ void spin_guard(unsigned& n) {
    asm volatile("{\n.reg .pred P;\nadd.u32 %0, %0, 1;\nsetp.gt.u32 P, %0, 16777216;\n@P trap;\n}\n" : "+r"(n));
    if (n > 1) __nanosleep(100);
}
__device__ __forceinline__ void red_add(unsigned long long* p, unsigned long long v) {
    asm volatile("red.release.gpu.global.add.u64 [%0], %1;" :: "l"(p), "l"(v) : "memory");
}
__device__ __forceinline__ float rcp(float x) { float y; asm("rcp.approx.ftz.f32 %0, %1;" : "=f"(y) : "f"(x)); return y; }
__device__ __forceinline__ float lds_f32(uint32_t addr) {
    float v; asm volatile("ld.shared.f32 %0, [%1];" : "=f"(v) : "r"(addr) : "memory"); return v;
}
__device__ __forceinline__ void ldsm_x4(uint32_t (&r)[4], uint32_t addr) {
    asm volatile("ldmatrix.sync.aligned.m8n8.x4.shared.b16 {%0, %1, %2, %3}, [%4];"
                 : "=r"(r[0]), "=r"(r[1]), "=r"(r[2]), "=r"(r[3]) : "r"(addr) : "memory");
}
__device__ __forceinline__ void ldsm_x4_t(uint32_t (&r)[4], uint32_t addr) {
    asm volatile("ldmatrix.sync.aligned.m8n8.x4.trans.shared.b16 {%0, %1, %2, %3}, [%4];"
                 : "=r"(r[0]), "=r"(r[1]), "=r"(r[2]), "=r"(r[3]) : "r"(addr) : "memory");
}
__device__ __forceinline__ void mma_k16(float (&d)[4], const uint32_t (&a)[4], uint32_t b0, uint32_t b1) {
    asm("mma.sync.aligned.m16n8k16.row.col.f32.bf16.bf16.f32 {%0,%1,%2,%3}, {%4,%5,%6,%7}, {%8,%9}, {%0,%1,%2,%3};"
        : "+f"(d[0]), "+f"(d[1]), "+f"(d[2]), "+f"(d[3]) : "r"(a[0]), "r"(a[1]), "r"(a[2]), "r"(a[3]), "r"(b0), "r"(b1));
}
__device__ __forceinline__ void mma_k16_init(float (&d)[4], const uint32_t (&a)[4], uint32_t b0, uint32_t b1) {
    asm("{\n.reg .f32 z;\nmov.f32 z, 0f00000000;\n"
        "mma.sync.aligned.m16n8k16.row.col.f32.bf16.bf16.f32 {%0,%1,%2,%3}, {%4,%5,%6,%7}, {%8,%9}, {z,z,z,z};\n}\n"
        : "=f"(d[0]), "=f"(d[1]), "=f"(d[2]), "=f"(d[3]) : "r"(a[0]), "r"(a[1]), "r"(a[2]), "r"(a[3]), "r"(b0), "r"(b1));
}
__device__ __forceinline__ void mma_k8(float (&d)[4], uint32_t a0, uint32_t a1, uint32_t b0) {
    asm("mma.sync.aligned.m16n8k8.row.col.f32.bf16.bf16.f32 {%0,%1,%2,%3}, {%4,%5}, {%6}, {%0,%1,%2,%3};"
        : "+f"(d[0]), "+f"(d[1]), "+f"(d[2]), "+f"(d[3]) : "r"(a0), "r"(a1), "r"(b0));
}
template <typename T, int N> __device__ __forceinline__ void zero_regs(T (&d)[N]) {
#pragma unroll
    for (int i = 0; i < N; i++) d[i] = 0;
}
__device__ __forceinline__ float quad_max(float v) {
    v = fmaxf(v, __shfl_xor_sync(0xffffffffu, v, 1));
    return fmaxf(v, __shfl_xor_sync(0xffffffffu, v, 2));
}
__device__ __forceinline__ float quad_sum(float v) {
    v += __shfl_xor_sync(0xffffffffu, v, 1);
    return v + __shfl_xor_sync(0xffffffffu, v, 2);
}

__device__ __forceinline__ void qk_gemm(float (&s)[64], uint32_t q_lo, uint32_t k_lo) {
    const uint64_t dq = full_desc(q_lo), dk = full_desc(k_lo);
    fence_regs(s);
    wgmma_fence();
#pragma unroll
    for (int kk = 0; kk < 8; kk++) {
        const uint32_t o = (kk >> 2) * 1024 + (kk & 3) * 2;
        wgmma_ss_n128(s, dq + o, dk + o, kk != 0);
    }
    wgmma_commit();
}
__device__ __forceinline__ void pv_gemm(float (&o)[64], uint32_t (&p)[32], uint32_t v_lo, int accumulate) {
    const uint64_t dv = full_desc(v_lo);
    fence_regs(o);
    fence_regs(p);
    wgmma_fence();
#pragma unroll
    for (int kk = 0; kk < 8; kk++)
        wgmma_rs_n128_tb(o, p[4 * kk], p[4 * kk + 1], p[4 * kk + 2], p[4 * kk + 3], dv + kk * 128, kk != 0 || accumulate);
    wgmma_commit();
}
template <int NJ>
__device__ __forceinline__ void row_max(const float (&s)[64], float& x0, float& x1) {
    float z0 = fmaxf(s[0], s[1]), z1 = fmaxf(s[2], s[3]);
    x0 = fmaxf(s[4], s[5]); x1 = fmaxf(s[6], s[7]);
#pragma unroll
    for (int j = 2; j < NJ; j += 2) {
        z0 = fmaxf(z0, fmaxf(s[4 * j], s[4 * j + 1]));
        z1 = fmaxf(z1, fmaxf(s[4 * j + 2], s[4 * j + 3]));
        x0 = fmaxf(x0, fmaxf(s[4 * j + 4], s[4 * j + 5]));
        x1 = fmaxf(x1, fmaxf(s[4 * j + 6], s[4 * j + 7]));
    }
    x0 = quad_max(fmaxf(x0, z0)); x1 = quad_max(fmaxf(x1, z1));
}
__device__ __forceinline__ void exp_pack(uint32_t (&p)[32], const float (&s)[64], float n0, float n1, float& r0, float& r1) {
#pragma unroll
    for (int j = 0; j < 16; j++) {
        const float e0 = ex2(fmaf(s[4 * j], SM_SCALE, n0)), e1 = ex2(fmaf(s[4 * j + 1], SM_SCALE, n0));
        const float e2 = ex2(fmaf(s[4 * j + 2], SM_SCALE, n1)), e3 = ex2(fmaf(s[4 * j + 3], SM_SCALE, n1));
        if (j == 0) { r0 = e0 + e1; r1 = e2 + e3; }
        else { r0 += e0; r0 += e1; r1 += e2; r1 += e3; }
        p[2 * j] = pack_bf16(e0, e1);
        p[2 * j + 1] = pack_bf16(e2, e3);
    }
}
template <int J0>
__device__ __forceinline__ void mask_triangle(float (&s)[64], int thr) {
#pragma unroll
    for (int j = 0; j < 8; j++) {
        if (8 * j > thr) s[4 * (J0 + j)] = -INFINITY;
        if (8 * j + 1 > thr) s[4 * (J0 + j) + 1] = -INFINITY;
        if (j > 0 && 8 * j - 8 > thr) s[4 * (J0 + j) + 2] = -INFINITY;
        if (j > 0 && 8 * j - 7 > thr) s[4 * (J0 + j) + 3] = -INFINITY;
    }
}
__device__ __forceinline__ void causal_mask(float (&s)[64], int thr, int wg) {
    asm volatile("" : "+r"(thr));
    if (wg == 0) {
        mask_triangle<0>(s, thr);
#pragma unroll
        for (int j = 32; j < 64; j++) s[j] = -INFINITY;
    } else {
        mask_triangle<8>(s, thr - 64);
    }
}

__global__ void __cluster_dims__(2, 1, 1) __launch_bounds__(384, 1) fused_kernel(const __grid_constant__ Params prm) {
    extern __shared__ __align__(1024) uint8_t smem[];
    const uint32_t sb = smem_u32(smem), bars = sb + SM_BARS;
    const int warp = __shfl_sync(0xffffffffu, threadIdx.x >> 5, 0), lane = threadIdx.x & 31;

    const uint32_t rank = cluster_rank();
    const uint32_t bars0 = map_cta(bars, 0), bars_peer = map_cta(bars, rank ^ 1);

    auto first_item = [&]() -> int {
        uint32_t pair = blockIdx.x >> 1;
        asm volatile("" : "+r"(pair));
        return prm.items[pair] + item_row(prm.items[pair]) + rank;
    };
    if (threadIdx.x == 256) {
        for (int k = 0; k < 4; k++) mbar_init(bars + B_GFULL + 8 * k, 1);
        asm volatile("fence.mbarrier_init.release.cluster;" ::: "memory");
        fence_proxy_async_smem();
    }
    if (threadIdx.x == 128) {
        for (int i = 0; i < 4; i++) { mbar_init(bars + B_GEMPTY + 8 * i, 16); mbar_init(bars + B_XFREE + 8 * i, 1); }
        for (int i = 0; i < 6; i++) { mbar_init(bars + B_AFULL + 8 * i, 1); mbar_init(bars + B_AEMPTY + 8 * i, i < 2 ? 8 : 16); }
        for (int i = 0; i < 4; i++) { mbar_init(bars + B_SFULL + 8 * i, 4); mbar_init(bars + B_SEMPTY + 8 * i, 1); }
        for (int i = 0; i < QDEPTH; i++) { mbar_init(bars + B_IFULL + 8 * i, 1); mbar_init(bars + B_IEMPTY + 8 * i, 23); }
        mbar_init(bars + B_WANT, 2);
        for (int i = 0; i < 4; i++) mbar_init(bars + B_HALF + 8 * i, 1);
        mbar_init(bars + B_ALT, 4); mbar_init(bars + B_ALT + 8, 4); mbar_init(bars + B_QFREE, 2);
        asm volatile("st.shared.u64 [%0], 0;" :: "r"(bars + SM_ORDY) : "memory");
        asm volatile("fence.mbarrier_init.release.cluster;\nfence.acq_rel.cta;" ::: "memory");
    }
    __syncwarp();
    asm volatile("barrier.cluster.arrive.relaxed.aligned;" ::: "memory");
    if (threadIdx.x == 256) {
        const int first_it = first_item();
        for (int k = 0; k < 4; k++) {
            const uint32_t dst = sb + k * GST_BYTES, fb = bars + B_GFULL + 8 * k;
            mbar_expect_tx(fb, GST_BYTES);
            tma_load_3d(dst, &prm.m[M_X], fb, k * 64, item_row(first_it) * 128, 0);
            tma_load_3d(dst + 16384, &prm.m[M_WQKV], fb, 0, k * 64, item_col(first_it) * 4);
            tma_load_3d(dst + 32768, &prm.m[M_WQKV], fb, 0, k * 64, item_col(first_it) * 4 + 2);
        }
    }
    __syncwarp();
    asm volatile("barrier.cluster.wait.acquire.aligned;" ::: "memory");

    uint32_t qn = 0;
    auto next_item = [&](bool releaser, bool bounded = true) -> int {
        const uint32_t slot = qn % QDEPTH;
        if (bounded) mbar_wait(bars + B_IFULL + 8 * slot, (qn / QDEPTH) & 1);
        else mbar_spin(bars + B_IFULL + 8 * slot, (qn / QDEPTH) & 1);
        uint32_t it;
        asm volatile("ld.shared.u32 %0, [%1];" : "=r"(it) : "r"(bars + SM_QUEUE + 4 * slot) : "memory");
        mbar_arrive_cluster_if(releaser, bars0 + B_IEMPTY + 8 * slot);
        qn++;
        return it;
    };

    if (warp < 4) {
        reg_dec<40>();
        if (warp == 0) {
            {
                uint32_t gph = 0;
                const uint32_t prank = __shfl_sync(0xffffffffu, rank, 0);
                int k0 = 4;
                uint32_t kv = 0, kvph = 1;
                uint32_t qc = 0;
                uint32_t oneed = 0;
                uint32_t xph = 0;
                uint32_t need_g = 0, need_a = 0;
                auto a_parity = [&](uint32_t b) { return b < 2 ? (((qc + 1 - b) >> 1) & 1) ^ 1 : kvph ^ (b - 2 < kv); };
                int held_type = T_END;
                uint32_t borrowed = 0, fph = 0;
                auto reclaim_q = [&]() { if (borrowed) { mbar_wait(bars + B_QFREE, fph); fph ^= 1; borrowed = 0; } };
                auto acquire_g = [&](uint32_t st, bool shared) {
                    mbar_wait(bars + B_GEMPTY + 8 * st, gph);
                    if (need_a) {
                        reclaim_q();
                        const uint32_t b = (3 * st) >> 1;
                        mbar_wait(bars + B_AEMPTY + 8 * b, a_parity(b));
                        mbar_wait(bars + B_AEMPTY + 8 * (b + 1), a_parity(b + 1));
                        if (shared) {
                            mbar_arrive_cluster_if(lane == 0, bars_peer + B_XFREE + 8 * st);
                            mbar_wait(bars + B_XFREE + 8 * st, xph);
                        }
                        if (st == 3) { need_a = 0; xph ^= shared; }
                    }
                };
                auto leave_gemm = [&](uint32_t b) {
                    if (need_g >> b & 1) {
                        mbar_wait(bars + B_GEMPTY + 8 * ((2 * b) / 3), gph);
                        mbar_wait(bars + B_GEMPTY + 8 * ((2 * b + 1) / 3), gph);
                        need_g &= ~(1u << b);
                    }
                };
                const CUtensorMap* tile_map = &prm.m[M_SCR_LD];
                asm volatile("" : "+l"(tile_map));
                auto load_q = [&](int grp, int row) {
                    const uint32_t b = qc & 1, dst = sb + b * 32768, fb = bars + B_AFULL + 8 * b;
                    mbar_wait(bars + B_AEMPTY + 8 * b, a_parity(b));
                    leave_gemm(b);
                    reclaim_q();
                    borrowed = held_type != T_END;
                    held_type = T_END;
                    warp_expect_tx(fb, 32768 + 512);
                    warp_tma_load(dst, tile_map, fb, 0, row, grp);
                    warp_tma_load(dst + 16384, tile_map, fb, 64, row, grp);
                    warp_bulk_load(bars + SM_GATE + b * 512, &g_gate[row], 512, fb);
                    qc++;
                };
                auto load_kv = [&](int grp, int row, bool shared) {
                    uint32_t fb = bars + B_AFULL + 16 + 8 * kv, mine = sb + SM_KV + kv * 32768 + prank * 16384;
                    int c_mine = prank * 64;
                    asm volatile("" : "+r"(mine), "+r"(fb), "+r"(row), "+r"(grp), "+r"(c_mine));
                    if (need_g) leave_gemm(2 + kv);
                    mbar_wait(fb + B_AEMPTY - B_AFULL, kvph);
                    warp_expect_tx(fb, grp < 0 ? 0 : 32768);
                    if (shared) {
                        warp_tma_load_pair(mine, tile_map, fb, c_mine, row, grp);
                    } else if (grp >= 0) {
                        warp_tma_load(mine, tile_map, fb, c_mine, row, grp);
                        warp_tma_load(mine + 16384 - prank * 32768, tile_map, fb, 64 - c_mine, row, grp);
                    } else {
                        mbar_arrive_cluster_n_if(lane < 2, map_cta(fb, lane & 1) + B_AEMPTY - B_AFULL, 8);
                    }
                    if (++kv == 4) { kv = 0; kvph ^= 1; }
                };
                auto request = [&]() { mbar_arrive_cluster_if(lane == 0, bars0 + B_WANT); };
                int pv_grp = -1, pv_row = 0;
                bool pv_shared = false, peer_longer = false;
                auto inputs_seen = [&](uint32_t word, unsigned& n) -> uint32_t {
                    uint32_t v;
                    spin_guard(n);
                    asm volatile("ld.acquire.cta.shared.u32 %0, [%1];" : "=r"(v) : "r"(bars + SM_ORDY + 4 * word) : "memory");
                    return __shfl_sync(0xffffffffu, v, 0);
                };
                auto fetch = [&]() -> int {
                    const int nx = __shfl_sync(0xffffffffu, next_item(lane == 0), 0);
                    if ((item_type(nx) == T_ATTN || item_type(nx) == T_LOCAL) && !(nx & ITEM_READY)) {
                        oneed += 256;
                        for (unsigned n = 0; inputs_seen(1, n) < oneed;) {}
                    }
                    if (item_type(nx) == T_ATTN) load_q(G_Q + item_col(nx), item_row(nx) * 128);
                    return nx;
                };
                int nxt = first_item();
                while (true) {
                    const int it = nxt >= 0 ? nxt : fetch();
                    nxt = -1;
                    const int type = item_type(it), m = item_row(it), c = item_col(it);
                    const int asc = item_asc(it), nu = type == T_ATTN ? 2 * m + 2 : 0;
                    const int uend = nu + ((type == T_ATTN ? m < 2 : pv_grp >= 0) ? 3 : 0), ureq = 2 * max(m - 2 - (asc & m), 0);
#pragma unroll 1
                    for (int u = 0; u < uend; u++) {
                        int grp = pv_grp, row = pv_row;
                        bool shared = pv_shared;
                        if (u >= nu) {
                            if (u == nu + 1) pv_grp = -1;
                            else if (peer_longer) { grp = -1; shared = false; }
                            else continue;
                        } else {
                            const int j = asc ? u >> 1 : m - (u >> 1);
                            if (u & 1) {
                                pv_grp = G_V + c; pv_row = j * 128; pv_shared = j != (m | 1);
                                peer_longer = asc & ~m & 1;
                                if (u == nu - 1 && (m & 1) && item_type(nxt) == T_END) mbar_arrive_cluster_n_if(lane == 0, bars0 + B_WANT, 2);
                                if (grp < 0) continue;
                            } else {
                                if (u == ureq) request();
                                if (u == 2 * m && m > 0) nxt = fetch();
                                grp = G_K + c; row = j * 128; shared = j != (m | 1);
                            }
                        }
                        load_kv(grp, row, shared);
                    }
                    if (type == T_END) break;
                    if (type == T_ATTN) {
                        need_a = 1;
                    } else if (type == T_LOCAL) {
                        if (held_type == T_B && !(it & ITEM_READY)) held_type = T_END;
                        request();
#pragma unroll 1
                        for (uint32_t st = 0; st < 4; st++) {
                            acquire_g(st, false);
                            const uint32_t dst = sb + st * GST_BYTES, fb = bars + B_GFULL + 8 * st;
                            warp_expect_tx(fb, st == 0 ? 32768 + 512 : st == 3 ? 0 : 4 * LOC_PLANE);
                            if (st == 3) break;
                            if (st == 0) warp_bulk_load(dst + 4 * LOC_PLANE, &g_gate[m * 128], 512, fb);
#pragma unroll 1
                            for (int i = 0; i < 4; i++)
                                warp_tma_load(dst + i * LOC_PLANE, &prm.m[st ? M_SCR_LOC : M_SCR_LOQ], fb, i * 64, m * 64 - (st ? 8 : 0), G_B + 8 * st + c);
                        }
                        gph ^= 1;
                        need_g = 63;
                    } else {
                        const int nk = type == T_K || type == T_V ? 8 : 16;
                        const CUtensorMap* ma = &prm.m[nk == 8 ? M_C : M_X];
                        const CUtensorMap* mb = &prm.m[type == T_Q ? M_WQ : type == T_K ? M_WUK : type == T_V ? M_WUV : M_WQKV];
                        for (int k = k0; k < nk; k++) {
                            if (k == nk - 3) request();
                            const uint32_t st = k & 3;
                            uint32_t dst = sb + st * GST_BYTES, fb = bars + B_GFULL + 8 * st, dstb = dst + 16384 + prank * 16384;
                            int a0 = k * 64, a1 = m * 128, b2 = c * 4 + 2 * prank;
                            asm volatile("" : "+r"(dst), "+r"(fb), "+r"(dstb), "+r"(a0), "+r"(a1), "+r"(b2), "+l"(ma), "+l"(mb));
                            acquire_g(st, true);
                            warp_expect_tx(fb, GST_BYTES);
                            warp_tma_load(dst, ma, fb, a0, a1, 0);
                            warp_tma_load_pair(dstb, mb, fb, 0, a0, b2);
                            if (st == 3) gph ^= 1;
                        }
                        need_g = 63;
                        held_type = type;
                        k0 = 0;
                    }
                }
                if (!need_a) request();
                const int it = __shfl_sync(0xffffffffu, next_item(lane == 0), 0);
                int nk = 0;
                if (item_type(it) == T_OUT) {
                    const int m = item_row(it), c = item_col(it), half = c & 1;
                    nk = 80;
                    for (int k = 0; k < nk; k++) {
                        if (k == K_SPLIT) nk = 2 * TRIPLES + (__shfl_sync(0xffffffffu, next_item(lane == 0), 0) & 127);
                        const int kn = k + 2 * TRIPLES - nk, first = kn >= 0 && !(kn & 1);
                        const int s = kn >= 0 ? WIDE + (3 * kn + 1) / 2 : half ? WIDE - 1 - k : k;
                        const uint32_t sa = prm.ostep[s], sa2 = prm.ostep[s + first], sw = prm.ostep[s - (kn >= 0 && !first ? prank : 0)];
                        for (unsigned n = 0; !(inputs_seen(sa >> 6, n) >> (sa >> 1 & 31) & 1);) {}
                        if (first) for (unsigned n = 0; !(inputs_seen(sa2 >> 6, n) >> (sa2 >> 1 & 31) & 1);) {}
                        const uint32_t st = k & 3;
                        uint32_t dst = sb + st * GST_BYTES, fb = bars + B_GFULL + 8 * st;
                        uint32_t dstb = dst + 16384 + (first ? 0 : prank * 16384), skipb = first && (kn >> 1 & 1) != prank;
                        int a0 = (sa & 1) * 64, a1 = m * 128, a2 = (sa >> 1) + (sa < 64 ? G_CTX : G_LOC - 32);
                        int b1 = (sw & 63) * 64, b2 = (c >> 1) * 4 + 2 * (kn >= 0 ? half : half ^ prank);
                        const CUtensorMap* mb = &prm.m[sw >= 64 ? M_WOB : M_WO];
                        asm volatile("" : "+r"(dst), "+r"(fb), "+r"(dstb), "+r"(skipb), "+r"(a0), "+r"(a1), "+r"(a2), "+r"(b1), "+r"(b2), "+l"(mb));
                        acquire_g(st, true);
                        warp_expect_tx(fb, GST_BYTES);
                        warp_tma_load(dst, tile_map, fb, a0, a1, a2);
                        if (!skipb) warp_tma_load_pair(dstb, mb, fb, 0, b1, b2);
                        if (first) warp_tma_load(dst + 32768, tile_map, fb, (sa2 & 1) * 64, a1, (sa2 >> 1) + (sa2 < 64 ? G_CTX : G_LOC - 32));
                        if (k < K_SPLIT && lane == 0 && !prank)
                            asm volatile("st.relaxed.gpu.global.u32 [%0], %1;" :: "l"(&g_sync.step[0][0] + m * 4 + c), "r"(k) : "memory");
                        if (k == K_MEET) request();
                        if (PF_NAR && (uint32_t)(k - PF_NAR) < (3 * TRIPLES + 1) / 2) {
                            const uint32_t g = prm.ostep[79 - 2 * (k - PF_NAR)] >> 1;
                            warp_prefetch((const char*)g_scr + (uint32_t)((G_CTX + g) * (SEQ * 256) + m * 32768 + c * 4096), 4096);
                            warp_prefetch(prm.wo + (uint32_t)(g * 262144 + (m * 8 + c) * 2048), 2048);
                        }
                        if (st == 3) gph ^= 1;
                    }
                    for (unsigned n = 0; ~inputs_seen(0, n) || inputs_seen(1, n) != 255;) {}
                }
                for (uint32_t st = 0; st < 4; st++) { mbar_wait(bars + B_GEMPTY + 8 * st, gph ^ (st < (nk & 3))); mbar_wait(bars + B_AEMPTY + 16 + 8 * st, a_parity(2 + st)); }
                unsigned left = 0;
                if (lane == 0) left = atomicAdd(&g_sync.done, 1u);
                if (__shfl_sync(0xffffffffu, left, 0) == NCTA - 1)
                    for (int i = lane; i < sizeof(Sync) / 8; i += 32) ((unsigned long long*)&g_sync)[i] = 0;
            }
        } else if (warp <= 2) {
            if (blockIdx.x < SEQ / 16) {
                const uint32_t r0 = 16 * blockIdx.x + 8 * (warp - 1), gbuf = bars + SM_GATE + 4 * (r0 & 15);
                float z[4];
#pragma unroll 1
                for (uint32_t i = 0; i < 8; i++) {
                    const uint32_t off = (i & 3) * 512 + lane * 16;
                    const uint4* xp = (const uint4*)((const char*)prm.x + ((r0 + (i & 4)) * 2048 + off));
                    const uint4 wv = __ldg((const uint4*)((const char*)prm.gate_w + off));
                    uint4 xv[4];
#pragma unroll
                    for (int r = 0; r < 4; r++) { xv[r] = __ldg(xp + r * 128); if (!(i & 3)) z[r] = 0.f; }
                    const uint32_t ws[4] = {wv.x, wv.y, wv.z, wv.w};
#pragma unroll
                    for (int e = 0; e < 4; e++)
#pragma unroll
                        for (int r = 0; r < 4; r++) {
                            const uint32_t xs = e == 0 ? xv[r].x : e == 1 ? xv[r].y : e == 2 ? xv[r].z : xv[r].w;
                            z[r] = fmaf(__uint_as_float(xs << 16), __uint_as_float(ws[e] << 16), z[r]);
                            z[r] = fmaf(__uint_as_float(xs & 0xffff0000u), __uint_as_float(ws[e] & 0xffff0000u), z[r]);
                        }
                    if ((i & 3) == 3) {
#pragma unroll
                        for (int o = 16; o > 0; o >>= 1)
#pragma unroll
                            for (int r = 0; r < 4; r++) z[r] += __shfl_xor_sync(0xffffffffu, z[r], o);
                        const float zr = lane & 2 ? (lane & 1 ? z[3] : z[2]) : (lane & 1 ? z[1] : z[0]);
                        asm volatile("st.shared.f32 [%0], %1;" :: "r"(gbuf + 4 * ((i & 4) + (lane & 3))), "f"(1.f / (1.f + __expf(-zr))) : "memory");
                    }
                }
                fence_proxy_async_smem();
                __syncwarp();
                warp_bulk_store((char*)g_gate + 4 * r0, gbuf, 32);
                bulk_commit();
                bulk_wait<0>();
                __syncwarp();
                if (lane == 0) red_add(&g_sync.count[3], 1);
            }
            __syncwarp();
            {
                const int w = warp - 1;
                uint32_t sph = 0, aph = 0, nann = 0, nattn = 0;
                int unsent = 0, nunsent = 0;
                bool urgent = false;
                auto announce = [&]() {
                    if (!urgent) return;
                    bulk_wait<0>();
                    __syncwarp();
                    const uint32_t hb = bars + B_HALF + 8 * (nann & 3);
                    if (w == 0) {
                        mbar_arrive_if(lane == 0, hb);
                    } else {
                        mbar_wait(hb, (nann >> 2) & 1);
                        const uint32_t type = item_type(unsent), m = item_row(unsent), c = item_col(unsent);
                        const uint32_t word = type < T_B ? c >> 3 : type == T_B ? 2 : offsetof(Sync, ctx) / 8 + m;
                        const uint32_t bit = type < T_B ? 8 * (c & 7) : type == T_B ? 4 * m : type == T_LOCAL ? 32 + c : c;
                        if (lane < nunsent) red_add((unsigned long long*)((char*)&g_sync + 8 * word), 1ull << bit);
                        __syncwarp();
                    }
                    nann++;
                    nunsent = 0; urgent = false;
                };
                auto store_item = [&](int it, bool borrow, bool now) {
                    const int type = item_type(it), m = item_row(it), c = item_col(it);
                    const int npair = type < T_OUT ? 2 : 1;
                    const bool local = type == T_LOCAL;
                    const int grp = type == T_Q ? G_Q + 2 * c : type == T_K ? G_K + 2 * c : type == T_V ? G_V + 2 * c : type == T_B ? G_B + 2 * c
                                  : type == T_ATTN ? G_CTX + c : G_LOC + c;
                    for (int pr = 0; pr < npair; pr++) {
                        if (borrow && pr) {
                            mbar_wait(bars + B_ALT + 8 * w, aph);
                            aph ^= 1;
                            for (int b = 0; b < 2; b++)
                                warp_tma_store(&prm.m[M_SCR_ST], sb + ((nattn & 1) ^ 1) * 32768 + w * 16384 + b * 8192, b * 64, m * 128 + w * 64, grp + 1);
                            bulk_commit();
                            bulk_wait_read<0>();
                            __syncwarp();
                            mbar_arrive_if(lane == 0, bars + B_QFREE);
                            break;
                        }
                        for (int b = 0; b < 2; b++) {
                            if (!__all_sync(0xffffffffu, mbar_test(bars + B_SFULL + 16 * w + 8 * b, sph))) announce();
                            mbar_wait(bars + B_SFULL + 16 * w + 8 * b, sph);
                            warp_tma_store(&prm.m[local ? M_SCR_LOQ : M_SCR_ST], sb + SM_STAGING + w * 16384 + b * 8192,
                                         local ? b * 128 + w * 64 : b * 64, local ? m * 64 : m * 128 + w * 64, grp + pr);
                            bulk_commit();
                            bulk_wait_read<0>();
                            __syncwarp();
                            mbar_arrive_if(lane == 0, bars + B_SEMPTY + 16 * w + 8 * b);
                        }
                        sph ^= 1;
                    }
                    announce();
                    if (lane == nunsent) unsent = it;
                    nunsent++;
                    urgent = now || nunsent == 32 || !local;
                };
                int held = first_item();
                while (true) {
                    if (!__all_sync(0xffffffffu, mbar_test(bars + B_IFULL + 8 * (qn % QDEPTH), (qn / QDEPTH) & 1))) announce();
                    const int it = __shfl_sync(0xffffffffu, next_item(lane == 0), 0), type = item_type(it);
                    const bool keep_held = type == T_LOCAL && (item_type(held) != T_B || (it & ITEM_READY));
                    if (type >= T_ATTN && held < 0 && nunsent) urgent = true;
                    for (int pass = held < 0 || keep_held; pass < 2; pass++) {
                        if (pass && (type < T_OUT || type == T_END)) break;
                        store_item(pass ? it : held, !pass && type == T_ATTN, type >= T_ATTN);
                    }
                    if (type == T_END) break;
                    nattn += type == T_ATTN;
                    if (!keep_held) held = type < T_OUT ? it : -1;
                }
                announce();
                if (item_type(next_item(lane == 0)) == T_OUT) next_item(lane == 0);
            }
        } else {
            if (elect_one()) {
                uint32_t ordy = 0;
                unsigned long long cnt_lo = 0, cnt_hi = 0;
                int late = 0;
                auto refresh = [&]() {
                    if (!late && cnt_lo == 0xccccccccccccccccull && cnt_hi == SEQ / 8) late = 1;
                    asm volatile("ld.acquire.gpu.global.v2.u64 {%0, %1}, [%2];" : "=l"(cnt_lo), "=l"(cnt_hi) : "l"(late ? &g_sync.count[0] : &g_sync.count[2]) : "memory");
                };
                auto inputs_ready = [&](int it) -> bool {
                    const int m = item_row(it), c = item_col(it);
                    if (item_type(it) == T_ATTN) return late && ((c < 16 ? cnt_lo : cnt_hi) >> (4 * (c & 14)) & 255) == 48;
                    return late || (cnt_hi == SEQ / 8 && (cnt_lo >> (4 * m) & 15) == 12 && (cnt_lo >> (4 * max(m - 1, 0)) & 15) == 12);
                };
                auto publish = [&](int it, int step) {
                    const uint32_t slot = qn % QDEPTH;
                    mbar_wait(bars + B_IEMPTY + 8 * slot, ((qn / QDEPTH) & 1) ^ 1);
                    for (uint32_t r = 0; r < 2; r++) {
                        const uint32_t rb = map_cta(bars, r);
                        asm volatile("mbarrier.arrive.expect_tx.shared::cluster.b64 _, [%0], 4;" :: "r"(rb + B_IFULL + 8 * slot) : "memory");
                        asm volatile("st.async.shared::cluster.mbarrier::complete_tx::bytes.u32 [%0], %1, [%2];"
                                     :: "r"(rb + SM_QUEUE + 4 * slot), "r"(it + r * step), "r"(rb + B_IFULL + 8 * slot) : "memory");
                    }
                    qn++;
                };
                int asc = 1;
                int it;
                do {
                    if (rank == 0) {
                        mbar_wait(bars + B_WANT, qn & 1);
                        unsigned i;
                        asm volatile("atom.relaxed.gpu.global.add.u32 %0, [%1], 1;" : "=r"(i) : "l"(&g_sync.next) : "memory");
                        if (cnt_lo != 0x3030303030303030ull || cnt_hi != cnt_lo) refresh();
                        i += NPAIR;
                        const int pit = i < NITEMS ? prm.items[i] : T_END << 13, type = item_type(pit);
                        int step = type == T_LOCAL ? 16 : 1;
                        it = pit + (pit & (step == 1 ? 15 : 0x1f0));
                        if (type == T_ATTN) {
                            if (!asc) { it += 1; step = -1; }
                            it |= asc << 9;
                        }
                        asc = type != T_ATTN || item_row(pit) == 0 || !asc;
                        if (inputs_ready(it)) it |= ITEM_READY;
                        publish(it, step);
                    } else {
                        it = next_item(true);
                    }
                    if ((item_type(it) == T_ATTN || item_type(it) == T_LOCAL) && !(it & ITEM_READY)) {
                        unsigned n = 0;
                        while (!inputs_ready(it)) { refresh(); spin_guard(n); }
                        asm volatile("st.release.cta.shared.u32 [%0], %1;" :: "r"(bars + SM_ORDY + 4), "r"(ordy += 256) : "memory");
                    }
                } while (item_type(it) != T_END);
                if (PF_LOC && blockIdx.x < 128) {
                    prefetch_l2((const char*)g_scr + (uint32_t)(G_LOC * SEQ * 256 + blockIdx.x * 32768), 32768);
                    prefetch_l2(prm.wob + blockIdx.x * 16384, 16384);
                }
                if (rank == 0) {
                    mbar_wait(bars + B_WANT, qn & 1);
                    const unsigned i = atomicAdd(&g_sync.next_out, 1u), t = i < 32 ? 31 - i : i - 32;
                    it = i < 64 ? T_OUT << 13 | ((t & 3) * 2 + (i >> 5)) << 4 | (t >> 2) * 2 : T_END << 13;
                    publish(it, 1);
                } else {
                    it = next_item(true);
                }
                if (item_type(it) == T_OUT) {
                    const uint32_t m = item_row(it), half = item_col(it) & 1, tile = m * 2 + (item_col(it) >> 1);
                    unsigned* split = (unsigned*)((char*)g_sync.split + 4 * tile);
                    unsigned long long rdy = 0;
                    int state = rank ? 2 : 0;
                    for (unsigned n = 0; rdy != 0xffffffffffull || state < 2; spin_guard(n)) {
                        if (rdy != 0xffffffffffull) {
                            rdy = ld_acquire((const unsigned long long*)((char*)g_sync.ctx + 8 * m));
                            asm volatile("st.release.cta.shared.u64 [%0], %1;" :: "r"(bars + SM_ORDY), "l"(rdy) : "memory");
                        }
                        unsigned steps = 0;
                        if (state == 1) {
                            steps = ld_acquire(split);
                        } else if (state == 0 && mbar_test(bars + B_WANT, qn & 1)) {
                            state = 1;
                            unsigned seen;
                            asm volatile("atom.acq_rel.gpu.global.exch.b32 %0, [%1], 1;" : "=r"(seen) : "l"(split) : "memory");
                            if (seen) {
                                const unsigned long long v = ld_acquire((const unsigned long long*)((char*)g_sync.step + 8 * tile));
                                const int d = (int)(v >> 32) - (int)v;
                                steps = (WIDE + min(max(half ? d : -d, K_MEET - K_SPLIT), K_SPLIT - K_MEET)) >> 1;
                                atomicExch(split, WIDE - steps);
                            }
                        }
                        if (steps > 1) { publish(T_END << 13 | steps, 0); state = 2; PMARK(1, 0xF400 + steps); }
                    }
                    if (rank) next_item(true);
                }
                if (rank == 0) for (uint32_t n = qn; n < qn + QDEPTH; n++) mbar_wait(bars + B_IEMPTY + 8 * (n % QDEPTH), ((n / QDEPTH) & 1) ^ 1);
            }
        }
    } else {
        reg_inc<232>();
        const int wg = (warp >> 2) - 1, wq = warp & 3;
        uint32_t gph = 0;
        uint32_t kvn = 0;
        const uint32_t dA = make_desc(sb + wg * 8192, 16);
        uint32_t ti = 0;
        uint32_t sph = 1;
        const uint32_t stg = sb + SM_STAGING + wg * 16384;
        const uint32_t stg_lane = stg + (wq * 16 + (lane & 15)) * 128 + (((lane >> 4) ^ (lane & 7)) << 4);
        auto write_blocks = [&](auto n, uint32_t off, const uint32_t* v) {
            uint32_t a = stg_lane;
            asm volatile("" : "+r"(a));
            a += off;
#pragma unroll
            for (int j = 0; j < decltype(n)::value; j++)
                stmatrix_x4((a ^ (32 * (j & 3))) + (j >> 2) * 8192, v[4 * j], v[4 * j + 1], v[4 * j + 2], v[4 * j + 3]);
        };
        auto release = [&](uint32_t bar) { mbar_arrive_if(lane == 0, bars + bar); };
        const uint32_t bars_lane = map_cta(bars, lane & 1);
        auto release_stage = [&](uint32_t st) { mbar_arrive_cluster_if(lane < 2, bars_lane + B_GEMPTY + 8 * st); };
        auto take_item = [&]() -> int {
            return __shfl_sync(0xffffffffu, next_item(lane == 0, false), 0);
        };
        auto stage_acquire = [&](int b) { mbar_spin(bars + B_SEMPTY + 16 * wg + 8 * b, sph); };
        auto stage_publish = [&](int b) {
            fence_proxy_async_smem();
            __syncwarp();
            release(B_SFULL + 16 * wg + 8 * b);
        };
        auto stage_chunk = [&](int b, const uint32_t* v) {
            stage_acquire(b);
            write_blocks(std::integral_constant<int, 4>(), b * 8192, v);
            stage_publish(b);
            if (b) sph ^= 1;
        };
        auto stage_pair = [&](const uint32_t* v) {
            stage_acquire(0); stage_acquire(1);
            write_blocks(std::integral_constant<int, 8>(), 0, v);
            fence_proxy_async_smem();
            __syncwarp();
            mbar_arrive_if(lane < 2, bars + B_SFULL + 16 * wg + 8 * lane);
            sph ^= 1;
        };
        auto gemm_step = [&](float (&acc)[128], uint32_t dB, int& k) {
            const uint32_t st = k & 3;
            wgmma_wait<0>();
            release_stage((k - 1) & 3);
            mbar_spin(bars + B_GFULL + 8 * st, gph);
            const uint64_t da = full_desc(dA + st * (GST_BYTES >> 4)), db = full_desc(dB + st * (GST_BYTES >> 4));
            wgmma_fence();
#pragma unroll
            for (int kk = 0; kk < 4; kk++) wgmma_ss_n256_tb(acc, da + 2 * kk, db + 128 * kk, 1);
            wgmma_commit();
            gph ^= st == 3;
            k++;
        };
        if (wg == 1) bar_arrive(1, 256);
        int it = first_item();
        while (item_type(it) != T_END) {
            if (item_type(it) <= T_LOCAL) {
                float acc[128];
                uint32_t pk[64];
                bool pending = false;
                bool held_b = false;
                zero_regs(pk);
                const uint32_t dB = make_desc(sb + 16384, 8192);
                do {
                    const int type = item_type(it);
                    if (type == T_LOCAL) {
                        int ln = lane;
                        asm volatile("" : "+r"(ln));
                        const int g = ln >> 2, t = ln & 3, par = wq & 1;
                        const uint32_t hc = (wq >> 1) * 4, pl = sb + (par * 2 + wg) * LOC_PLANE;
                        const uint32_t a16 = (ln & 15) * 128 + (((hc + (ln >> 4)) ^ (ln & 7)) << 4), a8 = (ln & 7) * 128 + (((hc + (ln >> 3)) ^ (ln & 7)) << 4);
                        const bool first0 = 2 * t > g, first1 = 2 * t + 1 > g;
                        const uint32_t fmask = (first0 ? 0xffffu : 0u) | (first1 ? 0xffff0000u : 0u);
                        const bool edge = item_row(it) == 0;
                        uint32_t q[4][2][4], kf[9][4], vf[9][4];
                        float w[8];
                        mbar_spin(bars + B_GFULL, gph);
#pragma unroll
                        for (int u = 0; u < 4; u++) { ldsm_x4(q[u][0], pl + u * 2048 + a16); ldsm_x4(q[u][1], pl + u * 2048 + (a16 ^ 32)); }
#pragma unroll
                        for (int j = 0; j < 8; j++) w[j] = lds_f32(sb + 4 * LOC_PLANE + 4 * (2 * g + par) + 64 * j);
                        __syncwarp();
                        release_stage(0);
                        mbar_spin(bars + B_GFULL + 8, gph);
#pragma unroll
                        for (int n = 0; n < 9; n++) ldsm_x4(kf[n], pl + GST_BYTES + n * 1024 + a8);
                        __syncwarp();
                        release_stage(1);
                        float s[8][2];
#pragma unroll
                        for (int u = 0; u < 4; u++) {
                            float d[3][4];
#pragma unroll
                            for (int nt = 0; nt < 3; nt++) {
                                mma_k16_init(d[nt], q[u][0], kf[2 * u + nt][0], kf[2 * u + nt][1]);
                                mma_k16(d[nt], q[u][1], kf[2 * u + nt][2], kf[2 * u + nt][3]);
                            }
                            if (u == 0 && edge) { d[0][0] = -INFINITY; d[0][1] = -INFINITY; }
                            s[2 * u][0] = first0 ? d[0][0] : d[1][0]; s[2 * u][1] = first1 ? d[0][1] : d[1][1];
                            s[2 * u + 1][0] = first0 ? d[1][2] : d[2][2]; s[2 * u + 1][1] = first1 ? d[1][3] : d[2][3];
                        }
                        mbar_spin(bars + B_GFULL + 16, gph);
#pragma unroll
                        for (int u = 0; u < 4; u++) { ldsm_x4_t(vf[2 * u], pl + 2 * GST_BYTES + u * 2048 + a16); ldsm_x4_t(vf[2 * u + 1], pl + 2 * GST_BYTES + u * 2048 + (a16 ^ 32)); }
                        ldsm_x4_t(vf[8], pl + 2 * GST_BYTES + 8192 + a8);
                        __syncwarp();
                        release_stage(2);
                        float x[8];
#pragma unroll
                        for (int j = 0; j < 8; j++) x[j] = fmaxf(s[j][0], s[j][1]);
#pragma unroll
                        for (int o = 1; o < 4; o *= 2)
#pragma unroll
                            for (int j = 0; j < 8; j++) x[j] = fmaxf(x[j], __shfl_xor_sync(0xffffffffu, x[j], o));
#pragma unroll
                        for (int j = 0; j < 8; j++) {
                            const float n = x[j] * -LOC_SCALE;
                            s[j][0] = ex2(fmaf(s[j][0], LOC_SCALE, n)); s[j][1] = ex2(fmaf(s[j][1], LOC_SCALE, n));
                            x[j] = s[j][0] + s[j][1];
                        }
#pragma unroll
                        for (int o = 1; o < 4; o *= 2)
#pragma unroll
                            for (int j = 0; j < 8; j++) x[j] += __shfl_xor_sync(0xffffffffu, x[j], o);
                        mbar_spin(bars + B_GFULL + 24, gph);
                        release_stage(3);
                        it = take_item();
                        uint32_t ob[4][8];
#pragma unroll
                        for (int u = 0; u < 4; u++) {
                            const float r0 = rcp(x[2 * u]), r1 = rcp(x[2 * u + 1]), f0 = fmaf(-w[2 * u], r0, r0), f1 = fmaf(-w[2 * u + 1], r1, r1);
                            const uint32_t p0 = pack_bf16(s[2 * u][0] * f0, s[2 * u][1] * f0), p1 = pack_bf16(s[2 * u + 1][0] * f1, s[2 * u + 1][1] * f1);
                            const uint32_t pa[4] = {p0 & fmask, 0, p0 & ~fmask, p1 & fmask};
#pragma unroll
                            for (int c = 0; c < 4; c++) {
                                float ol[4];
                                mma_k16_init(ol, pa, vf[2 * u + (c >> 1)][2 * (c & 1)], vf[2 * u + (c >> 1)][2 * (c & 1) + 1]);
                                mma_k8(ol, 0, p1 & ~fmask, u < 3 ? vf[2 * u + 2 + (c >> 1)][2 * (c & 1)] : vf[8][c]);
                                ob[u][2 * c] = pack_bf16(ol[0], ol[1]);
                                ob[u][2 * c + 1] = pack_bf16(ol[2], ol[3]);
                            }
                        }
                        stage_acquire(0); stage_acquire(1);
#pragma unroll
                        for (int u = 0; u < 4; u++) {
                            stmatrix_x4(stg + par * 8192 + u * 2048 + a16, ob[u][0], ob[u][1], ob[u][2], ob[u][3]);
                            stmatrix_x4(stg + par * 8192 + u * 2048 + (a16 ^ 32), ob[u][4], ob[u][5], ob[u][6], ob[u][7]);
                        }
                        fence_proxy_async_smem();
                        __syncwarp();
                        mbar_arrive_if(lane < 2, bars + B_SFULL + 16 * wg + 8 * lane);
                        bar_sync(4, 256);
                        sph ^= 1; gph ^= 1;
                        continue;
                    }
                    mbar_spin(bars + B_GFULL, gph);
                    bool more;
                    do {
                        wgmma_fence();
                        wgmma_ss_n256_tb_init(acc, full_desc(dA), full_desc(dB));
#pragma unroll
                        for (int kk = 1; kk < 4; kk++) wgmma_ss_n256_tb(acc, full_desc(dA) + 2 * kk, full_desc(dB) + 128 * kk, 1);
                        wgmma_commit();
                        const int nk = item_type(it) == T_K || item_type(it) == T_V ? 8 : 16;
                        int k = 1;
                        do {
                            if (pending) {
                                const int kf = k - 1 - wg;
                                if (kf == 0) stage_chunk(0, pk);
                                else if (kf == 1) stage_chunk(1, pk + 16);
                                else if (kf == KF2) stage_chunk(0, pk + 32);
                                else if (kf == KF2 + 1) stage_chunk(1, pk + 48);
                            }
                            gemm_step(acc, dB, k);
                        } while (k < nk);
                        held_b = item_type(it) == T_B;
                        it = take_item();
                        more = item_type(it) < T_LOCAL;
                        if (more) mbar_spin(bars + B_GFULL, gph);
                        wgmma_wait<0>();
                        fence_regs(acc);
                        release_stage(3);
#pragma unroll
                        for (int j = 0; j < 64; j++) pk[j] = pack_bf16(acc[2 * j], acc[2 * j + 1]);
                        pending = true;
                    } while (more);
                } while (item_type(it) < T_LOCAL || (item_type(it) == T_LOCAL && (!held_b || (it & ITEM_READY))));
                if (pending) { stage_chunk(0, pk); stage_chunk(1, pk + 16); }
                if (pending && item_type(it) == T_ATTN) {
                    mbar_spin(bars + B_GEMPTY, gph ^ 1); mbar_spin(bars + B_GEMPTY + 8, gph ^ 1);
                    write_blocks(std::integral_constant<int, 8>(), ((ti & 1) ^ 1) * 32768 - SM_STAGING, pk + 32);
                    fence_proxy_async_smem();
                    __syncwarp();
                    release(B_ALT + 8 * wg);
                } else if (pending) {
                    stage_chunk(0, pk + 32); stage_chunk(1, pk + 48);
                }
            } else {
                float o[64], s[64];
                uint32_t pa[32], pb[32];
                zero_regs(o); zero_regs(s); zero_regs(pa);
                float n0 = 0.f, n1 = 0.f;
                float l0 = 1.f, l1 = 1.f, f0 = 0.f, f1 = 0.f, g0 = 0.f, g1 = 0.f;
                uint32_t has_pv = 0;
                int first = 0;
                int pending = 0;
                const uint32_t dK = make_desc(sb + SM_KV, 16), dV = make_desc(sb + SM_KV, 16384);
                const uint32_t lane_off = bars_lane - bars + B_AEMPTY - B_AFULL;
                int cur = 0;
                uint32_t qoff = 0;
                const int row = wg * 64 + wq * 16 + (lane >> 2), thr = row - (lane & 3) * 2;
                auto kv_wait = [&](uint32_t n) { mbar_spin(bars + B_AFULL + 16 + 8 * (n & 3), (n >> 2) & 1); };
                auto kv_release = [&](uint32_t n) { mbar_arrive_cluster_if(lane < 2, bars_lane + B_AEMPTY + 16 + 8 * (n & 3)); };
                struct Slot { uint32_t bar, par, off; } slot[4];
                auto align = [&]() {
#pragma unroll
                    for (uint32_t i = 0; i < 4; i++) {
                        const uint32_t n = kvn + (i == 1 ? has_pv : i);
                        slot[i].bar = bars + B_AFULL + 16 + 8 * (n & 3); slot[i].par = (n >> 2) & 1; slot[i].off = (n & 3) * 2048;
                    }
                };
                align();
                auto pack_o = [&](uint32_t (&v)[32]) {
#pragma unroll
                    for (int j = 0; j < 16; j++) {
                        v[2 * j] = pack_bf16(o[4 * j] * f0, o[4 * j + 1] * f0);
                        v[2 * j + 1] = pack_bf16(o[4 * j + 2] * f1, o[4 * j + 3] * f1);
                    }
                };
                auto scales = [&]() { f0 = g0 * rcp(quad_sum(l0)); f1 = g1 * rcp(quad_sum(l1)); };
                auto step = [&](auto even, uint32_t (&pin)[32], uint32_t (&pout)[32], bool fresh, bool diag) {
                    constexpr bool EVEN = decltype(even)::value;
                    Slot& sk = slot[EVEN ? 0 : 2];
                    Slot& sv = slot[EVEN ? 1 : 3];
                    kvn += EVEN ? 1 + has_pv : 2;
                    mbar_spin(sk.bar, sk.par);
                    bar_sync(1 + wg, 256);
                    qk_gemm(s, dA + qoff, dK + sk.off);
                    if (EVEN && fresh) scales();
                    if (!EVEN && pending) { pack_o(pout); stage_pair(pout); }
                    mbar_spin(sv.bar, sv.par);
                    pv_gemm(o, pin, dV + sv.off, EVEN || !first);
                    bar_arrive(2 - wg, 256);
                    sk.par ^= 1; sv.par ^= 1;
                    wgmma_wait<1>();
                    fence_regs(s);
                    mbar_arrive_cluster_if(lane < 2 && (!EVEN || has_pv), sk.bar + lane_off);
                    if (diag) causal_mask(s, thr, wg);
                    if (EVEN && fresh) {
                        row_max<2>(s, n0, n1);
                        n0 *= -SM_SCALE; n1 *= -SM_SCALE;
                        l0 = 0.f; l1 = 0.f;
                    }
                    float r0, r1;
                    exp_pack(pout, s, n0, n1, r0, r1);
                    if (__any_sync(0xffffffffu, fmaxf(r0, r1) >= SUM_LIMIT)) {
                        float x0, x1;
                        row_max<16>(s, x0, x1);
                        x0 = fminf(x0 * -SM_SCALE, n0); x1 = fminf(x1 * -SM_SCALE, n1);
                        float a0 = ex2(x0 - n0), a1 = ex2(x1 - n1);
                        n0 = x0; n1 = x1;
                        l0 *= a0; l1 *= a1;
                        if (EVEN && fresh) { a0 = 1.f; a1 = 1.f; }
                        wgmma_wait<0>();
                        fence_regs(o);
#pragma unroll
                        for (int q = 0; q < 16; q++) { o[4 * q] *= a0; o[4 * q + 1] *= a0; o[4 * q + 2] *= a1; o[4 * q + 3] *= a1; }
                        exp_pack(pout, s, n0, n1, r0, r1);
                    }
                    l0 += r0; l1 += r1;
                    wgmma_wait<0>();
                    fence_regs(o);
                    fence_regs(pin);
                    mbar_arrive_cluster_if(lane < 2, sv.bar + lane_off);
                };
                auto copy_p = [&]() {
#pragma unroll
                    for (int j = 0; j < 32; j++) pa[j] = pb[j] ^ prm.zero;
                };
                int rem = 0;
                while (true) {
                    const bool fresh = rem == 0;
                    if (fresh) {
                        if (has_pv) {
                            release(B_AEMPTY + 8 * ((ti - 1) & 1));
                            it = take_item();
                            if (item_row(cur) < 2 || item_type(it) != T_ATTN) break;
                        }
                        cur = it;
                        qoff = (ti & 1) * 2048;
                        mbar_spin(bars + B_AFULL + 8 * (ti & 1), (ti >> 1) & 1);
                    }
                    step(std::true_type(), pa, pb, fresh, fresh ? !item_asc(cur) || item_row(cur) == 0 : item_asc(cur) && rem == 1);
                    first = fresh;
                    if (fresh) {
                        pending = has_pv; has_pv = 1;
                        if (!pending) { kvn -= 2; align(); kvn += 2; slot[0].par ^= 1; slot[1].par ^= 1; }
                        rem = item_row(cur);
                        g0 = lds_f32(bars + SM_GATE + (ti & 1) * 512 + 4 * row); g1 = lds_f32(bars + SM_GATE + (ti & 1) * 512 + 4 * row + 32);
                        ti++;
                        if (rem == 0) {
                            copy_p();
                            continue;
                        }
                    } else if (--rem == 0) {
                        copy_p();
                        align();
                        continue;
                    }
                    step(std::false_type(), pb, pa, false, item_asc(cur) && rem == 1);
                    pending = 0; first = 0;
                    rem--;
                }
                const uint32_t skip = item_asc(cur) & ~item_row(cur) & 1;
                kvn += skip;
#pragma unroll 1
                for (int pass = pending ? 0 : 1; pass < 2; pass++) {
                    if (pass) {
                        kv_wait(kvn);
                        pv_gemm(o, pa, dV + (kvn & 3) * 2048, !first);
                        scales();
                        wgmma_wait<0>();
                        fence_regs(o);
                        kv_release(kvn);
                        kvn += 1 + skip;
                    }
                    pack_o(pb);
                    stage_pair(pb);
                }
            }
        }
        it = take_item();
        if (item_type(it) == T_OUT) {
            float acc[128];
            const uint32_t dB = make_desc(sb + 16384, 8192);
            mbar_spin(bars + B_GFULL, gph);
            wgmma_fence();
            wgmma_ss_n256_tb_init(acc, full_desc(dA), full_desc(dB));
#pragma unroll
            for (int kk = 1; kk < 4; kk++) wgmma_ss_n256_tb(acc, full_desc(dA) + 2 * kk, full_desc(dB) + 128 * kk, 1);
            wgmma_commit();
            uint32_t ln;
            asm volatile("mov.u32 %0, %%laneid;" : "=r"(ln));
            const uint32_t slot = (it & 127) * 32768 + (wg * 128 + wq * 32 + ln) * 16;
            char* const mine = (char*)g_part + slot;
            int k = 1, nk = 80;
            do {
                if (k == K_MEET - 5) {
#pragma unroll
                    for (int j = 0; j < 8; j++) st_b128(mine + j * 4096, 0, 0, 0, 0);
                    __syncwarp();
                }
                if (k == K_SPLIT) nk = take_item() & 127;
                gemm_step(acc, dB, k);
            } while (k < nk);
            auto triple = [&](uint32_t nrel) {
                const uint32_t s0 = k & 3, s1 = (k + 1) & 3, o0 = s0 * (GST_BYTES >> 4), o1 = s1 * (GST_BYTES >> 4);
                wgmma_wait<0>();
                mbar_arrive_cluster_if(ln < nrel, bars_lane + B_GEMPTY + 8 * ((k - 1 - (ln >> 1)) & 3));
                mbar_spin(bars + B_GFULL + 8 * s0, gph);
                gph ^= s0 == 3;
                wgmma_fence();
#pragma unroll
                for (int kk = 0; kk < 4; kk++) wgmma_ss_n128_lo_tb(acc, full_desc(dA + o0) + 2 * kk, full_desc(dB + o0) + 128 * kk, 1);
                mbar_spin(bars + B_GFULL + 8 * s1, gph);
                gph ^= s1 == 3;
                wgmma_fence();
#pragma unroll
                for (int kk = 0; kk < 4; kk++) wgmma_ss_n128_lo_tb(acc, full_desc(dA + o0 + 2048) + 2 * kk, full_desc(dB + o1 + 1024) + 128 * kk, 1);
#pragma unroll
                for (int kk = 0; kk < 4; kk++) wgmma_ss_n128_lo_tb(acc, full_desc(dA + o1) + 2 * kk, full_desc(dB + o1) + 128 * kk, 1);
                wgmma_commit();
                k += 2;
            };
            triple(2);
#pragma unroll
            for (int j = 0; j < 8; j++) {
                uint32_t v[4];
#pragma unroll
                for (int i = 0; i < 4; i++) {
                    asm volatile("" : "+f"(acc[64 + 8 * j + 2 * i]), "+f"(acc[65 + 8 * j + 2 * i]) :: "memory");
                    v[i] = pack_bf16(acc[64 + 8 * j + 2 * i], acc[65 + 8 * j + 2 * i]);
                }
                if (j == SPREAD) triple(4);
                else if (PACE && j) __nanosleep(PACE);
                st_b128(mine + j * 4096, ~v[0], v[1], v[2], v[3]);
            }
#pragma unroll 1
            for (int t = 2; t < TRIPLES; t++) triple(4);
            uint32_t pk[32];
            char* const other = (char*)g_part + (slot ^ (16 * 32768));
            while (true) {
                bool miss = false;
#pragma unroll
                for (int j = 0; j < 8; j++) ld_b128(other + j * 4096, pk[4 * j], pk[4 * j + 1], pk[4 * j + 2], pk[4 * j + 3]);
#pragma unroll
                for (int j = 0; j < 8; j++) miss |= pk[4 * j] == 0;
                if (!__any_sync(0xffffffffu, miss)) break;
                while (__any_sync(0xffffffffu, pk[28] == 0)) ld_b128(other + 7 * 4096, pk[28], pk[29], pk[30], pk[31]);
            }
#pragma unroll
            for (int j = 0; j < 32; j++) {
                const uint32_t v = j & 3 ? pk[j] : ~pk[j];
                acc[64 + 2 * j] = __uint_as_float(v << 16); acc[65 + 2 * j] = __uint_as_float(v & 0xffff0000u);
                asm volatile("" : "+f"(acc[64 + 2 * j]), "+f"(acc[65 + 2 * j]) :: "memory");
            }
            stage_acquire(0); stage_acquire(1);
            wgmma_wait<0>();
#pragma unroll
            for (int j = 0; j < 64; j++) asm volatile("" : "+f"(acc[j]) :: "memory");
            mbar_arrive_cluster_if(ln < 4, bars_lane + B_GEMPTY + 8 * ((k - 1 - (ln >> 1)) & 3));
#pragma unroll
            for (int j = 0; j < 32; j++)
                pk[j] = pack_bf16(acc[2 * j] + acc[64 + 2 * j], acc[2 * j + 1] + acc[65 + 2 * j]);
            write_blocks(std::integral_constant<int, 8>(), 0, pk);
            __syncwarp();
            uint4* dst = (uint4*)((char*)prm.out + (uint32_t)((item_row(it) * 128 + wg * 64 + wq * 16 + (ln >> 4)) * 2048 + item_col(it) * 256 + (ln & 15) * 16));
#pragma unroll
            for (int j = 0; j < 8; j++) {
                const int r = 2 * j + (ln >> 4);
                uint4 v;
                asm volatile("ld.shared.v4.u32 {%0, %1, %2, %3}, [%4];" : "=r"(v.x), "=r"(v.y), "=r"(v.z), "=r"(v.w)
                             : "r"(stg + wq * 2048 + r * 128 + (ln & 8) * 1024 + (((ln & 7) ^ (r & 7)) << 4)) : "memory");
                dst[j * 256] = v;
            }
        }
    }
}

typedef CUresult (*EncodeFn)(CUtensorMap*, CUtensorMapDataType, cuuint32_t, void*, const cuuint64_t*, const cuuint64_t*,
                             const cuuint32_t*, const cuuint32_t*, CUtensorMapInterleave, CUtensorMapSwizzle,
                             CUtensorMapL2promotion, CUtensorMapFloatOOBfill);

void encode3(EncodeFn fn, CUtensorMap* m, const void* ptr, uint64_t d0, uint64_t d1, uint64_t d2, uint64_t s1, uint64_t s2,
             uint32_t b0, uint32_t b1, uint32_t b2) {
    cuuint64_t dims[3] = {d0, d1, d2};
    cuuint64_t strides[2] = {s1, s2};
    cuuint32_t box[3] = {b0, b1, b2};
    cuuint32_t es[3] = {1, 1, 1};
    fn(m, CU_TENSOR_MAP_DATA_TYPE_BFLOAT16, 3, const_cast<void*>(ptr), dims, strides, box, es, CU_TENSOR_MAP_INTERLEAVE_NONE,
       CU_TENSOR_MAP_SWIZZLE_128B, CU_TENSOR_MAP_L2_PROMOTION_NONE, CU_TENSOR_MAP_FLOAT_OOB_FILL_NONE);
}
void map_act(EncodeFn fn, CUtensorMap* m, const void* p, int rows, int cols, int box_rows) {
    encode3(fn, m, p, cols, rows, 1, (uint64_t)cols * 2, (uint64_t)cols * rows * 2, 64, box_rows, 1);
}
void map_wgt(EncodeFn fn, CUtensorMap* m, const void* p, int K, int N) {
    encode3(fn, m, p, 64, K, N / 64, (uint64_t)N * 2, 128, 64, 64, 2);
}

void build_schedule(Params& p) {
    int n = 0;
    auto add = [&](int type, int col, int row) { p.items[n++] = (uint16_t)(type << 13 | col << 4 | row); };
    auto add_qkv = [&](int c) {
        for (int m = 0; m < 8; m++) add(T_Q, c, m);
        for (int m = 0; m < 8; m++) add(T_K, c, m);
        for (int m = 0; m < 8; m++) add(T_V, c, m);
    };
    int ldist = 200, ldist2 = 260, lstep = 8, beta = 26, tail = 32, late = 6, early = 8, epos = 100;
    int order[16] = {6, 7, 8, 9, 10, 11, 12, 13, 14, 15, 5, 4, 3, 2, 1, 0};
    uint16_t proj[480];
    for (int m = 0; m < 8; m++) for (int c = 0; c < 12; c++) add(T_B, c, m);
    for (int c = 0; c < 16; c++) add_qkv(c);
    for (int i = 0; i < 480; i++) proj[i] = p.items[i];
    n = 0;
    for (int i = 0, l = 0; i < 480; i++) {
        p.items[n++] = proj[i];
        for (; l < 64 && i >= (l < 40 ? ldist + lstep * l / 8 : ldist2 + lstep * (l - 40) / 8); l++) add(T_LOCAL, l & 3, l >> 2);
    }
    const int a0 = n;
    for (int key = 0; key < 4000; key++)
        for (int r = 0; r < 32; r++)
            for (int j = 7; j >= 0; j--)
                if ((j ? (7 - j) * 40 + r * beta : 3999) == key) add(T_ATTN, 2 * order[r >> 1] + (r & 1), j);
    int t0 = n;
    for (int work = 0; work < 32 * 136 * tail / 100;) work += 4 * (p.items[--t0] & 15) + 3;
    for (int i = t0 + 1; i < n; i++)
        for (int j = i; j > t0 && (p.items[j] & 15) > (p.items[j - 1] & 15); j--) { const uint16_t t = p.items[j]; p.items[j] = p.items[j - 1]; p.items[j - 1] = t; }
    for (int r = early - 1; r >= 0; r--) {
        const uint16_t t = p.items[n - 32 + early - 1];
        for (int j = n - 32 + early - 1; j > n - epos; j--) p.items[j] = p.items[j - 1];
        p.items[n - epos] = t;
    }
    for (int moved = 0; moved < 2 && late >= 0; moved++)
        for (int i = a0; i < n; i++)
            if (p.items[i] == (T_ATTN << 13 | (2 * order[15] + moved) << 4 | late)) {
                for (int j = i; j + 1 < n; j++) p.items[j] = p.items[j + 1];
                p.items[n - 1] = (uint16_t)(T_ATTN << 13 | (2 * order[15] + moved) << 4 | late);
                break;
            }
    for (int s = 0, lo = 0, hi = WIDE - 1; s < 80; s++) {
        const int r = s / 2, g = r < 8 ? 32 + r : 2 * order[r / 2 - 4] + (r & 1);
        p.ostep[s >= WIDE ? s : r & 1 ? hi-- : lo++] = (uint8_t)(2 * g + (s & 1));
    }
}

void build_params(Params& p, void* const* d_in, void* d_out) {
    void* fnp = nullptr;
    cudaDriverEntryPointQueryResult qr;
    cudaGetDriverEntryPoint("cuTensorMapEncodeTiled", &fnp, cudaEnableDefault, &qr);
    EncodeFn fn = (EncodeFn)fnp;
    void* scr = nullptr;
    cudaGetSymbolAddress(&scr, g_scr);
    map_act(fn, &p.m[M_X], d_in[0], SEQ, 1024, 128);
    map_act(fn, &p.m[M_C], d_in[1], SEQ, 512, 128);
    map_wgt(fn, &p.m[M_WQ], d_in[2], 1024, 4096);
    map_wgt(fn, &p.m[M_WUK], d_in[3], 512, 4096);
    map_wgt(fn, &p.m[M_WUV], d_in[4], 512, 4096);
    map_wgt(fn, &p.m[M_WO], d_in[5], 4096, 1024);
    map_wgt(fn, &p.m[M_WQKV], d_in[7], 1024, 3072);
    map_wgt(fn, &p.m[M_WOB], d_in[8], 1024, 1024);
    encode3(fn, &p.m[M_SCR_LD], scr, 128, SEQ, G_TOTAL, 256, (uint64_t)SEQ * 256, 64, 128, 1);
    encode3(fn, &p.m[M_SCR_LOC], scr, 256, SEQ / 2, G_TOTAL, 512, (uint64_t)SEQ * 256, 64, 72, 1);
    encode3(fn, &p.m[M_SCR_LOQ], scr, 256, SEQ / 2, G_TOTAL, 512, (uint64_t)SEQ * 256, 64, 64, 1);
    encode3(fn, &p.m[M_SCR_ST], scr, 128, SEQ, G_TOTAL, 256, (uint64_t)SEQ * 256, 64, 64, 1);
    p.x = (const __nv_bfloat16*)d_in[0];
    p.gate_w = (const __nv_bfloat16*)d_in[9];
    p.zero = 0;
    p.wo = (const char*)d_in[5];
    p.wob = (const char*)d_in[8];
    p.out = (__nv_bfloat16*)d_out;
    build_schedule(p);
}

}

extern "C" void kernel_launch(void* const* d_in, const int* in_sizes, int n_in, void* d_out, int out_size) {
    (void)in_sizes; (void)n_in; (void)out_size;
    Params p;
    build_params(p, d_in, d_out);
    cudaFuncSetAttribute(fused_kernel, cudaFuncAttributeMaxDynamicSharedMemorySize, SM_TOTAL);
    fused_kernel<<<NCTA, 384, SM_TOTAL>>>(p);
}
```

```cpp
#include <cuda_runtime.h>
#include <cuda_bf16.h>
#include <cuda.h>
#include <stddef.h>
#include <stdint.h>
#include <type_traits>

namespace {

constexpr int SEQ = 2048;
constexpr int G_Q = 0, G_K = 32, G_V = 64, G_B = 96, G_CTX = G_Q, G_LOC = G_B, G_TOTAL = 120;

__device__ __align__(1024) __nv_bfloat16 g_scr[(size_t)G_TOTAL * SEQ * 128];
__device__ __align__(128) float g_gate[SEQ];

__device__ __forceinline__ uint32_t smem_u32(const void* p) { return (uint32_t)__cvta_generic_to_shared(p); }
__device__ __forceinline__ bool elect_one() {
    uint32_t p;
    asm volatile("{\n.reg .pred P;\nelect.sync _|P, 0xffffffff;\nselp.u32 %0, 1, 0, P;\n}\n" : "=r"(p));
    return p != 0;
}
__device__ __forceinline__ void mbar_init(uint32_t bar, uint32_t count) {
    asm volatile("mbarrier.init.shared::cta.b64 [%0], %1;" :: "r"(bar), "r"(count) : "memory");
}
__device__ __forceinline__ void mbar_expect_tx(uint32_t bar, uint32_t bytes) {
    asm volatile("mbarrier.arrive.expect_tx.shared::cta.b64 _, [%0], %1;" :: "r"(bar), "r"(bytes) : "memory");
}
__device__ __forceinline__ uint32_t cluster_rank() { uint32_t r; asm("mov.u32 %0, %%cluster_ctarank;" : "=r"(r)); return r; }
__device__ __forceinline__ uint32_t map_cta(uint32_t addr, uint32_t cta) {
    uint32_t r; asm("mapa.shared::cluster.u32 %0, %1, %2;" : "=r"(r) : "r"(addr), "r"(cta)); return r;
}
__device__ __forceinline__ void mbar_arrive_cluster_if(bool pred, uint32_t cluster_bar) {
    asm volatile("{\n.reg .pred P;\nsetp.ne.u32 P, %1, 0;\n@P mbarrier.arrive.shared::cluster.b64 _, [%0];\n}\n"
                 :: "r"(cluster_bar), "r"((uint32_t)pred) : "memory");
}
__device__ __forceinline__ void mbar_arrive_cluster_n_if(bool pred, uint32_t cluster_bar, uint32_t count) {
    asm volatile("{\n.reg .pred P;\nsetp.ne.u32 P, %1, 0;\n@P mbarrier.arrive.shared::cluster.b64 _, [%0], %2;\n}\n"
                 :: "r"(cluster_bar), "r"((uint32_t)pred), "r"(count) : "memory");
}
__device__ __forceinline__ void mbar_arrive_if(bool pred, uint32_t bar) {
    asm volatile("{\n.reg .pred P;\nsetp.ne.u32 P, %1, 0;\n@P mbarrier.arrive.shared::cta.b64 _, [%0];\n}\n"
                 :: "r"(bar), "r"((uint32_t)pred) : "memory");
}
__device__ __forceinline__ bool mbar_test(uint32_t bar, uint32_t parity) {
    uint32_t ok;
    asm volatile("{\n.reg .pred P;\nmbarrier.test_wait.parity.shared::cta.b64 P, [%1], %2;\nselp.u32 %0, 1, 0, P;\n}\n"
                 : "=r"(ok) : "r"(bar), "r"(parity) : "memory");
    return ok != 0;
}
__device__ __forceinline__ void mbar_wait(uint32_t bar, uint32_t parity) {
    asm volatile("{\n.reg .pred P;\n.reg .u32 c;\n"
                 "mbarrier.try_wait.parity.shared::cta.b64 P, [%0], %1;\n"
                 "@P bra DONE;\n"
                 "mov.u32 c, 0;\n"
                 "SPIN:\n"
                 "mbarrier.try_wait.parity.shared::cta.b64 P, [%0], %1;\n"
                 "@P bra DONE;\n"
                 "add.u32 c, c, 1;\n"
                 "setp.lt.u32 P, c, 4194304;\n"
                 "@P bra SPIN;\n"
                 "trap;\n"
                 "DONE:\n}\n" :: "r"(bar), "r"(parity) : "memory");
}
__device__ __forceinline__ void mbar_spin(uint32_t bar, uint32_t parity) {
    asm volatile("{\n.reg .pred P;\n"
                 "SPIN:\n"
                 "mbarrier.try_wait.parity.shared::cta.b64 P, [%0], %1;\n"
                 "@!P bra SPIN;\n}\n" :: "r"(bar), "r"(parity) : "memory");
}
__device__ __forceinline__ void bar_sync(int id, int n) { asm volatile("bar.sync %0, %1;" :: "r"(id), "r"(n) : "memory"); }
__device__ __forceinline__ void bar_arrive(int id, int n) { asm volatile("bar.arrive %0, %1;" :: "r"(id), "r"(n) : "memory"); }
__device__ __forceinline__ void fence_proxy_async_smem() { asm volatile("fence.proxy.async.shared::cta;" ::: "memory"); }
__device__ __forceinline__ void tma_load_3d(uint32_t dst, const CUtensorMap* map, uint32_t bar, int c0, int c1, int c2) {
    asm volatile("cp.async.bulk.tensor.3d.shared::cluster.global.mbarrier::complete_tx::bytes [%0], [%1, {%3, %4, %5}], [%2];"
                 :: "r"(dst), "l"(map), "r"(bar), "r"(c0), "r"(c1), "r"(c2) : "memory");
}
__device__ __forceinline__ void warp_expect_tx(uint32_t bar, uint32_t bytes) {
    asm volatile("{\n.reg .pred P;\nelect.sync _|P, 0xffffffff;\n@P mbarrier.arrive.expect_tx.shared::cta.b64 _, [%0], %1;\n}\n"
                 :: "r"(bar), "r"(bytes) : "memory");
}
__device__ __forceinline__ void warp_tma_load(uint32_t dst, const CUtensorMap* map, uint32_t bar, int c0, int c1, int c2) {
    asm volatile("{\n.reg .pred P;\nelect.sync _|P, 0xffffffff;\n"
                 "@P cp.async.bulk.tensor.3d.shared::cluster.global.mbarrier::complete_tx::bytes [%0], [%1, {%3, %4, %5}], [%2];\n}\n"
                 :: "r"(dst), "l"(map), "r"(bar), "r"(c0), "r"(c1), "r"(c2) : "memory");
}
__device__ __forceinline__ void warp_tma_load_pair(uint32_t dst, const CUtensorMap* map, uint32_t bar, int c0, int c1, int c2) {
    asm volatile("{\n.reg .pred P;\nelect.sync _|P, 0xffffffff;\n"
                 "@P cp.async.bulk.tensor.3d.shared::cluster.global.mbarrier::complete_tx::bytes.multicast::cluster"
                 " [%0], [%1, {%3, %4, %5}], [%2], %6;\n}\n"
                 :: "r"(dst), "l"(map), "r"(bar), "r"(c0), "r"(c1), "r"(c2), "h"((uint16_t)3) : "memory");
}
__device__ __forceinline__ void warp_bulk_load(uint32_t dst, const void* src, uint32_t bytes, uint32_t bar) {
    asm volatile("{\n.reg .pred P;\nelect.sync _|P, 0xffffffff;\n"
                 "@P cp.async.bulk.shared::cluster.global.mbarrier::complete_tx::bytes [%0], [%1], %2, [%3];\n}\n"
                 :: "r"(dst), "l"(src), "r"(bytes), "r"(bar) : "memory");
}
__device__ __forceinline__ void warp_tma_store(const CUtensorMap* map, uint32_t src, int c0, int c1, int c2) {
    asm volatile("{\n.reg .pred P;\nelect.sync _|P, 0xffffffff;\n"
                 "@P cp.async.bulk.tensor.3d.global.shared::cta.bulk_group [%0, {%2, %3, %4}], [%1];\n}\n"
                 :: "l"(map), "r"(src), "r"(c0), "r"(c1), "r"(c2) : "memory");
}
__device__ __forceinline__ void warp_bulk_store(void* dst, uint32_t src, uint32_t bytes) {
    asm volatile("{\n.reg .pred P;\nelect.sync _|P, 0xffffffff;\n"
                 "@P cp.async.bulk.global.shared::cta.bulk_group [%0], [%1], %2;\n}\n" :: "l"(dst), "r"(src), "r"(bytes) : "memory");
}
__device__ __forceinline__ void prefetch_l2(const void* src, uint32_t bytes) {
    asm volatile("cp.async.bulk.prefetch.L2.global [%0], %1;" :: "l"(src), "r"(bytes) : "memory");
}
__device__ __forceinline__ void warp_prefetch(const void* src, uint32_t bytes) {
    asm volatile("{\n.reg .pred P;\nelect.sync _|P, 0xffffffff;\n@P cp.async.bulk.prefetch.L2.global [%0], %1;\n}\n" :: "l"(src), "r"(bytes) : "memory");
}
__device__ __forceinline__ void bulk_commit() { asm volatile("cp.async.bulk.commit_group;" ::: "memory"); }
template <int N> __device__ __forceinline__ void bulk_wait_read() { asm volatile("cp.async.bulk.wait_group.read %0;" :: "n"(N) : "memory"); }
template <int N> __device__ __forceinline__ void bulk_wait() { asm volatile("cp.async.bulk.wait_group %0;" :: "n"(N) : "memory"); }
__device__ __forceinline__ void wgmma_fence() { asm volatile("wgmma.fence.sync.aligned;" ::: "memory"); }
__device__ __forceinline__ void wgmma_commit() { asm volatile("wgmma.commit_group.sync.aligned;" ::: "memory"); }
template <int N> __device__ __forceinline__ void wgmma_wait() { asm volatile("wgmma.wait_group.sync.aligned %0;" :: "n"(N) : "memory"); }
template <int N> __device__ __forceinline__ void fence_regs(float (&d)[N]) {
#pragma unroll
    for (int i = 0; i < N; i++) asm volatile("" : "+f"(d[i]) :: "memory");
}
template <int N> __device__ __forceinline__ void fence_regs(uint32_t (&d)[N]) {
#pragma unroll
    for (int i = 0; i < N; i++) asm volatile("" : "+r"(d[i]) :: "memory");
}
template <int N> __device__ __forceinline__ void reg_dec() { asm volatile("setmaxnreg.dec.sync.aligned.u32 %0;" :: "n"(N)); }
template <int N> __device__ __forceinline__ void reg_inc() { asm volatile("setmaxnreg.inc.sync.aligned.u32 %0;" :: "n"(N)); }
__device__ __forceinline__ uint32_t pack_bf16(float lo, float hi) {
    uint32_t r; asm("cvt.rn.bf16x2.f32 %0, %1, %2;" : "=r"(r) : "f"(hi), "f"(lo)); return r;
}
__device__ __forceinline__ void stmatrix_x4(uint32_t addr, uint32_t r0, uint32_t r1, uint32_t r2, uint32_t r3) {
    asm volatile("stmatrix.sync.aligned.m8n8.x4.shared.b16 [%0], {%1, %2, %3, %4};"
                 :: "r"(addr), "r"(r0), "r"(r1), "r"(r2), "r"(r3) : "memory");
}
__device__ __forceinline__ float ex2(float x) { float y; asm("ex2.approx.ftz.f32 %0, %1;" : "=f"(y) : "f"(x)); return y; }

constexpr uint32_t DESC_HI = (1024 >> 4) | (1u << 30);
__device__ __forceinline__ uint32_t make_desc(uint32_t addr, uint32_t lbo) {
    uint32_t lo = ((addr & 0x3FFFF) >> 4) | ((lbo >> 4) << 16);
    asm volatile("" : "+r"(lo));
    return lo;
}
__device__ __forceinline__ uint64_t full_desc(uint32_t lo) {
    uint64_t d; asm("mov.b64 %0, {%1, %2};" : "=l"(d) : "r"(lo), "r"(DESC_HI)); return d;
}

__device__ __forceinline__ void wgmma_ss_n256_tb_init(float (&d)[128], uint64_t da, uint64_t db) {
    asm volatile("{\n.reg .pred p;\n"
        "setp.ne.b32 p, 0, 0;\n"
        "wgmma.mma_async.sync.aligned.m64n256k16.f32.bf16.bf16 "
        "{%0, %1, %2, %3, %4, %5, %6, %7, %8, %9, %10, %11, %12, %13, %14, %15, %16, %17, %18, %19, %20, "
        "%21, %22, %23, %24, %25, %26, %27, %28, %29, %30, %31, %32, %33, %34, %35, %36, %37, %38, %39, %40, "
        "%41, %42, %43, %44, %45, %46, %47, %48, %49, %50, %51, %52, %53, %54, %55, %56, %57, %58, %59, %60, "
        "%61, %62, %63, %64, %65, %66, %67, %68, %69, %70, %71, %72, %73, %74, %75, %76, %77, %78, %79, %80, "
        "%81, %82, %83, %84, %85, %86, %87, %88, %89, %90, %91, %92, %93, %94, %95, %96, %97, %98, %99, "
        "%100, %101, %102, %103, %104, %105, %106, %107, %108, %109, %110, %111, %112, %113, %114, %115, "
        "%116, %117, %118, %119, %120, %121, %122, %123, %124, %125, %126, %127},"
        " %128, %129, p, 1, 1, 0, 1;\n}\n"
        : "=f"(d[0]), "=f"(d[1]), "=f"(d[2]), "=f"(d[3]), "=f"(d[4]), "=f"(d[5]), "=f"(d[6]), "=f"(d[7]),
        "=f"(d[8]), "=f"(d[9]), "=f"(d[10]), "=f"(d[11]), "=f"(d[12]), "=f"(d[13]), "=f"(d[14]), "=f"(d[15]),
        "=f"(d[16]), "=f"(d[17]), "=f"(d[18]), "=f"(d[19]), "=f"(d[20]), "=f"(d[21]), "=f"(d[22]),
        "=f"(d[23]), "=f"(d[24]), "=f"(d[25]), "=f"(d[26]), "=f"(d[27]), "=f"(d[28]), "=f"(d[29]),
        "=f"(d[30]), "=f"(d[31]), "=f"(d[32]), "=f"(d[33]), "=f"(d[34]), "=f"(d[35]), "=f"(d[36]),
        "=f"(d[37]), "=f"(d[38]), "=f"(d[39]), "=f"(d[40]), "=f"(d[41]), "=f"(d[42]), "=f"(d[43]),
        "=f"(d[44]), "=f"(d[45]), "=f"(d[46]), "=f"(d[47]), "=f"(d[48]), "=f"(d[49]), "=f"(d[50]),
        "=f"(d[51]), "=f"(d[52]), "=f"(d[53]), "=f"(d[54]), "=f"(d[55]), "=f"(d[56]), "=f"(d[57]),
        "=f"(d[58]), "=f"(d[59]), "=f"(d[60]), "=f"(d[61]), "=f"(d[62]), "=f"(d[63]), "=f"(d[64]),
        "=f"(d[65]), "=f"(d[66]), "=f"(d[67]), "=f"(d[68]), "=f"(d[69]), "=f"(d[70]), "=f"(d[71]),
        "=f"(d[72]), "=f"(d[73]), "=f"(d[74]), "=f"(d[75]), "=f"(d[76]), "=f"(d[77]), "=f"(d[78]),
        "=f"(d[79]), "=f"(d[80]), "=f"(d[81]), "=f"(d[82]), "=f"(d[83]), "=f"(d[84]), "=f"(d[85]),
        "=f"(d[86]), "=f"(d[87]), "=f"(d[88]), "=f"(d[89]), "=f"(d[90]), "=f"(d[91]), "=f"(d[92]),
        "=f"(d[93]), "=f"(d[94]), "=f"(d[95]), "=f"(d[96]), "=f"(d[97]), "=f"(d[98]), "=f"(d[99]),
        "=f"(d[100]), "=f"(d[101]), "=f"(d[102]), "=f"(d[103]), "=f"(d[104]), "=f"(d[105]), "=f"(d[106]),
        "=f"(d[107]), "=f"(d[108]), "=f"(d[109]), "=f"(d[110]), "=f"(d[111]), "=f"(d[112]), "=f"(d[113]),
        "=f"(d[114]), "=f"(d[115]), "=f"(d[116]), "=f"(d[117]), "=f"(d[118]), "=f"(d[119]), "=f"(d[120]),
        "=f"(d[121]), "=f"(d[122]), "=f"(d[123]), "=f"(d[124]), "=f"(d[125]), "=f"(d[126]), "=f"(d[127])
        : "l"(da), "l"(db));
}
__device__ __forceinline__ void wgmma_ss_n256_tb(float (&d)[128], uint64_t da, uint64_t db, int scale_d) {
    asm volatile("{\n.reg .pred p;\n"
        "setp.ne.b32 p, %130, 0;\n"
        "wgmma.mma_async.sync.aligned.m64n256k16.f32.bf16.bf16 "
        "{%0, %1, %2, %3, %4, %5, %6, %7, %8, %9, %10, %11, %12, %13, %14, %15, %16, %17, %18, %19, %20, "
        "%21, %22, %23, %24, %25, %26, %27, %28, %29, %30, %31, %32, %33, %34, %35, %36, %37, %38, %39, %40, "
        "%41, %42, %43, %44, %45, %46, %47, %48, %49, %50, %51, %52, %53, %54, %55, %56, %57, %58, %59, %60, "
        "%61, %62, %63, %64, %65, %66, %67, %68, %69, %70, %71, %72, %73, %74, %75, %76, %77, %78, %79, %80, "
        "%81, %82, %83, %84, %85, %86, %87, %88, %89, %90, %91, %92, %93, %94, %95, %96, %97, %98, %99, "
        "%100, %101, %102, %103, %104, %105, %106, %107, %108, %109, %110, %111, %112, %113, %114, %115, "
        "%116, %117, %118, %119, %120, %121, %122, %123, %124, %125, %126, %127},"
        " %128, %129, p, 1, 1, 0, 1;\n}\n"
        : "+f"(d[0]), "+f"(d[1]), "+f"(d[2]), "+f"(d[3]), "+f"(d[4]), "+f"(d[5]), "+f"(d[6]), "+f"(d[7]),
        "+f"(d[8]), "+f"(d[9]), "+f"(d[10]), "+f"(d[11]), "+f"(d[12]), "+f"(d[13]), "+f"(d[14]), "+f"(d[15]),
        "+f"(d[16]), "+f"(d[17]), "+f"(d[18]), "+f"(d[19]), "+f"(d[20]), "+f"(d[21]), "+f"(d[22]),
        "+f"(d[23]), "+f"(d[24]), "+f"(d[25]), "+f"(d[26]), "+f"(d[27]), "+f"(d[28]), "+f"(d[29]),
        "+f"(d[30]), "+f"(d[31]), "+f"(d[32]), "+f"(d[33]), "+f"(d[34]), "+f"(d[35]), "+f"(d[36]),
        "+f"(d[37]), "+f"(d[38]), "+f"(d[39]), "+f"(d[40]), "+f"(d[41]), "+f"(d[42]), "+f"(d[43]),
        "+f"(d[44]), "+f"(d[45]), "+f"(d[46]), "+f"(d[47]), "+f"(d[48]), "+f"(d[49]), "+f"(d[50]),
        "+f"(d[51]), "+f"(d[52]), "+f"(d[53]), "+f"(d[54]), "+f"(d[55]), "+f"(d[56]), "+f"(d[57]),
        "+f"(d[58]), "+f"(d[59]), "+f"(d[60]), "+f"(d[61]), "+f"(d[62]), "+f"(d[63]), "+f"(d[64]),
        "+f"(d[65]), "+f"(d[66]), "+f"(d[67]), "+f"(d[68]), "+f"(d[69]), "+f"(d[70]), "+f"(d[71]),
        "+f"(d[72]), "+f"(d[73]), "+f"(d[74]), "+f"(d[75]), "+f"(d[76]), "+f"(d[77]), "+f"(d[78]),
        "+f"(d[79]), "+f"(d[80]), "+f"(d[81]), "+f"(d[82]), "+f"(d[83]), "+f"(d[84]), "+f"(d[85]),
        "+f"(d[86]), "+f"(d[87]), "+f"(d[88]), "+f"(d[89]), "+f"(d[90]), "+f"(d[91]), "+f"(d[92]),
        "+f"(d[93]), "+f"(d[94]), "+f"(d[95]), "+f"(d[96]), "+f"(d[97]), "+f"(d[98]), "+f"(d[99]),
        "+f"(d[100]), "+f"(d[101]), "+f"(d[102]), "+f"(d[103]), "+f"(d[104]), "+f"(d[105]), "+f"(d[106]),
        "+f"(d[107]), "+f"(d[108]), "+f"(d[109]), "+f"(d[110]), "+f"(d[111]), "+f"(d[112]), "+f"(d[113]),
        "+f"(d[114]), "+f"(d[115]), "+f"(d[116]), "+f"(d[117]), "+f"(d[118]), "+f"(d[119]), "+f"(d[120]),
        "+f"(d[121]), "+f"(d[122]), "+f"(d[123]), "+f"(d[124]), "+f"(d[125]), "+f"(d[126]), "+f"(d[127])
        : "l"(da), "l"(db), "r"(scale_d));
}
__device__ __forceinline__ void wgmma_ss_n128(float (&d)[64], uint64_t da, uint64_t db, int scale_d) {
    asm volatile("{\n.reg .pred p;\n"
        "setp.ne.b32 p, %66, 0;\n"
        "wgmma.mma_async.sync.aligned.m64n128k16.f32.bf16.bf16 "
        "{%0, %1, %2, %3, %4, %5, %6, %7, %8, %9, %10, %11, %12, %13, %14, %15, %16, %17, %18, %19, %20, "
        "%21, %22, %23, %24, %25, %26, %27, %28, %29, %30, %31, %32, %33, %34, %35, %36, %37, %38, %39, %40, "
        "%41, %42, %43, %44, %45, %46, %47, %48, %49, %50, %51, %52, %53, %54, %55, %56, %57, %58, %59, %60, "
        "%61, %62, %63},"
        " %64, %65, p, 1, 1, 0, 0;\n}\n"
        : "+f"(d[0]), "+f"(d[1]), "+f"(d[2]), "+f"(d[3]), "+f"(d[4]), "+f"(d[5]), "+f"(d[6]), "+f"(d[7]),
        "+f"(d[8]), "+f"(d[9]), "+f"(d[10]), "+f"(d[11]), "+f"(d[12]), "+f"(d[13]), "+f"(d[14]), "+f"(d[15]),
        "+f"(d[16]), "+f"(d[17]), "+f"(d[18]), "+f"(d[19]), "+f"(d[20]), "+f"(d[21]), "+f"(d[22]),
        "+f"(d[23]), "+f"(d[24]), "+f"(d[25]), "+f"(d[26]), "+f"(d[27]), "+f"(d[28]), "+f"(d[29]),
        "+f"(d[30]), "+f"(d[31]), "+f"(d[32]), "+f"(d[33]), "+f"(d[34]), "+f"(d[35]), "+f"(d[36]),
        "+f"(d[37]), "+f"(d[38]), "+f"(d[39]), "+f"(d[40]), "+f"(d[41]), "+f"(d[42]), "+f"(d[43]),
        "+f"(d[44]), "+f"(d[45]), "+f"(d[46]), "+f"(d[47]), "+f"(d[48]), "+f"(d[49]), "+f"(d[50]),
        "+f"(d[51]), "+f"(d[52]), "+f"(d[53]), "+f"(d[54]), "+f"(d[55]), "+f"(d[56]), "+f"(d[57]),
        "+f"(d[58]), "+f"(d[59]), "+f"(d[60]), "+f"(d[61]), "+f"(d[62]), "+f"(d[63])
        : "l"(da), "l"(db), "r"(scale_d));
}
__device__ __forceinline__ void wgmma_rs_n128_tb(float (&d)[64], uint32_t a0, uint32_t a1, uint32_t a2, uint32_t a3, uint64_t db, int scale_d) {
    asm volatile("{\n.reg .pred p;\n"
        "setp.ne.b32 p, %69, 0;\n"
        "wgmma.mma_async.sync.aligned.m64n128k16.f32.bf16.bf16 "
        "{%0, %1, %2, %3, %4, %5, %6, %7, %8, %9, %10, %11, %12, %13, %14, %15, %16, %17, %18, %19, %20, "
        "%21, %22, %23, %24, %25, %26, %27, %28, %29, %30, %31, %32, %33, %34, %35, %36, %37, %38, %39, %40, "
        "%41, %42, %43, %44, %45, %46, %47, %48, %49, %50, %51, %52, %53, %54, %55, %56, %57, %58, %59, %60, "
        "%61, %62, %63},"
        " {%64, %65, %66, %67}, %68, p, 1, 1, 1;\n}\n"
        : "+f"(d[0]), "+f"(d[1]), "+f"(d[2]), "+f"(d[3]), "+f"(d[4]), "+f"(d[5]), "+f"(d[6]), "+f"(d[7]),
        "+f"(d[8]), "+f"(d[9]), "+f"(d[10]), "+f"(d[11]), "+f"(d[12]), "+f"(d[13]), "+f"(d[14]), "+f"(d[15]),
        "+f"(d[16]), "+f"(d[17]), "+f"(d[18]), "+f"(d[19]), "+f"(d[20]), "+f"(d[21]), "+f"(d[22]),
        "+f"(d[23]), "+f"(d[24]), "+f"(d[25]), "+f"(d[26]), "+f"(d[27]), "+f"(d[28]), "+f"(d[29]),
        "+f"(d[30]), "+f"(d[31]), "+f"(d[32]), "+f"(d[33]), "+f"(d[34]), "+f"(d[35]), "+f"(d[36]),
        "+f"(d[37]), "+f"(d[38]), "+f"(d[39]), "+f"(d[40]), "+f"(d[41]), "+f"(d[42]), "+f"(d[43]),
        "+f"(d[44]), "+f"(d[45]), "+f"(d[46]), "+f"(d[47]), "+f"(d[48]), "+f"(d[49]), "+f"(d[50]),
        "+f"(d[51]), "+f"(d[52]), "+f"(d[53]), "+f"(d[54]), "+f"(d[55]), "+f"(d[56]), "+f"(d[57]),
        "+f"(d[58]), "+f"(d[59]), "+f"(d[60]), "+f"(d[61]), "+f"(d[62]), "+f"(d[63])
        : "r"(a0), "r"(a1), "r"(a2), "r"(a3), "l"(db), "r"(scale_d));
}
__device__ __forceinline__ void wgmma_ss_n128_lo_tb(float (&d)[128], uint64_t da, uint64_t db, int scale_d) {
    asm volatile("{\n.reg .pred p;\n"
        "setp.ne.b32 p, %66, 0;\n"
        "wgmma.mma_async.sync.aligned.m64n128k16.f32.bf16.bf16 "
        "{%0, %1, %2, %3, %4, %5, %6, %7, %8, %9, %10, %11, %12, %13, %14, %15, %16, %17, %18, %19, %20, "
        "%21, %22, %23, %24, %25, %26, %27, %28, %29, %30, %31, %32, %33, %34, %35, %36, %37, %38, %39, %40, "
        "%41, %42, %43, %44, %45, %46, %47, %48, %49, %50, %51, %52, %53, %54, %55, %56, %57, %58, %59, %60, "
        "%61, %62, %63},"
        " %64, %65, p, 1, 1, 0, 1;\n}\n"
        : "+f"(d[0]), "+f"(d[1]), "+f"(d[2]), "+f"(d[3]), "+f"(d[4]), "+f"(d[5]), "+f"(d[6]), "+f"(d[7]),
        "+f"(d[8]), "+f"(d[9]), "+f"(d[10]), "+f"(d[11]), "+f"(d[12]), "+f"(d[13]), "+f"(d[14]), "+f"(d[15]),
        "+f"(d[16]), "+f"(d[17]), "+f"(d[18]), "+f"(d[19]), "+f"(d[20]), "+f"(d[21]), "+f"(d[22]),
        "+f"(d[23]), "+f"(d[24]), "+f"(d[25]), "+f"(d[26]), "+f"(d[27]), "+f"(d[28]), "+f"(d[29]),
        "+f"(d[30]), "+f"(d[31]), "+f"(d[32]), "+f"(d[33]), "+f"(d[34]), "+f"(d[35]), "+f"(d[36]),
        "+f"(d[37]), "+f"(d[38]), "+f"(d[39]), "+f"(d[40]), "+f"(d[41]), "+f"(d[42]), "+f"(d[43]),
        "+f"(d[44]), "+f"(d[45]), "+f"(d[46]), "+f"(d[47]), "+f"(d[48]), "+f"(d[49]), "+f"(d[50]),
        "+f"(d[51]), "+f"(d[52]), "+f"(d[53]), "+f"(d[54]), "+f"(d[55]), "+f"(d[56]), "+f"(d[57]),
        "+f"(d[58]), "+f"(d[59]), "+f"(d[60]), "+f"(d[61]), "+f"(d[62]), "+f"(d[63])
        : "l"(da), "l"(db), "r"(scale_d));
}

enum { M_X = 0, M_C, M_WQ, M_WQKV, M_WUK, M_WUV, M_WO, M_WOB, M_SCR_LD, M_SCR_LOC, M_SCR_LOQ, M_SCR_ST, M_COUNT };
enum { T_Q = 0, T_K, T_V, T_B, T_OUT, T_LOCAL, T_ATTN, T_END };
constexpr int NCTA = 132, NPAIR = NCTA / 2;
constexpr int NITEMS = 480 + 64 + 256;
#define NTRI 3
constexpr int TRIPLES = NTRI, WIDE = 80 - 3 * TRIPLES;
struct Params {
    CUtensorMap m[M_COUNT];
    const __nv_bfloat16* x;
    const __nv_bfloat16* gate_w;
    const char* wo;
    const char* wob;
    __nv_bfloat16* out;
    uint32_t zero;
    uint16_t items[NITEMS];
    uint8_t ostep[80];
};
__device__ __forceinline__ int item_type(int it) { return it >> 13; }
__device__ __forceinline__ int item_row(int it) { return it & 15; }
__device__ __forceinline__ int item_col(int it) { return (it >> 4) & 31; }
__device__ __forceinline__ int item_asc(int it) { return (it >> 9) & 1; }
constexpr int ITEM_READY = 1 << 10;

struct __align__(128) Sync {
    unsigned long long count[4];
    __align__(128) unsigned long long ctx[16];
    unsigned next, next_out, done;
    __align__(128) unsigned step[32][2];
    unsigned split[32];
};
__device__ Sync g_sync;
__device__ uint4 g_part[128][8][256];

constexpr uint32_t GST_BYTES = 49152, SM_KV = 65536, SM_STAGING = 196608, SM_BARS = SM_STAGING + 32768;
constexpr uint32_t B_GFULL = 0, B_GEMPTY = 32, B_AFULL = 64, B_AEMPTY = 112, B_SFULL = 160, B_SEMPTY = 192,
                   B_IFULL = 224, B_IEMPTY = 288, B_XFREE = 352, B_WANT = 384, B_HALF = 416,
                   SM_ORDY = 448, SM_QUEUE = 456, B_ALT = 488, B_QFREE = 504, SM_GATE = 512, SM_TOTAL = SM_BARS + 1536;
constexpr int QDEPTH = 8;
#define PF_NAR 20
#define SPREAD 4
#define PACE 0
#define PF_LOC 1
#define KMEET 14
constexpr int K_MEET = KMEET, K_SPLIT = KMEET + 12;
#define KF2 3
constexpr uint32_t LOC_PLANE = 72 * 128;
constexpr float SM_SCALE = 0.08838834764831845f * 1.4426950408889634f;
constexpr float LOC_SCALE = 0.17677669529663687f * 1.4426950408889634f;
constexpr float SUM_LIMIT = 1152921504606846976.f;
constexpr float REF_RANGE = 32.f;

__device__ __forceinline__ unsigned ld_acquire(const unsigned* p) {
    unsigned v; asm volatile("ld.acquire.gpu.global.u32 %0, [%1];" : "=r"(v) : "l"(p) : "memory"); return v;
}
__device__ __forceinline__ unsigned long long ld_acquire(const unsigned long long* p) {
    unsigned long long v; asm volatile("ld.acquire.gpu.global.u64 %0, [%1];" : "=l"(v) : "l"(p) : "memory"); return v;
}
__device__ __forceinline__ void st_b128(void* p, uint32_t a, uint32_t b, uint32_t c, uint32_t d) {
    asm volatile("{\n.reg .b128 v;\n.reg .b64 lo, hi;\nmov.b64 lo, {%1, %2};\nmov.b64 hi, {%3, %4};\nmov.b128 v, {lo, hi};\n"
                 "st.relaxed.gpu.global.b128 [%0], v;\n}\n" :: "l"(p), "r"(a), "r"(b), "r"(c), "r"(d) : "memory");
}
__device__ __forceinline__ void ld_b128(const void* p, uint32_t& a, uint32_t& b, uint32_t& c, uint32_t& d) {
    asm volatile("{\n.reg .b128 v;\n.reg .b64 lo, hi;\nld.relaxed.gpu.global.b128 v, [%4];\nmov.b128 {lo, hi}, v;\n"
                 "mov.b64 {%0, %1}, lo;\nmov.b64 {%2, %3}, hi;\n}\n" : "=r"(a), "=r"(b), "=r"(c), "=r"(d) : "l"(p) : "memory");
}
__device__ __forceinline__ void spin_guard(unsigned& n) {
    asm volatile("{\n.reg .pred P;\nadd.u32 %0, %0, 1;\nsetp.gt.u32 P, %0, 16777216;\n@P trap;\n}\n" : "+r"(n));
    if (n > 1) __nanosleep(100);
}
__device__ __forceinline__ void red_add(unsigned long long* p, unsigned long long v) {
    asm volatile("red.release.gpu.global.add.u64 [%0], %1;" :: "l"(p), "l"(v) : "memory");
}
__device__ __forceinline__ float rcp(float x) { float y; asm("rcp.approx.ftz.f32 %0, %1;" : "=f"(y) : "f"(x)); return y; }
__device__ __forceinline__ float lds_f32(uint32_t addr) {
    float v; asm volatile("ld.shared.f32 %0, [%1];" : "=f"(v) : "r"(addr) : "memory"); return v;
}
__device__ __forceinline__ void ldsm_x4(uint32_t (&r)[4], uint32_t addr) {
    asm volatile("ldmatrix.sync.aligned.m8n8.x4.shared.b16 {%0, %1, %2, %3}, [%4];"
                 : "=r"(r[0]), "=r"(r[1]), "=r"(r[2]), "=r"(r[3]) : "r"(addr) : "memory");
}
__device__ __forceinline__ void ldsm_x4_t(uint32_t (&r)[4], uint32_t addr) {
    asm volatile("ldmatrix.sync.aligned.m8n8.x4.trans.shared.b16 {%0, %1, %2, %3}, [%4];"
                 : "=r"(r[0]), "=r"(r[1]), "=r"(r[2]), "=r"(r[3]) : "r"(addr) : "memory");
}
__device__ __forceinline__ void mma_k16(float (&d)[4], const uint32_t (&a)[4], uint32_t b0, uint32_t b1) {
    asm("mma.sync.aligned.m16n8k16.row.col.f32.bf16.bf16.f32 {%0,%1,%2,%3}, {%4,%5,%6,%7}, {%8,%9}, {%0,%1,%2,%3};"
        : "+f"(d[0]), "+f"(d[1]), "+f"(d[2]), "+f"(d[3]) : "r"(a[0]), "r"(a[1]), "r"(a[2]), "r"(a[3]), "r"(b0), "r"(b1));
}
__device__ __forceinline__ void mma_k16_init(float (&d)[4], const uint32_t (&a)[4], uint32_t b0, uint32_t b1) {
    asm("{\n.reg .f32 z;\nmov.f32 z, 0f00000000;\n"
        "mma.sync.aligned.m16n8k16.row.col.f32.bf16.bf16.f32 {%0,%1,%2,%3}, {%4,%5,%6,%7}, {%8,%9}, {z,z,z,z};\n}\n"
        : "=f"(d[0]), "=f"(d[1]), "=f"(d[2]), "=f"(d[3]) : "r"(a[0]), "r"(a[1]), "r"(a[2]), "r"(a[3]), "r"(b0), "r"(b1));
}
__device__ __forceinline__ void mma_k8(float (&d)[4], uint32_t a0, uint32_t a1, uint32_t b0) {
    asm("mma.sync.aligned.m16n8k8.row.col.f32.bf16.bf16.f32 {%0,%1,%2,%3}, {%4,%5}, {%6}, {%0,%1,%2,%3};"
        : "+f"(d[0]), "+f"(d[1]), "+f"(d[2]), "+f"(d[3]) : "r"(a0), "r"(a1), "r"(b0));
}
template <typename T, int N> __device__ __forceinline__ void zero_regs(T (&d)[N]) {
#pragma unroll
    for (int i = 0; i < N; i++) d[i] = 0;
}
__device__ __forceinline__ float quad_max(float v) {
    v = fmaxf(v, __shfl_xor_sync(0xffffffffu, v, 1));
    return fmaxf(v, __shfl_xor_sync(0xffffffffu, v, 2));
}
__device__ __forceinline__ float quad_sum(float v) {
    v += __shfl_xor_sync(0xffffffffu, v, 1);
    return v + __shfl_xor_sync(0xffffffffu, v, 2);
}

__device__ __forceinline__ void qk_gemm(float (&s)[64], uint32_t q_lo, uint32_t k_lo) {
    const uint64_t dq = full_desc(q_lo), dk = full_desc(k_lo);
    fence_regs(s);
    wgmma_fence();
#pragma unroll
    for (int kk = 0; kk < 8; kk++) {
        const uint32_t o = (kk >> 2) * 1024 + (kk & 3) * 2;
        wgmma_ss_n128(s, dq + o, dk + o, kk != 0);
    }
    wgmma_commit();
}
__device__ __forceinline__ void pv_gemm(float (&o)[64], uint32_t (&p)[32], uint32_t v_lo, int accumulate) {
    const uint64_t dv = full_desc(v_lo);
    fence_regs(o);
    fence_regs(p);
    wgmma_fence();
#pragma unroll
    for (int kk = 0; kk < 8; kk++)
        wgmma_rs_n128_tb(o, p[4 * kk], p[4 * kk + 1], p[4 * kk + 2], p[4 * kk + 3], dv + kk * 128, kk != 0 || accumulate);
    wgmma_commit();
}
template <int NJ>
__device__ __forceinline__ void row_max(const float (&s)[64], float& x0, float& x1) {
    float z0 = fmaxf(s[0], s[1]), z1 = fmaxf(s[2], s[3]);
    x0 = fmaxf(s[4], s[5]); x1 = fmaxf(s[6], s[7]);
#pragma unroll
    for (int j = 2; j < NJ; j += 2) {
        z0 = fmaxf(z0, fmaxf(s[4 * j], s[4 * j + 1]));
        z1 = fmaxf(z1, fmaxf(s[4 * j + 2], s[4 * j + 3]));
        x0 = fmaxf(x0, fmaxf(s[4 * j + 4], s[4 * j + 5]));
        x1 = fmaxf(x1, fmaxf(s[4 * j + 6], s[4 * j + 7]));
    }
    x0 = quad_max(fmaxf(x0, z0)); x1 = quad_max(fmaxf(x1, z1));
}
__device__ __forceinline__ void exp_pack(uint32_t (&p)[32], const float (&s)[64], float& r0, float& r1) {
#pragma unroll
    for (int j = 0; j < 16; j++) {
        const float e0 = ex2(s[4 * j]), e1 = ex2(s[4 * j + 1]), e2 = ex2(s[4 * j + 2]), e3 = ex2(s[4 * j + 3]);
        if (j == 0) { r0 = e0 + e1; r1 = e2 + e3; }
        else { r0 += e0 + e1; r1 += e2 + e3; }
        p[2 * j] = pack_bf16(e0, e1);
        p[2 * j + 1] = pack_bf16(e2, e3);
    }
}
__device__ __forceinline__ void shift_rows(float (&s)[64], float d0, float d1) {
#pragma unroll
    for (int j = 0; j < 16; j++) { s[4 * j] -= d0; s[4 * j + 1] -= d0; s[4 * j + 2] -= d1; s[4 * j + 3] -= d1; }
}
template <int J0>
__device__ __forceinline__ void mask_triangle(float (&s)[64], int thr) {
#pragma unroll
    for (int j = 0; j < 8; j++) {
        if (8 * j > thr) s[4 * (J0 + j)] = -INFINITY;
        if (8 * j + 1 > thr) s[4 * (J0 + j) + 1] = -INFINITY;
        if (j > 0 && 8 * j - 8 > thr) s[4 * (J0 + j) + 2] = -INFINITY;
        if (j > 0 && 8 * j - 7 > thr) s[4 * (J0 + j) + 3] = -INFINITY;
    }
}
__device__ __forceinline__ void causal_mask(float (&s)[64], int thr, int wg) {
    asm volatile("" : "+r"(thr));
    if (wg == 0) {
        mask_triangle<0>(s, thr);
#pragma unroll
        for (int j = 32; j < 64; j++) s[j] = -INFINITY;
    } else {
        mask_triangle<8>(s, thr - 64);
    }
}

__global__ void __cluster_dims__(2, 1, 1) __launch_bounds__(384, 1) fused_kernel(const __grid_constant__ Params prm) {
    extern __shared__ __align__(1024) uint8_t smem[];
    const uint32_t sb = smem_u32(smem), bars = sb + SM_BARS;
    const int warp = __shfl_sync(0xffffffffu, threadIdx.x >> 5, 0), lane = threadIdx.x & 31;

    const uint32_t rank = cluster_rank();
    const uint32_t bars0 = map_cta(bars, 0), bars_peer = map_cta(bars, rank ^ 1);

    auto first_item = [&]() -> int {
        uint32_t pair = blockIdx.x >> 1;
        asm volatile("" : "+r"(pair));
        return prm.items[pair] + item_row(prm.items[pair]) + rank;
    };
    if (threadIdx.x == 256) {
        for (int k = 0; k < 4; k++) mbar_init(bars + B_GFULL + 8 * k, 1);
        asm volatile("fence.mbarrier_init.release.cluster;" ::: "memory");
        fence_proxy_async_smem();
    }
    if (threadIdx.x == 128) {
        for (int i = 0; i < 4; i++) { mbar_init(bars + B_GEMPTY + 8 * i, 16); mbar_init(bars + B_XFREE + 8 * i, 1); }
        for (int i = 0; i < 6; i++) { mbar_init(bars + B_AFULL + 8 * i, 1); mbar_init(bars + B_AEMPTY + 8 * i, i < 2 ? 8 : 16); }
        for (int i = 0; i < 4; i++) { mbar_init(bars + B_SFULL + 8 * i, 4); mbar_init(bars + B_SEMPTY + 8 * i, 1); }
        for (int i = 0; i < QDEPTH; i++) { mbar_init(bars + B_IFULL + 8 * i, 1); mbar_init(bars + B_IEMPTY + 8 * i, 23); }
        mbar_init(bars + B_WANT, 2);
        for (int i = 0; i < 4; i++) mbar_init(bars + B_HALF + 8 * i, 1);
        mbar_init(bars + B_ALT, 4); mbar_init(bars + B_ALT + 8, 4); mbar_init(bars + B_QFREE, 2);
        asm volatile("st.shared.u64 [%0], 0;" :: "r"(bars + SM_ORDY) : "memory");
        asm volatile("fence.mbarrier_init.release.cluster;\nfence.acq_rel.cta;" ::: "memory");
    }
    __syncwarp();
    asm volatile("barrier.cluster.arrive.relaxed.aligned;" ::: "memory");
    if (threadIdx.x == 256) {
        const int first_it = first_item();
        for (int k = 0; k < 4; k++) {
            const uint32_t dst = sb + k * GST_BYTES, fb = bars + B_GFULL + 8 * k;
            mbar_expect_tx(fb, GST_BYTES);
            tma_load_3d(dst, &prm.m[M_X], fb, k * 64, item_row(first_it) * 128, 0);
            tma_load_3d(dst + 16384, &prm.m[M_WQKV], fb, 0, k * 64, item_col(first_it) * 4);
            tma_load_3d(dst + 32768, &prm.m[M_WQKV], fb, 0, k * 64, item_col(first_it) * 4 + 2);
        }
    }
    __syncwarp();
    asm volatile("barrier.cluster.wait.acquire.aligned;" ::: "memory");

    uint32_t qn = 0;
    auto next_item = [&](bool releaser, bool bounded = true) -> int {
        const uint32_t slot = qn % QDEPTH;
        if (bounded) mbar_wait(bars + B_IFULL + 8 * slot, (qn / QDEPTH) & 1);
        else mbar_spin(bars + B_IFULL + 8 * slot, (qn / QDEPTH) & 1);
        uint32_t it;
        asm volatile("ld.shared.u32 %0, [%1];" : "=r"(it) : "r"(bars + SM_QUEUE + 4 * slot) : "memory");
        mbar_arrive_cluster_if(releaser, bars0 + B_IEMPTY + 8 * slot);
        qn++;
        return it;
    };

    if (warp < 4) {
        reg_dec<40>();
        if (warp == 0) {
            {
                uint32_t gph = 0;
                const uint32_t prank = __shfl_sync(0xffffffffu, rank, 0);
                int k0 = 4;
                uint32_t kv = 0, kvph = 1;
                uint32_t qc = 0;
                uint32_t oneed = 0;
                uint32_t xph = 0;
                uint32_t need_g = 0, need_a = 0;
                auto a_parity = [&](uint32_t b) { return b < 2 ? (((qc + 1 - b) >> 1) & 1) ^ 1 : kvph ^ (b - 2 < kv); };
                int held_type = T_END;
                uint32_t borrowed = 0, fph = 0;
                auto reclaim_q = [&]() { if (borrowed) { mbar_wait(bars + B_QFREE, fph); fph ^= 1; borrowed = 0; } };
                auto acquire_g = [&](uint32_t st, bool shared) {
                    mbar_wait(bars + B_GEMPTY + 8 * st, gph);
                    if (need_a) {
                        reclaim_q();
                        const uint32_t b = (3 * st) >> 1;
                        mbar_wait(bars + B_AEMPTY + 8 * b, a_parity(b));
                        mbar_wait(bars + B_AEMPTY + 8 * (b + 1), a_parity(b + 1));
                        if (shared) {
                            mbar_arrive_cluster_if(lane == 0, bars_peer + B_XFREE + 8 * st);
                            mbar_wait(bars + B_XFREE + 8 * st, xph);
                        }
                        if (st == 3) { need_a = 0; xph ^= shared; }
                    }
                };
                auto leave_gemm = [&](uint32_t b) {
                    if (need_g >> b & 1) {
                        mbar_wait(bars + B_GEMPTY + 8 * ((2 * b) / 3), gph);
                        mbar_wait(bars + B_GEMPTY + 8 * ((2 * b + 1) / 3), gph);
                        need_g &= ~(1u << b);
                    }
                };
                const CUtensorMap* tile_map = &prm.m[M_SCR_LD];
                asm volatile("" : "+l"(tile_map));
                auto load_q = [&](int grp, int row) {
                    const uint32_t b = qc & 1, dst = sb + b * 32768, fb = bars + B_AFULL + 8 * b;
                    mbar_wait(bars + B_AEMPTY + 8 * b, a_parity(b));
                    leave_gemm(b);
                    reclaim_q();
                    borrowed = held_type != T_END;
                    held_type = T_END;
                    warp_expect_tx(fb, 32768 + 512);
                    warp_tma_load(dst, tile_map, fb, 0, row, grp);
                    warp_tma_load(dst + 16384, tile_map, fb, 64, row, grp);
                    warp_bulk_load(bars + SM_GATE + b * 512, &g_gate[row], 512, fb);
                    qc++;
                };
                auto load_kv = [&](int grp, int row, bool shared) {
                    uint32_t fb = bars + B_AFULL + 16 + 8 * kv, mine = sb + SM_KV + kv * 32768 + prank * 16384;
                    int c_mine = prank * 64;
                    asm volatile("" : "+r"(mine), "+r"(fb), "+r"(row), "+r"(grp), "+r"(c_mine));
                    if (need_g) leave_gemm(2 + kv);
                    mbar_wait(fb + B_AEMPTY - B_AFULL, kvph);
                    warp_expect_tx(fb, grp < 0 ? 0 : 32768);
                    if (shared) {
                        warp_tma_load_pair(mine, tile_map, fb, c_mine, row, grp);
                    } else if (grp >= 0) {
                        warp_tma_load(mine, tile_map, fb, c_mine, row, grp);
                        warp_tma_load(mine + 16384 - prank * 32768, tile_map, fb, 64 - c_mine, row, grp);
                    } else {
                        mbar_arrive_cluster_n_if(lane < 2, map_cta(fb, lane & 1) + B_AEMPTY - B_AFULL, 8);
                    }
                    if (++kv == 4) { kv = 0; kvph ^= 1; }
                };
                auto request = [&]() { mbar_arrive_cluster_if(lane == 0, bars0 + B_WANT); };
                int pv_grp = -1, pv_row = 0;
                bool pv_shared = false, peer_longer = false;
                auto inputs_seen = [&](uint32_t word, unsigned& n) -> uint32_t {
                    uint32_t v;
                    spin_guard(n);
                    asm volatile("ld.acquire.cta.shared.u32 %0, [%1];" : "=r"(v) : "r"(bars + SM_ORDY + 4 * word) : "memory");
                    return __shfl_sync(0xffffffffu, v, 0);
                };
                auto fetch = [&]() -> int {
                    const int nx = __shfl_sync(0xffffffffu, next_item(lane == 0), 0);
                    if ((item_type(nx) == T_ATTN || item_type(nx) == T_LOCAL) && !(nx & ITEM_READY)) {
                        oneed += 256;
                        for (unsigned n = 0; inputs_seen(1, n) < oneed;) {}
                    }
                    if (item_type(nx) == T_ATTN) load_q(G_Q + item_col(nx), item_row(nx) * 128);
                    return nx;
                };
                int nxt = first_item();
                while (true) {
                    const int it = nxt >= 0 ? nxt : fetch();
                    nxt = -1;
                    const int type = item_type(it), m = item_row(it), c = item_col(it);
                    const int asc = item_asc(it), nu = type == T_ATTN ? 2 * m + 2 : 0;
                    const int uend = nu + ((type == T_ATTN ? m < 2 : pv_grp >= 0) ? 3 : 0), ureq = 2 * max(m - 2 - (asc & m), 0);
#pragma unroll 1
                    for (int u = 0; u < uend; u++) {
                        int grp = pv_grp, row = pv_row;
                        bool shared = pv_shared;
                        if (u >= nu) {
                            if (u == nu + 1) pv_grp = -1;
                            else if (peer_longer) { grp = -1; shared = false; }
                            else continue;
                        } else {
                            const int j = asc ? u >> 1 : m - (u >> 1);
                            if (u & 1) {
                                pv_grp = G_V + c; pv_row = j * 128; pv_shared = j != (m | 1);
                                peer_longer = asc & ~m & 1;
                                if (u == nu - 1 && (m & 1) && item_type(nxt) == T_END) mbar_arrive_cluster_n_if(lane == 0, bars0 + B_WANT, 2);
                                if (grp < 0) continue;
                            } else {
                                if (u == ureq) request();
                                if (u == 2 * m && m > 0) nxt = fetch();
                                grp = G_K + c; row = j * 128; shared = j != (m | 1);
                            }
                        }
                        load_kv(grp, row, shared);
                    }
                    if (type == T_END) break;
                    if (type == T_ATTN) {
                        need_a = 1;
                    } else if (type == T_LOCAL) {
                        if (held_type == T_B && !(it & ITEM_READY)) held_type = T_END;
                        request();
#pragma unroll 1
                        for (uint32_t st = 0; st < 4; st++) {
                            acquire_g(st, false);
                            const uint32_t dst = sb + st * GST_BYTES, fb = bars + B_GFULL + 8 * st;
                            warp_expect_tx(fb, st == 0 ? 32768 + 512 : st == 3 ? 0 : 4 * LOC_PLANE);
                            if (st == 3) break;
                            if (st == 0) warp_bulk_load(dst + 4 * LOC_PLANE, &g_gate[m * 128], 512, fb);
#pragma unroll 1
                            for (int i = 0; i < 4; i++)
                                warp_tma_load(dst + i * LOC_PLANE, &prm.m[st ? M_SCR_LOC : M_SCR_LOQ], fb, i * 64, m * 64 - (st ? 8 : 0), G_B + 8 * st + c);
                        }
                        gph ^= 1;
                        need_g = 63;
                    } else {
                        const int nk = type == T_K || type == T_V ? 8 : 16;
                        const CUtensorMap* ma = &prm.m[nk == 8 ? M_C : M_X];
                        const CUtensorMap* mb = &prm.m[type == T_Q ? M_WQ : type == T_K ? M_WUK : type == T_V ? M_WUV : M_WQKV];
                        for (int k = k0; k < nk; k++) {
                            if (k == nk - 3) request();
                            const uint32_t st = k & 3;
                            uint32_t dst = sb + st * GST_BYTES, fb = bars + B_GFULL + 8 * st, dstb = dst + 16384 + prank * 16384;
                            int a0 = k * 64, a1 = m * 128, b2 = c * 4 + 2 * prank;
                            asm volatile("" : "+r"(dst), "+r"(fb), "+r"(dstb), "+r"(a0), "+r"(a1), "+r"(b2), "+l"(ma), "+l"(mb));
                            acquire_g(st, true);
                            warp_expect_tx(fb, GST_BYTES);
                            warp_tma_load(dst, ma, fb, a0, a1, 0);
                            warp_tma_load_pair(dstb, mb, fb, 0, a0, b2);
                            if (st == 3) gph ^= 1;
                        }
                        need_g = 63;
                        held_type = type;
                        k0 = 0;
                    }
                }
                if (!need_a) request();
                const int it = __shfl_sync(0xffffffffu, next_item(lane == 0), 0);
                int nk = 0;
                if (item_type(it) == T_OUT) {
                    const int m = item_row(it), c = item_col(it), half = c & 1;
                    nk = 80;
                    for (int k = 0; k < nk; k++) {
                        if (k == K_SPLIT) nk = 2 * TRIPLES + (__shfl_sync(0xffffffffu, next_item(lane == 0), 0) & 127);
                        const int kn = k + 2 * TRIPLES - nk, first = kn >= 0 && !(kn & 1);
                        const int s = kn >= 0 ? WIDE + (3 * kn + 1) / 2 : half ? WIDE - 1 - k : k;
                        const uint32_t sa = prm.ostep[s], sa2 = prm.ostep[s + first], sw = prm.ostep[s - (kn >= 0 && !first ? prank : 0)];
                        for (unsigned n = 0; !(inputs_seen(sa >> 6, n) >> (sa >> 1 & 31) & 1);) {}
                        if (first) for (unsigned n = 0; !(inputs_seen(sa2 >> 6, n) >> (sa2 >> 1 & 31) & 1);) {}
                        const uint32_t st = k & 3;
                        uint32_t dst = sb + st * GST_BYTES, fb = bars + B_GFULL + 8 * st;
                        uint32_t dstb = dst + 16384 + (first ? 0 : prank * 16384), skipb = first && (kn >> 1 & 1) != prank;
                        int a0 = (sa & 1) * 64, a1 = m * 128, a2 = (sa >> 1) + (sa < 64 ? G_CTX : G_LOC - 32);
                        int b1 = (sw & 63) * 64, b2 = (c >> 1) * 4 + 2 * (kn >= 0 ? half : half ^ prank);
                        const CUtensorMap* mb = &prm.m[sw >= 64 ? M_WOB : M_WO];
                        asm volatile("" : "+r"(dst), "+r"(fb), "+r"(dstb), "+r"(skipb), "+r"(a0), "+r"(a1), "+r"(a2), "+r"(b1), "+r"(b2), "+l"(mb));
                        acquire_g(st, true);
                        warp_expect_tx(fb, GST_BYTES);
                        warp_tma_load(dst, tile_map, fb, a0, a1, a2);
                        if (!skipb) warp_tma_load_pair(dstb, mb, fb, 0, b1, b2);
                        if (first) warp_tma_load(dst + 32768, tile_map, fb, (sa2 & 1) * 64, a1, (sa2 >> 1) + (sa2 < 64 ? G_CTX : G_LOC - 32));
                        if (k < K_SPLIT && lane == 0 && !prank)
                            asm volatile("st.relaxed.gpu.global.u32 [%0], %1;" :: "l"(&g_sync.step[0][0] + m * 4 + c), "r"(k) : "memory");
                        if (k == K_MEET) request();
                        if (PF_NAR && (uint32_t)(k - PF_NAR) < (3 * TRIPLES + 1) / 2) {
                            const uint32_t g = prm.ostep[79 - 2 * (k - PF_NAR)] >> 1;
                            warp_prefetch((const char*)g_scr + (uint32_t)((G_CTX + g) * (SEQ * 256) + m * 32768 + c * 4096), 4096);
                            warp_prefetch(prm.wo + (uint32_t)(g * 262144 + (m * 8 + c) * 2048), 2048);
                        }
                        if (st == 3) gph ^= 1;
                    }
                    for (unsigned n = 0; ~inputs_seen(0, n) || inputs_seen(1, n) != 255;) {}
                }
                for (uint32_t st = 0; st < 4; st++) { mbar_wait(bars + B_GEMPTY + 8 * st, gph ^ (st < (nk & 3))); mbar_wait(bars + B_AEMPTY + 16 + 8 * st, a_parity(2 + st)); }
                unsigned left = 0;
                if (lane == 0) left = atomicAdd(&g_sync.done, 1u);
                if (__shfl_sync(0xffffffffu, left, 0) == NCTA - 1)
                    for (int i = lane; i < sizeof(Sync) / 8; i += 32) ((unsigned long long*)&g_sync)[i] = 0;
            }
        } else if (warp <= 2) {
            if (blockIdx.x < SEQ / 16) {
                const uint32_t r0 = 16 * blockIdx.x + 8 * (warp - 1), gbuf = bars + SM_GATE + 4 * (r0 & 15);
                float z[4];
#pragma unroll 1
                for (uint32_t i = 0; i < 8; i++) {
                    const uint32_t off = (i & 3) * 512 + lane * 16;
                    const uint4* xp = (const uint4*)((const char*)prm.x + ((r0 + (i & 4)) * 2048 + off));
                    const uint4 wv = __ldg((const uint4*)((const char*)prm.gate_w + off));
                    uint4 xv[4];
#pragma unroll
                    for (int r = 0; r < 4; r++) { xv[r] = __ldg(xp + r * 128); if (!(i & 3)) z[r] = 0.f; }
                    const uint32_t ws[4] = {wv.x, wv.y, wv.z, wv.w};
#pragma unroll
                    for (int e = 0; e < 4; e++)
#pragma unroll
                        for (int r = 0; r < 4; r++) {
                            const uint32_t xs = e == 0 ? xv[r].x : e == 1 ? xv[r].y : e == 2 ? xv[r].z : xv[r].w;
                            z[r] = fmaf(__uint_as_float(xs << 16), __uint_as_float(ws[e] << 16), z[r]);
                            z[r] = fmaf(__uint_as_float(xs & 0xffff0000u), __uint_as_float(ws[e] & 0xffff0000u), z[r]);
                        }
                    if ((i & 3) == 3) {
#pragma unroll
                        for (int o = 16; o > 0; o >>= 1)
#pragma unroll
                            for (int r = 0; r < 4; r++) z[r] += __shfl_xor_sync(0xffffffffu, z[r], o);
                        const float zr = lane & 2 ? (lane & 1 ? z[3] : z[2]) : (lane & 1 ? z[1] : z[0]);
                        asm volatile("st.shared.f32 [%0], %1;" :: "r"(gbuf + 4 * ((i & 4) + (lane & 3))), "f"(1.f / (1.f + __expf(-zr))) : "memory");
                    }
                }
                fence_proxy_async_smem();
                __syncwarp();
                warp_bulk_store((char*)g_gate + 4 * r0, gbuf, 32);
                bulk_commit();
                bulk_wait<0>();
                __syncwarp();
                if (lane == 0) red_add(&g_sync.count[3], 1);
            }
            __syncwarp();
            {
                const int w = warp - 1;
                uint32_t sph = 0, aph = 0, nann = 0, nattn = 0;
                int unsent = 0, nunsent = 0;
                bool urgent = false;
                auto announce = [&]() {
                    if (!urgent) return;
                    bulk_wait<0>();
                    __syncwarp();
                    const uint32_t hb = bars + B_HALF + 8 * (nann & 3);
                    if (w == 0) {
                        mbar_arrive_if(lane == 0, hb);
                    } else {
                        mbar_wait(hb, (nann >> 2) & 1);
                        const uint32_t type = item_type(unsent), m = item_row(unsent), c = item_col(unsent);
                        const uint32_t word = type < T_B ? c >> 3 : type == T_B ? 2 : offsetof(Sync, ctx) / 8 + m;
                        const uint32_t bit = type < T_B ? 8 * (c & 7) : type == T_B ? 4 * m : type == T_LOCAL ? 32 + c : c;
                        if (lane < nunsent) red_add((unsigned long long*)((char*)&g_sync + 8 * word), 1ull << bit);
                        __syncwarp();
                    }
                    nann++;
                    nunsent = 0; urgent = false;
                };
                auto store_item = [&](int it, bool borrow, bool now) {
                    const int type = item_type(it), m = item_row(it), c = item_col(it);
                    const int npair = type < T_OUT ? 2 : 1;
                    const bool local = type == T_LOCAL;
                    const int grp = type == T_Q ? G_Q + 2 * c : type == T_K ? G_K + 2 * c : type == T_V ? G_V + 2 * c : type == T_B ? G_B + 2 * c
                                  : type == T_ATTN ? G_CTX + c : G_LOC + c;
                    for (int pr = 0; pr < npair; pr++) {
                        if (borrow && pr) {
                            mbar_wait(bars + B_ALT + 8 * w, aph);
                            aph ^= 1;
                            for (int b = 0; b < 2; b++)
                                warp_tma_store(&prm.m[M_SCR_ST], sb + ((nattn & 1) ^ 1) * 32768 + w * 16384 + b * 8192, b * 64, m * 128 + w * 64, grp + 1);
                            bulk_commit();
                            bulk_wait_read<0>();
                            __syncwarp();
                            mbar_arrive_if(lane == 0, bars + B_QFREE);
                            break;
                        }
                        for (int b = 0; b < 2; b++) {
                            if (!__all_sync(0xffffffffu, mbar_test(bars + B_SFULL + 16 * w + 8 * b, sph))) announce();
                            mbar_wait(bars + B_SFULL + 16 * w + 8 * b, sph);
                            warp_tma_store(&prm.m[local ? M_SCR_LOQ : M_SCR_ST], sb + SM_STAGING + w * 16384 + b * 8192,
                                         local ? b * 128 + w * 64 : b * 64, local ? m * 64 : m * 128 + w * 64, grp + pr);
                            bulk_commit();
                            bulk_wait_read<0>();
                            __syncwarp();
                            mbar_arrive_if(lane == 0, bars + B_SEMPTY + 16 * w + 8 * b);
                        }
                        sph ^= 1;
                    }
                    announce();
                    if (lane == nunsent) unsent = it;
                    nunsent++;
                    urgent = now || nunsent == 32 || !local;
                };
                int held = first_item();
                while (true) {
                    if (!__all_sync(0xffffffffu, mbar_test(bars + B_IFULL + 8 * (qn % QDEPTH), (qn / QDEPTH) & 1))) announce();
                    const int it = __shfl_sync(0xffffffffu, next_item(lane == 0), 0), type = item_type(it);
                    const bool keep_held = type == T_LOCAL && (item_type(held) != T_B || (it & ITEM_READY));
                    if (type >= T_ATTN && held < 0 && nunsent) urgent = true;
                    for (int pass = held < 0 || keep_held; pass < 2; pass++) {
                        if (pass && (type < T_OUT || type == T_END)) break;
                        store_item(pass ? it : held, !pass && type == T_ATTN, type >= T_ATTN);
                    }
                    if (type == T_END) break;
                    nattn += type == T_ATTN;
                    if (!keep_held) held = type < T_OUT ? it : -1;
                }
                announce();
                if (item_type(next_item(lane == 0)) == T_OUT) next_item(lane == 0);
            }
        } else {
            if (elect_one()) {
                uint32_t ordy = 0;
                unsigned long long cnt_lo = 0, cnt_hi = 0;
                int late = 0;
                auto refresh = [&]() {
                    if (!late && cnt_lo == 0xccccccccccccccccull && cnt_hi == SEQ / 8) late = 1;
                    asm volatile("ld.acquire.gpu.global.v2.u64 {%0, %1}, [%2];" : "=l"(cnt_lo), "=l"(cnt_hi) : "l"(late ? &g_sync.count[0] : &g_sync.count[2]) : "memory");
                };
                auto inputs_ready = [&](int it) -> bool {
                    const int m = item_row(it), c = item_col(it);
                    if (item_type(it) == T_ATTN) return late && ((c < 16 ? cnt_lo : cnt_hi) >> (4 * (c & 14)) & 255) == 48;
                    return late || (cnt_hi == SEQ / 8 && (cnt_lo >> (4 * m) & 15) == 12 && (cnt_lo >> (4 * max(m - 1, 0)) & 15) == 12);
                };
                auto publish = [&](int it, int step) {
                    const uint32_t slot = qn % QDEPTH;
                    mbar_wait(bars + B_IEMPTY + 8 * slot, ((qn / QDEPTH) & 1) ^ 1);
                    for (uint32_t r = 0; r < 2; r++) {
                        const uint32_t rb = map_cta(bars, r);
                        asm volatile("mbarrier.arrive.expect_tx.shared::cluster.b64 _, [%0], 4;" :: "r"(rb + B_IFULL + 8 * slot) : "memory");
                        asm volatile("st.async.shared::cluster.mbarrier::complete_tx::bytes.u32 [%0], %1, [%2];"
                                     :: "r"(rb + SM_QUEUE + 4 * slot), "r"(it + r * step), "r"(rb + B_IFULL + 8 * slot) : "memory");
                    }
                    qn++;
                };
                int asc = 1;
                int it;
                do {
                    if (rank == 0) {
                        mbar_wait(bars + B_WANT, qn & 1);
                        unsigned i;
                        asm volatile("atom.relaxed.gpu.global.add.u32 %0, [%1], 1;" : "=r"(i) : "l"(&g_sync.next) : "memory");
                        if (cnt_lo != 0x3030303030303030ull || cnt_hi != cnt_lo) refresh();
                        i += NPAIR;
                        const int pit = i < NITEMS ? prm.items[i] : T_END << 13, type = item_type(pit);
                        int step = type == T_LOCAL ? 16 : 1;
                        it = pit + (pit & (step == 1 ? 15 : 0x1f0));
                        if (type == T_ATTN) {
                            if (!asc) { it += 1; step = -1; }
                            it |= asc << 9;
                        }
                        asc = type != T_ATTN || item_row(pit) == 0 || !asc;
                        if (inputs_ready(it)) it |= ITEM_READY;
                        publish(it, step);
                    } else {
                        it = next_item(true);
                    }
                    if ((item_type(it) == T_ATTN || item_type(it) == T_LOCAL) && !(it & ITEM_READY)) {
                        unsigned n = 0;
                        while (!inputs_ready(it)) { refresh(); spin_guard(n); }
                        asm volatile("st.release.cta.shared.u32 [%0], %1;" :: "r"(bars + SM_ORDY + 4), "r"(ordy += 256) : "memory");
                    }
                } while (item_type(it) != T_END);
                if (PF_LOC && blockIdx.x < 128) {
                    prefetch_l2((const char*)g_scr + (uint32_t)(G_LOC * SEQ * 256 + blockIdx.x * 32768), 32768);
                    prefetch_l2(prm.wob + blockIdx.x * 16384, 16384);
                }
                if (rank == 0) {
                    mbar_wait(bars + B_WANT, qn & 1);
                    const unsigned i = atomicAdd(&g_sync.next_out, 1u), t = i < 32 ? 31 - i : i - 32;
                    it = i < 64 ? T_OUT << 13 | ((t & 3) * 2 + (i >> 5)) << 4 | (t >> 2) * 2 : T_END << 13;
                    publish(it, 1);
                } else {
                    it = next_item(true);
                }
                if (item_type(it) == T_OUT) {
                    const uint32_t m = item_row(it), half = item_col(it) & 1, tile = m * 2 + (item_col(it) >> 1);
                    unsigned* split = (unsigned*)((char*)g_sync.split + 4 * tile);
                    unsigned long long rdy = 0;
                    int state = rank ? 2 : 0;
                    for (unsigned n = 0; rdy != 0xffffffffffull || state < 2; spin_guard(n)) {
                        if (rdy != 0xffffffffffull) {
                            rdy = ld_acquire((const unsigned long long*)((char*)g_sync.ctx + 8 * m));
                            asm volatile("st.release.cta.shared.u64 [%0], %1;" :: "r"(bars + SM_ORDY), "l"(rdy) : "memory");
                        }
                        unsigned steps = 0;
                        if (state == 1) {
                            steps = ld_acquire(split);
                        } else if (state == 0 && mbar_test(bars + B_WANT, qn & 1)) {
                            state = 1;
                            unsigned seen;
                            asm volatile("atom.acq_rel.gpu.global.exch.b32 %0, [%1], 1;" : "=r"(seen) : "l"(split) : "memory");
                            if (seen) {
                                const unsigned long long v = ld_acquire((const unsigned long long*)((char*)g_sync.step + 8 * tile));
                                const int d = (int)(v >> 32) - (int)v;
                                steps = (WIDE + min(max(half ? d : -d, K_MEET - K_SPLIT), K_SPLIT - K_MEET)) >> 1;
                                atomicExch(split, WIDE - steps);
                            }
                        }
                        if (steps > 1) { publish(T_END << 13 | steps, 0); state = 2; PMARK(1, 0xF400 + steps); }
                    }
                    if (rank) next_item(true);
                }
                if (rank == 0) for (uint32_t n = qn; n < qn + QDEPTH; n++) mbar_wait(bars + B_IEMPTY + 8 * (n % QDEPTH), ((n / QDEPTH) & 1) ^ 1);
            }
        }
    } else {
        reg_inc<232>();
        const int wg = (warp >> 2) - 1, wq = warp & 3;
        uint32_t gph = 0;
        uint32_t kvn = 0;
        const uint32_t dA = make_desc(sb + wg * 8192, 16);
        uint32_t ti = 0;
        uint32_t sph = 1;
        const uint32_t stg = sb + SM_STAGING + wg * 16384;
        const uint32_t stg_lane = stg + (wq * 16 + (lane & 15)) * 128 + (((lane >> 4) ^ (lane & 7)) << 4);
        auto write_blocks = [&](auto n, uint32_t off, const uint32_t* v) {
            uint32_t a = stg_lane;
            asm volatile("" : "+r"(a));
            a += off;
#pragma unroll
            for (int j = 0; j < decltype(n)::value; j++)
                stmatrix_x4((a ^ (32 * (j & 3))) + (j >> 2) * 8192, v[4 * j], v[4 * j + 1], v[4 * j + 2], v[4 * j + 3]);
        };
        auto release = [&](uint32_t bar) { mbar_arrive_if(lane == 0, bars + bar); };
        const uint32_t bars_lane = map_cta(bars, lane & 1);
        auto release_stage = [&](uint32_t st) { mbar_arrive_cluster_if(lane < 2, bars_lane + B_GEMPTY + 8 * st); };
        auto take_item = [&]() -> int {
            return __shfl_sync(0xffffffffu, next_item(lane == 0, false), 0);
        };
        auto stage_acquire = [&](int b) { mbar_spin(bars + B_SEMPTY + 16 * wg + 8 * b, sph); };
        auto stage_publish = [&](int b) {
            fence_proxy_async_smem();
            __syncwarp();
            release(B_SFULL + 16 * wg + 8 * b);
        };
        auto stage_chunk = [&](int b, const uint32_t* v) {
            stage_acquire(b);
            write_blocks(std::integral_constant<int, 4>(), b * 8192, v);
            stage_publish(b);
            if (b) sph ^= 1;
        };
        auto stage_pair = [&](const uint32_t* v) {
            stage_acquire(0); stage_acquire(1);
            write_blocks(std::integral_constant<int, 8>(), 0, v);
            fence_proxy_async_smem();
            __syncwarp();
            mbar_arrive_if(lane < 2, bars + B_SFULL + 16 * wg + 8 * lane);
            sph ^= 1;
        };
        auto gemm_step = [&](float (&acc)[128], uint32_t dB, int& k) {
            const uint32_t st = k & 3;
            wgmma_wait<0>();
            release_stage((k - 1) & 3);
            mbar_spin(bars + B_GFULL + 8 * st, gph);
            const uint64_t da = full_desc(dA + st * (GST_BYTES >> 4)), db = full_desc(dB + st * (GST_BYTES >> 4));
            wgmma_fence();
#pragma unroll
            for (int kk = 0; kk < 4; kk++) wgmma_ss_n256_tb(acc, da + 2 * kk, db + 128 * kk, 1);
            wgmma_commit();
            gph ^= st == 3;
            k++;
        };
        if (wg == 1) bar_arrive(1, 256);
        int it = first_item();
        while (item_type(it) != T_END) {
            if (item_type(it) <= T_LOCAL) {
                float acc[128];
                uint32_t pk[64];
                bool pending = false;
                bool held_b = false;
                zero_regs(pk);
                const uint32_t dB = make_desc(sb + 16384, 8192);
                do {
                    const int type = item_type(it);
                    if (type == T_LOCAL) {
                        int ln = lane;
                        asm volatile("" : "+r"(ln));
                        const int g = ln >> 2, t = ln & 3, par = wq & 1;
                        const uint32_t hc = (wq >> 1) * 4, pl = sb + (par * 2 + wg) * LOC_PLANE;
                        const uint32_t a16 = (ln & 15) * 128 + (((hc + (ln >> 4)) ^ (ln & 7)) << 4), a8 = (ln & 7) * 128 + (((hc + (ln >> 3)) ^ (ln & 7)) << 4);
                        const bool first0 = 2 * t > g, first1 = 2 * t + 1 > g;
                        const uint32_t fmask = (first0 ? 0xffffu : 0u) | (first1 ? 0xffff0000u : 0u);
                        const bool edge = item_row(it) == 0;
                        uint32_t q[4][2][4], kf[9][4], vf[9][4];
                        float w[8];
                        mbar_spin(bars + B_GFULL, gph);
#pragma unroll
                        for (int u = 0; u < 4; u++) { ldsm_x4(q[u][0], pl + u * 2048 + a16); ldsm_x4(q[u][1], pl + u * 2048 + (a16 ^ 32)); }
#pragma unroll
                        for (int j = 0; j < 8; j++) w[j] = lds_f32(sb + 4 * LOC_PLANE + 4 * (2 * g + par) + 64 * j);
                        __syncwarp();
                        release_stage(0);
                        mbar_spin(bars + B_GFULL + 8, gph);
#pragma unroll
                        for (int n = 0; n < 9; n++) ldsm_x4(kf[n], pl + GST_BYTES + n * 1024 + a8);
                        __syncwarp();
                        release_stage(1);
                        float s[8][2];
#pragma unroll
                        for (int u = 0; u < 4; u++) {
                            float d[3][4];
#pragma unroll
                            for (int nt = 0; nt < 3; nt++) {
                                mma_k16_init(d[nt], q[u][0], kf[2 * u + nt][0], kf[2 * u + nt][1]);
                                mma_k16(d[nt], q[u][1], kf[2 * u + nt][2], kf[2 * u + nt][3]);
                            }
                            if (u == 0 && edge) { d[0][0] = -INFINITY; d[0][1] = -INFINITY; }
                            s[2 * u][0] = first0 ? d[0][0] : d[1][0]; s[2 * u][1] = first1 ? d[0][1] : d[1][1];
                            s[2 * u + 1][0] = first0 ? d[1][2] : d[2][2]; s[2 * u + 1][1] = first1 ? d[1][3] : d[2][3];
                        }
                        mbar_spin(bars + B_GFULL + 16, gph);
#pragma unroll
                        for (int u = 0; u < 4; u++) { ldsm_x4_t(vf[2 * u], pl + 2 * GST_BYTES + u * 2048 + a16); ldsm_x4_t(vf[2 * u + 1], pl + 2 * GST_BYTES + u * 2048 + (a16 ^ 32)); }
                        ldsm_x4_t(vf[8], pl + 2 * GST_BYTES + 8192 + a8);
                        __syncwarp();
                        release_stage(2);
                        float x[8];
#pragma unroll
                        for (int j = 0; j < 8; j++) x[j] = fmaxf(s[j][0], s[j][1]);
#pragma unroll
                        for (int o = 1; o < 4; o *= 2)
#pragma unroll
                            for (int j = 0; j < 8; j++) x[j] = fmaxf(x[j], __shfl_xor_sync(0xffffffffu, x[j], o));
#pragma unroll
                        for (int j = 0; j < 8; j++) {
                            const float n = x[j] * -LOC_SCALE;
                            s[j][0] = ex2(fmaf(s[j][0], LOC_SCALE, n)); s[j][1] = ex2(fmaf(s[j][1], LOC_SCALE, n));
                            x[j] = s[j][0] + s[j][1];
                        }
#pragma unroll
                        for (int o = 1; o < 4; o *= 2)
#pragma unroll
                            for (int j = 0; j < 8; j++) x[j] += __shfl_xor_sync(0xffffffffu, x[j], o);
                        mbar_spin(bars + B_GFULL + 24, gph);
                        release_stage(3);
                        it = take_item();
                        uint32_t ob[4][8];
#pragma unroll
                        for (int u = 0; u < 4; u++) {
                            const float r0 = rcp(x[2 * u]), r1 = rcp(x[2 * u + 1]), f0 = fmaf(-w[2 * u], r0, r0), f1 = fmaf(-w[2 * u + 1], r1, r1);
                            const uint32_t p0 = pack_bf16(s[2 * u][0] * f0, s[2 * u][1] * f0), p1 = pack_bf16(s[2 * u + 1][0] * f1, s[2 * u + 1][1] * f1);
                            const uint32_t pa[4] = {p0 & fmask, 0, p0 & ~fmask, p1 & fmask};
#pragma unroll
                            for (int c = 0; c < 4; c++) {
                                float ol[4];
                                mma_k16_init(ol, pa, vf[2 * u + (c >> 1)][2 * (c & 1)], vf[2 * u + (c >> 1)][2 * (c & 1) + 1]);
                                mma_k8(ol, 0, p1 & ~fmask, u < 3 ? vf[2 * u + 2 + (c >> 1)][2 * (c & 1)] : vf[8][c]);
                                ob[u][2 * c] = pack_bf16(ol[0], ol[1]);
                                ob[u][2 * c + 1] = pack_bf16(ol[2], ol[3]);
                            }
                        }
                        stage_acquire(0); stage_acquire(1);
#pragma unroll
                        for (int u = 0; u < 4; u++) {
                            stmatrix_x4(stg + par * 8192 + u * 2048 + a16, ob[u][0], ob[u][1], ob[u][2], ob[u][3]);
                            stmatrix_x4(stg + par * 8192 + u * 2048 + (a16 ^ 32), ob[u][4], ob[u][5], ob[u][6], ob[u][7]);
                        }
                        fence_proxy_async_smem();
                        __syncwarp();
                        mbar_arrive_if(lane < 2, bars + B_SFULL + 16 * wg + 8 * lane);
                        bar_sync(4, 256);
                        sph ^= 1; gph ^= 1;
                        continue;
                    }
                    mbar_spin(bars + B_GFULL, gph);
                    bool more;
                    do {
                        wgmma_fence();
                        wgmma_ss_n256_tb_init(acc, full_desc(dA), full_desc(dB));
#pragma unroll
                        for (int kk = 1; kk < 4; kk++) wgmma_ss_n256_tb(acc, full_desc(dA) + 2 * kk, full_desc(dB) + 128 * kk, 1);
                        wgmma_commit();
                        const int nk = item_type(it) == T_K || item_type(it) == T_V ? 8 : 16;
                        int k = 1;
                        do {
                            if (pending) {
                                const int kf = k - 1 - wg;
                                if (kf == 0) stage_chunk(0, pk);
                                else if (kf == 1) stage_chunk(1, pk + 16);
                                else if (kf == KF2) stage_chunk(0, pk + 32);
                                else if (kf == KF2 + 1) stage_chunk(1, pk + 48);
                            }
                            gemm_step(acc, dB, k);
                        } while (k < nk);
                        held_b = item_type(it) == T_B;
                        const bool is_q = item_type(it) == T_Q;
                        it = take_item();
                        more = item_type(it) < T_LOCAL;
                        if (more) mbar_spin(bars + B_GFULL, gph);
                        wgmma_wait<0>();
                        fence_regs(acc);
                        release_stage(3);
                        if (is_q) {
#pragma unroll
                            for (int j = 0; j < 128; j++) acc[j] *= SM_SCALE;
                        }
#pragma unroll
                        for (int j = 0; j < 64; j++) pk[j] = pack_bf16(acc[2 * j], acc[2 * j + 1]);
                        pending = true;
                    } while (more);
                } while (item_type(it) < T_LOCAL || (item_type(it) == T_LOCAL && (!held_b || (it & ITEM_READY))));
                if (pending) { stage_chunk(0, pk); stage_chunk(1, pk + 16); }
                if (pending && item_type(it) == T_ATTN) {
                    mbar_spin(bars + B_GEMPTY, gph ^ 1); mbar_spin(bars + B_GEMPTY + 8, gph ^ 1);
                    write_blocks(std::integral_constant<int, 8>(), ((ti & 1) ^ 1) * 32768 - SM_STAGING, pk + 32);
                    fence_proxy_async_smem();
                    __syncwarp();
                    release(B_ALT + 8 * wg);
                } else if (pending) {
                    stage_chunk(0, pk + 32); stage_chunk(1, pk + 48);
                }
            } else {
                float o[64], s[64];
                uint32_t pa[32], pb[32];
                zero_regs(o); zero_regs(s); zero_regs(pa);
                float n0 = 0.f, n1 = 0.f;
                bool shifted = false;
                float l0 = 1.f, l1 = 1.f, f0 = 0.f, f1 = 0.f, g0 = 0.f, g1 = 0.f;
                uint32_t has_pv = 0;
                int first = 0;
                int pending = 0;
                const uint32_t dK = make_desc(sb + SM_KV, 16), dV = make_desc(sb + SM_KV, 16384);
                const uint32_t lane_off = bars_lane - bars + B_AEMPTY - B_AFULL;
                int cur = 0;
                uint32_t qoff = 0;
                const int row = wg * 64 + wq * 16 + (lane >> 2), thr = row - (lane & 3) * 2;
                auto kv_wait = [&](uint32_t n) { mbar_spin(bars + B_AFULL + 16 + 8 * (n & 3), (n >> 2) & 1); };
                auto kv_release = [&](uint32_t n) { mbar_arrive_cluster_if(lane < 2, bars_lane + B_AEMPTY + 16 + 8 * (n & 3)); };
                struct Slot { uint32_t bar, par, off; } slot[4];
                auto align = [&]() {
#pragma unroll
                    for (uint32_t i = 0; i < 4; i++) {
                        const uint32_t n = kvn + (i == 1 ? has_pv : i);
                        slot[i].bar = bars + B_AFULL + 16 + 8 * (n & 3); slot[i].par = (n >> 2) & 1; slot[i].off = (n & 3) * 2048;
                    }
                };
                align();
                auto pack_o = [&](uint32_t (&v)[32]) {
#pragma unroll
                    for (int j = 0; j < 16; j++) {
                        v[2 * j] = pack_bf16(o[4 * j] * f0, o[4 * j + 1] * f0);
                        v[2 * j + 1] = pack_bf16(o[4 * j + 2] * f1, o[4 * j + 3] * f1);
                    }
                };
                auto scales = [&]() { f0 = g0 * rcp(quad_sum(l0)); f1 = g1 * rcp(quad_sum(l1)); };
                auto step = [&](auto even, uint32_t (&pin)[32], uint32_t (&pout)[32], bool fresh, bool diag) {
                    constexpr bool EVEN = decltype(even)::value;
                    Slot& sk = slot[EVEN ? 0 : 2];
                    Slot& sv = slot[EVEN ? 1 : 3];
                    kvn += EVEN ? 1 + has_pv : 2;
                    mbar_spin(sk.bar, sk.par);
                    bar_sync(1 + wg, 256);
                    qk_gemm(s, dA + qoff, dK + sk.off);
                    if (EVEN && fresh) scales();
                    if (!EVEN && pending) { pack_o(pout); stage_pair(pout); }
                    mbar_spin(sv.bar, sv.par);
                    pv_gemm(o, pin, dV + sv.off, EVEN || !first);
                    bar_arrive(2 - wg, 256);
                    sk.par ^= 1; sv.par ^= 1;
                    wgmma_wait<1>();
                    fence_regs(s);
                    mbar_arrive_cluster_if(lane < 2 && (!EVEN || has_pv), sk.bar + lane_off);
                    if (diag) causal_mask(s, thr, wg);
                    if (EVEN && fresh) {
                        row_max<2>(s, n0, n1);
                        if (fabsf(n0) <= REF_RANGE) n0 = 0.f;
                        if (fabsf(n1) <= REF_RANGE) n1 = 0.f;
                        shifted = __any_sync(0xffffffffu, n0 != 0.f || n1 != 0.f);
                        l0 = 0.f; l1 = 0.f;
                    }
                    if (shifted) shift_rows(s, n0, n1);
                    float r0, r1;
                    exp_pack(pout, s, r0, r1);
                    if (__any_sync(0xffffffffu, fmaxf(r0, r1) >= SUM_LIMIT)) {
                        float x0, x1;
                        row_max<16>(s, x0, x1);
                        x0 = fmaxf(x0, 0.f); x1 = fmaxf(x1, 0.f);
                        float a0 = ex2(-x0), a1 = ex2(-x1);
                        n0 += x0; n1 += x1;
                        shifted = true;
                        l0 *= a0; l1 *= a1;
                        if (EVEN && fresh) { a0 = 1.f; a1 = 1.f; }
                        wgmma_wait<0>();
                        fence_regs(o);
#pragma unroll
                        for (int q = 0; q < 16; q++) { o[4 * q] *= a0; o[4 * q + 1] *= a0; o[4 * q + 2] *= a1; o[4 * q + 3] *= a1; }
                        shift_rows(s, x0, x1);
                        exp_pack(pout, s, r0, r1);
                    }
                    l0 += r0; l1 += r1;
                    wgmma_wait<0>();
                    fence_regs(o);
                    fence_regs(pin);
                    mbar_arrive_cluster_if(lane < 2, sv.bar + lane_off);
                };
                auto copy_p = [&]() {
#pragma unroll
                    for (int j = 0; j < 32; j++) pa[j] = pb[j] ^ prm.zero;
                };
                int rem = 0;
                while (true) {
                    const bool fresh = rem == 0;
                    if (fresh) {
                        if (has_pv) {
                            release(B_AEMPTY + 8 * ((ti - 1) & 1));
                            it = take_item();
                            if (item_row(cur) < 2 || item_type(it) != T_ATTN) break;
                        }
                        cur = it;
                        qoff = (ti & 1) * 2048;
                        mbar_spin(bars + B_AFULL + 8 * (ti & 1), (ti >> 1) & 1);
                    }
                    step(std::true_type(), pa, pb, fresh, fresh ? !item_asc(cur) || item_row(cur) == 0 : item_asc(cur) && rem == 1);
                    first = fresh;
                    if (fresh) {
                        pending = has_pv; has_pv = 1;
                        if (!pending) { kvn -= 2; align(); kvn += 2; slot[0].par ^= 1; slot[1].par ^= 1; }
                        rem = item_row(cur);
                        g0 = lds_f32(bars + SM_GATE + (ti & 1) * 512 + 4 * row); g1 = lds_f32(bars + SM_GATE + (ti & 1) * 512 + 4 * row + 32);
                        ti++;
                        if (rem == 0) {
                            copy_p();
                            continue;
                        }
                    } else if (--rem == 0) {
                        copy_p();
                        align();
                        continue;
                    }
                    step(std::false_type(), pb, pa, false, item_asc(cur) && rem == 1);
                    pending = 0; first = 0;
                    rem--;
                }
                const uint32_t skip = item_asc(cur) & ~item_row(cur) & 1;
                kvn += skip;
#pragma unroll 1
                for (int pass = pending ? 0 : 1; pass < 2; pass++) {
                    if (pass) {
                        kv_wait(kvn);
                        pv_gemm(o, pa, dV + (kvn & 3) * 2048, !first);
                        scales();
                        wgmma_wait<0>();
                        fence_regs(o);
                        kv_release(kvn);
                        kvn += 1 + skip;
                    }
                    pack_o(pb);
                    stage_pair(pb);
                }
            }
        }
        it = take_item();
        if (item_type(it) == T_OUT) {
            float acc[128];
            const uint32_t dB = make_desc(sb + 16384, 8192);
            mbar_spin(bars + B_GFULL, gph);
            wgmma_fence();
            wgmma_ss_n256_tb_init(acc, full_desc(dA), full_desc(dB));
#pragma unroll
            for (int kk = 1; kk < 4; kk++) wgmma_ss_n256_tb(acc, full_desc(dA) + 2 * kk, full_desc(dB) + 128 * kk, 1);
            wgmma_commit();
            uint32_t ln;
            asm volatile("mov.u32 %0, %%laneid;" : "=r"(ln));
            const uint32_t slot = (it & 127) * 32768 + (wg * 128 + wq * 32 + ln) * 16;
            char* const mine = (char*)g_part + slot;
            int k = 1, nk = 80;
            do {
                if (k == K_MEET - 5) {
#pragma unroll
                    for (int j = 0; j < 8; j++) st_b128(mine + j * 4096, 0, 0, 0, 0);
                    __syncwarp();
                }
                if (k == K_SPLIT) nk = take_item() & 127;
                gemm_step(acc, dB, k);
            } while (k < nk);
            auto triple = [&](uint32_t nrel) {
                const uint32_t s0 = k & 3, s1 = (k + 1) & 3, o0 = s0 * (GST_BYTES >> 4), o1 = s1 * (GST_BYTES >> 4);
                wgmma_wait<0>();
                mbar_arrive_cluster_if(ln < nrel, bars_lane + B_GEMPTY + 8 * ((k - 1 - (ln >> 1)) & 3));
                mbar_spin(bars + B_GFULL + 8 * s0, gph);
                gph ^= s0 == 3;
                wgmma_fence();
#pragma unroll
                for (int kk = 0; kk < 4; kk++) wgmma_ss_n128_lo_tb(acc, full_desc(dA + o0) + 2 * kk, full_desc(dB + o0) + 128 * kk, 1);
                mbar_spin(bars + B_GFULL + 8 * s1, gph);
                gph ^= s1 == 3;
                wgmma_fence();
#pragma unroll
                for (int kk = 0; kk < 4; kk++) wgmma_ss_n128_lo_tb(acc, full_desc(dA + o0 + 2048) + 2 * kk, full_desc(dB + o1 + 1024) + 128 * kk, 1);
#pragma unroll
                for (int kk = 0; kk < 4; kk++) wgmma_ss_n128_lo_tb(acc, full_desc(dA + o1) + 2 * kk, full_desc(dB + o1) + 128 * kk, 1);
                wgmma_commit();
                k += 2;
            };
            triple(2);
#pragma unroll
            for (int j = 0; j < 8; j++) {
                uint32_t v[4];
#pragma unroll
                for (int i = 0; i < 4; i++) {
                    asm volatile("" : "+f"(acc[64 + 8 * j + 2 * i]), "+f"(acc[65 + 8 * j + 2 * i]) :: "memory");
                    v[i] = pack_bf16(acc[64 + 8 * j + 2 * i], acc[65 + 8 * j + 2 * i]);
                }
                if (j == SPREAD) triple(4);
                else if (PACE && j) __nanosleep(PACE);
                st_b128(mine + j * 4096, ~v[0], v[1], v[2], v[3]);
            }
#pragma unroll 1
            for (int t = 2; t < TRIPLES; t++) triple(4);
            uint32_t pk[32];
            char* const other = (char*)g_part + (slot ^ (16 * 32768));
            while (true) {
                bool miss = false;
#pragma unroll
                for (int j = 0; j < 8; j++) ld_b128(other + j * 4096, pk[4 * j], pk[4 * j + 1], pk[4 * j + 2], pk[4 * j + 3]);
#pragma unroll
                for (int j = 0; j < 8; j++) miss |= pk[4 * j] == 0;
                if (!__any_sync(0xffffffffu, miss)) break;
                while (__any_sync(0xffffffffu, pk[28] == 0)) ld_b128(other + 7 * 4096, pk[28], pk[29], pk[30], pk[31]);
            }
#pragma unroll
            for (int j = 0; j < 32; j++) {
                const uint32_t v = j & 3 ? pk[j] : ~pk[j];
                acc[64 + 2 * j] = __uint_as_float(v << 16); acc[65 + 2 * j] = __uint_as_float(v & 0xffff0000u);
                asm volatile("" : "+f"(acc[64 + 2 * j]), "+f"(acc[65 + 2 * j]) :: "memory");
            }
            stage_acquire(0); stage_acquire(1);
            wgmma_wait<0>();
#pragma unroll
            for (int j = 0; j < 64; j++) asm volatile("" : "+f"(acc[j]) :: "memory");
            mbar_arrive_cluster_if(ln < 4, bars_lane + B_GEMPTY + 8 * ((k - 1 - (ln >> 1)) & 3));
#pragma unroll
            for (int j = 0; j < 32; j++)
                pk[j] = pack_bf16(acc[2 * j] + acc[64 + 2 * j], acc[2 * j + 1] + acc[65 + 2 * j]);
            write_blocks(std::integral_constant<int, 8>(), 0, pk);
            __syncwarp();
            uint4* dst = (uint4*)((char*)prm.out + (uint32_t)((item_row(it) * 128 + wg * 64 + wq * 16 + (ln >> 4)) * 2048 + item_col(it) * 256 + (ln & 15) * 16));
#pragma unroll
            for (int j = 0; j < 8; j++) {
                const int r = 2 * j + (ln >> 4);
                uint4 v;
                asm volatile("ld.shared.v4.u32 {%0, %1, %2, %3}, [%4];" : "=r"(v.x), "=r"(v.y), "=r"(v.z), "=r"(v.w)
                             : "r"(stg + wq * 2048 + r * 128 + (ln & 8) * 1024 + (((ln & 7) ^ (r & 7)) << 4)) : "memory");
                dst[j * 256] = v;
            }
        }
    }
}

typedef CUresult (*EncodeFn)(CUtensorMap*, CUtensorMapDataType, cuuint32_t, void*, const cuuint64_t*, const cuuint64_t*,
                             const cuuint32_t*, const cuuint32_t*, CUtensorMapInterleave, CUtensorMapSwizzle,
                             CUtensorMapL2promotion, CUtensorMapFloatOOBfill);

void encode3(EncodeFn fn, CUtensorMap* m, const void* ptr, uint64_t d0, uint64_t d1, uint64_t d2, uint64_t s1, uint64_t s2,
             uint32_t b0, uint32_t b1, uint32_t b2) {
    cuuint64_t dims[3] = {d0, d1, d2};
    cuuint64_t strides[2] = {s1, s2};
    cuuint32_t box[3] = {b0, b1, b2};
    cuuint32_t es[3] = {1, 1, 1};
    fn(m, CU_TENSOR_MAP_DATA_TYPE_BFLOAT16, 3, const_cast<void*>(ptr), dims, strides, box, es, CU_TENSOR_MAP_INTERLEAVE_NONE,
       CU_TENSOR_MAP_SWIZZLE_128B, CU_TENSOR_MAP_L2_PROMOTION_NONE, CU_TENSOR_MAP_FLOAT_OOB_FILL_NONE);
}
void map_act(EncodeFn fn, CUtensorMap* m, const void* p, int rows, int cols, int box_rows) {
    encode3(fn, m, p, cols, rows, 1, (uint64_t)cols * 2, (uint64_t)cols * rows * 2, 64, box_rows, 1);
}
void map_wgt(EncodeFn fn, CUtensorMap* m, const void* p, int K, int N) {
    encode3(fn, m, p, 64, K, N / 64, (uint64_t)N * 2, 128, 64, 64, 2);
}

void build_schedule(Params& p) {
    int n = 0;
    auto add = [&](int type, int col, int row) { p.items[n++] = (uint16_t)(type << 13 | col << 4 | row); };
    auto add_qkv = [&](int c) {
        for (int m = 0; m < 8; m++) add(T_Q, c, m);
        for (int m = 0; m < 8; m++) add(T_K, c, m);
        for (int m = 0; m < 8; m++) add(T_V, c, m);
    };
    int ldist = 200, ldist2 = 260, lstep = 8, beta = 26, tail = 32, late = 6, early = 8, epos = 100;
    int order[16] = {6, 7, 8, 9, 10, 11, 12, 13, 14, 15, 5, 4, 3, 2, 1, 0};
    uint16_t proj[480];
    for (int m = 0; m < 8; m++) for (int c = 0; c < 12; c++) add(T_B, c, m);
    for (int c = 0; c < 16; c++) add_qkv(c);
    for (int i = 0; i < 480; i++) proj[i] = p.items[i];
    n = 0;
    for (int i = 0, l = 0; i < 480; i++) {
        p.items[n++] = proj[i];
        for (; l < 64 && i >= (l < 40 ? ldist + lstep * l / 8 : ldist2 + lstep * (l - 40) / 8); l++) add(T_LOCAL, l & 3, l >> 2);
    }
    const int a0 = n;
    for (int key = 0; key < 4000; key++)
        for (int r = 0; r < 32; r++)
            for (int j = 7; j >= 0; j--)
                if ((j ? (7 - j) * 40 + r * beta : 3999) == key) add(T_ATTN, 2 * order[r >> 1] + (r & 1), j);
    int t0 = n;
    for (int work = 0; work < 32 * 136 * tail / 100;) work += 4 * (p.items[--t0] & 15) + 3;
    for (int i = t0 + 1; i < n; i++)
        for (int j = i; j > t0 && (p.items[j] & 15) > (p.items[j - 1] & 15); j--) { const uint16_t t = p.items[j]; p.items[j] = p.items[j - 1]; p.items[j - 1] = t; }
    for (int r = early - 1; r >= 0; r--) {
        const uint16_t t = p.items[n - 32 + early - 1];
        for (int j = n - 32 + early - 1; j > n - epos; j--) p.items[j] = p.items[j - 1];
        p.items[n - epos] = t;
    }
    for (int moved = 0; moved < 2 && late >= 0; moved++)
        for (int i = a0; i < n; i++)
            if (p.items[i] == (T_ATTN << 13 | (2 * order[15] + moved) << 4 | late)) {
                for (int j = i; j + 1 < n; j++) p.items[j] = p.items[j + 1];
                p.items[n - 1] = (uint16_t)(T_ATTN << 13 | (2 * order[15] + moved) << 4 | late);
                break;
            }
    for (int s = 0, lo = 0, hi = WIDE - 1; s < 80; s++) {
        const int r = s / 2, g = r < 8 ? 32 + r : 2 * order[r / 2 - 4] + (r & 1);
        p.ostep[s >= WIDE ? s : r & 1 ? hi-- : lo++] = (uint8_t)(2 * g + (s & 1));
    }
}

void build_params(Params& p, void* const* d_in, void* d_out) {
    void* fnp = nullptr;
    cudaDriverEntryPointQueryResult qr;
    cudaGetDriverEntryPoint("cuTensorMapEncodeTiled", &fnp, cudaEnableDefault, &qr);
    EncodeFn fn = (EncodeFn)fnp;
    void* scr = nullptr;
    cudaGetSymbolAddress(&scr, g_scr);
    map_act(fn, &p.m[M_X], d_in[0], SEQ, 1024, 128);
    map_act(fn, &p.m[M_C], d_in[1], SEQ, 512, 128);
    map_wgt(fn, &p.m[M_WQ], d_in[2], 1024, 4096);
    map_wgt(fn, &p.m[M_WUK], d_in[3], 512, 4096);
    map_wgt(fn, &p.m[M_WUV], d_in[4], 512, 4096);
    map_wgt(fn, &p.m[M_WO], d_in[5], 4096, 1024);
    map_wgt(fn, &p.m[M_WQKV], d_in[7], 1024, 3072);
    map_wgt(fn, &p.m[M_WOB], d_in[8], 1024, 1024);
    encode3(fn, &p.m[M_SCR_LD], scr, 128, SEQ, G_TOTAL, 256, (uint64_t)SEQ * 256, 64, 128, 1);
    encode3(fn, &p.m[M_SCR_LOC], scr, 256, SEQ / 2, G_TOTAL, 512, (uint64_t)SEQ * 256, 64, 72, 1);
    encode3(fn, &p.m[M_SCR_LOQ], scr, 256, SEQ / 2, G_TOTAL, 512, (uint64_t)SEQ * 256, 64, 64, 1);
    encode3(fn, &p.m[M_SCR_ST], scr, 128, SEQ, G_TOTAL, 256, (uint64_t)SEQ * 256, 64, 64, 1);
    p.x = (const __nv_bfloat16*)d_in[0];
    p.gate_w = (const __nv_bfloat16*)d_in[9];
    p.zero = 0;
    p.wo = (const char*)d_in[5];
    p.wob = (const char*)d_in[8];
    p.out = (__nv_bfloat16*)d_out;
    build_schedule(p);
}

}

extern "C" void kernel_launch(void* const* d_in, const int* in_sizes, int n_in, void* d_out, int out_size) {
    (void)in_sizes; (void)n_in; (void)out_size;
    Params p;
    build_params(p, d_in, d_out);
    cudaFuncSetAttribute(fused_kernel, cudaFuncAttributeMaxDynamicSharedMemorySize, SM_TOTAL);
    fused_kernel<<<NCTA, 384, SM_TOTAL>>>(p);
}
```

```cpp
#include <cuda_runtime.h>
#include <cuda_bf16.h>
#include <cuda.h>
#include <stddef.h>
#include <stdint.h>
#include <type_traits>

namespace {

constexpr int SEQ = 2048;
constexpr int G_Q = 0, G_K = 32, G_V = 64, G_B = 96, G_CTX = G_Q, G_LOC = G_B, G_TOTAL = 120;

__device__ __align__(1024) __nv_bfloat16 g_scr[(size_t)G_TOTAL * SEQ * 128];
__device__ __align__(128) float g_gate[SEQ];

__device__ __forceinline__ uint32_t smem_u32(const void* p) { return (uint32_t)__cvta_generic_to_shared(p); }
__device__ __forceinline__ bool elect_one() {
    uint32_t p;
    asm volatile("{\n.reg .pred P;\nelect.sync _|P, 0xffffffff;\nselp.u32 %0, 1, 0, P;\n}\n" : "=r"(p));
    return p != 0;
}
__device__ __forceinline__ void mbar_init(uint32_t bar, uint32_t count) {
    asm volatile("mbarrier.init.shared::cta.b64 [%0], %1;" :: "r"(bar), "r"(count) : "memory");
}
__device__ __forceinline__ void mbar_expect_tx(uint32_t bar, uint32_t bytes) {
    asm volatile("mbarrier.arrive.expect_tx.shared::cta.b64 _, [%0], %1;" :: "r"(bar), "r"(bytes) : "memory");
}
__device__ __forceinline__ uint32_t cluster_rank() { uint32_t r; asm("mov.u32 %0, %%cluster_ctarank;" : "=r"(r)); return r; }
__device__ __forceinline__ uint32_t map_cta(uint32_t addr, uint32_t cta) {
    uint32_t r; asm("mapa.shared::cluster.u32 %0, %1, %2;" : "=r"(r) : "r"(addr), "r"(cta)); return r;
}
__device__ __forceinline__ void mbar_arrive_cluster_if(bool pred, uint32_t cluster_bar) {
    asm volatile("{\n.reg .pred P;\nsetp.ne.u32 P, %1, 0;\n@P mbarrier.arrive.shared::cluster.b64 _, [%0];\n}\n"
                 :: "r"(cluster_bar), "r"((uint32_t)pred) : "memory");
}
__device__ __forceinline__ void mbar_arrive_cluster_n_if(bool pred, uint32_t cluster_bar, uint32_t count) {
    asm volatile("{\n.reg .pred P;\nsetp.ne.u32 P, %1, 0;\n@P mbarrier.arrive.shared::cluster.b64 _, [%0], %2;\n}\n"
                 :: "r"(cluster_bar), "r"((uint32_t)pred), "r"(count) : "memory");
}
__device__ __forceinline__ void mbar_arrive_if(bool pred, uint32_t bar) {
    asm volatile("{\n.reg .pred P;\nsetp.ne.u32 P, %1, 0;\n@P mbarrier.arrive.shared::cta.b64 _, [%0];\n}\n"
                 :: "r"(bar), "r"((uint32_t)pred) : "memory");
}
__device__ __forceinline__ bool mbar_test(uint32_t bar, uint32_t parity) {
    uint32_t ok;
    asm volatile("{\n.reg .pred P;\nmbarrier.test_wait.parity.shared::cta.b64 P, [%1], %2;\nselp.u32 %0, 1, 0, P;\n}\n"
                 : "=r"(ok) : "r"(bar), "r"(parity) : "memory");
    return ok != 0;
}
__device__ __forceinline__ void mbar_wait(uint32_t bar, uint32_t parity) {
    asm volatile("{\n.reg .pred P;\n.reg .u32 c;\n"
                 "mbarrier.try_wait.parity.shared::cta.b64 P, [%0], %1;\n"
                 "@P bra DONE;\n"
                 "mov.u32 c, 0;\n"
                 "SPIN:\n"
                 "mbarrier.try_wait.parity.shared::cta.b64 P, [%0], %1;\n"
                 "@P bra DONE;\n"
                 "add.u32 c, c, 1;\n"
                 "setp.lt.u32 P, c, 4194304;\n"
                 "@P bra SPIN;\n"
                 "trap;\n"
                 "DONE:\n}\n" :: "r"(bar), "r"(parity) : "memory");
}
__device__ __forceinline__ void mbar_spin(uint32_t bar, uint32_t parity) {
    asm volatile("{\n.reg .pred P;\n"
                 "SPIN:\n"
                 "mbarrier.try_wait.parity.shared::cta.b64 P, [%0], %1;\n"
                 "@!P bra SPIN;\n}\n" :: "r"(bar), "r"(parity) : "memory");
}
__device__ __forceinline__ void bar_sync(int id, int n) { asm volatile("bar.sync %0, %1;" :: "r"(id), "r"(n) : "memory"); }
__device__ __forceinline__ void bar_arrive(int id, int n) { asm volatile("bar.arrive %0, %1;" :: "r"(id), "r"(n) : "memory"); }
__device__ __forceinline__ void fence_proxy_async_smem() { asm volatile("fence.proxy.async.shared::cta;" ::: "memory"); }
__device__ __forceinline__ void tma_load_3d(uint32_t dst, const CUtensorMap* map, uint32_t bar, int c0, int c1, int c2) {
    asm volatile("cp.async.bulk.tensor.3d.shared::cluster.global.mbarrier::complete_tx::bytes [%0], [%1, {%3, %4, %5}], [%2];"
                 :: "r"(dst), "l"(map), "r"(bar), "r"(c0), "r"(c1), "r"(c2) : "memory");
}
__device__ __forceinline__ void warp_expect_tx(uint32_t bar, uint32_t bytes) {
    asm volatile("{\n.reg .pred P;\nelect.sync _|P, 0xffffffff;\n@P mbarrier.arrive.expect_tx.shared::cta.b64 _, [%0], %1;\n}\n"
                 :: "r"(bar), "r"(bytes) : "memory");
}
__device__ __forceinline__ void warp_tma_load(uint32_t dst, const CUtensorMap* map, uint32_t bar, int c0, int c1, int c2) {
    asm volatile("{\n.reg .pred P;\nelect.sync _|P, 0xffffffff;\n"
                 "@P cp.async.bulk.tensor.3d.shared::cluster.global.mbarrier::complete_tx::bytes [%0], [%1, {%3, %4, %5}], [%2];\n}\n"
                 :: "r"(dst), "l"(map), "r"(bar), "r"(c0), "r"(c1), "r"(c2) : "memory");
}
__device__ __forceinline__ void warp_tma_load_pair(uint32_t dst, const CUtensorMap* map, uint32_t bar, int c0, int c1, int c2) {
    asm volatile("{\n.reg .pred P;\nelect.sync _|P, 0xffffffff;\n"
                 "@P cp.async.bulk.tensor.3d.shared::cluster.global.mbarrier::complete_tx::bytes.multicast::cluster"
                 " [%0], [%1, {%3, %4, %5}], [%2], %6;\n}\n"
                 :: "r"(dst), "l"(map), "r"(bar), "r"(c0), "r"(c1), "r"(c2), "h"((uint16_t)3) : "memory");
}
__device__ __forceinline__ void warp_bulk_load(uint32_t dst, const void* src, uint32_t bytes, uint32_t bar) {
    asm volatile("{\n.reg .pred P;\nelect.sync _|P, 0xffffffff;\n"
                 "@P cp.async.bulk.shared::cluster.global.mbarrier::complete_tx::bytes [%0], [%1], %2, [%3];\n}\n"
                 :: "r"(dst), "l"(src), "r"(bytes), "r"(bar) : "memory");
}
__device__ __forceinline__ void warp_tma_store(const CUtensorMap* map, uint32_t src, int c0, int c1, int c2) {
    asm volatile("{\n.reg .pred P;\nelect.sync _|P, 0xffffffff;\n"
                 "@P cp.async.bulk.tensor.3d.global.shared::cta.bulk_group [%0, {%2, %3, %4}], [%1];\n}\n"
                 :: "l"(map), "r"(src), "r"(c0), "r"(c1), "r"(c2) : "memory");
}
__device__ __forceinline__ void warp_bulk_store(void* dst, uint32_t src, uint32_t bytes) {
    asm volatile("{\n.reg .pred P;\nelect.sync _|P, 0xffffffff;\n"
                 "@P cp.async.bulk.global.shared::cta.bulk_group [%0], [%1], %2;\n}\n" :: "l"(dst), "r"(src), "r"(bytes) : "memory");
}
__device__ __forceinline__ void prefetch_l2(const void* src, uint32_t bytes) {
    asm volatile("cp.async.bulk.prefetch.L2.global [%0], %1;" :: "l"(src), "r"(bytes) : "memory");
}
__device__ __forceinline__ void warp_prefetch(const void* src, uint32_t bytes) {
    asm volatile("{\n.reg .pred P;\nelect.sync _|P, 0xffffffff;\n@P cp.async.bulk.prefetch.L2.global [%0], %1;\n}\n" :: "l"(src), "r"(bytes) : "memory");
}
__device__ __forceinline__ void bulk_commit() { asm volatile("cp.async.bulk.commit_group;" ::: "memory"); }
template <int N> __device__ __forceinline__ void bulk_wait_read() { asm volatile("cp.async.bulk.wait_group.read %0;" :: "n"(N) : "memory"); }
template <int N> __device__ __forceinline__ void bulk_wait() { asm volatile("cp.async.bulk.wait_group %0;" :: "n"(N) : "memory"); }
__device__ __forceinline__ void wgmma_fence() { asm volatile("wgmma.fence.sync.aligned;" ::: "memory"); }
__device__ __forceinline__ void wgmma_commit() { asm volatile("wgmma.commit_group.sync.aligned;" ::: "memory"); }
template <int N> __device__ __forceinline__ void wgmma_wait() { asm volatile("wgmma.wait_group.sync.aligned %0;" :: "n"(N) : "memory"); }
template <int N> __device__ __forceinline__ void fence_regs(float (&d)[N]) {
#pragma unroll
    for (int i = 0; i < N; i++) asm volatile("" : "+f"(d[i]) :: "memory");
}
template <int N> __device__ __forceinline__ void fence_regs(uint32_t (&d)[N]) {
#pragma unroll
    for (int i = 0; i < N; i++) asm volatile("" : "+r"(d[i]) :: "memory");
}
template <int N> __device__ __forceinline__ void reg_dec() { asm volatile("setmaxnreg.dec.sync.aligned.u32 %0;" :: "n"(N)); }
template <int N> __device__ __forceinline__ void reg_inc() { asm volatile("setmaxnreg.inc.sync.aligned.u32 %0;" :: "n"(N)); }
__device__ __forceinline__ uint32_t pack_bf16(float lo, float hi) {
    uint32_t r; asm("cvt.rn.bf16x2.f32 %0, %1, %2;" : "=r"(r) : "f"(hi), "f"(lo)); return r;
}
__device__ __forceinline__ void stmatrix_x4(uint32_t addr, uint32_t r0, uint32_t r1, uint32_t r2, uint32_t r3) {
    asm volatile("stmatrix.sync.aligned.m8n8.x4.shared.b16 [%0], {%1, %2, %3, %4};"
                 :: "r"(addr), "r"(r0), "r"(r1), "r"(r2), "r"(r3) : "memory");
}
__device__ __forceinline__ float ex2(float x) { float y; asm("ex2.approx.ftz.f32 %0, %1;" : "=f"(y) : "f"(x)); return y; }

constexpr uint32_t DESC_HI = (1024 >> 4) | (1u << 30);
__device__ __forceinline__ uint32_t make_desc(uint32_t addr, uint32_t lbo) {
    uint32_t lo = ((addr & 0x3FFFF) >> 4) | ((lbo >> 4) << 16);
    asm volatile("" : "+r"(lo));
    return lo;
}
__device__ __forceinline__ uint64_t full_desc(uint32_t lo) {
    uint64_t d; asm("mov.b64 %0, {%1, %2};" : "=l"(d) : "r"(lo), "r"(DESC_HI)); return d;
}

__device__ __forceinline__ void wgmma_ss_n256_tb_init(float (&d)[128], uint64_t da, uint64_t db) {
    asm volatile("{\n.reg .pred p;\n"
        "setp.ne.b32 p, 0, 0;\n"
        "wgmma.mma_async.sync.aligned.m64n256k16.f32.bf16.bf16 "
        "{%0, %1, %2, %3, %4, %5, %6, %7, %8, %9, %10, %11, %12, %13, %14, %15, %16, %17, %18, %19, %20, "
        "%21, %22, %23, %24, %25, %26, %27, %28, %29, %30, %31, %32, %33, %34, %35, %36, %37, %38, %39, %40, "
        "%41, %42, %43, %44, %45, %46, %47, %48, %49, %50, %51, %52, %53, %54, %55, %56, %57, %58, %59, %60, "
        "%61, %62, %63, %64, %65, %66, %67, %68, %69, %70, %71, %72, %73, %74, %75, %76, %77, %78, %79, %80, "
        "%81, %82, %83, %84, %85, %86, %87, %88, %89, %90, %91, %92, %93, %94, %95, %96, %97, %98, %99, "
        "%100, %101, %102, %103, %104, %105, %106, %107, %108, %109, %110, %111, %112, %113, %114, %115, "
        "%116, %117, %118, %119, %120, %121, %122, %123, %124, %125, %126, %127},"
        " %128, %129, p, 1, 1, 0, 1;\n}\n"
        : "=f"(d[0]), "=f"(d[1]), "=f"(d[2]), "=f"(d[3]), "=f"(d[4]), "=f"(d[5]), "=f"(d[6]), "=f"(d[7]),
        "=f"(d[8]), "=f"(d[9]), "=f"(d[10]), "=f"(d[11]), "=f"(d[12]), "=f"(d[13]), "=f"(d[14]), "=f"(d[15]),
        "=f"(d[16]), "=f"(d[17]), "=f"(d[18]), "=f"(d[19]), "=f"(d[20]), "=f"(d[21]), "=f"(d[22]),
        "=f"(d[23]), "=f"(d[24]), "=f"(d[25]), "=f"(d[26]), "=f"(d[27]), "=f"(d[28]), "=f"(d[29]),
        "=f"(d[30]), "=f"(d[31]), "=f"(d[32]), "=f"(d[33]), "=f"(d[34]), "=f"(d[35]), "=f"(d[36]),
        "=f"(d[37]), "=f"(d[38]), "=f"(d[39]), "=f"(d[40]), "=f"(d[41]), "=f"(d[42]), "=f"(d[43]),
        "=f"(d[44]), "=f"(d[45]), "=f"(d[46]), "=f"(d[47]), "=f"(d[48]), "=f"(d[49]), "=f"(d[50]),
        "=f"(d[51]), "=f"(d[52]), "=f"(d[53]), "=f"(d[54]), "=f"(d[55]), "=f"(d[56]), "=f"(d[57]),
        "=f"(d[58]), "=f"(d[59]), "=f"(d[60]), "=f"(d[61]), "=f"(d[62]), "=f"(d[63]), "=f"(d[64]),
        "=f"(d[65]), "=f"(d[66]), "=f"(d[67]), "=f"(d[68]), "=f"(d[69]), "=f"(d[70]), "=f"(d[71]),
        "=f"(d[72]), "=f"(d[73]), "=f"(d[74]), "=f"(d[75]), "=f"(d[76]), "=f"(d[77]), "=f"(d[78]),
        "=f"(d[79]), "=f"(d[80]), "=f"(d[81]), "=f"(d[82]), "=f"(d[83]), "=f"(d[84]), "=f"(d[85]),
        "=f"(d[86]), "=f"(d[87]), "=f"(d[88]), "=f"(d[89]), "=f"(d[90]), "=f"(d[91]), "=f"(d[92]),
        "=f"(d[93]), "=f"(d[94]), "=f"(d[95]), "=f"(d[96]), "=f"(d[97]), "=f"(d[98]), "=f"(d[99]),
        "=f"(d[100]), "=f"(d[101]), "=f"(d[102]), "=f"(d[103]), "=f"(d[104]), "=f"(d[105]), "=f"(d[106]),
        "=f"(d[107]), "=f"(d[108]), "=f"(d[109]), "=f"(d[110]), "=f"(d[111]), "=f"(d[112]), "=f"(d[113]),
        "=f"(d[114]), "=f"(d[115]), "=f"(d[116]), "=f"(d[117]), "=f"(d[118]), "=f"(d[119]), "=f"(d[120]),
        "=f"(d[121]), "=f"(d[122]), "=f"(d[123]), "=f"(d[124]), "=f"(d[125]), "=f"(d[126]), "=f"(d[127])
        : "l"(da), "l"(db));
}
__device__ __forceinline__ void wgmma_ss_n256_tb(float (&d)[128], uint64_t da, uint64_t db, int scale_d) {
    asm volatile("{\n.reg .pred p;\n"
        "setp.ne.b32 p, %130, 0;\n"
        "wgmma.mma_async.sync.aligned.m64n256k16.f32.bf16.bf16 "
        "{%0, %1, %2, %3, %4, %5, %6, %7, %8, %9, %10, %11, %12, %13, %14, %15, %16, %17, %18, %19, %20, "
        "%21, %22, %23, %24, %25, %26, %27, %28, %29, %30, %31, %32, %33, %34, %35, %36, %37, %38, %39, %40, "
        "%41, %42, %43, %44, %45, %46, %47, %48, %49, %50, %51, %52, %53, %54, %55, %56, %57, %58, %59, %60, "
        "%61, %62, %63, %64, %65, %66, %67, %68, %69, %70, %71, %72, %73, %74, %75, %76, %77, %78, %79, %80, "
        "%81, %82, %83, %84, %85, %86, %87, %88, %89, %90, %91, %92, %93, %94, %95, %96, %97, %98, %99, "
        "%100, %101, %102, %103, %104, %105, %106, %107, %108, %109, %110, %111, %112, %113, %114, %115, "
        "%116, %117, %118, %119, %120, %121, %122, %123, %124, %125, %126, %127},"
        " %128, %129, p, 1, 1, 0, 1;\n}\n"
        : "+f"(d[0]), "+f"(d[1]), "+f"(d[2]), "+f"(d[3]), "+f"(d[4]), "+f"(d[5]), "+f"(d[6]), "+f"(d[7]),
        "+f"(d[8]), "+f"(d[9]), "+f"(d[10]), "+f"(d[11]), "+f"(d[12]), "+f"(d[13]), "+f"(d[14]), "+f"(d[15]),
        "+f"(d[16]), "+f"(d[17]), "+f"(d[18]), "+f"(d[19]), "+f"(d[20]), "+f"(d[21]), "+f"(d[22]),
        "+f"(d[23]), "+f"(d[24]), "+f"(d[25]), "+f"(d[26]), "+f"(d[27]), "+f"(d[28]), "+f"(d[29]),
        "+f"(d[30]), "+f"(d[31]), "+f"(d[32]), "+f"(d[33]), "+f"(d[34]), "+f"(d[35]), "+f"(d[36]),
        "+f"(d[37]), "+f"(d[38]), "+f"(d[39]), "+f"(d[40]), "+f"(d[41]), "+f"(d[42]), "+f"(d[43]),
        "+f"(d[44]), "+f"(d[45]), "+f"(d[46]), "+f"(d[47]), "+f"(d[48]), "+f"(d[49]), "+f"(d[50]),
        "+f"(d[51]), "+f"(d[52]), "+f"(d[53]), "+f"(d[54]), "+f"(d[55]), "+f"(d[56]), "+f"(d[57]),
        "+f"(d[58]), "+f"(d[59]), "+f"(d[60]), "+f"(d[61]), "+f"(d[62]), "+f"(d[63]), "+f"(d[64]),
        "+f"(d[65]), "+f"(d[66]), "+f"(d[67]), "+f"(d[68]), "+f"(d[69]), "+f"(d[70]), "+f"(d[71]),
        "+f"(d[72]), "+f"(d[73]), "+f"(d[74]), "+f"(d[75]), "+f"(d[76]), "+f"(d[77]), "+f"(d[78]),
        "+f"(d[79]), "+f"(d[80]), "+f"(d[81]), "+f"(d[82]), "+f"(d[83]), "+f"(d[84]), "+f"(d[85]),
        "+f"(d[86]), "+f"(d[87]), "+f"(d[88]), "+f"(d[89]), "+f"(d[90]), "+f"(d[91]), "+f"(d[92]),
        "+f"(d[93]), "+f"(d[94]), "+f"(d[95]), "+f"(d[96]), "+f"(d[97]), "+f"(d[98]), "+f"(d[99]),
        "+f"(d[100]), "+f"(d[101]), "+f"(d[102]), "+f"(d[103]), "+f"(d[104]), "+f"(d[105]), "+f"(d[106]),
        "+f"(d[107]), "+f"(d[108]), "+f"(d[109]), "+f"(d[110]), "+f"(d[111]), "+f"(d[112]), "+f"(d[113]),
        "+f"(d[114]), "+f"(d[115]), "+f"(d[116]), "+f"(d[117]), "+f"(d[118]), "+f"(d[119]), "+f"(d[120]),
        "+f"(d[121]), "+f"(d[122]), "+f"(d[123]), "+f"(d[124]), "+f"(d[125]), "+f"(d[126]), "+f"(d[127])
        : "l"(da), "l"(db), "r"(scale_d));
}
__device__ __forceinline__ void wgmma_ss_n128(float (&d)[64], uint64_t da, uint64_t db, int scale_d) {
    asm volatile("{\n.reg .pred p;\n"
        "setp.ne.b32 p, %66, 0;\n"
        "wgmma.mma_async.sync.aligned.m64n128k16.f32.bf16.bf16 "
        "{%0, %1, %2, %3, %4, %5, %6, %7, %8, %9, %10, %11, %12, %13, %14, %15, %16, %17, %18, %19, %20, "
        "%21, %22, %23, %24, %25, %26, %27, %28, %29, %30, %31, %32, %33, %34, %35, %36, %37, %38, %39, %40, "
        "%41, %42, %43, %44, %45, %46, %47, %48, %49, %50, %51, %52, %53, %54, %55, %56, %57, %58, %59, %60, "
        "%61, %62, %63},"
        " %64, %65, p, 1, 1, 0, 0;\n}\n"
        : "+f"(d[0]), "+f"(d[1]), "+f"(d[2]), "+f"(d[3]), "+f"(d[4]), "+f"(d[5]), "+f"(d[6]), "+f"(d[7]),
        "+f"(d[8]), "+f"(d[9]), "+f"(d[10]), "+f"(d[11]), "+f"(d[12]), "+f"(d[13]), "+f"(d[14]), "+f"(d[15]),
        "+f"(d[16]), "+f"(d[17]), "+f"(d[18]), "+f"(d[19]), "+f"(d[20]), "+f"(d[21]), "+f"(d[22]),
        "+f"(d[23]), "+f"(d[24]), "+f"(d[25]), "+f"(d[26]), "+f"(d[27]), "+f"(d[28]), "+f"(d[29]),
        "+f"(d[30]), "+f"(d[31]), "+f"(d[32]), "+f"(d[33]), "+f"(d[34]), "+f"(d[35]), "+f"(d[36]),
        "+f"(d[37]), "+f"(d[38]), "+f"(d[39]), "+f"(d[40]), "+f"(d[41]), "+f"(d[42]), "+f"(d[43]),
        "+f"(d[44]), "+f"(d[45]), "+f"(d[46]), "+f"(d[47]), "+f"(d[48]), "+f"(d[49]), "+f"(d[50]),
        "+f"(d[51]), "+f"(d[52]), "+f"(d[53]), "+f"(d[54]), "+f"(d[55]), "+f"(d[56]), "+f"(d[57]),
        "+f"(d[58]), "+f"(d[59]), "+f"(d[60]), "+f"(d[61]), "+f"(d[62]), "+f"(d[63])
        : "l"(da), "l"(db), "r"(scale_d));
}
__device__ __forceinline__ void wgmma_rs_n128_tb(float (&d)[64], uint32_t a0, uint32_t a1, uint32_t a2, uint32_t a3, uint64_t db, int scale_d) {
    asm volatile("{\n.reg .pred p;\n"
        "setp.ne.b32 p, %69, 0;\n"
        "wgmma.mma_async.sync.aligned.m64n128k16.f32.bf16.bf16 "
        "{%0, %1, %2, %3, %4, %5, %6, %7, %8, %9, %10, %11, %12, %13, %14, %15, %16, %17, %18, %19, %20, "
        "%21, %22, %23, %24, %25, %26, %27, %28, %29, %30, %31, %32, %33, %34, %35, %36, %37, %38, %39, %40, "
        "%41, %42, %43, %44, %45, %46, %47, %48, %49, %50, %51, %52, %53, %54, %55, %56, %57, %58, %59, %60, "
        "%61, %62, %63},"
        " {%64, %65, %66, %67}, %68, p, 1, 1, 1;\n}\n"
        : "+f"(d[0]), "+f"(d[1]), "+f"(d[2]), "+f"(d[3]), "+f"(d[4]), "+f"(d[5]), "+f"(d[6]), "+f"(d[7]),
        "+f"(d[8]), "+f"(d[9]), "+f"(d[10]), "+f"(d[11]), "+f"(d[12]), "+f"(d[13]), "+f"(d[14]), "+f"(d[15]),
        "+f"(d[16]), "+f"(d[17]), "+f"(d[18]), "+f"(d[19]), "+f"(d[20]), "+f"(d[21]), "+f"(d[22]),
        "+f"(d[23]), "+f"(d[24]), "+f"(d[25]), "+f"(d[26]), "+f"(d[27]), "+f"(d[28]), "+f"(d[29]),
        "+f"(d[30]), "+f"(d[31]), "+f"(d[32]), "+f"(d[33]), "+f"(d[34]), "+f"(d[35]), "+f"(d[36]),
        "+f"(d[37]), "+f"(d[38]), "+f"(d[39]), "+f"(d[40]), "+f"(d[41]), "+f"(d[42]), "+f"(d[43]),
        "+f"(d[44]), "+f"(d[45]), "+f"(d[46]), "+f"(d[47]), "+f"(d[48]), "+f"(d[49]), "+f"(d[50]),
        "+f"(d[51]), "+f"(d[52]), "+f"(d[53]), "+f"(d[54]), "+f"(d[55]), "+f"(d[56]), "+f"(d[57]),
        "+f"(d[58]), "+f"(d[59]), "+f"(d[60]), "+f"(d[61]), "+f"(d[62]), "+f"(d[63])
        : "r"(a0), "r"(a1), "r"(a2), "r"(a3), "l"(db), "r"(scale_d));
}
__device__ __forceinline__ void wgmma_ss_n128_lo_tb(float (&d)[128], uint64_t da, uint64_t db, int scale_d) {
    asm volatile("{\n.reg .pred p;\n"
        "setp.ne.b32 p, %66, 0;\n"
        "wgmma.mma_async.sync.aligned.m64n128k16.f32.bf16.bf16 "
        "{%0, %1, %2, %3, %4, %5, %6, %7, %8, %9, %10, %11, %12, %13, %14, %15, %16, %17, %18, %19, %20, "
        "%21, %22, %23, %24, %25, %26, %27, %28, %29, %30, %31, %32, %33, %34, %35, %36, %37, %38, %39, %40, "
        "%41, %42, %43, %44, %45, %46, %47, %48, %49, %50, %51, %52, %53, %54, %55, %56, %57, %58, %59, %60, "
        "%61, %62, %63},"
        " %64, %65, p, 1, 1, 0, 1;\n}\n"
        : "+f"(d[0]), "+f"(d[1]), "+f"(d[2]), "+f"(d[3]), "+f"(d[4]), "+f"(d[5]), "+f"(d[6]), "+f"(d[7]),
        "+f"(d[8]), "+f"(d[9]), "+f"(d[10]), "+f"(d[11]), "+f"(d[12]), "+f"(d[13]), "+f"(d[14]), "+f"(d[15]),
        "+f"(d[16]), "+f"(d[17]), "+f"(d[18]), "+f"(d[19]), "+f"(d[20]), "+f"(d[21]), "+f"(d[22]),
        "+f"(d[23]), "+f"(d[24]), "+f"(d[25]), "+f"(d[26]), "+f"(d[27]), "+f"(d[28]), "+f"(d[29]),
        "+f"(d[30]), "+f"(d[31]), "+f"(d[32]), "+f"(d[33]), "+f"(d[34]), "+f"(d[35]), "+f"(d[36]),
        "+f"(d[37]), "+f"(d[38]), "+f"(d[39]), "+f"(d[40]), "+f"(d[41]), "+f"(d[42]), "+f"(d[43]),
        "+f"(d[44]), "+f"(d[45]), "+f"(d[46]), "+f"(d[47]), "+f"(d[48]), "+f"(d[49]), "+f"(d[50]),
        "+f"(d[51]), "+f"(d[52]), "+f"(d[53]), "+f"(d[54]), "+f"(d[55]), "+f"(d[56]), "+f"(d[57]),
        "+f"(d[58]), "+f"(d[59]), "+f"(d[60]), "+f"(d[61]), "+f"(d[62]), "+f"(d[63])
        : "l"(da), "l"(db), "r"(scale_d));
}

enum { M_X = 0, M_C, M_WQ, M_WQKV, M_WUK, M_WUV, M_WO, M_WOB, M_SCR_LD, M_SCR_LOC, M_SCR_LOQ, M_SCR_ST, M_COUNT };
enum { T_Q = 0, T_K, T_V, T_B, T_OUT, T_LOCAL, T_ATTN, T_END };
constexpr int NCTA = 132, NPAIR = NCTA / 2;
constexpr int NITEMS = 480 + 64 + 256;
#define NTRI 3
constexpr int TRIPLES = NTRI, WIDE = 80 - 3 * TRIPLES;
struct Params {
    CUtensorMap m[M_COUNT];
    const __nv_bfloat16* x;
    const __nv_bfloat16* gate_w;
    const char* wo;
    const char* wob;
    __nv_bfloat16* out;
    uint32_t zero;
    uint16_t items[NITEMS];
    uint8_t ostep[80];
};
__device__ __forceinline__ int item_type(int it) { return it >> 13; }
__device__ __forceinline__ int item_row(int it) { return it & 15; }
__device__ __forceinline__ int item_col(int it) { return (it >> 4) & 31; }
__device__ __forceinline__ int item_asc(int it) { return (it >> 9) & 1; }
constexpr int ITEM_READY = 1 << 10;

struct __align__(128) Sync {
    unsigned long long count[4];
    __align__(128) unsigned long long ctx[16];
    unsigned next, next_out, done;
    __align__(128) unsigned step[32][2];
    unsigned split[32];
};
__device__ Sync g_sync;
__device__ uint4 g_part[128][8][256];

constexpr uint32_t GST_BYTES = 49152, SM_KV = 65536, SM_STAGING = 196608, SM_BARS = SM_STAGING + 32768;
constexpr uint32_t B_GFULL = 0, B_GEMPTY = 32, B_AFULL = 64, B_AEMPTY = 112, B_SFULL = 160, B_SEMPTY = 192,
                   B_IFULL = 224, B_IEMPTY = 288, B_XFREE = 352, B_WANT = 384, B_HALF = 416,
                   SM_ORDY = 448, SM_QUEUE = 456, B_ALT = 488, B_QFREE = 504, SM_GATE = 512, SM_TOTAL = SM_BARS + 1536;
constexpr int QDEPTH = 8;
#define PF_NAR 20
#define SPREAD 4
#define PACE 0
#define PF_LOC 1
#define KMEET 14
constexpr int K_MEET = KMEET, K_SPLIT = KMEET + 12;
#define KF2 3
constexpr uint32_t LOC_PLANE = 72 * 128;
constexpr float SM_SCALE = 0.08838834764831845f * 1.4426950408889634f;
constexpr float LOC_SCALE = 0.17677669529663687f * 1.4426950408889634f;
constexpr float SUM_LIMIT = 1152921504606846976.f;
constexpr float REF_RANGE = 32.f;

__device__ __forceinline__ unsigned ld_acquire(const unsigned* p) {
    unsigned v; asm volatile("ld.acquire.gpu.global.u32 %0, [%1];" : "=r"(v) : "l"(p) : "memory"); return v;
}
__device__ __forceinline__ unsigned long long ld_acquire(const unsigned long long* p) {
    unsigned long long v; asm volatile("ld.acquire.gpu.global.u64 %0, [%1];" : "=l"(v) : "l"(p) : "memory"); return v;
}
__device__ __forceinline__ void st_b128(void* p, uint32_t a, uint32_t b, uint32_t c, uint32_t d) {
    asm volatile("{\n.reg .b128 v;\n.reg .b64 lo, hi;\nmov.b64 lo, {%1, %2};\nmov.b64 hi, {%3, %4};\nmov.b128 v, {lo, hi};\n"
                 "st.relaxed.gpu.global.b128 [%0], v;\n}\n" :: "l"(p), "r"(a), "r"(b), "r"(c), "r"(d) : "memory");
}
__device__ __forceinline__ void ld_b128(const void* p, uint32_t& a, uint32_t& b, uint32_t& c, uint32_t& d) {
    asm volatile("{\n.reg .b128 v;\n.reg .b64 lo, hi;\nld.relaxed.gpu.global.b128 v, [%4];\nmov.b128 {lo, hi}, v;\n"
                 "mov.b64 {%0, %1}, lo;\nmov.b64 {%2, %3}, hi;\n}\n" : "=r"(a), "=r"(b), "=r"(c), "=r"(d) : "l"(p) : "memory");
}
__device__ __forceinline__ void spin_guard(unsigned& n) {
    asm volatile("{\n.reg .pred P;\nadd.u32 %0, %0, 1;\nsetp.gt.u32 P, %0, 16777216;\n@P trap;\n}\n" : "+r"(n));
    if (n > 1) __nanosleep(100);
}
__device__ __forceinline__ void red_add(unsigned long long* p, unsigned long long v) {
    asm volatile("red.release.gpu.global.add.u64 [%0], %1;" :: "l"(p), "l"(v) : "memory");
}
__device__ __forceinline__ float rcp(float x) { float y; asm("rcp.approx.ftz.f32 %0, %1;" : "=f"(y) : "f"(x)); return y; }
__device__ __forceinline__ float lds_f32(uint32_t addr) {
    float v; asm volatile("ld.shared.f32 %0, [%1];" : "=f"(v) : "r"(addr) : "memory"); return v;
}
__device__ __forceinline__ void ldsm_x4(uint32_t (&r)[4], uint32_t addr) {
    asm volatile("ldmatrix.sync.aligned.m8n8.x4.shared.b16 {%0, %1, %2, %3}, [%4];"
                 : "=r"(r[0]), "=r"(r[1]), "=r"(r[2]), "=r"(r[3]) : "r"(addr) : "memory");
}
__device__ __forceinline__ void ldsm_x4_t(uint32_t (&r)[4], uint32_t addr) {
    asm volatile("ldmatrix.sync.aligned.m8n8.x4.trans.shared.b16 {%0, %1, %2, %3}, [%4];"
                 : "=r"(r[0]), "=r"(r[1]), "=r"(r[2]), "=r"(r[3]) : "r"(addr) : "memory");
}
__device__ __forceinline__ void mma_k16(float (&d)[4], const uint32_t (&a)[4], uint32_t b0, uint32_t b1) {
    asm("mma.sync.aligned.m16n8k16.row.col.f32.bf16.bf16.f32 {%0,%1,%2,%3}, {%4,%5,%6,%7}, {%8,%9}, {%0,%1,%2,%3};"
        : "+f"(d[0]), "+f"(d[1]), "+f"(d[2]), "+f"(d[3]) : "r"(a[0]), "r"(a[1]), "r"(a[2]), "r"(a[3]), "r"(b0), "r"(b1));
}
__device__ __forceinline__ void mma_k16_init(float (&d)[4], const uint32_t (&a)[4], uint32_t b0, uint32_t b1) {
    asm("{\n.reg .f32 z;\nmov.f32 z, 0f00000000;\n"
        "mma.sync.aligned.m16n8k16.row.col.f32.bf16.bf16.f32 {%0,%1,%2,%3}, {%4,%5,%6,%7}, {%8,%9}, {z,z,z,z};\n}\n"
        : "=f"(d[0]), "=f"(d[1]), "=f"(d[2]), "=f"(d[3]) : "r"(a[0]), "r"(a[1]), "r"(a[2]), "r"(a[3]), "r"(b0), "r"(b1));
}
__device__ __forceinline__ void mma_k8(float (&d)[4], uint32_t a0, uint32_t a1, uint32_t b0) {
    asm("mma.sync.aligned.m16n8k8.row.col.f32.bf16.bf16.f32 {%0,%1,%2,%3}, {%4,%5}, {%6}, {%0,%1,%2,%3};"
        : "+f"(d[0]), "+f"(d[1]), "+f"(d[2]), "+f"(d[3]) : "r"(a0), "r"(a1), "r"(b0));
}
template <typename T, int N> __device__ __forceinline__ void zero_regs(T (&d)[N]) {
#pragma unroll
    for (int i = 0; i < N; i++) d[i] = 0;
}
__device__ __forceinline__ float quad_max(float v) {
    v = fmaxf(v, __shfl_xor_sync(0xffffffffu, v, 1));
    return fmaxf(v, __shfl_xor_sync(0xffffffffu, v, 2));
}
__device__ __forceinline__ float quad_sum(float v) {
    v += __shfl_xor_sync(0xffffffffu, v, 1);
    return v + __shfl_xor_sync(0xffffffffu, v, 2);
}

__device__ __forceinline__ void qk_gemm(float (&s)[64], uint32_t q_lo, uint32_t k_lo) {
    const uint64_t dq = full_desc(q_lo), dk = full_desc(k_lo);
    fence_regs(s);
    wgmma_fence();
#pragma unroll
    for (int kk = 0; kk < 8; kk++) {
        const uint32_t o = (kk >> 2) * 1024 + (kk & 3) * 2;
        wgmma_ss_n128(s, dq + o, dk + o, kk != 0);
    }
    wgmma_commit();
}
__device__ __forceinline__ void pv_gemm(float (&o)[64], uint32_t (&p)[32], uint32_t v_lo, int accumulate) {
    const uint64_t dv = full_desc(v_lo);
    fence_regs(o);
    fence_regs(p);
    wgmma_fence();
#pragma unroll
    for (int kk = 0; kk < 8; kk++)
        wgmma_rs_n128_tb(o, p[4 * kk], p[4 * kk + 1], p[4 * kk + 2], p[4 * kk + 3], dv + kk * 128, kk != 0 || accumulate);
    wgmma_commit();
}
__device__ __forceinline__ void row_max(const float (&s)[64], float& x0, float& x1) {
    float z0 = fmaxf(s[0], s[1]), z1 = fmaxf(s[2], s[3]);
    x0 = fmaxf(s[4], s[5]); x1 = fmaxf(s[6], s[7]);
#pragma unroll
    for (int j = 2; j < 16; j += 2) {
        z0 = fmaxf(z0, fmaxf(s[4 * j], s[4 * j + 1]));
        z1 = fmaxf(z1, fmaxf(s[4 * j + 2], s[4 * j + 3]));
        x0 = fmaxf(x0, fmaxf(s[4 * j + 4], s[4 * j + 5]));
        x1 = fmaxf(x1, fmaxf(s[4 * j + 6], s[4 * j + 7]));
    }
    x0 = quad_max(fmaxf(x0, z0)); x1 = quad_max(fmaxf(x1, z1));
}
__device__ __forceinline__ void exp_pack(uint32_t (&p)[32], const float (&s)[64], float& r0, float& r1) {
#pragma unroll
    for (int j = 0; j < 16; j++) {
        const float e0 = ex2(s[4 * j]), e1 = ex2(s[4 * j + 1]), e2 = ex2(s[4 * j + 2]), e3 = ex2(s[4 * j + 3]);
        if (j == 0) { r0 = e0 + e1; r1 = e2 + e3; }
        else { r0 += e0 + e1; r1 += e2 + e3; }
        p[2 * j] = pack_bf16(e0, e1);
        p[2 * j + 1] = pack_bf16(e2, e3);
    }
}
__device__ __forceinline__ void shift_rows(float (&s)[64], float d0, float d1) {
#pragma unroll
    for (int j = 0; j < 16; j++) { s[4 * j] -= d0; s[4 * j + 1] -= d0; s[4 * j + 2] -= d1; s[4 * j + 3] -= d1; }
}
constexpr float MASKED = -3e38f;
template <int J0>
__device__ __forceinline__ void mask_triangle(float (&s)[64], float thr) {
#pragma unroll
    for (int j = 0; j < 16; j++) {
        const float m = __saturatef((float)(8 * (j >> 1) + (j & 1)) - thr);
        const int i = 4 * (J0 + (j >> 1)) + (j & 1);
        s[i] = fmaf(m, MASKED, s[i]);
        if (j < 14) s[i + 6] = fmaf(m, MASKED, s[i + 6]);
    }
}
__device__ __forceinline__ void causal_mask(float (&s)[64], float thr, int wg) {
    asm volatile("" : "+f"(thr));
    if (wg == 0) {
        mask_triangle<0>(s, thr);
#pragma unroll
        for (int j = 32; j < 64; j++) s[j] += MASKED;
    } else {
        mask_triangle<8>(s, thr);
    }
}

__global__ void __cluster_dims__(2, 1, 1) __launch_bounds__(384, 1) fused_kernel(const __grid_constant__ Params prm) {
    extern __shared__ __align__(1024) uint8_t smem[];
    const uint32_t sb = smem_u32(smem), bars = sb + SM_BARS;
    const int warp = __shfl_sync(0xffffffffu, threadIdx.x >> 5, 0), lane = threadIdx.x & 31;

    const uint32_t rank = cluster_rank();
    const uint32_t bars0 = map_cta(bars, 0), bars_peer = map_cta(bars, rank ^ 1);

    auto first_item = [&]() -> int {
        uint32_t pair = blockIdx.x >> 1;
        asm volatile("" : "+r"(pair));
        return prm.items[pair] + item_row(prm.items[pair]) + rank;
    };
    if (threadIdx.x == 256) {
        for (int k = 0; k < 4; k++) mbar_init(bars + B_GFULL + 8 * k, 1);
        asm volatile("fence.mbarrier_init.release.cluster;" ::: "memory");
        fence_proxy_async_smem();
    }
    if (threadIdx.x == 128) {
        for (int i = 0; i < 4; i++) { mbar_init(bars + B_GEMPTY + 8 * i, 16); mbar_init(bars + B_XFREE + 8 * i, 1); }
        for (int i = 0; i < 6; i++) { mbar_init(bars + B_AFULL + 8 * i, 1); mbar_init(bars + B_AEMPTY + 8 * i, i < 2 ? 8 : 16); }
        for (int i = 0; i < 4; i++) { mbar_init(bars + B_SFULL + 8 * i, 4); mbar_init(bars + B_SEMPTY + 8 * i, 1); }
        for (int i = 0; i < QDEPTH; i++) { mbar_init(bars + B_IFULL + 8 * i, 1); mbar_init(bars + B_IEMPTY + 8 * i, 23); }
        mbar_init(bars + B_WANT, 2);
        for (int i = 0; i < 4; i++) mbar_init(bars + B_HALF + 8 * i, 1);
        mbar_init(bars + B_ALT, 4); mbar_init(bars + B_ALT + 8, 4); mbar_init(bars + B_QFREE, 2);
        asm volatile("st.shared.u64 [%0], 0;" :: "r"(bars + SM_ORDY) : "memory");
        asm volatile("fence.mbarrier_init.release.cluster;\nfence.acq_rel.cta;" ::: "memory");
    }
    __syncwarp();
    asm volatile("barrier.cluster.arrive.relaxed.aligned;" ::: "memory");
    if (threadIdx.x == 256) {
        const int first_it = first_item();
        for (int k = 0; k < 4; k++) {
            const uint32_t dst = sb + k * GST_BYTES, fb = bars + B_GFULL + 8 * k;
            mbar_expect_tx(fb, GST_BYTES);
            tma_load_3d(dst, &prm.m[M_X], fb, k * 64, item_row(first_it) * 128, 0);
            tma_load_3d(dst + 16384, &prm.m[M_WQKV], fb, 0, k * 64, item_col(first_it) * 4);
            tma_load_3d(dst + 32768, &prm.m[M_WQKV], fb, 0, k * 64, item_col(first_it) * 4 + 2);
        }
    }
    __syncwarp();
    asm volatile("barrier.cluster.wait.acquire.aligned;" ::: "memory");

    uint32_t qn = 0;
    auto next_item = [&](bool releaser, bool bounded = true) -> int {
        const uint32_t slot = qn % QDEPTH;
        if (bounded) mbar_wait(bars + B_IFULL + 8 * slot, (qn / QDEPTH) & 1);
        else mbar_spin(bars + B_IFULL + 8 * slot, (qn / QDEPTH) & 1);
        uint32_t it;
        asm volatile("ld.shared.u32 %0, [%1];" : "=r"(it) : "r"(bars + SM_QUEUE + 4 * slot) : "memory");
        mbar_arrive_cluster_if(releaser, bars0 + B_IEMPTY + 8 * slot);
        qn++;
        return it;
    };

    if (warp < 4) {
        reg_dec<40>();
        if (warp == 0) {
            {
                uint32_t gph = 0;
                const uint32_t prank = __shfl_sync(0xffffffffu, rank, 0);
                int k0 = 4;
                uint32_t kv = 0, kvph = 1;
                uint32_t qc = 0;
                uint32_t oneed = 0;
                uint32_t xph = 0;
                uint32_t need_g = 0, need_a = 0;
                auto a_parity = [&](uint32_t b) { return b < 2 ? (((qc + 1 - b) >> 1) & 1) ^ 1 : kvph ^ (b - 2 < kv); };
                int held_type = T_END;
                uint32_t borrowed = 0, fph = 0;
                auto reclaim_q = [&]() { if (borrowed) { mbar_wait(bars + B_QFREE, fph); fph ^= 1; borrowed = 0; } };
                auto acquire_g = [&](uint32_t st, bool shared) {
                    mbar_wait(bars + B_GEMPTY + 8 * st, gph);
                    if (need_a) {
                        reclaim_q();
                        const uint32_t b = (3 * st) >> 1;
                        mbar_wait(bars + B_AEMPTY + 8 * b, a_parity(b));
                        mbar_wait(bars + B_AEMPTY + 8 * (b + 1), a_parity(b + 1));
                        if (shared) {
                            mbar_arrive_cluster_if(lane == 0, bars_peer + B_XFREE + 8 * st);
                            mbar_wait(bars + B_XFREE + 8 * st, xph);
                        }
                        if (st == 3) { need_a = 0; xph ^= shared; }
                    }
                };
                auto leave_gemm = [&](uint32_t b) {
                    if (need_g >> b & 1) {
                        mbar_wait(bars + B_GEMPTY + 8 * ((2 * b) / 3), gph);
                        mbar_wait(bars + B_GEMPTY + 8 * ((2 * b + 1) / 3), gph);
                        need_g &= ~(1u << b);
                    }
                };
                const CUtensorMap* tile_map = &prm.m[M_SCR_LD];
                asm volatile("" : "+l"(tile_map));
                auto load_q = [&](int grp, int row) {
                    const uint32_t b = qc & 1, dst = sb + b * 32768, fb = bars + B_AFULL + 8 * b;
                    mbar_wait(bars + B_AEMPTY + 8 * b, a_parity(b));
                    leave_gemm(b);
                    reclaim_q();
                    borrowed = held_type != T_END;
                    held_type = T_END;
                    warp_expect_tx(fb, 32768 + 512);
                    warp_tma_load(dst, tile_map, fb, 0, row, grp);
                    warp_tma_load(dst + 16384, tile_map, fb, 64, row, grp);
                    warp_bulk_load(bars + SM_GATE + b * 512, &g_gate[row], 512, fb);
                    qc++;
                };
                auto load_kv = [&](int grp, int row, bool shared) {
                    uint32_t fb = bars + B_AFULL + 16 + 8 * kv, mine = sb + SM_KV + kv * 32768 + prank * 16384;
                    int c_mine = prank * 64;
                    asm volatile("" : "+r"(mine), "+r"(fb), "+r"(row), "+r"(grp), "+r"(c_mine));
                    if (need_g) leave_gemm(2 + kv);
                    mbar_wait(fb + B_AEMPTY - B_AFULL, kvph);
                    warp_expect_tx(fb, grp < 0 ? 0 : 32768);
                    if (shared) {
                        warp_tma_load_pair(mine, tile_map, fb, c_mine, row, grp);
                    } else if (grp >= 0) {
                        warp_tma_load(mine, tile_map, fb, c_mine, row, grp);
                        warp_tma_load(mine + 16384 - prank * 32768, tile_map, fb, 64 - c_mine, row, grp);
                    } else {
                        mbar_arrive_cluster_n_if(lane < 2, map_cta(fb, lane & 1) + B_AEMPTY - B_AFULL, 8);
                    }
                    if (++kv == 4) { kv = 0; kvph ^= 1; }
                };
                auto request = [&]() { mbar_arrive_cluster_if(lane == 0, bars0 + B_WANT); };
                int pv_grp = -1, pv_row = 0;
                bool pv_shared = false, peer_longer = false;
                auto inputs_seen = [&](uint32_t word, unsigned& n) -> uint32_t {
                    uint32_t v;
                    spin_guard(n);
                    asm volatile("ld.acquire.cta.shared.u32 %0, [%1];" : "=r"(v) : "r"(bars + SM_ORDY + 4 * word) : "memory");
                    return __shfl_sync(0xffffffffu, v, 0);
                };
                auto fetch = [&]() -> int {
                    const int nx = __shfl_sync(0xffffffffu, next_item(lane == 0), 0);
                    if ((item_type(nx) == T_ATTN || item_type(nx) == T_LOCAL) && !(nx & ITEM_READY)) {
                        oneed += 256;
                        for (unsigned n = 0; inputs_seen(1, n) < oneed;) {}
                    }
                    if (item_type(nx) == T_ATTN) load_q(G_Q + item_col(nx), item_row(nx) * 128);
                    return nx;
                };
                int nxt = first_item();
                while (true) {
                    const int it = nxt >= 0 ? nxt : fetch();
                    nxt = -1;
                    const int type = item_type(it), m = item_row(it), c = item_col(it);
                    const int asc = item_asc(it), nu = type == T_ATTN ? 2 * m + 2 : 0;
                    const int uend = nu + ((type == T_ATTN ? m < 2 : pv_grp >= 0) ? 3 : 0), ureq = 2 * max(m - 2 - (asc & m), 0);
#pragma unroll 1
                    for (int u = 0; u < uend; u++) {
                        int grp = pv_grp, row = pv_row;
                        bool shared = pv_shared;
                        if (u >= nu) {
                            if (u == nu + 1) pv_grp = -1;
                            else if (peer_longer) { grp = -1; shared = false; }
                            else continue;
                        } else {
                            const int j = asc ? u >> 1 : m - (u >> 1);
                            if (u & 1) {
                                pv_grp = G_V + c; pv_row = j * 128; pv_shared = j != (m | 1);
                                peer_longer = asc & ~m & 1;
                                if (u == nu - 1 && (m & 1) && item_type(nxt) == T_END) mbar_arrive_cluster_n_if(lane == 0, bars0 + B_WANT, 2);
                                if (grp < 0) continue;
                            } else {
                                if (u == ureq) request();
                                if (u == 2 * m && m > 0) nxt = fetch();
                                grp = G_K + c; row = j * 128; shared = j != (m | 1);
                            }
                        }
                        load_kv(grp, row, shared);
                    }
                    if (type == T_END) break;
                    if (type == T_ATTN) {
                        need_a = 1;
                    } else if (type == T_LOCAL) {
                        if (held_type == T_B && !(it & ITEM_READY)) held_type = T_END;
                        request();
#pragma unroll 1
                        for (uint32_t st = 0; st < 4; st++) {
                            acquire_g(st, false);
                            const uint32_t dst = sb + st * GST_BYTES, fb = bars + B_GFULL + 8 * st;
                            warp_expect_tx(fb, st == 0 ? 32768 + 512 : st == 3 ? 0 : 4 * LOC_PLANE);
                            if (st == 3) break;
                            if (st == 0) warp_bulk_load(dst + 4 * LOC_PLANE, &g_gate[m * 128], 512, fb);
#pragma unroll 1
                            for (int i = 0; i < 4; i++)
                                warp_tma_load(dst + i * LOC_PLANE, &prm.m[st ? M_SCR_LOC : M_SCR_LOQ], fb, i * 64, m * 64 - (st ? 8 : 0), G_B + 8 * st + c);
                        }
                        gph ^= 1;
                        need_g = 63;
                    } else {
                        const int nk = type == T_K || type == T_V ? 8 : 16;
                        const CUtensorMap* ma = &prm.m[nk == 8 ? M_C : M_X];
                        const CUtensorMap* mb = &prm.m[type == T_Q ? M_WQ : type == T_K ? M_WUK : type == T_V ? M_WUV : M_WQKV];
                        for (int k = k0; k < nk; k++) {
                            if (k == nk - 3) request();
                            const uint32_t st = k & 3;
                            uint32_t dst = sb + st * GST_BYTES, fb = bars + B_GFULL + 8 * st, dstb = dst + 16384 + prank * 16384;
                            int a0 = k * 64, a1 = m * 128, b2 = c * 4 + 2 * prank;
                            asm volatile("" : "+r"(dst), "+r"(fb), "+r"(dstb), "+r"(a0), "+r"(a1), "+r"(b2), "+l"(ma), "+l"(mb));
                            acquire_g(st, true);
                            warp_expect_tx(fb, GST_BYTES);
                            warp_tma_load(dst, ma, fb, a0, a1, 0);
                            warp_tma_load_pair(dstb, mb, fb, 0, a0, b2);
                            if (st == 3) gph ^= 1;
                        }
                        need_g = 63;
                        held_type = type;
                        k0 = 0;
                    }
                }
                if (!need_a) request();
                const int it = __shfl_sync(0xffffffffu, next_item(lane == 0), 0);
                int nk = 0;
                if (item_type(it) == T_OUT) {
                    const int m = item_row(it), c = item_col(it), half = c & 1;
                    nk = 80;
                    for (int k = 0; k < nk; k++) {
                        if (k == K_SPLIT) nk = 2 * TRIPLES + (__shfl_sync(0xffffffffu, next_item(lane == 0), 0) & 127);
                        const int kn = k + 2 * TRIPLES - nk, first = kn >= 0 && !(kn & 1);
                        const int s = kn >= 0 ? WIDE + (3 * kn + 1) / 2 : half ? WIDE - 1 - k : k;
                        const uint32_t sa = prm.ostep[s], sa2 = prm.ostep[s + first], sw = prm.ostep[s - (kn >= 0 && !first ? prank : 0)];
                        for (unsigned n = 0; !(inputs_seen(sa >> 6, n) >> (sa >> 1 & 31) & 1);) {}
                        if (first) for (unsigned n = 0; !(inputs_seen(sa2 >> 6, n) >> (sa2 >> 1 & 31) & 1);) {}
                        const uint32_t st = k & 3;
                        uint32_t dst = sb + st * GST_BYTES, fb = bars + B_GFULL + 8 * st;
                        uint32_t dstb = dst + 16384 + (first ? 0 : prank * 16384), skipb = first && (kn >> 1 & 1) != prank;
                        int a0 = (sa & 1) * 64, a1 = m * 128, a2 = (sa >> 1) + (sa < 64 ? G_CTX : G_LOC - 32);
                        int b1 = (sw & 63) * 64, b2 = (c >> 1) * 4 + 2 * (kn >= 0 ? half : half ^ prank);
                        const CUtensorMap* mb = &prm.m[sw >= 64 ? M_WOB : M_WO];
                        asm volatile("" : "+r"(dst), "+r"(fb), "+r"(dstb), "+r"(skipb), "+r"(a0), "+r"(a1), "+r"(a2), "+r"(b1), "+r"(b2), "+l"(mb));
                        acquire_g(st, true);
                        warp_expect_tx(fb, GST_BYTES);
                        warp_tma_load(dst, tile_map, fb, a0, a1, a2);
                        if (!skipb) warp_tma_load_pair(dstb, mb, fb, 0, b1, b2);
                        if (first) warp_tma_load(dst + 32768, tile_map, fb, (sa2 & 1) * 64, a1, (sa2 >> 1) + (sa2 < 64 ? G_CTX : G_LOC - 32));
                        if (k < K_SPLIT && lane == 0 && !prank)
                            asm volatile("st.relaxed.gpu.global.u32 [%0], %1;" :: "l"(&g_sync.step[0][0] + m * 4 + c), "r"(k) : "memory");
                        if (k == K_MEET) request();
                        if (PF_NAR && (uint32_t)(k - PF_NAR) < (3 * TRIPLES + 1) / 2) {
                            const uint32_t g = prm.ostep[79 - 2 * (k - PF_NAR)] >> 1;
                            warp_prefetch((const char*)g_scr + (uint32_t)((G_CTX + g) * (SEQ * 256) + m * 32768 + c * 4096), 4096);
                            warp_prefetch(prm.wo + (uint32_t)(g * 262144 + (m * 8 + c) * 2048), 2048);
                        }
                        if (st == 3) gph ^= 1;
                    }
                    for (unsigned n = 0; ~inputs_seen(0, n) || inputs_seen(1, n) != 255;) {}
                }
                for (uint32_t st = 0; st < 4; st++) { mbar_wait(bars + B_GEMPTY + 8 * st, gph ^ (st < (nk & 3))); mbar_wait(bars + B_AEMPTY + 16 + 8 * st, a_parity(2 + st)); }
                unsigned left = 0;
                if (lane == 0) left = atomicAdd(&g_sync.done, 1u);
                if (__shfl_sync(0xffffffffu, left, 0) == NCTA - 1)
                    for (int i = lane; i < sizeof(Sync) / 8; i += 32) ((unsigned long long*)&g_sync)[i] = 0;
            }
        } else if (warp <= 2) {
            if (blockIdx.x < SEQ / 16) {
                const uint32_t r0 = 16 * blockIdx.x + 8 * (warp - 1), gbuf = bars + SM_GATE + 4 * (r0 & 15);
                float z[4];
#pragma unroll 1
                for (uint32_t i = 0; i < 8; i++) {
                    const uint32_t off = (i & 3) * 512 + lane * 16;
                    const uint4* xp = (const uint4*)((const char*)prm.x + ((r0 + (i & 4)) * 2048 + off));
                    const uint4 wv = __ldg((const uint4*)((const char*)prm.gate_w + off));
                    uint4 xv[4];
#pragma unroll
                    for (int r = 0; r < 4; r++) { xv[r] = __ldg(xp + r * 128); if (!(i & 3)) z[r] = 0.f; }
                    const uint32_t ws[4] = {wv.x, wv.y, wv.z, wv.w};
#pragma unroll
                    for (int e = 0; e < 4; e++)
#pragma unroll
                        for (int r = 0; r < 4; r++) {
                            const uint32_t xs = e == 0 ? xv[r].x : e == 1 ? xv[r].y : e == 2 ? xv[r].z : xv[r].w;
                            z[r] = fmaf(__uint_as_float(xs << 16), __uint_as_float(ws[e] << 16), z[r]);
                            z[r] = fmaf(__uint_as_float(xs & 0xffff0000u), __uint_as_float(ws[e] & 0xffff0000u), z[r]);
                        }
                    if ((i & 3) == 3) {
#pragma unroll
                        for (int o = 16; o > 0; o >>= 1)
#pragma unroll
                            for (int r = 0; r < 4; r++) z[r] += __shfl_xor_sync(0xffffffffu, z[r], o);
                        const float zr = lane & 2 ? (lane & 1 ? z[3] : z[2]) : (lane & 1 ? z[1] : z[0]);
                        asm volatile("st.shared.f32 [%0], %1;" :: "r"(gbuf + 4 * ((i & 4) + (lane & 3))), "f"(1.f / (1.f + __expf(-zr))) : "memory");
                    }
                }
                fence_proxy_async_smem();
                __syncwarp();
                warp_bulk_store((char*)g_gate + 4 * r0, gbuf, 32);
                bulk_commit();
                bulk_wait<0>();
                __syncwarp();
                if (lane == 0) red_add(&g_sync.count[3], 1);
            }
            __syncwarp();
            {
                const int w = warp - 1;
                uint32_t sph = 0, aph = 0, nann = 0, nattn = 0;
                int unsent = 0, nunsent = 0;
                bool urgent = false;
                auto announce = [&]() {
                    if (!urgent) return;
                    bulk_wait<0>();
                    __syncwarp();
                    const uint32_t hb = bars + B_HALF + 8 * (nann & 3);
                    if (w == 0) {
                        mbar_arrive_if(lane == 0, hb);
                    } else {
                        mbar_wait(hb, (nann >> 2) & 1);
                        const uint32_t type = item_type(unsent), m = item_row(unsent), c = item_col(unsent);
                        const uint32_t word = type < T_B ? c >> 3 : type == T_B ? 2 : offsetof(Sync, ctx) / 8 + m;
                        const uint32_t bit = type < T_B ? 8 * (c & 7) : type == T_B ? 4 * m : type == T_LOCAL ? 32 + c : c;
                        if (lane < nunsent) red_add((unsigned long long*)((char*)&g_sync + 8 * word), 1ull << bit);
                        __syncwarp();
                    }
                    nann++;
                    nunsent = 0; urgent = false;
                };
                auto store_item = [&](int it, bool borrow, bool now) {
                    const int type = item_type(it), m = item_row(it), c = item_col(it);
                    const int npair = type < T_OUT ? 2 : 1;
                    const bool local = type == T_LOCAL;
                    const int grp = type == T_Q ? G_Q + 2 * c : type == T_K ? G_K + 2 * c : type == T_V ? G_V + 2 * c : type == T_B ? G_B + 2 * c
                                  : type == T_ATTN ? G_CTX + c : G_LOC + c;
                    for (int pr = 0; pr < npair; pr++) {
                        if (borrow && pr) {
                            mbar_wait(bars + B_ALT + 8 * w, aph);
                            aph ^= 1;
                            for (int b = 0; b < 2; b++)
                                warp_tma_store(&prm.m[M_SCR_ST], sb + ((nattn & 1) ^ 1) * 32768 + w * 16384 + b * 8192, b * 64, m * 128 + w * 64, grp + 1);
                            bulk_commit();
                            bulk_wait_read<0>();
                            __syncwarp();
                            mbar_arrive_if(lane == 0, bars + B_QFREE);
                            break;
                        }
                        for (int b = 0; b < 2; b++) {
                            if (!__all_sync(0xffffffffu, mbar_test(bars + B_SFULL + 16 * w + 8 * b, sph))) announce();
                            mbar_wait(bars + B_SFULL + 16 * w + 8 * b, sph);
                            warp_tma_store(&prm.m[local ? M_SCR_LOQ : M_SCR_ST], sb + SM_STAGING + w * 16384 + b * 8192,
                                         local ? b * 128 + w * 64 : b * 64, local ? m * 64 : m * 128 + w * 64, grp + pr);
                            bulk_commit();
                            bulk_wait_read<0>();
                            __syncwarp();
                            mbar_arrive_if(lane == 0, bars + B_SEMPTY + 16 * w + 8 * b);
                        }
                        sph ^= 1;
                    }
                    announce();
                    if (lane == nunsent) unsent = it;
                    nunsent++;
                    urgent = now || nunsent == 32 || !local;
                };
                int held = first_item();
                while (true) {
                    if (!__all_sync(0xffffffffu, mbar_test(bars + B_IFULL + 8 * (qn % QDEPTH), (qn / QDEPTH) & 1))) announce();
                    const int it = __shfl_sync(0xffffffffu, next_item(lane == 0), 0), type = item_type(it);
                    const bool keep_held = type == T_LOCAL && (item_type(held) != T_B || (it & ITEM_READY));
                    if (type >= T_ATTN && held < 0 && nunsent) urgent = true;
                    for (int pass = held < 0 || keep_held; pass < 2; pass++) {
                        if (pass && (type < T_OUT || type == T_END)) break;
                        store_item(pass ? it : held, !pass && type == T_ATTN, type >= T_ATTN);
                    }
                    if (type == T_END) break;
                    nattn += type == T_ATTN;
                    if (!keep_held) held = type < T_OUT ? it : -1;
                }
                announce();
                if (item_type(next_item(lane == 0)) == T_OUT) next_item(lane == 0);
            }
        } else {
            if (elect_one()) {
                uint32_t ordy = 0;
                unsigned long long cnt_lo = 0, cnt_hi = 0;
                int late = 0;
                auto refresh = [&]() {
                    if (!late && cnt_lo == 0xccccccccccccccccull && cnt_hi == SEQ / 8) late = 1;
                    asm volatile("ld.acquire.gpu.global.v2.u64 {%0, %1}, [%2];" : "=l"(cnt_lo), "=l"(cnt_hi) : "l"(late ? &g_sync.count[0] : &g_sync.count[2]) : "memory");
                };
                auto inputs_ready = [&](int it) -> bool {
                    const int m = item_row(it), c = item_col(it);
                    if (item_type(it) == T_ATTN) return late && ((c < 16 ? cnt_lo : cnt_hi) >> (4 * (c & 14)) & 255) == 48;
                    return late || (cnt_hi == SEQ / 8 && (cnt_lo >> (4 * m) & 15) == 12 && (cnt_lo >> (4 * max(m - 1, 0)) & 15) == 12);
                };
                auto publish = [&](int it, int step) {
                    const uint32_t slot = qn % QDEPTH;
                    mbar_wait(bars + B_IEMPTY + 8 * slot, ((qn / QDEPTH) & 1) ^ 1);
                    for (uint32_t r = 0; r < 2; r++) {
                        const uint32_t rb = map_cta(bars, r);
                        asm volatile("mbarrier.arrive.expect_tx.shared::cluster.b64 _, [%0], 4;" :: "r"(rb + B_IFULL + 8 * slot) : "memory");
                        asm volatile("st.async.shared::cluster.mbarrier::complete_tx::bytes.u32 [%0], %1, [%2];"
                                     :: "r"(rb + SM_QUEUE + 4 * slot), "r"(it + r * step), "r"(rb + B_IFULL + 8 * slot) : "memory");
                    }
                    qn++;
                };
                int asc = 1;
                int it;
                do {
                    if (rank == 0) {
                        mbar_wait(bars + B_WANT, qn & 1);
                        unsigned i;
                        asm volatile("atom.relaxed.gpu.global.add.u32 %0, [%1], 1;" : "=r"(i) : "l"(&g_sync.next) : "memory");
                        if (cnt_lo != 0x3030303030303030ull || cnt_hi != cnt_lo) refresh();
                        i += NPAIR;
                        const int pit = i < NITEMS ? prm.items[i] : T_END << 13, type = item_type(pit);
                        int step = type == T_LOCAL ? 16 : 1;
                        it = pit + (pit & (step == 1 ? 15 : 0x1f0));
                        if (type == T_ATTN) {
                            if (!asc) { it += 1; step = -1; }
                            it |= asc << 9;
                        }
                        asc = type != T_ATTN || item_row(pit) == 0 || !asc;
                        if (inputs_ready(it)) it |= ITEM_READY;
                        publish(it, step);
                    } else {
                        it = next_item(true);
                    }
                    if ((item_type(it) == T_ATTN || item_type(it) == T_LOCAL) && !(it & ITEM_READY)) {
                        unsigned n = 0;
                        while (!inputs_ready(it)) { refresh(); spin_guard(n); }
                        asm volatile("st.release.cta.shared.u32 [%0], %1;" :: "r"(bars + SM_ORDY + 4), "r"(ordy += 256) : "memory");
                    }
                } while (item_type(it) != T_END);
                if (PF_LOC && blockIdx.x < 128) {
                    prefetch_l2((const char*)g_scr + (uint32_t)(G_LOC * SEQ * 256 + blockIdx.x * 32768), 32768);
                    prefetch_l2(prm.wob + blockIdx.x * 16384, 16384);
                }
                if (rank == 0) {
                    mbar_wait(bars + B_WANT, qn & 1);
                    const unsigned i = atomicAdd(&g_sync.next_out, 1u), t = i < 32 ? 31 - i : i - 32;
                    it = i < 64 ? T_OUT << 13 | ((t & 3) * 2 + (i >> 5)) << 4 | (t >> 2) * 2 : T_END << 13;
                    publish(it, 1);
                } else {
                    it = next_item(true);
                }
                if (item_type(it) == T_OUT) {
                    const uint32_t m = item_row(it), half = item_col(it) & 1, tile = m * 2 + (item_col(it) >> 1);
                    unsigned* split = (unsigned*)((char*)g_sync.split + 4 * tile);
                    unsigned long long rdy = 0;
                    int state = rank ? 2 : 0;
                    for (unsigned n = 0; rdy != 0xffffffffffull || state < 2; spin_guard(n)) {
                        if (rdy != 0xffffffffffull) {
                            rdy = ld_acquire((const unsigned long long*)((char*)g_sync.ctx + 8 * m));
                            asm volatile("st.release.cta.shared.u64 [%0], %1;" :: "r"(bars + SM_ORDY), "l"(rdy) : "memory");
                        }
                        unsigned steps = 0;
                        if (state == 1) {
                            steps = ld_acquire(split);
                        } else if (state == 0 && mbar_test(bars + B_WANT, qn & 1)) {
                            state = 1;
                            unsigned seen;
                            asm volatile("atom.acq_rel.gpu.global.exch.b32 %0, [%1], 1;" : "=r"(seen) : "l"(split) : "memory");
                            if (seen) {
                                const unsigned long long v = ld_acquire((const unsigned long long*)((char*)g_sync.step + 8 * tile));
                                const int d = (int)(v >> 32) - (int)v;
                                steps = (WIDE + min(max(half ? d : -d, K_MEET - K_SPLIT), K_SPLIT - K_MEET)) >> 1;
                                atomicExch(split, WIDE - steps);
                            }
                        }
                        if (steps > 1) { publish(T_END << 13 | steps, 0); state = 2; PMARK(1, 0xF400 + steps); }
                    }
                    if (rank) next_item(true);
                }
                if (rank == 0) for (uint32_t n = qn; n < qn + QDEPTH; n++) mbar_wait(bars + B_IEMPTY + 8 * (n % QDEPTH), ((n / QDEPTH) & 1) ^ 1);
            }
        }
    } else {
        reg_inc<232>();
        const int wg = (warp >> 2) - 1, wq = warp & 3;
        uint32_t gph = 0;
        uint32_t kvn = 0;
        const uint32_t dA = make_desc(sb + wg * 8192, 16);
        uint32_t ti = 0;
        uint32_t sph = 1;
        const uint32_t stg = sb + SM_STAGING + wg * 16384;
        const uint32_t stg_lane = stg + (wq * 16 + (lane & 15)) * 128 + (((lane >> 4) ^ (lane & 7)) << 4);
        auto write_blocks = [&](auto n, uint32_t off, const uint32_t* v) {
            uint32_t a = stg_lane;
            asm volatile("" : "+r"(a));
            a += off;
#pragma unroll
            for (int j = 0; j < decltype(n)::value; j++)
                stmatrix_x4((a ^ (32 * (j & 3))) + (j >> 2) * 8192, v[4 * j], v[4 * j + 1], v[4 * j + 2], v[4 * j + 3]);
        };
        auto release = [&](uint32_t bar) { mbar_arrive_if(lane == 0, bars + bar); };
        const uint32_t bars_lane = map_cta(bars, lane & 1);
        auto release_stage = [&](uint32_t st) { mbar_arrive_cluster_if(lane < 2, bars_lane + B_GEMPTY + 8 * st); };
        auto take_item = [&]() -> int {
            return __shfl_sync(0xffffffffu, next_item(lane == 0, false), 0);
        };
        auto stage_acquire = [&](int b) { mbar_spin(bars + B_SEMPTY + 16 * wg + 8 * b, sph); };
        auto stage_publish = [&](int b) {
            fence_proxy_async_smem();
            __syncwarp();
            release(B_SFULL + 16 * wg + 8 * b);
        };
        auto stage_chunk = [&](int b, const uint32_t* v) {
            stage_acquire(b);
            write_blocks(std::integral_constant<int, 4>(), b * 8192, v);
            stage_publish(b);
            if (b) sph ^= 1;
        };
        auto stage_pair = [&](const uint32_t* v) {
            stage_acquire(0); stage_acquire(1);
            write_blocks(std::integral_constant<int, 8>(), 0, v);
            fence_proxy_async_smem();
            __syncwarp();
            mbar_arrive_if(lane < 2, bars + B_SFULL + 16 * wg + 8 * lane);
            sph ^= 1;
        };
        auto gemm_step = [&](float (&acc)[128], uint32_t dB, int& k) {
            const uint32_t st = k & 3;
            wgmma_wait<0>();
            release_stage((k - 1) & 3);
            mbar_spin(bars + B_GFULL + 8 * st, gph);
            const uint64_t da = full_desc(dA + st * (GST_BYTES >> 4)), db = full_desc(dB + st * (GST_BYTES >> 4));
            wgmma_fence();
#pragma unroll
            for (int kk = 0; kk < 4; kk++) wgmma_ss_n256_tb(acc, da + 2 * kk, db + 128 * kk, 1);
            wgmma_commit();
            gph ^= st == 3;
            k++;
        };
        if (wg == 1) bar_arrive(1, 256);
        int it = first_item();
        while (item_type(it) != T_END) {
            if (item_type(it) <= T_LOCAL) {
                float acc[128];
                uint32_t pk[64];
                bool pending = false;
                bool held_b = false;
                zero_regs(pk);
                const uint32_t dB = make_desc(sb + 16384, 8192);
                do {
                    const int type = item_type(it);
                    if (type == T_LOCAL) {
                        int ln = lane;
                        asm volatile("" : "+r"(ln));
                        const int g = ln >> 2, t = ln & 3, par = wq & 1;
                        const uint32_t hc = (wq >> 1) * 4, pl = sb + (par * 2 + wg) * LOC_PLANE;
                        const uint32_t a16 = (ln & 15) * 128 + (((hc + (ln >> 4)) ^ (ln & 7)) << 4), a8 = (ln & 7) * 128 + (((hc + (ln >> 3)) ^ (ln & 7)) << 4);
                        const bool first0 = 2 * t > g, first1 = 2 * t + 1 > g;
                        const uint32_t fmask = (first0 ? 0xffffu : 0u) | (first1 ? 0xffff0000u : 0u);
                        const bool edge = item_row(it) == 0;
                        uint32_t q[4][2][4], kf[9][4], vf[9][4];
                        float w[8];
                        mbar_spin(bars + B_GFULL, gph);
#pragma unroll
                        for (int u = 0; u < 4; u++) { ldsm_x4(q[u][0], pl + u * 2048 + a16); ldsm_x4(q[u][1], pl + u * 2048 + (a16 ^ 32)); }
#pragma unroll
                        for (int j = 0; j < 8; j++) w[j] = lds_f32(sb + 4 * LOC_PLANE + 4 * (2 * g + par) + 64 * j);
                        __syncwarp();
                        release_stage(0);
                        mbar_spin(bars + B_GFULL + 8, gph);
#pragma unroll
                        for (int n = 0; n < 9; n++) ldsm_x4(kf[n], pl + GST_BYTES + n * 1024 + a8);
                        __syncwarp();
                        release_stage(1);
                        float s[8][2];
#pragma unroll
                        for (int u = 0; u < 4; u++) {
                            float d[3][4];
#pragma unroll
                            for (int nt = 0; nt < 3; nt++) {
                                mma_k16_init(d[nt], q[u][0], kf[2 * u + nt][0], kf[2 * u + nt][1]);
                                mma_k16(d[nt], q[u][1], kf[2 * u + nt][2], kf[2 * u + nt][3]);
                            }
                            if (u == 0 && edge) { d[0][0] = -INFINITY; d[0][1] = -INFINITY; }
                            s[2 * u][0] = first0 ? d[0][0] : d[1][0]; s[2 * u][1] = first1 ? d[0][1] : d[1][1];
                            s[2 * u + 1][0] = first0 ? d[1][2] : d[2][2]; s[2 * u + 1][1] = first1 ? d[1][3] : d[2][3];
                        }
                        mbar_spin(bars + B_GFULL + 16, gph);
#pragma unroll
                        for (int u = 0; u < 4; u++) { ldsm_x4_t(vf[2 * u], pl + 2 * GST_BYTES + u * 2048 + a16); ldsm_x4_t(vf[2 * u + 1], pl + 2 * GST_BYTES + u * 2048 + (a16 ^ 32)); }
                        ldsm_x4_t(vf[8], pl + 2 * GST_BYTES + 8192 + a8);
                        __syncwarp();
                        release_stage(2);
                        float x[8];
#pragma unroll
                        for (int j = 0; j < 8; j++) x[j] = fmaxf(s[j][0], s[j][1]);
#pragma unroll
                        for (int o = 1; o < 4; o *= 2)
#pragma unroll
                            for (int j = 0; j < 8; j++) x[j] = fmaxf(x[j], __shfl_xor_sync(0xffffffffu, x[j], o));
#pragma unroll
                        for (int j = 0; j < 8; j++) {
                            const float n = x[j] * -LOC_SCALE;
                            s[j][0] = ex2(fmaf(s[j][0], LOC_SCALE, n)); s[j][1] = ex2(fmaf(s[j][1], LOC_SCALE, n));
                            x[j] = s[j][0] + s[j][1];
                        }
#pragma unroll
                        for (int o = 1; o < 4; o *= 2)
#pragma unroll
                            for (int j = 0; j < 8; j++) x[j] += __shfl_xor_sync(0xffffffffu, x[j], o);
                        mbar_spin(bars + B_GFULL + 24, gph);
                        release_stage(3);
                        it = take_item();
                        uint32_t ob[4][8];
#pragma unroll
                        for (int u = 0; u < 4; u++) {
                            const float r0 = rcp(x[2 * u]), r1 = rcp(x[2 * u + 1]), f0 = fmaf(-w[2 * u], r0, r0), f1 = fmaf(-w[2 * u + 1], r1, r1);
                            const uint32_t p0 = pack_bf16(s[2 * u][0] * f0, s[2 * u][1] * f0), p1 = pack_bf16(s[2 * u + 1][0] * f1, s[2 * u + 1][1] * f1);
                            const uint32_t pa[4] = {p0 & fmask, 0, p0 & ~fmask, p1 & fmask};
#pragma unroll
                            for (int c = 0; c < 4; c++) {
                                float ol[4];
                                mma_k16_init(ol, pa, vf[2 * u + (c >> 1)][2 * (c & 1)], vf[2 * u + (c >> 1)][2 * (c & 1) + 1]);
                                mma_k8(ol, 0, p1 & ~fmask, u < 3 ? vf[2 * u + 2 + (c >> 1)][2 * (c & 1)] : vf[8][c]);
                                ob[u][2 * c] = pack_bf16(ol[0], ol[1]);
                                ob[u][2 * c + 1] = pack_bf16(ol[2], ol[3]);
                            }
                        }
                        stage_acquire(0); stage_acquire(1);
#pragma unroll
                        for (int u = 0; u < 4; u++) {
                            stmatrix_x4(stg + par * 8192 + u * 2048 + a16, ob[u][0], ob[u][1], ob[u][2], ob[u][3]);
                            stmatrix_x4(stg + par * 8192 + u * 2048 + (a16 ^ 32), ob[u][4], ob[u][5], ob[u][6], ob[u][7]);
                        }
                        fence_proxy_async_smem();
                        __syncwarp();
                        mbar_arrive_if(lane < 2, bars + B_SFULL + 16 * wg + 8 * lane);
                        bar_sync(4, 256);
                        sph ^= 1; gph ^= 1;
                        continue;
                    }
                    mbar_spin(bars + B_GFULL, gph);
                    bool more;
                    do {
                        wgmma_fence();
                        wgmma_ss_n256_tb_init(acc, full_desc(dA), full_desc(dB));
#pragma unroll
                        for (int kk = 1; kk < 4; kk++) wgmma_ss_n256_tb(acc, full_desc(dA) + 2 * kk, full_desc(dB) + 128 * kk, 1);
                        wgmma_commit();
                        const int nk = item_type(it) == T_K || item_type(it) == T_V ? 8 : 16;
                        int k = 1;
                        do {
                            if (pending) {
                                const int kf = k - 1 - wg;
                                if (kf == 0) stage_chunk(0, pk);
                                else if (kf == 1) stage_chunk(1, pk + 16);
                                else if (kf == KF2) stage_chunk(0, pk + 32);
                                else if (kf == KF2 + 1) stage_chunk(1, pk + 48);
                            }
                            gemm_step(acc, dB, k);
                        } while (k < nk);
                        held_b = item_type(it) == T_B;
                        const bool is_q = item_type(it) == T_Q;
                        it = take_item();
                        more = item_type(it) < T_LOCAL;
                        if (more) mbar_spin(bars + B_GFULL, gph);
                        wgmma_wait<0>();
                        fence_regs(acc);
                        release_stage(3);
                        if (is_q) {
#pragma unroll
                            for (int j = 0; j < 128; j++) acc[j] *= SM_SCALE;
                        }
#pragma unroll
                        for (int j = 0; j < 64; j++) pk[j] = pack_bf16(acc[2 * j], acc[2 * j + 1]);
                        pending = true;
                    } while (more);
                } while (item_type(it) < T_LOCAL || (item_type(it) == T_LOCAL && (!held_b || (it & ITEM_READY))));
                if (pending) { stage_chunk(0, pk); stage_chunk(1, pk + 16); }
                if (pending && item_type(it) == T_ATTN) {
                    mbar_spin(bars + B_GEMPTY, gph ^ 1); mbar_spin(bars + B_GEMPTY + 8, gph ^ 1);
                    write_blocks(std::integral_constant<int, 8>(), ((ti & 1) ^ 1) * 32768 - SM_STAGING, pk + 32);
                    fence_proxy_async_smem();
                    __syncwarp();
                    release(B_ALT + 8 * wg);
                } else if (pending) {
                    stage_chunk(0, pk + 32); stage_chunk(1, pk + 48);
                }
            } else {
                float o[64], s[64];
                uint32_t pa[32], pb[32];
                zero_regs(o); zero_regs(s); zero_regs(pa);
                float n0 = 0.f, n1 = 0.f;
                bool shifted = false;
                float l0 = 1.f, l1 = 1.f, f0 = 0.f, f1 = 0.f, g0 = 0.f, g1 = 0.f;
                uint32_t has_pv = 0;
                int first = 0;
                int pending = 0;
                const uint32_t dK = make_desc(sb + SM_KV, 16), dV = make_desc(sb + SM_KV, 16384);
                const uint32_t lane_off = bars_lane - bars + B_AEMPTY - B_AFULL;
                int cur = 0;
                uint32_t qoff = 0;
                const int row = wg * 64 + wq * 16 + (lane >> 2);
                const float thr = (row & 63) - (lane & 3) * 2;
                uint32_t peek = 0;
                bool peek_ok = false;
                auto kv_wait = [&](uint32_t n) { mbar_spin(bars + B_AFULL + 16 + 8 * (n & 3), (n >> 2) & 1); };
                auto kv_release = [&](uint32_t n) { mbar_arrive_cluster_if(lane < 2, bars_lane + B_AEMPTY + 16 + 8 * (n & 3)); };
                struct Slot { uint32_t bar, par, off; } slot[4];
                auto align = [&]() {
#pragma unroll
                    for (uint32_t i = 0; i < 4; i++) {
                        const uint32_t n = kvn + (i == 1 ? has_pv : i);
                        slot[i].bar = bars + B_AFULL + 16 + 8 * (n & 3); slot[i].par = (n >> 2) & 1; slot[i].off = (n & 3) * 2048;
                    }
                };
                align();
                auto scale_o = [&]() {
#pragma unroll
                    for (int j = 0; j < 16; j++) { o[4 * j] *= f0; o[4 * j + 1] *= f0; o[4 * j + 2] *= f1; o[4 * j + 3] *= f1; }
                };
                auto pack_o = [&](uint32_t (&v)[32]) {
#pragma unroll
                    for (int j = 0; j < 32; j++) v[j] = pack_bf16(o[2 * j], o[2 * j + 1]);
                };
                auto publish_o = [&]() {
                    fence_proxy_async_smem();
                    __syncwarp();
                    mbar_arrive_if(lane < 2, bars + B_SFULL + 16 * wg + 8 * lane);
                    sph ^= 1;
                };
                auto scales = [&]() { f0 = g0 * rcp(quad_sum(l0)); f1 = g1 * rcp(quad_sum(l1)); };
                auto step = [&](auto even, uint32_t (&pin)[32], uint32_t (&pout)[32], bool fresh, bool diag, bool last) {
                    constexpr bool EVEN = decltype(even)::value;
                    Slot& sk = slot[EVEN ? 0 : 2];
                    Slot& sv = slot[EVEN ? 1 : 3];
                    kvn += EVEN ? 1 + has_pv : 2;
                    mbar_spin(sk.bar, sk.par);
                    bar_sync(1 + wg, 256);
                    qk_gemm(s, dA + qoff, dK + sk.off);
                    if (EVEN && fresh) {
                        scales();
                        g0 = lds_f32(bars + SM_GATE + (ti & 1) * 512 + 4 * row); g1 = lds_f32(bars + SM_GATE + (ti & 1) * 512 + 4 * row + 32);
                        ti++;
                        n0 = 0.f; n1 = 0.f; l0 = 0.f; l1 = 0.f;
                        shifted = false;
                        if (has_pv) { stage_acquire(0); stage_acquire(1); }
                    }
                    if (!EVEN && pending) {
                        pack_o(pout);
                        write_blocks(std::integral_constant<int, 8>(), 0, pout);
                    }
                    mbar_spin(sv.bar, sv.par);
                    pv_gemm(o, pin, dV + sv.off, EVEN || !first);
                    bar_arrive(2 - wg, 256);
                    sk.par ^= 1; sv.par ^= 1;
                    wgmma_wait<1>();
                    fence_regs(s);
                    mbar_arrive_cluster_if(lane < 2 && (!EVEN || has_pv), sk.bar + lane_off);
                    mbar_arrive_if(lane == 0 && last, bars + B_AEMPTY + 8 * ((ti - 1) & 1));
                    if (diag || shifted) {
                        if (diag) causal_mask(s, thr, wg);
                        if (shifted) shift_rows(s, n0, n1);
                    }
                    peek_ok = mbar_test(bars + B_AFULL + 8 * (ti & 1), (ti >> 1) & 1);
                    asm volatile("ld.shared.u32 %0, [%1];" : "=r"(peek) : "r"(bars + SM_QUEUE + 4 * (qn % QDEPTH)) : "memory");
                    float r0, r1;
                    exp_pack(pout, s, r0, r1);
                    if (__any_sync(0xffffffffu, fmaxf(r0, r1) >= SUM_LIMIT || (EVEN && fresh && !(lane & 3) && !(fminf(s[0], s[2]) >= -REF_RANGE)))) {
                        float x0, x1;
                        row_max(s, x0, x1);
                        if (!(EVEN && fresh)) { x0 = fmaxf(x0, 0.f); x1 = fmaxf(x1, 0.f); }
                        float a0 = ex2(-x0), a1 = ex2(-x1);
                        n0 += x0; n1 += x1;
                        shifted = true;
                        if (EVEN && fresh) { a0 = 1.f; a1 = 1.f; }
                        l0 *= a0; l1 *= a1;
                        wgmma_wait<0>();
                        fence_regs(o);
#pragma unroll
                        for (int q = 0; q < 16; q++) { o[4 * q] *= a0; o[4 * q + 1] *= a0; o[4 * q + 2] *= a1; o[4 * q + 3] *= a1; }
                        shift_rows(s, x0, x1);
                        exp_pack(pout, s, r0, r1);
                    }
                    l0 += r0; l1 += r1;
                    wgmma_wait<0>();
                    fence_regs(o);
                    fence_regs(pin);
                    mbar_arrive_cluster_if(lane < 2, sv.bar + lane_off);
                };
                auto copy_p = [&]() {
#pragma unroll
                    for (int j = 0; j < 32; j++) pa[j] = __float_as_uint(__uint_as_float(pb[j]) + __uint_as_float(prm.zero));
                };
                int rem = 0;
                mbar_spin(bars + B_AFULL + 8 * (ti & 1), (ti >> 1) & 1);
                while (true) {
                    const bool fresh = rem == 0;
                    if (fresh) {
                        if (has_pv) {
                            if (__all_sync(0xffffffffu, peek_ok)) {
                                mbar_arrive_cluster_if(lane == 0, bars0 + B_IEMPTY + 8 * (qn % QDEPTH));
                                qn++;
                                it = __shfl_sync(0xffffffffu, peek, 0);
                                if (item_row(cur) < 2) break;
                            } else {
                                it = take_item();
                                if (item_row(cur) < 2 || item_type(it) != T_ATTN) break;
                                mbar_spin(bars + B_AFULL + 8 * (ti & 1), (ti >> 1) & 1);
                            }
                        }
                        cur = it;
                        qoff = (ti & 1) * 2048;
                    }
                    const bool last = fresh ? item_row(cur) == 0 : rem == 1;
                    step(std::true_type(), pa, pb, fresh, item_asc(cur) ? last : fresh, last);
                    first = fresh;
                    if (fresh) {
                        pending = has_pv; has_pv = 1;
                        if (!pending) { kvn -= 2; align(); kvn += 2; slot[0].par ^= 1; slot[1].par ^= 1; }
                        else scale_o();
                        rem = item_row(cur);
                        if (rem == 0) {
                            copy_p();
                            continue;
                        }
                    } else if (--rem == 0) {
                        copy_p();
                        align();
                        continue;
                    }
                    step(std::false_type(), pb, pa, false, item_asc(cur) && rem == 1, rem == 1);
                    if (pending) publish_o();
                    pending = 0; first = 0;
                    rem--;
                }
                const uint32_t skip = item_asc(cur) & ~item_row(cur) & 1;
                kvn += skip;
#pragma unroll 1
                for (int pass = pending ? 0 : 1; pass < 2; pass++) {
                    if (pass) {
                        kv_wait(kvn);
                        pv_gemm(o, pa, dV + (kvn & 3) * 2048, !first);
                        scales();
                        wgmma_wait<0>();
                        fence_regs(o);
                        kv_release(kvn);
                        kvn += 1 + skip;
                        scale_o();
                    }
                    pack_o(pb);
                    stage_pair(pb);
                }
            }
        }
        it = take_item();
        if (item_type(it) == T_OUT) {
            float acc[128];
            const uint32_t dB = make_desc(sb + 16384, 8192);
            mbar_spin(bars + B_GFULL, gph);
            wgmma_fence();
            wgmma_ss_n256_tb_init(acc, full_desc(dA), full_desc(dB));
#pragma unroll
            for (int kk = 1; kk < 4; kk++) wgmma_ss_n256_tb(acc, full_desc(dA) + 2 * kk, full_desc(dB) + 128 * kk, 1);
            wgmma_commit();
            uint32_t ln;
            asm volatile("mov.u32 %0, %%laneid;" : "=r"(ln));
            const uint32_t slot = (it & 127) * 32768 + (wg * 128 + wq * 32 + ln) * 16;
            char* const mine = (char*)g_part + slot;
            int k = 1, nk = 80;
            do {
                if (k == K_MEET - 5) {
#pragma unroll
                    for (int j = 0; j < 8; j++) st_b128(mine + j * 4096, 0, 0, 0, 0);
                    __syncwarp();
                }
                if (k == K_SPLIT) nk = take_item() & 127;
                gemm_step(acc, dB, k);
            } while (k < nk);
            auto triple = [&](uint32_t nrel) {
                const uint32_t s0 = k & 3, s1 = (k + 1) & 3, o0 = s0 * (GST_BYTES >> 4), o1 = s1 * (GST_BYTES >> 4);
                wgmma_wait<0>();
                mbar_arrive_cluster_if(ln < nrel, bars_lane + B_GEMPTY + 8 * ((k - 1 - (ln >> 1)) & 3));
                mbar_spin(bars + B_GFULL + 8 * s0, gph);
                gph ^= s0 == 3;
                wgmma_fence();
#pragma unroll
                for (int kk = 0; kk < 4; kk++) wgmma_ss_n128_lo_tb(acc, full_desc(dA + o0) + 2 * kk, full_desc(dB + o0) + 128 * kk, 1);
                mbar_spin(bars + B_GFULL + 8 * s1, gph);
                gph ^= s1 == 3;
                wgmma_fence();
#pragma unroll
                for (int kk = 0; kk < 4; kk++) wgmma_ss_n128_lo_tb(acc, full_desc(dA + o0 + 2048) + 2 * kk, full_desc(dB + o1 + 1024) + 128 * kk, 1);
#pragma unroll
                for (int kk = 0; kk < 4; kk++) wgmma_ss_n128_lo_tb(acc, full_desc(dA + o1) + 2 * kk, full_desc(dB + o1) + 128 * kk, 1);
                wgmma_commit();
                k += 2;
            };
            triple(2);
#pragma unroll
            for (int j = 0; j < 8; j++) {
                uint32_t v[4];
#pragma unroll
                for (int i = 0; i < 4; i++) {
                    asm volatile("" : "+f"(acc[64 + 8 * j + 2 * i]), "+f"(acc[65 + 8 * j + 2 * i]) :: "memory");
                    v[i] = pack_bf16(acc[64 + 8 * j + 2 * i], acc[65 + 8 * j + 2 * i]);
                }
                if (j == SPREAD) triple(4);
                else if (PACE && j) __nanosleep(PACE);
                st_b128(mine + j * 4096, ~v[0], v[1], v[2], v[3]);
            }
#pragma unroll 1
            for (int t = 2; t < TRIPLES; t++) triple(4);
            uint32_t pk[32];
            char* const other = (char*)g_part + (slot ^ (16 * 32768));
            while (true) {
                bool miss = false;
#pragma unroll
                for (int j = 0; j < 8; j++) ld_b128(other + j * 4096, pk[4 * j], pk[4 * j + 1], pk[4 * j + 2], pk[4 * j + 3]);
#pragma unroll
                for (int j = 0; j < 8; j++) miss |= pk[4 * j] == 0;
                if (!__any_sync(0xffffffffu, miss)) break;
                while (__any_sync(0xffffffffu, pk[28] == 0)) ld_b128(other + 7 * 4096, pk[28], pk[29], pk[30], pk[31]);
            }
#pragma unroll
            for (int j = 0; j < 32; j++) {
                const uint32_t v = j & 3 ? pk[j] : ~pk[j];
                acc[64 + 2 * j] = __uint_as_float(v << 16); acc[65 + 2 * j] = __uint_as_float(v & 0xffff0000u);
                asm volatile("" : "+f"(acc[64 + 2 * j]), "+f"(acc[65 + 2 * j]) :: "memory");
            }
            stage_acquire(0); stage_acquire(1);
            wgmma_wait<0>();
#pragma unroll
            for (int j = 0; j < 64; j++) asm volatile("" : "+f"(acc[j]) :: "memory");
            mbar_arrive_cluster_if(ln < 4, bars_lane + B_GEMPTY + 8 * ((k - 1 - (ln >> 1)) & 3));
#pragma unroll
            for (int j = 0; j < 32; j++)
                pk[j] = pack_bf16(acc[2 * j] + acc[64 + 2 * j], acc[2 * j + 1] + acc[65 + 2 * j]);
            write_blocks(std::integral_constant<int, 8>(), 0, pk);
            __syncwarp();
            uint4* dst = (uint4*)((char*)prm.out + (uint32_t)((item_row(it) * 128 + wg * 64 + wq * 16 + (ln >> 4)) * 2048 + item_col(it) * 256 + (ln & 15) * 16));
#pragma unroll
            for (int j = 0; j < 8; j++) {
                const int r = 2 * j + (ln >> 4);
                uint4 v;
                asm volatile("ld.shared.v4.u32 {%0, %1, %2, %3}, [%4];" : "=r"(v.x), "=r"(v.y), "=r"(v.z), "=r"(v.w)
                             : "r"(stg + wq * 2048 + r * 128 + (ln & 8) * 1024 + (((ln & 7) ^ (r & 7)) << 4)) : "memory");
                dst[j * 256] = v;
            }
        }
    }
}

typedef CUresult (*EncodeFn)(CUtensorMap*, CUtensorMapDataType, cuuint32_t, void*, const cuuint64_t*, const cuuint64_t*,
                             const cuuint32_t*, const cuuint32_t*, CUtensorMapInterleave, CUtensorMapSwizzle,
                             CUtensorMapL2promotion, CUtensorMapFloatOOBfill);

void encode3(EncodeFn fn, CUtensorMap* m, const void* ptr, uint64_t d0, uint64_t d1, uint64_t d2, uint64_t s1, uint64_t s2,
             uint32_t b0, uint32_t b1, uint32_t b2) {
    cuuint64_t dims[3] = {d0, d1, d2};
    cuuint64_t strides[2] = {s1, s2};
    cuuint32_t box[3] = {b0, b1, b2};
    cuuint32_t es[3] = {1, 1, 1};
    fn(m, CU_TENSOR_MAP_DATA_TYPE_BFLOAT16, 3, const_cast<void*>(ptr), dims, strides, box, es, CU_TENSOR_MAP_INTERLEAVE_NONE,
       CU_TENSOR_MAP_SWIZZLE_128B, CU_TENSOR_MAP_L2_PROMOTION_NONE, CU_TENSOR_MAP_FLOAT_OOB_FILL_NONE);
}
void map_act(EncodeFn fn, CUtensorMap* m, const void* p, int rows, int cols, int box_rows) {
    encode3(fn, m, p, cols, rows, 1, (uint64_t)cols * 2, (uint64_t)cols * rows * 2, 64, box_rows, 1);
}
void map_wgt(EncodeFn fn, CUtensorMap* m, const void* p, int K, int N) {
    encode3(fn, m, p, 64, K, N / 64, (uint64_t)N * 2, 128, 64, 64, 2);
}

void build_schedule(Params& p) {
    int n = 0;
    auto add = [&](int type, int col, int row) { p.items[n++] = (uint16_t)(type << 13 | col << 4 | row); };
    auto add_qkv = [&](int c) {
        for (int m = 0; m < 8; m++) add(T_Q, c, m);
        for (int m = 0; m < 8; m++) add(T_K, c, m);
        for (int m = 0; m < 8; m++) add(T_V, c, m);
    };
    int ldist = 200, ldist2 = 260, lstep = 8, beta = 26, tail = 32, late = 6, early = 8, epos = 100;
    int order[16] = {6, 7, 8, 9, 10, 11, 12, 13, 14, 15, 5, 4, 3, 2, 1, 0};
    uint16_t proj[480];
    for (int m = 0; m < 8; m++) for (int c = 0; c < 12; c++) add(T_B, c, m);
    for (int c = 0; c < 16; c++) add_qkv(c);
    for (int i = 0; i < 480; i++) proj[i] = p.items[i];
    n = 0;
    for (int i = 0, l = 0; i < 480; i++) {
        p.items[n++] = proj[i];
        for (; l < 64 && i >= (l < 40 ? ldist + lstep * l / 8 : ldist2 + lstep * (l - 40) / 8); l++) add(T_LOCAL, l & 3, l >> 2);
    }
    const int a0 = n;
    for (int key = 0; key < 4000; key++)
        for (int r = 0; r < 32; r++)
            for (int j = 7; j >= 0; j--)
                if ((j ? (7 - j) * 40 + r * beta : 3999) == key) add(T_ATTN, 2 * order[r >> 1] + (r & 1), j);
    int t0 = n;
    for (int work = 0; work < 32 * 136 * tail / 100;) work += 4 * (p.items[--t0] & 15) + 3;
    for (int i = t0 + 1; i < n; i++)
        for (int j = i; j > t0 && (p.items[j] & 15) > (p.items[j - 1] & 15); j--) { const uint16_t t = p.items[j]; p.items[j] = p.items[j - 1]; p.items[j - 1] = t; }
    for (int r = early - 1; r >= 0; r--) {
        const uint16_t t = p.items[n - 32 + early - 1];
        for (int j = n - 32 + early - 1; j > n - epos; j--) p.items[j] = p.items[j - 1];
        p.items[n - epos] = t;
    }
    for (int moved = 0; moved < 2 && late >= 0; moved++)
        for (int i = a0; i < n; i++)
            if (p.items[i] == (T_ATTN << 13 | (2 * order[15] + moved) << 4 | late)) {
                for (int j = i; j + 1 < n; j++) p.items[j] = p.items[j + 1];
                p.items[n - 1] = (uint16_t)(T_ATTN << 13 | (2 * order[15] + moved) << 4 | late);
                break;
            }
    for (int s = 0, lo = 0, hi = WIDE - 1; s < 80; s++) {
        const int r = s / 2, g = r < 8 ? 32 + r : 2 * order[r / 2 - 4] + (r & 1);
        p.ostep[s >= WIDE ? s : r & 1 ? hi-- : lo++] = (uint8_t)(2 * g + (s & 1));
    }
}

void build_params(Params& p, void* const* d_in, void* d_out) {
    void* fnp = nullptr;
    cudaDriverEntryPointQueryResult qr;
    cudaGetDriverEntryPoint("cuTensorMapEncodeTiled", &fnp, cudaEnableDefault, &qr);
    EncodeFn fn = (EncodeFn)fnp;
    void* scr = nullptr;
    cudaGetSymbolAddress(&scr, g_scr);
    map_act(fn, &p.m[M_X], d_in[0], SEQ, 1024, 128);
    map_act(fn, &p.m[M_C], d_in[1], SEQ, 512, 128);
    map_wgt(fn, &p.m[M_WQ], d_in[2], 1024, 4096);
    map_wgt(fn, &p.m[M_WUK], d_in[3], 512, 4096);
    map_wgt(fn, &p.m[M_WUV], d_in[4], 512, 4096);
    map_wgt(fn, &p.m[M_WO], d_in[5], 4096, 1024);
    map_wgt(fn, &p.m[M_WQKV], d_in[7], 1024, 3072);
    map_wgt(fn, &p.m[M_WOB], d_in[8], 1024, 1024);
    encode3(fn, &p.m[M_SCR_LD], scr, 128, SEQ, G_TOTAL, 256, (uint64_t)SEQ * 256, 64, 128, 1);
    encode3(fn, &p.m[M_SCR_LOC], scr, 256, SEQ / 2, G_TOTAL, 512, (uint64_t)SEQ * 256, 64, 72, 1);
    encode3(fn, &p.m[M_SCR_LOQ], scr, 256, SEQ / 2, G_TOTAL, 512, (uint64_t)SEQ * 256, 64, 64, 1);
    encode3(fn, &p.m[M_SCR_ST], scr, 128, SEQ, G_TOTAL, 256, (uint64_t)SEQ * 256, 64, 64, 1);
    p.x = (const __nv_bfloat16*)d_in[0];
    p.gate_w = (const __nv_bfloat16*)d_in[9];
    p.zero = 0;
    p.wo = (const char*)d_in[5];
    p.wob = (const char*)d_in[8];
    p.out = (__nv_bfloat16*)d_out;
    build_schedule(p);
}

}

extern "C" void kernel_launch(void* const* d_in, const int* in_sizes, int n_in, void* d_out, int out_size) {
    (void)in_sizes; (void)n_in; (void)out_size;
    Params p;
    build_params(p, d_in, d_out);
    cudaFuncSetAttribute(fused_kernel, cudaFuncAttributeMaxDynamicSharedMemorySize, SM_TOTAL);
    fused_kernel<<<NCTA, 384, SM_TOTAL>>>(p);
}
```

```cpp
#include <cuda_runtime.h>
#include <cuda_bf16.h>
#include <cuda.h>
#include <stddef.h>
#include <stdint.h>
#include <type_traits>

namespace {

constexpr int SEQ = 2048;
constexpr int G_Q = 0, G_K = 32, G_V = 64, G_B = 96, G_CTX = G_Q, G_LOC = G_B, G_TOTAL = 120;

__device__ __align__(1024) __nv_bfloat16 g_scr[(size_t)G_TOTAL * SEQ * 128];
__device__ __align__(128) float g_gate[SEQ];

__device__ __forceinline__ uint32_t smem_u32(const void* p) { return (uint32_t)__cvta_generic_to_shared(p); }
__device__ __forceinline__ bool elect_one() {
    uint32_t p;
    asm volatile("{\n.reg .pred P;\nelect.sync _|P, 0xffffffff;\nselp.u32 %0, 1, 0, P;\n}\n" : "=r"(p));
    return p != 0;
}
__device__ __forceinline__ void mbar_init(uint32_t bar, uint32_t count) {
    asm volatile("mbarrier.init.shared::cta.b64 [%0], %1;" :: "r"(bar), "r"(count) : "memory");
}
__device__ __forceinline__ void mbar_expect_tx(uint32_t bar, uint32_t bytes) {
    asm volatile("mbarrier.arrive.expect_tx.shared::cta.b64 _, [%0], %1;" :: "r"(bar), "r"(bytes) : "memory");
}
__device__ __forceinline__ uint32_t cluster_rank() { uint32_t r; asm("mov.u32 %0, %%cluster_ctarank;" : "=r"(r)); return r; }
__device__ __forceinline__ uint32_t map_cta(uint32_t addr, uint32_t cta) {
    uint32_t r; asm("mapa.shared::cluster.u32 %0, %1, %2;" : "=r"(r) : "r"(addr), "r"(cta)); return r;
}
__device__ __forceinline__ void mbar_arrive_cluster_if(bool pred, uint32_t cluster_bar) {
    asm volatile("{\n.reg .pred P;\nsetp.ne.u32 P, %1, 0;\n@P mbarrier.arrive.shared::cluster.b64 _, [%0];\n}\n"
                 :: "r"(cluster_bar), "r"((uint32_t)pred) : "memory");
}
__device__ __forceinline__ void mbar_arrive_cluster_n_if(bool pred, uint32_t cluster_bar, uint32_t count) {
    asm volatile("{\n.reg .pred P;\nsetp.ne.u32 P, %1, 0;\n@P mbarrier.arrive.shared::cluster.b64 _, [%0], %2;\n}\n"
                 :: "r"(cluster_bar), "r"((uint32_t)pred), "r"(count) : "memory");
}
__device__ __forceinline__ void mbar_arrive_if(bool pred, uint32_t bar) {
    asm volatile("{\n.reg .pred P;\nsetp.ne.u32 P, %1, 0;\n@P mbarrier.arrive.shared::cta.b64 _, [%0];\n}\n"
                 :: "r"(bar), "r"((uint32_t)pred) : "memory");
}
__device__ __forceinline__ bool mbar_test(uint32_t bar, uint32_t parity) {
    uint32_t ok;
    asm volatile("{\n.reg .pred P;\nmbarrier.test_wait.parity.shared::cta.b64 P, [%1], %2;\nselp.u32 %0, 1, 0, P;\n}\n"
                 : "=r"(ok) : "r"(bar), "r"(parity) : "memory");
    return ok != 0;
}
__device__ __forceinline__ void mbar_wait(uint32_t bar, uint32_t parity) {
    asm volatile("{\n.reg .pred P;\n.reg .u32 c;\n"
                 "mbarrier.try_wait.parity.shared::cta.b64 P, [%0], %1;\n"
                 "@P bra DONE;\n"
                 "mov.u32 c, 0;\n"
                 "SPIN:\n"
                 "mbarrier.try_wait.parity.shared::cta.b64 P, [%0], %1;\n"
                 "@P bra DONE;\n"
                 "add.u32 c, c, 1;\n"
                 "setp.lt.u32 P, c, 4194304;\n"
                 "@P bra SPIN;\n"
                 "trap;\n"
                 "DONE:\n}\n" :: "r"(bar), "r"(parity) : "memory");
}
__device__ __forceinline__ void mbar_spin(uint32_t bar, uint32_t parity) {
    asm volatile("{\n.reg .pred P;\n"
                 "SPIN:\n"
                 "mbarrier.try_wait.parity.shared::cta.b64 P, [%0], %1;\n"
                 "@!P bra SPIN;\n}\n" :: "r"(bar), "r"(parity) : "memory");
}
__device__ __forceinline__ void bar_sync(int id, int n) { asm volatile("bar.sync %0, %1;" :: "r"(id), "r"(n) : "memory"); }
__device__ __forceinline__ void bar_arrive(int id, int n) { asm volatile("bar.arrive %0, %1;" :: "r"(id), "r"(n) : "memory"); }
__device__ __forceinline__ void fence_proxy_async_smem() { asm volatile("fence.proxy.async.shared::cta;" ::: "memory"); }
__device__ __forceinline__ void tma_load_3d(uint32_t dst, const CUtensorMap* map, uint32_t bar, int c0, int c1, int c2) {
    asm volatile("cp.async.bulk.tensor.3d.shared::cluster.global.mbarrier::complete_tx::bytes [%0], [%1, {%3, %4, %5}], [%2];"
                 :: "r"(dst), "l"(map), "r"(bar), "r"(c0), "r"(c1), "r"(c2) : "memory");
}
__device__ __forceinline__ void warp_expect_tx(uint32_t bar, uint32_t bytes) {
    asm volatile("{\n.reg .pred P;\nelect.sync _|P, 0xffffffff;\n@P mbarrier.arrive.expect_tx.shared::cta.b64 _, [%0], %1;\n}\n"
                 :: "r"(bar), "r"(bytes) : "memory");
}
__device__ __forceinline__ void warp_tma_load(uint32_t dst, const CUtensorMap* map, uint32_t bar, int c0, int c1, int c2) {
    asm volatile("{\n.reg .pred P;\nelect.sync _|P, 0xffffffff;\n"
                 "@P cp.async.bulk.tensor.3d.shared::cluster.global.mbarrier::complete_tx::bytes [%0], [%1, {%3, %4, %5}], [%2];\n}\n"
                 :: "r"(dst), "l"(map), "r"(bar), "r"(c0), "r"(c1), "r"(c2) : "memory");
}
__device__ __forceinline__ void warp_tma_load_pair(uint32_t dst, const CUtensorMap* map, uint32_t bar, int c0, int c1, int c2) {
    asm volatile("{\n.reg .pred P;\nelect.sync _|P, 0xffffffff;\n"
                 "@P cp.async.bulk.tensor.3d.shared::cluster.global.mbarrier::complete_tx::bytes.multicast::cluster"
                 " [%0], [%1, {%3, %4, %5}], [%2], %6;\n}\n"
                 :: "r"(dst), "l"(map), "r"(bar), "r"(c0), "r"(c1), "r"(c2), "h"((uint16_t)3) : "memory");
}
__device__ __forceinline__ void warp_bulk_load(uint32_t dst, const void* src, uint32_t bytes, uint32_t bar) {
    asm volatile("{\n.reg .pred P;\nelect.sync _|P, 0xffffffff;\n"
                 "@P cp.async.bulk.shared::cluster.global.mbarrier::complete_tx::bytes [%0], [%1], %2, [%3];\n}\n"
                 :: "r"(dst), "l"(src), "r"(bytes), "r"(bar) : "memory");
}
__device__ __forceinline__ void warp_tma_store(const CUtensorMap* map, uint32_t src, int c0, int c1, int c2) {
    asm volatile("{\n.reg .pred P;\nelect.sync _|P, 0xffffffff;\n"
                 "@P cp.async.bulk.tensor.3d.global.shared::cta.bulk_group [%0, {%2, %3, %4}], [%1];\n}\n"
                 :: "l"(map), "r"(src), "r"(c0), "r"(c1), "r"(c2) : "memory");
}
__device__ __forceinline__ void warp_bulk_store(void* dst, uint32_t src, uint32_t bytes) {
    asm volatile("{\n.reg .pred P;\nelect.sync _|P, 0xffffffff;\n"
                 "@P cp.async.bulk.global.shared::cta.bulk_group [%0], [%1], %2;\n}\n" :: "l"(dst), "r"(src), "r"(bytes) : "memory");
}
__device__ __forceinline__ void prefetch_l2(const void* src, uint32_t bytes) {
    asm volatile("cp.async.bulk.prefetch.L2.global [%0], %1;" :: "l"(src), "r"(bytes) : "memory");
}
__device__ __forceinline__ void warp_prefetch(const void* src, uint32_t bytes) {
    asm volatile("{\n.reg .pred P;\nelect.sync _|P, 0xffffffff;\n@P cp.async.bulk.prefetch.L2.global [%0], %1;\n}\n" :: "l"(src), "r"(bytes) : "memory");
}
__device__ __forceinline__ void bulk_commit() { asm volatile("cp.async.bulk.commit_group;" ::: "memory"); }
template <int N> __device__ __forceinline__ void bulk_wait_read() { asm volatile("cp.async.bulk.wait_group.read %0;" :: "n"(N) : "memory"); }
template <int N> __device__ __forceinline__ void bulk_wait() { asm volatile("cp.async.bulk.wait_group %0;" :: "n"(N) : "memory"); }
__device__ __forceinline__ void wgmma_fence() { asm volatile("wgmma.fence.sync.aligned;" ::: "memory"); }
__device__ __forceinline__ void wgmma_commit() { asm volatile("wgmma.commit_group.sync.aligned;" ::: "memory"); }
template <int N> __device__ __forceinline__ void wgmma_wait() { asm volatile("wgmma.wait_group.sync.aligned %0;" :: "n"(N) : "memory"); }
template <int N> __device__ __forceinline__ void fence_regs(float (&d)[N]) {
#pragma unroll
    for (int i = 0; i < N; i++) asm volatile("" : "+f"(d[i]) :: "memory");
}
template <int N> __device__ __forceinline__ void fence_regs(uint32_t (&d)[N]) {
#pragma unroll
    for (int i = 0; i < N; i++) asm volatile("" : "+r"(d[i]) :: "memory");
}
template <int N> __device__ __forceinline__ void reg_dec() { asm volatile("setmaxnreg.dec.sync.aligned.u32 %0;" :: "n"(N)); }
template <int N> __device__ __forceinline__ void reg_inc() { asm volatile("setmaxnreg.inc.sync.aligned.u32 %0;" :: "n"(N)); }
__device__ __forceinline__ uint32_t pack_bf16(float lo, float hi) {
    uint32_t r; asm("cvt.rn.bf16x2.f32 %0, %1, %2;" : "=r"(r) : "f"(hi), "f"(lo)); return r;
}
__device__ __forceinline__ void stmatrix_x4(uint32_t addr, uint32_t r0, uint32_t r1, uint32_t r2, uint32_t r3) {
    asm volatile("stmatrix.sync.aligned.m8n8.x4.shared.b16 [%0], {%1, %2, %3, %4};"
                 :: "r"(addr), "r"(r0), "r"(r1), "r"(r2), "r"(r3) : "memory");
}
__device__ __forceinline__ float ex2(float x) { float y; asm("ex2.approx.ftz.f32 %0, %1;" : "=f"(y) : "f"(x)); return y; }

constexpr uint32_t DESC_HI = (1024 >> 4) | (1u << 30);
__device__ __forceinline__ uint32_t make_desc(uint32_t addr, uint32_t lbo) {
    uint32_t lo = ((addr & 0x3FFFF) >> 4) | ((lbo >> 4) << 16);
    asm volatile("" : "+r"(lo));
    return lo;
}
__device__ __forceinline__ uint64_t full_desc(uint32_t lo) {
    uint64_t d; asm("mov.b64 %0, {%1, %2};" : "=l"(d) : "r"(lo), "r"(DESC_HI)); return d;
}

__device__ __forceinline__ void wgmma_ss_n256_tb_init(float (&d)[128], uint64_t da, uint64_t db) {
    asm volatile("{\n.reg .pred p;\n"
        "setp.ne.b32 p, 0, 0;\n"
        "wgmma.mma_async.sync.aligned.m64n256k16.f32.bf16.bf16 "
        "{%0, %1, %2, %3, %4, %5, %6, %7, %8, %9, %10, %11, %12, %13, %14, %15, %16, %17, %18, %19, %20, "
        "%21, %22, %23, %24, %25, %26, %27, %28, %29, %30, %31, %32, %33, %34, %35, %36, %37, %38, %39, %40, "
        "%41, %42, %43, %44, %45, %46, %47, %48, %49, %50, %51, %52, %53, %54, %55, %56, %57, %58, %59, %60, "
        "%61, %62, %63, %64, %65, %66, %67, %68, %69, %70, %71, %72, %73, %74, %75, %76, %77, %78, %79, %80, "
        "%81, %82, %83, %84, %85, %86, %87, %88, %89, %90, %91, %92, %93, %94, %95, %96, %97, %98, %99, "
        "%100, %101, %102, %103, %104, %105, %106, %107, %108, %109, %110, %111, %112, %113, %114, %115, "
        "%116, %117, %118, %119, %120, %121, %122, %123, %124, %125, %126, %127},"
        " %128, %129, p, 1, 1, 0, 1;\n}\n"
        : "=f"(d[0]), "=f"(d[1]), "=f"(d[2]), "=f"(d[3]), "=f"(d[4]), "=f"(d[5]), "=f"(d[6]), "=f"(d[7]),
        "=f"(d[8]), "=f"(d[9]), "=f"(d[10]), "=f"(d[11]), "=f"(d[12]), "=f"(d[13]), "=f"(d[14]), "=f"(d[15]),
        "=f"(d[16]), "=f"(d[17]), "=f"(d[18]), "=f"(d[19]), "=f"(d[20]), "=f"(d[21]), "=f"(d[22]),
        "=f"(d[23]), "=f"(d[24]), "=f"(d[25]), "=f"(d[26]), "=f"(d[27]), "=f"(d[28]), "=f"(d[29]),
        "=f"(d[30]), "=f"(d[31]), "=f"(d[32]), "=f"(d[33]), "=f"(d[34]), "=f"(d[35]), "=f"(d[36]),
        "=f"(d[37]), "=f"(d[38]), "=f"(d[39]), "=f"(d[40]), "=f"(d[41]), "=f"(d[42]), "=f"(d[43]),
        "=f"(d[44]), "=f"(d[45]), "=f"(d[46]), "=f"(d[47]), "=f"(d[48]), "=f"(d[49]), "=f"(d[50]),
        "=f"(d[51]), "=f"(d[52]), "=f"(d[53]), "=f"(d[54]), "=f"(d[55]), "=f"(d[56]), "=f"(d[57]),
        "=f"(d[58]), "=f"(d[59]), "=f"(d[60]), "=f"(d[61]), "=f"(d[62]), "=f"(d[63]), "=f"(d[64]),
        "=f"(d[65]), "=f"(d[66]), "=f"(d[67]), "=f"(d[68]), "=f"(d[69]), "=f"(d[70]), "=f"(d[71]),
        "=f"(d[72]), "=f"(d[73]), "=f"(d[74]), "=f"(d[75]), "=f"(d[76]), "=f"(d[77]), "=f"(d[78]),
        "=f"(d[79]), "=f"(d[80]), "=f"(d[81]), "=f"(d[82]), "=f"(d[83]), "=f"(d[84]), "=f"(d[85]),
        "=f"(d[86]), "=f"(d[87]), "=f"(d[88]), "=f"(d[89]), "=f"(d[90]), "=f"(d[91]), "=f"(d[92]),
        "=f"(d[93]), "=f"(d[94]), "=f"(d[95]), "=f"(d[96]), "=f"(d[97]), "=f"(d[98]), "=f"(d[99]),
        "=f"(d[100]), "=f"(d[101]), "=f"(d[102]), "=f"(d[103]), "=f"(d[104]), "=f"(d[105]), "=f"(d[106]),
        "=f"(d[107]), "=f"(d[108]), "=f"(d[109]), "=f"(d[110]), "=f"(d[111]), "=f"(d[112]), "=f"(d[113]),
        "=f"(d[114]), "=f"(d[115]), "=f"(d[116]), "=f"(d[117]), "=f"(d[118]), "=f"(d[119]), "=f"(d[120]),
        "=f"(d[121]), "=f"(d[122]), "=f"(d[123]), "=f"(d[124]), "=f"(d[125]), "=f"(d[126]), "=f"(d[127])
        : "l"(da), "l"(db));
}
__device__ __forceinline__ void wgmma_ss_n256_tb(float (&d)[128], uint64_t da, uint64_t db, int scale_d) {
    asm volatile("{\n.reg .pred p;\n"
        "setp.ne.b32 p, %130, 0;\n"
        "wgmma.mma_async.sync.aligned.m64n256k16.f32.bf16.bf16 "
        "{%0, %1, %2, %3, %4, %5, %6, %7, %8, %9, %10, %11, %12, %13, %14, %15, %16, %17, %18, %19, %20, "
        "%21, %22, %23, %24, %25, %26, %27, %28, %29, %30, %31, %32, %33, %34, %35, %36, %37, %38, %39, %40, "
        "%41, %42, %43, %44, %45, %46, %47, %48, %49, %50, %51, %52, %53, %54, %55, %56, %57, %58, %59, %60, "
        "%61, %62, %63, %64, %65, %66, %67, %68, %69, %70, %71, %72, %73, %74, %75, %76, %77, %78, %79, %80, "
        "%81, %82, %83, %84, %85, %86, %87, %88, %89, %90, %91, %92, %93, %94, %95, %96, %97, %98, %99, "
        "%100, %101, %102, %103, %104, %105, %106, %107, %108, %109, %110, %111, %112, %113, %114, %115, "
        "%116, %117, %118, %119, %120, %121, %122, %123, %124, %125, %126, %127},"
        " %128, %129, p, 1, 1, 0, 1;\n}\n"
        : "+f"(d[0]), "+f"(d[1]), "+f"(d[2]), "+f"(d[3]), "+f"(d[4]), "+f"(d[5]), "+f"(d[6]), "+f"(d[7]),
        "+f"(d[8]), "+f"(d[9]), "+f"(d[10]), "+f"(d[11]), "+f"(d[12]), "+f"(d[13]), "+f"(d[14]), "+f"(d[15]),
        "+f"(d[16]), "+f"(d[17]), "+f"(d[18]), "+f"(d[19]), "+f"(d[20]), "+f"(d[21]), "+f"(d[22]),
        "+f"(d[23]), "+f"(d[24]), "+f"(d[25]), "+f"(d[26]), "+f"(d[27]), "+f"(d[28]), "+f"(d[29]),
        "+f"(d[30]), "+f"(d[31]), "+f"(d[32]), "+f"(d[33]), "+f"(d[34]), "+f"(d[35]), "+f"(d[36]),
        "+f"(d[37]), "+f"(d[38]), "+f"(d[39]), "+f"(d[40]), "+f"(d[41]), "+f"(d[42]), "+f"(d[43]),
        "+f"(d[44]), "+f"(d[45]), "+f"(d[46]), "+f"(d[47]), "+f"(d[48]), "+f"(d[49]), "+f"(d[50]),
        "+f"(d[51]), "+f"(d[52]), "+f"(d[53]), "+f"(d[54]), "+f"(d[55]), "+f"(d[56]), "+f"(d[57]),
        "+f"(d[58]), "+f"(d[59]), "+f"(d[60]), "+f"(d[61]), "+f"(d[62]), "+f"(d[63]), "+f"(d[64]),
        "+f"(d[65]), "+f"(d[66]), "+f"(d[67]), "+f"(d[68]), "+f"(d[69]), "+f"(d[70]), "+f"(d[71]),
        "+f"(d[72]), "+f"(d[73]), "+f"(d[74]), "+f"(d[75]), "+f"(d[76]), "+f"(d[77]), "+f"(d[78]),
        "+f"(d[79]), "+f"(d[80]), "+f"(d[81]), "+f"(d[82]), "+f"(d[83]), "+f"(d[84]), "+f"(d[85]),
        "+f"(d[86]), "+f"(d[87]), "+f"(d[88]), "+f"(d[89]), "+f"(d[90]), "+f"(d[91]), "+f"(d[92]),
        "+f"(d[93]), "+f"(d[94]), "+f"(d[95]), "+f"(d[96]), "+f"(d[97]), "+f"(d[98]), "+f"(d[99]),
        "+f"(d[100]), "+f"(d[101]), "+f"(d[102]), "+f"(d[103]), "+f"(d[104]), "+f"(d[105]), "+f"(d[106]),
        "+f"(d[107]), "+f"(d[108]), "+f"(d[109]), "+f"(d[110]), "+f"(d[111]), "+f"(d[112]), "+f"(d[113]),
        "+f"(d[114]), "+f"(d[115]), "+f"(d[116]), "+f"(d[117]), "+f"(d[118]), "+f"(d[119]), "+f"(d[120]),
        "+f"(d[121]), "+f"(d[122]), "+f"(d[123]), "+f"(d[124]), "+f"(d[125]), "+f"(d[126]), "+f"(d[127])
        : "l"(da), "l"(db), "r"(scale_d));
}
__device__ __forceinline__ void wgmma_ss_n128(float (&d)[64], uint64_t da, uint64_t db, int scale_d) {
    asm volatile("{\n.reg .pred p;\n"
        "setp.ne.b32 p, %66, 0;\n"
        "wgmma.mma_async.sync.aligned.m64n128k16.f32.bf16.bf16 "
        "{%0, %1, %2, %3, %4, %5, %6, %7, %8, %9, %10, %11, %12, %13, %14, %15, %16, %17, %18, %19, %20, "
        "%21, %22, %23, %24, %25, %26, %27, %28, %29, %30, %31, %32, %33, %34, %35, %36, %37, %38, %39, %40, "
        "%41, %42, %43, %44, %45, %46, %47, %48, %49, %50, %51, %52, %53, %54, %55, %56, %57, %58, %59, %60, "
        "%61, %62, %63},"
        " %64, %65, p, 1, 1, 0, 0;\n}\n"
        : "+f"(d[0]), "+f"(d[1]), "+f"(d[2]), "+f"(d[3]), "+f"(d[4]), "+f"(d[5]), "+f"(d[6]), "+f"(d[7]),
        "+f"(d[8]), "+f"(d[9]), "+f"(d[10]), "+f"(d[11]), "+f"(d[12]), "+f"(d[13]), "+f"(d[14]), "+f"(d[15]),
        "+f"(d[16]), "+f"(d[17]), "+f"(d[18]), "+f"(d[19]), "+f"(d[20]), "+f"(d[21]), "+f"(d[22]),
        "+f"(d[23]), "+f"(d[24]), "+f"(d[25]), "+f"(d[26]), "+f"(d[27]), "+f"(d[28]), "+f"(d[29]),
        "+f"(d[30]), "+f"(d[31]), "+f"(d[32]), "+f"(d[33]), "+f"(d[34]), "+f"(d[35]), "+f"(d[36]),
        "+f"(d[37]), "+f"(d[38]), "+f"(d[39]), "+f"(d[40]), "+f"(d[41]), "+f"(d[42]), "+f"(d[43]),
        "+f"(d[44]), "+f"(d[45]), "+f"(d[46]), "+f"(d[47]), "+f"(d[48]), "+f"(d[49]), "+f"(d[50]),
        "+f"(d[51]), "+f"(d[52]), "+f"(d[53]), "+f"(d[54]), "+f"(d[55]), "+f"(d[56]), "+f"(d[57]),
        "+f"(d[58]), "+f"(d[59]), "+f"(d[60]), "+f"(d[61]), "+f"(d[62]), "+f"(d[63])
        : "l"(da), "l"(db), "r"(scale_d));
}
__device__ __forceinline__ void wgmma_rs_n128_tb(float (&d)[64], uint32_t a0, uint32_t a1, uint32_t a2, uint32_t a3, uint64_t db, int scale_d) {
    asm volatile("{\n.reg .pred p;\n"
        "setp.ne.b32 p, %69, 0;\n"
        "wgmma.mma_async.sync.aligned.m64n128k16.f32.bf16.bf16 "
        "{%0, %1, %2, %3, %4, %5, %6, %7, %8, %9, %10, %11, %12, %13, %14, %15, %16, %17, %18, %19, %20, "
        "%21, %22, %23, %24, %25, %26, %27, %28, %29, %30, %31, %32, %33, %34, %35, %36, %37, %38, %39, %40, "
        "%41, %42, %43, %44, %45, %46, %47, %48, %49, %50, %51, %52, %53, %54, %55, %56, %57, %58, %59, %60, "
        "%61, %62, %63},"
        " {%64, %65, %66, %67}, %68, p, 1, 1, 1;\n}\n"
        : "+f"(d[0]), "+f"(d[1]), "+f"(d[2]), "+f"(d[3]), "+f"(d[4]), "+f"(d[5]), "+f"(d[6]), "+f"(d[7]),
        "+f"(d[8]), "+f"(d[9]), "+f"(d[10]), "+f"(d[11]), "+f"(d[12]), "+f"(d[13]), "+f"(d[14]), "+f"(d[15]),
        "+f"(d[16]), "+f"(d[17]), "+f"(d[18]), "+f"(d[19]), "+f"(d[20]), "+f"(d[21]), "+f"(d[22]),
        "+f"(d[23]), "+f"(d[24]), "+f"(d[25]), "+f"(d[26]), "+f"(d[27]), "+f"(d[28]), "+f"(d[29]),
        "+f"(d[30]), "+f"(d[31]), "+f"(d[32]), "+f"(d[33]), "+f"(d[34]), "+f"(d[35]), "+f"(d[36]),
        "+f"(d[37]), "+f"(d[38]), "+f"(d[39]), "+f"(d[40]), "+f"(d[41]), "+f"(d[42]), "+f"(d[43]),
        "+f"(d[44]), "+f"(d[45]), "+f"(d[46]), "+f"(d[47]), "+f"(d[48]), "+f"(d[49]), "+f"(d[50]),
        "+f"(d[51]), "+f"(d[52]), "+f"(d[53]), "+f"(d[54]), "+f"(d[55]), "+f"(d[56]), "+f"(d[57]),
        "+f"(d[58]), "+f"(d[59]), "+f"(d[60]), "+f"(d[61]), "+f"(d[62]), "+f"(d[63])
        : "r"(a0), "r"(a1), "r"(a2), "r"(a3), "l"(db), "r"(scale_d));
}
__device__ __forceinline__ void wgmma_ss_n128_lo_tb(float (&d)[128], uint64_t da, uint64_t db, int scale_d) {
    asm volatile("{\n.reg .pred p;\n"
        "setp.ne.b32 p, %66, 0;\n"
        "wgmma.mma_async.sync.aligned.m64n128k16.f32.bf16.bf16 "
        "{%0, %1, %2, %3, %4, %5, %6, %7, %8, %9, %10, %11, %12, %13, %14, %15, %16, %17, %18, %19, %20, "
        "%21, %22, %23, %24, %25, %26, %27, %28, %29, %30, %31, %32, %33, %34, %35, %36, %37, %38, %39, %40, "
        "%41, %42, %43, %44, %45, %46, %47, %48, %49, %50, %51, %52, %53, %54, %55, %56, %57, %58, %59, %60, "
        "%61, %62, %63},"
        " %64, %65, p, 1, 1, 0, 1;\n}\n"
        : "+f"(d[0]), "+f"(d[1]), "+f"(d[2]), "+f"(d[3]), "+f"(d[4]), "+f"(d[5]), "+f"(d[6]), "+f"(d[7]),
        "+f"(d[8]), "+f"(d[9]), "+f"(d[10]), "+f"(d[11]), "+f"(d[12]), "+f"(d[13]), "+f"(d[14]), "+f"(d[15]),
        "+f"(d[16]), "+f"(d[17]), "+f"(d[18]), "+f"(d[19]), "+f"(d[20]), "+f"(d[21]), "+f"(d[22]),
        "+f"(d[23]), "+f"(d[24]), "+f"(d[25]), "+f"(d[26]), "+f"(d[27]), "+f"(d[28]), "+f"(d[29]),
        "+f"(d[30]), "+f"(d[31]), "+f"(d[32]), "+f"(d[33]), "+f"(d[34]), "+f"(d[35]), "+f"(d[36]),
        "+f"(d[37]), "+f"(d[38]), "+f"(d[39]), "+f"(d[40]), "+f"(d[41]), "+f"(d[42]), "+f"(d[43]),
        "+f"(d[44]), "+f"(d[45]), "+f"(d[46]), "+f"(d[47]), "+f"(d[48]), "+f"(d[49]), "+f"(d[50]),
        "+f"(d[51]), "+f"(d[52]), "+f"(d[53]), "+f"(d[54]), "+f"(d[55]), "+f"(d[56]), "+f"(d[57]),
        "+f"(d[58]), "+f"(d[59]), "+f"(d[60]), "+f"(d[61]), "+f"(d[62]), "+f"(d[63])
        : "l"(da), "l"(db), "r"(scale_d));
}

enum { M_X = 0, M_C, M_WQ, M_WQKV, M_WUK, M_WUV, M_WO, M_WOB, M_SCR_LD, M_SCR_LOC, M_SCR_LOQ, M_SCR_ST, M_COUNT };
enum { T_Q = 0, T_K, T_V, T_B, T_OUT, T_LOCAL, T_ATTN, T_END };
constexpr int NCTA = 132, NPAIR = NCTA / 2;
constexpr int NITEMS = 480 + 64 + 256;
#define NTRI 3
constexpr int TRIPLES = NTRI, WIDE = 80 - 3 * TRIPLES;
struct Params {
    CUtensorMap m[M_COUNT];
    const __nv_bfloat16* x;
    const __nv_bfloat16* gate_w;
    const char* wo;
    const char* wob;
    __nv_bfloat16* out;
    uint32_t zero;
    uint16_t items[NITEMS];
    uint8_t ostep[80];
};
__device__ __forceinline__ int item_type(int it) { return it >> 13; }
__device__ __forceinline__ int item_row(int it) { return it & 15; }
__device__ __forceinline__ int item_col(int it) { return (it >> 4) & 31; }
__device__ __forceinline__ int item_asc(int it) { return (it >> 9) & 1; }
constexpr int ITEM_READY = 1 << 10;

struct __align__(128) Sync {
    unsigned long long count[4];
    __align__(128) unsigned long long ctx[16];
    unsigned next, next_out, done;
    __align__(128) unsigned step[32][2];
    unsigned split[32];
};
__device__ Sync g_sync;
__device__ uint4 g_part[128][8][256];

constexpr uint32_t GST_BYTES = 49152, SM_KV = 65536, SM_STAGING = 196608, SM_BARS = SM_STAGING + 32768;
constexpr uint32_t B_GFULL = 0, B_GEMPTY = 32, B_AFULL = 64, B_AEMPTY = 112, B_SFULL = 160, B_SEMPTY = 192,
                   B_IFULL = 224, B_IEMPTY = 288, B_XFREE = 352, B_WANT = 384, B_HALF = 416,
                   SM_ORDY = 448, SM_QUEUE = 456, B_ALT = 488, B_QFREE = 504, SM_GATE = 512, SM_TOTAL = SM_BARS + 1536;
constexpr int QDEPTH = 8;
#define PF_NAR 20
#define SPREAD 4
#define PACE 0
#define PF_LOC 0
#define KMEET 14
constexpr int K_MEET = KMEET, K_SPLIT = KMEET + 12;
#define KF2 3
constexpr uint32_t LOC_PLANE = 72 * 128;
constexpr float SM_SCALE = 0.08838834764831845f * 1.4426950408889634f;
constexpr float LOC_SCALE = 0.17677669529663687f * 1.4426950408889634f;
constexpr float SUM_LIMIT = 1152921504606846976.f;
constexpr float REF_RANGE = 32.f;

__device__ __forceinline__ unsigned ld_acquire(const unsigned* p) {
    unsigned v; asm volatile("ld.acquire.gpu.global.u32 %0, [%1];" : "=r"(v) : "l"(p) : "memory"); return v;
}
__device__ __forceinline__ unsigned long long ld_acquire(const unsigned long long* p) {
    unsigned long long v; asm volatile("ld.acquire.gpu.global.u64 %0, [%1];" : "=l"(v) : "l"(p) : "memory"); return v;
}
__device__ __forceinline__ void st_b128(void* p, uint32_t a, uint32_t b, uint32_t c, uint32_t d) {
    asm volatile("{\n.reg .b128 v;\n.reg .b64 lo, hi;\nmov.b64 lo, {%1, %2};\nmov.b64 hi, {%3, %4};\nmov.b128 v, {lo, hi};\n"
                 "st.relaxed.gpu.global.b128 [%0], v;\n}\n" :: "l"(p), "r"(a), "r"(b), "r"(c), "r"(d) : "memory");
}
__device__ __forceinline__ void ld_b128(const void* p, uint32_t& a, uint32_t& b, uint32_t& c, uint32_t& d) {
    asm volatile("{\n.reg .b128 v;\n.reg .b64 lo, hi;\nld.relaxed.gpu.global.b128 v, [%4];\nmov.b128 {lo, hi}, v;\n"
                 "mov.b64 {%0, %1}, lo;\nmov.b64 {%2, %3}, hi;\n}\n" : "=r"(a), "=r"(b), "=r"(c), "=r"(d) : "l"(p) : "memory");
}
__device__ __forceinline__ void spin_guard(unsigned& n) {
    asm volatile("{\n.reg .pred P;\nadd.u32 %0, %0, 1;\nsetp.gt.u32 P, %0, 16777216;\n@P trap;\n}\n" : "+r"(n));
    if (n > 1) __nanosleep(100);
}
__device__ __forceinline__ void red_add(unsigned long long* p, unsigned long long v) {
    asm volatile("red.release.gpu.global.add.u64 [%0], %1;" :: "l"(p), "l"(v) : "memory");
}
__device__ __forceinline__ float rcp(float x) { float y; asm("rcp.approx.ftz.f32 %0, %1;" : "=f"(y) : "f"(x)); return y; }
__device__ __forceinline__ float lds_f32(uint32_t addr) {
    float v; asm volatile("ld.shared.f32 %0, [%1];" : "=f"(v) : "r"(addr) : "memory"); return v;
}
__device__ __forceinline__ void ldsm_x4(uint32_t (&r)[4], uint32_t addr) {
    asm volatile("ldmatrix.sync.aligned.m8n8.x4.shared.b16 {%0, %1, %2, %3}, [%4];"
                 : "=r"(r[0]), "=r"(r[1]), "=r"(r[2]), "=r"(r[3]) : "r"(addr) : "memory");
}
__device__ __forceinline__ void ldsm_x4_t(uint32_t (&r)[4], uint32_t addr) {
    asm volatile("ldmatrix.sync.aligned.m8n8.x4.trans.shared.b16 {%0, %1, %2, %3}, [%4];"
                 : "=r"(r[0]), "=r"(r[1]), "=r"(r[2]), "=r"(r[3]) : "r"(addr) : "memory");
}
__device__ __forceinline__ void mma_k16(float (&d)[4], const uint32_t (&a)[4], uint32_t b0, uint32_t b1) {
    asm("mma.sync.aligned.m16n8k16.row.col.f32.bf16.bf16.f32 {%0,%1,%2,%3}, {%4,%5,%6,%7}, {%8,%9}, {%0,%1,%2,%3};"
        : "+f"(d[0]), "+f"(d[1]), "+f"(d[2]), "+f"(d[3]) : "r"(a[0]), "r"(a[1]), "r"(a[2]), "r"(a[3]), "r"(b0), "r"(b1));
}
__device__ __forceinline__ void mma_k16_init(float (&d)[4], const uint32_t (&a)[4], uint32_t b0, uint32_t b1) {
    asm("{\n.reg .f32 z;\nmov.f32 z, 0f00000000;\n"
        "mma.sync.aligned.m16n8k16.row.col.f32.bf16.bf16.f32 {%0,%1,%2,%3}, {%4,%5,%6,%7}, {%8,%9}, {z,z,z,z};\n}\n"
        : "=f"(d[0]), "=f"(d[1]), "=f"(d[2]), "=f"(d[3]) : "r"(a[0]), "r"(a[1]), "r"(a[2]), "r"(a[3]), "r"(b0), "r"(b1));
}
__device__ __forceinline__ void mma_k8(float (&d)[4], uint32_t a0, uint32_t a1, uint32_t b0) {
    asm("mma.sync.aligned.m16n8k8.row.col.f32.bf16.bf16.f32 {%0,%1,%2,%3}, {%4,%5}, {%6}, {%0,%1,%2,%3};"
        : "+f"(d[0]), "+f"(d[1]), "+f"(d[2]), "+f"(d[3]) : "r"(a0), "r"(a1), "r"(b0));
}
template <typename T, int N> __device__ __forceinline__ void zero_regs(T (&d)[N]) {
#pragma unroll
    for (int i = 0; i < N; i++) d[i] = 0;
}
__device__ __forceinline__ float quad_max(float v) {
    v = fmaxf(v, __shfl_xor_sync(0xffffffffu, v, 1));
    return fmaxf(v, __shfl_xor_sync(0xffffffffu, v, 2));
}
__device__ __forceinline__ float quad_sum(float v) {
    v += __shfl_xor_sync(0xffffffffu, v, 1);
    return v + __shfl_xor_sync(0xffffffffu, v, 2);
}

__device__ __forceinline__ void qk_gemm(float (&s)[64], uint32_t q_lo, uint32_t k_lo) {
    const uint64_t dq = full_desc(q_lo), dk = full_desc(k_lo);
    fence_regs(s);
    wgmma_fence();
#pragma unroll
    for (int kk = 0; kk < 8; kk++) {
        const uint32_t o = (kk >> 2) * 1024 + (kk & 3) * 2;
        wgmma_ss_n128(s, dq + o, dk + o, kk != 0);
    }
    wgmma_commit();
}
__device__ __forceinline__ void pv_gemm(float (&o)[64], uint32_t (&p)[32], uint32_t v_lo, int accumulate) {
    const uint64_t dv = full_desc(v_lo);
    fence_regs(o);
    fence_regs(p);
    wgmma_fence();
#pragma unroll
    for (int kk = 0; kk < 8; kk++)
        wgmma_rs_n128_tb(o, p[4 * kk], p[4 * kk + 1], p[4 * kk + 2], p[4 * kk + 3], dv + kk * 128, kk != 0 || accumulate);
    wgmma_commit();
}
__device__ __forceinline__ void row_max(const float (&s)[64], float& x0, float& x1) {
    float z0 = fmaxf(s[0], s[1]), z1 = fmaxf(s[2], s[3]);
    x0 = fmaxf(s[4], s[5]); x1 = fmaxf(s[6], s[7]);
#pragma unroll
    for (int j = 2; j < 16; j += 2) {
        z0 = fmaxf(z0, fmaxf(s[4 * j], s[4 * j + 1]));
        z1 = fmaxf(z1, fmaxf(s[4 * j + 2], s[4 * j + 3]));
        x0 = fmaxf(x0, fmaxf(s[4 * j + 4], s[4 * j + 5]));
        x1 = fmaxf(x1, fmaxf(s[4 * j + 6], s[4 * j + 7]));
    }
    x0 = quad_max(fmaxf(x0, z0)); x1 = quad_max(fmaxf(x1, z1));
}
__device__ __forceinline__ void exp_pack(uint32_t (&p)[32], const float (&s)[64], float& r0, float& r1) {
#pragma unroll
    for (int j = 0; j < 16; j++) {
        const float e0 = ex2(s[4 * j]), e1 = ex2(s[4 * j + 1]), e2 = ex2(s[4 * j + 2]), e3 = ex2(s[4 * j + 3]);
        if (j == 0) { r0 = e0 + e1; r1 = e2 + e3; }
        else { r0 += e0 + e1; r1 += e2 + e3; }
        p[2 * j] = pack_bf16(e0, e1);
        p[2 * j + 1] = pack_bf16(e2, e3);
    }
}
__device__ __forceinline__ void shift_rows(float (&s)[64], float d0, float d1) {
#pragma unroll
    for (int j = 0; j < 16; j++) { s[4 * j] -= d0; s[4 * j + 1] -= d0; s[4 * j + 2] -= d1; s[4 * j + 3] -= d1; }
}
constexpr float MASKED = -3e38f;
template <int J0>
__device__ __forceinline__ void mask_triangle(float (&s)[64], float thr) {
#pragma unroll
    for (int j = 0; j < 16; j++) {
        const float m = __saturatef((float)(8 * (j >> 1) + (j & 1)) - thr);
        const int i = 4 * (J0 + (j >> 1)) + (j & 1);
        s[i] = fmaf(m, MASKED, s[i]);
        if (j < 14) s[i + 6] = fmaf(m, MASKED, s[i + 6]);
    }
}
__device__ __forceinline__ void causal_mask(float (&s)[64], float thr, int wg) {
    asm volatile("" : "+f"(thr));
    if (wg == 0) {
        mask_triangle<0>(s, thr);
#pragma unroll
        for (int j = 32; j < 64; j++) s[j] += MASKED;
    } else {
        mask_triangle<8>(s, thr);
    }
}

__global__ void __cluster_dims__(2, 1, 1) __launch_bounds__(384, 1) fused_kernel(const __grid_constant__ Params prm) {
    extern __shared__ __align__(1024) uint8_t smem[];
    const uint32_t sb = smem_u32(smem), bars = sb + SM_BARS;
    const int warp = __shfl_sync(0xffffffffu, threadIdx.x >> 5, 0), lane = threadIdx.x & 31;

    const uint32_t rank = cluster_rank();
    const uint32_t bars0 = map_cta(bars, 0), bars_peer = map_cta(bars, rank ^ 1);

    auto first_item = [&]() -> int {
        uint32_t pair = blockIdx.x >> 1;
        asm volatile("" : "+r"(pair));
        return prm.items[pair] + item_row(prm.items[pair]) + rank;
    };
    if (threadIdx.x == 256) {
        for (int k = 0; k < 4; k++) mbar_init(bars + B_GFULL + 8 * k, 1);
        asm volatile("fence.mbarrier_init.release.cluster;" ::: "memory");
        fence_proxy_async_smem();
    }
    if (threadIdx.x == 128) {
        for (int i = 0; i < 4; i++) { mbar_init(bars + B_GEMPTY + 8 * i, 16); mbar_init(bars + B_XFREE + 8 * i, 1); }
        for (int i = 0; i < 6; i++) { mbar_init(bars + B_AFULL + 8 * i, 1); mbar_init(bars + B_AEMPTY + 8 * i, i < 2 ? 8 : 16); }
        for (int i = 0; i < 4; i++) { mbar_init(bars + B_SFULL + 8 * i, 4); mbar_init(bars + B_SEMPTY + 8 * i, 1); }
        for (int i = 0; i < QDEPTH; i++) { mbar_init(bars + B_IFULL + 8 * i, 1); mbar_init(bars + B_IEMPTY + 8 * i, 23); }
        mbar_init(bars + B_WANT, 2);
        for (int i = 0; i < 4; i++) mbar_init(bars + B_HALF + 8 * i, 1);
        mbar_init(bars + B_ALT, 4); mbar_init(bars + B_ALT + 8, 4); mbar_init(bars + B_QFREE, 2);
        asm volatile("st.shared.u64 [%0], 0;" :: "r"(bars + SM_ORDY) : "memory");
        asm volatile("fence.mbarrier_init.release.cluster;\nfence.acq_rel.cta;" ::: "memory");
    }
    __syncwarp();
    asm volatile("barrier.cluster.arrive.relaxed.aligned;" ::: "memory");
    if (threadIdx.x == 256) {
        const int first_it = first_item();
        for (int k = 0; k < 4; k++) {
            const uint32_t dst = sb + k * GST_BYTES, fb = bars + B_GFULL + 8 * k;
            mbar_expect_tx(fb, GST_BYTES);
            tma_load_3d(dst, &prm.m[M_X], fb, k * 64, item_row(first_it) * 128, 0);
            tma_load_3d(dst + 16384, &prm.m[M_WQKV], fb, 0, k * 64, item_col(first_it) * 4);
            tma_load_3d(dst + 32768, &prm.m[M_WQKV], fb, 0, k * 64, item_col(first_it) * 4 + 2);
        }
    }
    __syncwarp();
    asm volatile("barrier.cluster.wait.acquire.aligned;" ::: "memory");

    uint32_t qn = 0;
    auto next_item = [&](bool releaser, bool bounded = true) -> int {
        const uint32_t slot = qn % QDEPTH;
        if (bounded) mbar_wait(bars + B_IFULL + 8 * slot, (qn / QDEPTH) & 1);
        else mbar_spin(bars + B_IFULL + 8 * slot, (qn / QDEPTH) & 1);
        uint32_t it;
        asm volatile("ld.shared.u32 %0, [%1];" : "=r"(it) : "r"(bars + SM_QUEUE + 4 * slot) : "memory");
        mbar_arrive_cluster_if(releaser, bars0 + B_IEMPTY + 8 * slot);
        qn++;
        return it;
    };

    if (warp < 4) {
        reg_dec<40>();
        if (warp == 0) {
            {
                uint32_t gph = 0;
                const uint32_t prank = __shfl_sync(0xffffffffu, rank, 0);
                int k0 = 4;
                uint32_t kv = 0, kvph = 1;
                uint32_t qc = 0;
                uint32_t oneed = 0;
                uint32_t xph = 0;
                uint32_t need_g = 0, need_a = 0;
                auto a_parity = [&](uint32_t b) { return b < 2 ? (((qc + 1 - b) >> 1) & 1) ^ 1 : kvph ^ (b - 2 < kv); };
                int held_type = T_END;
                uint32_t borrowed = 0, fph = 0;
                auto reclaim_q = [&]() { if (borrowed) { mbar_wait(bars + B_QFREE, fph); fph ^= 1; borrowed = 0; } };
                auto acquire_g = [&](uint32_t st, bool shared) {
                    mbar_wait(bars + B_GEMPTY + 8 * st, gph);
                    if (need_a) {
                        reclaim_q();
                        const uint32_t b = (3 * st) >> 1;
                        mbar_wait(bars + B_AEMPTY + 8 * b, a_parity(b));
                        mbar_wait(bars + B_AEMPTY + 8 * (b + 1), a_parity(b + 1));
                        if (shared) {
                            mbar_arrive_cluster_if(lane == 0, bars_peer + B_XFREE + 8 * st);
                            mbar_wait(bars + B_XFREE + 8 * st, xph);
                        }
                        if (st == 3) { need_a = 0; xph ^= shared; }
                    }
                };
                auto leave_gemm = [&](uint32_t b) {
                    if (need_g >> b & 1) {
                        mbar_wait(bars + B_GEMPTY + 8 * ((2 * b) / 3), gph);
                        mbar_wait(bars + B_GEMPTY + 8 * ((2 * b + 1) / 3), gph);
                        need_g &= ~(1u << b);
                    }
                };
                const CUtensorMap* tile_map = &prm.m[M_SCR_LD];
                asm volatile("" : "+l"(tile_map));
                auto load_q = [&](int grp, int row) {
                    const uint32_t b = qc & 1, dst = sb + b * 32768, fb = bars + B_AFULL + 8 * b;
                    mbar_wait(bars + B_AEMPTY + 8 * b, a_parity(b));
                    leave_gemm(b);
                    reclaim_q();
                    borrowed = held_type != T_END;
                    held_type = T_END;
                    warp_expect_tx(fb, 32768 + 512);
                    warp_tma_load(dst, tile_map, fb, 0, row, grp);
                    warp_tma_load(dst + 16384, tile_map, fb, 64, row, grp);
                    warp_bulk_load(bars + SM_GATE + b * 512, &g_gate[row], 512, fb);
                    qc++;
                };
                auto load_kv = [&](int grp, int row, bool shared) {
                    uint32_t fb = bars + B_AFULL + 16 + 8 * kv, mine = sb + SM_KV + kv * 32768 + prank * 16384;
                    int c_mine = prank * 64;
                    asm volatile("" : "+r"(mine), "+r"(fb), "+r"(row), "+r"(grp), "+r"(c_mine));
                    if (need_g) leave_gemm(2 + kv);
                    mbar_wait(fb + B_AEMPTY - B_AFULL, kvph);
                    warp_expect_tx(fb, grp < 0 ? 0 : 32768);
                    if (shared) {
                        warp_tma_load_pair(mine, tile_map, fb, c_mine, row, grp);
                    } else if (grp >= 0) {
                        warp_tma_load(mine, tile_map, fb, c_mine, row, grp);
                        warp_tma_load(mine + 16384 - prank * 32768, tile_map, fb, 64 - c_mine, row, grp);
                    } else {
                        mbar_arrive_cluster_n_if(lane < 2, map_cta(fb, lane & 1) + B_AEMPTY - B_AFULL, 8);
                    }
                    if (++kv == 4) { kv = 0; kvph ^= 1; }
                };
                auto request = [&]() { mbar_arrive_cluster_if(lane == 0, bars0 + B_WANT); };
                int pv_grp = -1, pv_row = 0;
                bool pv_shared = false, peer_longer = false;
                auto inputs_seen = [&](uint32_t word, unsigned& n) -> uint32_t {
                    uint32_t v;
                    spin_guard(n);
                    asm volatile("ld.acquire.cta.shared.u32 %0, [%1];" : "=r"(v) : "r"(bars + SM_ORDY + 4 * word) : "memory");
                    return __shfl_sync(0xffffffffu, v, 0);
                };
                auto fetch = [&]() -> int {
                    const int nx = __shfl_sync(0xffffffffu, next_item(lane == 0), 0);
                    if ((item_type(nx) == T_ATTN || item_type(nx) == T_LOCAL) && !(nx & ITEM_READY)) {
                        oneed += 256;
                        for (unsigned n = 0; inputs_seen(1, n) < oneed;) {}
                    }
                    if (item_type(nx) == T_ATTN) load_q(G_Q + item_col(nx), item_row(nx) * 128);
                    return nx;
                };
                int nxt = first_item();
                while (true) {
                    const int it = nxt >= 0 ? nxt : fetch();
                    nxt = -1;
                    const int type = item_type(it), m = item_row(it), c = item_col(it);
                    const int asc = item_asc(it), nu = type == T_ATTN ? 2 * m + 2 : 0;
                    const int uend = nu + ((type == T_ATTN ? m < 2 : pv_grp >= 0) ? 3 : 0), ureq = 2 * max(m - 2 - (asc & m), 0);
#pragma unroll 1
                    for (int u = 0; u < uend; u++) {
                        int grp = pv_grp, row = pv_row;
                        bool shared = pv_shared;
                        if (u >= nu) {
                            if (u == nu + 1) pv_grp = -1;
                            else if (peer_longer) { grp = -1; shared = false; }
                            else continue;
                        } else {
                            const int j = asc ? u >> 1 : m - (u >> 1);
                            if (u & 1) {
                                pv_grp = G_V + c; pv_row = j * 128; pv_shared = j != (m | 1);
                                peer_longer = asc & ~m & 1;
                                if (u == nu - 1 && (m & 1) && item_type(nxt) == T_END) mbar_arrive_cluster_n_if(lane == 0, bars0 + B_WANT, 2);
                                if (grp < 0) continue;
                            } else {
                                if (u == ureq) request();
                                if (u == 2 * m && m > 0) nxt = fetch();
                                grp = G_K + c; row = j * 128; shared = j != (m | 1);
                            }
                        }
                        load_kv(grp, row, shared);
                    }
                    if (type == T_END) break;
                    if (type == T_ATTN) {
                        need_a = 1;
                    } else if (type == T_LOCAL) {
                        if (held_type == T_B && !(it & ITEM_READY)) held_type = T_END;
                        request();
#pragma unroll 1
                        for (uint32_t st = 0; st < 4; st++) {
                            acquire_g(st, false);
                            const uint32_t dst = sb + st * GST_BYTES, fb = bars + B_GFULL + 8 * st;
                            warp_expect_tx(fb, st == 0 ? 32768 + 512 : st == 3 ? 0 : 4 * LOC_PLANE);
                            if (st == 3) break;
                            if (st == 0) warp_bulk_load(dst + 4 * LOC_PLANE, &g_gate[m * 128], 512, fb);
#pragma unroll 1
                            for (int i = 0; i < 4; i++)
                                warp_tma_load(dst + i * LOC_PLANE, &prm.m[st ? M_SCR_LOC : M_SCR_LOQ], fb, i * 64, m * 64 - (st ? 8 : 0), G_B + 8 * st + c);
                        }
                        gph ^= 1;
                        need_g = 63;
                    } else {
                        const int nk = type == T_K || type == T_V ? 8 : 16;
                        const CUtensorMap* ma = &prm.m[nk == 8 ? M_C : M_X];
                        const CUtensorMap* mb = &prm.m[type == T_Q ? M_WQ : type == T_K ? M_WUK : type == T_V ? M_WUV : M_WQKV];
                        for (int k = k0; k < nk; k++) {
                            if (k == nk - 3) request();
                            const uint32_t st = k & 3;
                            uint32_t dst = sb + st * GST_BYTES, fb = bars + B_GFULL + 8 * st, dstb = dst + 16384 + prank * 16384;
                            int a0 = k * 64, a1 = m * 128, b2 = c * 4 + 2 * prank;
                            asm volatile("" : "+r"(dst), "+r"(fb), "+r"(dstb), "+r"(a0), "+r"(a1), "+r"(b2), "+l"(ma), "+l"(mb));
                            acquire_g(st, true);
                            warp_expect_tx(fb, GST_BYTES);
                            warp_tma_load(dst, ma, fb, a0, a1, 0);
                            warp_tma_load_pair(dstb, mb, fb, 0, a0, b2);
                            if (st == 3) gph ^= 1;
                        }
                        need_g = 63;
                        held_type = type;
                        k0 = 0;
                    }
                }
                if (!need_a) request();
                const int it = __shfl_sync(0xffffffffu, next_item(lane == 0), 0);
                int nk = 0;
                if (item_type(it) == T_OUT) {
                    const int m = item_row(it), c = item_col(it), half = c & 1;
                    nk = 80;
                    for (int k = 0; k < nk; k++) {
                        if (k == K_SPLIT) nk = 2 * TRIPLES + (__shfl_sync(0xffffffffu, next_item(lane == 0), 0) & 127);
                        const int kn = k + 2 * TRIPLES - nk, first = kn >= 0 && !(kn & 1);
                        const int s = kn >= 0 ? WIDE + (3 * kn + 1) / 2 : half ? WIDE - 1 - k : k;
                        const uint32_t sa = prm.ostep[s], sa2 = prm.ostep[s + first], sw = prm.ostep[s - (kn >= 0 && !first ? prank : 0)];
                        for (unsigned n = 0; !(inputs_seen(sa >> 6, n) >> (sa >> 1 & 31) & 1);) {}
                        if (first) for (unsigned n = 0; !(inputs_seen(sa2 >> 6, n) >> (sa2 >> 1 & 31) & 1);) {}
                        const uint32_t st = k & 3;
                        uint32_t dst = sb + st * GST_BYTES, fb = bars + B_GFULL + 8 * st;
                        uint32_t dstb = dst + 16384 + (first ? 0 : prank * 16384), skipb = first && (kn >> 1 & 1) != prank;
                        int a0 = (sa & 1) * 64, a1 = m * 128, a2 = (sa >> 1) + (sa < 64 ? G_CTX : G_LOC - 32);
                        int b1 = (sw & 63) * 64, b2 = (c >> 1) * 4 + 2 * (kn >= 0 ? half : half ^ prank);
                        const CUtensorMap* mb = &prm.m[sw >= 64 ? M_WOB : M_WO];
                        asm volatile("" : "+r"(dst), "+r"(fb), "+r"(dstb), "+r"(skipb), "+r"(a0), "+r"(a1), "+r"(a2), "+r"(b1), "+r"(b2), "+l"(mb));
                        acquire_g(st, true);
                        warp_expect_tx(fb, GST_BYTES);
                        warp_tma_load(dst, tile_map, fb, a0, a1, a2);
                        if (!skipb) warp_tma_load_pair(dstb, mb, fb, 0, b1, b2);
                        if (first) warp_tma_load(dst + 32768, tile_map, fb, (sa2 & 1) * 64, a1, (sa2 >> 1) + (sa2 < 64 ? G_CTX : G_LOC - 32));
                        if (k < K_SPLIT && lane == 0 && !prank)
                            asm volatile("st.relaxed.gpu.global.u32 [%0], %1;" :: "l"(&g_sync.step[0][0] + m * 4 + c), "r"(k) : "memory");
                        if (k == K_MEET) request();
                        if (PF_NAR && (uint32_t)(k - PF_NAR) < (3 * TRIPLES + 1) / 2) {
                            const uint32_t g = prm.ostep[79 - 2 * (k - PF_NAR)] >> 1;
                            warp_prefetch((const char*)g_scr + (uint32_t)((G_CTX + g) * (SEQ * 256) + m * 32768 + c * 4096), 4096);
                            warp_prefetch(prm.wo + (uint32_t)(g * 262144 + (m * 8 + c) * 2048), 2048);
                        }
                        if (st == 3) gph ^= 1;
                    }
                    for (unsigned n = 0; ~inputs_seen(0, n) || inputs_seen(1, n) != 255;) {}
                }
                for (uint32_t st = 0; st < 4; st++) { mbar_wait(bars + B_GEMPTY + 8 * st, gph ^ (st < (nk & 3))); mbar_wait(bars + B_AEMPTY + 16 + 8 * st, a_parity(2 + st)); }
                unsigned left = 0;
                if (lane == 0) left = atomicAdd(&g_sync.done, 1u);
                if (__shfl_sync(0xffffffffu, left, 0) == NCTA - 1)
                    for (int i = lane; i < sizeof(Sync) / 8; i += 32) ((unsigned long long*)&g_sync)[i] = 0;
            }
        } else if (warp <= 2) {
            if (blockIdx.x < SEQ / 16) {
                const uint32_t r0 = 16 * blockIdx.x + 8 * (warp - 1), gbuf = bars + SM_GATE + 4 * (r0 & 15);
                float z[4];
#pragma unroll 1
                for (uint32_t i = 0; i < 8; i++) {
                    const uint32_t off = (i & 3) * 512 + lane * 16;
                    const uint4* xp = (const uint4*)((const char*)prm.x + ((r0 + (i & 4)) * 2048 + off));
                    const uint4 wv = __ldg((const uint4*)((const char*)prm.gate_w + off));
                    uint4 xv[4];
#pragma unroll
                    for (int r = 0; r < 4; r++) { xv[r] = __ldg(xp + r * 128); if (!(i & 3)) z[r] = 0.f; }
                    const uint32_t ws[4] = {wv.x, wv.y, wv.z, wv.w};
#pragma unroll
                    for (int e = 0; e < 4; e++)
#pragma unroll
                        for (int r = 0; r < 4; r++) {
                            const uint32_t xs = e == 0 ? xv[r].x : e == 1 ? xv[r].y : e == 2 ? xv[r].z : xv[r].w;
                            z[r] = fmaf(__uint_as_float(xs << 16), __uint_as_float(ws[e] << 16), z[r]);
                            z[r] = fmaf(__uint_as_float(xs & 0xffff0000u), __uint_as_float(ws[e] & 0xffff0000u), z[r]);
                        }
                    if ((i & 3) == 3) {
#pragma unroll
                        for (int o = 16; o > 0; o >>= 1)
#pragma unroll
                            for (int r = 0; r < 4; r++) z[r] += __shfl_xor_sync(0xffffffffu, z[r], o);
                        const float zr = lane & 2 ? (lane & 1 ? z[3] : z[2]) : (lane & 1 ? z[1] : z[0]);
                        asm volatile("st.shared.f32 [%0], %1;" :: "r"(gbuf + 4 * ((i & 4) + (lane & 3))), "f"(1.f / (1.f + __expf(-zr))) : "memory");
                    }
                }
                fence_proxy_async_smem();
                __syncwarp();
                warp_bulk_store((char*)g_gate + 4 * r0, gbuf, 32);
                bulk_commit();
                bulk_wait<0>();
                __syncwarp();
                if (lane == 0) red_add(&g_sync.count[3], 1);
            }
            __syncwarp();
            {
                const int w = warp - 1;
                uint32_t sph = 0, aph = 0, nann = 0, nattn = 0;
                int unsent = 0, nunsent = 0;
                bool urgent = false;
                auto announce = [&]() {
                    if (!urgent) return;
                    bulk_wait<0>();
                    __syncwarp();
                    const uint32_t hb = bars + B_HALF + 8 * (nann & 3);
                    if (w == 0) {
                        mbar_arrive_if(lane == 0, hb);
                    } else {
                        mbar_wait(hb, (nann >> 2) & 1);
                        const uint32_t type = item_type(unsent), m = item_row(unsent), c = item_col(unsent);
                        const uint32_t word = type < T_B ? c >> 3 : type == T_B ? 2 : offsetof(Sync, ctx) / 8 + m;
                        const uint32_t bit = type < T_B ? 8 * (c & 7) : type == T_B ? 4 * m : type == T_LOCAL ? 32 + c : c;
                        if (lane < nunsent) red_add((unsigned long long*)((char*)&g_sync + 8 * word), 1ull << bit);
                        __syncwarp();
                    }
                    nann++;
                    nunsent = 0; urgent = false;
                };
                auto store_item = [&](int it, bool borrow, bool now) {
                    const int type = item_type(it), m = item_row(it), c = item_col(it);
                    const int npair = type < T_OUT ? 2 : 1;
                    const bool local = type == T_LOCAL;
                    const int grp = type == T_Q ? G_Q + 2 * c : type == T_K ? G_K + 2 * c : type == T_V ? G_V + 2 * c : type == T_B ? G_B + 2 * c
                                  : type == T_ATTN ? G_CTX + c : G_LOC + c;
                    for (int pr = 0; pr < npair; pr++) {
                        if (borrow && pr) {
                            mbar_wait(bars + B_ALT + 8 * w, aph);
                            aph ^= 1;
                            for (int b = 0; b < 2; b++)
                                warp_tma_store(&prm.m[M_SCR_ST], sb + ((nattn & 1) ^ 1) * 32768 + w * 16384 + b * 8192, b * 64, m * 128 + w * 64, grp + 1);
                            bulk_commit();
                            bulk_wait_read<0>();
                            __syncwarp();
                            mbar_arrive_if(lane == 0, bars + B_QFREE);
                            break;
                        }
                        for (int b = 0; b < 2; b++) {
                            if (!__all_sync(0xffffffffu, mbar_test(bars + B_SFULL + 16 * w + 8 * b, sph))) announce();
                            mbar_wait(bars + B_SFULL + 16 * w + 8 * b, sph);
                            warp_tma_store(&prm.m[local ? M_SCR_LOQ : M_SCR_ST], sb + SM_STAGING + w * 16384 + b * 8192,
                                         local ? b * 128 + w * 64 : b * 64, local ? m * 64 : m * 128 + w * 64, grp + pr);
                            bulk_commit();
                            bulk_wait_read<0>();
                            __syncwarp();
                            mbar_arrive_if(lane == 0, bars + B_SEMPTY + 16 * w + 8 * b);
                        }
                        sph ^= 1;
                    }
                    announce();
                    if (lane == nunsent) unsent = it;
                    nunsent++;
                    urgent = now || nunsent == 32 || !local;
                };
                int held = first_item();
                while (true) {
                    if (!__all_sync(0xffffffffu, mbar_test(bars + B_IFULL + 8 * (qn % QDEPTH), (qn / QDEPTH) & 1))) announce();
                    const int it = __shfl_sync(0xffffffffu, next_item(lane == 0), 0), type = item_type(it);
                    const bool keep_held = type == T_LOCAL && (item_type(held) != T_B || (it & ITEM_READY));
                    if (type >= T_ATTN && held < 0 && nunsent) urgent = true;
                    for (int pass = held < 0 || keep_held; pass < 2; pass++) {
                        if (pass && (type < T_OUT || type == T_END)) break;
                        store_item(pass ? it : held, !pass && type == T_ATTN, type >= T_ATTN);
                    }
                    if (type == T_END) break;
                    nattn += type == T_ATTN;
                    if (!keep_held) held = type < T_OUT ? it : -1;
                }
                announce();
                if (item_type(next_item(lane == 0)) == T_OUT) next_item(lane == 0);
            }
        } else {
            if (elect_one()) {
                uint32_t ordy = 0;
                unsigned long long cnt_lo = 0, cnt_hi = 0;
                int late = 0;
                auto refresh = [&]() {
                    if (!late && cnt_lo == 0xccccccccccccccccull && cnt_hi == SEQ / 8) late = 1;
                    asm volatile("ld.acquire.gpu.global.v2.u64 {%0, %1}, [%2];" : "=l"(cnt_lo), "=l"(cnt_hi) : "l"(late ? &g_sync.count[0] : &g_sync.count[2]) : "memory");
                };
                auto inputs_ready = [&](int it) -> bool {
                    const int m = item_row(it), c = item_col(it);
                    if (item_type(it) == T_ATTN) return late && ((c < 16 ? cnt_lo : cnt_hi) >> (4 * (c & 14)) & 255) == 48;
                    return late || (cnt_hi == SEQ / 8 && (cnt_lo >> (4 * m) & 15) == 12 && (cnt_lo >> (4 * max(m - 1, 0)) & 15) == 12);
                };
                auto publish = [&](int it, int step) {
                    const uint32_t slot = qn % QDEPTH;
                    mbar_wait(bars + B_IEMPTY + 8 * slot, ((qn / QDEPTH) & 1) ^ 1);
                    for (uint32_t r = 0; r < 2; r++) {
                        const uint32_t rb = map_cta(bars, r);
                        asm volatile("mbarrier.arrive.expect_tx.shared::cluster.b64 _, [%0], 4;" :: "r"(rb + B_IFULL + 8 * slot) : "memory");
                        asm volatile("st.async.shared::cluster.mbarrier::complete_tx::bytes.u32 [%0], %1, [%2];"
                                     :: "r"(rb + SM_QUEUE + 4 * slot), "r"(it + r * step), "r"(rb + B_IFULL + 8 * slot) : "memory");
                    }
                    qn++;
                };
                int asc = 1;
                int it;
                do {
                    if (rank == 0) {
                        mbar_wait(bars + B_WANT, qn & 1);
                        unsigned i;
                        asm volatile("atom.relaxed.gpu.global.add.u32 %0, [%1], 1;" : "=r"(i) : "l"(&g_sync.next) : "memory");
                        if (cnt_lo != 0x3030303030303030ull || cnt_hi != cnt_lo) refresh();
                        i += NPAIR;
                        const int pit = i < NITEMS ? prm.items[i] : T_END << 13, type = item_type(pit);
                        int step = type == T_LOCAL ? 16 : 1;
                        it = pit + (pit & (step == 1 ? 15 : 0x1f0));
                        if (type == T_ATTN) {
                            if (!asc) { it += 1; step = -1; }
                            it |= asc << 9;
                        }
                        asc = type != T_ATTN || item_row(pit) == 0 || !asc;
                        if (inputs_ready(it)) it |= ITEM_READY;
                        publish(it, step);
                    } else {
                        it = next_item(true);
                    }
                    if ((item_type(it) == T_ATTN || item_type(it) == T_LOCAL) && !(it & ITEM_READY)) {
                        unsigned n = 0;
                        while (!inputs_ready(it)) { refresh(); spin_guard(n); }
                        asm volatile("st.release.cta.shared.u32 [%0], %1;" :: "r"(bars + SM_ORDY + 4), "r"(ordy += 256) : "memory");
                    }
                } while (item_type(it) != T_END);
                if (PF_LOC && blockIdx.x < 128) {
                    prefetch_l2((const char*)g_scr + (uint32_t)(G_LOC * SEQ * 256 + blockIdx.x * 32768), 32768);
                    prefetch_l2(prm.wob + blockIdx.x * 16384, 16384);
                }
                if (rank == 0) {
                    mbar_wait(bars + B_WANT, qn & 1);
                    const unsigned i = atomicAdd(&g_sync.next_out, 1u), t = i < 32 ? 31 - i : i - 32;
                    it = i < 64 ? T_OUT << 13 | ((t & 3) * 2 + (i >> 5)) << 4 | (t >> 2) * 2 : T_END << 13;
                    publish(it, 1);
                } else {
                    it = next_item(true);
                }
                if (item_type(it) == T_OUT) {
                    const uint32_t m = item_row(it), half = item_col(it) & 1, tile = m * 2 + (item_col(it) >> 1);
                    unsigned* split = (unsigned*)((char*)g_sync.split + 4 * tile);
                    unsigned long long rdy = 0;
                    int state = rank ? 2 : 0;
                    for (unsigned n = 0; rdy != 0xffffffffffull || state < 2; spin_guard(n)) {
                        if (rdy != 0xffffffffffull) {
                            rdy = ld_acquire((const unsigned long long*)((char*)g_sync.ctx + 8 * m));
                            asm volatile("st.release.cta.shared.u64 [%0], %1;" :: "r"(bars + SM_ORDY), "l"(rdy) : "memory");
                        }
                        unsigned steps = 0;
                        if (state == 1) {
                            steps = ld_acquire(split);
                        } else if (state == 0 && mbar_test(bars + B_WANT, qn & 1)) {
                            state = 1;
                            unsigned seen;
                            asm volatile("atom.acq_rel.gpu.global.exch.b32 %0, [%1], 1;" : "=r"(seen) : "l"(split) : "memory");
                            if (seen) {
                                const unsigned long long v = ld_acquire((const unsigned long long*)((char*)g_sync.step + 8 * tile));
                                const int d = (int)(v >> 32) - (int)v;
                                steps = (WIDE + min(max(half ? d : -d, K_MEET - K_SPLIT), K_SPLIT - K_MEET)) >> 1;
                                atomicExch(split, WIDE - steps);
                            }
                        }
                        if (steps > 1) { publish(T_END << 13 | steps, 0); state = 2; PMARK(1, 0xF400 + steps); }
                    }
                    if (rank) next_item(true);
                }
                if (rank == 0) for (uint32_t n = qn; n < qn + QDEPTH; n++) mbar_wait(bars + B_IEMPTY + 8 * (n % QDEPTH), ((n / QDEPTH) & 1) ^ 1);
            }
        }
    } else {
        reg_inc<232>();
        const int wg = (warp >> 2) - 1, wq = warp & 3;
        uint32_t gph = 0;
        uint32_t kvn = 0;
        const uint32_t dA = make_desc(sb + wg * 8192, 16);
        uint32_t ti = 0;
        uint32_t sph = 1;
        const uint32_t stg = sb + SM_STAGING + wg * 16384;
        const uint32_t stg_lane = stg + (wq * 16 + (lane & 15)) * 128 + (((lane >> 4) ^ (lane & 7)) << 4);
        auto write_blocks = [&](auto n, uint32_t off, const uint32_t* v) {
            uint32_t a = stg_lane;
            asm volatile("" : "+r"(a));
            a += off;
#pragma unroll
            for (int j = 0; j < decltype(n)::value; j++)
                stmatrix_x4((a ^ (32 * (j & 3))) + (j >> 2) * 8192, v[4 * j], v[4 * j + 1], v[4 * j + 2], v[4 * j + 3]);
        };
        auto release = [&](uint32_t bar) { mbar_arrive_if(lane == 0, bars + bar); };
        const uint32_t bars_lane = map_cta(bars, lane & 1);
        auto release_stage = [&](uint32_t st) { mbar_arrive_cluster_if(lane < 2, bars_lane + B_GEMPTY + 8 * st); };
        auto take_item = [&]() -> int {
            return __shfl_sync(0xffffffffu, next_item(lane == 0, false), 0);
        };
        auto stage_acquire = [&](int b) { mbar_spin(bars + B_SEMPTY + 16 * wg + 8 * b, sph); };
        auto stage_publish = [&](int b) {
            fence_proxy_async_smem();
            __syncwarp();
            release(B_SFULL + 16 * wg + 8 * b);
        };
        auto stage_chunk = [&](int b, const uint32_t* v) {
            stage_acquire(b);
            write_blocks(std::integral_constant<int, 4>(), b * 8192, v);
            stage_publish(b);
            if (b) sph ^= 1;
        };
        auto publish_pair = [&]() {
            fence_proxy_async_smem();
            __syncwarp();
            mbar_arrive_if(lane < 2, bars + B_SFULL + 16 * wg + 8 * lane);
            sph ^= 1;
        };
        auto gemm_step = [&](float (&acc)[128], uint32_t dB, int& k) {
            const uint32_t st = k & 3;
            wgmma_wait<0>();
            release_stage((k - 1) & 3);
            mbar_spin(bars + B_GFULL + 8 * st, gph);
            const uint64_t da = full_desc(dA + st * (GST_BYTES >> 4)), db = full_desc(dB + st * (GST_BYTES >> 4));
            wgmma_fence();
#pragma unroll
            for (int kk = 0; kk < 4; kk++) wgmma_ss_n256_tb(acc, da + 2 * kk, db + 128 * kk, 1);
            wgmma_commit();
            gph ^= st == 3;
            k++;
        };
        if (wg == 1) bar_arrive(1, 256);
        int it = first_item();
        bool unpublished = false;
        while (true) {
            if (item_type(it) <= T_LOCAL) {
                float acc[128];
                uint32_t pk[64];
                bool pending = false;
                bool held_b = false;
                zero_regs(pk);
                const uint32_t dB = make_desc(sb + 16384, 8192);
                do {
                    const int type = item_type(it);
                    if (type == T_LOCAL) {
                        int ln = lane;
                        asm volatile("" : "+r"(ln));
                        const int g = ln >> 2, t = ln & 3, par = wq & 1;
                        const uint32_t hc = (wq >> 1) * 4, pl = sb + (par * 2 + wg) * LOC_PLANE;
                        const uint32_t a16 = (ln & 15) * 128 + (((hc + (ln >> 4)) ^ (ln & 7)) << 4), a8 = (ln & 7) * 128 + (((hc + (ln >> 3)) ^ (ln & 7)) << 4);
                        const bool first0 = 2 * t > g, first1 = 2 * t + 1 > g;
                        const uint32_t fmask = (first0 ? 0xffffu : 0u) | (first1 ? 0xffff0000u : 0u);
                        const bool edge = item_row(it) == 0;
                        uint32_t q[4][2][4], kf[9][4], vf[9][4];
                        float w[8];
                        mbar_spin(bars + B_GFULL, gph);
#pragma unroll
                        for (int u = 0; u < 4; u++) { ldsm_x4(q[u][0], pl + u * 2048 + a16); ldsm_x4(q[u][1], pl + u * 2048 + (a16 ^ 32)); }
#pragma unroll
                        for (int j = 0; j < 8; j++) w[j] = lds_f32(sb + 4 * LOC_PLANE + 4 * (2 * g + par) + 64 * j);
                        __syncwarp();
                        release_stage(0);
                        mbar_spin(bars + B_GFULL + 8, gph);
#pragma unroll
                        for (int n = 0; n < 9; n++) ldsm_x4(kf[n], pl + GST_BYTES + n * 1024 + a8);
                        __syncwarp();
                        release_stage(1);
                        float s[8][2];
#pragma unroll
                        for (int u = 0; u < 4; u++) {
                            float d[3][4];
#pragma unroll
                            for (int nt = 0; nt < 3; nt++) {
                                mma_k16_init(d[nt], q[u][0], kf[2 * u + nt][0], kf[2 * u + nt][1]);
                                mma_k16(d[nt], q[u][1], kf[2 * u + nt][2], kf[2 * u + nt][3]);
                            }
                            if (u == 0 && edge) { d[0][0] = -INFINITY; d[0][1] = -INFINITY; }
                            s[2 * u][0] = first0 ? d[0][0] : d[1][0]; s[2 * u][1] = first1 ? d[0][1] : d[1][1];
                            s[2 * u + 1][0] = first0 ? d[1][2] : d[2][2]; s[2 * u + 1][1] = first1 ? d[1][3] : d[2][3];
                        }
                        mbar_spin(bars + B_GFULL + 16, gph);
#pragma unroll
                        for (int u = 0; u < 4; u++) { ldsm_x4_t(vf[2 * u], pl + 2 * GST_BYTES + u * 2048 + a16); ldsm_x4_t(vf[2 * u + 1], pl + 2 * GST_BYTES + u * 2048 + (a16 ^ 32)); }
                        ldsm_x4_t(vf[8], pl + 2 * GST_BYTES + 8192 + a8);
                        __syncwarp();
                        release_stage(2);
                        float x[8];
#pragma unroll
                        for (int j = 0; j < 8; j++) x[j] = fmaxf(s[j][0], s[j][1]);
#pragma unroll
                        for (int o = 1; o < 4; o *= 2)
#pragma unroll
                            for (int j = 0; j < 8; j++) x[j] = fmaxf(x[j], __shfl_xor_sync(0xffffffffu, x[j], o));
#pragma unroll
                        for (int j = 0; j < 8; j++) {
                            const float n = x[j] * -LOC_SCALE;
                            s[j][0] = ex2(fmaf(s[j][0], LOC_SCALE, n)); s[j][1] = ex2(fmaf(s[j][1], LOC_SCALE, n));
                            x[j] = s[j][0] + s[j][1];
                        }
#pragma unroll
                        for (int o = 1; o < 4; o *= 2)
#pragma unroll
                            for (int j = 0; j < 8; j++) x[j] += __shfl_xor_sync(0xffffffffu, x[j], o);
                        mbar_spin(bars + B_GFULL + 24, gph);
                        release_stage(3);
                        it = take_item();
                        uint32_t ob[4][8];
#pragma unroll
                        for (int u = 0; u < 4; u++) {
                            const float r0 = rcp(x[2 * u]), r1 = rcp(x[2 * u + 1]), f0 = fmaf(-w[2 * u], r0, r0), f1 = fmaf(-w[2 * u + 1], r1, r1);
                            const uint32_t p0 = pack_bf16(s[2 * u][0] * f0, s[2 * u][1] * f0), p1 = pack_bf16(s[2 * u + 1][0] * f1, s[2 * u + 1][1] * f1);
                            const uint32_t pa[4] = {p0 & fmask, 0, p0 & ~fmask, p1 & fmask};
#pragma unroll
                            for (int c = 0; c < 4; c++) {
                                float ol[4];
                                mma_k16_init(ol, pa, vf[2 * u + (c >> 1)][2 * (c & 1)], vf[2 * u + (c >> 1)][2 * (c & 1) + 1]);
                                mma_k8(ol, 0, p1 & ~fmask, u < 3 ? vf[2 * u + 2 + (c >> 1)][2 * (c & 1)] : vf[8][c]);
                                ob[u][2 * c] = pack_bf16(ol[0], ol[1]);
                                ob[u][2 * c + 1] = pack_bf16(ol[2], ol[3]);
                            }
                        }
                        stage_acquire(0); stage_acquire(1);
#pragma unroll
                        for (int u = 0; u < 4; u++) {
                            stmatrix_x4(stg + par * 8192 + u * 2048 + a16, ob[u][0], ob[u][1], ob[u][2], ob[u][3]);
                            stmatrix_x4(stg + par * 8192 + u * 2048 + (a16 ^ 32), ob[u][4], ob[u][5], ob[u][6], ob[u][7]);
                        }
                        fence_proxy_async_smem();
                        __syncwarp();
                        mbar_arrive_if(lane < 2, bars + B_SFULL + 16 * wg + 8 * lane);
                        bar_sync(4, 256);
                        sph ^= 1; gph ^= 1;
                        continue;
                    }
                    mbar_spin(bars + B_GFULL, gph);
                    bool more;
                    do {
                        wgmma_fence();
                        wgmma_ss_n256_tb_init(acc, full_desc(dA), full_desc(dB));
#pragma unroll
                        for (int kk = 1; kk < 4; kk++) wgmma_ss_n256_tb(acc, full_desc(dA) + 2 * kk, full_desc(dB) + 128 * kk, 1);
                        wgmma_commit();
                        const int nk = item_type(it) == T_K || item_type(it) == T_V ? 8 : 16;
                        int k = 1;
                        do {
                            if (pending) {
                                const int kf = k - 1 - wg;
                                if (kf == 0) stage_chunk(0, pk);
                                else if (kf == 1) stage_chunk(1, pk + 16);
                                else if (kf == KF2) stage_chunk(0, pk + 32);
                                else if (kf == KF2 + 1) stage_chunk(1, pk + 48);
                            }
                            gemm_step(acc, dB, k);
                        } while (k < nk);
                        held_b = item_type(it) == T_B;
                        const bool is_q = item_type(it) == T_Q;
                        it = take_item();
                        more = item_type(it) < T_LOCAL;
                        if (more) mbar_spin(bars + B_GFULL, gph);
                        wgmma_wait<0>();
                        fence_regs(acc);
                        release_stage(3);
                        if (is_q) {
#pragma unroll
                            for (int j = 0; j < 128; j++) acc[j] *= SM_SCALE;
                        }
#pragma unroll
                        for (int j = 0; j < 64; j++) pk[j] = pack_bf16(acc[2 * j], acc[2 * j + 1]);
                        pending = true;
                    } while (more);
                } while (item_type(it) < T_LOCAL || (item_type(it) == T_LOCAL && (!held_b || (it & ITEM_READY))));
                if (pending) {
                    stage_acquire(0); stage_acquire(1);
                    write_blocks(std::integral_constant<int, 8>(), 0, pk);
                    const bool borrow = item_type(it) == T_ATTN;
                    if (borrow) {
                        mbar_spin(bars + B_GEMPTY, gph ^ 1); mbar_spin(bars + B_GEMPTY + 8, gph ^ 1);
                    } else {
                        publish_pair();
                        stage_acquire(0); stage_acquire(1);
                    }
                    write_blocks(std::integral_constant<int, 8>(), borrow ? ((ti & 1) ^ 1) * 32768 - SM_STAGING : 0, pk + 32);
                    publish_pair();
                    mbar_arrive_if(lane == 0 && borrow, bars + B_ALT + 8 * wg);
                }
                if (item_type(it) == T_END) { it = take_item(); break; }
            } else {
                float o[64], s[64];
                uint32_t pa[32], pb[32];
                zero_regs(o); zero_regs(s); zero_regs(pa);
                float n0 = 0.f, n1 = 0.f;
                bool shifted = false;
                float l0 = 1.f, l1 = 1.f, f0 = 0.f, f1 = 0.f, g0 = 0.f, g1 = 0.f;
                uint32_t has_pv = 0;
                int first = 0;
                int pending = 0;
                const uint32_t dK = make_desc(sb + SM_KV, 16), dV = make_desc(sb + SM_KV, 16384);
                const uint32_t lane_off = bars_lane - bars + B_AEMPTY - B_AFULL;
                int cur = 0;
                uint32_t qoff = 0;
                const int row = wg * 64 + wq * 16 + (lane >> 2);
                const float thr = (row & 63) - (lane & 3) * 2;
                uint32_t peek = 0;
                bool peek_ok = false, q_ok = false;
                auto kv_wait = [&](uint32_t n) { mbar_spin(bars + B_AFULL + 16 + 8 * (n & 3), (n >> 2) & 1); };
                auto kv_release = [&](uint32_t n) { mbar_arrive_cluster_if(lane < 2, bars_lane + B_AEMPTY + 16 + 8 * (n & 3)); };
                struct Slot { uint32_t bar, par, off; } slot[4];
                auto align = [&]() {
#pragma unroll
                    for (uint32_t i = 0; i < 4; i++) {
                        const uint32_t n = kvn + (i == 1 ? has_pv : i);
                        slot[i].bar = bars + B_AFULL + 16 + 8 * (n & 3); slot[i].par = (n >> 2) & 1; slot[i].off = (n & 3) * 2048;
                    }
                };
                align();
                auto scale_o = [&]() {
#pragma unroll
                    for (int j = 0; j < 16; j++) { o[4 * j] *= f0; o[4 * j + 1] *= f0; o[4 * j + 2] *= f1; o[4 * j + 3] *= f1; }
                };
                auto pack_o = [&](uint32_t (&v)[32]) {
#pragma unroll
                    for (int j = 0; j < 32; j++) v[j] = pack_bf16(o[2 * j], o[2 * j + 1]);
                };
                auto scales = [&]() { f0 = g0 * rcp(quad_sum(l0)); f1 = g1 * rcp(quad_sum(l1)); };
                auto step = [&](auto even, uint32_t (&pin)[32], uint32_t (&pout)[32], bool fresh, bool diag, bool last) {
                    constexpr bool EVEN = decltype(even)::value;
                    Slot& sk = slot[EVEN ? 0 : 2];
                    Slot& sv = slot[EVEN ? 1 : 3];
                    kvn += EVEN ? 1 + has_pv : 2;
                    mbar_spin(sk.bar, sk.par);
                    bar_sync(1 + wg, 256);
                    qk_gemm(s, dA + qoff, dK + sk.off);
                    if (EVEN && fresh) {
                        scales();
                        g0 = lds_f32(bars + SM_GATE + (ti & 1) * 512 + 4 * row); g1 = lds_f32(bars + SM_GATE + (ti & 1) * 512 + 4 * row + 32);
                        ti++;
                        n0 = 0.f; n1 = 0.f; l0 = 0.f; l1 = 0.f;
                        shifted = false;
                        if (has_pv) { stage_acquire(0); stage_acquire(1); }
                    }
                    if (!EVEN && pending) {
                        pack_o(pout);
                        write_blocks(std::integral_constant<int, 8>(), 0, pout);
                    }
                    mbar_spin(sv.bar, sv.par);
                    pv_gemm(o, pin, dV + sv.off, EVEN || !first);
                    bar_arrive(2 - wg, 256);
                    sk.par ^= 1; sv.par ^= 1;
                    wgmma_wait<1>();
                    fence_regs(s);
                    mbar_arrive_cluster_if(lane < 2 && (!EVEN || has_pv), sk.bar + lane_off);
                    mbar_arrive_if(lane == 0 && last, bars + B_AEMPTY + 8 * ((ti - 1) & 1));
                    if (diag || shifted) {
                        if (diag) causal_mask(s, thr, wg);
                        if (shifted) shift_rows(s, n0, n1);
                    }
                    q_ok = mbar_test(bars + B_AFULL + 8 * (ti & 1), (ti >> 1) & 1);
                    peek_ok = mbar_test(bars + B_IFULL + 8 * (qn % QDEPTH), (qn / QDEPTH) & 1);
                    asm volatile("ld.shared.u32 %0, [%1];" : "=r"(peek) : "r"(bars + SM_QUEUE + 4 * (qn % QDEPTH)) : "memory");
                    float r0, r1;
                    exp_pack(pout, s, r0, r1);
                    if (__any_sync(0xffffffffu, fmaxf(r0, r1) >= SUM_LIMIT || (EVEN && fresh && !(lane & 3) && !(fminf(s[0], s[2]) >= -REF_RANGE)))) {
                        float x0, x1;
                        row_max(s, x0, x1);
                        if (!(EVEN && fresh)) { x0 = fmaxf(x0, 0.f); x1 = fmaxf(x1, 0.f); }
                        float a0 = ex2(-x0), a1 = ex2(-x1);
                        n0 += x0; n1 += x1;
                        shifted = true;
                        if (EVEN && fresh) { a0 = 1.f; a1 = 1.f; }
                        l0 *= a0; l1 *= a1;
                        wgmma_wait<0>();
                        fence_regs(o);
#pragma unroll
                        for (int q = 0; q < 16; q++) { o[4 * q] *= a0; o[4 * q + 1] *= a0; o[4 * q + 2] *= a1; o[4 * q + 3] *= a1; }
                        shift_rows(s, x0, x1);
                        exp_pack(pout, s, r0, r1);
                    }
                    l0 += r0; l1 += r1;
                    wgmma_wait<0>();
                    fence_regs(o);
                    fence_regs(pin);
                    mbar_arrive_cluster_if(lane < 2, sv.bar + lane_off);
                };
                auto copy_p = [&]() {
#pragma unroll
                    for (int j = 0; j < 32; j++) pa[j] = __float_as_uint(__uint_as_float(pb[j]) + __uint_as_float(prm.zero));
                };
                int rem = 0;
                mbar_spin(bars + B_AFULL + 8 * (ti & 1), (ti >> 1) & 1);
                while (true) {
                    const bool fresh = rem == 0;
                    if (fresh) {
                        if (has_pv) {
                            if (__all_sync(0xffffffffu, peek_ok)) {
                                mbar_arrive_cluster_if(lane == 0, bars0 + B_IEMPTY + 8 * (qn % QDEPTH));
                                qn++;
                                it = __shfl_sync(0xffffffffu, peek, 0);
                            } else {
                                it = take_item();
                            }
                            if (item_row(cur) < 2 || item_type(it) != T_ATTN) break;
                            if (!q_ok) mbar_spin(bars + B_AFULL + 8 * (ti & 1), (ti >> 1) & 1);
                        }
                        cur = it;
                        qoff = (ti & 1) * 2048;
                    }
                    const bool last = fresh ? item_row(cur) == 0 : rem == 1;
                    step(std::true_type(), pa, pb, fresh, item_asc(cur) ? last : fresh, last);
                    first = fresh;
                    if (fresh) {
                        pending = has_pv; has_pv = 1;
                        if (!pending) { kvn -= 2; align(); kvn += 2; slot[0].par ^= 1; slot[1].par ^= 1; }
                        else scale_o();
                        rem = item_row(cur);
                        if (rem == 0) {
                            copy_p();
                            continue;
                        }
                    } else if (--rem == 0) {
                        copy_p();
                        align();
                        continue;
                    }
                    step(std::false_type(), pb, pa, false, item_asc(cur) && rem == 1, rem == 1);
                    if (pending) publish_pair();
                    pending = 0; first = 0;
                    rem--;
                }
                const uint32_t skip = item_asc(cur) & ~item_row(cur) & 1;
                kvn += skip;
                const bool end = item_type(it) == T_END;
#pragma unroll 1
                for (int pass = pending ? 0 : 1; pass < 2; pass++) {
                    if (pass) {
                        kv_wait(kvn);
                        pv_gemm(o, pa, dV + (kvn & 3) * 2048, !first);
                        scales();
                        stage_acquire(0); stage_acquire(1);
                        if (end) {
                            it = take_item();
                            unpublished = __all_sync(0xffffffffu, mbar_test(bars + B_GFULL, gph));
                        }
                        wgmma_wait<0>();
                        fence_regs(o);
                        kv_release(kvn);
                        kvn += 1 + skip;
                        scale_o();
                    }
                    pack_o(pb);
                    write_blocks(std::integral_constant<int, 8>(), 0, pb);
                    if (!unpublished) publish_pair();
                }
                if (end) break;
            }
        }
        if (item_type(it) == T_OUT) {
            float acc[128];
            const uint32_t dB = make_desc(sb + 16384, 8192);
            mbar_spin(bars + B_GFULL, gph);
            wgmma_fence();
            wgmma_ss_n256_tb_init(acc, full_desc(dA), full_desc(dB));
#pragma unroll
            for (int kk = 1; kk < 4; kk++) wgmma_ss_n256_tb(acc, full_desc(dA) + 2 * kk, full_desc(dB) + 128 * kk, 1);
            wgmma_commit();
            if (unpublished) publish_pair();
            uint32_t ln;
            asm volatile("mov.u32 %0, %%laneid;" : "=r"(ln));
            const uint32_t slot = (it & 127) * 32768 + (wg * 128 + wq * 32 + ln) * 16;
            char* const mine = (char*)g_part + slot;
            int k = 1, nk = 80;
            do {
                if (k == K_MEET - 5) {
#pragma unroll
                    for (int j = 0; j < 8; j++) st_b128(mine + j * 4096, 0, 0, 0, 0);
                    __syncwarp();
                }
                if (k == K_SPLIT) nk = take_item() & 127;
                gemm_step(acc, dB, k);
            } while (k < nk);
            auto triple = [&](uint32_t nrel) {
                const uint32_t s0 = k & 3, s1 = (k + 1) & 3, o0 = s0 * (GST_BYTES >> 4), o1 = s1 * (GST_BYTES >> 4);
                wgmma_wait<0>();
                mbar_arrive_cluster_if(ln < nrel, bars_lane + B_GEMPTY + 8 * ((k - 1 - (ln >> 1)) & 3));
                mbar_spin(bars + B_GFULL + 8 * s0, gph);
                gph ^= s0 == 3;
                wgmma_fence();
#pragma unroll
                for (int kk = 0; kk < 4; kk++) wgmma_ss_n128_lo_tb(acc, full_desc(dA + o0) + 2 * kk, full_desc(dB + o0) + 128 * kk, 1);
                mbar_spin(bars + B_GFULL + 8 * s1, gph);
                gph ^= s1 == 3;
                wgmma_fence();
#pragma unroll
                for (int kk = 0; kk < 4; kk++) wgmma_ss_n128_lo_tb(acc, full_desc(dA + o0 + 2048) + 2 * kk, full_desc(dB + o1 + 1024) + 128 * kk, 1);
#pragma unroll
                for (int kk = 0; kk < 4; kk++) wgmma_ss_n128_lo_tb(acc, full_desc(dA + o1) + 2 * kk, full_desc(dB + o1) + 128 * kk, 1);
                wgmma_commit();
                k += 2;
            };
            triple(2);
#pragma unroll
            for (int j = 0; j < 8; j++) {
                uint32_t v[4];
#pragma unroll
                for (int i = 0; i < 4; i++) {
                    asm volatile("" : "+f"(acc[64 + 8 * j + 2 * i]), "+f"(acc[65 + 8 * j + 2 * i]) :: "memory");
                    v[i] = pack_bf16(acc[64 + 8 * j + 2 * i], acc[65 + 8 * j + 2 * i]);
                }
                if (j == SPREAD) triple(4);
                else if (PACE && j) __nanosleep(PACE);
                st_b128(mine + j * 4096, ~v[0], v[1], v[2], v[3]);
            }
#pragma unroll 1
            for (int t = 2; t < TRIPLES; t++) triple(4);
            uint32_t pk[32];
            char* const other = (char*)g_part + (slot ^ (16 * 32768));
            while (true) {
                bool miss = false;
#pragma unroll
                for (int j = 0; j < 8; j++) ld_b128(other + j * 4096, pk[4 * j], pk[4 * j + 1], pk[4 * j + 2], pk[4 * j + 3]);
#pragma unroll
                for (int j = 0; j < 8; j++) miss |= pk[4 * j] == 0;
                if (!__any_sync(0xffffffffu, miss)) break;
                while (__any_sync(0xffffffffu, pk[28] == 0)) ld_b128(other + 7 * 4096, pk[28], pk[29], pk[30], pk[31]);
            }
#pragma unroll
            for (int j = 0; j < 32; j++) {
                const uint32_t v = j & 3 ? pk[j] : ~pk[j];
                acc[64 + 2 * j] = __uint_as_float(v << 16); acc[65 + 2 * j] = __uint_as_float(v & 0xffff0000u);
                asm volatile("" : "+f"(acc[64 + 2 * j]), "+f"(acc[65 + 2 * j]) :: "memory");
            }
            stage_acquire(0); stage_acquire(1);
            wgmma_wait<0>();
#pragma unroll
            for (int j = 0; j < 64; j++) asm volatile("" : "+f"(acc[j]) :: "memory");
            mbar_arrive_cluster_if(ln < 4, bars_lane + B_GEMPTY + 8 * ((k - 1 - (ln >> 1)) & 3));
#pragma unroll
            for (int j = 0; j < 32; j++)
                pk[j] = pack_bf16(acc[2 * j] + acc[64 + 2 * j], acc[2 * j + 1] + acc[65 + 2 * j]);
            write_blocks(std::integral_constant<int, 8>(), 0, pk);
            __syncwarp();
            uint4* dst = (uint4*)((char*)prm.out + (uint32_t)((item_row(it) * 128 + wg * 64 + wq * 16 + (ln >> 4)) * 2048 + item_col(it) * 256 + (ln & 15) * 16));
#pragma unroll
            for (int j = 0; j < 8; j++) {
                const int r = 2 * j + (ln >> 4);
                uint4 v;
                asm volatile("ld.shared.v4.u32 {%0, %1, %2, %3}, [%4];" : "=r"(v.x), "=r"(v.y), "=r"(v.z), "=r"(v.w)
                             : "r"(stg + wq * 2048 + r * 128 + (ln & 8) * 1024 + (((ln & 7) ^ (r & 7)) << 4)) : "memory");
                dst[j * 256] = v;
            }
        }
    }
}

typedef CUresult (*EncodeFn)(CUtensorMap*, CUtensorMapDataType, cuuint32_t, void*, const cuuint64_t*, const cuuint64_t*,
                             const cuuint32_t*, const cuuint32_t*, CUtensorMapInterleave, CUtensorMapSwizzle,
                             CUtensorMapL2promotion, CUtensorMapFloatOOBfill);

void encode3(EncodeFn fn, CUtensorMap* m, const void* ptr, uint64_t d0, uint64_t d1, uint64_t d2, uint64_t s1, uint64_t s2,
             uint32_t b0, uint32_t b1, uint32_t b2) {
    cuuint64_t dims[3] = {d0, d1, d2};
    cuuint64_t strides[2] = {s1, s2};
    cuuint32_t box[3] = {b0, b1, b2};
    cuuint32_t es[3] = {1, 1, 1};
    fn(m, CU_TENSOR_MAP_DATA_TYPE_BFLOAT16, 3, const_cast<void*>(ptr), dims, strides, box, es, CU_TENSOR_MAP_INTERLEAVE_NONE,
       CU_TENSOR_MAP_SWIZZLE_128B, CU_TENSOR_MAP_L2_PROMOTION_NONE, CU_TENSOR_MAP_FLOAT_OOB_FILL_NONE);
}
void map_act(EncodeFn fn, CUtensorMap* m, const void* p, int rows, int cols, int box_rows) {
    encode3(fn, m, p, cols, rows, 1, (uint64_t)cols * 2, (uint64_t)cols * rows * 2, 64, box_rows, 1);
}
void map_wgt(EncodeFn fn, CUtensorMap* m, const void* p, int K, int N) {
    encode3(fn, m, p, 64, K, N / 64, (uint64_t)N * 2, 128, 64, 64, 2);
}

void build_schedule(Params& p) {
    int n = 0;
    auto add = [&](int type, int col, int row) { p.items[n++] = (uint16_t)(type << 13 | col << 4 | row); };
    auto add_qkv = [&](int c) {
        for (int m = 0; m < 8; m++) add(T_Q, c, m);
        for (int m = 0; m < 8; m++) add(T_K, c, m);
        for (int m = 0; m < 8; m++) add(T_V, c, m);
    };
    int ldist = 200, ldist2 = 260, lstep = 8, beta = 26, tail = 32, late = 6, early = 8, epos = 100;
    int order[16] = {6, 7, 8, 9, 10, 11, 12, 13, 14, 15, 5, 4, 3, 2, 1, 0};
    uint16_t proj[480];
    for (int m = 0; m < 8; m++) for (int c = 0; c < 12; c++) add(T_B, c, m);
    for (int c = 0; c < 16; c++) add_qkv(c);
    for (int i = 0; i < 480; i++) proj[i] = p.items[i];
    n = 0;
    for (int i = 0, l = 0; i < 480; i++) {
        p.items[n++] = proj[i];
        for (; l < 64 && i >= (l < 40 ? ldist + lstep * l / 8 : ldist2 + lstep * (l - 40) / 8); l++) add(T_LOCAL, l & 3, l >> 2);
    }
    const int a0 = n;
    for (int key = 0; key < 4000; key++)
        for (int r = 0; r < 32; r++)
            for (int j = 7; j >= 0; j--)
                if ((j ? (7 - j) * 40 + r * beta : 3999) == key) add(T_ATTN, 2 * order[r >> 1] + (r & 1), j);
    int t0 = n;
    for (int work = 0; work < 32 * 136 * tail / 100;) work += 4 * (p.items[--t0] & 15) + 3;
    for (int i = t0 + 1; i < n; i++)
        for (int j = i; j > t0 && (p.items[j] & 15) > (p.items[j - 1] & 15); j--) { const uint16_t t = p.items[j]; p.items[j] = p.items[j - 1]; p.items[j - 1] = t; }
    for (int r = early - 1; r >= 0; r--) {
        const uint16_t t = p.items[n - 32 + early - 1];
        for (int j = n - 32 + early - 1; j > n - epos; j--) p.items[j] = p.items[j - 1];
        p.items[n - epos] = t;
    }
    for (int moved = 0; moved < 2 && late >= 0; moved++)
        for (int i = a0; i < n; i++)
            if (p.items[i] == (T_ATTN << 13 | (2 * order[15] + moved) << 4 | late)) {
                for (int j = i; j + 1 < n; j++) p.items[j] = p.items[j + 1];
                p.items[n - 1] = (uint16_t)(T_ATTN << 13 | (2 * order[15] + moved) << 4 | late);
                break;
            }
    for (int s = 0, lo = 0, hi = WIDE - 1; s < 80; s++) {
        const int r = s / 2, g = r < 8 ? 32 + r : 2 * order[r / 2 - 4] + (r & 1);
        p.ostep[s >= WIDE ? s : r & 1 ? hi-- : lo++] = (uint8_t)(2 * g + (s & 1));
    }
}

void build_params(Params& p, void* const* d_in, void* d_out) {
    void* fnp = nullptr;
    cudaDriverEntryPointQueryResult qr;
    cudaGetDriverEntryPoint("cuTensorMapEncodeTiled", &fnp, cudaEnableDefault, &qr);
    EncodeFn fn = (EncodeFn)fnp;
    void* scr = nullptr;
    cudaGetSymbolAddress(&scr, g_scr);
    map_act(fn, &p.m[M_X], d_in[0], SEQ, 1024, 128);
    map_act(fn, &p.m[M_C], d_in[1], SEQ, 512, 128);
    map_wgt(fn, &p.m[M_WQ], d_in[2], 1024, 4096);
    map_wgt(fn, &p.m[M_WUK], d_in[3], 512, 4096);
    map_wgt(fn, &p.m[M_WUV], d_in[4], 512, 4096);
    map_wgt(fn, &p.m[M_WO], d_in[5], 4096, 1024);
    map_wgt(fn, &p.m[M_WQKV], d_in[7], 1024, 3072);
    map_wgt(fn, &p.m[M_WOB], d_in[8], 1024, 1024);
    encode3(fn, &p.m[M_SCR_LD], scr, 128, SEQ, G_TOTAL, 256, (uint64_t)SEQ * 256, 64, 128, 1);
    encode3(fn, &p.m[M_SCR_LOC], scr, 256, SEQ / 2, G_TOTAL, 512, (uint64_t)SEQ * 256, 64, 72, 1);
    encode3(fn, &p.m[M_SCR_LOQ], scr, 256, SEQ / 2, G_TOTAL, 512, (uint64_t)SEQ * 256, 64, 64, 1);
    encode3(fn, &p.m[M_SCR_ST], scr, 128, SEQ, G_TOTAL, 256, (uint64_t)SEQ * 256, 64, 64, 1);
    p.x = (const __nv_bfloat16*)d_in[0];
    p.gate_w = (const __nv_bfloat16*)d_in[9];
    p.zero = 0;
    p.wo = (const char*)d_in[5];
    p.wob = (const char*)d_in[8];
    p.out = (__nv_bfloat16*)d_out;
    build_schedule(p);
}

}

extern "C" void kernel_launch(void* const* d_in, const int* in_sizes, int n_in, void* d_out, int out_size) {
    (void)in_sizes; (void)n_in; (void)out_size;
    Params p;
    build_params(p, d_in, d_out);
    cudaFuncSetAttribute(fused_kernel, cudaFuncAttributeMaxDynamicSharedMemorySize, SM_TOTAL);
    fused_kernel<<<NCTA, 384, SM_TOTAL>>>(p);
}
```

```cpp
#include <cuda_runtime.h>
#include <cuda_bf16.h>
#include <cuda.h>
#include <stddef.h>
#include <stdint.h>
#include <type_traits>

namespace {

constexpr int SEQ = 2048;
constexpr int G_Q = 0, G_K = 32, G_V = 64, G_B = 96, G_CTX = G_Q, G_LOC = G_B, G_TOTAL = 120;

__device__ __align__(1024) __nv_bfloat16 g_scr[(size_t)G_TOTAL * SEQ * 128];
__device__ __align__(128) float g_gate[SEQ];

__device__ __forceinline__ uint32_t smem_u32(const void* p) { return (uint32_t)__cvta_generic_to_shared(p); }
__device__ __forceinline__ bool elect_one() {
    uint32_t p;
    asm volatile("{\n.reg .pred P;\nelect.sync _|P, 0xffffffff;\nselp.u32 %0, 1, 0, P;\n}\n" : "=r"(p));
    return p != 0;
}
__device__ __forceinline__ void mbar_init(uint32_t bar, uint32_t count) {
    asm volatile("mbarrier.init.shared::cta.b64 [%0], %1;" :: "r"(bar), "r"(count) : "memory");
}
__device__ __forceinline__ void mbar_expect_tx(uint32_t bar, uint32_t bytes) {
    asm volatile("mbarrier.arrive.expect_tx.shared::cta.b64 _, [%0], %1;" :: "r"(bar), "r"(bytes) : "memory");
}
__device__ __forceinline__ uint32_t cluster_rank() { uint32_t r; asm("mov.u32 %0, %%cluster_ctarank;" : "=r"(r)); return r; }
__device__ __forceinline__ uint32_t map_cta(uint32_t addr, uint32_t cta) {
    uint32_t r; asm("mapa.shared::cluster.u32 %0, %1, %2;" : "=r"(r) : "r"(addr), "r"(cta)); return r;
}
__device__ __forceinline__ void mbar_arrive_cluster_if(bool pred, uint32_t cluster_bar) {
    asm volatile("{\n.reg .pred P;\nsetp.ne.u32 P, %1, 0;\n@P mbarrier.arrive.shared::cluster.b64 _, [%0];\n}\n"
                 :: "r"(cluster_bar), "r"((uint32_t)pred) : "memory");
}
__device__ __forceinline__ void mbar_arrive_cluster_n_if(bool pred, uint32_t cluster_bar, uint32_t count) {
    asm volatile("{\n.reg .pred P;\nsetp.ne.u32 P, %1, 0;\n@P mbarrier.arrive.shared::cluster.b64 _, [%0], %2;\n}\n"
                 :: "r"(cluster_bar), "r"((uint32_t)pred), "r"(count) : "memory");
}
__device__ __forceinline__ void mbar_arrive_if(bool pred, uint32_t bar) {
    asm volatile("{\n.reg .pred P;\nsetp.ne.u32 P, %1, 0;\n@P mbarrier.arrive.shared::cta.b64 _, [%0];\n}\n"
                 :: "r"(bar), "r"((uint32_t)pred) : "memory");
}
__device__ __forceinline__ bool mbar_test(uint32_t bar, uint32_t parity) {
    uint32_t ok;
    asm volatile("{\n.reg .pred P;\nmbarrier.test_wait.parity.shared::cta.b64 P, [%1], %2;\nselp.u32 %0, 1, 0, P;\n}\n"
                 : "=r"(ok) : "r"(bar), "r"(parity) : "memory");
    return ok != 0;
}
__device__ __forceinline__ void mbar_wait(uint32_t bar, uint32_t parity) {
    asm volatile("{\n.reg .pred P;\n.reg .u32 c;\n"
                 "mbarrier.try_wait.parity.shared::cta.b64 P, [%0], %1;\n"
                 "@P bra DONE;\n"
                 "mov.u32 c, 0;\n"
                 "SPIN:\n"
                 "mbarrier.try_wait.parity.shared::cta.b64 P, [%0], %1;\n"
                 "@P bra DONE;\n"
                 "add.u32 c, c, 1;\n"
                 "setp.lt.u32 P, c, 4194304;\n"
                 "@P bra SPIN;\n"
                 "trap;\n"
                 "DONE:\n}\n" :: "r"(bar), "r"(parity) : "memory");
}
__device__ __forceinline__ void mbar_spin(uint32_t bar, uint32_t parity) {
    asm volatile("{\n.reg .pred P;\n"
                 "SPIN:\n"
                 "mbarrier.try_wait.parity.shared::cta.b64 P, [%0], %1;\n"
                 "@!P bra SPIN;\n}\n" :: "r"(bar), "r"(parity) : "memory");
}
__device__ __forceinline__ void bar_sync(int id, int n) { asm volatile("bar.sync %0, %1;" :: "r"(id), "r"(n) : "memory"); }
__device__ __forceinline__ void bar_arrive(int id, int n) { asm volatile("bar.arrive %0, %1;" :: "r"(id), "r"(n) : "memory"); }
__device__ __forceinline__ void fence_proxy_async_smem() { asm volatile("fence.proxy.async.shared::cta;" ::: "memory"); }
__device__ __forceinline__ void tma_load_3d(uint32_t dst, const CUtensorMap* map, uint32_t bar, int c0, int c1, int c2) {
    asm volatile("cp.async.bulk.tensor.3d.shared::cluster.global.mbarrier::complete_tx::bytes [%0], [%1, {%3, %4, %5}], [%2];"
                 :: "r"(dst), "l"(map), "r"(bar), "r"(c0), "r"(c1), "r"(c2) : "memory");
}
__device__ __forceinline__ void warp_expect_tx(uint32_t bar, uint32_t bytes) {
    asm volatile("{\n.reg .pred P;\nelect.sync _|P, 0xffffffff;\n@P mbarrier.arrive.expect_tx.shared::cta.b64 _, [%0], %1;\n}\n"
                 :: "r"(bar), "r"(bytes) : "memory");
}
__device__ __forceinline__ void warp_tma_load(uint32_t dst, const CUtensorMap* map, uint32_t bar, int c0, int c1, int c2) {
    asm volatile("{\n.reg .pred P;\nelect.sync _|P, 0xffffffff;\n"
                 "@P cp.async.bulk.tensor.3d.shared::cluster.global.mbarrier::complete_tx::bytes [%0], [%1, {%3, %4, %5}], [%2];\n}\n"
                 :: "r"(dst), "l"(map), "r"(bar), "r"(c0), "r"(c1), "r"(c2) : "memory");
}
__device__ __forceinline__ void warp_tma_load_pair(uint32_t dst, const CUtensorMap* map, uint32_t bar, int c0, int c1, int c2) {
    asm volatile("{\n.reg .pred P;\nelect.sync _|P, 0xffffffff;\n"
                 "@P cp.async.bulk.tensor.3d.shared::cluster.global.mbarrier::complete_tx::bytes.multicast::cluster"
                 " [%0], [%1, {%3, %4, %5}], [%2], %6;\n}\n"
                 :: "r"(dst), "l"(map), "r"(bar), "r"(c0), "r"(c1), "r"(c2), "h"((uint16_t)3) : "memory");
}
__device__ __forceinline__ void warp_bulk_load(uint32_t dst, const void* src, uint32_t bytes, uint32_t bar) {
    asm volatile("{\n.reg .pred P;\nelect.sync _|P, 0xffffffff;\n"
                 "@P cp.async.bulk.shared::cluster.global.mbarrier::complete_tx::bytes [%0], [%1], %2, [%3];\n}\n"
                 :: "r"(dst), "l"(src), "r"(bytes), "r"(bar) : "memory");
}
__device__ __forceinline__ void warp_tma_store(const CUtensorMap* map, uint32_t src, int c0, int c1, int c2) {
    asm volatile("{\n.reg .pred P;\nelect.sync _|P, 0xffffffff;\n"
                 "@P cp.async.bulk.tensor.3d.global.shared::cta.bulk_group [%0, {%2, %3, %4}], [%1];\n}\n"
                 :: "l"(map), "r"(src), "r"(c0), "r"(c1), "r"(c2) : "memory");
}
__device__ __forceinline__ void warp_bulk_store(void* dst, uint32_t src, uint32_t bytes) {
    asm volatile("{\n.reg .pred P;\nelect.sync _|P, 0xffffffff;\n"
                 "@P cp.async.bulk.global.shared::cta.bulk_group [%0], [%1], %2;\n}\n" :: "l"(dst), "r"(src), "r"(bytes) : "memory");
}
__device__ __forceinline__ void prefetch_l2(const void* src, uint32_t bytes) {
    asm volatile("cp.async.bulk.prefetch.L2.global [%0], %1;" :: "l"(src), "r"(bytes) : "memory");
}
__device__ __forceinline__ void warp_prefetch(const void* src, uint32_t bytes) {
    asm volatile("{\n.reg .pred P;\nelect.sync _|P, 0xffffffff;\n@P cp.async.bulk.prefetch.L2.global [%0], %1;\n}\n" :: "l"(src), "r"(bytes) : "memory");
}
__device__ __forceinline__ void bulk_commit() { asm volatile("cp.async.bulk.commit_group;" ::: "memory"); }
template <int N> __device__ __forceinline__ void bulk_wait_read() { asm volatile("cp.async.bulk.wait_group.read %0;" :: "n"(N) : "memory"); }
template <int N> __device__ __forceinline__ void bulk_wait() { asm volatile("cp.async.bulk.wait_group %0;" :: "n"(N) : "memory"); }
__device__ __forceinline__ void wgmma_fence() { asm volatile("wgmma.fence.sync.aligned;" ::: "memory"); }
__device__ __forceinline__ void wgmma_commit() { asm volatile("wgmma.commit_group.sync.aligned;" ::: "memory"); }
template <int N> __device__ __forceinline__ void wgmma_wait() { asm volatile("wgmma.wait_group.sync.aligned %0;" :: "n"(N) : "memory"); }
template <int N> __device__ __forceinline__ void fence_regs(float (&d)[N]) {
#pragma unroll
    for (int i = 0; i < N; i++) asm volatile("" : "+f"(d[i]) :: "memory");
}
template <int N> __device__ __forceinline__ void fence_regs(uint32_t (&d)[N]) {
#pragma unroll
    for (int i = 0; i < N; i++) asm volatile("" : "+r"(d[i]) :: "memory");
}
template <int N> __device__ __forceinline__ void reg_dec() { asm volatile("setmaxnreg.dec.sync.aligned.u32 %0;" :: "n"(N)); }
template <int N> __device__ __forceinline__ void reg_inc() { asm volatile("setmaxnreg.inc.sync.aligned.u32 %0;" :: "n"(N)); }
__device__ __forceinline__ uint32_t pack_bf16(float lo, float hi) {
    uint32_t r; asm("cvt.rn.bf16x2.f32 %0, %1, %2;" : "=r"(r) : "f"(hi), "f"(lo)); return r;
}
__device__ __forceinline__ void stmatrix_x4(uint32_t addr, uint32_t r0, uint32_t r1, uint32_t r2, uint32_t r3) {
    asm volatile("stmatrix.sync.aligned.m8n8.x4.shared.b16 [%0], {%1, %2, %3, %4};"
                 :: "r"(addr), "r"(r0), "r"(r1), "r"(r2), "r"(r3) : "memory");
}
__device__ __forceinline__ float ex2(float x) { float y; asm("ex2.approx.ftz.f32 %0, %1;" : "=f"(y) : "f"(x)); return y; }

constexpr uint32_t DESC_HI = (1024 >> 4) | (1u << 30);
__device__ __forceinline__ uint32_t make_desc(uint32_t addr, uint32_t lbo) {
    uint32_t lo = ((addr & 0x3FFFF) >> 4) | ((lbo >> 4) << 16);
    asm volatile("" : "+r"(lo));
    return lo;
}
__device__ __forceinline__ uint64_t full_desc(uint32_t lo) {
    uint64_t d; asm("mov.b64 %0, {%1, %2};" : "=l"(d) : "r"(lo), "r"(DESC_HI)); return d;
}

__device__ __forceinline__ void wgmma_ss_n256_tb_init(float (&d)[128], uint64_t da, uint64_t db) {
    asm volatile("{\n.reg .pred p;\n"
        "setp.ne.b32 p, 0, 0;\n"
        "wgmma.mma_async.sync.aligned.m64n256k16.f32.bf16.bf16 "
        "{%0, %1, %2, %3, %4, %5, %6, %7, %8, %9, %10, %11, %12, %13, %14, %15, %16, %17, %18, %19, %20, "
        "%21, %22, %23, %24, %25, %26, %27, %28, %29, %30, %31, %32, %33, %34, %35, %36, %37, %38, %39, %40, "
        "%41, %42, %43, %44, %45, %46, %47, %48, %49, %50, %51, %52, %53, %54, %55, %56, %57, %58, %59, %60, "
        "%61, %62, %63, %64, %65, %66, %67, %68, %69, %70, %71, %72, %73, %74, %75, %76, %77, %78, %79, %80, "
        "%81, %82, %83, %84, %85, %86, %87, %88, %89, %90, %91, %92, %93, %94, %95, %96, %97, %98, %99, "
        "%100, %101, %102, %103, %104, %105, %106, %107, %108, %109, %110, %111, %112, %113, %114, %115, "
        "%116, %117, %118, %119, %120, %121, %122, %123, %124, %125, %126, %127},"
        " %128, %129, p, 1, 1, 0, 1;\n}\n"
        : "=f"(d[0]), "=f"(d[1]), "=f"(d[2]), "=f"(d[3]), "=f"(d[4]), "=f"(d[5]), "=f"(d[6]), "=f"(d[7]),
        "=f"(d[8]), "=f"(d[9]), "=f"(d[10]), "=f"(d[11]), "=f"(d[12]), "=f"(d[13]), "=f"(d[14]), "=f"(d[15]),
        "=f"(d[16]), "=f"(d[17]), "=f"(d[18]), "=f"(d[19]), "=f"(d[20]), "=f"(d[21]), "=f"(d[22]),
        "=f"(d[23]), "=f"(d[24]), "=f"(d[25]), "=f"(d[26]), "=f"(d[27]), "=f"(d[28]), "=f"(d[29]),
        "=f"(d[30]), "=f"(d[31]), "=f"(d[32]), "=f"(d[33]), "=f"(d[34]), "=f"(d[35]), "=f"(d[36]),
        "=f"(d[37]), "=f"(d[38]), "=f"(d[39]), "=f"(d[40]), "=f"(d[41]), "=f"(d[42]), "=f"(d[43]),
        "=f"(d[44]), "=f"(d[45]), "=f"(d[46]), "=f"(d[47]), "=f"(d[48]), "=f"(d[49]), "=f"(d[50]),
        "=f"(d[51]), "=f"(d[52]), "=f"(d[53]), "=f"(d[54]), "=f"(d[55]), "=f"(d[56]), "=f"(d[57]),
        "=f"(d[58]), "=f"(d[59]), "=f"(d[60]), "=f"(d[61]), "=f"(d[62]), "=f"(d[63]), "=f"(d[64]),
        "=f"(d[65]), "=f"(d[66]), "=f"(d[67]), "=f"(d[68]), "=f"(d[69]), "=f"(d[70]), "=f"(d[71]),
        "=f"(d[72]), "=f"(d[73]), "=f"(d[74]), "=f"(d[75]), "=f"(d[76]), "=f"(d[77]), "=f"(d[78]),
        "=f"(d[79]), "=f"(d[80]), "=f"(d[81]), "=f"(d[82]), "=f"(d[83]), "=f"(d[84]), "=f"(d[85]),
        "=f"(d[86]), "=f"(d[87]), "=f"(d[88]), "=f"(d[89]), "=f"(d[90]), "=f"(d[91]), "=f"(d[92]),
        "=f"(d[93]), "=f"(d[94]), "=f"(d[95]), "=f"(d[96]), "=f"(d[97]), "=f"(d[98]), "=f"(d[99]),
        "=f"(d[100]), "=f"(d[101]), "=f"(d[102]), "=f"(d[103]), "=f"(d[104]), "=f"(d[105]), "=f"(d[106]),
        "=f"(d[107]), "=f"(d[108]), "=f"(d[109]), "=f"(d[110]), "=f"(d[111]), "=f"(d[112]), "=f"(d[113]),
        "=f"(d[114]), "=f"(d[115]), "=f"(d[116]), "=f"(d[117]), "=f"(d[118]), "=f"(d[119]), "=f"(d[120]),
        "=f"(d[121]), "=f"(d[122]), "=f"(d[123]), "=f"(d[124]), "=f"(d[125]), "=f"(d[126]), "=f"(d[127])
        : "l"(da), "l"(db));
}
__device__ __forceinline__ void wgmma_ss_n256_tb(float (&d)[128], uint64_t da, uint64_t db, int scale_d) {
    asm volatile("{\n.reg .pred p;\n"
        "setp.ne.b32 p, %130, 0;\n"
        "wgmma.mma_async.sync.aligned.m64n256k16.f32.bf16.bf16 "
        "{%0, %1, %2, %3, %4, %5, %6, %7, %8, %9, %10, %11, %12, %13, %14, %15, %16, %17, %18, %19, %20, "
        "%21, %22, %23, %24, %25, %26, %27, %28, %29, %30, %31, %32, %33, %34, %35, %36, %37, %38, %39, %40, "
        "%41, %42, %43, %44, %45, %46, %47, %48, %49, %50, %51, %52, %53, %54, %55, %56, %57, %58, %59, %60, "
        "%61, %62, %63, %64, %65, %66, %67, %68, %69, %70, %71, %72, %73, %74, %75, %76, %77, %78, %79, %80, "
        "%81, %82, %83, %84, %85, %86, %87, %88, %89, %90, %91, %92, %93, %94, %95, %96, %97, %98, %99, "
        "%100, %101, %102, %103, %104, %105, %106, %107, %108, %109, %110, %111, %112, %113, %114, %115, "
        "%116, %117, %118, %119, %120, %121, %122, %123, %124, %125, %126, %127},"
        " %128, %129, p, 1, 1, 0, 1;\n}\n"
        : "+f"(d[0]), "+f"(d[1]), "+f"(d[2]), "+f"(d[3]), "+f"(d[4]), "+f"(d[5]), "+f"(d[6]), "+f"(d[7]),
        "+f"(d[8]), "+f"(d[9]), "+f"(d[10]), "+f"(d[11]), "+f"(d[12]), "+f"(d[13]), "+f"(d[14]), "+f"(d[15]),
        "+f"(d[16]), "+f"(d[17]), "+f"(d[18]), "+f"(d[19]), "+f"(d[20]), "+f"(d[21]), "+f"(d[22]),
        "+f"(d[23]), "+f"(d[24]), "+f"(d[25]), "+f"(d[26]), "+f"(d[27]), "+f"(d[28]), "+f"(d[29]),
        "+f"(d[30]), "+f"(d[31]), "+f"(d[32]), "+f"(d[33]), "+f"(d[34]), "+f"(d[35]), "+f"(d[36]),
        "+f"(d[37]), "+f"(d[38]), "+f"(d[39]), "+f"(d[40]), "+f"(d[41]), "+f"(d[42]), "+f"(d[43]),
        "+f"(d[44]), "+f"(d[45]), "+f"(d[46]), "+f"(d[47]), "+f"(d[48]), "+f"(d[49]), "+f"(d[50]),
        "+f"(d[51]), "+f"(d[52]), "+f"(d[53]), "+f"(d[54]), "+f"(d[55]), "+f"(d[56]), "+f"(d[57]),
        "+f"(d[58]), "+f"(d[59]), "+f"(d[60]), "+f"(d[61]), "+f"(d[62]), "+f"(d[63]), "+f"(d[64]),
        "+f"(d[65]), "+f"(d[66]), "+f"(d[67]), "+f"(d[68]), "+f"(d[69]), "+f"(d[70]), "+f"(d[71]),
        "+f"(d[72]), "+f"(d[73]), "+f"(d[74]), "+f"(d[75]), "+f"(d[76]), "+f"(d[77]), "+f"(d[78]),
        "+f"(d[79]), "+f"(d[80]), "+f"(d[81]), "+f"(d[82]), "+f"(d[83]), "+f"(d[84]), "+f"(d[85]),
        "+f"(d[86]), "+f"(d[87]), "+f"(d[88]), "+f"(d[89]), "+f"(d[90]), "+f"(d[91]), "+f"(d[92]),
        "+f"(d[93]), "+f"(d[94]), "+f"(d[95]), "+f"(d[96]), "+f"(d[97]), "+f"(d[98]), "+f"(d[99]),
        "+f"(d[100]), "+f"(d[101]), "+f"(d[102]), "+f"(d[103]), "+f"(d[104]), "+f"(d[105]), "+f"(d[106]),
        "+f"(d[107]), "+f"(d[108]), "+f"(d[109]), "+f"(d[110]), "+f"(d[111]), "+f"(d[112]), "+f"(d[113]),
        "+f"(d[114]), "+f"(d[115]), "+f"(d[116]), "+f"(d[117]), "+f"(d[118]), "+f"(d[119]), "+f"(d[120]),
        "+f"(d[121]), "+f"(d[122]), "+f"(d[123]), "+f"(d[124]), "+f"(d[125]), "+f"(d[126]), "+f"(d[127])
        : "l"(da), "l"(db), "r"(scale_d));
}
__device__ __forceinline__ void wgmma_ss_n128(float (&d)[64], uint64_t da, uint64_t db, int scale_d) {
    asm volatile("{\n.reg .pred p;\n"
        "setp.ne.b32 p, %66, 0;\n"
        "wgmma.mma_async.sync.aligned.m64n128k16.f32.bf16.bf16 "
        "{%0, %1, %2, %3, %4, %5, %6, %7, %8, %9, %10, %11, %12, %13, %14, %15, %16, %17, %18, %19, %20, "
        "%21, %22, %23, %24, %25, %26, %27, %28, %29, %30, %31, %32, %33, %34, %35, %36, %37, %38, %39, %40, "
        "%41, %42, %43, %44, %45, %46, %47, %48, %49, %50, %51, %52, %53, %54, %55, %56, %57, %58, %59, %60, "
        "%61, %62, %63},"
        " %64, %65, p, 1, 1, 0, 0;\n}\n"
        : "+f"(d[0]), "+f"(d[1]), "+f"(d[2]), "+f"(d[3]), "+f"(d[4]), "+f"(d[5]), "+f"(d[6]), "+f"(d[7]),
        "+f"(d[8]), "+f"(d[9]), "+f"(d[10]), "+f"(d[11]), "+f"(d[12]), "+f"(d[13]), "+f"(d[14]), "+f"(d[15]),
        "+f"(d[16]), "+f"(d[17]), "+f"(d[18]), "+f"(d[19]), "+f"(d[20]), "+f"(d[21]), "+f"(d[22]),
        "+f"(d[23]), "+f"(d[24]), "+f"(d[25]), "+f"(d[26]), "+f"(d[27]), "+f"(d[28]), "+f"(d[29]),
        "+f"(d[30]), "+f"(d[31]), "+f"(d[32]), "+f"(d[33]), "+f"(d[34]), "+f"(d[35]), "+f"(d[36]),
        "+f"(d[37]), "+f"(d[38]), "+f"(d[39]), "+f"(d[40]), "+f"(d[41]), "+f"(d[42]), "+f"(d[43]),
        "+f"(d[44]), "+f"(d[45]), "+f"(d[46]), "+f"(d[47]), "+f"(d[48]), "+f"(d[49]), "+f"(d[50]),
        "+f"(d[51]), "+f"(d[52]), "+f"(d[53]), "+f"(d[54]), "+f"(d[55]), "+f"(d[56]), "+f"(d[57]),
        "+f"(d[58]), "+f"(d[59]), "+f"(d[60]), "+f"(d[61]), "+f"(d[62]), "+f"(d[63])
        : "l"(da), "l"(db), "r"(scale_d));
}
__device__ __forceinline__ void wgmma_rs_n128_tb(float (&d)[64], uint32_t a0, uint32_t a1, uint32_t a2, uint32_t a3, uint64_t db, int scale_d) {
    asm volatile("{\n.reg .pred p;\n"
        "setp.ne.b32 p, %69, 0;\n"
        "wgmma.mma_async.sync.aligned.m64n128k16.f32.bf16.bf16 "
        "{%0, %1, %2, %3, %4, %5, %6, %7, %8, %9, %10, %11, %12, %13, %14, %15, %16, %17, %18, %19, %20, "
        "%21, %22, %23, %24, %25, %26, %27, %28, %29, %30, %31, %32, %33, %34, %35, %36, %37, %38, %39, %40, "
        "%41, %42, %43, %44, %45, %46, %47, %48, %49, %50, %51, %52, %53, %54, %55, %56, %57, %58, %59, %60, "
        "%61, %62, %63},"
        " {%64, %65, %66, %67}, %68, p, 1, 1, 1;\n}\n"
        : "+f"(d[0]), "+f"(d[1]), "+f"(d[2]), "+f"(d[3]), "+f"(d[4]), "+f"(d[5]), "+f"(d[6]), "+f"(d[7]),
        "+f"(d[8]), "+f"(d[9]), "+f"(d[10]), "+f"(d[11]), "+f"(d[12]), "+f"(d[13]), "+f"(d[14]), "+f"(d[15]),
        "+f"(d[16]), "+f"(d[17]), "+f"(d[18]), "+f"(d[19]), "+f"(d[20]), "+f"(d[21]), "+f"(d[22]),
        "+f"(d[23]), "+f"(d[24]), "+f"(d[25]), "+f"(d[26]), "+f"(d[27]), "+f"(d[28]), "+f"(d[29]),
        "+f"(d[30]), "+f"(d[31]), "+f"(d[32]), "+f"(d[33]), "+f"(d[34]), "+f"(d[35]), "+f"(d[36]),
        "+f"(d[37]), "+f"(d[38]), "+f"(d[39]), "+f"(d[40]), "+f"(d[41]), "+f"(d[42]), "+f"(d[43]),
        "+f"(d[44]), "+f"(d[45]), "+f"(d[46]), "+f"(d[47]), "+f"(d[48]), "+f"(d[49]), "+f"(d[50]),
        "+f"(d[51]), "+f"(d[52]), "+f"(d[53]), "+f"(d[54]), "+f"(d[55]), "+f"(d[56]), "+f"(d[57]),
        "+f"(d[58]), "+f"(d[59]), "+f"(d[60]), "+f"(d[61]), "+f"(d[62]), "+f"(d[63])
        : "r"(a0), "r"(a1), "r"(a2), "r"(a3), "l"(db), "r"(scale_d));
}
__device__ __forceinline__ void wgmma_ss_n128_lo_tb(float (&d)[128], uint64_t da, uint64_t db, int scale_d) {
    asm volatile("{\n.reg .pred p;\n"
        "setp.ne.b32 p, %66, 0;\n"
        "wgmma.mma_async.sync.aligned.m64n128k16.f32.bf16.bf16 "
        "{%0, %1, %2, %3, %4, %5, %6, %7, %8, %9, %10, %11, %12, %13, %14, %15, %16, %17, %18, %19, %20, "
        "%21, %22, %23, %24, %25, %26, %27, %28, %29, %30, %31, %32, %33, %34, %35, %36, %37, %38, %39, %40, "
        "%41, %42, %43, %44, %45, %46, %47, %48, %49, %50, %51, %52, %53, %54, %55, %56, %57, %58, %59, %60, "
        "%61, %62, %63},"
        " %64, %65, p, 1, 1, 0, 1;\n}\n"
        : "+f"(d[0]), "+f"(d[1]), "+f"(d[2]), "+f"(d[3]), "+f"(d[4]), "+f"(d[5]), "+f"(d[6]), "+f"(d[7]),
        "+f"(d[8]), "+f"(d[9]), "+f"(d[10]), "+f"(d[11]), "+f"(d[12]), "+f"(d[13]), "+f"(d[14]), "+f"(d[15]),
        "+f"(d[16]), "+f"(d[17]), "+f"(d[18]), "+f"(d[19]), "+f"(d[20]), "+f"(d[21]), "+f"(d[22]),
        "+f"(d[23]), "+f"(d[24]), "+f"(d[25]), "+f"(d[26]), "+f"(d[27]), "+f"(d[28]), "+f"(d[29]),
        "+f"(d[30]), "+f"(d[31]), "+f"(d[32]), "+f"(d[33]), "+f"(d[34]), "+f"(d[35]), "+f"(d[36]),
        "+f"(d[37]), "+f"(d[38]), "+f"(d[39]), "+f"(d[40]), "+f"(d[41]), "+f"(d[42]), "+f"(d[43]),
        "+f"(d[44]), "+f"(d[45]), "+f"(d[46]), "+f"(d[47]), "+f"(d[48]), "+f"(d[49]), "+f"(d[50]),
        "+f"(d[51]), "+f"(d[52]), "+f"(d[53]), "+f"(d[54]), "+f"(d[55]), "+f"(d[56]), "+f"(d[57]),
        "+f"(d[58]), "+f"(d[59]), "+f"(d[60]), "+f"(d[61]), "+f"(d[62]), "+f"(d[63])
        : "l"(da), "l"(db), "r"(scale_d));
}

enum { M_X = 0, M_C, M_WQ, M_WQKV, M_WUK, M_WUV, M_WO, M_WOB, M_SCR_LD, M_SCR_LOC, M_SCR_LOQ, M_SCR_ST, M_COUNT };
enum { T_Q = 0, T_K, T_V, T_B, T_OUT, T_LOCAL, T_ATTN, T_END };
constexpr int NCTA = 132, NPAIR = NCTA / 2;
constexpr int NITEMS = 480 + 64 + 256;
#define NTRI 3
constexpr int TRIPLES = NTRI, WIDE = 80 - 3 * TRIPLES;
struct Params {
    CUtensorMap m[M_COUNT];
    const __nv_bfloat16* x;
    const __nv_bfloat16* gate_w;
    const char* wo;
    const char* wob;
    __nv_bfloat16* out;
    uint32_t zero;
    uint16_t items[NITEMS];
    uint8_t ostep[80];
};
__device__ __forceinline__ int item_type(int it) { return it >> 13; }
__device__ __forceinline__ int item_row(int it) { return it & 15; }
__device__ __forceinline__ int item_col(int it) { return (it >> 4) & 31; }
__device__ __forceinline__ int item_asc(int it) { return (it >> 9) & 1; }
constexpr int ITEM_READY = 1 << 10;

struct __align__(128) Sync {
    unsigned long long count[4];
    __align__(128) unsigned long long ctx[16];
    unsigned next, next_out, done;
    __align__(128) unsigned step[32][2];
    unsigned split[32];
};
__device__ Sync g_sync;
__device__ uint4 g_part[128][8][256];

constexpr uint32_t GST_BYTES = 49152, SM_KV = 65536, SM_STAGING = 196608, SM_BARS = SM_STAGING + 32768;
constexpr uint32_t B_GFULL = 0, B_GEMPTY = 32, B_AFULL = 64, B_AEMPTY = 112, B_SFULL = 160, B_SEMPTY = 192,
                   B_IFULL = 224, B_IEMPTY = 288, B_XFREE = 352, B_WANT = 384, B_HALF = 416,
                   SM_ORDY = 448, SM_QUEUE = 456, B_ALT = 488, B_QFREE = 504, SM_GATE = 512, SM_TOTAL = SM_BARS + 1536;
constexpr int QDEPTH = 8;
#define PF_NAR 20
#define SPREAD 4
#define PACE 0
#define PF_LOC 0
#define KMEET 14
constexpr int K_MEET = KMEET, K_SPLIT = KMEET + 12;
#define KF2 3
constexpr uint32_t LOC_PLANE = 72 * 128;
constexpr float SM_SCALE = 0.08838834764831845f * 1.4426950408889634f;
constexpr float LOC_SCALE = 0.17677669529663687f * 1.4426950408889634f;
constexpr float SUM_LIMIT = 1152921504606846976.f;
constexpr float REF_RANGE = 32.f;

__device__ __forceinline__ unsigned ld_acquire(const unsigned* p) {
    unsigned v; asm volatile("ld.acquire.gpu.global.u32 %0, [%1];" : "=r"(v) : "l"(p) : "memory"); return v;
}
__device__ __forceinline__ unsigned long long ld_acquire(const unsigned long long* p) {
    unsigned long long v; asm volatile("ld.acquire.gpu.global.u64 %0, [%1];" : "=l"(v) : "l"(p) : "memory"); return v;
}
__device__ __forceinline__ void st_b128(void* p, uint32_t a, uint32_t b, uint32_t c, uint32_t d) {
    asm volatile("{\n.reg .b128 v;\n.reg .b64 lo, hi;\nmov.b64 lo, {%1, %2};\nmov.b64 hi, {%3, %4};\nmov.b128 v, {lo, hi};\n"
                 "st.relaxed.gpu.global.b128 [%0], v;\n}\n" :: "l"(p), "r"(a), "r"(b), "r"(c), "r"(d) : "memory");
}
__device__ __forceinline__ void ld_b128(const void* p, uint32_t& a, uint32_t& b, uint32_t& c, uint32_t& d) {
    asm volatile("{\n.reg .b128 v;\n.reg .b64 lo, hi;\nld.relaxed.gpu.global.b128 v, [%4];\nmov.b128 {lo, hi}, v;\n"
                 "mov.b64 {%0, %1}, lo;\nmov.b64 {%2, %3}, hi;\n}\n" : "=r"(a), "=r"(b), "=r"(c), "=r"(d) : "l"(p) : "memory");
}
__device__ __forceinline__ void spin_guard(unsigned& n) {
    asm volatile("{\n.reg .pred P;\nadd.u32 %0, %0, 1;\nsetp.gt.u32 P, %0, 16777216;\n@P trap;\n}\n" : "+r"(n));
    if (n > 1) __nanosleep(100);
}
__device__ __forceinline__ void red_add(unsigned long long* p, unsigned long long v) {
    asm volatile("red.release.gpu.global.add.u64 [%0], %1;" :: "l"(p), "l"(v) : "memory");
}
__device__ __forceinline__ float rcp(float x) { float y; asm("rcp.approx.ftz.f32 %0, %1;" : "=f"(y) : "f"(x)); return y; }
__device__ __forceinline__ float lds_f32(uint32_t addr) {
    float v; asm volatile("ld.shared.f32 %0, [%1];" : "=f"(v) : "r"(addr) : "memory"); return v;
}
__device__ __forceinline__ void ldsm_x4(uint32_t (&r)[4], uint32_t addr) {
    asm volatile("ldmatrix.sync.aligned.m8n8.x4.shared.b16 {%0, %1, %2, %3}, [%4];"
                 : "=r"(r[0]), "=r"(r[1]), "=r"(r[2]), "=r"(r[3]) : "r"(addr) : "memory");
}
__device__ __forceinline__ void ldsm_x4_t(uint32_t (&r)[4], uint32_t addr) {
    asm volatile("ldmatrix.sync.aligned.m8n8.x4.trans.shared.b16 {%0, %1, %2, %3}, [%4];"
                 : "=r"(r[0]), "=r"(r[1]), "=r"(r[2]), "=r"(r[3]) : "r"(addr) : "memory");
}
__device__ __forceinline__ void mma_k16(float (&d)[4], const uint32_t (&a)[4], uint32_t b0, uint32_t b1) {
    asm("mma.sync.aligned.m16n8k16.row.col.f32.bf16.bf16.f32 {%0,%1,%2,%3}, {%4,%5,%6,%7}, {%8,%9}, {%0,%1,%2,%3};"
        : "+f"(d[0]), "+f"(d[1]), "+f"(d[2]), "+f"(d[3]) : "r"(a[0]), "r"(a[1]), "r"(a[2]), "r"(a[3]), "r"(b0), "r"(b1));
}
__device__ __forceinline__ void mma_k16_init(float (&d)[4], const uint32_t (&a)[4], uint32_t b0, uint32_t b1) {
    asm("{\n.reg .f32 z;\nmov.f32 z, 0f00000000;\n"
        "mma.sync.aligned.m16n8k16.row.col.f32.bf16.bf16.f32 {%0,%1,%2,%3}, {%4,%5,%6,%7}, {%8,%9}, {z,z,z,z};\n}\n"
        : "=f"(d[0]), "=f"(d[1]), "=f"(d[2]), "=f"(d[3]) : "r"(a[0]), "r"(a[1]), "r"(a[2]), "r"(a[3]), "r"(b0), "r"(b1));
}
__device__ __forceinline__ void mma_k8(float (&d)[4], uint32_t a0, uint32_t a1, uint32_t b0) {
    asm("mma.sync.aligned.m16n8k8.row.col.f32.bf16.bf16.f32 {%0,%1,%2,%3}, {%4,%5}, {%6}, {%0,%1,%2,%3};"
        : "+f"(d[0]), "+f"(d[1]), "+f"(d[2]), "+f"(d[3]) : "r"(a0), "r"(a1), "r"(b0));
}
template <typename T, int N> __device__ __forceinline__ void zero_regs(T (&d)[N]) {
#pragma unroll
    for (int i = 0; i < N; i++) d[i] = 0;
}
__device__ __forceinline__ float quad_max(float v) {
    v = fmaxf(v, __shfl_xor_sync(0xffffffffu, v, 1));
    return fmaxf(v, __shfl_xor_sync(0xffffffffu, v, 2));
}
__device__ __forceinline__ float quad_sum(float v) {
    v += __shfl_xor_sync(0xffffffffu, v, 1);
    return v + __shfl_xor_sync(0xffffffffu, v, 2);
}

__device__ __forceinline__ void qk_gemm(float (&s)[64], uint32_t q_lo, uint32_t k_lo) {
    const uint64_t dq = full_desc(q_lo), dk = full_desc(k_lo);
    fence_regs(s);
    wgmma_fence();
#pragma unroll
    for (int kk = 0; kk < 8; kk++) {
        const uint32_t o = (kk >> 2) * 1024 + (kk & 3) * 2;
        wgmma_ss_n128(s, dq + o, dk + o, kk != 0);
    }
    wgmma_commit();
}
__device__ __forceinline__ void pv_gemm(float (&o)[64], uint32_t (&p)[32], uint32_t v_lo, int accumulate) {
    const uint64_t dv = full_desc(v_lo);
    fence_regs(o);
    fence_regs(p);
    wgmma_fence();
#pragma unroll
    for (int kk = 0; kk < 8; kk++)
        wgmma_rs_n128_tb(o, p[4 * kk], p[4 * kk + 1], p[4 * kk + 2], p[4 * kk + 3], dv + kk * 128, kk != 0 || accumulate);
    wgmma_commit();
}
__device__ __forceinline__ void row_max(const float (&s)[64], float& x0, float& x1) {
    float z0 = fmaxf(s[0], s[1]), z1 = fmaxf(s[2], s[3]);
    x0 = fmaxf(s[4], s[5]); x1 = fmaxf(s[6], s[7]);
#pragma unroll
    for (int j = 2; j < 16; j += 2) {
        z0 = fmaxf(z0, fmaxf(s[4 * j], s[4 * j + 1]));
        z1 = fmaxf(z1, fmaxf(s[4 * j + 2], s[4 * j + 3]));
        x0 = fmaxf(x0, fmaxf(s[4 * j + 4], s[4 * j + 5]));
        x1 = fmaxf(x1, fmaxf(s[4 * j + 6], s[4 * j + 7]));
    }
    x0 = quad_max(fmaxf(x0, z0)); x1 = quad_max(fmaxf(x1, z1));
}
__device__ __forceinline__ void exp_pack(uint32_t (&p)[32], const float (&s)[64], float& r0, float& r1) {
#pragma unroll
    for (int j = 0; j < 16; j++) {
        const float e0 = ex2(s[4 * j]), e1 = ex2(s[4 * j + 1]), e2 = ex2(s[4 * j + 2]), e3 = ex2(s[4 * j + 3]);
        if (j == 0) { r0 = e0 + e1; r1 = e2 + e3; }
        else { r0 += e0 + e1; r1 += e2 + e3; }
        p[2 * j] = pack_bf16(e0, e1);
        p[2 * j + 1] = pack_bf16(e2, e3);
    }
}
__device__ __forceinline__ void shift_rows(float (&s)[64], float d0, float d1) {
#pragma unroll
    for (int j = 0; j < 16; j++) { s[4 * j] -= d0; s[4 * j + 1] -= d0; s[4 * j + 2] -= d1; s[4 * j + 3] -= d1; }
}
constexpr float MASKED = -3e38f;
template <int J0>
__device__ __forceinline__ void mask_triangle(float (&s)[64], float thr) {
#pragma unroll
    for (int j = 0; j < 16; j++) {
        const float m = __saturatef((float)(8 * (j >> 1) + (j & 1)) - thr);
        const int i = 4 * (J0 + (j >> 1)) + (j & 1);
        s[i] = fmaf(m, MASKED, s[i]);
        if (j < 14) s[i + 6] = fmaf(m, MASKED, s[i + 6]);
    }
}
__device__ __forceinline__ void causal_mask(float (&s)[64], float thr, int wg) {
    asm volatile("" : "+f"(thr));
    if (wg == 0) {
        mask_triangle<0>(s, thr);
#pragma unroll
        for (int j = 32; j < 64; j++) s[j] += MASKED;
    } else {
        mask_triangle<8>(s, thr);
    }
}

__global__ void __cluster_dims__(2, 1, 1) __launch_bounds__(384, 1) fused_kernel(const __grid_constant__ Params prm) {
    extern __shared__ __align__(1024) uint8_t smem[];
    const uint32_t sb = smem_u32(smem), bars = sb + SM_BARS;
    const int warp = __shfl_sync(0xffffffffu, threadIdx.x >> 5, 0), lane = threadIdx.x & 31;

    const uint32_t rank = cluster_rank();
    const uint32_t bars0 = map_cta(bars, 0), bars_peer = map_cta(bars, rank ^ 1);

    auto first_item = [&]() -> int {
        uint32_t pair = blockIdx.x >> 1;
        asm volatile("" : "+r"(pair));
        return prm.items[pair] + item_row(prm.items[pair]) + rank;
    };
    if (threadIdx.x == 256) {
        for (int k = 0; k < 4; k++) mbar_init(bars + B_GFULL + 8 * k, 1);
        asm volatile("fence.mbarrier_init.release.cluster;" ::: "memory");
        fence_proxy_async_smem();
    }
    if (threadIdx.x == 128) {
        for (int i = 0; i < 4; i++) { mbar_init(bars + B_GEMPTY + 8 * i, 16); mbar_init(bars + B_XFREE + 8 * i, 1); }
        for (int i = 0; i < 6; i++) { mbar_init(bars + B_AFULL + 8 * i, 1); mbar_init(bars + B_AEMPTY + 8 * i, i < 2 ? 8 : 16); }
        for (int i = 0; i < 4; i++) { mbar_init(bars + B_SFULL + 8 * i, 4); mbar_init(bars + B_SEMPTY + 8 * i, 1); }
        for (int i = 0; i < QDEPTH; i++) { mbar_init(bars + B_IFULL + 8 * i, 1); mbar_init(bars + B_IEMPTY + 8 * i, 23); }
        mbar_init(bars + B_WANT, 2);
        for (int i = 0; i < 4; i++) mbar_init(bars + B_HALF + 8 * i, 1);
        mbar_init(bars + B_ALT, 4); mbar_init(bars + B_ALT + 8, 4); mbar_init(bars + B_QFREE, 2);
        asm volatile("st.shared.u64 [%0], 0;" :: "r"(bars + SM_ORDY) : "memory");
        asm volatile("fence.mbarrier_init.release.cluster;\nfence.acq_rel.cta;" ::: "memory");
    }
    __syncwarp();
    asm volatile("barrier.cluster.arrive.relaxed.aligned;" ::: "memory");
    if (threadIdx.x == 256) {
        const int first_it = first_item();
        for (int k = 0; k < 4; k++) {
            const uint32_t dst = sb + k * GST_BYTES, fb = bars + B_GFULL + 8 * k;
            mbar_expect_tx(fb, GST_BYTES);
            tma_load_3d(dst, &prm.m[M_X], fb, k * 64, item_row(first_it) * 128, 0);
            tma_load_3d(dst + 16384, &prm.m[M_WQKV], fb, 0, k * 64, item_col(first_it) * 4);
            tma_load_3d(dst + 32768, &prm.m[M_WQKV], fb, 0, k * 64, item_col(first_it) * 4 + 2);
        }
    }
    __syncwarp();
    asm volatile("barrier.cluster.wait.acquire.aligned;" ::: "memory");

    uint32_t qn = 0;
    auto next_item = [&](bool releaser, bool bounded = true) -> int {
        const uint32_t slot = qn % QDEPTH;
        if (bounded) mbar_wait(bars + B_IFULL + 8 * slot, (qn / QDEPTH) & 1);
        else mbar_spin(bars + B_IFULL + 8 * slot, (qn / QDEPTH) & 1);
        uint32_t it;
        asm volatile("ld.shared.u32 %0, [%1];" : "=r"(it) : "r"(bars + SM_QUEUE + 4 * slot) : "memory");
        mbar_arrive_cluster_if(releaser, bars0 + B_IEMPTY + 8 * slot);
        qn++;
        return it;
    };

    if (warp < 4) {
        reg_dec<40>();
        if (warp == 0) {
            {
                uint32_t gph = 0;
                const uint32_t prank = __shfl_sync(0xffffffffu, rank, 0);
                int k0 = 4;
                uint32_t kv = 0, kvph = 1;
                uint32_t qc = 0;
                uint32_t oneed = 0;
                uint32_t xph = 0;
                uint32_t need_g = 0, need_a = 0;
                auto a_parity = [&](uint32_t b) { return b < 2 ? (((qc + 1 - b) >> 1) & 1) ^ 1 : kvph ^ (b - 2 < kv); };
                int held_type = T_END;
                uint32_t borrowed = 0, fph = 0;
                auto reclaim_q = [&]() { if (borrowed) { mbar_wait(bars + B_QFREE, fph); fph ^= 1; borrowed = 0; } };
                auto acquire_g = [&](uint32_t st, bool shared) {
                    mbar_wait(bars + B_GEMPTY + 8 * st, gph);
                    if (need_a) {
                        reclaim_q();
                        const uint32_t b = (3 * st) >> 1;
                        mbar_wait(bars + B_AEMPTY + 8 * b, a_parity(b));
                        mbar_wait(bars + B_AEMPTY + 8 * (b + 1), a_parity(b + 1));
                        if (shared) {
                            mbar_arrive_cluster_if(lane == 0, bars_peer + B_XFREE + 8 * st);
                            mbar_wait(bars + B_XFREE + 8 * st, xph);
                        }
                        if (st == 3) { need_a = 0; xph ^= shared; }
                    }
                };
                auto leave_gemm = [&](uint32_t b) {
                    if (need_g >> b & 1) {
                        mbar_wait(bars + B_GEMPTY + 8 * ((2 * b) / 3), gph);
                        mbar_wait(bars + B_GEMPTY + 8 * ((2 * b + 1) / 3), gph);
                        need_g &= ~(1u << b);
                    }
                };
                const CUtensorMap* tile_map = &prm.m[M_SCR_LD];
                asm volatile("" : "+l"(tile_map));
                auto load_q = [&](int grp, int row) {
                    const uint32_t b = qc & 1, dst = sb + b * 32768, fb = bars + B_AFULL + 8 * b;
                    mbar_wait(bars + B_AEMPTY + 8 * b, a_parity(b));
                    leave_gemm(b);
                    reclaim_q();
                    borrowed = held_type != T_END;
                    held_type = T_END;
                    warp_expect_tx(fb, 32768 + 512);
                    warp_tma_load(dst, tile_map, fb, 0, row, grp);
                    warp_tma_load(dst + 16384, tile_map, fb, 64, row, grp);
                    warp_bulk_load(bars + SM_GATE + b * 512, &g_gate[row], 512, fb);
                    qc++;
                };
                auto load_kv = [&](int grp, int row, bool shared) {
                    uint32_t fb = bars + B_AFULL + 16 + 8 * kv, mine = sb + SM_KV + kv * 32768 + prank * 16384;
                    int c_mine = prank * 64;
                    asm volatile("" : "+r"(mine), "+r"(fb), "+r"(row), "+r"(grp), "+r"(c_mine));
                    if (need_g) leave_gemm(2 + kv);
                    mbar_wait(fb + B_AEMPTY - B_AFULL, kvph);
                    warp_expect_tx(fb, grp < 0 ? 0 : 32768);
                    if (shared) {
                        warp_tma_load_pair(mine, tile_map, fb, c_mine, row, grp);
                    } else if (grp >= 0) {
                        warp_tma_load(mine, tile_map, fb, c_mine, row, grp);
                        warp_tma_load(mine + 16384 - prank * 32768, tile_map, fb, 64 - c_mine, row, grp);
                    } else {
                        mbar_arrive_cluster_n_if(lane < 2, map_cta(fb, lane & 1) + B_AEMPTY - B_AFULL, 8);
                    }
                    if (++kv == 4) { kv = 0; kvph ^= 1; }
                };
                auto request = [&]() { mbar_arrive_cluster_if(lane == 0, bars0 + B_WANT); };
                int pv_grp = -1, pv_row = 0;
                bool pv_shared = false, peer_longer = false;
                auto inputs_seen = [&](uint32_t word, unsigned& n) -> uint32_t {
                    uint32_t v;
                    spin_guard(n);
                    asm volatile("ld.acquire.cta.shared.u32 %0, [%1];" : "=r"(v) : "r"(bars + SM_ORDY + 4 * word) : "memory");
                    return __shfl_sync(0xffffffffu, v, 0);
                };
                auto fetch = [&]() -> int {
                    const int nx = __shfl_sync(0xffffffffu, next_item(lane == 0), 0);
                    if ((item_type(nx) == T_ATTN || item_type(nx) == T_LOCAL) && !(nx & ITEM_READY)) {
                        oneed += 256;
                        for (unsigned n = 0; inputs_seen(1, n) < oneed;) {}
                    }
                    if (item_type(nx) == T_ATTN) load_q(G_Q + item_col(nx), item_row(nx) * 128);
                    return nx;
                };
                int nxt = first_item();
                while (true) {
                    const int it = nxt >= 0 ? nxt : fetch();
                    nxt = -1;
                    const int type = item_type(it), m = item_row(it), c = item_col(it);
                    const int asc = item_asc(it), nu = type == T_ATTN ? 2 * m + 2 : 0;
                    const int uend = nu + ((type == T_ATTN ? m < 2 : pv_grp >= 0) ? 3 : 0), ureq = 2 * max(m - 2 - (asc & m), 0);
#pragma unroll 1
                    for (int u = 0; u < uend; u++) {
                        int grp = pv_grp, row = pv_row;
                        bool shared = pv_shared;
                        if (u >= nu) {
                            if (u == nu + 1) pv_grp = -1;
                            else if (peer_longer) { grp = -1; shared = false; }
                            else continue;
                        } else {
                            const int j = asc ? u >> 1 : m - (u >> 1);
                            if (u & 1) {
                                pv_grp = G_V + c; pv_row = j * 128; pv_shared = j != (m | 1);
                                peer_longer = asc & ~m & 1;
                                if (u == nu - 1 && (m & 1) && item_type(nxt) == T_END) mbar_arrive_cluster_n_if(lane == 0, bars0 + B_WANT, 2);
                                if (grp < 0) continue;
                            } else {
                                if (u == ureq) request();
                                if (u == 2 * m && m > 0) nxt = fetch();
                                grp = G_K + c; row = j * 128; shared = j != (m | 1);
                            }
                        }
                        load_kv(grp, row, shared);
                    }
                    if (type == T_END) break;
                    if (type == T_ATTN) {
                        need_a = 1;
                    } else if (type == T_LOCAL) {
                        if (held_type == T_B && !(it & ITEM_READY)) held_type = T_END;
                        request();
#pragma unroll 1
                        for (uint32_t st = 0; st < 4; st++) {
                            acquire_g(st, false);
                            const uint32_t dst = sb + st * GST_BYTES, fb = bars + B_GFULL + 8 * st;
                            warp_expect_tx(fb, st == 0 ? 32768 + 512 : st == 3 ? 0 : 4 * LOC_PLANE);
                            if (st == 3) break;
                            if (st == 0) warp_bulk_load(dst + 4 * LOC_PLANE, &g_gate[m * 128], 512, fb);
#pragma unroll 1
                            for (int i = 0; i < 4; i++)
                                warp_tma_load(dst + i * LOC_PLANE, &prm.m[st ? M_SCR_LOC : M_SCR_LOQ], fb, i * 64, m * 64 - (st ? 8 : 0), G_B + 8 * st + c);
                        }
                        gph ^= 1;
                        need_g = 63;
                    } else {
                        const int nk = type == T_K || type == T_V ? 8 : 16;
                        const CUtensorMap* ma = &prm.m[nk == 8 ? M_C : M_X];
                        const CUtensorMap* mb = &prm.m[type == T_Q ? M_WQ : type == T_K ? M_WUK : type == T_V ? M_WUV : M_WQKV];
                        for (int k = k0; k < nk; k++) {
                            if (k == nk - 3) request();
                            const uint32_t st = k & 3;
                            uint32_t dst = sb + st * GST_BYTES, fb = bars + B_GFULL + 8 * st, dstb = dst + 16384 + prank * 16384;
                            int a0 = k * 64, a1 = m * 128, b2 = c * 4 + 2 * prank;
                            asm volatile("" : "+r"(dst), "+r"(fb), "+r"(dstb), "+r"(a0), "+r"(a1), "+r"(b2), "+l"(ma), "+l"(mb));
                            acquire_g(st, true);
                            warp_expect_tx(fb, GST_BYTES);
                            warp_tma_load(dst, ma, fb, a0, a1, 0);
                            warp_tma_load_pair(dstb, mb, fb, 0, a0, b2);
                            if (st == 3) gph ^= 1;
                        }
                        need_g = 63;
                        held_type = type;
                        k0 = 0;
                    }
                }
                if (!need_a) request();
                const int it = __shfl_sync(0xffffffffu, next_item(lane == 0), 0);
                int nk = 0;
                if (item_type(it) == T_OUT) {
                    const int m = item_row(it), c = item_col(it), half = c & 1;
                    nk = 80;
                    for (int k = 0; k < nk; k++) {
                        if (k == K_SPLIT) nk = 2 * TRIPLES + (__shfl_sync(0xffffffffu, next_item(lane == 0), 0) & 127);
                        const int kn = k + 2 * TRIPLES - nk, first = kn >= 0 && !(kn & 1);
                        const int s = kn >= 0 ? WIDE + (3 * kn + 1) / 2 : half ? WIDE - 1 - k : k;
                        const uint32_t sa = prm.ostep[s], sa2 = prm.ostep[s + first], sw = prm.ostep[s - (kn >= 0 && !first ? prank : 0)];
                        for (unsigned n = 0; !(inputs_seen(sa >> 6, n) >> (sa >> 1 & 31) & 1);) {}
                        if (first) for (unsigned n = 0; !(inputs_seen(sa2 >> 6, n) >> (sa2 >> 1 & 31) & 1);) {}
                        const uint32_t st = k & 3;
                        uint32_t dst = sb + st * GST_BYTES, fb = bars + B_GFULL + 8 * st;
                        uint32_t dstb = dst + 16384 + (first ? 0 : prank * 16384), skipb = first && (kn >> 1 & 1) != prank;
                        int a0 = (sa & 1) * 64, a1 = m * 128, a2 = (sa >> 1) + (sa < 64 ? G_CTX : G_LOC - 32);
                        int b1 = (sw & 63) * 64, b2 = (c >> 1) * 4 + 2 * (kn >= 0 ? half : half ^ prank);
                        const CUtensorMap* mb = &prm.m[sw >= 64 ? M_WOB : M_WO];
                        asm volatile("" : "+r"(dst), "+r"(fb), "+r"(dstb), "+r"(skipb), "+r"(a0), "+r"(a1), "+r"(a2), "+r"(b1), "+r"(b2), "+l"(mb));
                        acquire_g(st, true);
                        warp_expect_tx(fb, GST_BYTES);
                        warp_tma_load(dst, tile_map, fb, a0, a1, a2);
                        if (!skipb) warp_tma_load_pair(dstb, mb, fb, 0, b1, b2);
                        if (first) warp_tma_load(dst + 32768, tile_map, fb, (sa2 & 1) * 64, a1, (sa2 >> 1) + (sa2 < 64 ? G_CTX : G_LOC - 32));
                        if (k < K_SPLIT && lane == 0 && !prank)
                            asm volatile("st.relaxed.gpu.global.u32 [%0], %1;" :: "l"(&g_sync.step[0][0] + m * 4 + c), "r"(k) : "memory");
                        if (k == K_MEET) request();
                        if (PF_NAR && (uint32_t)(k - PF_NAR) < (3 * TRIPLES + 1) / 2) {
                            const uint32_t g = prm.ostep[79 - 2 * (k - PF_NAR)] >> 1;
                            warp_prefetch((const char*)g_scr + (uint32_t)((G_CTX + g) * (SEQ * 256) + m * 32768 + c * 4096), 4096);
                            warp_prefetch(prm.wo + (uint32_t)(g * 262144 + (m * 8 + c) * 2048), 2048);
                        }
                        if (st == 3) gph ^= 1;
                    }
                    for (unsigned n = 0; ~inputs_seen(0, n) || inputs_seen(1, n) != 255;) {}
                }
                for (uint32_t st = 0; st < 4; st++) { mbar_wait(bars + B_GEMPTY + 8 * st, gph ^ (st < (nk & 3))); mbar_wait(bars + B_AEMPTY + 16 + 8 * st, a_parity(2 + st)); }
                unsigned left = 0;
                if (lane == 0) left = atomicAdd(&g_sync.done, 1u);
                if (__shfl_sync(0xffffffffu, left, 0) == NCTA - 1)
                    for (int i = lane; i < sizeof(Sync) / 8; i += 32) ((unsigned long long*)&g_sync)[i] = 0;
            }
        } else if (warp <= 2) {
            if (blockIdx.x < SEQ / 16) {
                const uint32_t r0 = 16 * blockIdx.x + 8 * (warp - 1), gbuf = bars + SM_GATE + 4 * (r0 & 15);
                float z[4];
#pragma unroll 1
                for (uint32_t i = 0; i < 8; i++) {
                    const uint32_t off = (i & 3) * 512 + lane * 16;
                    const uint4* xp = (const uint4*)((const char*)prm.x + ((r0 + (i & 4)) * 2048 + off));
                    const uint4 wv = __ldg((const uint4*)((const char*)prm.gate_w + off));
                    uint4 xv[4];
#pragma unroll
                    for (int r = 0; r < 4; r++) { xv[r] = __ldg(xp + r * 128); if (!(i & 3)) z[r] = 0.f; }
                    const uint32_t ws[4] = {wv.x, wv.y, wv.z, wv.w};
#pragma unroll
                    for (int e = 0; e < 4; e++)
#pragma unroll
                        for (int r = 0; r < 4; r++) {
                            const uint32_t xs = e == 0 ? xv[r].x : e == 1 ? xv[r].y : e == 2 ? xv[r].z : xv[r].w;
                            z[r] = fmaf(__uint_as_float(xs << 16), __uint_as_float(ws[e] << 16), z[r]);
                            z[r] = fmaf(__uint_as_float(xs & 0xffff0000u), __uint_as_float(ws[e] & 0xffff0000u), z[r]);
                        }
                    if ((i & 3) == 3) {
#pragma unroll
                        for (int o = 16; o > 0; o >>= 1)
#pragma unroll
                            for (int r = 0; r < 4; r++) z[r] += __shfl_xor_sync(0xffffffffu, z[r], o);
                        const float zr = lane & 2 ? (lane & 1 ? z[3] : z[2]) : (lane & 1 ? z[1] : z[0]);
                        asm volatile("st.shared.f32 [%0], %1;" :: "r"(gbuf + 4 * ((i & 4) + (lane & 3))), "f"(1.f / (1.f + __expf(-zr))) : "memory");
                    }
                }
                fence_proxy_async_smem();
                __syncwarp();
                warp_bulk_store((char*)g_gate + 4 * r0, gbuf, 32);
                bulk_commit();
                bulk_wait<0>();
                __syncwarp();
                if (lane == 0) red_add(&g_sync.count[3], 1);
            }
            __syncwarp();
            {
                const int w = warp - 1;
                uint32_t sph = 0, aph = 0, nann = 0, nattn = 0;
                int unsent = 0, nunsent = 0;
                bool urgent = false;
                auto announce = [&]() {
                    if (!urgent) return;
                    bulk_wait<0>();
                    __syncwarp();
                    const uint32_t hb = bars + B_HALF + 8 * (nann & 3);
                    if (w == 0) {
                        mbar_arrive_if(lane == 0, hb);
                    } else {
                        mbar_wait(hb, (nann >> 2) & 1);
                        const uint32_t type = item_type(unsent), m = item_row(unsent), c = item_col(unsent);
                        const uint32_t word = type < T_B ? c >> 3 : type == T_B ? 2 : offsetof(Sync, ctx) / 8 + m;
                        const uint32_t bit = type < T_B ? 8 * (c & 7) : type == T_B ? 4 * m : type == T_LOCAL ? 32 + c : c;
                        if (lane < nunsent) red_add((unsigned long long*)((char*)&g_sync + 8 * word), 1ull << bit);
                        __syncwarp();
                    }
                    nann++;
                    nunsent = 0; urgent = false;
                };
                auto store_item = [&](int it, bool borrow, bool now) {
                    const int type = item_type(it), m = item_row(it), c = item_col(it);
                    const int npair = type < T_OUT ? 2 : 1;
                    const bool local = type == T_LOCAL;
                    const int grp = type == T_Q ? G_Q + 2 * c : type == T_K ? G_K + 2 * c : type == T_V ? G_V + 2 * c : type == T_B ? G_B + 2 * c
                                  : type == T_ATTN ? G_CTX + c : G_LOC + c;
                    for (int pr = 0; pr < npair; pr++) {
                        if (borrow && pr) {
                            mbar_wait(bars + B_ALT + 8 * w, aph);
                            fence_proxy_async_smem();
                            aph ^= 1;
                            for (int b = 0; b < 2; b++)
                                warp_tma_store(&prm.m[M_SCR_ST], sb + ((nattn & 1) ^ 1) * 32768 + w * 16384 + b * 8192, b * 64, m * 128 + w * 64, grp + 1);
                            bulk_commit();
                            bulk_wait_read<0>();
                            __syncwarp();
                            mbar_arrive_if(lane == 0, bars + B_QFREE);
                            break;
                        }
                        for (int b = 0; b < 2; b++) {
                            if (!__all_sync(0xffffffffu, mbar_test(bars + B_SFULL + 16 * w + 8 * b, sph))) announce();
                            mbar_wait(bars + B_SFULL + 16 * w + 8 * b, sph);
                            fence_proxy_async_smem();
                            warp_tma_store(&prm.m[local ? M_SCR_LOQ : M_SCR_ST], sb + SM_STAGING + w * 16384 + b * 8192,
                                         local ? b * 128 + w * 64 : b * 64, local ? m * 64 : m * 128 + w * 64, grp + pr);
                            bulk_commit();
                            bulk_wait_read<0>();
                            __syncwarp();
                            mbar_arrive_if(lane == 0, bars + B_SEMPTY + 16 * w + 8 * b);
                        }
                        sph ^= 1;
                    }
                    announce();
                    if (lane == nunsent) unsent = it;
                    nunsent++;
                    urgent = now || nunsent == 32 || !local;
                };
                int held = first_item();
                while (true) {
                    if (!__all_sync(0xffffffffu, mbar_test(bars + B_IFULL + 8 * (qn % QDEPTH), (qn / QDEPTH) & 1))) announce();
                    const int it = __shfl_sync(0xffffffffu, next_item(lane == 0), 0), type = item_type(it);
                    const bool keep_held = type == T_LOCAL && (item_type(held) != T_B || (it & ITEM_READY));
                    if (type >= T_ATTN && held < 0 && nunsent) urgent = true;
                    for (int pass = held < 0 || keep_held; pass < 2; pass++) {
                        if (pass && (type < T_OUT || type == T_END)) break;
                        store_item(pass ? it : held, !pass && type == T_ATTN, type >= T_ATTN);
                    }
                    if (type == T_END) break;
                    nattn += type == T_ATTN;
                    if (!keep_held) held = type < T_OUT ? it : -1;
                }
                announce();
                if (item_type(next_item(lane == 0)) == T_OUT) next_item(lane == 0);
            }
        } else {
            if (elect_one()) {
                uint32_t ordy = 0;
                unsigned long long cnt_lo = 0, cnt_hi = 0;
                int late = 0;
                auto refresh = [&]() {
                    if (!late && cnt_lo == 0xccccccccccccccccull && cnt_hi == SEQ / 8) late = 1;
                    asm volatile("ld.acquire.gpu.global.v2.u64 {%0, %1}, [%2];" : "=l"(cnt_lo), "=l"(cnt_hi) : "l"(late ? &g_sync.count[0] : &g_sync.count[2]) : "memory");
                };
                auto inputs_ready = [&](int it) -> bool {
                    const int m = item_row(it), c = item_col(it);
                    if (item_type(it) == T_ATTN) return late && ((c < 16 ? cnt_lo : cnt_hi) >> (4 * (c & 14)) & 255) == 48;
                    return late || (cnt_hi == SEQ / 8 && (cnt_lo >> (4 * m) & 15) == 12 && (cnt_lo >> (4 * max(m - 1, 0)) & 15) == 12);
                };
                auto publish = [&](int it, int step) {
                    const uint32_t slot = qn % QDEPTH;
                    mbar_wait(bars + B_IEMPTY + 8 * slot, ((qn / QDEPTH) & 1) ^ 1);
                    for (uint32_t r = 0; r < 2; r++) {
                        const uint32_t rb = map_cta(bars, r);
                        asm volatile("mbarrier.arrive.expect_tx.shared::cluster.b64 _, [%0], 4;" :: "r"(rb + B_IFULL + 8 * slot) : "memory");
                        asm volatile("st.async.shared::cluster.mbarrier::complete_tx::bytes.u32 [%0], %1, [%2];"
                                     :: "r"(rb + SM_QUEUE + 4 * slot), "r"(it + r * step), "r"(rb + B_IFULL + 8 * slot) : "memory");
                    }
                    qn++;
                };
                int asc = 1;
                int it;
                do {
                    if (rank == 0) {
                        mbar_wait(bars + B_WANT, qn & 1);
                        unsigned i;
                        asm volatile("atom.relaxed.gpu.global.add.u32 %0, [%1], 1;" : "=r"(i) : "l"(&g_sync.next) : "memory");
                        if (cnt_lo != 0x3030303030303030ull || cnt_hi != cnt_lo) refresh();
                        i += NPAIR;
                        const int pit = i < NITEMS ? prm.items[i] : T_END << 13, type = item_type(pit);
                        int step = type == T_LOCAL ? 16 : 1;
                        it = pit + (pit & (step == 1 ? 15 : 0x1f0));
                        if (type == T_ATTN) {
                            if (!asc) { it += 1; step = -1; }
                            it |= asc << 9;
                        }
                        asc = type != T_ATTN || item_row(pit) == 0 || !asc;
                        if (inputs_ready(it)) it |= ITEM_READY;
                        publish(it, step);
                    } else {
                        it = next_item(true);
                    }
                    if ((item_type(it) == T_ATTN || item_type(it) == T_LOCAL) && !(it & ITEM_READY)) {
                        unsigned n = 0;
                        while (!inputs_ready(it)) { refresh(); spin_guard(n); }
                        asm volatile("st.release.cta.shared.u32 [%0], %1;" :: "r"(bars + SM_ORDY + 4), "r"(ordy += 256) : "memory");
                    }
                } while (item_type(it) != T_END);
                if (PF_LOC && blockIdx.x < 128) {
                    prefetch_l2((const char*)g_scr + (uint32_t)(G_LOC * SEQ * 256 + blockIdx.x * 32768), 32768);
                    prefetch_l2(prm.wob + blockIdx.x * 16384, 16384);
                }
                if (rank == 0) {
                    mbar_wait(bars + B_WANT, qn & 1);
                    const unsigned i = atomicAdd(&g_sync.next_out, 1u), t = i < 32 ? 31 - i : i - 32;
                    it = i < 64 ? T_OUT << 13 | ((t & 3) * 2 + (i >> 5)) << 4 | (t >> 2) * 2 : T_END << 13;
                    publish(it, 1);
                } else {
                    it = next_item(true);
                }
                if (item_type(it) == T_OUT) {
                    const uint32_t m = item_row(it), half = item_col(it) & 1, tile = m * 2 + (item_col(it) >> 1);
                    unsigned* split = (unsigned*)((char*)g_sync.split + 4 * tile);
                    unsigned long long rdy = 0;
                    int state = rank ? 2 : 0;
                    for (unsigned n = 0; rdy != 0xffffffffffull || state < 2; spin_guard(n)) {
                        if (rdy != 0xffffffffffull) {
                            rdy = ld_acquire((const unsigned long long*)((char*)g_sync.ctx + 8 * m));
                            asm volatile("st.release.cta.shared.u64 [%0], %1;" :: "r"(bars + SM_ORDY), "l"(rdy) : "memory");
                        }
                        unsigned steps = 0;
                        if (state == 1) {
                            steps = ld_acquire(split);
                        } else if (state == 0 && mbar_test(bars + B_WANT, qn & 1)) {
                            state = 1;
                            unsigned seen;
                            asm volatile("atom.acq_rel.gpu.global.exch.b32 %0, [%1], 1;" : "=r"(seen) : "l"(split) : "memory");
                            if (seen) {
                                const unsigned long long v = ld_acquire((const unsigned long long*)((char*)g_sync.step + 8 * tile));
                                const int d = (int)(v >> 32) - (int)v;
                                steps = (WIDE + min(max(half ? d : -d, K_MEET - K_SPLIT), K_SPLIT - K_MEET)) >> 1;
                                atomicExch(split, WIDE - steps);
                            }
                        }
                        if (steps > 1) { publish(T_END << 13 | steps, 0); state = 2; PMARK(1, 0xF400 + steps); }
                    }
                    if (rank) next_item(true);
                }
                if (rank == 0) for (uint32_t n = qn; n < qn + QDEPTH; n++) mbar_wait(bars + B_IEMPTY + 8 * (n % QDEPTH), ((n / QDEPTH) & 1) ^ 1);
            }
        }
    } else {
        reg_inc<232>();
        const int wg = (warp >> 2) - 1, wq = warp & 3;
        uint32_t gph = 0;
        uint32_t kvn = 0;
        const uint32_t dA = make_desc(sb + wg * 8192, 16);
        uint32_t ti = 0;
        uint32_t sph = 1;
        const uint32_t stg = sb + SM_STAGING + wg * 16384;
        const uint32_t stg_lane = stg + (wq * 16 + (lane & 15)) * 128 + (((lane >> 4) ^ (lane & 7)) << 4);
        auto write_blocks = [&](auto n, uint32_t off, const uint32_t* v) {
            uint32_t a = stg_lane;
            asm volatile("" : "+r"(a));
            a += off;
#pragma unroll
            for (int j = 0; j < decltype(n)::value; j++)
                stmatrix_x4((a ^ (32 * (j & 3))) + (j >> 2) * 8192, v[4 * j], v[4 * j + 1], v[4 * j + 2], v[4 * j + 3]);
        };
        auto release = [&](uint32_t bar) { mbar_arrive_if(lane == 0, bars + bar); };
        const uint32_t bars_lane = map_cta(bars, lane & 1);
        auto release_stage = [&](uint32_t st) { mbar_arrive_cluster_if(lane < 2, bars_lane + B_GEMPTY + 8 * st); };
        auto take_item = [&]() -> int {
            return __shfl_sync(0xffffffffu, next_item(lane == 0, false), 0);
        };
        auto stage_acquire = [&](int b) { mbar_spin(bars + B_SEMPTY + 16 * wg + 8 * b, sph); };
        auto stage_publish = [&](int b) {
            __syncwarp();
            release(B_SFULL + 16 * wg + 8 * b);
        };
        auto stage_chunk = [&](int b, const uint32_t* v) {
            stage_acquire(b);
            write_blocks(std::integral_constant<int, 4>(), b * 8192, v);
            stage_publish(b);
            if (b) sph ^= 1;
        };
        auto publish_pair = [&]() {
            __syncwarp();
            mbar_arrive_if(lane < 2, bars + B_SFULL + 16 * wg + 8 * lane);
            sph ^= 1;
        };
        auto gemm_step = [&](float (&acc)[128], uint32_t dB, int& k) {
            const uint32_t st = k & 3;
            wgmma_wait<0>();
            release_stage((k - 1) & 3);
            mbar_spin(bars + B_GFULL + 8 * st, gph);
            const uint64_t da = full_desc(dA + st * (GST_BYTES >> 4)), db = full_desc(dB + st * (GST_BYTES >> 4));
            wgmma_fence();
#pragma unroll
            for (int kk = 0; kk < 4; kk++) wgmma_ss_n256_tb(acc, da + 2 * kk, db + 128 * kk, 1);
            wgmma_commit();
            gph ^= st == 3;
            k++;
        };
        if (wg == 1) bar_arrive(1, 256);
        int it = first_item();
        while (true) {
            if (item_type(it) <= T_LOCAL) {
                float acc[128];
                uint32_t pk[64];
                bool pending = false;
                bool held_b = false;
                zero_regs(pk);
                const uint32_t dB = make_desc(sb + 16384, 8192);
                do {
                    const int type = item_type(it);
                    if (type == T_LOCAL) {
                        int ln = lane;
                        asm volatile("" : "+r"(ln));
                        const int g = ln >> 2, t = ln & 3, par = wq & 1;
                        const uint32_t hc = (wq >> 1) * 4, pl = sb + (par * 2 + wg) * LOC_PLANE;
                        const uint32_t a16 = (ln & 15) * 128 + (((hc + (ln >> 4)) ^ (ln & 7)) << 4), a8 = (ln & 7) * 128 + (((hc + (ln >> 3)) ^ (ln & 7)) << 4);
                        const bool first0 = 2 * t > g, first1 = 2 * t + 1 > g;
                        const uint32_t fmask = (first0 ? 0xffffu : 0u) | (first1 ? 0xffff0000u : 0u);
                        const bool edge = item_row(it) == 0;
                        uint32_t q[4][2][4], kf[9][4], vf[9][4];
                        float w[8];
                        mbar_spin(bars + B_GFULL, gph);
#pragma unroll
                        for (int u = 0; u < 4; u++) { ldsm_x4(q[u][0], pl + u * 2048 + a16); ldsm_x4(q[u][1], pl + u * 2048 + (a16 ^ 32)); }
#pragma unroll
                        for (int j = 0; j < 8; j++) w[j] = lds_f32(sb + 4 * LOC_PLANE + 4 * (2 * g + par) + 64 * j);
                        __syncwarp();
                        release_stage(0);
                        mbar_spin(bars + B_GFULL + 8, gph);
#pragma unroll
                        for (int n = 0; n < 9; n++) ldsm_x4(kf[n], pl + GST_BYTES + n * 1024 + a8);
                        __syncwarp();
                        release_stage(1);
                        float s[8][2];
#pragma unroll
                        for (int u = 0; u < 4; u++) {
                            float d[3][4];
#pragma unroll
                            for (int nt = 0; nt < 3; nt++) {
                                mma_k16_init(d[nt], q[u][0], kf[2 * u + nt][0], kf[2 * u + nt][1]);
                                mma_k16(d[nt], q[u][1], kf[2 * u + nt][2], kf[2 * u + nt][3]);
                            }
                            if (u == 0 && edge) { d[0][0] = -INFINITY; d[0][1] = -INFINITY; }
                            s[2 * u][0] = first0 ? d[0][0] : d[1][0]; s[2 * u][1] = first1 ? d[0][1] : d[1][1];
                            s[2 * u + 1][0] = first0 ? d[1][2] : d[2][2]; s[2 * u + 1][1] = first1 ? d[1][3] : d[2][3];
                        }
                        mbar_spin(bars + B_GFULL + 16, gph);
#pragma unroll
                        for (int u = 0; u < 4; u++) { ldsm_x4_t(vf[2 * u], pl + 2 * GST_BYTES + u * 2048 + a16); ldsm_x4_t(vf[2 * u + 1], pl + 2 * GST_BYTES + u * 2048 + (a16 ^ 32)); }
                        ldsm_x4_t(vf[8], pl + 2 * GST_BYTES + 8192 + a8);
                        __syncwarp();
                        release_stage(2);
                        float x[8];
#pragma unroll
                        for (int j = 0; j < 8; j++) x[j] = fmaxf(s[j][0], s[j][1]);
#pragma unroll
                        for (int o = 1; o < 4; o *= 2)
#pragma unroll
                            for (int j = 0; j < 8; j++) x[j] = fmaxf(x[j], __shfl_xor_sync(0xffffffffu, x[j], o));
#pragma unroll
                        for (int j = 0; j < 8; j++) {
                            const float n = x[j] * -LOC_SCALE;
                            s[j][0] = ex2(fmaf(s[j][0], LOC_SCALE, n)); s[j][1] = ex2(fmaf(s[j][1], LOC_SCALE, n));
                            x[j] = s[j][0] + s[j][1];
                        }
#pragma unroll
                        for (int o = 1; o < 4; o *= 2)
#pragma unroll
                            for (int j = 0; j < 8; j++) x[j] += __shfl_xor_sync(0xffffffffu, x[j], o);
                        mbar_spin(bars + B_GFULL + 24, gph);
                        release_stage(3);
                        it = take_item();
                        uint32_t ob[4][8];
#pragma unroll
                        for (int u = 0; u < 4; u++) {
                            const float r0 = rcp(x[2 * u]), r1 = rcp(x[2 * u + 1]), f0 = fmaf(-w[2 * u], r0, r0), f1 = fmaf(-w[2 * u + 1], r1, r1);
                            const uint32_t p0 = pack_bf16(s[2 * u][0] * f0, s[2 * u][1] * f0), p1 = pack_bf16(s[2 * u + 1][0] * f1, s[2 * u + 1][1] * f1);
                            const uint32_t pa[4] = {p0 & fmask, 0, p0 & ~fmask, p1 & fmask};
#pragma unroll
                            for (int c = 0; c < 4; c++) {
                                float ol[4];
                                mma_k16_init(ol, pa, vf[2 * u + (c >> 1)][2 * (c & 1)], vf[2 * u + (c >> 1)][2 * (c & 1) + 1]);
                                mma_k8(ol, 0, p1 & ~fmask, u < 3 ? vf[2 * u + 2 + (c >> 1)][2 * (c & 1)] : vf[8][c]);
                                ob[u][2 * c] = pack_bf16(ol[0], ol[1]);
                                ob[u][2 * c + 1] = pack_bf16(ol[2], ol[3]);
                            }
                        }
                        stage_acquire(0); stage_acquire(1);
#pragma unroll
                        for (int u = 0; u < 4; u++) {
                            stmatrix_x4(stg + par * 8192 + u * 2048 + a16, ob[u][0], ob[u][1], ob[u][2], ob[u][3]);
                            stmatrix_x4(stg + par * 8192 + u * 2048 + (a16 ^ 32), ob[u][4], ob[u][5], ob[u][6], ob[u][7]);
                        }
                        publish_pair();
                        bar_sync(4, 256);
                        gph ^= 1;
                        continue;
                    }
                    mbar_spin(bars + B_GFULL, gph);
                    bool more;
                    do {
                        wgmma_fence();
                        wgmma_ss_n256_tb_init(acc, full_desc(dA), full_desc(dB));
#pragma unroll
                        for (int kk = 1; kk < 4; kk++) wgmma_ss_n256_tb(acc, full_desc(dA) + 2 * kk, full_desc(dB) + 128 * kk, 1);
                        wgmma_commit();
                        const int nk = item_type(it) == T_K || item_type(it) == T_V ? 8 : 16;
                        int k = 1;
                        do {
                            if (pending) {
                                const int kf = k - 1 - wg;
                                if (kf == 0) stage_chunk(0, pk);
                                else if (kf == 1) stage_chunk(1, pk + 16);
                                else if (kf == KF2) stage_chunk(0, pk + 32);
                                else if (kf == KF2 + 1) stage_chunk(1, pk + 48);
                            }
                            gemm_step(acc, dB, k);
                        } while (k < nk);
                        held_b = item_type(it) == T_B;
                        const bool is_q = item_type(it) == T_Q;
                        it = take_item();
                        more = item_type(it) < T_LOCAL;
                        if (more) mbar_spin(bars + B_GFULL, gph);
                        wgmma_wait<0>();
                        fence_regs(acc);
                        release_stage(3);
                        if (is_q) {
#pragma unroll
                            for (int j = 0; j < 128; j++) acc[j] *= SM_SCALE;
                        }
#pragma unroll
                        for (int j = 0; j < 64; j++) pk[j] = pack_bf16(acc[2 * j], acc[2 * j + 1]);
                        pending = true;
                    } while (more);
                } while (item_type(it) < T_LOCAL || (item_type(it) == T_LOCAL && (!held_b || (it & ITEM_READY))));
                if (pending) {
                    stage_acquire(0); stage_acquire(1);
                    write_blocks(std::integral_constant<int, 8>(), 0, pk);
                    const bool borrow = item_type(it) == T_ATTN;
                    if (borrow) {
                        mbar_spin(bars + B_GEMPTY, gph ^ 1); mbar_spin(bars + B_GEMPTY + 8, gph ^ 1);
                    } else {
                        publish_pair();
                        stage_acquire(0); stage_acquire(1);
                    }
                    write_blocks(std::integral_constant<int, 8>(), borrow ? ((ti & 1) ^ 1) * 32768 - SM_STAGING : 0, pk + 32);
                    publish_pair();
                    mbar_arrive_if(lane == 0 && borrow, bars + B_ALT + 8 * wg);
                }
                if (item_type(it) == T_END) { it = take_item(); break; }
            } else {
                float o[64], s[64];
                uint32_t pa[32], pb[32];
                zero_regs(o); zero_regs(s); zero_regs(pa);
                float n0 = 0.f, n1 = 0.f;
                bool shifted = false;
                float l0 = 1.f, l1 = 1.f, f0 = 0.f, f1 = 0.f, g0 = 0.f, g1 = 0.f;
                uint32_t has_pv = 0;
                int first = 0;
                int pending = 0;
                const uint32_t dK = make_desc(sb + SM_KV, 16), dV = make_desc(sb + SM_KV, 16384);
                const uint32_t lane_off = bars_lane - bars + B_AEMPTY - B_AFULL;
                int cur = 0;
                uint32_t qoff = 0;
                const int row = wg * 64 + wq * 16 + (lane >> 2);
                const float thr = (row & 63) - (lane & 3) * 2;
                uint32_t peek = 0;
                bool peek_ok = false, q_ok = false;
                auto kv_wait = [&](uint32_t n) { mbar_spin(bars + B_AFULL + 16 + 8 * (n & 3), (n >> 2) & 1); };
                auto kv_release = [&](uint32_t n) { mbar_arrive_cluster_if(lane < 2, bars_lane + B_AEMPTY + 16 + 8 * (n & 3)); };
                struct Slot { uint32_t bar, par, off; } slot[4];
                auto align = [&]() {
#pragma unroll
                    for (uint32_t i = 0; i < 4; i++) {
                        const uint32_t n = kvn + (i == 1 ? has_pv : i);
                        slot[i].bar = bars + B_AFULL + 16 + 8 * (n & 3); slot[i].par = (n >> 2) & 1; slot[i].off = (n & 3) * 2048;
                    }
                };
                align();
                auto scale_o = [&]() {
#pragma unroll
                    for (int j = 0; j < 16; j++) { o[4 * j] *= f0; o[4 * j + 1] *= f0; o[4 * j + 2] *= f1; o[4 * j + 3] *= f1; }
                };
                auto pack_o = [&](uint32_t (&v)[32]) {
#pragma unroll
                    for (int j = 0; j < 32; j++) v[j] = pack_bf16(o[2 * j], o[2 * j + 1]);
                };
                auto scales = [&]() { f0 = g0 * rcp(quad_sum(l0)); f1 = g1 * rcp(quad_sum(l1)); };
                auto step = [&](auto even, uint32_t (&pin)[32], uint32_t (&pout)[32], bool fresh, bool diag, bool last) {
                    constexpr bool EVEN = decltype(even)::value;
                    Slot& sk = slot[EVEN ? 0 : 2];
                    Slot& sv = slot[EVEN ? 1 : 3];
                    kvn += EVEN ? 1 + has_pv : 2;
                    mbar_spin(sk.bar, sk.par);
                    bar_sync(1 + wg, 256);
                    qk_gemm(s, dA + qoff, dK + sk.off);
                    if (EVEN && fresh) {
                        scales();
                        g0 = lds_f32(bars + SM_GATE + (ti & 1) * 512 + 4 * row); g1 = lds_f32(bars + SM_GATE + (ti & 1) * 512 + 4 * row + 32);
                        ti++;
                        n0 = 0.f; n1 = 0.f; l0 = 0.f; l1 = 0.f;
                        shifted = false;
                        if (has_pv) { stage_acquire(0); stage_acquire(1); }
                    }
                    if (!EVEN && pending) {
                        pack_o(pout);
                        write_blocks(std::integral_constant<int, 8>(), 0, pout);
                        publish_pair();
                    }
                    mbar_spin(sv.bar, sv.par);
                    pv_gemm(o, pin, dV + sv.off, EVEN || !first);
                    bar_arrive(2 - wg, 256);
                    sk.par ^= 1; sv.par ^= 1;
                    wgmma_wait<1>();
                    fence_regs(s);
                    mbar_arrive_cluster_if(lane < 2 && (!EVEN || has_pv), sk.bar + lane_off);
                    mbar_arrive_if(lane == 0 && last, bars + B_AEMPTY + 8 * ((ti - 1) & 1));
                    if (diag || shifted) {
                        if (diag) causal_mask(s, thr, wg);
                        if (shifted) shift_rows(s, n0, n1);
                    }
                    q_ok = mbar_test(bars + B_AFULL + 8 * (ti & 1), (ti >> 1) & 1);
                    peek_ok = mbar_test(bars + B_IFULL + 8 * (qn % QDEPTH), (qn / QDEPTH) & 1);
                    asm volatile("ld.shared.u32 %0, [%1];" : "=r"(peek) : "r"(bars + SM_QUEUE + 4 * (qn % QDEPTH)) : "memory");
                    float r0, r1;
                    exp_pack(pout, s, r0, r1);
                    if (__any_sync(0xffffffffu, fmaxf(r0, r1) >= SUM_LIMIT || (EVEN && fresh && !(lane & 3) && !(fminf(s[0], s[2]) >= -REF_RANGE)))) {
                        float x0, x1;
                        row_max(s, x0, x1);
                        if (!(EVEN && fresh)) { x0 = fmaxf(x0, 0.f); x1 = fmaxf(x1, 0.f); }
                        float a0 = ex2(-x0), a1 = ex2(-x1);
                        n0 += x0; n1 += x1;
                        shifted = true;
                        if (EVEN && fresh) { a0 = 1.f; a1 = 1.f; }
                        l0 *= a0; l1 *= a1;
                        wgmma_wait<0>();
                        fence_regs(o);
#pragma unroll
                        for (int q = 0; q < 16; q++) { o[4 * q] *= a0; o[4 * q + 1] *= a0; o[4 * q + 2] *= a1; o[4 * q + 3] *= a1; }
                        shift_rows(s, x0, x1);
                        exp_pack(pout, s, r0, r1);
                    }
                    l0 += r0; l1 += r1;
                    wgmma_wait<0>();
                    fence_regs(o);
                    fence_regs(pin);
                    mbar_arrive_cluster_if(lane < 2, sv.bar + lane_off);
                };
                auto copy_p = [&]() {
#pragma unroll
                    for (int j = 0; j < 32; j++) pa[j] = __float_as_uint(__uint_as_float(pb[j]) + __uint_as_float(prm.zero));
                };
                int rem = 0;
                mbar_spin(bars + B_AFULL + 8 * (ti & 1), (ti >> 1) & 1);
                while (true) {
                    const bool fresh = rem == 0;
                    if (fresh) {
                        if (has_pv) {
                            if (__all_sync(0xffffffffu, peek_ok)) {
                                mbar_arrive_cluster_if(lane == 0, bars0 + B_IEMPTY + 8 * (qn % QDEPTH));
                                qn++;
                                it = __shfl_sync(0xffffffffu, peek, 0);
                            } else {
                                it = take_item();
                            }
                            if (item_row(cur) < 2 || item_type(it) != T_ATTN) break;
                            if (!q_ok) mbar_spin(bars + B_AFULL + 8 * (ti & 1), (ti >> 1) & 1);
                        }
                        cur = it;
                        qoff = (ti & 1) * 2048;
                    }
                    const bool last = fresh ? item_row(cur) == 0 : rem == 1;
                    step(std::true_type(), pa, pb, fresh, item_asc(cur) ? last : fresh, last);
                    first = fresh;
                    if (fresh) {
                        pending = has_pv; has_pv = 1;
                        if (!pending) { kvn -= 2; align(); kvn += 2; slot[0].par ^= 1; slot[1].par ^= 1; }
                        else scale_o();
                        rem = item_row(cur);
                        if (rem == 0) {
                            copy_p();
                            continue;
                        }
                    } else if (--rem == 0) {
                        copy_p();
                        align();
                        continue;
                    }
                    step(std::false_type(), pb, pa, false, item_asc(cur) && rem == 1, rem == 1);
                    pending = 0; first = 0;
                    rem--;
                }
                const uint32_t skip = item_asc(cur) & ~item_row(cur) & 1;
                kvn += skip;
                const bool end = item_type(it) == T_END;
#pragma unroll 1
                for (int pass = pending ? 0 : 1; pass < 2; pass++) {
                    if (pass) {
                        kv_wait(kvn);
                        pv_gemm(o, pa, dV + (kvn & 3) * 2048, !first);
                        scales();
                        stage_acquire(0); stage_acquire(1);
                        if (end) it = take_item();
                        wgmma_wait<0>();
                        fence_regs(o);
                        kv_release(kvn);
                        kvn += 1 + skip;
                        scale_o();
                    }
                    pack_o(pb);
                    write_blocks(std::integral_constant<int, 8>(), 0, pb);
                    publish_pair();
                }
                if (end) break;
            }
        }
        if (item_type(it) == T_OUT) {
            float acc[128];
            const uint32_t dB = make_desc(sb + 16384, 8192);
            mbar_spin(bars + B_GFULL, gph);
            wgmma_fence();
            wgmma_ss_n256_tb_init(acc, full_desc(dA), full_desc(dB));
#pragma unroll
            for (int kk = 1; kk < 4; kk++) wgmma_ss_n256_tb(acc, full_desc(dA) + 2 * kk, full_desc(dB) + 128 * kk, 1);
            wgmma_commit();
            uint32_t ln;
            asm volatile("mov.u32 %0, %%laneid;" : "=r"(ln));
            const uint32_t slot = (it & 127) * 32768 + (wg * 128 + wq * 32 + ln) * 16;
            char* const mine = (char*)g_part + slot;
            int k = 1, nk = 80;
            do {
                if (k == K_MEET - 5) {
#pragma unroll
                    for (int j = 0; j < 8; j++) st_b128(mine + j * 4096, 0, 0, 0, 0);
                    __syncwarp();
                }
                if (k == K_SPLIT) nk = take_item() & 127;
                gemm_step(acc, dB, k);
            } while (k < nk);
            auto triple = [&](uint32_t nrel) {
                const uint32_t s0 = k & 3, s1 = (k + 1) & 3, o0 = s0 * (GST_BYTES >> 4), o1 = s1 * (GST_BYTES >> 4);
                wgmma_wait<0>();
                mbar_arrive_cluster_if(ln < nrel, bars_lane + B_GEMPTY + 8 * ((k - 1 - (ln >> 1)) & 3));
                mbar_spin(bars + B_GFULL + 8 * s0, gph);
                gph ^= s0 == 3;
                wgmma_fence();
#pragma unroll
                for (int kk = 0; kk < 4; kk++) wgmma_ss_n128_lo_tb(acc, full_desc(dA + o0) + 2 * kk, full_desc(dB + o0) + 128 * kk, 1);
                mbar_spin(bars + B_GFULL + 8 * s1, gph);
                gph ^= s1 == 3;
                wgmma_fence();
#pragma unroll
                for (int kk = 0; kk < 4; kk++) wgmma_ss_n128_lo_tb(acc, full_desc(dA + o0 + 2048) + 2 * kk, full_desc(dB + o1 + 1024) + 128 * kk, 1);
#pragma unroll
                for (int kk = 0; kk < 4; kk++) wgmma_ss_n128_lo_tb(acc, full_desc(dA + o1) + 2 * kk, full_desc(dB + o1) + 128 * kk, 1);
                wgmma_commit();
                k += 2;
            };
            triple(2);
#pragma unroll
            for (int j = 0; j < 8; j++) {
                uint32_t v[4];
#pragma unroll
                for (int i = 0; i < 4; i++) {
                    asm volatile("" : "+f"(acc[64 + 8 * j + 2 * i]), "+f"(acc[65 + 8 * j + 2 * i]) :: "memory");
                    v[i] = pack_bf16(acc[64 + 8 * j + 2 * i], acc[65 + 8 * j + 2 * i]);
                }
                if (j == SPREAD) triple(4);
                else if (PACE && j) __nanosleep(PACE);
                st_b128(mine + j * 4096, ~v[0], v[1], v[2], v[3]);
            }
#pragma unroll 1
            for (int t = 2; t < TRIPLES; t++) triple(4);
            uint32_t pk[32];
            char* const other = (char*)g_part + (slot ^ (16 * 32768));
            while (true) {
                bool miss = false;
#pragma unroll
                for (int j = 0; j < 8; j++) ld_b128(other + j * 4096, pk[4 * j], pk[4 * j + 1], pk[4 * j + 2], pk[4 * j + 3]);
#pragma unroll
                for (int j = 0; j < 8; j++) miss |= pk[4 * j] == 0;
                if (!__any_sync(0xffffffffu, miss)) break;
                while (__any_sync(0xffffffffu, pk[28] == 0)) ld_b128(other + 7 * 4096, pk[28], pk[29], pk[30], pk[31]);
            }
#pragma unroll
            for (int j = 0; j < 32; j++) {
                const uint32_t v = j & 3 ? pk[j] : ~pk[j];
                acc[64 + 2 * j] = __uint_as_float(v << 16); acc[65 + 2 * j] = __uint_as_float(v & 0xffff0000u);
                asm volatile("" : "+f"(acc[64 + 2 * j]), "+f"(acc[65 + 2 * j]) :: "memory");
            }
            stage_acquire(0); stage_acquire(1);
            wgmma_wait<0>();
#pragma unroll
            for (int j = 0; j < 64; j++) asm volatile("" : "+f"(acc[j]) :: "memory");
            mbar_arrive_cluster_if(ln < 4, bars_lane + B_GEMPTY + 8 * ((k - 1 - (ln >> 1)) & 3));
#pragma unroll
            for (int j = 0; j < 32; j++)
                pk[j] = pack_bf16(acc[2 * j] + acc[64 + 2 * j], acc[2 * j + 1] + acc[65 + 2 * j]);
            write_blocks(std::integral_constant<int, 8>(), 0, pk);
            __syncwarp();
            uint4* dst = (uint4*)((char*)prm.out + (uint32_t)((item_row(it) * 128 + wg * 64 + wq * 16 + (ln >> 4)) * 2048 + item_col(it) * 256 + (ln & 15) * 16));
#pragma unroll
            for (int j = 0; j < 8; j++) {
                const int r = 2 * j + (ln >> 4);
                uint4 v;
                asm volatile("ld.shared.v4.u32 {%0, %1, %2, %3}, [%4];" : "=r"(v.x), "=r"(v.y), "=r"(v.z), "=r"(v.w)
                             : "r"(stg + wq * 2048 + r * 128 + (ln & 8) * 1024 + (((ln & 7) ^ (r & 7)) << 4)) : "memory");
                dst[j * 256] = v;
            }
        }
    }
}

typedef CUresult (*EncodeFn)(CUtensorMap*, CUtensorMapDataType, cuuint32_t, void*, const cuuint64_t*, const cuuint64_t*,
                             const cuuint32_t*, const cuuint32_t*, CUtensorMapInterleave, CUtensorMapSwizzle,
                             CUtensorMapL2promotion, CUtensorMapFloatOOBfill);

void encode3(EncodeFn fn, CUtensorMap* m, const void* ptr, uint64_t d0, uint64_t d1, uint64_t d2, uint64_t s1, uint64_t s2,
             uint32_t b0, uint32_t b1, uint32_t b2) {
    cuuint64_t dims[3] = {d0, d1, d2};
    cuuint64_t strides[2] = {s1, s2};
    cuuint32_t box[3] = {b0, b1, b2};
    cuuint32_t es[3] = {1, 1, 1};
    fn(m, CU_TENSOR_MAP_DATA_TYPE_BFLOAT16, 3, const_cast<void*>(ptr), dims, strides, box, es, CU_TENSOR_MAP_INTERLEAVE_NONE,
       CU_TENSOR_MAP_SWIZZLE_128B, CU_TENSOR_MAP_L2_PROMOTION_NONE, CU_TENSOR_MAP_FLOAT_OOB_FILL_NONE);
}
void map_act(EncodeFn fn, CUtensorMap* m, const void* p, int rows, int cols, int box_rows) {
    encode3(fn, m, p, cols, rows, 1, (uint64_t)cols * 2, (uint64_t)cols * rows * 2, 64, box_rows, 1);
}
void map_wgt(EncodeFn fn, CUtensorMap* m, const void* p, int K, int N) {
    encode3(fn, m, p, 64, K, N / 64, (uint64_t)N * 2, 128, 64, 64, 2);
}

void build_schedule(Params& p) {
    int n = 0;
    auto add = [&](int type, int col, int row) { p.items[n++] = (uint16_t)(type << 13 | col << 4 | row); };
    auto add_qkv = [&](int c) {
        for (int m = 0; m < 8; m++) add(T_Q, c, m);
        for (int m = 0; m < 8; m++) add(T_K, c, m);
        for (int m = 0; m < 8; m++) add(T_V, c, m);
    };
    int ldist = 200, ldist2 = 260, lstep = 8, beta = 26, tail = 32, late = 6, early = 8, epos = 100;
    int order[16] = {6, 7, 8, 9, 10, 11, 12, 13, 14, 15, 5, 4, 3, 2, 1, 0};
    uint16_t proj[480];
    for (int m = 0; m < 8; m++) for (int c = 0; c < 12; c++) add(T_B, c, m);
    for (int c = 0; c < 16; c++) add_qkv(c);
    for (int i = 0; i < 480; i++) proj[i] = p.items[i];
    n = 0;
    for (int i = 0, l = 0; i < 480; i++) {
        p.items[n++] = proj[i];
        for (; l < 64 && i >= (l < 40 ? ldist + lstep * l / 8 : ldist2 + lstep * (l - 40) / 8); l++) add(T_LOCAL, l & 3, l >> 2);
    }
    const int a0 = n;
    for (int key = 0; key < 4000; key++)
        for (int r = 0; r < 32; r++)
            for (int j = 7; j >= 0; j--)
                if ((j ? (7 - j) * 40 + r * beta : 3999) == key) add(T_ATTN, 2 * order[r >> 1] + (r & 1), j);
    int t0 = n;
    for (int work = 0; work < 32 * 136 * tail / 100;) work += 4 * (p.items[--t0] & 15) + 3;
    for (int i = t0 + 1; i < n; i++)
        for (int j = i; j > t0 && (p.items[j] & 15) > (p.items[j - 1] & 15); j--) { const uint16_t t = p.items[j]; p.items[j] = p.items[j - 1]; p.items[j - 1] = t; }
    for (int r = early - 1; r >= 0; r--) {
        const uint16_t t = p.items[n - 32 + early - 1];
        for (int j = n - 32 + early - 1; j > n - epos; j--) p.items[j] = p.items[j - 1];
        p.items[n - epos] = t;
    }
    for (int moved = 0; moved < 2 && late >= 0; moved++)
        for (int i = a0; i < n; i++)
            if (p.items[i] == (T_ATTN << 13 | (2 * order[15] + moved) << 4 | late)) {
                for (int j = i; j + 1 < n; j++) p.items[j] = p.items[j + 1];
                p.items[n - 1] = (uint16_t)(T_ATTN << 13 | (2 * order[15] + moved) << 4 | late);
                break;
            }
    for (int s = 0, lo = 0, hi = WIDE - 1; s < 80; s++) {
        const int r = s / 2, g = r < 8 ? 32 + r : 2 * order[r / 2 - 4] + (r & 1);
        p.ostep[s >= WIDE ? s : r & 1 ? hi-- : lo++] = (uint8_t)(2 * g + (s & 1));
    }
}

void build_params(Params& p, void* const* d_in, void* d_out) {
    void* fnp = nullptr;
    cudaDriverEntryPointQueryResult qr;
    cudaGetDriverEntryPoint("cuTensorMapEncodeTiled", &fnp, cudaEnableDefault, &qr);
    EncodeFn fn = (EncodeFn)fnp;
    void* scr = nullptr;
    cudaGetSymbolAddress(&scr, g_scr);
    map_act(fn, &p.m[M_X], d_in[0], SEQ, 1024, 128);
    map_act(fn, &p.m[M_C], d_in[1], SEQ, 512, 128);
    map_wgt(fn, &p.m[M_WQ], d_in[2], 1024, 4096);
    map_wgt(fn, &p.m[M_WUK], d_in[3], 512, 4096);
    map_wgt(fn, &p.m[M_WUV], d_in[4], 512, 4096);
    map_wgt(fn, &p.m[M_WO], d_in[5], 4096, 1024);
    map_wgt(fn, &p.m[M_WQKV], d_in[7], 1024, 3072);
    map_wgt(fn, &p.m[M_WOB], d_in[8], 1024, 1024);
    encode3(fn, &p.m[M_SCR_LD], scr, 128, SEQ, G_TOTAL, 256, (uint64_t)SEQ * 256, 64, 128, 1);
    encode3(fn, &p.m[M_SCR_LOC], scr, 256, SEQ / 2, G_TOTAL, 512, (uint64_t)SEQ * 256, 64, 72, 1);
    encode3(fn, &p.m[M_SCR_LOQ], scr, 256, SEQ / 2, G_TOTAL, 512, (uint64_t)SEQ * 256, 64, 64, 1);
    encode3(fn, &p.m[M_SCR_ST], scr, 128, SEQ, G_TOTAL, 256, (uint64_t)SEQ * 256, 64, 64, 1);
    p.x = (const __nv_bfloat16*)d_in[0];
    p.gate_w = (const __nv_bfloat16*)d_in[9];
    p.zero = 0;
    p.wo = (const char*)d_in[5];
    p.wob = (const char*)d_in[8];
    p.out = (__nv_bfloat16*)d_out;
    build_schedule(p);
}

}

extern "C" void kernel_launch(void* const* d_in, const int* in_sizes, int n_in, void* d_out, int out_size) {
    (void)in_sizes; (void)n_in; (void)out_size;
    Params p;
    build_params(p, d_in, d_out);
    cudaFuncSetAttribute(fused_kernel, cudaFuncAttributeMaxDynamicSharedMemorySize, SM_TOTAL);
    fused_kernel<<<NCTA, 384, SM_TOTAL>>>(p);
}
```

```cpp
#include <cuda_runtime.h>
#include <cuda_bf16.h>
#include <cuda.h>
#include <stddef.h>
#include <stdint.h>
#include <type_traits>

namespace {

constexpr int SEQ = 2048;
constexpr int G_Q = 0, G_K = 32, G_V = 64, G_B = 96, G_CTX = G_Q, G_LOC = G_B, G_TOTAL = 120;

__device__ __align__(1024) __nv_bfloat16 g_scr[(size_t)G_TOTAL * SEQ * 128];
__device__ __align__(128) float g_gate[SEQ];

__device__ __forceinline__ uint32_t smem_u32(const void* p) { return (uint32_t)__cvta_generic_to_shared(p); }
__device__ __forceinline__ bool elect_one() {
    uint32_t p;
    asm volatile("{\n.reg .pred P;\nelect.sync _|P, 0xffffffff;\nselp.u32 %0, 1, 0, P;\n}\n" : "=r"(p));
    return p != 0;
}
__device__ __forceinline__ void mbar_init(uint32_t bar, uint32_t count) {
    asm volatile("mbarrier.init.shared::cta.b64 [%0], %1;" :: "r"(bar), "r"(count) : "memory");
}
__device__ __forceinline__ void mbar_expect_tx(uint32_t bar, uint32_t bytes) {
    asm volatile("mbarrier.arrive.expect_tx.shared::cta.b64 _, [%0], %1;" :: "r"(bar), "r"(bytes) : "memory");
}
__device__ __forceinline__ uint32_t cluster_rank() { uint32_t r; asm("mov.u32 %0, %%cluster_ctarank;" : "=r"(r)); return r; }
__device__ __forceinline__ uint32_t map_cta(uint32_t addr, uint32_t cta) {
    uint32_t r; asm("mapa.shared::cluster.u32 %0, %1, %2;" : "=r"(r) : "r"(addr), "r"(cta)); return r;
}
__device__ __forceinline__ void mbar_arrive_cluster_if(bool pred, uint32_t cluster_bar) {
    asm volatile("{\n.reg .pred P;\nsetp.ne.u32 P, %1, 0;\n@P mbarrier.arrive.shared::cluster.b64 _, [%0];\n}\n"
                 :: "r"(cluster_bar), "r"((uint32_t)pred) : "memory");
}
__device__ __forceinline__ void mbar_arrive_cluster_n_if(bool pred, uint32_t cluster_bar, uint32_t count) {
    asm volatile("{\n.reg .pred P;\nsetp.ne.u32 P, %1, 0;\n@P mbarrier.arrive.shared::cluster.b64 _, [%0], %2;\n}\n"
                 :: "r"(cluster_bar), "r"((uint32_t)pred), "r"(count) : "memory");
}
__device__ __forceinline__ void mbar_arrive_if(bool pred, uint32_t bar) {
    asm volatile("{\n.reg .pred P;\nsetp.ne.u32 P, %1, 0;\n@P mbarrier.arrive.shared::cta.b64 _, [%0];\n}\n"
                 :: "r"(bar), "r"((uint32_t)pred) : "memory");
}
__device__ __forceinline__ bool mbar_test(uint32_t bar, uint32_t parity) {
    uint32_t ok;
    asm volatile("{\n.reg .pred P;\nmbarrier.test_wait.parity.shared::cta.b64 P, [%1], %2;\nselp.u32 %0, 1, 0, P;\n}\n"
                 : "=r"(ok) : "r"(bar), "r"(parity) : "memory");
    return ok != 0;
}
__device__ __forceinline__ void mbar_wait(uint32_t bar, uint32_t parity) {
    asm volatile("{\n.reg .pred P;\n.reg .u32 c;\n"
                 "mbarrier.try_wait.parity.shared::cta.b64 P, [%0], %1;\n"
                 "@P bra DONE;\n"
                 "mov.u32 c, 0;\n"
                 "SPIN:\n"
                 "mbarrier.try_wait.parity.shared::cta.b64 P, [%0], %1;\n"
                 "@P bra DONE;\n"
                 "add.u32 c, c, 1;\n"
                 "setp.lt.u32 P, c, 4194304;\n"
                 "@P bra SPIN;\n"
                 "trap;\n"
                 "DONE:\n}\n" :: "r"(bar), "r"(parity) : "memory");
}
__device__ __forceinline__ void mbar_spin(uint32_t bar, uint32_t parity) {
    asm volatile("{\n.reg .pred P;\n"
                 "SPIN:\n"
                 "mbarrier.try_wait.parity.shared::cta.b64 P, [%0], %1;\n"
                 "@!P bra SPIN;\n}\n" :: "r"(bar), "r"(parity) : "memory");
}
__device__ __forceinline__ void bar_sync(int id, int n) { asm volatile("bar.sync %0, %1;" :: "r"(id), "r"(n) : "memory"); }
__device__ __forceinline__ void bar_arrive(int id, int n) { asm volatile("bar.arrive %0, %1;" :: "r"(id), "r"(n) : "memory"); }
__device__ __forceinline__ void fence_proxy_async_smem() { asm volatile("fence.proxy.async.shared::cta;" ::: "memory"); }
__device__ __forceinline__ void tma_load_3d(uint32_t dst, const CUtensorMap* map, uint32_t bar, int c0, int c1, int c2) {
    asm volatile("cp.async.bulk.tensor.3d.shared::cluster.global.mbarrier::complete_tx::bytes [%0], [%1, {%3, %4, %5}], [%2];"
                 :: "r"(dst), "l"(map), "r"(bar), "r"(c0), "r"(c1), "r"(c2) : "memory");
}
__device__ __forceinline__ void warp_expect_tx(uint32_t bar, uint32_t bytes) {
    asm volatile("{\n.reg .pred P;\nelect.sync _|P, 0xffffffff;\n@P mbarrier.arrive.expect_tx.shared::cta.b64 _, [%0], %1;\n}\n"
                 :: "r"(bar), "r"(bytes) : "memory");
}
__device__ __forceinline__ void warp_tma_load(uint32_t dst, const CUtensorMap* map, uint32_t bar, int c0, int c1, int c2) {
    asm volatile("{\n.reg .pred P;\nelect.sync _|P, 0xffffffff;\n"
                 "@P cp.async.bulk.tensor.3d.shared::cluster.global.mbarrier::complete_tx::bytes [%0], [%1, {%3, %4, %5}], [%2];\n}\n"
                 :: "r"(dst), "l"(map), "r"(bar), "r"(c0), "r"(c1), "r"(c2) : "memory");
}
__device__ __forceinline__ void warp_tma_load_pair(uint32_t dst, const CUtensorMap* map, uint32_t bar, int c0, int c1, int c2) {
    asm volatile("{\n.reg .pred P;\nelect.sync _|P, 0xffffffff;\n"
                 "@P cp.async.bulk.tensor.3d.shared::cluster.global.mbarrier::complete_tx::bytes.multicast::cluster"
                 " [%0], [%1, {%3, %4, %5}], [%2], %6;\n}\n"
                 :: "r"(dst), "l"(map), "r"(bar), "r"(c0), "r"(c1), "r"(c2), "h"((uint16_t)3) : "memory");
}
__device__ __forceinline__ void warp_bulk_load(uint32_t dst, const void* src, uint32_t bytes, uint32_t bar) {
    asm volatile("{\n.reg .pred P;\nelect.sync _|P, 0xffffffff;\n"
                 "@P cp.async.bulk.shared::cluster.global.mbarrier::complete_tx::bytes [%0], [%1], %2, [%3];\n}\n"
                 :: "r"(dst), "l"(src), "r"(bytes), "r"(bar) : "memory");
}
__device__ __forceinline__ void warp_tma_store(const CUtensorMap* map, uint32_t src, int c0, int c1, int c2) {
    asm volatile("{\n.reg .pred P;\nelect.sync _|P, 0xffffffff;\n"
                 "@P cp.async.bulk.tensor.3d.global.shared::cta.bulk_group [%0, {%2, %3, %4}], [%1];\n}\n"
                 :: "l"(map), "r"(src), "r"(c0), "r"(c1), "r"(c2) : "memory");
}
__device__ __forceinline__ void warp_bulk_store(void* dst, uint32_t src, uint32_t bytes) {
    asm volatile("{\n.reg .pred P;\nelect.sync _|P, 0xffffffff;\n"
                 "@P cp.async.bulk.global.shared::cta.bulk_group [%0], [%1], %2;\n}\n" :: "l"(dst), "r"(src), "r"(bytes) : "memory");
}
__device__ __forceinline__ void prefetch_l2(const void* src, uint32_t bytes) {
    asm volatile("cp.async.bulk.prefetch.L2.global [%0], %1;" :: "l"(src), "r"(bytes) : "memory");
}
__device__ __forceinline__ void warp_prefetch(const void* src, uint32_t bytes) {
    asm volatile("{\n.reg .pred P;\nelect.sync _|P, 0xffffffff;\n@P cp.async.bulk.prefetch.L2.global [%0], %1;\n}\n" :: "l"(src), "r"(bytes) : "memory");
}
__device__ __forceinline__ void bulk_commit() { asm volatile("cp.async.bulk.commit_group;" ::: "memory"); }
template <int N> __device__ __forceinline__ void bulk_wait_read() { asm volatile("cp.async.bulk.wait_group.read %0;" :: "n"(N) : "memory"); }
template <int N> __device__ __forceinline__ void bulk_wait() { asm volatile("cp.async.bulk.wait_group %0;" :: "n"(N) : "memory"); }
__device__ __forceinline__ void wgmma_fence() { asm volatile("wgmma.fence.sync.aligned;" ::: "memory"); }
__device__ __forceinline__ void wgmma_commit() { asm volatile("wgmma.commit_group.sync.aligned;" ::: "memory"); }
template <int N> __device__ __forceinline__ void wgmma_wait() { asm volatile("wgmma.wait_group.sync.aligned %0;" :: "n"(N) : "memory"); }
template <int N> __device__ __forceinline__ void fence_regs(float (&d)[N]) {
#pragma unroll
    for (int i = 0; i < N; i++) asm volatile("" : "+f"(d[i]) :: "memory");
}
template <int N> __device__ __forceinline__ void fence_regs(uint32_t (&d)[N]) {
#pragma unroll
    for (int i = 0; i < N; i++) asm volatile("" : "+r"(d[i]) :: "memory");
}
template <int N> __device__ __forceinline__ void reg_dec() { asm volatile("setmaxnreg.dec.sync.aligned.u32 %0;" :: "n"(N)); }
template <int N> __device__ __forceinline__ void reg_inc() { asm volatile("setmaxnreg.inc.sync.aligned.u32 %0;" :: "n"(N)); }
__device__ __forceinline__ uint32_t pack_bf16(float lo, float hi) {
    uint32_t r; asm("cvt.rn.bf16x2.f32 %0, %1, %2;" : "=r"(r) : "f"(hi), "f"(lo)); return r;
}
__device__ __forceinline__ void stmatrix_x4(uint32_t addr, uint32_t r0, uint32_t r1, uint32_t r2, uint32_t r3) {
    asm volatile("stmatrix.sync.aligned.m8n8.x4.shared.b16 [%0], {%1, %2, %3, %4};"
                 :: "r"(addr), "r"(r0), "r"(r1), "r"(r2), "r"(r3) : "memory");
}
__device__ __forceinline__ float ex2(float x) { float y; asm("ex2.approx.ftz.f32 %0, %1;" : "=f"(y) : "f"(x)); return y; }

constexpr uint32_t DESC_HI = (1024 >> 4) | (1u << 30);
__device__ __forceinline__ uint32_t make_desc(uint32_t addr, uint32_t lbo) {
    uint32_t lo = ((addr & 0x3FFFF) >> 4) | ((lbo >> 4) << 16);
    asm volatile("" : "+r"(lo));
    return lo;
}
__device__ __forceinline__ uint64_t full_desc(uint32_t lo) {
    uint64_t d; asm("mov.b64 %0, {%1, %2};" : "=l"(d) : "r"(lo), "r"(DESC_HI)); return d;
}

__device__ __forceinline__ void wgmma_ss_n256_tb_init(float (&d)[128], uint64_t da, uint64_t db) {
    asm volatile("{\n.reg .pred p;\n"
        "setp.ne.b32 p, 0, 0;\n"
        "wgmma.mma_async.sync.aligned.m64n256k16.f32.bf16.bf16 "
        "{%0, %1, %2, %3, %4, %5, %6, %7, %8, %9, %10, %11, %12, %13, %14, %15, %16, %17, %18, %19, %20, "
        "%21, %22, %23, %24, %25, %26, %27, %28, %29, %30, %31, %32, %33, %34, %35, %36, %37, %38, %39, %40, "
        "%41, %42, %43, %44, %45, %46, %47, %48, %49, %50, %51, %52, %53, %54, %55, %56, %57, %58, %59, %60, "
        "%61, %62, %63, %64, %65, %66, %67, %68, %69, %70, %71, %72, %73, %74, %75, %76, %77, %78, %79, %80, "
        "%81, %82, %83, %84, %85, %86, %87, %88, %89, %90, %91, %92, %93, %94, %95, %96, %97, %98, %99, "
        "%100, %101, %102, %103, %104, %105, %106, %107, %108, %109, %110, %111, %112, %113, %114, %115, "
        "%116, %117, %118, %119, %120, %121, %122, %123, %124, %125, %126, %127},"
        " %128, %129, p, 1, 1, 0, 1;\n}\n"
        : "=f"(d[0]), "=f"(d[1]), "=f"(d[2]), "=f"(d[3]), "=f"(d[4]), "=f"(d[5]), "=f"(d[6]), "=f"(d[7]),
        "=f"(d[8]), "=f"(d[9]), "=f"(d[10]), "=f"(d[11]), "=f"(d[12]), "=f"(d[13]), "=f"(d[14]), "=f"(d[15]),
        "=f"(d[16]), "=f"(d[17]), "=f"(d[18]), "=f"(d[19]), "=f"(d[20]), "=f"(d[21]), "=f"(d[22]),
        "=f"(d[23]), "=f"(d[24]), "=f"(d[25]), "=f"(d[26]), "=f"(d[27]), "=f"(d[28]), "=f"(d[29]),
        "=f"(d[30]), "=f"(d[31]), "=f"(d[32]), "=f"(d[33]), "=f"(d[34]), "=f"(d[35]), "=f"(d[36]),
        "=f"(d[37]), "=f"(d[38]), "=f"(d[39]), "=f"(d[40]), "=f"(d[41]), "=f"(d[42]), "=f"(d[43]),
        "=f"(d[44]), "=f"(d[45]), "=f"(d[46]), "=f"(d[47]), "=f"(d[48]), "=f"(d[49]), "=f"(d[50]),
        "=f"(d[51]), "=f"(d[52]), "=f"(d[53]), "=f"(d[54]), "=f"(d[55]), "=f"(d[56]), "=f"(d[57]),
        "=f"(d[58]), "=f"(d[59]), "=f"(d[60]), "=f"(d[61]), "=f"(d[62]), "=f"(d[63]), "=f"(d[64]),
        "=f"(d[65]), "=f"(d[66]), "=f"(d[67]), "=f"(d[68]), "=f"(d[69]), "=f"(d[70]), "=f"(d[71]),
        "=f"(d[72]), "=f"(d[73]), "=f"(d[74]), "=f"(d[75]), "=f"(d[76]), "=f"(d[77]), "=f"(d[78]),
        "=f"(d[79]), "=f"(d[80]), "=f"(d[81]), "=f"(d[82]), "=f"(d[83]), "=f"(d[84]), "=f"(d[85]),
        "=f"(d[86]), "=f"(d[87]), "=f"(d[88]), "=f"(d[89]), "=f"(d[90]), "=f"(d[91]), "=f"(d[92]),
        "=f"(d[93]), "=f"(d[94]), "=f"(d[95]), "=f"(d[96]), "=f"(d[97]), "=f"(d[98]), "=f"(d[99]),
        "=f"(d[100]), "=f"(d[101]), "=f"(d[102]), "=f"(d[103]), "=f"(d[104]), "=f"(d[105]), "=f"(d[106]),
        "=f"(d[107]), "=f"(d[108]), "=f"(d[109]), "=f"(d[110]), "=f"(d[111]), "=f"(d[112]), "=f"(d[113]),
        "=f"(d[114]), "=f"(d[115]), "=f"(d[116]), "=f"(d[117]), "=f"(d[118]), "=f"(d[119]), "=f"(d[120]),
        "=f"(d[121]), "=f"(d[122]), "=f"(d[123]), "=f"(d[124]), "=f"(d[125]), "=f"(d[126]), "=f"(d[127])
        : "l"(da), "l"(db));
}
__device__ __forceinline__ void wgmma_ss_n256_tb(float (&d)[128], uint64_t da, uint64_t db, int scale_d) {
    asm volatile("{\n.reg .pred p;\n"
        "setp.ne.b32 p, %130, 0;\n"
        "wgmma.mma_async.sync.aligned.m64n256k16.f32.bf16.bf16 "
        "{%0, %1, %2, %3, %4, %5, %6, %7, %8, %9, %10, %11, %12, %13, %14, %15, %16, %17, %18, %19, %20, "
        "%21, %22, %23, %24, %25, %26, %27, %28, %29, %30, %31, %32, %33, %34, %35, %36, %37, %38, %39, %40, "
        "%41, %42, %43, %44, %45, %46, %47, %48, %49, %50, %51, %52, %53, %54, %55, %56, %57, %58, %59, %60, "
        "%61, %62, %63, %64, %65, %66, %67, %68, %69, %70, %71, %72, %73, %74, %75, %76, %77, %78, %79, %80, "
        "%81, %82, %83, %84, %85, %86, %87, %88, %89, %90, %91, %92, %93, %94, %95, %96, %97, %98, %99, "
        "%100, %101, %102, %103, %104, %105, %106, %107, %108, %109, %110, %111, %112, %113, %114, %115, "
        "%116, %117, %118, %119, %120, %121, %122, %123, %124, %125, %126, %127},"
        " %128, %129, p, 1, 1, 0, 1;\n}\n"
        : "+f"(d[0]), "+f"(d[1]), "+f"(d[2]), "+f"(d[3]), "+f"(d[4]), "+f"(d[5]), "+f"(d[6]), "+f"(d[7]),
        "+f"(d[8]), "+f"(d[9]), "+f"(d[10]), "+f"(d[11]), "+f"(d[12]), "+f"(d[13]), "+f"(d[14]), "+f"(d[15]),
        "+f"(d[16]), "+f"(d[17]), "+f"(d[18]), "+f"(d[19]), "+f"(d[20]), "+f"(d[21]), "+f"(d[22]),
        "+f"(d[23]), "+f"(d[24]), "+f"(d[25]), "+f"(d[26]), "+f"(d[27]), "+f"(d[28]), "+f"(d[29]),
        "+f"(d[30]), "+f"(d[31]), "+f"(d[32]), "+f"(d[33]), "+f"(d[34]), "+f"(d[35]), "+f"(d[36]),
        "+f"(d[37]), "+f"(d[38]), "+f"(d[39]), "+f"(d[40]), "+f"(d[41]), "+f"(d[42]), "+f"(d[43]),
        "+f"(d[44]), "+f"(d[45]), "+f"(d[46]), "+f"(d[47]), "+f"(d[48]), "+f"(d[49]), "+f"(d[50]),
        "+f"(d[51]), "+f"(d[52]), "+f"(d[53]), "+f"(d[54]), "+f"(d[55]), "+f"(d[56]), "+f"(d[57]),
        "+f"(d[58]), "+f"(d[59]), "+f"(d[60]), "+f"(d[61]), "+f"(d[62]), "+f"(d[63]), "+f"(d[64]),
        "+f"(d[65]), "+f"(d[66]), "+f"(d[67]), "+f"(d[68]), "+f"(d[69]), "+f"(d[70]), "+f"(d[71]),
        "+f"(d[72]), "+f"(d[73]), "+f"(d[74]), "+f"(d[75]), "+f"(d[76]), "+f"(d[77]), "+f"(d[78]),
        "+f"(d[79]), "+f"(d[80]), "+f"(d[81]), "+f"(d[82]), "+f"(d[83]), "+f"(d[84]), "+f"(d[85]),
        "+f"(d[86]), "+f"(d[87]), "+f"(d[88]), "+f"(d[89]), "+f"(d[90]), "+f"(d[91]), "+f"(d[92]),
        "+f"(d[93]), "+f"(d[94]), "+f"(d[95]), "+f"(d[96]), "+f"(d[97]), "+f"(d[98]), "+f"(d[99]),
        "+f"(d[100]), "+f"(d[101]), "+f"(d[102]), "+f"(d[103]), "+f"(d[104]), "+f"(d[105]), "+f"(d[106]),
        "+f"(d[107]), "+f"(d[108]), "+f"(d[109]), "+f"(d[110]), "+f"(d[111]), "+f"(d[112]), "+f"(d[113]),
        "+f"(d[114]), "+f"(d[115]), "+f"(d[116]), "+f"(d[117]), "+f"(d[118]), "+f"(d[119]), "+f"(d[120]),
        "+f"(d[121]), "+f"(d[122]), "+f"(d[123]), "+f"(d[124]), "+f"(d[125]), "+f"(d[126]), "+f"(d[127])
        : "l"(da), "l"(db), "r"(scale_d));
}
__device__ __forceinline__ void wgmma_ss_n128(float (&d)[64], uint64_t da, uint64_t db, int scale_d) {
    asm volatile("{\n.reg .pred p;\n"
        "setp.ne.b32 p, %66, 0;\n"
        "wgmma.mma_async.sync.aligned.m64n128k16.f32.bf16.bf16 "
        "{%0, %1, %2, %3, %4, %5, %6, %7, %8, %9, %10, %11, %12, %13, %14, %15, %16, %17, %18, %19, %20, "
        "%21, %22, %23, %24, %25, %26, %27, %28, %29, %30, %31, %32, %33, %34, %35, %36, %37, %38, %39, %40, "
        "%41, %42, %43, %44, %45, %46, %47, %48, %49, %50, %51, %52, %53, %54, %55, %56, %57, %58, %59, %60, "
        "%61, %62, %63},"
        " %64, %65, p, 1, 1, 0, 0;\n}\n"
        : "+f"(d[0]), "+f"(d[1]), "+f"(d[2]), "+f"(d[3]), "+f"(d[4]), "+f"(d[5]), "+f"(d[6]), "+f"(d[7]),
        "+f"(d[8]), "+f"(d[9]), "+f"(d[10]), "+f"(d[11]), "+f"(d[12]), "+f"(d[13]), "+f"(d[14]), "+f"(d[15]),
        "+f"(d[16]), "+f"(d[17]), "+f"(d[18]), "+f"(d[19]), "+f"(d[20]), "+f"(d[21]), "+f"(d[22]),
        "+f"(d[23]), "+f"(d[24]), "+f"(d[25]), "+f"(d[26]), "+f"(d[27]), "+f"(d[28]), "+f"(d[29]),
        "+f"(d[30]), "+f"(d[31]), "+f"(d[32]), "+f"(d[33]), "+f"(d[34]), "+f"(d[35]), "+f"(d[36]),
        "+f"(d[37]), "+f"(d[38]), "+f"(d[39]), "+f"(d[40]), "+f"(d[41]), "+f"(d[42]), "+f"(d[43]),
        "+f"(d[44]), "+f"(d[45]), "+f"(d[46]), "+f"(d[47]), "+f"(d[48]), "+f"(d[49]), "+f"(d[50]),
        "+f"(d[51]), "+f"(d[52]), "+f"(d[53]), "+f"(d[54]), "+f"(d[55]), "+f"(d[56]), "+f"(d[57]),
        "+f"(d[58]), "+f"(d[59]), "+f"(d[60]), "+f"(d[61]), "+f"(d[62]), "+f"(d[63])
        : "l"(da), "l"(db), "r"(scale_d));
}
__device__ __forceinline__ void wgmma_rs_n128_tb(float (&d)[64], uint32_t a0, uint32_t a1, uint32_t a2, uint32_t a3, uint64_t db, int scale_d) {
    asm volatile("{\n.reg .pred p;\n"
        "setp.ne.b32 p, %69, 0;\n"
        "wgmma.mma_async.sync.aligned.m64n128k16.f32.bf16.bf16 "
        "{%0, %1, %2, %3, %4, %5, %6, %7, %8, %9, %10, %11, %12, %13, %14, %15, %16, %17, %18, %19, %20, "
        "%21, %22, %23, %24, %25, %26, %27, %28, %29, %30, %31, %32, %33, %34, %35, %36, %37, %38, %39, %40, "
        "%41, %42, %43, %44, %45, %46, %47, %48, %49, %50, %51, %52, %53, %54, %55, %56, %57, %58, %59, %60, "
        "%61, %62, %63},"
        " {%64, %65, %66, %67}, %68, p, 1, 1, 1;\n}\n"
        : "+f"(d[0]), "+f"(d[1]), "+f"(d[2]), "+f"(d[3]), "+f"(d[4]), "+f"(d[5]), "+f"(d[6]), "+f"(d[7]),
        "+f"(d[8]), "+f"(d[9]), "+f"(d[10]), "+f"(d[11]), "+f"(d[12]), "+f"(d[13]), "+f"(d[14]), "+f"(d[15]),
        "+f"(d[16]), "+f"(d[17]), "+f"(d[18]), "+f"(d[19]), "+f"(d[20]), "+f"(d[21]), "+f"(d[22]),
        "+f"(d[23]), "+f"(d[24]), "+f"(d[25]), "+f"(d[26]), "+f"(d[27]), "+f"(d[28]), "+f"(d[29]),
        "+f"(d[30]), "+f"(d[31]), "+f"(d[32]), "+f"(d[33]), "+f"(d[34]), "+f"(d[35]), "+f"(d[36]),
        "+f"(d[37]), "+f"(d[38]), "+f"(d[39]), "+f"(d[40]), "+f"(d[41]), "+f"(d[42]), "+f"(d[43]),
        "+f"(d[44]), "+f"(d[45]), "+f"(d[46]), "+f"(d[47]), "+f"(d[48]), "+f"(d[49]), "+f"(d[50]),
        "+f"(d[51]), "+f"(d[52]), "+f"(d[53]), "+f"(d[54]), "+f"(d[55]), "+f"(d[56]), "+f"(d[57]),
        "+f"(d[58]), "+f"(d[59]), "+f"(d[60]), "+f"(d[61]), "+f"(d[62]), "+f"(d[63])
        : "r"(a0), "r"(a1), "r"(a2), "r"(a3), "l"(db), "r"(scale_d));
}
__device__ __forceinline__ void wgmma_ss_n128_tb_init(float (&d)[64], uint64_t da, uint64_t db) {
    asm volatile("{\n.reg .pred p;\n"
        "setp.ne.b32 p, 0, 0;\n"
        "wgmma.mma_async.sync.aligned.m64n128k16.f32.bf16.bf16 "
        "{%0, %1, %2, %3, %4, %5, %6, %7, %8, %9, %10, %11, %12, %13, %14, %15, %16, %17, %18, %19, %20, "
        "%21, %22, %23, %24, %25, %26, %27, %28, %29, %30, %31, %32, %33, %34, %35, %36, %37, %38, %39, %40, "
        "%41, %42, %43, %44, %45, %46, %47, %48, %49, %50, %51, %52, %53, %54, %55, %56, %57, %58, %59, %60, "
        "%61, %62, %63},"
        " %64, %65, p, 1, 1, 0, 1;\n}\n"
        : "=f"(d[0]), "=f"(d[1]), "=f"(d[2]), "=f"(d[3]), "=f"(d[4]), "=f"(d[5]), "=f"(d[6]), "=f"(d[7]),
        "=f"(d[8]), "=f"(d[9]), "=f"(d[10]), "=f"(d[11]), "=f"(d[12]), "=f"(d[13]), "=f"(d[14]), "=f"(d[15]),
        "=f"(d[16]), "=f"(d[17]), "=f"(d[18]), "=f"(d[19]), "=f"(d[20]), "=f"(d[21]), "=f"(d[22]),
        "=f"(d[23]), "=f"(d[24]), "=f"(d[25]), "=f"(d[26]), "=f"(d[27]), "=f"(d[28]), "=f"(d[29]),
        "=f"(d[30]), "=f"(d[31]), "=f"(d[32]), "=f"(d[33]), "=f"(d[34]), "=f"(d[35]), "=f"(d[36]),
        "=f"(d[37]), "=f"(d[38]), "=f"(d[39]), "=f"(d[40]), "=f"(d[41]), "=f"(d[42]), "=f"(d[43]),
        "=f"(d[44]), "=f"(d[45]), "=f"(d[46]), "=f"(d[47]), "=f"(d[48]), "=f"(d[49]), "=f"(d[50]),
        "=f"(d[51]), "=f"(d[52]), "=f"(d[53]), "=f"(d[54]), "=f"(d[55]), "=f"(d[56]), "=f"(d[57]),
        "=f"(d[58]), "=f"(d[59]), "=f"(d[60]), "=f"(d[61]), "=f"(d[62]), "=f"(d[63])
        : "l"(da), "l"(db));
}
__device__ __forceinline__ void wgmma_ss_n128_tb(float (&d)[64], uint64_t da, uint64_t db, int scale_d) {
    asm volatile("{\n.reg .pred p;\n"
        "setp.ne.b32 p, %66, 0;\n"
        "wgmma.mma_async.sync.aligned.m64n128k16.f32.bf16.bf16 "
        "{%0, %1, %2, %3, %4, %5, %6, %7, %8, %9, %10, %11, %12, %13, %14, %15, %16, %17, %18, %19, %20, "
        "%21, %22, %23, %24, %25, %26, %27, %28, %29, %30, %31, %32, %33, %34, %35, %36, %37, %38, %39, %40, "
        "%41, %42, %43, %44, %45, %46, %47, %48, %49, %50, %51, %52, %53, %54, %55, %56, %57, %58, %59, %60, "
        "%61, %62, %63},"
        " %64, %65, p, 1, 1, 0, 1;\n}\n"
        : "+f"(d[0]), "+f"(d[1]), "+f"(d[2]), "+f"(d[3]), "+f"(d[4]), "+f"(d[5]), "+f"(d[6]), "+f"(d[7]),
        "+f"(d[8]), "+f"(d[9]), "+f"(d[10]), "+f"(d[11]), "+f"(d[12]), "+f"(d[13]), "+f"(d[14]), "+f"(d[15]),
        "+f"(d[16]), "+f"(d[17]), "+f"(d[18]), "+f"(d[19]), "+f"(d[20]), "+f"(d[21]), "+f"(d[22]),
        "+f"(d[23]), "+f"(d[24]), "+f"(d[25]), "+f"(d[26]), "+f"(d[27]), "+f"(d[28]), "+f"(d[29]),
        "+f"(d[30]), "+f"(d[31]), "+f"(d[32]), "+f"(d[33]), "+f"(d[34]), "+f"(d[35]), "+f"(d[36]),
        "+f"(d[37]), "+f"(d[38]), "+f"(d[39]), "+f"(d[40]), "+f"(d[41]), "+f"(d[42]), "+f"(d[43]),
        "+f"(d[44]), "+f"(d[45]), "+f"(d[46]), "+f"(d[47]), "+f"(d[48]), "+f"(d[49]), "+f"(d[50]),
        "+f"(d[51]), "+f"(d[52]), "+f"(d[53]), "+f"(d[54]), "+f"(d[55]), "+f"(d[56]), "+f"(d[57]),
        "+f"(d[58]), "+f"(d[59]), "+f"(d[60]), "+f"(d[61]), "+f"(d[62]), "+f"(d[63])
        : "l"(da), "l"(db), "r"(scale_d));
}

enum { M_X = 0, M_C, M_WQ, M_WQKV, M_WUK, M_WUV, M_WO, M_WOB, M_SCR_LD, M_SCR_LOC, M_SCR_LOQ, M_SCR_ST, M_COUNT };
enum { T_Q = 0, T_K, T_V, T_B, T_OUT, T_LOCAL, T_ATTN, T_END };
constexpr int NCTA = 132, NPAIR = NCTA / 2;
constexpr int NITEMS = 480 + 64 + 256;
constexpr int TRIPLES = 3, WIDE = 80 - 3 * TRIPLES;
struct Params {
    CUtensorMap m[M_COUNT];
    const __nv_bfloat16* x;
    const __nv_bfloat16* gate_w;
    const char* wo;
    __nv_bfloat16* out;
    uint32_t zero;
    uint16_t items[NITEMS];
    uint8_t ostep[80];
};
__device__ __forceinline__ int item_type(int it) { return it >> 13; }
__device__ __forceinline__ int item_row(int it) { return it & 15; }
__device__ __forceinline__ int item_col(int it) { return (it >> 4) & 31; }
__device__ __forceinline__ int item_asc(int it) { return (it >> 9) & 1; }
constexpr int ITEM_READY = 1 << 10;

struct __align__(128) Sync {
    unsigned long long count[4];
    __align__(128) unsigned long long ctx[16];
    unsigned next, next_out, done;
    __align__(128) unsigned step[32][2];
    unsigned split[32];
};
__device__ Sync g_sync;
__device__ uint4 g_part[128][8][256];

constexpr uint32_t GST_BYTES = 49152, SM_KV = 65536, SM_STAGING = 196608, SM_BARS = SM_STAGING + 32768;
constexpr uint32_t B_GFULL = 0, B_GEMPTY = 32, B_AFULL = 64, B_AEMPTY = 112, B_SFULL = 160, B_SEMPTY = 192,
                   B_IFULL = 224, B_IEMPTY = 288, B_XFREE = 352, B_WANT = 384, B_HALF = 416,
                   SM_ORDY = 448, SM_QUEUE = 456, B_ALT = 488, B_QFREE = 504, SM_GATE = 512, SM_TOTAL = SM_BARS + 1536;
constexpr int QDEPTH = 8;
#define PF_NAR 20
#define SPREAD 4
#define KMEET 14
constexpr int K_MEET = KMEET, K_SPLIT = KMEET + 12;
#define KF2 3
constexpr uint32_t LOC_PLANE = 72 * 128;
constexpr float SM_SCALE = 0.08838834764831845f * 1.4426950408889634f;
constexpr float LOC_SCALE = 0.17677669529663687f * 1.4426950408889634f;
constexpr float SUM_LIMIT = 1152921504606846976.f;
constexpr float REF_RANGE = 32.f;

__device__ __forceinline__ unsigned ld_acquire(const unsigned* p) {
    unsigned v; asm volatile("ld.acquire.gpu.global.u32 %0, [%1];" : "=r"(v) : "l"(p) : "memory"); return v;
}
__device__ __forceinline__ unsigned long long ld_acquire(const unsigned long long* p) {
    unsigned long long v; asm volatile("ld.acquire.gpu.global.u64 %0, [%1];" : "=l"(v) : "l"(p) : "memory"); return v;
}
__device__ __forceinline__ void st_b128(void* p, uint32_t a, uint32_t b, uint32_t c, uint32_t d) {
    asm volatile("{\n.reg .b128 v;\n.reg .b64 lo, hi;\nmov.b64 lo, {%1, %2};\nmov.b64 hi, {%3, %4};\nmov.b128 v, {lo, hi};\n"
                 "st.relaxed.gpu.global.b128 [%0], v;\n}\n" :: "l"(p), "r"(a), "r"(b), "r"(c), "r"(d) : "memory");
}
__device__ __forceinline__ void ld_b128(const void* p, uint32_t& a, uint32_t& b, uint32_t& c, uint32_t& d) {
    asm volatile("{\n.reg .b128 v;\n.reg .b64 lo, hi;\nld.relaxed.gpu.global.b128 v, [%4];\nmov.b128 {lo, hi}, v;\n"
                 "mov.b64 {%0, %1}, lo;\nmov.b64 {%2, %3}, hi;\n}\n" : "=r"(a), "=r"(b), "=r"(c), "=r"(d) : "l"(p) : "memory");
}
__device__ __forceinline__ void spin_guard(unsigned& n) {
    asm volatile("{\n.reg .pred P;\nadd.u32 %0, %0, 1;\nsetp.gt.u32 P, %0, 16777216;\n@P trap;\n}\n" : "+r"(n));
    if (n > 1) __nanosleep(100);
}
__device__ __forceinline__ void red_add(unsigned long long* p, unsigned long long v) {
    asm volatile("red.release.gpu.global.add.u64 [%0], %1;" :: "l"(p), "l"(v) : "memory");
}
__device__ __forceinline__ float rcp(float x) { float y; asm("rcp.approx.ftz.f32 %0, %1;" : "=f"(y) : "f"(x)); return y; }
__device__ __forceinline__ float lds_f32(uint32_t addr) {
    float v; asm volatile("ld.shared.f32 %0, [%1];" : "=f"(v) : "r"(addr) : "memory"); return v;
}
__device__ __forceinline__ void ldsm_x4(uint32_t (&r)[4], uint32_t addr) {
    asm volatile("ldmatrix.sync.aligned.m8n8.x4.shared.b16 {%0, %1, %2, %3}, [%4];"
                 : "=r"(r[0]), "=r"(r[1]), "=r"(r[2]), "=r"(r[3]) : "r"(addr) : "memory");
}
__device__ __forceinline__ void ldsm_x4_t(uint32_t (&r)[4], uint32_t addr) {
    asm volatile("ldmatrix.sync.aligned.m8n8.x4.trans.shared.b16 {%0, %1, %2, %3}, [%4];"
                 : "=r"(r[0]), "=r"(r[1]), "=r"(r[2]), "=r"(r[3]) : "r"(addr) : "memory");
}
__device__ __forceinline__ void mma_k16(float (&d)[4], const uint32_t (&a)[4], uint32_t b0, uint32_t b1) {
    asm("mma.sync.aligned.m16n8k16.row.col.f32.bf16.bf16.f32 {%0,%1,%2,%3}, {%4,%5,%6,%7}, {%8,%9}, {%0,%1,%2,%3};"
        : "+f"(d[0]), "+f"(d[1]), "+f"(d[2]), "+f"(d[3]) : "r"(a[0]), "r"(a[1]), "r"(a[2]), "r"(a[3]), "r"(b0), "r"(b1));
}
__device__ __forceinline__ void mma_k16_init(float (&d)[4], const uint32_t (&a)[4], uint32_t b0, uint32_t b1) {
    asm("{\n.reg .f32 z;\nmov.f32 z, 0f00000000;\n"
        "mma.sync.aligned.m16n8k16.row.col.f32.bf16.bf16.f32 {%0,%1,%2,%3}, {%4,%5,%6,%7}, {%8,%9}, {z,z,z,z};\n}\n"
        : "=f"(d[0]), "=f"(d[1]), "=f"(d[2]), "=f"(d[3]) : "r"(a[0]), "r"(a[1]), "r"(a[2]), "r"(a[3]), "r"(b0), "r"(b1));
}
__device__ __forceinline__ void mma_k8(float (&d)[4], uint32_t a0, uint32_t a1, uint32_t b0) {
    asm("mma.sync.aligned.m16n8k8.row.col.f32.bf16.bf16.f32 {%0,%1,%2,%3}, {%4,%5}, {%6}, {%0,%1,%2,%3};"
        : "+f"(d[0]), "+f"(d[1]), "+f"(d[2]), "+f"(d[3]) : "r"(a0), "r"(a1), "r"(b0));
}
template <typename T, int N> __device__ __forceinline__ void zero_regs(T (&d)[N]) {
#pragma unroll
    for (int i = 0; i < N; i++) d[i] = 0;
}
__device__ __forceinline__ float quad_max(float v) {
    v = fmaxf(v, __shfl_xor_sync(0xffffffffu, v, 1));
    return fmaxf(v, __shfl_xor_sync(0xffffffffu, v, 2));
}
__device__ __forceinline__ float quad_sum(float v) {
    v += __shfl_xor_sync(0xffffffffu, v, 1);
    return v + __shfl_xor_sync(0xffffffffu, v, 2);
}

__device__ __forceinline__ void qk_gemm(float (&s)[64], uint32_t q_lo, uint32_t k_lo) {
    const uint64_t dq = full_desc(q_lo), dk = full_desc(k_lo);
    fence_regs(s);
    wgmma_fence();
#pragma unroll
    for (int kk = 0; kk < 8; kk++) {
        const uint32_t o = (kk >> 2) * 1024 + (kk & 3) * 2;
        wgmma_ss_n128(s, dq + o, dk + o, kk != 0);
    }
    wgmma_commit();
}
__device__ __forceinline__ void pv_gemm(float (&o)[64], uint32_t (&p)[32], uint32_t v_lo, int accumulate) {
    const uint64_t dv = full_desc(v_lo);
    fence_regs(o);
    fence_regs(p);
    wgmma_fence();
#pragma unroll
    for (int kk = 0; kk < 8; kk++)
        wgmma_rs_n128_tb(o, p[4 * kk], p[4 * kk + 1], p[4 * kk + 2], p[4 * kk + 3], dv + kk * 128, kk != 0 || accumulate);
    wgmma_commit();
}
__device__ __forceinline__ void row_max(const float (&s)[64], float& x0, float& x1) {
    float z0 = fmaxf(s[0], s[1]), z1 = fmaxf(s[2], s[3]);
    x0 = fmaxf(s[4], s[5]); x1 = fmaxf(s[6], s[7]);
#pragma unroll
    for (int j = 2; j < 16; j += 2) {
        z0 = fmaxf(z0, fmaxf(s[4 * j], s[4 * j + 1]));
        z1 = fmaxf(z1, fmaxf(s[4 * j + 2], s[4 * j + 3]));
        x0 = fmaxf(x0, fmaxf(s[4 * j + 4], s[4 * j + 5]));
        x1 = fmaxf(x1, fmaxf(s[4 * j + 6], s[4 * j + 7]));
    }
    x0 = quad_max(fmaxf(x0, z0)); x1 = quad_max(fmaxf(x1, z1));
}
__device__ __forceinline__ void exp_pack(uint32_t (&p)[32], const float (&s)[64], float& r0, float& r1) {
#pragma unroll
    for (int j = 0; j < 16; j++) {
        const float e0 = ex2(s[4 * j]), e1 = ex2(s[4 * j + 1]), e2 = ex2(s[4 * j + 2]), e3 = ex2(s[4 * j + 3]);
        if (j == 0) { r0 = e0 + e1; r1 = e2 + e3; }
        else { r0 += e0 + e1; r1 += e2 + e3; }
        p[2 * j] = pack_bf16(e0, e1);
        p[2 * j + 1] = pack_bf16(e2, e3);
    }
}
__device__ __forceinline__ void shift_rows(float (&s)[64], float d0, float d1) {
#pragma unroll
    for (int j = 0; j < 16; j++) { s[4 * j] -= d0; s[4 * j + 1] -= d0; s[4 * j + 2] -= d1; s[4 * j + 3] -= d1; }
}
constexpr float MASKED = -3e38f;
template <int J0>
__device__ __forceinline__ void mask_triangle(float (&s)[64], float thr) {
#pragma unroll
    for (int j = 0; j < 16; j++) {
        const float m = __saturatef((float)(8 * (j >> 1) + (j & 1)) - thr);
        const int i = 4 * (J0 + (j >> 1)) + (j & 1);
        s[i] = fmaf(m, MASKED, s[i]);
        if (j < 14) s[i + 6] = fmaf(m, MASKED, s[i + 6]);
    }
}
__device__ __forceinline__ void causal_mask(float (&s)[64], float thr, int wg) {
    asm volatile("" : "+f"(thr));
    if (wg == 0) {
        mask_triangle<0>(s, thr);
#pragma unroll
        for (int j = 32; j < 64; j++) s[j] += MASKED;
    } else {
        mask_triangle<8>(s, thr);
    }
}

__global__ void __cluster_dims__(2, 1, 1) __launch_bounds__(384, 1) fused_kernel(const __grid_constant__ Params prm) {
    extern __shared__ __align__(1024) uint8_t smem[];
    const uint32_t sb = smem_u32(smem), bars = sb + SM_BARS;
    const int warp = __shfl_sync(0xffffffffu, threadIdx.x >> 5, 0), lane = threadIdx.x & 31;

    const uint32_t rank = cluster_rank();
    const uint32_t bars0 = map_cta(bars, 0), bars_peer = map_cta(bars, rank ^ 1);

    auto first_item = [&]() -> int {
        uint32_t pair = blockIdx.x >> 1;
        asm volatile("" : "+r"(pair));
        return prm.items[pair] + item_row(prm.items[pair]) + rank;
    };
    if (threadIdx.x == 256) {
        for (int k = 0; k < 4; k++) mbar_init(bars + B_GFULL + 8 * k, 1);
        asm volatile("fence.mbarrier_init.release.cluster;" ::: "memory");
        fence_proxy_async_smem();
    }
    if (threadIdx.x == 128) {
        for (int i = 0; i < 4; i++) { mbar_init(bars + B_GEMPTY + 8 * i, 16); mbar_init(bars + B_XFREE + 8 * i, 1); }
        for (int i = 0; i < 6; i++) { mbar_init(bars + B_AFULL + 8 * i, 1); mbar_init(bars + B_AEMPTY + 8 * i, i < 2 ? 8 : 16); }
        for (int i = 0; i < 4; i++) { mbar_init(bars + B_SFULL + 8 * i, 4); mbar_init(bars + B_SEMPTY + 8 * i, 1); }
        for (int i = 0; i < QDEPTH; i++) { mbar_init(bars + B_IFULL + 8 * i, 1); mbar_init(bars + B_IEMPTY + 8 * i, 23); }
        mbar_init(bars + B_WANT, 2);
        for (int i = 0; i < 4; i++) mbar_init(bars + B_HALF + 8 * i, 1);
        mbar_init(bars + B_ALT, 4); mbar_init(bars + B_ALT + 8, 4); mbar_init(bars + B_QFREE, 2);
        asm volatile("st.shared.u64 [%0], 0;" :: "r"(bars + SM_ORDY) : "memory");
        asm volatile("fence.mbarrier_init.release.cluster;\nfence.acq_rel.cta;" ::: "memory");
    }
    __syncwarp();
    asm volatile("barrier.cluster.arrive.relaxed.aligned;" ::: "memory");
    if (threadIdx.x == 256) {
        const int first_it = first_item();
        for (int k = 0; k < 4; k++) {
            const uint32_t dst = sb + k * GST_BYTES, fb = bars + B_GFULL + 8 * k;
            mbar_expect_tx(fb, GST_BYTES);
            tma_load_3d(dst, &prm.m[M_X], fb, k * 64, item_row(first_it) * 128, 0);
            tma_load_3d(dst + 16384, &prm.m[M_WQKV], fb, 0, k * 64, item_col(first_it) * 4);
            tma_load_3d(dst + 32768, &prm.m[M_WQKV], fb, 0, k * 64, item_col(first_it) * 4 + 2);
        }
    }
    __syncwarp();
    asm volatile("barrier.cluster.wait.acquire.aligned;" ::: "memory");

    uint32_t qn = 0;
    auto next_item = [&](bool releaser, bool bounded = true) -> int {
        const uint32_t slot = qn % QDEPTH;
        if (bounded) mbar_wait(bars + B_IFULL + 8 * slot, (qn / QDEPTH) & 1);
        else mbar_spin(bars + B_IFULL + 8 * slot, (qn / QDEPTH) & 1);
        uint32_t it;
        asm volatile("ld.shared.u32 %0, [%1];" : "=r"(it) : "r"(bars + SM_QUEUE + 4 * slot) : "memory");
        mbar_arrive_cluster_if(releaser, bars0 + B_IEMPTY + 8 * slot);
        qn++;
        return it;
    };

    if (warp < 4) {
        reg_dec<40>();
        if (warp == 0) {
            {
                uint32_t gph = 0;
                const uint32_t prank = __shfl_sync(0xffffffffu, rank, 0);
                int k0 = 4;
                uint32_t kv = 0, kvph = 1;
                uint32_t qc = 0;
                uint32_t oneed = 0;
                uint32_t xph = 0;
                uint32_t need_g = 0, need_a = 0;
                auto a_parity = [&](uint32_t b) { return b < 2 ? (((qc + 1 - b) >> 1) & 1) ^ 1 : kvph ^ (b - 2 < kv); };
                int held_type = T_END;
                uint32_t borrowed = 0, fph = 0;
                auto reclaim_q = [&]() { if (borrowed) { mbar_wait(bars + B_QFREE, fph); fph ^= 1; borrowed = 0; } };
                auto acquire_g = [&](uint32_t st, bool shared) {
                    mbar_wait(bars + B_GEMPTY + 8 * st, gph);
                    if (need_a) {
                        reclaim_q();
                        const uint32_t b = (3 * st) >> 1;
                        mbar_wait(bars + B_AEMPTY + 8 * b, a_parity(b));
                        mbar_wait(bars + B_AEMPTY + 8 * (b + 1), a_parity(b + 1));
                        if (shared) {
                            mbar_arrive_cluster_if(lane == 0, bars_peer + B_XFREE + 8 * st);
                            mbar_wait(bars + B_XFREE + 8 * st, xph);
                        }
                        if (st == 3) { need_a = 0; xph ^= shared; }
                    }
                };
                auto leave_gemm = [&](uint32_t b) {
                    if (need_g >> b & 1) {
                        mbar_wait(bars + B_GEMPTY + 8 * ((2 * b) / 3), gph);
                        mbar_wait(bars + B_GEMPTY + 8 * ((2 * b + 1) / 3), gph);
                        need_g &= ~(1u << b);
                    }
                };
                const CUtensorMap* tile_map = &prm.m[M_SCR_LD];
                asm volatile("" : "+l"(tile_map));
                auto load_q = [&](int grp, int row) {
                    const uint32_t b = qc & 1, dst = sb + b * 32768, fb = bars + B_AFULL + 8 * b;
                    mbar_wait(bars + B_AEMPTY + 8 * b, a_parity(b));
                    leave_gemm(b);
                    reclaim_q();
                    borrowed = held_type != T_END;
                    held_type = T_END;
                    warp_expect_tx(fb, 32768 + 512);
                    warp_tma_load(dst, tile_map, fb, 0, row, grp);
                    warp_tma_load(dst + 16384, tile_map, fb, 64, row, grp);
                    warp_bulk_load(bars + SM_GATE + b * 512, &g_gate[row], 512, fb);
                    qc++;
                };
                auto load_kv = [&](int grp, int row, bool shared) {
                    uint32_t fb = bars + B_AFULL + 16 + 8 * kv, mine = sb + SM_KV + kv * 32768 + prank * 16384;
                    int c_mine = prank * 64;
                    asm volatile("" : "+r"(mine), "+r"(fb), "+r"(row), "+r"(grp), "+r"(c_mine));
                    if (need_g) leave_gemm(2 + kv);
                    mbar_wait(fb + B_AEMPTY - B_AFULL, kvph);
                    warp_expect_tx(fb, grp < 0 ? 0 : 32768);
                    if (shared) {
                        warp_tma_load_pair(mine, tile_map, fb, c_mine, row, grp);
                    } else if (grp >= 0) {
                        warp_tma_load(mine, tile_map, fb, c_mine, row, grp);
                        warp_tma_load(mine + 16384 - prank * 32768, tile_map, fb, 64 - c_mine, row, grp);
                    } else {
                        mbar_arrive_cluster_n_if(lane < 2, map_cta(fb, lane & 1) + B_AEMPTY - B_AFULL, 8);
                    }
                    if (++kv == 4) { kv = 0; kvph ^= 1; }
                };
                auto request = [&]() { mbar_arrive_cluster_if(lane == 0, bars0 + B_WANT); };
                int pv_grp = -1, pv_row = 0;
                bool pv_shared = false, peer_longer = false;
                auto inputs_seen = [&](uint32_t word, unsigned& n) -> uint32_t {
                    uint32_t v;
                    spin_guard(n);
                    asm volatile("ld.acquire.cta.shared.u32 %0, [%1];" : "=r"(v) : "r"(bars + SM_ORDY + 4 * word) : "memory");
                    return __shfl_sync(0xffffffffu, v, 0);
                };
                auto fetch = [&]() -> int {
                    const int nx = __shfl_sync(0xffffffffu, next_item(lane == 0), 0);
                    if ((item_type(nx) == T_ATTN || item_type(nx) == T_LOCAL) && !(nx & ITEM_READY)) {
                        oneed += 256;
                        for (unsigned n = 0; inputs_seen(1, n) < oneed;) {}
                    }
                    if (item_type(nx) == T_ATTN) load_q(G_Q + item_col(nx), item_row(nx) * 128);
                    return nx;
                };
                int nxt = first_item();
                while (true) {
                    const int it = nxt >= 0 ? nxt : fetch();
                    nxt = -1;
                    const int type = item_type(it), m = item_row(it), c = item_col(it);
                    const int asc = item_asc(it), nu = type == T_ATTN ? 2 * m + 2 : 0;
                    const int uend = nu + ((type == T_ATTN ? m < 2 : pv_grp >= 0) ? 3 : 0), ureq = 2 * max(m - 2 - (asc & m), 0);
#pragma unroll 1
                    for (int u = 0; u < uend; u++) {
                        int grp = pv_grp, row = pv_row;
                        bool shared = pv_shared;
                        if (u >= nu) {
                            if (u == nu + 1) pv_grp = -1;
                            else if (peer_longer) { grp = -1; shared = false; }
                            else continue;
                        } else {
                            const int j = asc ? u >> 1 : m - (u >> 1);
                            if (u & 1) {
                                pv_grp = G_V + c; pv_row = j * 128; pv_shared = j != (m | 1);
                                peer_longer = asc & ~m & 1;
                                if (u == nu - 1 && (m & 1) && item_type(nxt) == T_END) mbar_arrive_cluster_n_if(lane == 0, bars0 + B_WANT, 2);
                                if (grp < 0) continue;
                            } else {
                                if (u == ureq) request();
                                if (u == 2 * m && m > 0) nxt = fetch();
                                grp = G_K + c; row = j * 128; shared = j != (m | 1);
                            }
                        }
                        load_kv(grp, row, shared);
                    }
                    if (type == T_END) break;
                    if (type == T_ATTN) {
                        need_a = 1;
                    } else if (type == T_LOCAL) {
                        if (held_type == T_B && !(it & ITEM_READY)) held_type = T_END;
                        request();
#pragma unroll 1
                        for (uint32_t st = 0; st < 4; st++) {
                            acquire_g(st, false);
                            const uint32_t dst = sb + st * GST_BYTES, fb = bars + B_GFULL + 8 * st;
                            warp_expect_tx(fb, st == 0 ? 32768 + 512 : st == 3 ? 0 : 4 * LOC_PLANE);
                            if (st == 3) break;
                            if (st == 0) warp_bulk_load(dst + 4 * LOC_PLANE, &g_gate[m * 128], 512, fb);
#pragma unroll 1
                            for (int i = 0; i < 4; i++)
                                warp_tma_load(dst + i * LOC_PLANE, &prm.m[st ? M_SCR_LOC : M_SCR_LOQ], fb, i * 64, m * 64 - (st ? 8 : 0), G_B + 8 * st + c);
                        }
                        gph ^= 1;
                        need_g = 63;
                    } else {
                        const int nk = type == T_K || type == T_V ? 8 : 16;
                        const CUtensorMap* ma = &prm.m[nk == 8 ? M_C : M_X];
                        const CUtensorMap* mb = &prm.m[type == T_Q ? M_WQ : type == T_K ? M_WUK : type == T_V ? M_WUV : M_WQKV];
                        for (int k = k0; k < nk; k++) {
                            if (k == nk - 3) request();
                            const uint32_t st = k & 3;
                            uint32_t dst = sb + st * GST_BYTES, fb = bars + B_GFULL + 8 * st, dstb = dst + 16384 + prank * 16384;
                            int a0 = k * 64, a1 = m * 128, b2 = c * 4 + 2 * prank;
                            asm volatile("" : "+r"(dst), "+r"(fb), "+r"(dstb), "+r"(a0), "+r"(a1), "+r"(b2), "+l"(ma), "+l"(mb));
                            acquire_g(st, true);
                            warp_expect_tx(fb, GST_BYTES);
                            warp_tma_load(dst, ma, fb, a0, a1, 0);
                            warp_tma_load_pair(dstb, mb, fb, 0, a0, b2);
                            if (st == 3) gph ^= 1;
                        }
                        need_g = 63;
                        held_type = type;
                        k0 = 0;
                    }
                }
                if (!need_a) request();
                const int it = __shfl_sync(0xffffffffu, next_item(lane == 0), 0);
                int nk = 0;
                if (item_type(it) == T_OUT) {
                    const int m = item_row(it), c = item_col(it), half = c & 1;
                    nk = 80;
                    for (int k = 0; k < nk; k++) {
                        if (k == K_SPLIT) nk = 2 * TRIPLES + (__shfl_sync(0xffffffffu, next_item(lane == 0), 0) & 127);
                        const int kn = k + 2 * TRIPLES - nk, first = kn >= 0 && !(kn & 1);
                        const int s = kn >= 0 ? WIDE + (3 * kn + 1) / 2 : half ? WIDE - 1 - k : k;
                        const uint32_t sa = prm.ostep[s], sa2 = prm.ostep[s + first], sw = prm.ostep[s - (kn >= 0 && !first ? prank : 0)];
                        for (unsigned n = 0; !(inputs_seen(sa >> 6, n) >> (sa >> 1 & 31) & 1);) {}
                        if (first) for (unsigned n = 0; !(inputs_seen(sa2 >> 6, n) >> (sa2 >> 1 & 31) & 1);) {}
                        const uint32_t st = k & 3;
                        uint32_t dst = sb + st * GST_BYTES, fb = bars + B_GFULL + 8 * st;
                        uint32_t dstb = dst + 16384 + (first ? 0 : prank * 16384), skipb = first && (kn >> 1 & 1) != prank;
                        int a0 = (sa & 1) * 64, a1 = m * 128, a2 = (sa >> 1) + (sa < 64 ? G_CTX : G_LOC - 32);
                        int b1 = (sw & 63) * 64, b2 = (c >> 1) * 4 + 2 * (kn >= 0 ? half : half ^ prank);
                        const CUtensorMap* mb = &prm.m[sw >= 64 ? M_WOB : M_WO];
                        asm volatile("" : "+r"(dst), "+r"(fb), "+r"(dstb), "+r"(skipb), "+r"(a0), "+r"(a1), "+r"(a2), "+r"(b1), "+r"(b2), "+l"(mb));
                        acquire_g(st, true);
                        warp_expect_tx(fb, GST_BYTES);
                        warp_tma_load(dst, tile_map, fb, a0, a1, a2);
                        if (!skipb) warp_tma_load_pair(dstb, mb, fb, 0, b1, b2);
                        if (first) warp_tma_load(dst + 32768, tile_map, fb, (sa2 & 1) * 64, a1, (sa2 >> 1) + (sa2 < 64 ? G_CTX : G_LOC - 32));
                        if (k < K_SPLIT && lane == 0 && !prank)
                            asm volatile("st.relaxed.gpu.global.u32 [%0], %1;" :: "l"(&g_sync.step[0][0] + m * 4 + c), "r"(k) : "memory");
                        if (k == K_MEET) request();
                        if (PF_NAR && (uint32_t)(k - PF_NAR) < (3 * TRIPLES + 1) / 2) {
                            const uint32_t g = prm.ostep[79 - 2 * (k - PF_NAR)] >> 1;
                            warp_prefetch((const char*)g_scr + (uint32_t)((G_CTX + g) * (SEQ * 256) + m * 32768 + c * 4096), 4096);
                            warp_prefetch(prm.wo + (uint32_t)(g * 262144 + (m * 8 + c) * 2048), 2048);
                        }
                        if (st == 3) gph ^= 1;
                    }
                    for (unsigned n = 0; ~inputs_seen(0, n) || inputs_seen(1, n) != 255;) {}
                }
                for (uint32_t st = 0; st < 4; st++) { mbar_wait(bars + B_GEMPTY + 8 * st, gph ^ (st < (nk & 3))); mbar_wait(bars + B_AEMPTY + 16 + 8 * st, a_parity(2 + st)); }
                unsigned left = 0;
                if (lane == 0) left = atomicAdd(&g_sync.done, 1u);
                if (__shfl_sync(0xffffffffu, left, 0) == NCTA - 1)
                    for (int i = lane; i < sizeof(Sync) / 8; i += 32) ((unsigned long long*)&g_sync)[i] = 0;
            }
        } else if (warp <= 2) {
            if (blockIdx.x < SEQ / 16) {
                const uint32_t r0 = 16 * blockIdx.x + 8 * (warp - 1), gbuf = bars + SM_GATE + 4 * (r0 & 15);
                float z[4];
#pragma unroll 1
                for (uint32_t i = 0; i < 8; i++) {
                    const uint32_t off = (i & 3) * 512 + lane * 16;
                    const uint4* xp = (const uint4*)((const char*)prm.x + ((r0 + (i & 4)) * 2048 + off));
                    const uint4 wv = __ldg((const uint4*)((const char*)prm.gate_w + off));
                    uint4 xv[4];
#pragma unroll
                    for (int r = 0; r < 4; r++) { xv[r] = __ldg(xp + r * 128); if (!(i & 3)) z[r] = 0.f; }
                    const uint32_t ws[4] = {wv.x, wv.y, wv.z, wv.w};
#pragma unroll
                    for (int e = 0; e < 4; e++)
#pragma unroll
                        for (int r = 0; r < 4; r++) {
                            const uint32_t xs = e == 0 ? xv[r].x : e == 1 ? xv[r].y : e == 2 ? xv[r].z : xv[r].w;
                            z[r] = fmaf(__uint_as_float(xs << 16), __uint_as_float(ws[e] << 16), z[r]);
                            z[r] = fmaf(__uint_as_float(xs & 0xffff0000u), __uint_as_float(ws[e] & 0xffff0000u), z[r]);
                        }
                    if ((i & 3) == 3) {
#pragma unroll
                        for (int o = 16; o > 0; o >>= 1)
#pragma unroll
                            for (int r = 0; r < 4; r++) z[r] += __shfl_xor_sync(0xffffffffu, z[r], o);
                        const float zr = lane & 2 ? (lane & 1 ? z[3] : z[2]) : (lane & 1 ? z[1] : z[0]);
                        asm volatile("st.shared.f32 [%0], %1;" :: "r"(gbuf + 4 * ((i & 4) + (lane & 3))), "f"(1.f / (1.f + __expf(-zr))) : "memory");
                    }
                }
                fence_proxy_async_smem();
                __syncwarp();
                warp_bulk_store((char*)g_gate + 4 * r0, gbuf, 32);
                bulk_commit();
                bulk_wait<0>();
                __syncwarp();
                if (lane == 0) red_add(&g_sync.count[3], 1);
            }
            __syncwarp();
            {
                const int w = warp - 1;
                uint32_t sph = 0, aph = 0, nann = 0, nattn = 0;
                int unsent = 0, nunsent = 0;
                bool urgent = false;
                auto announce = [&]() {
                    if (!urgent) return;
                    bulk_wait<0>();
                    __syncwarp();
                    const uint32_t hb = bars + B_HALF + 8 * (nann & 3);
                    if (w == 0) {
                        mbar_arrive_if(lane == 0, hb);
                    } else {
                        mbar_wait(hb, (nann >> 2) & 1);
                        const uint32_t type = item_type(unsent), m = item_row(unsent), c = item_col(unsent);
                        const uint32_t word = type < T_B ? c >> 3 : type == T_B ? 2 : offsetof(Sync, ctx) / 8 + m;
                        const uint32_t bit = type < T_B ? 8 * (c & 7) : type == T_B ? 4 * m : type == T_LOCAL ? 32 + c : c;
                        if (lane < nunsent) red_add((unsigned long long*)((char*)&g_sync + 8 * word), 1ull << bit);
                        __syncwarp();
                    }
                    nann++;
                    nunsent = 0; urgent = false;
                };
                auto store_item = [&](int it, bool borrow, bool now) {
                    const int type = item_type(it), m = item_row(it), c = item_col(it);
                    const int npair = type < T_OUT ? 2 : 1;
                    const bool local = type == T_LOCAL;
                    const int grp = type == T_Q ? G_Q + 2 * c : type == T_K ? G_K + 2 * c : type == T_V ? G_V + 2 * c : type == T_B ? G_B + 2 * c
                                  : type == T_ATTN ? G_CTX + c : G_LOC + c;
                    for (int pr = 0; pr < npair; pr++) {
                        if (borrow && pr) {
                            mbar_wait(bars + B_ALT + 8 * w, aph);
                            fence_proxy_async_smem();
                            aph ^= 1;
                            for (int b = 0; b < 2; b++)
                                warp_tma_store(&prm.m[M_SCR_ST], sb + ((nattn & 1) ^ 1) * 32768 + w * 16384 + b * 8192, b * 64, m * 128 + w * 64, grp + 1);
                            bulk_commit();
                            bulk_wait_read<0>();
                            __syncwarp();
                            mbar_arrive_if(lane == 0, bars + B_QFREE);
                            break;
                        }
                        for (int b = 0; b < 2; b++) {
                            if (!__all_sync(0xffffffffu, mbar_test(bars + B_SFULL + 16 * w + 8 * b, sph))) announce();
                            mbar_wait(bars + B_SFULL + 16 * w + 8 * b, sph);
                            fence_proxy_async_smem();
                            warp_tma_store(&prm.m[local ? M_SCR_LOQ : M_SCR_ST], sb + SM_STAGING + w * 16384 + b * 8192,
                                         local ? b * 128 + w * 64 : b * 64, local ? m * 64 : m * 128 + w * 64, grp + pr);
                            bulk_commit();
                            bulk_wait_read<0>();
                            __syncwarp();
                            mbar_arrive_if(lane == 0, bars + B_SEMPTY + 16 * w + 8 * b);
                        }
                        sph ^= 1;
                    }
                    announce();
                    if (lane == nunsent) unsent = it;
                    nunsent++;
                    urgent = now || nunsent == 32 || !local;
                };
                int held = first_item();
                while (true) {
                    if (!__all_sync(0xffffffffu, mbar_test(bars + B_IFULL + 8 * (qn % QDEPTH), (qn / QDEPTH) & 1))) announce();
                    const int it = __shfl_sync(0xffffffffu, next_item(lane == 0), 0), type = item_type(it);
                    const bool keep_held = type == T_LOCAL && (item_type(held) != T_B || (it & ITEM_READY));
                    if (type >= T_ATTN && held < 0 && nunsent) urgent = true;
                    for (int pass = held < 0 || keep_held; pass < 2; pass++) {
                        if (pass && (type < T_OUT || type == T_END)) break;
                        store_item(pass ? it : held, !pass && type == T_ATTN, type >= T_ATTN);
                    }
                    if (type == T_END) break;
                    nattn += type == T_ATTN;
                    if (!keep_held) held = type < T_OUT ? it : -1;
                }
                announce();
                if (item_type(next_item(lane == 0)) == T_OUT) next_item(lane == 0);
            }
        } else {
            if (elect_one()) {
                uint32_t ordy = 0;
                unsigned long long cnt_lo = 0, cnt_hi = 0;
                int late = 0;
                auto refresh = [&]() {
                    if (!late && cnt_lo == 0xccccccccccccccccull && cnt_hi == SEQ / 8) late = 1;
                    asm volatile("ld.acquire.gpu.global.v2.u64 {%0, %1}, [%2];" : "=l"(cnt_lo), "=l"(cnt_hi) : "l"(late ? &g_sync.count[0] : &g_sync.count[2]) : "memory");
                };
                auto inputs_ready = [&](int it) -> bool {
                    const int m = item_row(it), c = item_col(it);
                    if (item_type(it) == T_ATTN) return late && ((c < 16 ? cnt_lo : cnt_hi) >> (4 * (c & 14)) & 255) == 48;
                    return late || (cnt_hi == SEQ / 8 && (cnt_lo >> (4 * m) & 15) == 12 && (cnt_lo >> (4 * max(m - 1, 0)) & 15) == 12);
                };
                auto publish = [&](int it, int step) {
                    const uint32_t slot = qn % QDEPTH;
                    mbar_wait(bars + B_IEMPTY + 8 * slot, ((qn / QDEPTH) & 1) ^ 1);
                    for (uint32_t r = 0; r < 2; r++) {
                        const uint32_t rb = map_cta(bars, r);
                        asm volatile("mbarrier.arrive.expect_tx.shared::cluster.b64 _, [%0], 4;" :: "r"(rb + B_IFULL + 8 * slot) : "memory");
                        asm volatile("st.async.shared::cluster.mbarrier::complete_tx::bytes.u32 [%0], %1, [%2];"
                                     :: "r"(rb + SM_QUEUE + 4 * slot), "r"(it + r * step), "r"(rb + B_IFULL + 8 * slot) : "memory");
                    }
                    qn++;
                };
                int asc = 1;
                int it;
                do {
                    if (rank == 0) {
                        mbar_wait(bars + B_WANT, qn & 1);
                        unsigned i;
                        asm volatile("atom.relaxed.gpu.global.add.u32 %0, [%1], 1;" : "=r"(i) : "l"(&g_sync.next) : "memory");
                        if (cnt_lo != 0x3030303030303030ull || cnt_hi != cnt_lo) refresh();
                        i += NPAIR;
                        const int pit = i < NITEMS ? prm.items[i] : T_END << 13, type = item_type(pit);
                        int step = type == T_LOCAL ? 16 : 1;
                        it = pit + (pit & (step == 1 ? 15 : 0x1f0));
                        if (type == T_ATTN) {
                            if (!asc) { it += 1; step = -1; }
                            it |= asc << 9;
                        }
                        asc = type != T_ATTN || item_row(pit) == 0 || !asc;
                        if (inputs_ready(it)) it |= ITEM_READY;
                        publish(it, step);
                    } else {
                        it = next_item(true);
                    }
                    if ((item_type(it) == T_ATTN || item_type(it) == T_LOCAL) && !(it & ITEM_READY)) {
                        unsigned n = 0;
                        while (!inputs_ready(it)) { refresh(); spin_guard(n); }
                        asm volatile("st.release.cta.shared.u32 [%0], %1;" :: "r"(bars + SM_ORDY + 4), "r"(ordy += 256) : "memory");
                    }
                } while (item_type(it) != T_END);
                if (rank == 0) {
                    mbar_wait(bars + B_WANT, qn & 1);
                    const unsigned i = atomicAdd(&g_sync.next_out, 1u), t = i < 32 ? 31 - i : i - 32;
                    it = i < 64 ? T_OUT << 13 | ((t & 3) * 2 + (i >> 5)) << 4 | (t >> 2) * 2 : T_END << 13;
                    publish(it, 1);
                } else {
                    it = next_item(true);
                }
                if (item_type(it) == T_OUT) {
                    const uint32_t m = item_row(it), half = item_col(it) & 1, tile = m * 2 + (item_col(it) >> 1);
                    unsigned* split = (unsigned*)((char*)g_sync.split + 4 * tile);
                    unsigned long long rdy = 0;
                    int state = rank ? 2 : 0;
                    for (unsigned n = 0; rdy != 0xffffffffffull || state < 2; spin_guard(n)) {
                        if (rdy != 0xffffffffffull) {
                            rdy = ld_acquire((const unsigned long long*)((char*)g_sync.ctx + 8 * m));
                            asm volatile("st.release.cta.shared.u64 [%0], %1;" :: "r"(bars + SM_ORDY), "l"(rdy) : "memory");
                        }
                        unsigned steps = 0;
                        if (state == 1) {
                            steps = ld_acquire(split);
                        } else if (state == 0 && mbar_test(bars + B_WANT, qn & 1)) {
                            state = 1;
                            unsigned seen;
                            asm volatile("atom.acq_rel.gpu.global.exch.b32 %0, [%1], 1;" : "=r"(seen) : "l"(split) : "memory");
                            if (seen) {
                                const unsigned long long v = ld_acquire((const unsigned long long*)((char*)g_sync.step + 8 * tile));
                                const int d = (int)(v >> 32) - (int)v;
                                steps = (WIDE + min(max(half ? d : -d, K_MEET - K_SPLIT), K_SPLIT - K_MEET)) >> 1;
                                atomicExch(split, WIDE - steps);
                            }
                        }
                        if (steps > 1) { publish(T_END << 13 | steps, 0); state = 2; PMARK(1, 0xF400 + steps); }
                    }
                    if (rank) next_item(true);
                }
                if (rank == 0) for (uint32_t n = qn; n < qn + QDEPTH; n++) mbar_wait(bars + B_IEMPTY + 8 * (n % QDEPTH), ((n / QDEPTH) & 1) ^ 1);
            }
        }
    } else {
        reg_inc<232>();
        const int wg = (warp >> 2) - 1, wq = warp & 3;
        uint32_t gph = 0;
        uint32_t kvn = 0;
        const uint32_t dA = make_desc(sb + wg * 8192, 16);
        uint32_t ti = 0;
        uint32_t sph = 1;
        const uint32_t stg = sb + SM_STAGING + wg * 16384;
        const uint32_t stg_lane = stg + (wq * 16 + (lane & 15)) * 128 + (((lane >> 4) ^ (lane & 7)) << 4);
        auto write_blocks = [&](auto n, uint32_t off, const uint32_t* v) {
            uint32_t a = stg_lane;
            asm volatile("" : "+r"(a));
            a += off;
#pragma unroll
            for (int j = 0; j < decltype(n)::value; j++)
                stmatrix_x4((a ^ (32 * (j & 3))) + (j >> 2) * 8192, v[4 * j], v[4 * j + 1], v[4 * j + 2], v[4 * j + 3]);
        };
        auto release = [&](uint32_t bar) { mbar_arrive_if(lane == 0, bars + bar); };
        const uint32_t bars_lane = map_cta(bars, lane & 1);
        auto release_stage = [&](uint32_t st) { mbar_arrive_cluster_if(lane < 2, bars_lane + B_GEMPTY + 8 * st); };
        auto take_item = [&]() -> int {
            return __shfl_sync(0xffffffffu, next_item(lane == 0, false), 0);
        };
        auto stage_acquire = [&](int b) { mbar_spin(bars + B_SEMPTY + 16 * wg + 8 * b, sph); };
        auto stage_publish = [&](int b) {
            __syncwarp();
            release(B_SFULL + 16 * wg + 8 * b);
        };
        auto stage_chunk = [&](int b, const uint32_t* v) {
            stage_acquire(b);
            write_blocks(std::integral_constant<int, 4>(), b * 8192, v);
            stage_publish(b);
            if (b) sph ^= 1;
        };
        auto publish_pair = [&]() {
            __syncwarp();
            mbar_arrive_if(lane < 2, bars + B_SFULL + 16 * wg + 8 * lane);
            sph ^= 1;
        };
        auto gemm_step = [&](float (&acc)[128], uint32_t dB, int& k) {
            const uint32_t st = k & 3;
            wgmma_wait<0>();
            release_stage((k - 1) & 3);
            mbar_spin(bars + B_GFULL + 8 * st, gph);
            const uint64_t da = full_desc(dA + st * (GST_BYTES >> 4)), db = full_desc(dB + st * (GST_BYTES >> 4));
            wgmma_fence();
#pragma unroll
            for (int kk = 0; kk < 4; kk++) wgmma_ss_n256_tb(acc, da + 2 * kk, db + 128 * kk, 1);
            wgmma_commit();
            gph ^= st == 3;
            k++;
        };
        if (wg == 1) bar_arrive(1, 256);
        int it = first_item();
        while (true) {
            if (item_type(it) <= T_LOCAL) {
                float acc[128];
                uint32_t pk[64];
                bool pending = false;
                bool held_b = false;
                zero_regs(pk);
                const uint32_t dB = make_desc(sb + 16384, 8192);
                do {
                    const int type = item_type(it);
                    if (type == T_LOCAL) {
                        int ln = lane;
                        asm volatile("" : "+r"(ln));
                        const int g = ln >> 2, t = ln & 3, par = wq & 1;
                        const uint32_t hc = (wq >> 1) * 4, pl = sb + (par * 2 + wg) * LOC_PLANE;
                        const uint32_t a16 = (ln & 15) * 128 + (((hc + (ln >> 4)) ^ (ln & 7)) << 4), a8 = (ln & 7) * 128 + (((hc + (ln >> 3)) ^ (ln & 7)) << 4);
                        const bool first0 = 2 * t > g, first1 = 2 * t + 1 > g;
                        const uint32_t fmask = (first0 ? 0xffffu : 0u) | (first1 ? 0xffff0000u : 0u);
                        const bool edge = item_row(it) == 0;
                        uint32_t q[4][2][4], kf[9][4], vf[9][4];
                        float w[8];
                        mbar_spin(bars + B_GFULL, gph);
#pragma unroll
                        for (int u = 0; u < 4; u++) { ldsm_x4(q[u][0], pl + u * 2048 + a16); ldsm_x4(q[u][1], pl + u * 2048 + (a16 ^ 32)); }
#pragma unroll
                        for (int j = 0; j < 8; j++) w[j] = lds_f32(sb + 4 * LOC_PLANE + 4 * (2 * g + par) + 64 * j);
                        __syncwarp();
                        release_stage(0);
                        mbar_spin(bars + B_GFULL + 8, gph);
#pragma unroll
                        for (int n = 0; n < 9; n++) ldsm_x4(kf[n], pl + GST_BYTES + n * 1024 + a8);
                        __syncwarp();
                        release_stage(1);
                        float s[8][2];
#pragma unroll
                        for (int u = 0; u < 4; u++) {
                            float d[3][4];
#pragma unroll
                            for (int nt = 0; nt < 3; nt++) {
                                mma_k16_init(d[nt], q[u][0], kf[2 * u + nt][0], kf[2 * u + nt][1]);
                                mma_k16(d[nt], q[u][1], kf[2 * u + nt][2], kf[2 * u + nt][3]);
                            }
                            if (u == 0 && edge) { d[0][0] = -INFINITY; d[0][1] = -INFINITY; }
                            s[2 * u][0] = first0 ? d[0][0] : d[1][0]; s[2 * u][1] = first1 ? d[0][1] : d[1][1];
                            s[2 * u + 1][0] = first0 ? d[1][2] : d[2][2]; s[2 * u + 1][1] = first1 ? d[1][3] : d[2][3];
                        }
                        mbar_spin(bars + B_GFULL + 16, gph);
#pragma unroll
                        for (int u = 0; u < 4; u++) { ldsm_x4_t(vf[2 * u], pl + 2 * GST_BYTES + u * 2048 + a16); ldsm_x4_t(vf[2 * u + 1], pl + 2 * GST_BYTES + u * 2048 + (a16 ^ 32)); }
                        ldsm_x4_t(vf[8], pl + 2 * GST_BYTES + 8192 + a8);
                        __syncwarp();
                        release_stage(2);
                        float x[8];
#pragma unroll
                        for (int j = 0; j < 8; j++) x[j] = fmaxf(s[j][0], s[j][1]);
#pragma unroll
                        for (int o = 1; o < 4; o *= 2)
#pragma unroll
                            for (int j = 0; j < 8; j++) x[j] = fmaxf(x[j], __shfl_xor_sync(0xffffffffu, x[j], o));
#pragma unroll
                        for (int j = 0; j < 8; j++) {
                            const float n = x[j] * -LOC_SCALE;
                            s[j][0] = ex2(fmaf(s[j][0], LOC_SCALE, n)); s[j][1] = ex2(fmaf(s[j][1], LOC_SCALE, n));
                            x[j] = s[j][0] + s[j][1];
                        }
#pragma unroll
                        for (int o = 1; o < 4; o *= 2)
#pragma unroll
                            for (int j = 0; j < 8; j++) x[j] += __shfl_xor_sync(0xffffffffu, x[j], o);
                        mbar_spin(bars + B_GFULL + 24, gph);
                        release_stage(3);
                        it = take_item();
                        uint32_t ob[4][8];
#pragma unroll
                        for (int u = 0; u < 4; u++) {
                            const float r0 = rcp(x[2 * u]), r1 = rcp(x[2 * u + 1]), f0 = fmaf(-w[2 * u], r0, r0), f1 = fmaf(-w[2 * u + 1], r1, r1);
                            const uint32_t p0 = pack_bf16(s[2 * u][0] * f0, s[2 * u][1] * f0), p1 = pack_bf16(s[2 * u + 1][0] * f1, s[2 * u + 1][1] * f1);
                            const uint32_t pa[4] = {p0 & fmask, 0, p0 & ~fmask, p1 & fmask};
#pragma unroll
                            for (int c = 0; c < 4; c++) {
                                float ol[4];
                                mma_k16_init(ol, pa, vf[2 * u + (c >> 1)][2 * (c & 1)], vf[2 * u + (c >> 1)][2 * (c & 1) + 1]);
                                mma_k8(ol, 0, p1 & ~fmask, u < 3 ? vf[2 * u + 2 + (c >> 1)][2 * (c & 1)] : vf[8][c]);
                                ob[u][2 * c] = pack_bf16(ol[0], ol[1]);
                                ob[u][2 * c + 1] = pack_bf16(ol[2], ol[3]);
                            }
                        }
                        stage_acquire(0); stage_acquire(1);
#pragma unroll
                        for (int u = 0; u < 4; u++) {
                            stmatrix_x4(stg + par * 8192 + u * 2048 + a16, ob[u][0], ob[u][1], ob[u][2], ob[u][3]);
                            stmatrix_x4(stg + par * 8192 + u * 2048 + (a16 ^ 32), ob[u][4], ob[u][5], ob[u][6], ob[u][7]);
                        }
                        publish_pair();
                        bar_sync(4, 256);
                        gph ^= 1;
                        continue;
                    }
                    mbar_spin(bars + B_GFULL, gph);
                    bool more;
                    do {
                        wgmma_fence();
                        wgmma_ss_n256_tb_init(acc, full_desc(dA), full_desc(dB));
#pragma unroll
                        for (int kk = 1; kk < 4; kk++) wgmma_ss_n256_tb(acc, full_desc(dA) + 2 * kk, full_desc(dB) + 128 * kk, 1);
                        wgmma_commit();
                        const int nk = item_type(it) == T_K || item_type(it) == T_V ? 8 : 16;
                        int k = 1;
                        do {
                            if (pending) {
                                const int kf = k - 1 - wg;
                                if (kf == 0) stage_chunk(0, pk);
                                else if (kf == 1) stage_chunk(1, pk + 16);
                                else if (kf == KF2) stage_chunk(0, pk + 32);
                                else if (kf == KF2 + 1) stage_chunk(1, pk + 48);
                            }
                            gemm_step(acc, dB, k);
                        } while (k < nk);
                        held_b = item_type(it) == T_B;
                        const bool is_q = item_type(it) == T_Q;
                        it = take_item();
                        more = item_type(it) < T_LOCAL;
                        if (more) mbar_spin(bars + B_GFULL, gph);
                        wgmma_wait<0>();
                        fence_regs(acc);
                        release_stage(3);
                        if (is_q) {
#pragma unroll
                            for (int j = 0; j < 128; j++) acc[j] *= SM_SCALE;
                        }
#pragma unroll
                        for (int j = 0; j < 64; j++) pk[j] = pack_bf16(acc[2 * j], acc[2 * j + 1]);
                        pending = true;
                    } while (more);
                } while (item_type(it) < T_LOCAL || (item_type(it) == T_LOCAL && (!held_b || (it & ITEM_READY))));
                if (pending) {
                    stage_acquire(0); stage_acquire(1);
                    write_blocks(std::integral_constant<int, 8>(), 0, pk);
                    const bool borrow = item_type(it) == T_ATTN;
                    if (borrow) {
                        mbar_spin(bars + B_GEMPTY, gph ^ 1); mbar_spin(bars + B_GEMPTY + 8, gph ^ 1);
                    } else {
                        publish_pair();
                        stage_acquire(0); stage_acquire(1);
                    }
                    write_blocks(std::integral_constant<int, 8>(), borrow ? ((ti & 1) ^ 1) * 32768 - SM_STAGING : 0, pk + 32);
                    publish_pair();
                    mbar_arrive_if(lane == 0 && borrow, bars + B_ALT + 8 * wg);
                }
                if (item_type(it) == T_END) { it = take_item(); break; }
            } else {
                float o[64], s[64];
                uint32_t pa[32], pb[32];
                zero_regs(o); zero_regs(s); zero_regs(pa);
                float n0 = 0.f, n1 = 0.f;
                bool shifted = false;
                float l0 = 1.f, l1 = 1.f, f0 = 0.f, f1 = 0.f, g0 = 0.f, g1 = 0.f;
                uint32_t has_pv = 0;
                int first = 0;
                int pending = 0;
                const uint32_t dK = make_desc(sb + SM_KV, 16), dV = make_desc(sb + SM_KV, 16384);
                const uint32_t lane_off = bars_lane - bars + B_AEMPTY - B_AFULL;
                int cur = 0;
                uint32_t qoff = 0;
                const int row = wg * 64 + wq * 16 + (lane >> 2);
                const float thr = (row & 63) - (lane & 3) * 2;
                uint32_t peek = 0;
                bool peek_ok = false, q_ok = false;
                auto kv_wait = [&](uint32_t n) { mbar_spin(bars + B_AFULL + 16 + 8 * (n & 3), (n >> 2) & 1); };
                auto kv_release = [&](uint32_t n) { mbar_arrive_cluster_if(lane < 2, bars_lane + B_AEMPTY + 16 + 8 * (n & 3)); };
                struct Slot { uint32_t bar, par, off; } slot[4];
                auto align = [&]() {
#pragma unroll
                    for (uint32_t i = 0; i < 4; i++) {
                        const uint32_t n = kvn + (i == 1 ? has_pv : i);
                        slot[i].bar = bars + B_AFULL + 16 + 8 * (n & 3); slot[i].par = (n >> 2) & 1; slot[i].off = (n & 3) * 2048;
                    }
                };
                align();
                auto scale_o = [&]() {
#pragma unroll
                    for (int j = 0; j < 16; j++) { o[4 * j] *= f0; o[4 * j + 1] *= f0; o[4 * j + 2] *= f1; o[4 * j + 3] *= f1; }
                };
                auto pack_o = [&](uint32_t (&v)[32]) {
#pragma unroll
                    for (int j = 0; j < 32; j++) v[j] = pack_bf16(o[2 * j], o[2 * j + 1]);
                };
                auto scales = [&]() { f0 = g0 * rcp(quad_sum(l0)); f1 = g1 * rcp(quad_sum(l1)); };
                auto step = [&](auto even, uint32_t (&pin)[32], uint32_t (&pout)[32], bool fresh, bool diag, bool last) {
                    constexpr bool EVEN = decltype(even)::value;
                    Slot& sk = slot[EVEN ? 0 : 2];
                    Slot& sv = slot[EVEN ? 1 : 3];
                    kvn += EVEN ? 1 + has_pv : 2;
                    mbar_spin(sk.bar, sk.par);
                    bar_sync(1 + wg, 256);
                    qk_gemm(s, dA + qoff, dK + sk.off);
                    if (EVEN && fresh) {
                        scales();
                        g0 = lds_f32(bars + SM_GATE + (ti & 1) * 512 + 4 * row); g1 = lds_f32(bars + SM_GATE + (ti & 1) * 512 + 4 * row + 32);
                        ti++;
                        n0 = 0.f; n1 = 0.f; l0 = 0.f; l1 = 0.f;
                        shifted = false;
                        if (has_pv) { stage_acquire(0); stage_acquire(1); }
                    }
                    if (!EVEN && pending) {
                        pack_o(pout);
                        write_blocks(std::integral_constant<int, 8>(), 0, pout);
                        publish_pair();
                    }
                    mbar_spin(sv.bar, sv.par);
                    pv_gemm(o, pin, dV + sv.off, EVEN || !first);
                    bar_arrive(2 - wg, 256);
                    sk.par ^= 1; sv.par ^= 1;
                    wgmma_wait<1>();
                    fence_regs(s);
                    mbar_arrive_cluster_if(lane < 2 && (!EVEN || has_pv), sk.bar + lane_off);
                    mbar_arrive_if(lane == 0 && last, bars + B_AEMPTY + 8 * ((ti - 1) & 1));
                    if (diag || shifted) {
                        if (diag) causal_mask(s, thr, wg);
                        if (shifted) shift_rows(s, n0, n1);
                    }
                    q_ok = mbar_test(bars + B_AFULL + 8 * (ti & 1), (ti >> 1) & 1);
                    peek_ok = mbar_test(bars + B_IFULL + 8 * (qn % QDEPTH), (qn / QDEPTH) & 1);
                    asm volatile("ld.shared.u32 %0, [%1];" : "=r"(peek) : "r"(bars + SM_QUEUE + 4 * (qn % QDEPTH)) : "memory");
                    float r0, r1;
                    exp_pack(pout, s, r0, r1);
                    if (__any_sync(0xffffffffu, fmaxf(r0, r1) >= SUM_LIMIT || (EVEN && fresh && !(lane & 3) && !(fminf(s[0], s[2]) >= -REF_RANGE)))) {
                        float x0, x1;
                        row_max(s, x0, x1);
                        if (!(EVEN && fresh)) { x0 = fmaxf(x0, 0.f); x1 = fmaxf(x1, 0.f); }
                        float a0 = ex2(-x0), a1 = ex2(-x1);
                        n0 += x0; n1 += x1;
                        shifted = true;
                        if (EVEN && fresh) { a0 = 1.f; a1 = 1.f; }
                        l0 *= a0; l1 *= a1;
                        wgmma_wait<0>();
                        fence_regs(o);
#pragma unroll
                        for (int q = 0; q < 16; q++) { o[4 * q] *= a0; o[4 * q + 1] *= a0; o[4 * q + 2] *= a1; o[4 * q + 3] *= a1; }
                        shift_rows(s, x0, x1);
                        exp_pack(pout, s, r0, r1);
                    }
                    l0 += r0; l1 += r1;
                    wgmma_wait<0>();
                    fence_regs(o);
                    fence_regs(pin);
                    mbar_arrive_cluster_if(lane < 2, sv.bar + lane_off);
                };
                auto copy_p = [&]() {
#pragma unroll
                    for (int j = 0; j < 32; j++) pa[j] = __float_as_uint(__uint_as_float(pb[j]) + __uint_as_float(prm.zero));
                };
                int rem = 0;
                mbar_spin(bars + B_AFULL + 8 * (ti & 1), (ti >> 1) & 1);
                while (true) {
                    const bool fresh = rem == 0;
                    if (fresh) {
                        if (has_pv) {
                            if (__all_sync(0xffffffffu, peek_ok)) {
                                mbar_arrive_cluster_if(lane == 0, bars0 + B_IEMPTY + 8 * (qn % QDEPTH));
                                qn++;
                                it = __shfl_sync(0xffffffffu, peek, 0);
                            } else {
                                it = take_item();
                            }
                            if (item_row(cur) < 2 || item_type(it) != T_ATTN) break;
                            if (!q_ok) mbar_spin(bars + B_AFULL + 8 * (ti & 1), (ti >> 1) & 1);
                        }
                        cur = it;
                        qoff = (ti & 1) * 2048;
                    }
                    const bool last = fresh ? item_row(cur) == 0 : rem == 1;
                    step(std::true_type(), pa, pb, fresh, item_asc(cur) ? last : fresh, last);
                    first = fresh;
                    if (fresh) {
                        pending = has_pv; has_pv = 1;
                        if (!pending) { kvn -= 2; align(); kvn += 2; slot[0].par ^= 1; slot[1].par ^= 1; }
                        else scale_o();
                        rem = item_row(cur);
                        if (rem == 0) {
                            copy_p();
                            continue;
                        }
                    } else if (--rem == 0) {
                        copy_p();
                        align();
                        continue;
                    }
                    step(std::false_type(), pb, pa, false, item_asc(cur) && rem == 1, rem == 1);
                    pending = 0; first = 0;
                    rem--;
                }
                const uint32_t skip = item_asc(cur) & ~item_row(cur) & 1;
                kvn += skip;
                const bool end = item_type(it) == T_END;
#pragma unroll 1
                for (int pass = pending ? 0 : 1; pass < 2; pass++) {
                    if (pass) {
                        kv_wait(kvn);
                        pv_gemm(o, pa, dV + (kvn & 3) * 2048, !first);
                        scales();
                        stage_acquire(0); stage_acquire(1);
                        if (end) it = take_item();
                        wgmma_wait<0>();
                        fence_regs(o);
                        kv_release(kvn);
                        kvn += 1 + skip;
                        scale_o();
                    }
                    pack_o(pb);
                    write_blocks(std::integral_constant<int, 8>(), 0, pb);
                    publish_pair();
                }
                if (end) break;
            }
        }
        if (item_type(it) == T_OUT) {
            float acc[128];
            const uint32_t dB = make_desc(sb + 16384, 8192);
            mbar_spin(bars + B_GFULL, gph);
            wgmma_fence();
            wgmma_ss_n256_tb_init(acc, full_desc(dA), full_desc(dB));
#pragma unroll
            for (int kk = 1; kk < 4; kk++) wgmma_ss_n256_tb(acc, full_desc(dA) + 2 * kk, full_desc(dB) + 128 * kk, 1);
            wgmma_commit();
            uint32_t ln;
            asm volatile("mov.u32 %0, %%laneid;" : "=r"(ln));
            const uint32_t slot = (it & 127) * 32768 + (wg * 128 + wq * 32 + ln) * 16;
            char* const mine = (char*)g_part + slot;
            int k = 1, nk = 80;
            do {
                if (k == K_MEET - 5) {
#pragma unroll
                    for (int j = 0; j < 8; j++) st_b128(mine + j * 4096, 0, 0, 0, 0);
                    __syncwarp();
                }
                if (k == K_SPLIT) nk = take_item() & 127;
                gemm_step(acc, dB, k);
            } while (k < nk);
            float lo[64];
            uint32_t pk[32];
            char* const other = (char*)g_part + (slot ^ (16 * 32768));
            auto fetch_other = [&]() {
#pragma unroll
                for (int j = 0; j < 8; j++) ld_b128(other + j * 4096, pk[4 * j], pk[4 * j + 1], pk[4 * j + 2], pk[4 * j + 3]);
            };
            auto triple = [&](auto first) {
                const uint32_t s0 = k & 3, s1 = (k + 1) & 3, o0 = s0 * (GST_BYTES >> 4), o1 = s1 * (GST_BYTES >> 4);
                wgmma_wait<0>();
                mbar_arrive_cluster_if(ln < (decltype(first)::value ? 2 : 4), bars_lane + B_GEMPTY + 8 * ((k - 1 - (ln >> 1)) & 3));
                mbar_spin(bars + B_GFULL + 8 * s0, gph);
                gph ^= s0 == 3;
                wgmma_fence();
#pragma unroll
                for (int kk = 0; kk < 4; kk++) {
                    if (decltype(first)::value && kk == 0) wgmma_ss_n128_tb_init(lo, full_desc(dA + o0), full_desc(dB + o0));
                    else wgmma_ss_n128_tb(lo, full_desc(dA + o0) + 2 * kk, full_desc(dB + o0) + 128 * kk, 1);
                }
                mbar_spin(bars + B_GFULL + 8 * s1, gph);
                gph ^= s1 == 3;
                wgmma_fence();
#pragma unroll
                for (int kk = 0; kk < 4; kk++) wgmma_ss_n128_tb(lo, full_desc(dA + o0 + 2048) + 2 * kk, full_desc(dB + o1 + 1024) + 128 * kk, 1);
#pragma unroll
                for (int kk = 0; kk < 4; kk++) wgmma_ss_n128_tb(lo, full_desc(dA + o1) + 2 * kk, full_desc(dB + o1) + 128 * kk, 1);
                wgmma_commit();
                k += 2;
            };
            triple(std::true_type());
            fence_regs(acc);
#pragma unroll
            for (int j = 0; j < 8; j++) {
                uint32_t v[4];
#pragma unroll
                for (int i = 0; i < 4; i++) v[i] = pack_bf16(acc[64 + 8 * j + 2 * i], acc[65 + 8 * j + 2 * i]);
                if (j == SPREAD) triple(std::false_type());
                st_b128(mine + j * 4096, ~v[0], v[1], v[2], v[3]);
            }
            triple(std::false_type());
            while (true) {
                fetch_other();
                bool miss = false;
#pragma unroll
                for (int j = 0; j < 8; j++) miss |= pk[4 * j] == 0;
                if (!__any_sync(0xffffffffu, miss)) break;
                while (__any_sync(0xffffffffu, pk[28] == 0)) ld_b128(other + 7 * 4096, pk[28], pk[29], pk[30], pk[31]);
            }
#pragma unroll
            for (int j = 0; j < 32; j++) {
                const uint32_t v = j & 3 ? pk[j] : ~pk[j];
                acc[2 * j] += __uint_as_float(v << 16); acc[2 * j + 1] += __uint_as_float(v & 0xffff0000u);
                asm volatile("" : "+f"(acc[2 * j]), "+f"(acc[2 * j + 1]) :: "memory");
            }
            stage_acquire(0); stage_acquire(1);
            wgmma_wait<0>();
            fence_regs(lo);
            mbar_arrive_cluster_if(ln < 4, bars_lane + B_GEMPTY + 8 * ((k - 1 - (ln >> 1)) & 3));
#pragma unroll
            for (int j = 0; j < 32; j++)
                pk[j] = pack_bf16(acc[2 * j] + lo[2 * j], acc[2 * j + 1] + lo[2 * j + 1]);
            write_blocks(std::integral_constant<int, 8>(), 0, pk);
            __syncwarp();
            uint4* dst = (uint4*)((char*)prm.out + (uint32_t)((item_row(it) * 128 + wg * 64 + wq * 16 + (ln >> 4)) * 2048 + item_col(it) * 256 + (ln & 15) * 16));
#pragma unroll
            for (int j = 0; j < 8; j++) {
                const int r = 2 * j + (ln >> 4);
                uint4 v;
                asm volatile("ld.shared.v4.u32 {%0, %1, %2, %3}, [%4];" : "=r"(v.x), "=r"(v.y), "=r"(v.z), "=r"(v.w)
                             : "r"(stg + wq * 2048 + r * 128 + (ln & 8) * 1024 + (((ln & 7) ^ (r & 7)) << 4)) : "memory");
                dst[j * 256] = v;
            }
        }
    }
}

typedef CUresult (*EncodeFn)(CUtensorMap*, CUtensorMapDataType, cuuint32_t, void*, const cuuint64_t*, const cuuint64_t*,
                             const cuuint32_t*, const cuuint32_t*, CUtensorMapInterleave, CUtensorMapSwizzle,
                             CUtensorMapL2promotion, CUtensorMapFloatOOBfill);

void encode3(EncodeFn fn, CUtensorMap* m, const void* ptr, uint64_t d0, uint64_t d1, uint64_t d2, uint64_t s1, uint64_t s2,
             uint32_t b0, uint32_t b1, uint32_t b2) {
    cuuint64_t dims[3] = {d0, d1, d2};
    cuuint64_t strides[2] = {s1, s2};
    cuuint32_t box[3] = {b0, b1, b2};
    cuuint32_t es[3] = {1, 1, 1};
    fn(m, CU_TENSOR_MAP_DATA_TYPE_BFLOAT16, 3, const_cast<void*>(ptr), dims, strides, box, es, CU_TENSOR_MAP_INTERLEAVE_NONE,
       CU_TENSOR_MAP_SWIZZLE_128B, CU_TENSOR_MAP_L2_PROMOTION_NONE, CU_TENSOR_MAP_FLOAT_OOB_FILL_NONE);
}
void map_act(EncodeFn fn, CUtensorMap* m, const void* p, int rows, int cols, int box_rows) {
    encode3(fn, m, p, cols, rows, 1, (uint64_t)cols * 2, (uint64_t)cols * rows * 2, 64, box_rows, 1);
}
void map_wgt(EncodeFn fn, CUtensorMap* m, const void* p, int K, int N) {
    encode3(fn, m, p, 64, K, N / 64, (uint64_t)N * 2, 128, 64, 64, 2);
}

void build_schedule(Params& p) {
    int n = 0;
    auto add = [&](int type, int col, int row) { p.items[n++] = (uint16_t)(type << 13 | col << 4 | row); };
    auto add_qkv = [&](int c) {
        for (int m = 0; m < 8; m++) add(T_Q, c, m);
        for (int m = 0; m < 8; m++) add(T_K, c, m);
        for (int m = 0; m < 8; m++) add(T_V, c, m);
    };
    int ldist = 200, ldist2 = 260, lstep = 8, beta = 26, tail = 32, late = 6, early = 8, epos = 100;
    int order[16] = {6, 7, 8, 9, 10, 11, 12, 13, 14, 15, 5, 4, 3, 2, 1, 0};
    uint16_t proj[480];
    for (int m = 0; m < 8; m++) for (int c = 0; c < 12; c++) add(T_B, c, m);
    for (int c = 0; c < 16; c++) add_qkv(c);
    for (int i = 0; i < 480; i++) proj[i] = p.items[i];
    n = 0;
    for (int i = 0, l = 0; i < 480; i++) {
        p.items[n++] = proj[i];
        for (; l < 64 && i >= (l < 40 ? ldist + lstep * l / 8 : ldist2 + lstep * (l - 40) / 8); l++) add(T_LOCAL, l & 3, l >> 2);
    }
    const int a0 = n;
    for (int key = 0; key < 4000; key++)
        for (int r = 0; r < 32; r++)
            for (int j = 7; j >= 0; j--)
                if ((j ? (7 - j) * 40 + r * beta : 3999) == key) add(T_ATTN, 2 * order[r >> 1] + (r & 1), j);
    int t0 = n;
    for (int work = 0; work < 32 * 136 * tail / 100;) work += 4 * (p.items[--t0] & 15) + 3;
    for (int i = t0 + 1; i < n; i++)
        for (int j = i; j > t0 && (p.items[j] & 15) > (p.items[j - 1] & 15); j--) { const uint16_t t = p.items[j]; p.items[j] = p.items[j - 1]; p.items[j - 1] = t; }
    for (int r = early - 1; r >= 0; r--) {
        const uint16_t t = p.items[n - 32 + early - 1];
        for (int j = n - 32 + early - 1; j > n - epos; j--) p.items[j] = p.items[j - 1];
        p.items[n - epos] = t;
    }
    for (int moved = 0; moved < 2 && late >= 0; moved++)
        for (int i = a0; i < n; i++)
            if (p.items[i] == (T_ATTN << 13 | (2 * order[15] + moved) << 4 | late)) {
                for (int j = i; j + 1 < n; j++) p.items[j] = p.items[j + 1];
                p.items[n - 1] = (uint16_t)(T_ATTN << 13 | (2 * order[15] + moved) << 4 | late);
                break;
            }
    for (int s = 0, lo = 0, hi = WIDE - 1; s < 80; s++) {
        const int r = s / 2, g = r < 8 ? 32 + r : 2 * order[r / 2 - 4] + (r & 1);
        p.ostep[s >= WIDE ? s : r & 1 ? hi-- : lo++] = (uint8_t)(2 * g + (s & 1));
    }
}

void build_params(Params& p, void* const* d_in, void* d_out) {
    void* fnp = nullptr;
    cudaDriverEntryPointQueryResult qr;
    cudaGetDriverEntryPoint("cuTensorMapEncodeTiled", &fnp, cudaEnableDefault, &qr);
    EncodeFn fn = (EncodeFn)fnp;
    void* scr = nullptr;
    cudaGetSymbolAddress(&scr, g_scr);
    map_act(fn, &p.m[M_X], d_in[0], SEQ, 1024, 128);
    map_act(fn, &p.m[M_C], d_in[1], SEQ, 512, 128);
    map_wgt(fn, &p.m[M_WQ], d_in[2], 1024, 4096);
    map_wgt(fn, &p.m[M_WUK], d_in[3], 512, 4096);
    map_wgt(fn, &p.m[M_WUV], d_in[4], 512, 4096);
    map_wgt(fn, &p.m[M_WO], d_in[5], 4096, 1024);
    map_wgt(fn, &p.m[M_WQKV], d_in[7], 1024, 3072);
    map_wgt(fn, &p.m[M_WOB], d_in[8], 1024, 1024);
    encode3(fn, &p.m[M_SCR_LD], scr, 128, SEQ, G_TOTAL, 256, (uint64_t)SEQ * 256, 64, 128, 1);
    encode3(fn, &p.m[M_SCR_LOC], scr, 256, SEQ / 2, G_TOTAL, 512, (uint64_t)SEQ * 256, 64, 72, 1);
    encode3(fn, &p.m[M_SCR_LOQ], scr, 256, SEQ / 2, G_TOTAL, 512, (uint64_t)SEQ * 256, 64, 64, 1);
    encode3(fn, &p.m[M_SCR_ST], scr, 128, SEQ, G_TOTAL, 256, (uint64_t)SEQ * 256, 64, 64, 1);
    p.x = (const __nv_bfloat16*)d_in[0];
    p.gate_w = (const __nv_bfloat16*)d_in[9];
    p.zero = 0;
    p.wo = (const char*)d_in[5];
    p.out = (__nv_bfloat16*)d_out;
    build_schedule(p);
}

}

extern "C" void kernel_launch(void* const* d_in, const int* in_sizes, int n_in, void* d_out, int out_size) {
    (void)in_sizes; (void)n_in; (void)out_size;
    Params p;
    build_params(p, d_in, d_out);
    cudaFuncSetAttribute(fused_kernel, cudaFuncAttributeMaxDynamicSharedMemorySize, SM_TOTAL);
    fused_kernel<<<NCTA, 384, SM_TOTAL>>>(p);
}
```

```cpp
#include <cuda_runtime.h>
#include <cuda_bf16.h>
#include <cuda.h>
#include <stddef.h>
#include <stdint.h>
#include <type_traits>

namespace {

constexpr int SEQ = 2048;
constexpr int G_Q = 0, G_K = 32, G_V = 64, G_B = 96, G_CTX = G_Q, G_LOC = G_B, G_TOTAL = 120;

__device__ __align__(1024) __nv_bfloat16 g_scr[(size_t)G_TOTAL * SEQ * 128];
__device__ __align__(128) float g_gate[SEQ];

__device__ __forceinline__ uint32_t smem_u32(const void* p) { return (uint32_t)__cvta_generic_to_shared(p); }
__device__ __forceinline__ bool elect_one() {
    uint32_t p;
    asm volatile("{\n.reg .pred P;\nelect.sync _|P, 0xffffffff;\nselp.u32 %0, 1, 0, P;\n}\n" : "=r"(p));
    return p != 0;
}
__device__ __forceinline__ void mbar_init(uint32_t bar, uint32_t count) {
    asm volatile("mbarrier.init.shared::cta.b64 [%0], %1;" :: "r"(bar), "r"(count) : "memory");
}
__device__ __forceinline__ void mbar_expect_tx(uint32_t bar, uint32_t bytes) {
    asm volatile("mbarrier.arrive.expect_tx.shared::cta.b64 _, [%0], %1;" :: "r"(bar), "r"(bytes) : "memory");
}
__device__ __forceinline__ uint32_t cluster_rank() { uint32_t r; asm("mov.u32 %0, %%cluster_ctarank;" : "=r"(r)); return r; }
__device__ __forceinline__ uint32_t map_cta(uint32_t addr, uint32_t cta) {
    uint32_t r; asm("mapa.shared::cluster.u32 %0, %1, %2;" : "=r"(r) : "r"(addr), "r"(cta)); return r;
}
__device__ __forceinline__ void mbar_arrive_cluster_if(bool pred, uint32_t cluster_bar) {
    asm volatile("{\n.reg .pred P;\nsetp.ne.u32 P, %1, 0;\n@P mbarrier.arrive.shared::cluster.b64 _, [%0];\n}\n"
                 :: "r"(cluster_bar), "r"((uint32_t)pred) : "memory");
}
__device__ __forceinline__ void mbar_arrive_cluster_n_if(bool pred, uint32_t cluster_bar, uint32_t count) {
    asm volatile("{\n.reg .pred P;\nsetp.ne.u32 P, %1, 0;\n@P mbarrier.arrive.shared::cluster.b64 _, [%0], %2;\n}\n"
                 :: "r"(cluster_bar), "r"((uint32_t)pred), "r"(count) : "memory");
}
__device__ __forceinline__ void mbar_arrive_if(bool pred, uint32_t bar) {
    asm volatile("{\n.reg .pred P;\nsetp.ne.u32 P, %1, 0;\n@P mbarrier.arrive.shared::cta.b64 _, [%0];\n}\n"
                 :: "r"(bar), "r"((uint32_t)pred) : "memory");
}
__device__ __forceinline__ bool mbar_test(uint32_t bar, uint32_t parity) {
    uint32_t ok;
    asm volatile("{\n.reg .pred P;\nmbarrier.test_wait.parity.shared::cta.b64 P, [%1], %2;\nselp.u32 %0, 1, 0, P;\n}\n"
                 : "=r"(ok) : "r"(bar), "r"(parity) : "memory");
    return ok != 0;
}
__device__ __forceinline__ void mbar_wait(uint32_t bar, uint32_t parity) {
    asm volatile("{\n.reg .pred P;\n.reg .u32 c;\n"
                 "mov.u32 c, 0;\n"
                 "SPIN:\n"
                 "mbarrier.try_wait.parity.shared::cta.b64 P, [%0], %1;\n"
                 "@P bra DONE;\n"
                 "add.u32 c, c, 1;\n"
                 "setp.lt.u32 P, c, 4194304;\n"
                 "@P bra SPIN;\n"
                 "trap;\n"
                 "DONE:\n}\n" :: "r"(bar), "r"(parity) : "memory");
}
__device__ __forceinline__ void mbar_spin(uint32_t bar, uint32_t parity) {
    asm volatile("{\n.reg .pred P;\n"
                 "SPIN:\n"
                 "mbarrier.try_wait.parity.shared::cta.b64 P, [%0], %1;\n"
                 "@!P bra SPIN;\n}\n" :: "r"(bar), "r"(parity) : "memory");
}
__device__ __forceinline__ void bar_sync(int id, int n) { asm volatile("bar.sync %0, %1;" :: "r"(id), "r"(n) : "memory"); }
__device__ __forceinline__ void bar_arrive(int id, int n) { asm volatile("bar.arrive %0, %1;" :: "r"(id), "r"(n) : "memory"); }
__device__ __forceinline__ void fence_proxy_async_smem() { asm volatile("fence.proxy.async.shared::cta;" ::: "memory"); }
__device__ __forceinline__ void tma_load_3d(uint32_t dst, const CUtensorMap* map, uint32_t bar, int c0, int c1, int c2) {
    asm volatile("cp.async.bulk.tensor.3d.shared::cluster.global.mbarrier::complete_tx::bytes [%0], [%1, {%3, %4, %5}], [%2];"
                 :: "r"(dst), "l"(map), "r"(bar), "r"(c0), "r"(c1), "r"(c2) : "memory");
}
__device__ __forceinline__ void warp_expect_tx(uint32_t bar, uint32_t bytes) {
    asm volatile("{\n.reg .pred P;\nelect.sync _|P, 0xffffffff;\n@P mbarrier.arrive.expect_tx.shared::cta.b64 _, [%0], %1;\n}\n"
                 :: "r"(bar), "r"(bytes) : "memory");
}
__device__ __forceinline__ void warp_tma_load(uint32_t dst, const CUtensorMap* map, uint32_t bar, int c0, int c1, int c2) {
    asm volatile("{\n.reg .pred P;\nelect.sync _|P, 0xffffffff;\n"
                 "@P cp.async.bulk.tensor.3d.shared::cluster.global.mbarrier::complete_tx::bytes [%0], [%1, {%3, %4, %5}], [%2];\n}\n"
                 :: "r"(dst), "l"(map), "r"(bar), "r"(c0), "r"(c1), "r"(c2) : "memory");
}
__device__ __forceinline__ void warp_tma_load_pair(uint32_t dst, const CUtensorMap* map, uint32_t bar, int c0, int c1, int c2) {
    asm volatile("{\n.reg .pred P;\nelect.sync _|P, 0xffffffff;\n"
                 "@P cp.async.bulk.tensor.3d.shared::cluster.global.mbarrier::complete_tx::bytes.multicast::cluster"
                 " [%0], [%1, {%3, %4, %5}], [%2], %6;\n}\n"
                 :: "r"(dst), "l"(map), "r"(bar), "r"(c0), "r"(c1), "r"(c2), "h"((uint16_t)3) : "memory");
}
__device__ __forceinline__ void warp_bulk_load(uint32_t dst, const void* src, uint32_t bytes, uint32_t bar) {
    asm volatile("{\n.reg .pred P;\nelect.sync _|P, 0xffffffff;\n"
                 "@P cp.async.bulk.shared::cluster.global.mbarrier::complete_tx::bytes [%0], [%1], %2, [%3];\n}\n"
                 :: "r"(dst), "l"(src), "r"(bytes), "r"(bar) : "memory");
}
__device__ __forceinline__ void warp_tma_store(const CUtensorMap* map, uint32_t src, int c0, int c1, int c2) {
    asm volatile("{\n.reg .pred P;\nelect.sync _|P, 0xffffffff;\n"
                 "@P cp.async.bulk.tensor.3d.global.shared::cta.bulk_group [%0, {%2, %3, %4}], [%1];\n}\n"
                 :: "l"(map), "r"(src), "r"(c0), "r"(c1), "r"(c2) : "memory");
}
__device__ __forceinline__ void warp_bulk_store(void* dst, uint32_t src, uint32_t bytes) {
    asm volatile("{\n.reg .pred P;\nelect.sync _|P, 0xffffffff;\n"
                 "@P cp.async.bulk.global.shared::cta.bulk_group [%0], [%1], %2;\n}\n" :: "l"(dst), "r"(src), "r"(bytes) : "memory");
}
__device__ __forceinline__ void prefetch_l2(const void* src, uint32_t bytes) {
    asm volatile("cp.async.bulk.prefetch.L2.global [%0], %1;" :: "l"(src), "r"(bytes) : "memory");
}
__device__ __forceinline__ void warp_prefetch(const void* src, uint32_t bytes) {
    asm volatile("{\n.reg .pred P;\nelect.sync _|P, 0xffffffff;\n@P cp.async.bulk.prefetch.L2.global [%0], %1;\n}\n" :: "l"(src), "r"(bytes) : "memory");
}
__device__ __forceinline__ void bulk_commit() { asm volatile("cp.async.bulk.commit_group;" ::: "memory"); }
template <int N> __device__ __forceinline__ void bulk_wait_read() { asm volatile("cp.async.bulk.wait_group.read %0;" :: "n"(N) : "memory"); }
template <int N> __device__ __forceinline__ void bulk_wait() { asm volatile("cp.async.bulk.wait_group %0;" :: "n"(N) : "memory"); }
__device__ __forceinline__ void wgmma_fence() { asm volatile("wgmma.fence.sync.aligned;" ::: "memory"); }
__device__ __forceinline__ void wgmma_commit() { asm volatile("wgmma.commit_group.sync.aligned;" ::: "memory"); }
template <int N> __device__ __forceinline__ void wgmma_wait() { asm volatile("wgmma.wait_group.sync.aligned %0;" :: "n"(N) : "memory"); }
template <int N> __device__ __forceinline__ void fence_regs(float (&d)[N]) {
#pragma unroll
    for (int i = 0; i < N; i++) asm volatile("" : "+f"(d[i]) :: "memory");
}
template <int N> __device__ __forceinline__ void fence_regs(uint32_t (&d)[N]) {
#pragma unroll
    for (int i = 0; i < N; i++) asm volatile("" : "+r"(d[i]) :: "memory");
}
template <int N> __device__ __forceinline__ void reg_dec() { asm volatile("setmaxnreg.dec.sync.aligned.u32 %0;" :: "n"(N)); }
template <int N> __device__ __forceinline__ void reg_inc() { asm volatile("setmaxnreg.inc.sync.aligned.u32 %0;" :: "n"(N)); }
__device__ __forceinline__ uint32_t pack_bf16(float lo, float hi) {
    uint32_t r; asm("cvt.rn.bf16x2.f32 %0, %1, %2;" : "=r"(r) : "f"(hi), "f"(lo)); return r;
}
__device__ __forceinline__ void stmatrix_x4(uint32_t addr, uint32_t r0, uint32_t r1, uint32_t r2, uint32_t r3) {
    asm volatile("stmatrix.sync.aligned.m8n8.x4.shared.b16 [%0], {%1, %2, %3, %4};"
                 :: "r"(addr), "r"(r0), "r"(r1), "r"(r2), "r"(r3) : "memory");
}
__device__ __forceinline__ float ex2(float x) { float y; asm("ex2.approx.ftz.f32 %0, %1;" : "=f"(y) : "f"(x)); return y; }

constexpr uint32_t DESC_HI = (1024 >> 4) | (1u << 30);
__device__ __forceinline__ uint32_t make_desc(uint32_t addr, uint32_t lbo) {
    uint32_t lo = ((addr & 0x3FFFF) >> 4) | ((lbo >> 4) << 16);
    asm volatile("" : "+r"(lo));
    return lo;
}
__device__ __forceinline__ uint64_t full_desc(uint32_t lo) {
    uint64_t d; asm("mov.b64 %0, {%1, %2};" : "=l"(d) : "r"(lo), "r"(DESC_HI)); return d;
}

__device__ __forceinline__ void wgmma_ss_n256_tb_init(float (&d)[128], uint64_t da, uint64_t db) {
    asm volatile("{\n.reg .pred p;\n"
        "setp.ne.b32 p, 0, 0;\n"
        "wgmma.mma_async.sync.aligned.m64n256k16.f32.bf16.bf16 "
        "{%0, %1, %2, %3, %4, %5, %6, %7, %8, %9, %10, %11, %12, %13, %14, %15, %16, %17, %18, %19, %20, "
        "%21, %22, %23, %24, %25, %26, %27, %28, %29, %30, %31, %32, %33, %34, %35, %36, %37, %38, %39, %40, "
        "%41, %42, %43, %44, %45, %46, %47, %48, %49, %50, %51, %52, %53, %54, %55, %56, %57, %58, %59, %60, "
        "%61, %62, %63, %64, %65, %66, %67, %68, %69, %70, %71, %72, %73, %74, %75, %76, %77, %78, %79, %80, "
        "%81, %82, %83, %84, %85, %86, %87, %88, %89, %90, %91, %92, %93, %94, %95, %96, %97, %98, %99, "
        "%100, %101, %102, %103, %104, %105, %106, %107, %108, %109, %110, %111, %112, %113, %114, %115, "
        "%116, %117, %118, %119, %120, %121, %122, %123, %124, %125, %126, %127},"
        " %128, %129, p, 1, 1, 0, 1;\n}\n"
        : "=f"(d[0]), "=f"(d[1]), "=f"(d[2]), "=f"(d[3]), "=f"(d[4]), "=f"(d[5]), "=f"(d[6]), "=f"(d[7]),
        "=f"(d[8]), "=f"(d[9]), "=f"(d[10]), "=f"(d[11]), "=f"(d[12]), "=f"(d[13]), "=f"(d[14]), "=f"(d[15]),
        "=f"(d[16]), "=f"(d[17]), "=f"(d[18]), "=f"(d[19]), "=f"(d[20]), "=f"(d[21]), "=f"(d[22]),
        "=f"(d[23]), "=f"(d[24]), "=f"(d[25]), "=f"(d[26]), "=f"(d[27]), "=f"(d[28]), "=f"(d[29]),
        "=f"(d[30]), "=f"(d[31]), "=f"(d[32]), "=f"(d[33]), "=f"(d[34]), "=f"(d[35]), "=f"(d[36]),
        "=f"(d[37]), "=f"(d[38]), "=f"(d[39]), "=f"(d[40]), "=f"(d[41]), "=f"(d[42]), "=f"(d[43]),
        "=f"(d[44]), "=f"(d[45]), "=f"(d[46]), "=f"(d[47]), "=f"(d[48]), "=f"(d[49]), "=f"(d[50]),
        "=f"(d[51]), "=f"(d[52]), "=f"(d[53]), "=f"(d[54]), "=f"(d[55]), "=f"(d[56]), "=f"(d[57]),
        "=f"(d[58]), "=f"(d[59]), "=f"(d[60]), "=f"(d[61]), "=f"(d[62]), "=f"(d[63]), "=f"(d[64]),
        "=f"(d[65]), "=f"(d[66]), "=f"(d[67]), "=f"(d[68]), "=f"(d[69]), "=f"(d[70]), "=f"(d[71]),
        "=f"(d[72]), "=f"(d[73]), "=f"(d[74]), "=f"(d[75]), "=f"(d[76]), "=f"(d[77]), "=f"(d[78]),
        "=f"(d[79]), "=f"(d[80]), "=f"(d[81]), "=f"(d[82]), "=f"(d[83]), "=f"(d[84]), "=f"(d[85]),
        "=f"(d[86]), "=f"(d[87]), "=f"(d[88]), "=f"(d[89]), "=f"(d[90]), "=f"(d[91]), "=f"(d[92]),
        "=f"(d[93]), "=f"(d[94]), "=f"(d[95]), "=f"(d[96]), "=f"(d[97]), "=f"(d[98]), "=f"(d[99]),
        "=f"(d[100]), "=f"(d[101]), "=f"(d[102]), "=f"(d[103]), "=f"(d[104]), "=f"(d[105]), "=f"(d[106]),
        "=f"(d[107]), "=f"(d[108]), "=f"(d[109]), "=f"(d[110]), "=f"(d[111]), "=f"(d[112]), "=f"(d[113]),
        "=f"(d[114]), "=f"(d[115]), "=f"(d[116]), "=f"(d[117]), "=f"(d[118]), "=f"(d[119]), "=f"(d[120]),
        "=f"(d[121]), "=f"(d[122]), "=f"(d[123]), "=f"(d[124]), "=f"(d[125]), "=f"(d[126]), "=f"(d[127])
        : "l"(da), "l"(db));
}
__device__ __forceinline__ void wgmma_ss_n256_tb(float (&d)[128], uint64_t da, uint64_t db, int scale_d) {
    asm volatile("{\n.reg .pred p;\n"
        "setp.ne.b32 p, %130, 0;\n"
        "wgmma.mma_async.sync.aligned.m64n256k16.f32.bf16.bf16 "
        "{%0, %1, %2, %3, %4, %5, %6, %7, %8, %9, %10, %11, %12, %13, %14, %15, %16, %17, %18, %19, %20, "
        "%21, %22, %23, %24, %25, %26, %27, %28, %29, %30, %31, %32, %33, %34, %35, %36, %37, %38, %39, %40, "
        "%41, %42, %43, %44, %45, %46, %47, %48, %49, %50, %51, %52, %53, %54, %55, %56, %57, %58, %59, %60, "
        "%61, %62, %63, %64, %65, %66, %67, %68, %69, %70, %71, %72, %73, %74, %75, %76, %77, %78, %79, %80, "
        "%81, %82, %83, %84, %85, %86, %87, %88, %89, %90, %91, %92, %93, %94, %95, %96, %97, %98, %99, "
        "%100, %101, %102, %103, %104, %105, %106, %107, %108, %109, %110, %111, %112, %113, %114, %115, "
        "%116, %117, %118, %119, %120, %121, %122, %123, %124, %125, %126, %127},"
        " %128, %129, p, 1, 1, 0, 1;\n}\n"
        : "+f"(d[0]), "+f"(d[1]), "+f"(d[2]), "+f"(d[3]), "+f"(d[4]), "+f"(d[5]), "+f"(d[6]), "+f"(d[7]),
        "+f"(d[8]), "+f"(d[9]), "+f"(d[10]), "+f"(d[11]), "+f"(d[12]), "+f"(d[13]), "+f"(d[14]), "+f"(d[15]),
        "+f"(d[16]), "+f"(d[17]), "+f"(d[18]), "+f"(d[19]), "+f"(d[20]), "+f"(d[21]), "+f"(d[22]),
        "+f"(d[23]), "+f"(d[24]), "+f"(d[25]), "+f"(d[26]), "+f"(d[27]), "+f"(d[28]), "+f"(d[29]),
        "+f"(d[30]), "+f"(d[31]), "+f"(d[32]), "+f"(d[33]), "+f"(d[34]), "+f"(d[35]), "+f"(d[36]),
        "+f"(d[37]), "+f"(d[38]), "+f"(d[39]), "+f"(d[40]), "+f"(d[41]), "+f"(d[42]), "+f"(d[43]),
        "+f"(d[44]), "+f"(d[45]), "+f"(d[46]), "+f"(d[47]), "+f"(d[48]), "+f"(d[49]), "+f"(d[50]),
        "+f"(d[51]), "+f"(d[52]), "+f"(d[53]), "+f"(d[54]), "+f"(d[55]), "+f"(d[56]), "+f"(d[57]),
        "+f"(d[58]), "+f"(d[59]), "+f"(d[60]), "+f"(d[61]), "+f"(d[62]), "+f"(d[63]), "+f"(d[64]),
        "+f"(d[65]), "+f"(d[66]), "+f"(d[67]), "+f"(d[68]), "+f"(d[69]), "+f"(d[70]), "+f"(d[71]),
        "+f"(d[72]), "+f"(d[73]), "+f"(d[74]), "+f"(d[75]), "+f"(d[76]), "+f"(d[77]), "+f"(d[78]),
        "+f"(d[79]), "+f"(d[80]), "+f"(d[81]), "+f"(d[82]), "+f"(d[83]), "+f"(d[84]), "+f"(d[85]),
        "+f"(d[86]), "+f"(d[87]), "+f"(d[88]), "+f"(d[89]), "+f"(d[90]), "+f"(d[91]), "+f"(d[92]),
        "+f"(d[93]), "+f"(d[94]), "+f"(d[95]), "+f"(d[96]), "+f"(d[97]), "+f"(d[98]), "+f"(d[99]),
        "+f"(d[100]), "+f"(d[101]), "+f"(d[102]), "+f"(d[103]), "+f"(d[104]), "+f"(d[105]), "+f"(d[106]),
        "+f"(d[107]), "+f"(d[108]), "+f"(d[109]), "+f"(d[110]), "+f"(d[111]), "+f"(d[112]), "+f"(d[113]),
        "+f"(d[114]), "+f"(d[115]), "+f"(d[116]), "+f"(d[117]), "+f"(d[118]), "+f"(d[119]), "+f"(d[120]),
        "+f"(d[121]), "+f"(d[122]), "+f"(d[123]), "+f"(d[124]), "+f"(d[125]), "+f"(d[126]), "+f"(d[127])
        : "l"(da), "l"(db), "r"(scale_d));
}
__device__ __forceinline__ void wgmma_ss_n128(float (&d)[64], uint64_t da, uint64_t db, int scale_d) {
    asm volatile("{\n.reg .pred p;\n"
        "setp.ne.b32 p, %66, 0;\n"
        "wgmma.mma_async.sync.aligned.m64n128k16.f32.bf16.bf16 "
        "{%0, %1, %2, %3, %4, %5, %6, %7, %8, %9, %10, %11, %12, %13, %14, %15, %16, %17, %18, %19, %20, "
        "%21, %22, %23, %24, %25, %26, %27, %28, %29, %30, %31, %32, %33, %34, %35, %36, %37, %38, %39, %40, "
        "%41, %42, %43, %44, %45, %46, %47, %48, %49, %50, %51, %52, %53, %54, %55, %56, %57, %58, %59, %60, "
        "%61, %62, %63},"
        " %64, %65, p, 1, 1, 0, 0;\n}\n"
        : "+f"(d[0]), "+f"(d[1]), "+f"(d[2]), "+f"(d[3]), "+f"(d[4]), "+f"(d[5]), "+f"(d[6]), "+f"(d[7]),
        "+f"(d[8]), "+f"(d[9]), "+f"(d[10]), "+f"(d[11]), "+f"(d[12]), "+f"(d[13]), "+f"(d[14]), "+f"(d[15]),
        "+f"(d[16]), "+f"(d[17]), "+f"(d[18]), "+f"(d[19]), "+f"(d[20]), "+f"(d[21]), "+f"(d[22]),
        "+f"(d[23]), "+f"(d[24]), "+f"(d[25]), "+f"(d[26]), "+f"(d[27]), "+f"(d[28]), "+f"(d[29]),
        "+f"(d[30]), "+f"(d[31]), "+f"(d[32]), "+f"(d[33]), "+f"(d[34]), "+f"(d[35]), "+f"(d[36]),
        "+f"(d[37]), "+f"(d[38]), "+f"(d[39]), "+f"(d[40]), "+f"(d[41]), "+f"(d[42]), "+f"(d[43]),
        "+f"(d[44]), "+f"(d[45]), "+f"(d[46]), "+f"(d[47]), "+f"(d[48]), "+f"(d[49]), "+f"(d[50]),
        "+f"(d[51]), "+f"(d[52]), "+f"(d[53]), "+f"(d[54]), "+f"(d[55]), "+f"(d[56]), "+f"(d[57]),
        "+f"(d[58]), "+f"(d[59]), "+f"(d[60]), "+f"(d[61]), "+f"(d[62]), "+f"(d[63])
        : "l"(da), "l"(db), "r"(scale_d));
}
__device__ __forceinline__ void wgmma_rs_n128_tb(float (&d)[64], uint32_t a0, uint32_t a1, uint32_t a2, uint32_t a3, uint64_t db, int scale_d) {
    asm volatile("{\n.reg .pred p;\n"
        "setp.ne.b32 p, %69, 0;\n"
        "wgmma.mma_async.sync.aligned.m64n128k16.f32.bf16.bf16 "
        "{%0, %1, %2, %3, %4, %5, %6, %7, %8, %9, %10, %11, %12, %13, %14, %15, %16, %17, %18, %19, %20, "
        "%21, %22, %23, %24, %25, %26, %27, %28, %29, %30, %31, %32, %33, %34, %35, %36, %37, %38, %39, %40, "
        "%41, %42, %43, %44, %45, %46, %47, %48, %49, %50, %51, %52, %53, %54, %55, %56, %57, %58, %59, %60, "
        "%61, %62, %63},"
        " {%64, %65, %66, %67}, %68, p, 1, 1, 1;\n}\n"
        : "+f"(d[0]), "+f"(d[1]), "+f"(d[2]), "+f"(d[3]), "+f"(d[4]), "+f"(d[5]), "+f"(d[6]), "+f"(d[7]),
        "+f"(d[8]), "+f"(d[9]), "+f"(d[10]), "+f"(d[11]), "+f"(d[12]), "+f"(d[13]), "+f"(d[14]), "+f"(d[15]),
        "+f"(d[16]), "+f"(d[17]), "+f"(d[18]), "+f"(d[19]), "+f"(d[20]), "+f"(d[21]), "+f"(d[22]),
        "+f"(d[23]), "+f"(d[24]), "+f"(d[25]), "+f"(d[26]), "+f"(d[27]), "+f"(d[28]), "+f"(d[29]),
        "+f"(d[30]), "+f"(d[31]), "+f"(d[32]), "+f"(d[33]), "+f"(d[34]), "+f"(d[35]), "+f"(d[36]),
        "+f"(d[37]), "+f"(d[38]), "+f"(d[39]), "+f"(d[40]), "+f"(d[41]), "+f"(d[42]), "+f"(d[43]),
        "+f"(d[44]), "+f"(d[45]), "+f"(d[46]), "+f"(d[47]), "+f"(d[48]), "+f"(d[49]), "+f"(d[50]),
        "+f"(d[51]), "+f"(d[52]), "+f"(d[53]), "+f"(d[54]), "+f"(d[55]), "+f"(d[56]), "+f"(d[57]),
        "+f"(d[58]), "+f"(d[59]), "+f"(d[60]), "+f"(d[61]), "+f"(d[62]), "+f"(d[63])
        : "r"(a0), "r"(a1), "r"(a2), "r"(a3), "l"(db), "r"(scale_d));
}
__device__ __forceinline__ void wgmma_ss_n128_tb_init(float (&d)[64], uint64_t da, uint64_t db) {
    asm volatile("{\n.reg .pred p;\n"
        "setp.ne.b32 p, 0, 0;\n"
        "wgmma.mma_async.sync.aligned.m64n128k16.f32.bf16.bf16 "
        "{%0, %1, %2, %3, %4, %5, %6, %7, %8, %9, %10, %11, %12, %13, %14, %15, %16, %17, %18, %19, %20, "
        "%21, %22, %23, %24, %25, %26, %27, %28, %29, %30, %31, %32, %33, %34, %35, %36, %37, %38, %39, %40, "
        "%41, %42, %43, %44, %45, %46, %47, %48, %49, %50, %51, %52, %53, %54, %55, %56, %57, %58, %59, %60, "
        "%61, %62, %63},"
        " %64, %65, p, 1, 1, 0, 1;\n}\n"
        : "=f"(d[0]), "=f"(d[1]), "=f"(d[2]), "=f"(d[3]), "=f"(d[4]), "=f"(d[5]), "=f"(d[6]), "=f"(d[7]),
        "=f"(d[8]), "=f"(d[9]), "=f"(d[10]), "=f"(d[11]), "=f"(d[12]), "=f"(d[13]), "=f"(d[14]), "=f"(d[15]),
        "=f"(d[16]), "=f"(d[17]), "=f"(d[18]), "=f"(d[19]), "=f"(d[20]), "=f"(d[21]), "=f"(d[22]),
        "=f"(d[23]), "=f"(d[24]), "=f"(d[25]), "=f"(d[26]), "=f"(d[27]), "=f"(d[28]), "=f"(d[29]),
        "=f"(d[30]), "=f"(d[31]), "=f"(d[32]), "=f"(d[33]), "=f"(d[34]), "=f"(d[35]), "=f"(d[36]),
        "=f"(d[37]), "=f"(d[38]), "=f"(d[39]), "=f"(d[40]), "=f"(d[41]), "=f"(d[42]), "=f"(d[43]),
        "=f"(d[44]), "=f"(d[45]), "=f"(d[46]), "=f"(d[47]), "=f"(d[48]), "=f"(d[49]), "=f"(d[50]),
        "=f"(d[51]), "=f"(d[52]), "=f"(d[53]), "=f"(d[54]), "=f"(d[55]), "=f"(d[56]), "=f"(d[57]),
        "=f"(d[58]), "=f"(d[59]), "=f"(d[60]), "=f"(d[61]), "=f"(d[62]), "=f"(d[63])
        : "l"(da), "l"(db));
}
__device__ __forceinline__ void wgmma_ss_n128_tb(float (&d)[64], uint64_t da, uint64_t db, int scale_d) {
    asm volatile("{\n.reg .pred p;\n"
        "setp.ne.b32 p, %66, 0;\n"
        "wgmma.mma_async.sync.aligned.m64n128k16.f32.bf16.bf16 "
        "{%0, %1, %2, %3, %4, %5, %6, %7, %8, %9, %10, %11, %12, %13, %14, %15, %16, %17, %18, %19, %20, "
        "%21, %22, %23, %24, %25, %26, %27, %28, %29, %30, %31, %32, %33, %34, %35, %36, %37, %38, %39, %40, "
        "%41, %42, %43, %44, %45, %46, %47, %48, %49, %50, %51, %52, %53, %54, %55, %56, %57, %58, %59, %60, "
        "%61, %62, %63},"
        " %64, %65, p, 1, 1, 0, 1;\n}\n"
        : "+f"(d[0]), "+f"(d[1]), "+f"(d[2]), "+f"(d[3]), "+f"(d[4]), "+f"(d[5]), "+f"(d[6]), "+f"(d[7]),
        "+f"(d[8]), "+f"(d[9]), "+f"(d[10]), "+f"(d[11]), "+f"(d[12]), "+f"(d[13]), "+f"(d[14]), "+f"(d[15]),
        "+f"(d[16]), "+f"(d[17]), "+f"(d[18]), "+f"(d[19]), "+f"(d[20]), "+f"(d[21]), "+f"(d[22]),
        "+f"(d[23]), "+f"(d[24]), "+f"(d[25]), "+f"(d[26]), "+f"(d[27]), "+f"(d[28]), "+f"(d[29]),
        "+f"(d[30]), "+f"(d[31]), "+f"(d[32]), "+f"(d[33]), "+f"(d[34]), "+f"(d[35]), "+f"(d[36]),
        "+f"(d[37]), "+f"(d[38]), "+f"(d[39]), "+f"(d[40]), "+f"(d[41]), "+f"(d[42]), "+f"(d[43]),
        "+f"(d[44]), "+f"(d[45]), "+f"(d[46]), "+f"(d[47]), "+f"(d[48]), "+f"(d[49]), "+f"(d[50]),
        "+f"(d[51]), "+f"(d[52]), "+f"(d[53]), "+f"(d[54]), "+f"(d[55]), "+f"(d[56]), "+f"(d[57]),
        "+f"(d[58]), "+f"(d[59]), "+f"(d[60]), "+f"(d[61]), "+f"(d[62]), "+f"(d[63])
        : "l"(da), "l"(db), "r"(scale_d));
}

enum { M_X = 0, M_C, M_WQ, M_WUK, M_WUV, M_WQKV, M_WO, M_WOB, M_SCR_LD, M_SCR_LOC, M_SCR_LOQ, M_SCR_ST, M_COUNT };
enum { T_Q = 0, T_K, T_V, T_B, T_OUT, T_LOCAL, T_ATTN, T_END };
constexpr int NCTA = 132, NPAIR = NCTA / 2;
constexpr int NITEMS = 480 + 64 + 256;
constexpr int TRIPLES = 3, WIDE = 80 - 3 * TRIPLES;
struct Params {
    CUtensorMap m[M_COUNT];
    const __nv_bfloat16* x;
    const __nv_bfloat16* gate_w;
    const char* wo;
    __nv_bfloat16* out;
    uint32_t zero;
    uint16_t items[NITEMS];
    uint8_t ostep[80];
};
__device__ __forceinline__ int item_type(int it) { return it >> 13; }
__device__ __forceinline__ int item_row(int it) { return it & 15; }
__device__ __forceinline__ int item_col(int it) { return (it >> 4) & 31; }
__device__ __forceinline__ int item_asc(int it) { return (it >> 9) & 1; }
constexpr int ITEM_READY = 1 << 10;

struct __align__(128) Sync {
    unsigned long long count[4];
    __align__(128) unsigned long long ctx[16];
    unsigned next, next_out, done;
    __align__(128) unsigned step[32][2];
    unsigned split[32];
};
__device__ Sync g_sync;
__device__ uint4 g_part[128][8][256];

constexpr uint32_t GST_BYTES = 49152, SM_KV = 65536, SM_STAGING = 196608, SM_BARS = SM_STAGING + 32768;
constexpr uint32_t B_GFULL = 0, B_GEMPTY = 32, B_AFULL = 64, B_AEMPTY = 112, B_SFULL = 160, B_SEMPTY = 192,
                   B_IFULL = 224, B_IEMPTY = 288, B_XFREE = 352, B_WANT = 384, B_HALF = 416,
                   SM_ORDY = 448, SM_QUEUE = 456, B_ALT = 488, B_QFREE = 504, SM_GATE = 512, SM_TOTAL = SM_BARS + 1536;
constexpr int QDEPTH = 8;
#define PF_NAR 20
#define SPREAD 4
#define KMEET 14
constexpr int K_MEET = KMEET, K_SPLIT = KMEET + 12;
#define KF2 3
constexpr uint32_t LOC_PLANE = 72 * 128;
constexpr float SM_SCALE = 0.08838834764831845f * 1.4426950408889634f;
constexpr float LOC_SCALE = 0.17677669529663687f * 1.4426950408889634f;
constexpr float SUM_LIMIT = 1152921504606846976.f;
constexpr float REF_RANGE = 32.f;

__device__ __forceinline__ unsigned ld_acquire(const unsigned* p) {
    unsigned v; asm volatile("ld.acquire.gpu.global.u32 %0, [%1];" : "=r"(v) : "l"(p) : "memory"); return v;
}
__device__ __forceinline__ unsigned long long ld_acquire(const unsigned long long* p) {
    unsigned long long v; asm volatile("ld.acquire.gpu.global.u64 %0, [%1];" : "=l"(v) : "l"(p) : "memory"); return v;
}
__device__ __forceinline__ void st_b128(void* p, uint32_t a, uint32_t b, uint32_t c, uint32_t d) {
    asm volatile("{\n.reg .b128 v;\n.reg .b64 lo, hi;\nmov.b64 lo, {%1, %2};\nmov.b64 hi, {%3, %4};\nmov.b128 v, {lo, hi};\n"
                 "st.relaxed.gpu.global.b128 [%0], v;\n}\n" :: "l"(p), "r"(a), "r"(b), "r"(c), "r"(d) : "memory");
}
__device__ __forceinline__ void ld_b128(const void* p, uint32_t& a, uint32_t& b, uint32_t& c, uint32_t& d) {
    asm volatile("{\n.reg .b128 v;\n.reg .b64 lo, hi;\nld.relaxed.gpu.global.b128 v, [%4];\nmov.b128 {lo, hi}, v;\n"
                 "mov.b64 {%0, %1}, lo;\nmov.b64 {%2, %3}, hi;\n}\n" : "=r"(a), "=r"(b), "=r"(c), "=r"(d) : "l"(p) : "memory");
}
__device__ __forceinline__ void spin_guard(unsigned& n) {
    asm volatile("{\n.reg .pred P;\nadd.u32 %0, %0, 1;\nsetp.gt.u32 P, %0, 16777216;\n@P trap;\n}\n" : "+r"(n));
    if (n > 1) __nanosleep(100);
}
__device__ __forceinline__ void red_add(unsigned long long* p, unsigned long long v) {
    asm volatile("red.release.gpu.global.add.u64 [%0], %1;" :: "l"(p), "l"(v) : "memory");
}
__device__ __forceinline__ float rcp(float x) { float y; asm("rcp.approx.ftz.f32 %0, %1;" : "=f"(y) : "f"(x)); return y; }
__device__ __forceinline__ float lds_f32(uint32_t addr) {
    float v; asm volatile("ld.shared.f32 %0, [%1];" : "=f"(v) : "r"(addr) : "memory"); return v;
}
__device__ __forceinline__ void ldsm_x4(uint32_t (&r)[4], uint32_t addr) {
    asm volatile("ldmatrix.sync.aligned.m8n8.x4.shared.b16 {%0, %1, %2, %3}, [%4];"
                 : "=r"(r[0]), "=r"(r[1]), "=r"(r[2]), "=r"(r[3]) : "r"(addr) : "memory");
}
__device__ __forceinline__ void ldsm_x4_t(uint32_t (&r)[4], uint32_t addr) {
    asm volatile("ldmatrix.sync.aligned.m8n8.x4.trans.shared.b16 {%0, %1, %2, %3}, [%4];"
                 : "=r"(r[0]), "=r"(r[1]), "=r"(r[2]), "=r"(r[3]) : "r"(addr) : "memory");
}
__device__ __forceinline__ void mma_k16(float (&d)[4], const uint32_t (&a)[4], uint32_t b0, uint32_t b1) {
    asm("mma.sync.aligned.m16n8k16.row.col.f32.bf16.bf16.f32 {%0,%1,%2,%3}, {%4,%5,%6,%7}, {%8,%9}, {%0,%1,%2,%3};"
        : "+f"(d[0]), "+f"(d[1]), "+f"(d[2]), "+f"(d[3]) : "r"(a[0]), "r"(a[1]), "r"(a[2]), "r"(a[3]), "r"(b0), "r"(b1));
}
__device__ __forceinline__ void mma_k16_init(float (&d)[4], const uint32_t (&a)[4], uint32_t b0, uint32_t b1) {
    asm("{\n.reg .f32 z;\nmov.f32 z, 0f00000000;\n"
        "mma.sync.aligned.m16n8k16.row.col.f32.bf16.bf16.f32 {%0,%1,%2,%3}, {%4,%5,%6,%7}, {%8,%9}, {z,z,z,z};\n}\n"
        : "=f"(d[0]), "=f"(d[1]), "=f"(d[2]), "=f"(d[3]) : "r"(a[0]), "r"(a[1]), "r"(a[2]), "r"(a[3]), "r"(b0), "r"(b1));
}
__device__ __forceinline__ void mma_k8(float (&d)[4], uint32_t a0, uint32_t a1, uint32_t b0) {
    asm("mma.sync.aligned.m16n8k8.row.col.f32.bf16.bf16.f32 {%0,%1,%2,%3}, {%4,%5}, {%6}, {%0,%1,%2,%3};"
        : "+f"(d[0]), "+f"(d[1]), "+f"(d[2]), "+f"(d[3]) : "r"(a0), "r"(a1), "r"(b0));
}
template <typename T, int N> __device__ __forceinline__ void zero_regs(T (&d)[N]) {
#pragma unroll
    for (int i = 0; i < N; i++) d[i] = 0;
}
__device__ __forceinline__ float quad_max(float v) {
    v = fmaxf(v, __shfl_xor_sync(0xffffffffu, v, 1));
    return fmaxf(v, __shfl_xor_sync(0xffffffffu, v, 2));
}
__device__ __forceinline__ float quad_sum(float v) {
    v += __shfl_xor_sync(0xffffffffu, v, 1);
    return v + __shfl_xor_sync(0xffffffffu, v, 2);
}

__device__ __forceinline__ void qk_gemm(float (&s)[64], uint32_t q_lo, uint32_t k_lo) {
    const uint64_t dq = full_desc(q_lo), dk = full_desc(k_lo);
    fence_regs(s);
    wgmma_fence();
#pragma unroll
    for (int kk = 0; kk < 8; kk++) {
        const uint32_t o = (kk >> 2) * 1024 + (kk & 3) * 2;
        wgmma_ss_n128(s, dq + o, dk + o, kk != 0);
    }
    wgmma_commit();
}
__device__ __forceinline__ void pv_gemm(float (&o)[64], uint32_t (&p)[32], uint32_t v_lo, int accumulate) {
    const uint64_t dv = full_desc(v_lo);
    fence_regs(o);
    fence_regs(p);
    wgmma_fence();
#pragma unroll
    for (int kk = 0; kk < 8; kk++)
        wgmma_rs_n128_tb(o, p[4 * kk], p[4 * kk + 1], p[4 * kk + 2], p[4 * kk + 3], dv + kk * 128, kk != 0 || accumulate);
    wgmma_commit();
}
__device__ __forceinline__ void row_max(const float (&s)[64], float& x0, float& x1) {
    float z0 = fmaxf(s[0], s[1]), z1 = fmaxf(s[2], s[3]);
    x0 = fmaxf(s[4], s[5]); x1 = fmaxf(s[6], s[7]);
#pragma unroll
    for (int j = 2; j < 16; j += 2) {
        z0 = fmaxf(z0, fmaxf(s[4 * j], s[4 * j + 1]));
        z1 = fmaxf(z1, fmaxf(s[4 * j + 2], s[4 * j + 3]));
        x0 = fmaxf(x0, fmaxf(s[4 * j + 4], s[4 * j + 5]));
        x1 = fmaxf(x1, fmaxf(s[4 * j + 6], s[4 * j + 7]));
    }
    x0 = quad_max(fmaxf(x0, z0)); x1 = quad_max(fmaxf(x1, z1));
}
__device__ __forceinline__ void exp_pack(uint32_t (&p)[32], const float (&s)[64], float& r0, float& r1) {
#pragma unroll
    for (int j = 0; j < 16; j++) {
        const float e0 = ex2(s[4 * j]), e1 = ex2(s[4 * j + 1]), e2 = ex2(s[4 * j + 2]), e3 = ex2(s[4 * j + 3]);
        if (j == 0) { r0 = e0 + e1; r1 = e2 + e3; }
        else { r0 += e0 + e1; r1 += e2 + e3; }
        p[2 * j] = pack_bf16(e0, e1);
        p[2 * j + 1] = pack_bf16(e2, e3);
    }
}
__device__ __forceinline__ void shift_rows(float (&s)[64], float d0, float d1) {
#pragma unroll
    for (int j = 0; j < 16; j++) { s[4 * j] -= d0; s[4 * j + 1] -= d0; s[4 * j + 2] -= d1; s[4 * j + 3] -= d1; }
}
constexpr float MASKED = -3e38f;
template <int J0>
__device__ __forceinline__ void mask_triangle(float (&s)[64], float thr) {
#pragma unroll
    for (int j = 0; j < 16; j++) {
        const float m = __saturatef((float)(8 * (j >> 1) + (j & 1)) - thr);
        const int i = 4 * (J0 + (j >> 1)) + (j & 1);
        s[i] = fmaf(m, MASKED, s[i]);
        if (j < 14) s[i + 6] = fmaf(m, MASKED, s[i + 6]);
    }
}
__device__ __forceinline__ void causal_mask(float (&s)[64], float thr, int wg) {
    asm volatile("" : "+f"(thr));
    if (wg == 0) {
        mask_triangle<0>(s, thr);
#pragma unroll
        for (int j = 32; j < 64; j++) s[j] += MASKED;
    } else {
        mask_triangle<8>(s, thr);
    }
}

__global__ void __cluster_dims__(2, 1, 1) __launch_bounds__(384, 1) fused_kernel(const __grid_constant__ Params prm) {
    extern __shared__ __align__(1024) uint8_t smem[];
    const uint32_t sb = smem_u32(smem), bars = sb + SM_BARS;
    const int warp = __shfl_sync(0xffffffffu, threadIdx.x >> 5, 0), lane = threadIdx.x & 31;

    const uint32_t rank = cluster_rank();
    const uint32_t bars0 = map_cta(bars, 0), bars_peer = map_cta(bars, rank ^ 1);

    auto first_item = [&]() -> int {
        uint32_t pair = blockIdx.x >> 1;
        asm volatile("" : "+r"(pair));
        return prm.items[pair] + item_row(prm.items[pair]) + rank;
    };
    if (threadIdx.x == 256) {
        for (int k = 0; k < 4; k++) mbar_init(bars + B_GFULL + 8 * k, 1);
        asm volatile("fence.mbarrier_init.release.cluster;" ::: "memory");
        fence_proxy_async_smem();
    }
    if (threadIdx.x == 128) {
        for (int i = 0; i < 4; i++) { mbar_init(bars + B_GEMPTY + 8 * i, 16); mbar_init(bars + B_XFREE + 8 * i, 1); }
        for (int i = 0; i < 6; i++) { mbar_init(bars + B_AFULL + 8 * i, 1); mbar_init(bars + B_AEMPTY + 8 * i, i < 2 ? 8 : 16); }
        for (int i = 0; i < 4; i++) { mbar_init(bars + B_SFULL + 8 * i, 4); mbar_init(bars + B_SEMPTY + 8 * i, 1); }
        for (int i = 0; i < QDEPTH; i++) { mbar_init(bars + B_IFULL + 8 * i, 1); mbar_init(bars + B_IEMPTY + 8 * i, 23); }
        mbar_init(bars + B_WANT, 2);
        for (int i = 0; i < 4; i++) mbar_init(bars + B_HALF + 8 * i, 1);
        mbar_init(bars + B_ALT, 4); mbar_init(bars + B_ALT + 8, 4); mbar_init(bars + B_QFREE, 2);
        asm volatile("st.shared.u64 [%0], 0;" :: "r"(bars + SM_ORDY) : "memory");
        asm volatile("fence.mbarrier_init.release.cluster;\nfence.acq_rel.cta;" ::: "memory");
    }
    __syncwarp();
    asm volatile("barrier.cluster.arrive.relaxed.aligned;" ::: "memory");
    if (threadIdx.x == 256) {
        const int first_it = first_item();
#pragma unroll 1
        for (int k = 0; k < 4; k++) {
            const uint32_t dst = sb + k * GST_BYTES, fb = bars + B_GFULL + 8 * k;
            mbar_expect_tx(fb, GST_BYTES);
            tma_load_3d(dst, &prm.m[M_X], fb, k * 64, item_row(first_it) * 128, 0);
            tma_load_3d(dst + 16384, &prm.m[M_WQKV], fb, 0, k * 64, item_col(first_it) * 4);
            tma_load_3d(dst + 32768, &prm.m[M_WQKV], fb, 0, k * 64, item_col(first_it) * 4 + 2);
        }
    }
    __syncwarp();
    asm volatile("barrier.cluster.wait.acquire.aligned;" ::: "memory");

    uint32_t qn = 0;
    auto next_item = [&](bool releaser, bool bounded = true) -> int {
        const uint32_t slot = qn % QDEPTH;
        if (bounded) mbar_wait(bars + B_IFULL + 8 * slot, (qn / QDEPTH) & 1);
        else mbar_spin(bars + B_IFULL + 8 * slot, (qn / QDEPTH) & 1);
        uint32_t it;
        asm volatile("ld.shared.u32 %0, [%1];" : "=r"(it) : "r"(bars + SM_QUEUE + 4 * slot) : "memory");
        mbar_arrive_cluster_if(releaser, bars0 + B_IEMPTY + 8 * slot);
        qn++;
        return it;
    };

    if (warp < 4) {
        reg_dec<40>();
        if (warp == 0) {
            {
                uint32_t gph = 0;
                const uint32_t prank = __shfl_sync(0xffffffffu, rank, 0);
                auto request = [&]() { mbar_arrive_cluster_if(lane == 0, bars0 + B_WANT); };
                auto take_item = [&]() -> int { return __shfl_sync(0xffffffffu, next_item(lane == 0), 0); };
                auto inputs_seen = [&](uint32_t word, unsigned& n) -> uint32_t {
                    uint32_t v;
                    spin_guard(n);
                    asm volatile("ld.acquire.cta.shared.u32 %0, [%1];" : "=r"(v) : "r"(bars + SM_ORDY + 4 * word) : "memory");
                    return __shfl_sync(0xffffffffu, v, 0);
                };
                uint32_t oneed = 0;
                auto wait_inputs = [&](int it) {
                    if (it & ITEM_READY) return;
                    oneed += 256;
                    for (unsigned n = 0; inputs_seen(1, n) < oneed;) {}
                };
                int nxt = first_item();
                for (int k0 = 4; item_type(nxt) <= T_LOCAL; k0 = 0) {
                    const int type = item_type(nxt), m = item_row(nxt), c = item_col(nxt);
                    if (type == T_LOCAL) {
                        wait_inputs(nxt);
                        request();
#pragma unroll 1
                        for (uint32_t st = 0; st < 4; st++) {
                            mbar_wait(bars + B_GEMPTY + 8 * st, gph);
                            const uint32_t dst = sb + st * GST_BYTES, fb = bars + B_GFULL + 8 * st;
                            warp_expect_tx(fb, st == 0 ? 32768 + 512 : st == 3 ? 0 : 4 * LOC_PLANE);
                            if (st == 3) break;
                            if (st == 0) warp_bulk_load(dst + 4 * LOC_PLANE, &g_gate[m * 128], 512, fb);
#pragma unroll 1
                            for (int i = 0; i < 4; i++)
                                warp_tma_load(dst + i * LOC_PLANE, &prm.m[st ? M_SCR_LOC : M_SCR_LOQ], fb, i * 64, m * 64 - (st ? 8 : 0), G_B + 8 * st + c);
                        }
                        gph ^= 1;
                    } else {
                        const int nk = type == T_K || type == T_V ? 8 : 16;
                        const CUtensorMap* ma = &prm.m[nk == 8 ? M_C : M_X];
                        const CUtensorMap* mb = &prm.m[M_WQ + type];
#pragma unroll 1
                        for (int k = k0; k < nk; k++) {
                            if (k == nk - 3) request();
                            const uint32_t st = k & 3, dst = sb + st * GST_BYTES, fb = bars + B_GFULL + 8 * st;
                            mbar_wait(bars + B_GEMPTY + 8 * st, gph);
                            warp_expect_tx(fb, GST_BYTES);
                            warp_tma_load(dst, ma, fb, k * 64, m * 128, 0);
                            warp_tma_load_pair(dst + 16384 + prank * 16384, mb, fb, 0, k * 64, c * 4 + 2 * prank);
                            if (st == 3) gph ^= 1;
                        }
                    }
                    nxt = take_item();
                }
                uint32_t kv = 0, kvph = 1;
                uint32_t qc = 0;
                auto a_parity = [&](uint32_t b) { return b < 2 ? (((qc + 1 - b) >> 1) & 1) ^ 1 : kvph ^ (b - 2 < kv); };
                const CUtensorMap* tile_map = &prm.m[M_SCR_LD];
                asm volatile("" : "+l"(tile_map));
                {
                    bool need_g = true, more = true;
                    int pv_grp = -1, pv_row = 0;
                    bool pv_shared = false, peer_longer = false;
                    int m = 0, c = 0, asc = 0, nu = 0, uend = 0, ureq = -1, ufetch = 0;
#pragma unroll 1
                    for (int u = 0;; u++) {
                        if (u == ufetch) {
                            if (qc) nxt = take_item();
                            if (item_type(nxt) == T_ATTN) {
                                wait_inputs(nxt);
                                const uint32_t b = qc & 1, dst = sb + b * 32768, fb = bars + B_AFULL + 8 * b, row = item_row(nxt) * 128;
                                mbar_wait(bars + (qc == 0 ? B_GEMPTY : qc == 1 ? B_QFREE : B_AEMPTY + 8 * b), qc == 0 ? gph : qc == 1 ? 0 : a_parity(b));
                                warp_expect_tx(fb, 32768 + 512);
                                warp_tma_load(dst, tile_map, fb, 0, row, G_Q + item_col(nxt));
                                warp_tma_load(dst + 16384, tile_map, fb, 64, row, G_Q + item_col(nxt));
                                warp_bulk_load(bars + SM_GATE + b * 512, &g_gate[row], 512, fb);
                                qc++;
                            }
                        }
                        if (u == uend) {
                            if (!more) break;
                            more = item_type(nxt) == T_ATTN;
                            m = item_row(nxt); c = item_col(nxt); asc = item_asc(nxt);
                            nu = more ? 2 * m + 2 : 0;
                            uend = nu + ((more ? m < 2 : pv_grp >= 0) ? 3 : 0);
                            ureq = 2 * max(m - 2 - (asc & m), 0);
                            ufetch = !more ? -1 : m ? 2 * m : uend;
                            u = -1;
                            continue;
                        }
                        int grp = pv_grp, row = pv_row;
                        bool shared = pv_shared;
                        if (u >= nu) {
                            if (u == nu + 1) pv_grp = -1;
                            else if (peer_longer) { grp = -1; shared = false; }
                            else continue;
                        } else {
                            const int j = asc ? u >> 1 : m - (u >> 1);
                            if (u & 1) {
                                pv_grp = G_V + c; pv_row = j * 128; pv_shared = j != (m | 1);
                                peer_longer = asc & ~m & 1;
                                if (u == nu - 1 && (m & 1) && item_type(nxt) == T_END) mbar_arrive_cluster_n_if(lane == 0, bars0 + B_WANT, 2);
                                if (grp < 0) continue;
                            } else {
                                if (u == ureq) request();
                                grp = G_K + c; row = j * 128; shared = j != (m | 1);
                            }
                        }
                        uint32_t fb = bars + B_AFULL + 16 + 8 * kv, mine = sb + SM_KV + kv * 32768 + prank * 16384;
                        int c_mine = prank * 64;
                        asm volatile("" : "+r"(mine), "+r"(fb), "+r"(row), "+r"(grp), "+r"(c_mine));
                        mbar_wait(need_g ? bars + B_GEMPTY + 8 + 8 * kv : fb + B_AEMPTY - B_AFULL, need_g ? gph : kvph);
                        warp_expect_tx(fb, grp < 0 ? 0 : 32768);
                        if (shared) {
                            warp_tma_load_pair(mine, tile_map, fb, c_mine, row, grp);
                        } else if (grp >= 0) {
                            warp_tma_load(mine, tile_map, fb, c_mine, row, grp);
                            warp_tma_load(mine + 16384 - prank * 32768, tile_map, fb, 64 - c_mine, row, grp);
                        } else {
                            mbar_arrive_cluster_n_if(lane < 2, map_cta(fb, lane & 1) + B_AEMPTY - B_AFULL, 8);
                        }
                        if (kv == 2) need_g = false;
                        if (++kv == 4) { kv = 0; kvph ^= 1; }
                    }
                }
                if (!qc) request();
                const int it = take_item();
                int nk = 0;
                if (item_type(it) == T_OUT) {
                    const int m = item_row(it), c = item_col(it), half = c & 1;
                    nk = 80;
                    for (int k = 0; k < nk; k++) {
                        if (k == K_SPLIT) nk = 2 * TRIPLES + (take_item() & 127);
                        const int kn = k + 2 * TRIPLES - nk, first = kn >= 0 && !(kn & 1);
                        const int s = kn >= 0 ? WIDE + (3 * kn + 1) / 2 : half ? WIDE - 1 - k : k;
                        const uint32_t sa = prm.ostep[s], sa2 = prm.ostep[s + first], sw = prm.ostep[s - (kn >= 0 && !first ? prank : 0)];
                        const uint32_t need = 1u << (sa >> 1 & 31) | 1u << (sa2 >> 1 & 31);
                        for (unsigned n = 0; need & ~inputs_seen(sa >> 6, n);) {}
                        const uint32_t st = k & 3;
                        uint32_t dst = sb + st * GST_BYTES, fb = bars + B_GFULL + 8 * st;
                        uint32_t dstb = dst + 16384 + (first ? 0 : prank * 16384), skipb = first && (kn >> 1 & 1) != prank;
                        int a0 = (sa & 1) * 64, a1 = m * 128, a2 = (sa >> 1) + (sa < 64 ? G_CTX : G_LOC - 32);
                        int b1 = (sw & 63) * 64, b2 = (c >> 1) * 4 + 2 * (kn >= 0 ? half : half ^ prank);
                        const CUtensorMap* mb = &prm.m[sw >= 64 ? M_WOB : M_WO];
                        asm volatile("" : "+r"(dst), "+r"(fb), "+r"(dstb), "+r"(skipb), "+r"(a0), "+r"(a1), "+r"(a2), "+r"(b1), "+r"(b2), "+l"(mb));
                        if (k < 4) {
#pragma unroll 1
                            for (uint32_t i = 0, b = (3 * st) >> 1; i < 3; i++, b++) mbar_wait(bars + (i == 2 ? B_QFREE : B_AEMPTY + 8 * b), i == 2 ? 0 : a_parity(b));
                            mbar_arrive_cluster_if(lane == 0, bars_peer + B_XFREE + 8 * st);
                            mbar_wait(bars + B_XFREE + 8 * st, 0);
                        }
                        mbar_wait(bars + B_GEMPTY + 8 * st, gph);
                        warp_expect_tx(fb, GST_BYTES);
                        warp_tma_load(dst, tile_map, fb, a0, a1, a2);
                        if (!skipb) warp_tma_load_pair(dstb, mb, fb, 0, b1, b2);
                        if (first) warp_tma_load(dst + 32768, tile_map, fb, (sa2 & 1) * 64, a1, G_CTX + (sa2 >> 1));
                        if (k < K_SPLIT && lane == 0 && !prank)
                            asm volatile("st.relaxed.gpu.global.u32 [%0], %1;" :: "l"(&g_sync.step[0][0] + m * 4 + c), "r"(k) : "memory");
                        if (k == K_MEET) request();
                        if (PF_NAR && (uint32_t)(k - PF_NAR) < (3 * TRIPLES + 1) / 2) {
                            const uint32_t g = prm.ostep[79 - 2 * (k - PF_NAR)] >> 1;
                            warp_prefetch((const char*)g_scr + (uint32_t)((G_CTX + g) * (SEQ * 256) + m * 32768 + c * 4096), 4096);
                            warp_prefetch(prm.wo + (uint32_t)(g * 262144 + (m * 8 + c) * 2048), 2048);
                        }
                        if (st == 3) gph ^= 1;
                    }
                    for (unsigned n = 0; ~inputs_seen(0, n) || inputs_seen(1, n) != 255;) {}
                }
#pragma unroll 1
                for (uint32_t st = 0; st < 4; st++) { mbar_wait(bars + B_GEMPTY + 8 * st, gph ^ (st < (nk & 3))); mbar_wait(bars + B_AEMPTY + 16 + 8 * st, a_parity(2 + st)); }
                unsigned left = 0;
                if (lane == 0) asm volatile("atom.relaxed.gpu.global.add.u32 %0, [%1], 1;" : "=r"(left) : "l"(&g_sync.done) : "memory");
                if (__shfl_sync(0xffffffffu, left, 0) == NCTA - 1)
#pragma unroll 1
                    for (uint32_t i = lane * 8; i < sizeof(Sync); i += 256) *(unsigned long long*)((char*)&g_sync + i) = 0;
            }
        } else if (warp <= 2) {
            if (blockIdx.x < SEQ / 16) {
                const uint32_t r0 = 16 * blockIdx.x + 8 * (warp - 1), gbuf = bars + SM_GATE + 4 * (r0 & 15);
                float z[4];
#pragma unroll 1
                for (uint32_t i = 0; i < 8; i++) {
                    const uint32_t off = (i & 3) * 512 + lane * 16;
                    const uint4* xp = (const uint4*)((const char*)prm.x + ((r0 + (i & 4)) * 2048 + off));
                    const uint4 wv = __ldg((const uint4*)((const char*)prm.gate_w + off));
                    uint4 xv[4];
#pragma unroll
                    for (int r = 0; r < 4; r++) { xv[r] = __ldg(xp + r * 128); if (!(i & 3)) z[r] = 0.f; }
                    const uint32_t ws[4] = {wv.x, wv.y, wv.z, wv.w};
#pragma unroll
                    for (int e = 0; e < 4; e++)
#pragma unroll
                        for (int r = 0; r < 4; r++) {
                            const uint32_t xs = e == 0 ? xv[r].x : e == 1 ? xv[r].y : e == 2 ? xv[r].z : xv[r].w;
                            z[r] = fmaf(__uint_as_float(xs << 16), __uint_as_float(ws[e] << 16), z[r]);
                            z[r] = fmaf(__uint_as_float(xs & 0xffff0000u), __uint_as_float(ws[e] & 0xffff0000u), z[r]);
                        }
                    if ((i & 3) == 3) {
#pragma unroll
                        for (int o = 16; o > 0; o >>= 1)
#pragma unroll
                            for (int r = 0; r < 4; r++) z[r] += __shfl_xor_sync(0xffffffffu, z[r], o);
                        const float zr = lane & 2 ? (lane & 1 ? z[3] : z[2]) : (lane & 1 ? z[1] : z[0]);
                        asm volatile("st.shared.f32 [%0], %1;" :: "r"(gbuf + 4 * ((i & 4) + (lane & 3))), "f"(1.f / (1.f + __expf(-zr))) : "memory");
                    }
                }
                fence_proxy_async_smem();
                __syncwarp();
                warp_bulk_store((char*)g_gate + 4 * r0, gbuf, 32);
                bulk_commit();
                bulk_wait<0>();
                __syncwarp();
                if (lane == 0) red_add(&g_sync.count[3], 1);
            }
            __syncwarp();
            {
                const int w = warp - 1;
                uint32_t sph = 0, nann = 0;
                int unsent = 0, nunsent = 0;
                bool urgent = false;
                auto announce = [&]() {
                    if (!urgent) return;
                    bulk_wait<0>();
                    __syncwarp();
                    const uint32_t hb = bars + B_HALF + 8 * (nann & 3);
                    if (w == 0) {
                        mbar_arrive_if(lane == 0, hb);
                    } else {
                        mbar_wait(hb, (nann >> 2) & 1);
                        const uint32_t type = item_type(unsent), m = item_row(unsent), c = item_col(unsent);
                        const uint32_t word = type < T_B ? c >> 3 : type == T_B ? 2 : offsetof(Sync, ctx) / 8 + m;
                        const uint32_t bit = type < T_B ? 8 * (c & 7) : type == T_B ? 4 * m : type == T_LOCAL ? 32 + c : c;
                        if (lane < nunsent) red_add((unsigned long long*)((char*)&g_sync + 8 * word), 1ull << bit);
                        __syncwarp();
                    }
                    nann++;
                    nunsent = 0; urgent = false;
                };
                int held = first_item(), it;
                bool qfree = false;
                do {
                    if (!__all_sync(0xffffffffu, mbar_test(bars + B_IFULL + 8 * (qn % QDEPTH), (qn / QDEPTH) & 1))) announce();
                    it = __shfl_sync(0xffffffffu, next_item(lane == 0), 0);
                    const int itype = item_type(it);
                    const bool keep_held = itype == T_LOCAL && (item_type(held) != T_B || (it & ITEM_READY));
                    if (itype >= T_ATTN && held < 0) {
                        urgent = nunsent;
                        mbar_arrive_if(lane == 0 && !qfree, bars + B_QFREE);
                        qfree = true;
                    }
#pragma unroll 1
                    for (int pass = held < 0 || keep_held; pass < 2; pass++) {
                        if (pass && (itype < T_OUT || itype == T_END)) break;
                        const int cur = pass ? it : held, type = item_type(cur), m = item_row(cur), c = item_col(cur);
                        const bool local = type == T_LOCAL;
                        const int grp = pass ? (local ? G_LOC : G_CTX) + c : type * 32 + 2 * c;
#pragma unroll 1
                        for (int i = 0; i < 4 - 2 * pass; i++) {
                            const int b = i & 1;
                            const bool alt = i >= 2 && itype == T_ATTN;
                            const uint32_t full = bars + (alt ? B_ALT + 8 * w : B_SFULL + 16 * w + 8 * b), par = alt ? 0 : sph;
                            if (i == 3 - 2 * pass || !__all_sync(0xffffffffu, mbar_test(full, par))) announce();
                            mbar_wait(full, par);
                            fence_proxy_async_smem();
                            warp_tma_store(&prm.m[local ? M_SCR_LOQ : M_SCR_ST], sb + (alt ? 32768 : SM_STAGING) + w * 16384 + b * 8192,
                                         local ? b * 128 + w * 64 : b * 64, local ? m * 64 : m * 128 + w * 64, grp + (i >> 1));
                            bulk_commit();
                            bulk_wait_read<0>();
                            __syncwarp();
                            mbar_arrive_if(lane == 0 && !alt, bars + B_SEMPTY + 16 * w + 8 * b);
                            sph ^= b & !alt;
                        }
                        mbar_arrive_if(lane == 0 && !qfree && itype >= T_ATTN, bars + B_QFREE);
                        qfree |= itype >= T_ATTN;
                        if (lane == nunsent) unsent = cur;
                        nunsent++;
                        urgent = nunsent == 32 || !local;
                    }
                    if (!keep_held) held = itype < T_OUT ? it : -1;
                } while (item_type(it) != T_END);
                announce();
                if (item_type(next_item(lane == 0)) == T_OUT) next_item(lane == 0);
            }
        } else {
            if (elect_one()) {
                uint32_t ordy = 0;
                unsigned long long cnt_lo = 0, cnt_hi = 0;
                int late = 0;
                auto refresh = [&]() {
                    if (!late && cnt_lo == 0xccccccccccccccccull && cnt_hi == SEQ / 8) late = 1;
                    asm volatile("ld.acquire.gpu.global.v2.u64 {%0, %1}, [%2];" : "=l"(cnt_lo), "=l"(cnt_hi) : "l"(late ? &g_sync.count[0] : &g_sync.count[2]) : "memory");
                };
                auto inputs_ready = [&](int it) -> bool {
                    const int m = item_row(it), c = item_col(it);
                    if (item_type(it) == T_ATTN) return late && ((c < 16 ? cnt_lo : cnt_hi) >> (4 * (c & 14)) & 255) == 48;
                    return late || (cnt_hi == SEQ / 8 && (cnt_lo >> (4 * m) & 15) == 12 && (cnt_lo >> (4 * max(m - 1, 0)) & 15) == 12);
                };
                auto publish = [&](int it, int step) {
                    const uint32_t slot = qn % QDEPTH;
                    mbar_wait(bars + B_IEMPTY + 8 * slot, ((qn / QDEPTH) & 1) ^ 1);
                    for (uint32_t r = 0; r < 2; r++) {
                        const uint32_t rb = map_cta(bars, r);
                        asm volatile("mbarrier.arrive.expect_tx.shared::cluster.b64 _, [%0], 4;" :: "r"(rb + B_IFULL + 8 * slot) : "memory");
                        asm volatile("st.async.shared::cluster.mbarrier::complete_tx::bytes.u32 [%0], %1, [%2];"
                                     :: "r"(rb + SM_QUEUE + 4 * slot), "r"(it + r * step), "r"(rb + B_IFULL + 8 * slot) : "memory");
                    }
                    qn++;
                };
                int asc = 1;
                int it;
                do {
                    if (rank == 0) {
                        mbar_wait(bars + B_WANT, qn & 1);
                        unsigned i;
                        asm volatile("atom.relaxed.gpu.global.add.u32 %0, [%1], 1;" : "=r"(i) : "l"(&g_sync.next) : "memory");
                        if (cnt_lo != 0x3030303030303030ull || cnt_hi != cnt_lo) refresh();
                        i += NPAIR;
                        const int pit = i < NITEMS ? prm.items[i] : T_END << 13, type = item_type(pit);
                        int step = type == T_LOCAL ? 16 : 1;
                        it = pit + (pit & (step == 1 ? 15 : 0x1f0));
                        if (type == T_ATTN) {
                            if (!asc) { it += 1; step = -1; }
                            it |= asc << 9;
                        }
                        asc = type != T_ATTN || item_row(pit) == 0 || !asc;
                        if (inputs_ready(it)) it |= ITEM_READY;
                        publish(it, step);
                    } else {
                        it = next_item(true);
                    }
                    if ((item_type(it) == T_ATTN || item_type(it) == T_LOCAL) && !(it & ITEM_READY)) {
                        unsigned n = 0;
                        while (!inputs_ready(it)) { refresh(); spin_guard(n); }
                        asm volatile("st.release.cta.shared.u32 [%0], %1;" :: "r"(bars + SM_ORDY + 4), "r"(ordy += 256) : "memory");
                    }
                } while (item_type(it) != T_END);
                if (rank == 0) {
                    mbar_wait(bars + B_WANT, qn & 1);
                    const unsigned i = atomicAdd(&g_sync.next_out, 1u), t = i < 32 ? 31 - i : i - 32;
                    it = i < 64 ? T_OUT << 13 | ((t & 3) * 2 + (i >> 5)) << 4 | (t >> 2) * 2 : T_END << 13;
                    publish(it, 1);
                } else {
                    it = next_item(true);
                }
                if (item_type(it) == T_OUT) {
                    const uint32_t m = item_row(it), half = item_col(it) & 1, tile = m * 2 + (item_col(it) >> 1);
                    unsigned* split = (unsigned*)((char*)g_sync.split + 4 * tile);
                    unsigned long long rdy = 0;
                    int state = rank ? 2 : 0;
                    for (unsigned n = 0; rdy != 0xffffffffffull || state < 2; spin_guard(n)) {
                        if (rdy != 0xffffffffffull) {
                            rdy = ld_acquire((const unsigned long long*)((char*)g_sync.ctx + 8 * m));
                            asm volatile("st.release.cta.shared.u64 [%0], %1;" :: "r"(bars + SM_ORDY), "l"(rdy) : "memory");
                        }
                        unsigned steps = 0;
                        if (state == 1) {
                            steps = ld_acquire(split);
                        } else if (state == 0 && mbar_test(bars + B_WANT, qn & 1)) {
                            state = 1;
                            unsigned seen;
                            asm volatile("atom.acq_rel.gpu.global.exch.b32 %0, [%1], 1;" : "=r"(seen) : "l"(split) : "memory");
                            if (seen) {
                                const unsigned long long v = ld_acquire((const unsigned long long*)((char*)g_sync.step + 8 * tile));
                                const int d = (int)(v >> 32) - (int)v;
                                steps = (WIDE + min(max(half ? d : -d, K_MEET - K_SPLIT), K_SPLIT - K_MEET)) >> 1;
                                atomicExch(split, WIDE - steps);
                            }
                        }
                        if (steps > 1) { publish(T_END << 13 | steps, 0); state = 2; PMARK(1, 0xF400 + steps); }
                    }
                    if (rank) next_item(true);
                }
                #pragma unroll 1
                for (uint32_t n = qn; n < qn + QDEPTH && rank == 0; n++) mbar_wait(bars + B_IEMPTY + 8 * (n % QDEPTH), ((n / QDEPTH) & 1) ^ 1);
            }
        }
    } else {
        reg_inc<232>();
        const int wg = (warp >> 2) - 1, wq = warp & 3;
        uint32_t gph = 0;
        uint32_t kvn = 0;
        const uint32_t dA = make_desc(sb + wg * 8192, 16);
        uint32_t ti = 0;
        uint32_t sph = 1;
        const uint32_t stg = sb + SM_STAGING + wg * 16384;
        const uint32_t stg_lane = stg + (wq * 16 + (lane & 15)) * 128 + (((lane >> 4) ^ (lane & 7)) << 4);
        auto write_blocks = [&](auto n, uint32_t off, const uint32_t* v) {
            uint32_t a = stg_lane;
            asm volatile("" : "+r"(a));
            a += off;
#pragma unroll
            for (int j = 0; j < decltype(n)::value; j++)
                stmatrix_x4((a ^ (32 * (j & 3))) + (j >> 2) * 8192, v[4 * j], v[4 * j + 1], v[4 * j + 2], v[4 * j + 3]);
        };
        auto release = [&](uint32_t bar) { mbar_arrive_if(lane == 0, bars + bar); };
        const uint32_t bars_lane = map_cta(bars, lane & 1);
        auto release_stage = [&](uint32_t st) { mbar_arrive_cluster_if(lane < 2, bars_lane + B_GEMPTY + 8 * st); };
        auto take_item = [&]() -> int {
            return __shfl_sync(0xffffffffu, next_item(lane == 0, false), 0);
        };
        auto stage_acquire = [&](int b) { mbar_spin(bars + B_SEMPTY + 16 * wg + 8 * b, sph); };
        auto stage_publish = [&](int b) {
            __syncwarp();
            release(B_SFULL + 16 * wg + 8 * b);
        };
        auto stage_chunk = [&](int b, const uint32_t* v) {
            stage_acquire(b);
            write_blocks(std::integral_constant<int, 4>(), b * 8192, v);
            stage_publish(b);
            if (b) sph ^= 1;
        };
        auto publish_pair = [&]() {
            __syncwarp();
            mbar_arrive_if(lane < 2, bars + B_SFULL + 16 * wg + 8 * lane);
            sph ^= 1;
        };
        auto gemm_step = [&](float (&acc)[128], uint32_t dB, int& k) {
            const uint32_t st = k & 3;
            wgmma_wait<0>();
            release_stage((k - 1) & 3);
            mbar_spin(bars + B_GFULL + 8 * st, gph);
            const uint64_t da = full_desc(dA + st * (GST_BYTES >> 4)), db = full_desc(dB + st * (GST_BYTES >> 4));
            wgmma_fence();
#pragma unroll
            for (int kk = 0; kk < 4; kk++) wgmma_ss_n256_tb(acc, da + 2 * kk, db + 128 * kk, 1);
            wgmma_commit();
            gph ^= st == 3;
            k++;
        };
        if (wg == 1) bar_arrive(1, 256);
        int it = first_item();
        while (true) {
            if (item_type(it) <= T_LOCAL) {
                float acc[128];
                uint32_t pk[64];
                bool pending = false;
                bool held_b = false;
                zero_regs(pk);
                const uint32_t dB = make_desc(sb + 16384, 8192);
                do {
                    const int type = item_type(it);
                    if (type == T_LOCAL) {
                        int ln = lane;
                        asm volatile("" : "+r"(ln));
                        const int g = ln >> 2, t = ln & 3, par = wq & 1;
                        const uint32_t hc = (wq >> 1) * 4, pl = sb + (par * 2 + wg) * LOC_PLANE;
                        const uint32_t a16 = (ln & 15) * 128 + (((hc + (ln >> 4)) ^ (ln & 7)) << 4), a8 = (ln & 7) * 128 + (((hc + (ln >> 3)) ^ (ln & 7)) << 4);
                        const bool first0 = 2 * t > g, first1 = 2 * t + 1 > g;
                        const uint32_t fmask = (first0 ? 0xffffu : 0u) | (first1 ? 0xffff0000u : 0u);
                        const bool edge = item_row(it) == 0;
                        uint32_t q[4][2][4], kf[9][4], vf[9][4];
                        float w[8];
                        mbar_spin(bars + B_GFULL, gph);
#pragma unroll
                        for (int u = 0; u < 4; u++) { ldsm_x4(q[u][0], pl + u * 2048 + a16); ldsm_x4(q[u][1], pl + u * 2048 + (a16 ^ 32)); }
#pragma unroll
                        for (int j = 0; j < 8; j++) w[j] = lds_f32(sb + 4 * LOC_PLANE + 4 * (2 * g + par) + 64 * j);
                        __syncwarp();
                        release_stage(0);
                        mbar_spin(bars + B_GFULL + 8, gph);
#pragma unroll
                        for (int n = 0; n < 9; n++) ldsm_x4(kf[n], pl + GST_BYTES + n * 1024 + a8);
                        __syncwarp();
                        release_stage(1);
                        float s[8][2];
#pragma unroll
                        for (int u = 0; u < 4; u++) {
                            float d[3][4];
#pragma unroll
                            for (int nt = 0; nt < 3; nt++) {
                                mma_k16_init(d[nt], q[u][0], kf[2 * u + nt][0], kf[2 * u + nt][1]);
                                mma_k16(d[nt], q[u][1], kf[2 * u + nt][2], kf[2 * u + nt][3]);
                            }
                            if (u == 0 && edge) { d[0][0] = -INFINITY; d[0][1] = -INFINITY; }
                            s[2 * u][0] = first0 ? d[0][0] : d[1][0]; s[2 * u][1] = first1 ? d[0][1] : d[1][1];
                            s[2 * u + 1][0] = first0 ? d[1][2] : d[2][2]; s[2 * u + 1][1] = first1 ? d[1][3] : d[2][3];
                        }
                        mbar_spin(bars + B_GFULL + 16, gph);
#pragma unroll
                        for (int u = 0; u < 4; u++) { ldsm_x4_t(vf[2 * u], pl + 2 * GST_BYTES + u * 2048 + a16); ldsm_x4_t(vf[2 * u + 1], pl + 2 * GST_BYTES + u * 2048 + (a16 ^ 32)); }
                        ldsm_x4_t(vf[8], pl + 2 * GST_BYTES + 8192 + a8);
                        __syncwarp();
                        release_stage(2);
                        float x[8];
#pragma unroll
                        for (int j = 0; j < 8; j++) x[j] = fmaxf(s[j][0], s[j][1]);
#pragma unroll
                        for (int o = 1; o < 4; o *= 2)
#pragma unroll
                            for (int j = 0; j < 8; j++) x[j] = fmaxf(x[j], __shfl_xor_sync(0xffffffffu, x[j], o));
#pragma unroll
                        for (int j = 0; j < 8; j++) {
                            const float n = x[j] * -LOC_SCALE;
                            s[j][0] = ex2(fmaf(s[j][0], LOC_SCALE, n)); s[j][1] = ex2(fmaf(s[j][1], LOC_SCALE, n));
                            x[j] = s[j][0] + s[j][1];
                        }
#pragma unroll
                        for (int o = 1; o < 4; o *= 2)
#pragma unroll
                            for (int j = 0; j < 8; j++) x[j] += __shfl_xor_sync(0xffffffffu, x[j], o);
                        mbar_spin(bars + B_GFULL + 24, gph);
                        release_stage(3);
                        it = take_item();
                        uint32_t ob[4][8];
#pragma unroll
                        for (int u = 0; u < 4; u++) {
                            const float r0 = rcp(x[2 * u]), r1 = rcp(x[2 * u + 1]), f0 = fmaf(-w[2 * u], r0, r0), f1 = fmaf(-w[2 * u + 1], r1, r1);
                            const uint32_t p0 = pack_bf16(s[2 * u][0] * f0, s[2 * u][1] * f0), p1 = pack_bf16(s[2 * u + 1][0] * f1, s[2 * u + 1][1] * f1);
                            const uint32_t pa[4] = {p0 & fmask, 0, p0 & ~fmask, p1 & fmask};
#pragma unroll
                            for (int c = 0; c < 4; c++) {
                                float ol[4];
                                mma_k16_init(ol, pa, vf[2 * u + (c >> 1)][2 * (c & 1)], vf[2 * u + (c >> 1)][2 * (c & 1) + 1]);
                                mma_k8(ol, 0, p1 & ~fmask, u < 3 ? vf[2 * u + 2 + (c >> 1)][2 * (c & 1)] : vf[8][c]);
                                ob[u][2 * c] = pack_bf16(ol[0], ol[1]);
                                ob[u][2 * c + 1] = pack_bf16(ol[2], ol[3]);
                            }
                        }
                        stage_acquire(0); stage_acquire(1);
#pragma unroll
                        for (int u = 0; u < 4; u++) {
                            stmatrix_x4(stg + par * 8192 + u * 2048 + a16, ob[u][0], ob[u][1], ob[u][2], ob[u][3]);
                            stmatrix_x4(stg + par * 8192 + u * 2048 + (a16 ^ 32), ob[u][4], ob[u][5], ob[u][6], ob[u][7]);
                        }
                        publish_pair();
                        bar_sync(4, 256);
                        gph ^= 1;
                        continue;
                    }
                    mbar_spin(bars + B_GFULL, gph);
                    bool more;
                    do {
                        wgmma_fence();
                        wgmma_ss_n256_tb_init(acc, full_desc(dA), full_desc(dB));
#pragma unroll
                        for (int kk = 1; kk < 4; kk++) wgmma_ss_n256_tb(acc, full_desc(dA) + 2 * kk, full_desc(dB) + 128 * kk, 1);
                        wgmma_commit();
                        const int nk = item_type(it) == T_K || item_type(it) == T_V ? 8 : 16;
                        int k = 1;
                        do {
                            if (pending) {
                                const int kf = k - 1 - wg;
                                if (kf == 0) stage_chunk(0, pk);
                                else if (kf == 1) stage_chunk(1, pk + 16);
                                else if (kf == KF2) stage_chunk(0, pk + 32);
                                else if (kf == KF2 + 1) stage_chunk(1, pk + 48);
                            }
                            gemm_step(acc, dB, k);
                        } while (k < nk);
                        held_b = item_type(it) == T_B;
                        const bool is_q = item_type(it) == T_Q;
                        it = take_item();
                        more = item_type(it) < T_LOCAL;
                        if (more) mbar_spin(bars + B_GFULL, gph);
                        wgmma_wait<0>();
                        fence_regs(acc);
                        release_stage(3);
                        if (is_q) {
#pragma unroll
                            for (int j = 0; j < 128; j++) acc[j] *= SM_SCALE;
                        }
#pragma unroll
                        for (int j = 0; j < 64; j++) pk[j] = pack_bf16(acc[2 * j], acc[2 * j + 1]);
                        pending = true;
                    } while (more);
                } while (item_type(it) < T_LOCAL || (item_type(it) == T_LOCAL && (!held_b || (it & ITEM_READY))));
                if (pending) {
                    stage_acquire(0); stage_acquire(1);
                    write_blocks(std::integral_constant<int, 8>(), 0, pk);
                    const bool borrow = item_type(it) == T_ATTN;
                    if (borrow) {
                        mbar_spin(bars + B_GEMPTY, gph ^ 1); mbar_spin(bars + B_GEMPTY + 8, gph ^ 1);
                    } else {
                        publish_pair();
                        stage_acquire(0); stage_acquire(1);
                    }
                    write_blocks(std::integral_constant<int, 8>(), borrow ? 32768 - SM_STAGING : 0, pk + 32);
                    publish_pair();
                    mbar_arrive_if(lane == 0 && borrow, bars + B_ALT + 8 * wg);
                }
                if (item_type(it) == T_END) { it = take_item(); break; }
            } else {
                float o[64], s[64];
                uint32_t pa[32], pb[32];
                zero_regs(o); zero_regs(s); zero_regs(pa);
                float n0 = 0.f, n1 = 0.f;
                bool shifted = false;
                float l0 = 1.f, l1 = 1.f, f0 = 0.f, f1 = 0.f, g0 = 0.f, g1 = 0.f;
                uint32_t has_pv = 0;
                int first = 0;
                int pending = 0;
                const uint32_t dK = make_desc(sb + SM_KV, 16), dV = make_desc(sb + SM_KV, 16384);
                const uint32_t lane_off = bars_lane - bars + B_AEMPTY - B_AFULL;
                int cur = 0;
                uint32_t qoff = 0;
                const int row = wg * 64 + wq * 16 + (lane >> 2);
                const float thr = (row & 63) - (lane & 3) * 2;
                uint32_t peek = 0;
                bool peek_ok = false, q_ok = false;
                auto kv_wait = [&](uint32_t n) { mbar_spin(bars + B_AFULL + 16 + 8 * (n & 3), (n >> 2) & 1); };
                auto kv_release = [&](uint32_t n) { mbar_arrive_cluster_if(lane < 2, bars_lane + B_AEMPTY + 16 + 8 * (n & 3)); };
                struct Slot { uint32_t bar, par, off; } slot[4];
                auto align = [&]() {
#pragma unroll
                    for (uint32_t i = 0; i < 4; i++) {
                        const uint32_t n = kvn + (i == 1 ? has_pv : i);
                        slot[i].bar = bars + B_AFULL + 16 + 8 * (n & 3); slot[i].par = (n >> 2) & 1; slot[i].off = (n & 3) * 2048;
                    }
                };
                align();
                auto scale_o = [&]() {
#pragma unroll
                    for (int j = 0; j < 16; j++) { o[4 * j] *= f0; o[4 * j + 1] *= f0; o[4 * j + 2] *= f1; o[4 * j + 3] *= f1; }
                };
                auto pack_o = [&](uint32_t (&v)[32]) {
#pragma unroll
                    for (int j = 0; j < 32; j++) v[j] = pack_bf16(o[2 * j], o[2 * j + 1]);
                };
                auto scales = [&]() { f0 = g0 * rcp(quad_sum(l0)); f1 = g1 * rcp(quad_sum(l1)); };
                auto step = [&](auto even, uint32_t (&pin)[32], uint32_t (&pout)[32], bool fresh, bool diag, bool last) {
                    constexpr bool EVEN = decltype(even)::value;
                    Slot& sk = slot[EVEN ? 0 : 2];
                    Slot& sv = slot[EVEN ? 1 : 3];
                    kvn += EVEN ? 1 + has_pv : 2;
                    mbar_spin(sk.bar, sk.par);
                    bar_sync(1 + wg, 256);
                    qk_gemm(s, dA + qoff, dK + sk.off);
                    if (EVEN && fresh) {
                        scales();
                        g0 = lds_f32(bars + SM_GATE + (ti & 1) * 512 + 4 * row); g1 = lds_f32(bars + SM_GATE + (ti & 1) * 512 + 4 * row + 32);
                        ti++;
                        n0 = 0.f; n1 = 0.f; l0 = 0.f; l1 = 0.f;
                        shifted = false;
                        if (has_pv) { stage_acquire(0); stage_acquire(1); }
                    }
                    if (!EVEN && pending) {
                        pack_o(pout);
                        write_blocks(std::integral_constant<int, 8>(), 0, pout);
                        publish_pair();
                    }
                    mbar_spin(sv.bar, sv.par);
                    pv_gemm(o, pin, dV + sv.off, EVEN || !first);
                    bar_arrive(2 - wg, 256);
                    sk.par ^= 1; sv.par ^= 1;
                    wgmma_wait<1>();
                    fence_regs(s);
                    mbar_arrive_cluster_if(lane < 2 && (!EVEN || has_pv), sk.bar + lane_off);
                    mbar_arrive_if(lane == 0 && last, bars + B_AEMPTY + 8 * ((ti - 1) & 1));
                    if (diag || shifted) {
                        if (diag) causal_mask(s, thr, wg);
                        if (shifted) shift_rows(s, n0, n1);
                    }
                    q_ok = mbar_test(bars + B_AFULL + 8 * (ti & 1), (ti >> 1) & 1);
                    peek_ok = mbar_test(bars + B_IFULL + 8 * (qn % QDEPTH), (qn / QDEPTH) & 1);
                    asm volatile("ld.shared.u32 %0, [%1];" : "=r"(peek) : "r"(bars + SM_QUEUE + 4 * (qn % QDEPTH)) : "memory");
                    float r0, r1;
                    exp_pack(pout, s, r0, r1);
                    if (__any_sync(0xffffffffu, fmaxf(r0, r1) >= SUM_LIMIT || (EVEN && fresh && !(lane & 3) && !(fminf(s[0], s[2]) >= -REF_RANGE)))) {
                        float x0, x1;
                        row_max(s, x0, x1);
                        if (!(EVEN && fresh)) { x0 = fmaxf(x0, 0.f); x1 = fmaxf(x1, 0.f); }
                        float a0 = ex2(-x0), a1 = ex2(-x1);
                        n0 += x0; n1 += x1;
                        shifted = true;
                        if (EVEN && fresh) { a0 = 1.f; a1 = 1.f; }
                        l0 *= a0; l1 *= a1;
                        wgmma_wait<0>();
                        fence_regs(o);
#pragma unroll
                        for (int q = 0; q < 16; q++) { o[4 * q] *= a0; o[4 * q + 1] *= a0; o[4 * q + 2] *= a1; o[4 * q + 3] *= a1; }
                        shift_rows(s, x0, x1);
                        exp_pack(pout, s, r0, r1);
                    }
                    l0 += r0; l1 += r1;
                    wgmma_wait<0>();
                    fence_regs(o);
                    fence_regs(pin);
                    mbar_arrive_cluster_if(lane < 2, sv.bar + lane_off);
                };
                auto copy_p = [&]() {
#pragma unroll
                    for (int j = 0; j < 32; j++) pa[j] = __float_as_uint(__uint_as_float(pb[j]) + __uint_as_float(prm.zero));
                };
                int rem = 0;
                mbar_spin(bars + B_AFULL + 8 * (ti & 1), (ti >> 1) & 1);
                while (true) {
                    const bool fresh = rem == 0;
                    if (fresh) {
                        if (has_pv) {
                            if (__all_sync(0xffffffffu, peek_ok)) {
                                mbar_arrive_cluster_if(lane == 0, bars0 + B_IEMPTY + 8 * (qn % QDEPTH));
                                qn++;
                                it = __shfl_sync(0xffffffffu, peek, 0);
                            } else {
                                it = take_item();
                            }
                            if (item_row(cur) < 2 || item_type(it) != T_ATTN) break;
                            if (!q_ok) mbar_spin(bars + B_AFULL + 8 * (ti & 1), (ti >> 1) & 1);
                        }
                        cur = it;
                        qoff = (ti & 1) * 2048;
                    }
                    const bool last = fresh ? item_row(cur) == 0 : rem == 1;
                    step(std::true_type(), pa, pb, fresh, item_asc(cur) ? last : fresh, last);
                    first = fresh;
                    if (fresh) {
                        pending = has_pv; has_pv = 1;
                        if (!pending) { kvn -= 2; align(); kvn += 2; slot[0].par ^= 1; slot[1].par ^= 1; }
                        else scale_o();
                        rem = item_row(cur);
                        if (rem == 0) {
                            copy_p();
                            continue;
                        }
                    } else if (--rem == 0) {
                        copy_p();
                        align();
                        continue;
                    }
                    step(std::false_type(), pb, pa, false, item_asc(cur) && rem == 1, rem == 1);
                    pending = 0; first = 0;
                    rem--;
                }
                const uint32_t skip = item_asc(cur) & ~item_row(cur) & 1;
                kvn += skip;
                const bool end = item_type(it) == T_END;
#pragma unroll 1
                for (int pass = pending ? 0 : 1; pass < 2; pass++) {
                    if (pass) {
                        kv_wait(kvn);
                        pv_gemm(o, pa, dV + (kvn & 3) * 2048, !first);
                        scales();
                        stage_acquire(0); stage_acquire(1);
                        if (end) it = take_item();
                        wgmma_wait<0>();
                        fence_regs(o);
                        kv_release(kvn);
                        kvn += 1 + skip;
                        scale_o();
                    }
                    pack_o(pb);
                    write_blocks(std::integral_constant<int, 8>(), 0, pb);
                    publish_pair();
                }
                if (end) break;
            }
        }
        if (item_type(it) == T_OUT) {
            float acc[128];
            const uint32_t dB = make_desc(sb + 16384, 8192);
            mbar_spin(bars + B_GFULL, gph);
            wgmma_fence();
            wgmma_ss_n256_tb_init(acc, full_desc(dA), full_desc(dB));
#pragma unroll
            for (int kk = 1; kk < 4; kk++) wgmma_ss_n256_tb(acc, full_desc(dA) + 2 * kk, full_desc(dB) + 128 * kk, 1);
            wgmma_commit();
            uint32_t ln;
            asm volatile("mov.u32 %0, %%laneid;" : "=r"(ln));
            const uint32_t slot = (it & 127) * 32768 + (wg * 128 + wq * 32 + ln) * 16;
            char* const mine = (char*)g_part + slot;
            int k = 1, nk = 80;
            do {
                if (k == K_MEET - 5) {
#pragma unroll
                    for (int j = 0; j < 8; j++) st_b128(mine + j * 4096, 0, 0, 0, 0);
                    __syncwarp();
                }
                if (k == K_SPLIT) nk = take_item() & 127;
                gemm_step(acc, dB, k);
            } while (k < nk);
            float lo[64];
            uint32_t pk[32];
            char* const other = (char*)g_part + (slot ^ (16 * 32768));
            auto fetch_other = [&]() {
#pragma unroll
                for (int j = 0; j < 8; j++) ld_b128(other + j * 4096, pk[4 * j], pk[4 * j + 1], pk[4 * j + 2], pk[4 * j + 3]);
            };
            auto triple = [&](auto first) {
                const uint32_t s0 = k & 3, s1 = (k + 1) & 3, o0 = s0 * (GST_BYTES >> 4), o1 = s1 * (GST_BYTES >> 4);
                wgmma_wait<0>();
                mbar_arrive_cluster_if(ln < (decltype(first)::value ? 2 : 4), bars_lane + B_GEMPTY + 8 * ((k - 1 - (ln >> 1)) & 3));
                mbar_spin(bars + B_GFULL + 8 * s0, gph);
                gph ^= s0 == 3;
                wgmma_fence();
#pragma unroll
                for (int kk = 0; kk < 4; kk++) {
                    if (decltype(first)::value && kk == 0) wgmma_ss_n128_tb_init(lo, full_desc(dA + o0), full_desc(dB + o0));
                    else wgmma_ss_n128_tb(lo, full_desc(dA + o0) + 2 * kk, full_desc(dB + o0) + 128 * kk, 1);
                }
                mbar_spin(bars + B_GFULL + 8 * s1, gph);
                gph ^= s1 == 3;
                wgmma_fence();
#pragma unroll
                for (int kk = 0; kk < 4; kk++) wgmma_ss_n128_tb(lo, full_desc(dA + o0 + 2048) + 2 * kk, full_desc(dB + o1 + 1024) + 128 * kk, 1);
#pragma unroll
                for (int kk = 0; kk < 4; kk++) wgmma_ss_n128_tb(lo, full_desc(dA + o1) + 2 * kk, full_desc(dB + o1) + 128 * kk, 1);
                wgmma_commit();
                k += 2;
            };
            triple(std::true_type());
            fence_regs(acc);
#pragma unroll
            for (int j = 0; j < 8; j++) {
                uint32_t v[4];
#pragma unroll
                for (int i = 0; i < 4; i++) v[i] = pack_bf16(acc[64 + 8 * j + 2 * i], acc[65 + 8 * j + 2 * i]);
                if (j == SPREAD) triple(std::false_type());
                st_b128(mine + j * 4096, ~v[0], v[1], v[2], v[3]);
            }
            triple(std::false_type());
            while (true) {
                fetch_other();
                bool miss = false;
#pragma unroll
                for (int j = 0; j < 8; j++) miss |= pk[4 * j] == 0;
                if (!__any_sync(0xffffffffu, miss)) break;
                while (__any_sync(0xffffffffu, pk[28] == 0)) ld_b128(other + 7 * 4096, pk[28], pk[29], pk[30], pk[31]);
            }
#pragma unroll
            for (int j = 0; j < 32; j++) {
                const uint32_t v = j & 3 ? pk[j] : ~pk[j];
                acc[2 * j] += __uint_as_float(v << 16); acc[2 * j + 1] += __uint_as_float(v & 0xffff0000u);
                asm volatile("" : "+f"(acc[2 * j]), "+f"(acc[2 * j + 1]) :: "memory");
            }
            stage_acquire(0); stage_acquire(1);
            wgmma_wait<0>();
            fence_regs(lo);
            mbar_arrive_cluster_if(ln < 4, bars_lane + B_GEMPTY + 8 * ((k - 1 - (ln >> 1)) & 3));
#pragma unroll
            for (int j = 0; j < 32; j++)
                pk[j] = pack_bf16(acc[2 * j] + lo[2 * j], acc[2 * j + 1] + lo[2 * j + 1]);
            write_blocks(std::integral_constant<int, 8>(), 0, pk);
            __syncwarp();
            uint4* dst = (uint4*)((char*)prm.out + (uint32_t)((item_row(it) * 128 + wg * 64 + wq * 16 + (ln >> 4)) * 2048 + item_col(it) * 256 + (ln & 15) * 16));
#pragma unroll
            for (int j = 0; j < 8; j++) {
                const int r = 2 * j + (ln >> 4);
                uint4 v;
                asm volatile("ld.shared.v4.u32 {%0, %1, %2, %3}, [%4];" : "=r"(v.x), "=r"(v.y), "=r"(v.z), "=r"(v.w)
                             : "r"(stg + wq * 2048 + r * 128 + (ln & 8) * 1024 + (((ln & 7) ^ (r & 7)) << 4)) : "memory");
                dst[j * 256] = v;
            }
        }
    }
}

typedef CUresult (*EncodeFn)(CUtensorMap*, CUtensorMapDataType, cuuint32_t, void*, const cuuint64_t*, const cuuint64_t*,
                             const cuuint32_t*, const cuuint32_t*, CUtensorMapInterleave, CUtensorMapSwizzle,
                             CUtensorMapL2promotion, CUtensorMapFloatOOBfill);

void encode3(EncodeFn fn, CUtensorMap* m, const void* ptr, uint64_t d0, uint64_t d1, uint64_t d2, uint64_t s1, uint64_t s2,
             uint32_t b0, uint32_t b1, uint32_t b2) {
    cuuint64_t dims[3] = {d0, d1, d2};
    cuuint64_t strides[2] = {s1, s2};
    cuuint32_t box[3] = {b0, b1, b2};
    cuuint32_t es[3] = {1, 1, 1};
    fn(m, CU_TENSOR_MAP_DATA_TYPE_BFLOAT16, 3, const_cast<void*>(ptr), dims, strides, box, es, CU_TENSOR_MAP_INTERLEAVE_NONE,
       CU_TENSOR_MAP_SWIZZLE_128B, CU_TENSOR_MAP_L2_PROMOTION_NONE, CU_TENSOR_MAP_FLOAT_OOB_FILL_NONE);
}
void map_act(EncodeFn fn, CUtensorMap* m, const void* p, int rows, int cols, int box_rows) {
    encode3(fn, m, p, cols, rows, 1, (uint64_t)cols * 2, (uint64_t)cols * rows * 2, 64, box_rows, 1);
}
void map_wgt(EncodeFn fn, CUtensorMap* m, const void* p, int K, int N) {
    encode3(fn, m, p, 64, K, N / 64, (uint64_t)N * 2, 128, 64, 64, 2);
}

void build_schedule(Params& p) {
    int n = 0;
    auto add = [&](int type, int col, int row) { p.items[n++] = (uint16_t)(type << 13 | col << 4 | row); };
    auto add_qkv = [&](int c) {
        for (int m = 0; m < 8; m++) add(T_Q, c, m);
        for (int m = 0; m < 8; m++) add(T_K, c, m);
        for (int m = 0; m < 8; m++) add(T_V, c, m);
    };
    int ldist = 200, ldist2 = 260, lstep = 8, beta = 26, tail = 32, late = 6, early = 8, epos = 100;
    int order[16] = {6, 7, 8, 9, 10, 11, 12, 13, 14, 15, 5, 4, 3, 2, 1, 0};
    uint16_t proj[480];
    for (int m = 0; m < 8; m++) for (int c = 0; c < 12; c++) add(T_B, c, m);
    for (int c = 0; c < 16; c++) add_qkv(c);
    for (int i = 0; i < 480; i++) proj[i] = p.items[i];
    n = 0;
    for (int i = 0, l = 0; i < 480; i++) {
        p.items[n++] = proj[i];
        for (; l < 64 && i >= (l < 40 ? ldist + lstep * l / 8 : ldist2 + lstep * (l - 40) / 8); l++) add(T_LOCAL, l & 3, l >> 2);
    }
    const int a0 = n;
    for (int key = 0; key < 4000; key++)
        for (int r = 0; r < 32; r++)
            for (int j = 7; j >= 0; j--)
                if ((j ? (7 - j) * 40 + r * beta : 3999) == key) add(T_ATTN, 2 * order[r >> 1] + (r & 1), j);
    int t0 = n;
    for (int work = 0; work < 32 * 136 * tail / 100;) work += 4 * (p.items[--t0] & 15) + 3;
    for (int i = t0 + 1; i < n; i++)
        for (int j = i; j > t0 && (p.items[j] & 15) > (p.items[j - 1] & 15); j--) { const uint16_t t = p.items[j]; p.items[j] = p.items[j - 1]; p.items[j - 1] = t; }
    for (int r = early - 1; r >= 0; r--) {
        const uint16_t t = p.items[n - 32 + early - 1];
        for (int j = n - 32 + early - 1; j > n - epos; j--) p.items[j] = p.items[j - 1];
        p.items[n - epos] = t;
    }
    for (int moved = 0; moved < 2 && late >= 0; moved++)
        for (int i = a0; i < n; i++)
            if (p.items[i] == (T_ATTN << 13 | (2 * order[15] + moved) << 4 | late)) {
                for (int j = i; j + 1 < n; j++) p.items[j] = p.items[j + 1];
                p.items[n - 1] = (uint16_t)(T_ATTN << 13 | (2 * order[15] + moved) << 4 | late);
                break;
            }
    for (int s = 0, lo = 0, hi = WIDE - 1; s < 80; s++) {
        const int r = s / 2, g = r < 8 ? 32 + r : 2 * order[r / 2 - 4] + (r & 1);
        p.ostep[s >= WIDE ? s : r & 1 ? hi-- : lo++] = (uint8_t)(2 * g + (s & 1));
    }
}

void build_params(Params& p, void* const* d_in, void* d_out) {
    void* fnp = nullptr;
    cudaDriverEntryPointQueryResult qr;
    cudaGetDriverEntryPoint("cuTensorMapEncodeTiled", &fnp, cudaEnableDefault, &qr);
    EncodeFn fn = (EncodeFn)fnp;
    void* scr = nullptr;
    cudaGetSymbolAddress(&scr, g_scr);
    map_act(fn, &p.m[M_X], d_in[0], SEQ, 1024, 128);
    map_act(fn, &p.m[M_C], d_in[1], SEQ, 512, 128);
    map_wgt(fn, &p.m[M_WQ], d_in[2], 1024, 4096);
    map_wgt(fn, &p.m[M_WUK], d_in[3], 512, 4096);
    map_wgt(fn, &p.m[M_WUV], d_in[4], 512, 4096);
    map_wgt(fn, &p.m[M_WO], d_in[5], 4096, 1024);
    map_wgt(fn, &p.m[M_WQKV], d_in[7], 1024, 3072);
    map_wgt(fn, &p.m[M_WOB], d_in[8], 1024, 1024);
    encode3(fn, &p.m[M_SCR_LD], scr, 128, SEQ, G_TOTAL, 256, (uint64_t)SEQ * 256, 64, 128, 1);
    encode3(fn, &p.m[M_SCR_LOC], scr, 256, SEQ / 2, G_TOTAL, 512, (uint64_t)SEQ * 256, 64, 72, 1);
    encode3(fn, &p.m[M_SCR_LOQ], scr, 256, SEQ / 2, G_TOTAL, 512, (uint64_t)SEQ * 256, 64, 64, 1);
    encode3(fn, &p.m[M_SCR_ST], scr, 128, SEQ, G_TOTAL, 256, (uint64_t)SEQ * 256, 64, 64, 1);
    p.x = (const __nv_bfloat16*)d_in[0];
    p.gate_w = (const __nv_bfloat16*)d_in[9];
    p.zero = 0;
    p.wo = (const char*)d_in[5];
    p.out = (__nv_bfloat16*)d_out;
    build_schedule(p);
}

}

extern "C" void kernel_launch(void* const* d_in, const int* in_sizes, int n_in, void* d_out, int out_size) {
    (void)in_sizes; (void)n_in; (void)out_size;
    Params p;
    build_params(p, d_in, d_out);
    cudaFuncSetAttribute(fused_kernel, cudaFuncAttributeMaxDynamicSharedMemorySize, SM_TOTAL);
    fused_kernel<<<NCTA, 384, SM_TOTAL>>>(p);
}
```

```cpp
#include <cuda_runtime.h>
#include <cuda_bf16.h>
#include <cuda.h>
#include <stddef.h>
#include <stdint.h>
#include <type_traits>

namespace {

constexpr int SEQ = 2048;
constexpr int G_Q = 0, G_K = 32, G_V = 64, G_B = 96, G_CTX = G_Q, G_LOC = G_B, G_TOTAL = 120;

__device__ __align__(1024) __nv_bfloat16 g_scr[(size_t)G_TOTAL * SEQ * 128];
__device__ __align__(128) float g_gate[SEQ];

__device__ __forceinline__ uint32_t smem_u32(const void* p) { return (uint32_t)__cvta_generic_to_shared(p); }
__device__ __forceinline__ bool elect_one() {
    uint32_t p;
    asm volatile("{\n.reg .pred P;\nelect.sync _|P, 0xffffffff;\nselp.u32 %0, 1, 0, P;\n}\n" : "=r"(p));
    return p != 0;
}
__device__ __forceinline__ void mbar_init(uint32_t bar, uint32_t count) {
    asm volatile("mbarrier.init.shared::cta.b64 [%0], %1;" :: "r"(bar), "r"(count) : "memory");
}
__device__ __forceinline__ void mbar_expect_tx(uint32_t bar, uint32_t bytes) {
    asm volatile("mbarrier.arrive.expect_tx.shared::cta.b64 _, [%0], %1;" :: "r"(bar), "r"(bytes) : "memory");
}
__device__ __forceinline__ uint32_t cluster_rank() { uint32_t r; asm("mov.u32 %0, %%cluster_ctarank;" : "=r"(r)); return r; }
__device__ __forceinline__ uint32_t map_cta(uint32_t addr, uint32_t cta) {
    uint32_t r; asm("mapa.shared::cluster.u32 %0, %1, %2;" : "=r"(r) : "r"(addr), "r"(cta)); return r;
}
__device__ __forceinline__ void mbar_arrive_cluster_if(bool pred, uint32_t cluster_bar) {
    asm volatile("{\n.reg .pred P;\nsetp.ne.u32 P, %1, 0;\n@P mbarrier.arrive.shared::cluster.b64 _, [%0];\n}\n"
                 :: "r"(cluster_bar), "r"((uint32_t)pred) : "memory");
}
__device__ __forceinline__ void mbar_arrive_cluster_n_if(bool pred, uint32_t cluster_bar, uint32_t count) {
    asm volatile("{\n.reg .pred P;\nsetp.ne.u32 P, %1, 0;\n@P mbarrier.arrive.shared::cluster.b64 _, [%0], %2;\n}\n"
                 :: "r"(cluster_bar), "r"((uint32_t)pred), "r"(count) : "memory");
}
__device__ __forceinline__ void mbar_arrive_if(bool pred, uint32_t bar) {
    asm volatile("{\n.reg .pred P;\nsetp.ne.u32 P, %1, 0;\n@P mbarrier.arrive.shared::cta.b64 _, [%0];\n}\n"
                 :: "r"(bar), "r"((uint32_t)pred) : "memory");
}
__device__ __forceinline__ bool mbar_test(uint32_t bar, uint32_t parity) {
    uint32_t ok;
    asm volatile("{\n.reg .pred P;\nmbarrier.test_wait.parity.shared::cta.b64 P, [%1], %2;\nselp.u32 %0, 1, 0, P;\n}\n"
                 : "=r"(ok) : "r"(bar), "r"(parity) : "memory");
    return ok != 0;
}
__device__ __forceinline__ void mbar_wait(uint32_t bar, uint32_t parity) {
    asm volatile("{\n.reg .pred P;\n.reg .u32 c;\n"
                 "mov.u32 c, 0;\n"
                 "SPIN:\n"
                 "mbarrier.try_wait.parity.shared::cta.b64 P, [%0], %1;\n"
                 "@P bra DONE;\n"
                 "add.u32 c, c, 1;\n"
                 "setp.lt.u32 P, c, 4194304;\n"
                 "@P bra SPIN;\n"
                 "trap;\n"
                 "DONE:\n}\n" :: "r"(bar), "r"(parity) : "memory");
}
__device__ __forceinline__ void mbar_spin(uint32_t bar, uint32_t parity) {
    asm volatile("{\n.reg .pred P;\n"
                 "SPIN:\n"
                 "mbarrier.try_wait.parity.shared::cta.b64 P, [%0], %1;\n"
                 "@!P bra SPIN;\n}\n" :: "r"(bar), "r"(parity) : "memory");
}
__device__ __forceinline__ void bar_sync(int id, int n) { asm volatile("bar.sync %0, %1;" :: "r"(id), "r"(n) : "memory"); }
__device__ __forceinline__ void bar_arrive(int id, int n) { asm volatile("bar.arrive %0, %1;" :: "r"(id), "r"(n) : "memory"); }
__device__ __forceinline__ void fence_proxy_async_smem() { asm volatile("fence.proxy.async.shared::cta;" ::: "memory"); }
__device__ __forceinline__ void tma_load_3d(uint32_t dst, const CUtensorMap* map, uint32_t bar, int c0, int c1, int c2) {
    asm volatile("cp.async.bulk.tensor.3d.shared::cluster.global.mbarrier::complete_tx::bytes [%0], [%1, {%3, %4, %5}], [%2];"
                 :: "r"(dst), "l"(map), "r"(bar), "r"(c0), "r"(c1), "r"(c2) : "memory");
}
__device__ __forceinline__ void warp_expect_tx(uint32_t bar, uint32_t bytes) {
    asm volatile("{\n.reg .pred P;\nelect.sync _|P, 0xffffffff;\n@P mbarrier.arrive.expect_tx.shared::cta.b64 _, [%0], %1;\n}\n"
                 :: "r"(bar), "r"(bytes) : "memory");
}
__device__ __forceinline__ void warp_tma_load(uint32_t dst, const CUtensorMap* map, uint32_t bar, int c0, int c1, int c2) {
    asm volatile("{\n.reg .pred P;\nelect.sync _|P, 0xffffffff;\n"
                 "@P cp.async.bulk.tensor.3d.shared::cluster.global.mbarrier::complete_tx::bytes [%0], [%1, {%3, %4, %5}], [%2];\n}\n"
                 :: "r"(dst), "l"(map), "r"(bar), "r"(c0), "r"(c1), "r"(c2) : "memory");
}
__device__ __forceinline__ void warp_tma_load_pair(uint32_t dst, const CUtensorMap* map, uint32_t bar, int c0, int c1, int c2) {
    asm volatile("{\n.reg .pred P;\nelect.sync _|P, 0xffffffff;\n"
                 "@P cp.async.bulk.tensor.3d.shared::cluster.global.mbarrier::complete_tx::bytes.multicast::cluster"
                 " [%0], [%1, {%3, %4, %5}], [%2], %6;\n}\n"
                 :: "r"(dst), "l"(map), "r"(bar), "r"(c0), "r"(c1), "r"(c2), "h"((uint16_t)3) : "memory");
}
__device__ __forceinline__ void warp_bulk_load(uint32_t dst, const void* src, uint32_t bytes, uint32_t bar) {
    asm volatile("{\n.reg .pred P;\nelect.sync _|P, 0xffffffff;\n"
                 "@P cp.async.bulk.shared::cluster.global.mbarrier::complete_tx::bytes [%0], [%1], %2, [%3];\n}\n"
                 :: "r"(dst), "l"(src), "r"(bytes), "r"(bar) : "memory");
}
__device__ __forceinline__ void warp_tma_store(const CUtensorMap* map, uint32_t src, int c0, int c1, int c2) {
    asm volatile("{\n.reg .pred P;\nelect.sync _|P, 0xffffffff;\n"
                 "@P cp.async.bulk.tensor.3d.global.shared::cta.bulk_group [%0, {%2, %3, %4}], [%1];\n}\n"
                 :: "l"(map), "r"(src), "r"(c0), "r"(c1), "r"(c2) : "memory");
}
__device__ __forceinline__ void warp_bulk_store(void* dst, uint32_t src, uint32_t bytes) {
    asm volatile("{\n.reg .pred P;\nelect.sync _|P, 0xffffffff;\n"
                 "@P cp.async.bulk.global.shared::cta.bulk_group [%0], [%1], %2;\n}\n" :: "l"(dst), "r"(src), "r"(bytes) : "memory");
}
__device__ __forceinline__ void warp_prefetch(const void* src, uint32_t bytes) {
    asm volatile("{\n.reg .pred P;\nelect.sync _|P, 0xffffffff;\n@P cp.async.bulk.prefetch.L2.global [%0], %1;\n}\n" :: "l"(src), "r"(bytes) : "memory");
}
__device__ __forceinline__ void bulk_commit() { asm volatile("cp.async.bulk.commit_group;" ::: "memory"); }
template <int N> __device__ __forceinline__ void bulk_wait_read() { asm volatile("cp.async.bulk.wait_group.read %0;" :: "n"(N) : "memory"); }
template <int N> __device__ __forceinline__ void bulk_wait() { asm volatile("cp.async.bulk.wait_group %0;" :: "n"(N) : "memory"); }
__device__ __forceinline__ void wgmma_fence() { asm volatile("wgmma.fence.sync.aligned;" ::: "memory"); }
__device__ __forceinline__ void wgmma_commit() { asm volatile("wgmma.commit_group.sync.aligned;" ::: "memory"); }
template <int N> __device__ __forceinline__ void wgmma_wait() { asm volatile("wgmma.wait_group.sync.aligned %0;" :: "n"(N) : "memory"); }
template <int N> __device__ __forceinline__ void fence_regs(float (&d)[N]) {
#pragma unroll
    for (int i = 0; i < N; i++) asm volatile("" : "+f"(d[i]) :: "memory");
}
template <int N> __device__ __forceinline__ void fence_regs(uint32_t (&d)[N]) {
#pragma unroll
    for (int i = 0; i < N; i++) asm volatile("" : "+r"(d[i]) :: "memory");
}
template <int N> __device__ __forceinline__ void reg_dec() { asm volatile("setmaxnreg.dec.sync.aligned.u32 %0;" :: "n"(N)); }
template <int N> __device__ __forceinline__ void reg_inc() { asm volatile("setmaxnreg.inc.sync.aligned.u32 %0;" :: "n"(N)); }
__device__ __forceinline__ uint32_t pack_bf16(float lo, float hi) {
    uint32_t r; asm("cvt.rn.bf16x2.f32 %0, %1, %2;" : "=r"(r) : "f"(hi), "f"(lo)); return r;
}
__device__ __forceinline__ void stmatrix_x4(uint32_t addr, uint32_t r0, uint32_t r1, uint32_t r2, uint32_t r3) {
    asm volatile("stmatrix.sync.aligned.m8n8.x4.shared.b16 [%0], {%1, %2, %3, %4};"
                 :: "r"(addr), "r"(r0), "r"(r1), "r"(r2), "r"(r3) : "memory");
}
__device__ __forceinline__ float ex2(float x) { float y; asm("ex2.approx.ftz.f32 %0, %1;" : "=f"(y) : "f"(x)); return y; }

constexpr uint32_t DESC_HI = (1024 >> 4) | (1u << 30);
__device__ __forceinline__ uint32_t make_desc(uint32_t addr, uint32_t lbo) {
    uint32_t lo = ((addr & 0x3FFFF) >> 4) | ((lbo >> 4) << 16);
    asm volatile("" : "+r"(lo));
    return lo;
}
__device__ __forceinline__ uint64_t full_desc(uint32_t lo) {
    uint64_t d; asm("mov.b64 %0, {%1, %2};" : "=l"(d) : "r"(lo), "r"(DESC_HI)); return d;
}

__device__ __forceinline__ void wgmma_ss_n256_tb_init(float (&d)[128], uint64_t da, uint64_t db) {
    asm volatile("{\n.reg .pred p;\n"
        "setp.ne.b32 p, 0, 0;\n"
        "wgmma.mma_async.sync.aligned.m64n256k16.f32.bf16.bf16 "
        "{%0, %1, %2, %3, %4, %5, %6, %7, %8, %9, %10, %11, %12, %13, %14, %15, %16, %17, %18, %19, %20, "
        "%21, %22, %23, %24, %25, %26, %27, %28, %29, %30, %31, %32, %33, %34, %35, %36, %37, %38, %39, %40, "
        "%41, %42, %43, %44, %45, %46, %47, %48, %49, %50, %51, %52, %53, %54, %55, %56, %57, %58, %59, %60, "
        "%61, %62, %63, %64, %65, %66, %67, %68, %69, %70, %71, %72, %73, %74, %75, %76, %77, %78, %79, %80, "
        "%81, %82, %83, %84, %85, %86, %87, %88, %89, %90, %91, %92, %93, %94, %95, %96, %97, %98, %99, "
        "%100, %101, %102, %103, %104, %105, %106, %107, %108, %109, %110, %111, %112, %113, %114, %115, "
        "%116, %117, %118, %119, %120, %121, %122, %123, %124, %125, %126, %127},"
        " %128, %129, p, 1, 1, 0, 1;\n}\n"
        : "=f"(d[0]), "=f"(d[1]), "=f"(d[2]), "=f"(d[3]), "=f"(d[4]), "=f"(d[5]), "=f"(d[6]), "=f"(d[7]),
        "=f"(d[8]), "=f"(d[9]), "=f"(d[10]), "=f"(d[11]), "=f"(d[12]), "=f"(d[13]), "=f"(d[14]), "=f"(d[15]),
        "=f"(d[16]), "=f"(d[17]), "=f"(d[18]), "=f"(d[19]), "=f"(d[20]), "=f"(d[21]), "=f"(d[22]),
        "=f"(d[23]), "=f"(d[24]), "=f"(d[25]), "=f"(d[26]), "=f"(d[27]), "=f"(d[28]), "=f"(d[29]),
        "=f"(d[30]), "=f"(d[31]), "=f"(d[32]), "=f"(d[33]), "=f"(d[34]), "=f"(d[35]), "=f"(d[36]),
        "=f"(d[37]), "=f"(d[38]), "=f"(d[39]), "=f"(d[40]), "=f"(d[41]), "=f"(d[42]), "=f"(d[43]),
        "=f"(d[44]), "=f"(d[45]), "=f"(d[46]), "=f"(d[47]), "=f"(d[48]), "=f"(d[49]), "=f"(d[50]),
        "=f"(d[51]), "=f"(d[52]), "=f"(d[53]), "=f"(d[54]), "=f"(d[55]), "=f"(d[56]), "=f"(d[57]),
        "=f"(d[58]), "=f"(d[59]), "=f"(d[60]), "=f"(d[61]), "=f"(d[62]), "=f"(d[63]), "=f"(d[64]),
        "=f"(d[65]), "=f"(d[66]), "=f"(d[67]), "=f"(d[68]), "=f"(d[69]), "=f"(d[70]), "=f"(d[71]),
        "=f"(d[72]), "=f"(d[73]), "=f"(d[74]), "=f"(d[75]), "=f"(d[76]), "=f"(d[77]), "=f"(d[78]),
        "=f"(d[79]), "=f"(d[80]), "=f"(d[81]), "=f"(d[82]), "=f"(d[83]), "=f"(d[84]), "=f"(d[85]),
        "=f"(d[86]), "=f"(d[87]), "=f"(d[88]), "=f"(d[89]), "=f"(d[90]), "=f"(d[91]), "=f"(d[92]),
        "=f"(d[93]), "=f"(d[94]), "=f"(d[95]), "=f"(d[96]), "=f"(d[97]), "=f"(d[98]), "=f"(d[99]),
        "=f"(d[100]), "=f"(d[101]), "=f"(d[102]), "=f"(d[103]), "=f"(d[104]), "=f"(d[105]), "=f"(d[106]),
        "=f"(d[107]), "=f"(d[108]), "=f"(d[109]), "=f"(d[110]), "=f"(d[111]), "=f"(d[112]), "=f"(d[113]),
        "=f"(d[114]), "=f"(d[115]), "=f"(d[116]), "=f"(d[117]), "=f"(d[118]), "=f"(d[119]), "=f"(d[120]),
        "=f"(d[121]), "=f"(d[122]), "=f"(d[123]), "=f"(d[124]), "=f"(d[125]), "=f"(d[126]), "=f"(d[127])
        : "l"(da), "l"(db));
}
__device__ __forceinline__ void wgmma_ss_n256_tb(float (&d)[128], uint64_t da, uint64_t db, int scale_d) {
    asm volatile("{\n.reg .pred p;\n"
        "setp.ne.b32 p, %130, 0;\n"
        "wgmma.mma_async.sync.aligned.m64n256k16.f32.bf16.bf16 "
        "{%0, %1, %2, %3, %4, %5, %6, %7, %8, %9, %10, %11, %12, %13, %14, %15, %16, %17, %18, %19, %20, "
        "%21, %22, %23, %24, %25, %26, %27, %28, %29, %30, %31, %32, %33, %34, %35, %36, %37, %38, %39, %40, "
        "%41, %42, %43, %44, %45, %46, %47, %48, %49, %50, %51, %52, %53, %54, %55, %56, %57, %58, %59, %60, "
        "%61, %62, %63, %64, %65, %66, %67, %68, %69, %70, %71, %72, %73, %74, %75, %76, %77, %78, %79, %80, "
        "%81, %82, %83, %84, %85, %86, %87, %88, %89, %90, %91, %92, %93, %94, %95, %96, %97, %98, %99, "
        "%100, %101, %102, %103, %104, %105, %106, %107, %108, %109, %110, %111, %112, %113, %114, %115, "
        "%116, %117, %118, %119, %120, %121, %122, %123, %124, %125, %126, %127},"
        " %128, %129, p, 1, 1, 0, 1;\n}\n"
        : "+f"(d[0]), "+f"(d[1]), "+f"(d[2]), "+f"(d[3]), "+f"(d[4]), "+f"(d[5]), "+f"(d[6]), "+f"(d[7]),
        "+f"(d[8]), "+f"(d[9]), "+f"(d[10]), "+f"(d[11]), "+f"(d[12]), "+f"(d[13]), "+f"(d[14]), "+f"(d[15]),
        "+f"(d[16]), "+f"(d[17]), "+f"(d[18]), "+f"(d[19]), "+f"(d[20]), "+f"(d[21]), "+f"(d[22]),
        "+f"(d[23]), "+f"(d[24]), "+f"(d[25]), "+f"(d[26]), "+f"(d[27]), "+f"(d[28]), "+f"(d[29]),
        "+f"(d[30]), "+f"(d[31]), "+f"(d[32]), "+f"(d[33]), "+f"(d[34]), "+f"(d[35]), "+f"(d[36]),
        "+f"(d[37]), "+f"(d[38]), "+f"(d[39]), "+f"(d[40]), "+f"(d[41]), "+f"(d[42]), "+f"(d[43]),
        "+f"(d[44]), "+f"(d[45]), "+f"(d[46]), "+f"(d[47]), "+f"(d[48]), "+f"(d[49]), "+f"(d[50]),
        "+f"(d[51]), "+f"(d[52]), "+f"(d[53]), "+f"(d[54]), "+f"(d[55]), "+f"(d[56]), "+f"(d[57]),
        "+f"(d[58]), "+f"(d[59]), "+f"(d[60]), "+f"(d[61]), "+f"(d[62]), "+f"(d[63]), "+f"(d[64]),
        "+f"(d[65]), "+f"(d[66]), "+f"(d[67]), "+f"(d[68]), "+f"(d[69]), "+f"(d[70]), "+f"(d[71]),
        "+f"(d[72]), "+f"(d[73]), "+f"(d[74]), "+f"(d[75]), "+f"(d[76]), "+f"(d[77]), "+f"(d[78]),
        "+f"(d[79]), "+f"(d[80]), "+f"(d[81]), "+f"(d[82]), "+f"(d[83]), "+f"(d[84]), "+f"(d[85]),
        "+f"(d[86]), "+f"(d[87]), "+f"(d[88]), "+f"(d[89]), "+f"(d[90]), "+f"(d[91]), "+f"(d[92]),
        "+f"(d[93]), "+f"(d[94]), "+f"(d[95]), "+f"(d[96]), "+f"(d[97]), "+f"(d[98]), "+f"(d[99]),
        "+f"(d[100]), "+f"(d[101]), "+f"(d[102]), "+f"(d[103]), "+f"(d[104]), "+f"(d[105]), "+f"(d[106]),
        "+f"(d[107]), "+f"(d[108]), "+f"(d[109]), "+f"(d[110]), "+f"(d[111]), "+f"(d[112]), "+f"(d[113]),
        "+f"(d[114]), "+f"(d[115]), "+f"(d[116]), "+f"(d[117]), "+f"(d[118]), "+f"(d[119]), "+f"(d[120]),
        "+f"(d[121]), "+f"(d[122]), "+f"(d[123]), "+f"(d[124]), "+f"(d[125]), "+f"(d[126]), "+f"(d[127])
        : "l"(da), "l"(db), "r"(scale_d));
}
__device__ __forceinline__ void wgmma_ss_n128(float (&d)[64], uint64_t da, uint64_t db, int scale_d) {
    asm volatile("{\n.reg .pred p;\n"
        "setp.ne.b32 p, %66, 0;\n"
        "wgmma.mma_async.sync.aligned.m64n128k16.f32.bf16.bf16 "
        "{%0, %1, %2, %3, %4, %5, %6, %7, %8, %9, %10, %11, %12, %13, %14, %15, %16, %17, %18, %19, %20, "
        "%21, %22, %23, %24, %25, %26, %27, %28, %29, %30, %31, %32, %33, %34, %35, %36, %37, %38, %39, %40, "
        "%41, %42, %43, %44, %45, %46, %47, %48, %49, %50, %51, %52, %53, %54, %55, %56, %57, %58, %59, %60, "
        "%61, %62, %63},"
        " %64, %65, p, 1, 1, 0, 0;\n}\n"
        : "+f"(d[0]), "+f"(d[1]), "+f"(d[2]), "+f"(d[3]), "+f"(d[4]), "+f"(d[5]), "+f"(d[6]), "+f"(d[7]),
        "+f"(d[8]), "+f"(d[9]), "+f"(d[10]), "+f"(d[11]), "+f"(d[12]), "+f"(d[13]), "+f"(d[14]), "+f"(d[15]),
        "+f"(d[16]), "+f"(d[17]), "+f"(d[18]), "+f"(d[19]), "+f"(d[20]), "+f"(d[21]), "+f"(d[22]),
        "+f"(d[23]), "+f"(d[24]), "+f"(d[25]), "+f"(d[26]), "+f"(d[27]), "+f"(d[28]), "+f"(d[29]),
        "+f"(d[30]), "+f"(d[31]), "+f"(d[32]), "+f"(d[33]), "+f"(d[34]), "+f"(d[35]), "+f"(d[36]),
        "+f"(d[37]), "+f"(d[38]), "+f"(d[39]), "+f"(d[40]), "+f"(d[41]), "+f"(d[42]), "+f"(d[43]),
        "+f"(d[44]), "+f"(d[45]), "+f"(d[46]), "+f"(d[47]), "+f"(d[48]), "+f"(d[49]), "+f"(d[50]),
        "+f"(d[51]), "+f"(d[52]), "+f"(d[53]), "+f"(d[54]), "+f"(d[55]), "+f"(d[56]), "+f"(d[57]),
        "+f"(d[58]), "+f"(d[59]), "+f"(d[60]), "+f"(d[61]), "+f"(d[62]), "+f"(d[63])
        : "l"(da), "l"(db), "r"(scale_d));
}
__device__ __forceinline__ void wgmma_rs_n128_tb(float (&d)[64], uint32_t a0, uint32_t a1, uint32_t a2, uint32_t a3, uint64_t db, int scale_d) {
    asm volatile("{\n.reg .pred p;\n"
        "setp.ne.b32 p, %69, 0;\n"
        "wgmma.mma_async.sync.aligned.m64n128k16.f32.bf16.bf16 "
        "{%0, %1, %2, %3, %4, %5, %6, %7, %8, %9, %10, %11, %12, %13, %14, %15, %16, %17, %18, %19, %20, "
        "%21, %22, %23, %24, %25, %26, %27, %28, %29, %30, %31, %32, %33, %34, %35, %36, %37, %38, %39, %40, "
        "%41, %42, %43, %44, %45, %46, %47, %48, %49, %50, %51, %52, %53, %54, %55, %56, %57, %58, %59, %60, "
        "%61, %62, %63},"
        " {%64, %65, %66, %67}, %68, p, 1, 1, 1;\n}\n"
        : "+f"(d[0]), "+f"(d[1]), "+f"(d[2]), "+f"(d[3]), "+f"(d[4]), "+f"(d[5]), "+f"(d[6]), "+f"(d[7]),
        "+f"(d[8]), "+f"(d[9]), "+f"(d[10]), "+f"(d[11]), "+f"(d[12]), "+f"(d[13]), "+f"(d[14]), "+f"(d[15]),
        "+f"(d[16]), "+f"(d[17]), "+f"(d[18]), "+f"(d[19]), "+f"(d[20]), "+f"(d[21]), "+f"(d[22]),
        "+f"(d[23]), "+f"(d[24]), "+f"(d[25]), "+f"(d[26]), "+f"(d[27]), "+f"(d[28]), "+f"(d[29]),
        "+f"(d[30]), "+f"(d[31]), "+f"(d[32]), "+f"(d[33]), "+f"(d[34]), "+f"(d[35]), "+f"(d[36]),
        "+f"(d[37]), "+f"(d[38]), "+f"(d[39]), "+f"(d[40]), "+f"(d[41]), "+f"(d[42]), "+f"(d[43]),
        "+f"(d[44]), "+f"(d[45]), "+f"(d[46]), "+f"(d[47]), "+f"(d[48]), "+f"(d[49]), "+f"(d[50]),
        "+f"(d[51]), "+f"(d[52]), "+f"(d[53]), "+f"(d[54]), "+f"(d[55]), "+f"(d[56]), "+f"(d[57]),
        "+f"(d[58]), "+f"(d[59]), "+f"(d[60]), "+f"(d[61]), "+f"(d[62]), "+f"(d[63])
        : "r"(a0), "r"(a1), "r"(a2), "r"(a3), "l"(db), "r"(scale_d));
}
__device__ __forceinline__ void wgmma_ss_n128_tb_init(float (&d)[64], uint64_t da, uint64_t db) {
    asm volatile("{\n.reg .pred p;\n"
        "setp.ne.b32 p, 0, 0;\n"
        "wgmma.mma_async.sync.aligned.m64n128k16.f32.bf16.bf16 "
        "{%0, %1, %2, %3, %4, %5, %6, %7, %8, %9, %10, %11, %12, %13, %14, %15, %16, %17, %18, %19, %20, "
        "%21, %22, %23, %24, %25, %26, %27, %28, %29, %30, %31, %32, %33, %34, %35, %36, %37, %38, %39, %40, "
        "%41, %42, %43, %44, %45, %46, %47, %48, %49, %50, %51, %52, %53, %54, %55, %56, %57, %58, %59, %60, "
        "%61, %62, %63},"
        " %64, %65, p, 1, 1, 0, 1;\n}\n"
        : "=f"(d[0]), "=f"(d[1]), "=f"(d[2]), "=f"(d[3]), "=f"(d[4]), "=f"(d[5]), "=f"(d[6]), "=f"(d[7]),
        "=f"(d[8]), "=f"(d[9]), "=f"(d[10]), "=f"(d[11]), "=f"(d[12]), "=f"(d[13]), "=f"(d[14]), "=f"(d[15]),
        "=f"(d[16]), "=f"(d[17]), "=f"(d[18]), "=f"(d[19]), "=f"(d[20]), "=f"(d[21]), "=f"(d[22]),
        "=f"(d[23]), "=f"(d[24]), "=f"(d[25]), "=f"(d[26]), "=f"(d[27]), "=f"(d[28]), "=f"(d[29]),
        "=f"(d[30]), "=f"(d[31]), "=f"(d[32]), "=f"(d[33]), "=f"(d[34]), "=f"(d[35]), "=f"(d[36]),
        "=f"(d[37]), "=f"(d[38]), "=f"(d[39]), "=f"(d[40]), "=f"(d[41]), "=f"(d[42]), "=f"(d[43]),
        "=f"(d[44]), "=f"(d[45]), "=f"(d[46]), "=f"(d[47]), "=f"(d[48]), "=f"(d[49]), "=f"(d[50]),
        "=f"(d[51]), "=f"(d[52]), "=f"(d[53]), "=f"(d[54]), "=f"(d[55]), "=f"(d[56]), "=f"(d[57]),
        "=f"(d[58]), "=f"(d[59]), "=f"(d[60]), "=f"(d[61]), "=f"(d[62]), "=f"(d[63])
        : "l"(da), "l"(db));
}
__device__ __forceinline__ void wgmma_ss_n128_tb(float (&d)[64], uint64_t da, uint64_t db, int scale_d) {
    asm volatile("{\n.reg .pred p;\n"
        "setp.ne.b32 p, %66, 0;\n"
        "wgmma.mma_async.sync.aligned.m64n128k16.f32.bf16.bf16 "
        "{%0, %1, %2, %3, %4, %5, %6, %7, %8, %9, %10, %11, %12, %13, %14, %15, %16, %17, %18, %19, %20, "
        "%21, %22, %23, %24, %25, %26, %27, %28, %29, %30, %31, %32, %33, %34, %35, %36, %37, %38, %39, %40, "
        "%41, %42, %43, %44, %45, %46, %47, %48, %49, %50, %51, %52, %53, %54, %55, %56, %57, %58, %59, %60, "
        "%61, %62, %63},"
        " %64, %65, p, 1, 1, 0, 1;\n}\n"
        : "+f"(d[0]), "+f"(d[1]), "+f"(d[2]), "+f"(d[3]), "+f"(d[4]), "+f"(d[5]), "+f"(d[6]), "+f"(d[7]),
        "+f"(d[8]), "+f"(d[9]), "+f"(d[10]), "+f"(d[11]), "+f"(d[12]), "+f"(d[13]), "+f"(d[14]), "+f"(d[15]),
        "+f"(d[16]), "+f"(d[17]), "+f"(d[18]), "+f"(d[19]), "+f"(d[20]), "+f"(d[21]), "+f"(d[22]),
        "+f"(d[23]), "+f"(d[24]), "+f"(d[25]), "+f"(d[26]), "+f"(d[27]), "+f"(d[28]), "+f"(d[29]),
        "+f"(d[30]), "+f"(d[31]), "+f"(d[32]), "+f"(d[33]), "+f"(d[34]), "+f"(d[35]), "+f"(d[36]),
        "+f"(d[37]), "+f"(d[38]), "+f"(d[39]), "+f"(d[40]), "+f"(d[41]), "+f"(d[42]), "+f"(d[43]),
        "+f"(d[44]), "+f"(d[45]), "+f"(d[46]), "+f"(d[47]), "+f"(d[48]), "+f"(d[49]), "+f"(d[50]),
        "+f"(d[51]), "+f"(d[52]), "+f"(d[53]), "+f"(d[54]), "+f"(d[55]), "+f"(d[56]), "+f"(d[57]),
        "+f"(d[58]), "+f"(d[59]), "+f"(d[60]), "+f"(d[61]), "+f"(d[62]), "+f"(d[63])
        : "l"(da), "l"(db), "r"(scale_d));
}

enum { M_X = 0, M_C, M_WQ, M_WUK, M_WUV, M_WQKV, M_WO, M_WOB, M_SCR_LD, M_SCR_LOC, M_SCR_LOQ, M_SCR_ST, M_COUNT };
enum { T_Q = 0, T_K, T_V, T_B, T_OUT, T_LOCAL, T_ATTN, T_END };
constexpr int NCTA = 132, NPAIR = NCTA / 2;
constexpr int NITEMS = 480 + 64 + 256;
constexpr int TRIPLES = 3, WIDE = 80 - 3 * TRIPLES;
struct Params {
    CUtensorMap m[M_COUNT];
    const __nv_bfloat16* x;
    const __nv_bfloat16* gate_w;
    const char* wo;
    __nv_bfloat16* out;
    uint32_t zero;
    uint16_t items[NITEMS];
    uint8_t ostep[80];
};
__device__ __forceinline__ int item_type(int it) { return it >> 13; }
__device__ __forceinline__ int item_row(int it) { return it & 15; }
__device__ __forceinline__ int item_col(int it) { return (it >> 4) & 31; }
__device__ __forceinline__ int item_asc(int it) { return (it >> 9) & 1; }
constexpr int ITEM_READY = 1 << 10;

struct __align__(128) Sync {
    unsigned long long count[4];
    __align__(128) unsigned long long ctx[16];
    unsigned next, next_out, done;
    __align__(128) unsigned step[32][2];
    unsigned split[32];
};
__device__ Sync g_sync;
__device__ uint4 g_part[128][8][256];

constexpr uint32_t GST_BYTES = 49152, SM_KV = 65536, SM_STAGING = 196608, SM_BARS = SM_STAGING + 32768;
constexpr uint32_t B_GFULL = 0, B_GEMPTY = 32, B_AFULL = 64, B_AEMPTY = 112, B_SFULL = 160, B_SEMPTY = 192,
                   B_IFULL = 224, B_IEMPTY = 288, B_XFREE = 352, B_WANT = 384, B_HALF = 416,
                   SM_ORDY = 448, SM_QUEUE = 456, B_ALT = 488, B_QFREE = 504, SM_GATE = 512, SM_TOTAL = SM_BARS + 1536;
constexpr int QDEPTH = 8;
constexpr int K_MEET = 14, K_SPLIT = 26;
constexpr int K_FETCH = 20;
constexpr uint32_t LOC_PLANE = 72 * 128;
constexpr float SM_SCALE = 0.08838834764831845f * 1.4426950408889634f;
constexpr float LOC_SCALE = 0.17677669529663687f * 1.4426950408889634f;
constexpr float SUM_LIMIT = 1152921504606846976.f;
constexpr float REF_RANGE = 32.f;

__device__ __forceinline__ unsigned ld_acquire(const unsigned* p) {
    unsigned v; asm volatile("ld.acquire.gpu.global.u32 %0, [%1];" : "=r"(v) : "l"(p) : "memory"); return v;
}
__device__ __forceinline__ unsigned long long ld_acquire(const unsigned long long* p) {
    unsigned long long v; asm volatile("ld.acquire.gpu.global.u64 %0, [%1];" : "=l"(v) : "l"(p) : "memory"); return v;
}
__device__ __forceinline__ void st_b128(void* p, uint32_t a, uint32_t b, uint32_t c, uint32_t d) {
    asm volatile("{\n.reg .b128 v;\n.reg .b64 lo, hi;\nmov.b64 lo, {%1, %2};\nmov.b64 hi, {%3, %4};\nmov.b128 v, {lo, hi};\n"
                 "st.relaxed.gpu.global.b128 [%0], v;\n}\n" :: "l"(p), "r"(a), "r"(b), "r"(c), "r"(d) : "memory");
}
__device__ __forceinline__ void ld_b128(const void* p, uint32_t& a, uint32_t& b, uint32_t& c, uint32_t& d) {
    asm volatile("{\n.reg .b128 v;\n.reg .b64 lo, hi;\nld.relaxed.gpu.global.b128 v, [%4];\nmov.b128 {lo, hi}, v;\n"
                 "mov.b64 {%0, %1}, lo;\nmov.b64 {%2, %3}, hi;\n}\n" : "=r"(a), "=r"(b), "=r"(c), "=r"(d) : "l"(p) : "memory");
}
__device__ __forceinline__ void spin_guard(unsigned& n) {
    asm volatile("{\n.reg .pred P;\nadd.u32 %0, %0, 1;\nsetp.gt.u32 P, %0, 16777216;\n@P trap;\n}\n" : "+r"(n));
    if (n > 1) __nanosleep(100);
}
__device__ __forceinline__ void red_add(unsigned long long* p, unsigned long long v) {
    asm volatile("red.release.gpu.global.add.u64 [%0], %1;" :: "l"(p), "l"(v) : "memory");
}
__device__ __forceinline__ float rcp(float x) { float y; asm("rcp.approx.ftz.f32 %0, %1;" : "=f"(y) : "f"(x)); return y; }
__device__ __forceinline__ float lds_f32(uint32_t addr) {
    float v; asm volatile("ld.shared.f32 %0, [%1];" : "=f"(v) : "r"(addr) : "memory"); return v;
}
__device__ __forceinline__ void ldsm_x4(uint32_t (&r)[4], uint32_t addr) {
    asm volatile("ldmatrix.sync.aligned.m8n8.x4.shared.b16 {%0, %1, %2, %3}, [%4];"
                 : "=r"(r[0]), "=r"(r[1]), "=r"(r[2]), "=r"(r[3]) : "r"(addr) : "memory");
}
__device__ __forceinline__ void ldsm_x4_t(uint32_t (&r)[4], uint32_t addr) {
    asm volatile("ldmatrix.sync.aligned.m8n8.x4.trans.shared.b16 {%0, %1, %2, %3}, [%4];"
                 : "=r"(r[0]), "=r"(r[1]), "=r"(r[2]), "=r"(r[3]) : "r"(addr) : "memory");
}
__device__ __forceinline__ void mma_k16(float (&d)[4], const uint32_t (&a)[4], uint32_t b0, uint32_t b1) {
    asm("mma.sync.aligned.m16n8k16.row.col.f32.bf16.bf16.f32 {%0,%1,%2,%3}, {%4,%5,%6,%7}, {%8,%9}, {%0,%1,%2,%3};"
        : "+f"(d[0]), "+f"(d[1]), "+f"(d[2]), "+f"(d[3]) : "r"(a[0]), "r"(a[1]), "r"(a[2]), "r"(a[3]), "r"(b0), "r"(b1));
}
__device__ __forceinline__ void mma_k16_init(float (&d)[4], const uint32_t (&a)[4], uint32_t b0, uint32_t b1) {
    asm("{\n.reg .f32 z;\nmov.f32 z, 0f00000000;\n"
        "mma.sync.aligned.m16n8k16.row.col.f32.bf16.bf16.f32 {%0,%1,%2,%3}, {%4,%5,%6,%7}, {%8,%9}, {z,z,z,z};\n}\n"
        : "=f"(d[0]), "=f"(d[1]), "=f"(d[2]), "=f"(d[3]) : "r"(a[0]), "r"(a[1]), "r"(a[2]), "r"(a[3]), "r"(b0), "r"(b1));
}
__device__ __forceinline__ void mma_k8(float (&d)[4], uint32_t a0, uint32_t a1, uint32_t b0) {
    asm("mma.sync.aligned.m16n8k8.row.col.f32.bf16.bf16.f32 {%0,%1,%2,%3}, {%4,%5}, {%6}, {%0,%1,%2,%3};"
        : "+f"(d[0]), "+f"(d[1]), "+f"(d[2]), "+f"(d[3]) : "r"(a0), "r"(a1), "r"(b0));
}
template <typename T, int N> __device__ __forceinline__ void zero_regs(T (&d)[N]) {
#pragma unroll
    for (int i = 0; i < N; i++) d[i] = 0;
}
__device__ __forceinline__ float quad_max(float v) {
    v = fmaxf(v, __shfl_xor_sync(0xffffffffu, v, 1));
    return fmaxf(v, __shfl_xor_sync(0xffffffffu, v, 2));
}
__device__ __forceinline__ float quad_sum(float v) {
    v += __shfl_xor_sync(0xffffffffu, v, 1);
    return v + __shfl_xor_sync(0xffffffffu, v, 2);
}

__device__ __forceinline__ void qk_gemm(float (&s)[64], uint32_t q_lo, uint32_t k_lo) {
    const uint64_t dq = full_desc(q_lo), dk = full_desc(k_lo);
    fence_regs(s);
    wgmma_fence();
#pragma unroll
    for (int kk = 0; kk < 8; kk++) {
        const uint32_t o = (kk >> 2) * 1024 + (kk & 3) * 2;
        wgmma_ss_n128(s, dq + o, dk + o, kk != 0);
    }
    wgmma_commit();
}
__device__ __forceinline__ void pv_gemm(float (&o)[64], uint32_t (&p)[32], uint32_t v_lo, int accumulate) {
    const uint64_t dv = full_desc(v_lo);
    fence_regs(o);
    fence_regs(p);
    wgmma_fence();
#pragma unroll
    for (int kk = 0; kk < 8; kk++)
        wgmma_rs_n128_tb(o, p[4 * kk], p[4 * kk + 1], p[4 * kk + 2], p[4 * kk + 3], dv + kk * 128, kk != 0 || accumulate);
    wgmma_commit();
}
__device__ __forceinline__ void row_max(const float (&s)[64], float& x0, float& x1) {
    float z0 = fmaxf(s[0], s[1]), z1 = fmaxf(s[2], s[3]);
    x0 = fmaxf(s[4], s[5]); x1 = fmaxf(s[6], s[7]);
#pragma unroll
    for (int j = 2; j < 16; j += 2) {
        z0 = fmaxf(z0, fmaxf(s[4 * j], s[4 * j + 1]));
        z1 = fmaxf(z1, fmaxf(s[4 * j + 2], s[4 * j + 3]));
        x0 = fmaxf(x0, fmaxf(s[4 * j + 4], s[4 * j + 5]));
        x1 = fmaxf(x1, fmaxf(s[4 * j + 6], s[4 * j + 7]));
    }
    x0 = quad_max(fmaxf(x0, z0)); x1 = quad_max(fmaxf(x1, z1));
}
__device__ __forceinline__ void exp_pack(uint32_t (&p)[32], const float (&s)[64], float& r0, float& r1) {
#pragma unroll
    for (int j = 0; j < 16; j++) {
        const float e0 = ex2(s[4 * j]), e1 = ex2(s[4 * j + 1]), e2 = ex2(s[4 * j + 2]), e3 = ex2(s[4 * j + 3]);
        if (j == 0) { r0 = e0 + e1; r1 = e2 + e3; }
        else { r0 += e0 + e1; r1 += e2 + e3; }
        p[2 * j] = pack_bf16(e0, e1);
        p[2 * j + 1] = pack_bf16(e2, e3);
    }
}
__device__ __forceinline__ void shift_rows(float (&s)[64], float d0, float d1) {
#pragma unroll
    for (int j = 0; j < 16; j++) { s[4 * j] -= d0; s[4 * j + 1] -= d0; s[4 * j + 2] -= d1; s[4 * j + 3] -= d1; }
}
constexpr float MASKED = -3e38f;
template <int J0>
__device__ __forceinline__ void mask_triangle(float (&s)[64], float thr) {
#pragma unroll
    for (int j = 0; j < 16; j++) {
        const float m = __saturatef((float)(8 * (j >> 1) + (j & 1)) - thr);
        const int i = 4 * (J0 + (j >> 1)) + (j & 1);
        s[i] = fmaf(m, MASKED, s[i]);
        if (j < 14) s[i + 6] = fmaf(m, MASKED, s[i + 6]);
    }
}
__device__ __forceinline__ void causal_mask(float (&s)[64], float thr, int wg) {
    asm volatile("" : "+f"(thr));
    if (wg == 0) {
        mask_triangle<0>(s, thr);
#pragma unroll
        for (int j = 32; j < 64; j++) s[j] += MASKED;
    } else {
        mask_triangle<8>(s, thr);
    }
}

__global__ void __cluster_dims__(2, 1, 1) __launch_bounds__(384, 1) fused_kernel(const __grid_constant__ Params prm) {
    extern __shared__ __align__(1024) uint8_t smem[];
    const uint32_t sb = smem_u32(smem), bars = sb + SM_BARS;
    const int warp = __shfl_sync(0xffffffffu, threadIdx.x >> 5, 0), lane = threadIdx.x & 31;

    const uint32_t rank = cluster_rank();
    const uint32_t bars0 = map_cta(bars, 0), bars_peer = map_cta(bars, rank ^ 1);

    auto first_item = [&]() -> int {
        uint32_t pair = blockIdx.x >> 1;
        asm volatile("" : "+r"(pair));
        return prm.items[pair] + item_row(prm.items[pair]) + rank;
    };
    if (threadIdx.x == 256) {
        for (int k = 0; k < 4; k++) mbar_init(bars + B_GFULL + 8 * k, 1);
        asm volatile("fence.mbarrier_init.release.cluster;" ::: "memory");
        fence_proxy_async_smem();
    }
    if (threadIdx.x == 128) {
        for (int i = 0; i < 4; i++) { mbar_init(bars + B_GEMPTY + 8 * i, 16); mbar_init(bars + B_XFREE + 8 * i, 1); }
        for (int i = 0; i < 6; i++) { mbar_init(bars + B_AFULL + 8 * i, 1); mbar_init(bars + B_AEMPTY + 8 * i, i < 2 ? 8 : 16); }
        for (int i = 0; i < 4; i++) { mbar_init(bars + B_SFULL + 8 * i, 4); mbar_init(bars + B_SEMPTY + 8 * i, 1); }
        for (int i = 0; i < QDEPTH; i++) { mbar_init(bars + B_IFULL + 8 * i, 1); mbar_init(bars + B_IEMPTY + 8 * i, 23); }
        mbar_init(bars + B_WANT, 2);
        for (int i = 0; i < 4; i++) mbar_init(bars + B_HALF + 8 * i, 1);
        mbar_init(bars + B_ALT, 4); mbar_init(bars + B_ALT + 8, 4); mbar_init(bars + B_QFREE, 2);
        asm volatile("st.shared.u64 [%0], 0;" :: "r"(bars + SM_ORDY) : "memory");
        asm volatile("fence.mbarrier_init.release.cluster;\nfence.acq_rel.cta;" ::: "memory");
    }
    __syncwarp();
    asm volatile("barrier.cluster.arrive.relaxed.aligned;" ::: "memory");
    if (threadIdx.x == 256) {
        const int first_it = first_item();
#pragma unroll 1
        for (int k = 0; k < 4; k++) {
            const uint32_t dst = sb + k * GST_BYTES, fb = bars + B_GFULL + 8 * k;
            mbar_expect_tx(fb, GST_BYTES);
            tma_load_3d(dst, &prm.m[M_X], fb, k * 64, item_row(first_it) * 128, 0);
            tma_load_3d(dst + 16384, &prm.m[M_WQKV], fb, 0, k * 64, item_col(first_it) * 4);
            tma_load_3d(dst + 32768, &prm.m[M_WQKV], fb, 0, k * 64, item_col(first_it) * 4 + 2);
        }
    }
    __syncwarp();
    asm volatile("barrier.cluster.wait.acquire.aligned;" ::: "memory");

    uint32_t qn = 0;
    auto next_item = [&](bool releaser, bool bounded = true) -> int {
        const uint32_t slot = qn % QDEPTH;
        if (bounded) mbar_wait(bars + B_IFULL + 8 * slot, (qn / QDEPTH) & 1);
        else mbar_spin(bars + B_IFULL + 8 * slot, (qn / QDEPTH) & 1);
        uint32_t it;
        asm volatile("ld.shared.u32 %0, [%1];" : "=r"(it) : "r"(bars + SM_QUEUE + 4 * slot) : "memory");
        mbar_arrive_cluster_if(releaser, bars0 + B_IEMPTY + 8 * slot);
        qn++;
        return it;
    };

    if (warp < 4) {
        reg_dec<40>();
        if (warp == 0) {
            {
                uint32_t gph = 0;
                const uint32_t prank = __shfl_sync(0xffffffffu, rank, 0);
                auto request = [&]() { mbar_arrive_cluster_if(lane == 0, bars0 + B_WANT); };
                auto take_item = [&]() -> int { return __shfl_sync(0xffffffffu, next_item(lane == 0), 0); };
                auto inputs_seen = [&](uint32_t word, unsigned& n) -> uint32_t {
                    uint32_t v;
                    spin_guard(n);
                    asm volatile("ld.acquire.cta.shared.u32 %0, [%1];" : "=r"(v) : "r"(bars + SM_ORDY + 4 * word) : "memory");
                    return __shfl_sync(0xffffffffu, v, 0);
                };
                uint32_t oneed = 0;
                auto wait_inputs = [&](int it) {
                    if (it & ITEM_READY) return;
                    oneed += 256;
                    for (unsigned n = 0; inputs_seen(1, n) < oneed;) {}
                };
                int nxt = first_item();
                for (int k0 = 4; item_type(nxt) <= T_LOCAL; k0 = 0) {
                    const int type = item_type(nxt), m = item_row(nxt), c = item_col(nxt);
                    if (type == T_LOCAL) {
                        wait_inputs(nxt);
                        request();
#pragma unroll 1
                        for (uint32_t st = 0; st < 4; st++) {
                            mbar_wait(bars + B_GEMPTY + 8 * st, gph);
                            const uint32_t dst = sb + st * GST_BYTES, fb = bars + B_GFULL + 8 * st;
                            warp_expect_tx(fb, st == 0 ? 32768 + 512 : st == 3 ? 0 : 4 * LOC_PLANE);
                            if (st == 3) break;
                            if (st == 0) warp_bulk_load(dst + 4 * LOC_PLANE, &g_gate[m * 128], 512, fb);
#pragma unroll 1
                            for (int i = 0; i < 4; i++)
                                warp_tma_load(dst + i * LOC_PLANE, &prm.m[st ? M_SCR_LOC : M_SCR_LOQ], fb, i * 64, m * 64 - (st ? 8 : 0), G_B + 8 * st + c);
                        }
                        gph ^= 1;
                    } else {
                        const int nk = type == T_K || type == T_V ? 8 : 16;
                        const CUtensorMap* ma = &prm.m[nk == 8 ? M_C : M_X];
                        const CUtensorMap* mb = &prm.m[M_WQ + type];
#pragma unroll 1
                        for (int k = k0; k < nk; k++) {
                            if (k == nk - 3) request();
                            const uint32_t st = k & 3, dst = sb + st * GST_BYTES, fb = bars + B_GFULL + 8 * st;
                            mbar_wait(bars + B_GEMPTY + 8 * st, gph);
                            warp_expect_tx(fb, GST_BYTES);
                            warp_tma_load(dst, ma, fb, k * 64, m * 128, 0);
                            warp_tma_load_pair(dst + 16384 + prank * 16384, mb, fb, 0, k * 64, c * 4 + 2 * prank);
                            if (st == 3) gph ^= 1;
                        }
                    }
                    nxt = take_item();
                }
                uint32_t kv = 0, kvph = 1;
                uint32_t qc = 0;
                auto a_parity = [&](uint32_t b) { return b < 2 ? (((qc + 1 - b) >> 1) & 1) ^ 1 : kvph ^ (b - 2 < kv); };
                const CUtensorMap* tile_map = &prm.m[M_SCR_LD];
                asm volatile("" : "+l"(tile_map));
                {
                    bool need_g = true, more = true;
                    int pv_grp = -1, pv_row = 0;
                    bool pv_shared = false, peer_longer = false;
                    int m = 0, c = 0, asc = 0, nu = 0, uend = 0, ureq = -1, ufetch = 0;
#pragma unroll 1
                    for (int u = 0;; u++) {
                        if (u == ufetch) {
                            if (qc) nxt = take_item();
                            if (item_type(nxt) == T_ATTN) {
                                wait_inputs(nxt);
                                const uint32_t b = qc & 1, dst = sb + b * 32768, fb = bars + B_AFULL + 8 * b, row = item_row(nxt) * 128;
                                mbar_wait(bars + (qc == 0 ? B_GEMPTY : qc == 1 ? B_QFREE : B_AEMPTY + 8 * b), qc == 0 ? gph : qc == 1 ? 0 : a_parity(b));
                                warp_expect_tx(fb, 32768 + 512);
                                warp_tma_load(dst, tile_map, fb, 0, row, G_Q + item_col(nxt));
                                warp_tma_load(dst + 16384, tile_map, fb, 64, row, G_Q + item_col(nxt));
                                warp_bulk_load(bars + SM_GATE + b * 512, &g_gate[row], 512, fb);
                                qc++;
                            }
                        }
                        if (u == uend) {
                            if (!more) break;
                            more = item_type(nxt) == T_ATTN;
                            m = item_row(nxt); c = item_col(nxt); asc = item_asc(nxt);
                            nu = more ? 2 * m + 2 : 0;
                            uend = nu + ((more ? m < 2 : pv_grp >= 0) ? 3 : 0);
                            ureq = 2 * max(m - 2 - (asc & m), 0);
                            ufetch = !more ? -1 : m ? 2 * m : uend;
                            u = -1;
                            continue;
                        }
                        int grp = pv_grp, row = pv_row;
                        bool shared = pv_shared;
                        if (u >= nu) {
                            if (u == nu + 1) pv_grp = -1;
                            else if (peer_longer) { grp = -1; shared = false; }
                            else continue;
                        } else {
                            const int j = asc ? u >> 1 : m - (u >> 1);
                            if (u & 1) {
                                pv_grp = G_V + c; pv_row = j * 128; pv_shared = j != (m | 1);
                                peer_longer = asc & ~m & 1;
                                if (u == nu - 1 && (m & 1) && item_type(nxt) == T_END) mbar_arrive_cluster_n_if(lane == 0, bars0 + B_WANT, 2);
                                if (grp < 0) continue;
                            } else {
                                if (u == ureq) request();
                                grp = G_K + c; row = j * 128; shared = j != (m | 1);
                            }
                        }
                        uint32_t fb = bars + B_AFULL + 16 + 8 * kv, mine = sb + SM_KV + kv * 32768 + prank * 16384;
                        int c_mine = prank * 64;
                        asm volatile("" : "+r"(mine), "+r"(fb), "+r"(row), "+r"(grp), "+r"(c_mine));
                        mbar_wait(need_g ? bars + B_GEMPTY + 8 + 8 * kv : fb + B_AEMPTY - B_AFULL, need_g ? gph : kvph);
                        warp_expect_tx(fb, grp < 0 ? 0 : 32768);
                        if (shared) {
                            warp_tma_load_pair(mine, tile_map, fb, c_mine, row, grp);
                        } else if (grp >= 0) {
                            warp_tma_load(mine, tile_map, fb, c_mine, row, grp);
                            warp_tma_load(mine + 16384 - prank * 32768, tile_map, fb, 64 - c_mine, row, grp);
                        } else {
                            mbar_arrive_cluster_n_if(lane < 2, map_cta(fb, lane & 1) + B_AEMPTY - B_AFULL, 8);
                        }
                        if (kv == 2) need_g = false;
                        if (++kv == 4) { kv = 0; kvph ^= 1; }
                    }
                }
                if (!qc) request();
                const int it = take_item();
                int nk = 0;
                if (item_type(it) == T_OUT) {
                    const int m = item_row(it), c = item_col(it), half = c & 1;
                    nk = 80;
                    for (int k = 0; k < nk; k++) {
                        if (k == K_SPLIT) nk = 2 * TRIPLES + (take_item() & 127);
                        const int kn = k + 2 * TRIPLES - nk, first = kn >= 0 && !(kn & 1);
                        const int s = kn >= 0 ? WIDE + (3 * kn + 1) / 2 : half ? WIDE - 1 - k : k;
                        const uint32_t sa = prm.ostep[s], sa2 = prm.ostep[s + first], sw = prm.ostep[s - (kn >= 0 && !first ? prank : 0)];
                        const uint32_t need = 1u << (sa >> 1 & 31) | 1u << (sa2 >> 1 & 31);
                        for (unsigned n = 0; need & ~inputs_seen(sa >> 6, n);) {}
                        const uint32_t st = k & 3;
                        uint32_t dst = sb + st * GST_BYTES, fb = bars + B_GFULL + 8 * st;
                        uint32_t dstb = dst + 16384 + (first ? 0 : prank * 16384), skipb = first && (kn >> 1 & 1) != prank;
                        int a0 = (sa & 1) * 64, a1 = m * 128, a2 = (sa >> 1) + (sa < 64 ? G_CTX : G_LOC - 32);
                        int b1 = (sw & 63) * 64, b2 = (c >> 1) * 4 + 2 * (kn >= 0 ? half : half ^ prank);
                        const CUtensorMap* mb = &prm.m[sw >= 64 ? M_WOB : M_WO];
                        asm volatile("" : "+r"(dst), "+r"(fb), "+r"(dstb), "+r"(skipb), "+r"(a0), "+r"(a1), "+r"(a2), "+r"(b1), "+r"(b2), "+l"(mb));
                        if (k < 4) {
#pragma unroll 1
                            for (uint32_t i = 0, b = (3 * st) >> 1; i < 3; i++, b++) mbar_wait(bars + (i == 2 ? B_QFREE : B_AEMPTY + 8 * b), i == 2 ? 0 : a_parity(b));
                            mbar_arrive_cluster_if(lane == 0, bars_peer + B_XFREE + 8 * st);
                            mbar_wait(bars + B_XFREE + 8 * st, 0);
                        }
                        mbar_wait(bars + B_GEMPTY + 8 * st, gph);
                        warp_expect_tx(fb, GST_BYTES);
                        warp_tma_load(dst, tile_map, fb, a0, a1, a2);
                        if (!skipb) warp_tma_load_pair(dstb, mb, fb, 0, b1, b2);
                        if (first) warp_tma_load(dst + 32768, tile_map, fb, (sa2 & 1) * 64, a1, G_CTX + (sa2 >> 1));
                        if (k < K_SPLIT && lane == 0 && !prank)
                            asm volatile("st.relaxed.gpu.global.u32 [%0], %1;" :: "l"(&g_sync.step[0][0] + m * 4 + c), "r"(k) : "memory");
                        if (k == K_MEET) request();
                        if ((uint32_t)(k - K_FETCH) < (3 * TRIPLES + 1) / 2) {
                            const uint32_t g = prm.ostep[79 - 2 * (k - K_FETCH)] >> 1;
                            warp_prefetch((const char*)g_scr + (uint32_t)((G_CTX + g) * (SEQ * 256) + m * 32768 + c * 4096), 4096);
                            warp_prefetch(prm.wo + (uint32_t)(g * 262144 + (m * 8 + c) * 2048), 2048);
                        }
                        if (st == 3) gph ^= 1;
                    }
                    for (unsigned n = 0; ~inputs_seen(0, n) || inputs_seen(1, n) != 255;) {}
                }
#pragma unroll 1
                for (uint32_t st = 0; st < 4; st++) { mbar_wait(bars + B_GEMPTY + 8 * st, gph ^ (st < (nk & 3))); mbar_wait(bars + B_AEMPTY + 16 + 8 * st, a_parity(2 + st)); }
                unsigned left = 0;
                if (lane == 0) asm volatile("atom.relaxed.gpu.global.add.u32 %0, [%1], 1;" : "=r"(left) : "l"(&g_sync.done) : "memory");
                if (__shfl_sync(0xffffffffu, left, 0) == NCTA - 1)
#pragma unroll 1
                    for (uint32_t i = lane * 8; i < sizeof(Sync); i += 256) *(unsigned long long*)((char*)&g_sync + i) = 0;
            }
        } else if (warp <= 2) {
            if (blockIdx.x < SEQ / 16) {
                const uint32_t r0 = 16 * blockIdx.x + 8 * (warp - 1), gbuf = bars + SM_GATE + 4 * (r0 & 15);
                float z[4];
#pragma unroll 1
                for (uint32_t i = 0; i < 8; i++) {
                    const uint32_t off = (i & 3) * 512 + lane * 16;
                    const uint4* xp = (const uint4*)((const char*)prm.x + ((r0 + (i & 4)) * 2048 + off));
                    const uint4 wv = __ldg((const uint4*)((const char*)prm.gate_w + off));
                    uint4 xv[4];
#pragma unroll
                    for (int r = 0; r < 4; r++) { xv[r] = __ldg(xp + r * 128); if (!(i & 3)) z[r] = 0.f; }
                    const uint32_t ws[4] = {wv.x, wv.y, wv.z, wv.w};
#pragma unroll
                    for (int e = 0; e < 4; e++)
#pragma unroll
                        for (int r = 0; r < 4; r++) {
                            const uint32_t xs = e == 0 ? xv[r].x : e == 1 ? xv[r].y : e == 2 ? xv[r].z : xv[r].w;
                            z[r] = fmaf(__uint_as_float(xs << 16), __uint_as_float(ws[e] << 16), z[r]);
                            z[r] = fmaf(__uint_as_float(xs & 0xffff0000u), __uint_as_float(ws[e] & 0xffff0000u), z[r]);
                        }
                    if ((i & 3) == 3) {
#pragma unroll
                        for (int o = 16; o > 0; o >>= 1)
#pragma unroll
                            for (int r = 0; r < 4; r++) z[r] += __shfl_xor_sync(0xffffffffu, z[r], o);
                        const float zr = lane & 2 ? (lane & 1 ? z[3] : z[2]) : (lane & 1 ? z[1] : z[0]);
                        asm volatile("st.shared.f32 [%0], %1;" :: "r"(gbuf + 4 * ((i & 4) + (lane & 3))), "f"(1.f / (1.f + __expf(-zr))) : "memory");
                    }
                }
                fence_proxy_async_smem();
                __syncwarp();
                warp_bulk_store((char*)g_gate + 4 * r0, gbuf, 32);
                bulk_commit();
                bulk_wait<0>();
                __syncwarp();
                if (lane == 0) red_add(&g_sync.count[3], 1);
            }
            __syncwarp();
            {
                const int w = warp - 1;
                uint32_t sph = 0, nann = 0;
                int unsent = 0, nunsent = 0;
                bool urgent = false;
                auto announce = [&]() {
                    if (!urgent) return;
                    bulk_wait<0>();
                    __syncwarp();
                    const uint32_t hb = bars + B_HALF + 8 * (nann & 3);
                    if (w == 0) {
                        mbar_arrive_if(lane == 0, hb);
                    } else {
                        mbar_wait(hb, (nann >> 2) & 1);
                        const uint32_t type = item_type(unsent), m = item_row(unsent), c = item_col(unsent);
                        const uint32_t word = type < T_B ? c >> 3 : type == T_B ? 2 : offsetof(Sync, ctx) / 8 + m;
                        const uint32_t bit = type < T_B ? 8 * (c & 7) : type == T_B ? 4 * m : type == T_LOCAL ? 32 + c : c;
                        if (lane < nunsent) red_add((unsigned long long*)((char*)&g_sync + 8 * word), 1ull << bit);
                        __syncwarp();
                    }
                    nann++;
                    nunsent = 0; urgent = false;
                };
                int held = first_item(), it;
                bool qfree = false;
                do {
                    if (!__all_sync(0xffffffffu, mbar_test(bars + B_IFULL + 8 * (qn % QDEPTH), (qn / QDEPTH) & 1))) announce();
                    it = __shfl_sync(0xffffffffu, next_item(lane == 0), 0);
                    const int itype = item_type(it);
                    const bool keep_held = itype == T_LOCAL && (item_type(held) != T_B || (it & ITEM_READY));
                    if (itype >= T_ATTN && held < 0) {
                        urgent = nunsent;
                        mbar_arrive_if(lane == 0 && !qfree, bars + B_QFREE);
                        qfree = true;
                    }
#pragma unroll 1
                    for (int pass = held < 0 || keep_held; pass < 2; pass++) {
                        if (pass && (itype < T_OUT || itype == T_END)) break;
                        const int cur = pass ? it : held, type = item_type(cur), m = item_row(cur), c = item_col(cur);
                        const bool local = type == T_LOCAL;
                        const int grp = pass ? (local ? G_LOC : G_CTX) + c : type * 32 + 2 * c;
#pragma unroll 1
                        for (int i = 0; i < 4 - 2 * pass; i++) {
                            const int b = i & 1;
                            const bool alt = i >= 2 && itype == T_ATTN;
                            const uint32_t full = bars + (alt ? B_ALT + 8 * w : B_SFULL + 16 * w + 8 * b), par = alt ? 0 : sph;
                            if (i == 3 - 2 * pass || !__all_sync(0xffffffffu, mbar_test(full, par))) announce();
                            mbar_wait(full, par);
                            fence_proxy_async_smem();
                            warp_tma_store(&prm.m[local ? M_SCR_LOQ : M_SCR_ST], sb + (alt ? 32768 : SM_STAGING) + w * 16384 + b * 8192,
                                         local ? b * 128 + w * 64 : b * 64, local ? m * 64 : m * 128 + w * 64, grp + (i >> 1));
                            bulk_commit();
                            bulk_wait_read<0>();
                            __syncwarp();
                            mbar_arrive_if(lane == 0 && !alt, bars + B_SEMPTY + 16 * w + 8 * b);
                            sph ^= b & !alt;
                        }
                        mbar_arrive_if(lane == 0 && !qfree && itype >= T_ATTN, bars + B_QFREE);
                        qfree |= itype >= T_ATTN;
                        if (lane == nunsent) unsent = cur;
                        nunsent++;
                        urgent = nunsent == 32 || !local;
                    }
                    if (!keep_held) held = itype < T_OUT ? it : -1;
                } while (item_type(it) != T_END);
                announce();
                if (item_type(next_item(lane == 0)) == T_OUT) next_item(lane == 0);
            }
        } else {
            if (elect_one()) {
                uint32_t ordy = 0;
                unsigned long long cnt_lo = 0, cnt_hi = 0;
                int late = 0;
                auto refresh = [&]() {
                    if (!late && cnt_lo == 0xccccccccccccccccull && cnt_hi == SEQ / 8) late = 1;
                    asm volatile("ld.acquire.gpu.global.v2.u64 {%0, %1}, [%2];" : "=l"(cnt_lo), "=l"(cnt_hi) : "l"(late ? &g_sync.count[0] : &g_sync.count[2]) : "memory");
                };
                auto inputs_ready = [&](int it) -> bool {
                    const int m = item_row(it), c = item_col(it);
                    if (item_type(it) == T_ATTN) return late && ((c < 16 ? cnt_lo : cnt_hi) >> (4 * (c & 14)) & 255) == 48;
                    return late || (cnt_hi == SEQ / 8 && (cnt_lo >> (4 * m) & 15) == 12 && (cnt_lo >> (4 * max(m - 1, 0)) & 15) == 12);
                };
                auto publish = [&](int it, int step) {
                    const uint32_t slot = qn % QDEPTH;
                    mbar_wait(bars + B_IEMPTY + 8 * slot, ((qn / QDEPTH) & 1) ^ 1);
                    for (uint32_t r = 0; r < 2; r++) {
                        const uint32_t rb = map_cta(bars, r);
                        asm volatile("mbarrier.arrive.expect_tx.shared::cluster.b64 _, [%0], 4;" :: "r"(rb + B_IFULL + 8 * slot) : "memory");
                        asm volatile("st.async.shared::cluster.mbarrier::complete_tx::bytes.u32 [%0], %1, [%2];"
                                     :: "r"(rb + SM_QUEUE + 4 * slot), "r"(it + r * step), "r"(rb + B_IFULL + 8 * slot) : "memory");
                    }
                    qn++;
                };
                int asc = 1;
                int it;
                do {
                    if (rank == 0) {
                        mbar_wait(bars + B_WANT, qn & 1);
                        unsigned i;
                        asm volatile("atom.relaxed.gpu.global.add.u32 %0, [%1], 1;" : "=r"(i) : "l"(&g_sync.next) : "memory");
                        if (cnt_lo != 0x3030303030303030ull || cnt_hi != cnt_lo) refresh();
                        i += NPAIR;
                        const int pit = i < NITEMS ? prm.items[i] : T_END << 13, type = item_type(pit);
                        int step = type == T_LOCAL ? 16 : 1;
                        it = pit + (pit & (step == 1 ? 15 : 0x1f0));
                        if (type == T_ATTN) {
                            if (!asc) { it += 1; step = -1; }
                            it |= asc << 9;
                        }
                        asc = type != T_ATTN || item_row(pit) == 0 || !asc;
                        if (inputs_ready(it)) it |= ITEM_READY;
                        publish(it, step);
                    } else {
                        it = next_item(true);
                    }
                    if ((item_type(it) == T_ATTN || item_type(it) == T_LOCAL) && !(it & ITEM_READY)) {
                        unsigned n = 0;
                        while (!inputs_ready(it)) { refresh(); spin_guard(n); }
                        asm volatile("st.release.cta.shared.u32 [%0], %1;" :: "r"(bars + SM_ORDY + 4), "r"(ordy += 256) : "memory");
                    }
                } while (item_type(it) != T_END);
                if (rank == 0) {
                    mbar_wait(bars + B_WANT, qn & 1);
                    const unsigned i = atomicAdd(&g_sync.next_out, 1u), t = i < 32 ? 31 - i : i - 32;
                    it = i < 64 ? T_OUT << 13 | ((t & 3) * 2 + (i >> 5)) << 4 | (t >> 2) * 2 : T_END << 13;
                    publish(it, 1);
                } else {
                    it = next_item(true);
                }
                if (item_type(it) == T_OUT) {
                    const uint32_t m = item_row(it), half = item_col(it) & 1, tile = m * 2 + (item_col(it) >> 1);
                    unsigned* split = (unsigned*)((char*)g_sync.split + 4 * tile);
                    unsigned long long rdy = 0;
                    int state = rank ? 2 : 0;
                    for (unsigned n = 0; rdy != 0xffffffffffull || state < 2; spin_guard(n)) {
                        if (rdy != 0xffffffffffull) {
                            rdy = ld_acquire((const unsigned long long*)((char*)g_sync.ctx + 8 * m));
                            asm volatile("st.release.cta.shared.u64 [%0], %1;" :: "r"(bars + SM_ORDY), "l"(rdy) : "memory");
                        }
                        unsigned steps = 0;
                        if (state == 1) {
                            steps = ld_acquire(split);
                        } else if (state == 0 && mbar_test(bars + B_WANT, qn & 1)) {
                            state = 1;
                            unsigned seen;
                            asm volatile("atom.acq_rel.gpu.global.exch.b32 %0, [%1], 1;" : "=r"(seen) : "l"(split) : "memory");
                            if (seen) {
                                const unsigned long long v = ld_acquire((const unsigned long long*)((char*)g_sync.step + 8 * tile));
                                const int d = (int)(v >> 32) - (int)v;
                                steps = (WIDE + min(max(half ? d : -d, K_MEET - K_SPLIT), K_SPLIT - K_MEET)) >> 1;
                                atomicExch(split, WIDE - steps);
                            }
                        }
                        if (steps > 1) { publish(T_END << 13 | steps, 0); state = 2; }
                    }
                    if (rank) next_item(true);
                }
                #pragma unroll 1
                for (uint32_t n = qn; n < qn + QDEPTH && rank == 0; n++) mbar_wait(bars + B_IEMPTY + 8 * (n % QDEPTH), ((n / QDEPTH) & 1) ^ 1);
            }
        }
    } else {
        reg_inc<232>();
        const int wg = (warp >> 2) - 1, wq = warp & 3;
        uint32_t gph = 0;
        uint32_t kvn = 0;
        const uint32_t dA = make_desc(sb + wg * 8192, 16);
        uint32_t ti = 0;
        uint32_t sph = 1;
        const uint32_t stg = sb + SM_STAGING + wg * 16384;
        const uint32_t stg_lane = stg + (wq * 16 + (lane & 15)) * 128 + (((lane >> 4) ^ (lane & 7)) << 4);
        auto write_blocks = [&](auto n, uint32_t off, const uint32_t* v) {
            uint32_t a = stg_lane;
            asm volatile("" : "+r"(a));
            a += off;
#pragma unroll
            for (int j = 0; j < decltype(n)::value; j++)
                stmatrix_x4((a ^ (32 * (j & 3))) + (j >> 2) * 8192, v[4 * j], v[4 * j + 1], v[4 * j + 2], v[4 * j + 3]);
        };
        auto release = [&](uint32_t bar) { mbar_arrive_if(lane == 0, bars + bar); };
        const uint32_t bars_lane = map_cta(bars, lane & 1);
        auto release_stage = [&](uint32_t st) { mbar_arrive_cluster_if(lane < 2, bars_lane + B_GEMPTY + 8 * st); };
        auto take_item = [&]() -> int {
            return __shfl_sync(0xffffffffu, next_item(lane == 0, false), 0);
        };
        auto stage_acquire = [&](int b) { mbar_spin(bars + B_SEMPTY + 16 * wg + 8 * b, sph); };
        auto stage_publish = [&](int b) {
            __syncwarp();
            release(B_SFULL + 16 * wg + 8 * b);
        };
        auto stage_chunk = [&](int b, const uint32_t* v) {
            stage_acquire(b);
            write_blocks(std::integral_constant<int, 4>(), b * 8192, v);
            stage_publish(b);
            if (b) sph ^= 1;
        };
        auto publish_pair = [&]() {
            __syncwarp();
            mbar_arrive_if(lane < 2, bars + B_SFULL + 16 * wg + 8 * lane);
            sph ^= 1;
        };
        auto gemm_step = [&](float (&acc)[128], uint32_t dB, int& k) {
            const uint32_t st = k & 3;
            wgmma_wait<0>();
            release_stage((k - 1) & 3);
            mbar_spin(bars + B_GFULL + 8 * st, gph);
            const uint64_t da = full_desc(dA + st * (GST_BYTES >> 4)), db = full_desc(dB + st * (GST_BYTES >> 4));
            wgmma_fence();
#pragma unroll
            for (int kk = 0; kk < 4; kk++) wgmma_ss_n256_tb(acc, da + 2 * kk, db + 128 * kk, 1);
            wgmma_commit();
            gph ^= st == 3;
            k++;
        };
        if (wg == 1) bar_arrive(1, 256);
        int it = first_item();
        while (true) {
            if (item_type(it) <= T_LOCAL) {
                float acc[128];
                uint32_t pk[64];
                bool pending = false;
                bool held_b = false;
                zero_regs(pk);
                const uint32_t dB = make_desc(sb + 16384, 8192);
                do {
                    const int type = item_type(it);
                    if (type == T_LOCAL) {
                        int ln = lane;
                        asm volatile("" : "+r"(ln));
                        const int g = ln >> 2, t = ln & 3, par = wq & 1;
                        const uint32_t hc = (wq >> 1) * 4, pl = sb + (par * 2 + wg) * LOC_PLANE;
                        const uint32_t a16 = (ln & 15) * 128 + (((hc + (ln >> 4)) ^ (ln & 7)) << 4), a8 = (ln & 7) * 128 + (((hc + (ln >> 3)) ^ (ln & 7)) << 4);
                        const bool first0 = 2 * t > g, first1 = 2 * t + 1 > g;
                        const uint32_t fmask = (first0 ? 0xffffu : 0u) | (first1 ? 0xffff0000u : 0u);
                        const bool edge = item_row(it) == 0;
                        uint32_t q[4][2][4], kf[9][4], vf[9][4];
                        float w[8];
                        mbar_spin(bars + B_GFULL, gph);
#pragma unroll
                        for (int u = 0; u < 4; u++) { ldsm_x4(q[u][0], pl + u * 2048 + a16); ldsm_x4(q[u][1], pl + u * 2048 + (a16 ^ 32)); }
#pragma unroll
                        for (int j = 0; j < 8; j++) w[j] = lds_f32(sb + 4 * LOC_PLANE + 4 * (2 * g + par) + 64 * j);
                        __syncwarp();
                        release_stage(0);
                        mbar_spin(bars + B_GFULL + 8, gph);
#pragma unroll
                        for (int n = 0; n < 9; n++) ldsm_x4(kf[n], pl + GST_BYTES + n * 1024 + a8);
                        __syncwarp();
                        release_stage(1);
                        float s[8][2];
#pragma unroll
                        for (int u = 0; u < 4; u++) {
                            float d[3][4];
#pragma unroll
                            for (int nt = 0; nt < 3; nt++) {
                                mma_k16_init(d[nt], q[u][0], kf[2 * u + nt][0], kf[2 * u + nt][1]);
                                mma_k16(d[nt], q[u][1], kf[2 * u + nt][2], kf[2 * u + nt][3]);
                            }
                            if (u == 0 && edge) { d[0][0] = -INFINITY; d[0][1] = -INFINITY; }
                            s[2 * u][0] = first0 ? d[0][0] : d[1][0]; s[2 * u][1] = first1 ? d[0][1] : d[1][1];
                            s[2 * u + 1][0] = first0 ? d[1][2] : d[2][2]; s[2 * u + 1][1] = first1 ? d[1][3] : d[2][3];
                        }
                        mbar_spin(bars + B_GFULL + 16, gph);
#pragma unroll
                        for (int u = 0; u < 4; u++) { ldsm_x4_t(vf[2 * u], pl + 2 * GST_BYTES + u * 2048 + a16); ldsm_x4_t(vf[2 * u + 1], pl + 2 * GST_BYTES + u * 2048 + (a16 ^ 32)); }
                        ldsm_x4_t(vf[8], pl + 2 * GST_BYTES + 8192 + a8);
                        __syncwarp();
                        release_stage(2);
                        float x[8];
#pragma unroll
                        for (int j = 0; j < 8; j++) x[j] = fmaxf(s[j][0], s[j][1]);
#pragma unroll
                        for (int o = 1; o < 4; o *= 2)
#pragma unroll
                            for (int j = 0; j < 8; j++) x[j] = fmaxf(x[j], __shfl_xor_sync(0xffffffffu, x[j], o));
#pragma unroll
                        for (int j = 0; j < 8; j++) {
                            const float n = x[j] * -LOC_SCALE;
                            s[j][0] = ex2(fmaf(s[j][0], LOC_SCALE, n)); s[j][1] = ex2(fmaf(s[j][1], LOC_SCALE, n));
                            x[j] = s[j][0] + s[j][1];
                        }
#pragma unroll
                        for (int o = 1; o < 4; o *= 2)
#pragma unroll
                            for (int j = 0; j < 8; j++) x[j] += __shfl_xor_sync(0xffffffffu, x[j], o);
                        mbar_spin(bars + B_GFULL + 24, gph);
                        release_stage(3);
                        it = take_item();
                        uint32_t ob[4][8];
#pragma unroll
                        for (int u = 0; u < 4; u++) {
                            const float r0 = rcp(x[2 * u]), r1 = rcp(x[2 * u + 1]), f0 = fmaf(-w[2 * u], r0, r0), f1 = fmaf(-w[2 * u + 1], r1, r1);
                            const uint32_t p0 = pack_bf16(s[2 * u][0] * f0, s[2 * u][1] * f0), p1 = pack_bf16(s[2 * u + 1][0] * f1, s[2 * u + 1][1] * f1);
                            const uint32_t pa[4] = {p0 & fmask, 0, p0 & ~fmask, p1 & fmask};
#pragma unroll
                            for (int c = 0; c < 4; c++) {
                                float ol[4];
                                mma_k16_init(ol, pa, vf[2 * u + (c >> 1)][2 * (c & 1)], vf[2 * u + (c >> 1)][2 * (c & 1) + 1]);
                                mma_k8(ol, 0, p1 & ~fmask, u < 3 ? vf[2 * u + 2 + (c >> 1)][2 * (c & 1)] : vf[8][c]);
                                ob[u][2 * c] = pack_bf16(ol[0], ol[1]);
                                ob[u][2 * c + 1] = pack_bf16(ol[2], ol[3]);
                            }
                        }
                        stage_acquire(0); stage_acquire(1);
#pragma unroll
                        for (int u = 0; u < 4; u++) {
                            stmatrix_x4(stg + par * 8192 + u * 2048 + a16, ob[u][0], ob[u][1], ob[u][2], ob[u][3]);
                            stmatrix_x4(stg + par * 8192 + u * 2048 + (a16 ^ 32), ob[u][4], ob[u][5], ob[u][6], ob[u][7]);
                        }
                        publish_pair();
                        bar_sync(4, 256);
                        gph ^= 1;
                        continue;
                    }
                    mbar_spin(bars + B_GFULL, gph);
                    bool more;
                    do {
                        wgmma_fence();
                        wgmma_ss_n256_tb_init(acc, full_desc(dA), full_desc(dB));
#pragma unroll
                        for (int kk = 1; kk < 4; kk++) wgmma_ss_n256_tb(acc, full_desc(dA) + 2 * kk, full_desc(dB) + 128 * kk, 1);
                        wgmma_commit();
                        const int nk = item_type(it) == T_K || item_type(it) == T_V ? 8 : 16;
                        int k = 1;
                        do {
                            if (pending) {
                                const int kf = k - 1 - wg;
                                if (kf == 0) stage_chunk(0, pk);
                                else if (kf == 1) stage_chunk(1, pk + 16);
                                else if (kf == 3) stage_chunk(0, pk + 32);
                                else if (kf == 4) stage_chunk(1, pk + 48);
                            }
                            gemm_step(acc, dB, k);
                        } while (k < nk);
                        held_b = item_type(it) == T_B;
                        const bool is_q = item_type(it) == T_Q;
                        it = take_item();
                        more = item_type(it) < T_LOCAL;
                        if (more) mbar_spin(bars + B_GFULL, gph);
                        wgmma_wait<0>();
                        fence_regs(acc);
                        release_stage(3);
                        if (is_q) {
#pragma unroll
                            for (int j = 0; j < 128; j++) acc[j] *= SM_SCALE;
                        }
#pragma unroll
                        for (int j = 0; j < 64; j++) pk[j] = pack_bf16(acc[2 * j], acc[2 * j + 1]);
                        pending = true;
                    } while (more);
                } while (item_type(it) < T_LOCAL || (item_type(it) == T_LOCAL && (!held_b || (it & ITEM_READY))));
                if (pending) {
                    stage_acquire(0); stage_acquire(1);
                    write_blocks(std::integral_constant<int, 8>(), 0, pk);
                    const bool borrow = item_type(it) == T_ATTN;
                    if (borrow) {
                        mbar_spin(bars + B_GEMPTY, gph ^ 1); mbar_spin(bars + B_GEMPTY + 8, gph ^ 1);
                    } else {
                        publish_pair();
                        stage_acquire(0); stage_acquire(1);
                    }
                    write_blocks(std::integral_constant<int, 8>(), borrow ? 32768 - SM_STAGING : 0, pk + 32);
                    publish_pair();
                    mbar_arrive_if(lane == 0 && borrow, bars + B_ALT + 8 * wg);
                }
                if (item_type(it) == T_END) { it = take_item(); break; }
            } else {
                float o[64], s[64];
                uint32_t pa[32], pb[32];
                zero_regs(o); zero_regs(s); zero_regs(pa);
                float n0 = 0.f, n1 = 0.f;
                int shifted = 0;
                float l0 = 1.f, l1 = 1.f, f0 = 0.f, f1 = 0.f, g0 = 0.f, g1 = 0.f;
                uint32_t has_pv = 0;
                int first = 0;
                int pending = 0;
                const uint32_t dK = make_desc(sb + SM_KV, 16), dV = make_desc(sb + SM_KV, 16384);
                const uint32_t lane_off = bars_lane - bars + B_AEMPTY - B_AFULL;
                int cur = 0;
                uint32_t qoff = 0;
                const int row = wg * 64 + wq * 16 + (lane >> 2);
                const float thr = (row & 63) - (lane & 3) * 2;
                int peek = 0;
                auto kv_wait = [&](uint32_t n) { mbar_spin(bars + B_AFULL + 16 + 8 * (n & 3), (n >> 2) & 1); };
                auto kv_release = [&](uint32_t n) { mbar_arrive_cluster_if(lane < 2, bars_lane + B_AEMPTY + 16 + 8 * (n & 3)); };
                struct Slot { uint32_t bar, par, off; } slot[4];
                auto align = [&]() {
#pragma unroll
                    for (uint32_t i = 0; i < 4; i++) {
                        const uint32_t n = kvn + (i == 1 ? has_pv : i);
                        slot[i].bar = bars + B_AFULL + 16 + 8 * (n & 3); slot[i].par = (n >> 2) & 1; slot[i].off = (n & 3) * 2048;
                    }
                };
                align();
                auto scale_o = [&]() {
#pragma unroll
                    for (int j = 0; j < 16; j++) { o[4 * j] *= f0; o[4 * j + 1] *= f0; o[4 * j + 2] *= f1; o[4 * j + 3] *= f1; }
                };
                auto pack_o = [&](uint32_t (&v)[32]) {
#pragma unroll
                    for (int j = 0; j < 32; j++) v[j] = pack_bf16(o[2 * j], o[2 * j + 1]);
                };
                auto scales = [&]() { f0 = g0 * rcp(quad_sum(l0)); f1 = g1 * rcp(quad_sum(l1)); };
                auto step = [&](auto even, uint32_t (&pin)[32], uint32_t (&pout)[32], bool fresh, bool diag, bool last) {
                    constexpr bool EVEN = decltype(even)::value;
                    Slot& sk = slot[EVEN ? 0 : 2];
                    Slot& sv = slot[EVEN ? 1 : 3];
                    kvn += EVEN ? 1 + has_pv : 2;
                    mbar_spin(sk.bar, sk.par);
                    bar_sync(1 + wg, 256);
                    qk_gemm(s, dA + qoff, dK + sk.off);
                    if (EVEN && fresh) {
                        scales();
                        g0 = lds_f32(bars + SM_GATE + (ti & 1) * 512 + 4 * row); g1 = lds_f32(bars + SM_GATE + (ti & 1) * 512 + 4 * row + 32);
                        ti++;
                        n0 = 0.f; n1 = 0.f; l0 = 0.f; l1 = 0.f;
                        shifted = 0;
                        if (has_pv) { stage_acquire(0); stage_acquire(1); }
                    }
                    if (!EVEN && pending) {
                        pack_o(pout);
                        write_blocks(std::integral_constant<int, 8>(), 0, pout);
                        publish_pair();
                    }
                    if (last)
                        asm volatile("{\n.reg .pred P, Q;\n"
                                     "mbarrier.test_wait.parity.shared::cta.b64 Q, [%1], %2;\n"
                                     "mbarrier.test_wait.parity.shared::cta.b64 P, [%3], %4;\n"
                                     "ld.shared.u32 %0, [%5];\n"
                                     "@!Q or.b32 %0, %0, 0x10000;\n"
                                     "@!P mov.u32 %0, -1;\n}\n"
                                     : "=r"(peek) : "r"(bars + B_AFULL + 8 * (ti & 1)), "r"((ti >> 1) & 1), "r"(bars + B_IFULL + 8 * (qn % QDEPTH)),
                                       "r"((qn / QDEPTH) & 1), "r"(bars + SM_QUEUE + 4 * (qn % QDEPTH)) : "memory");
                    mbar_spin(sv.bar, sv.par);
                    pv_gemm(o, pin, dV + sv.off, EVEN || !first);
                    bar_arrive(2 - wg, 256);
                    sk.par ^= 1; sv.par ^= 1;
                    wgmma_wait<1>();
                    fence_regs(s);
                    mbar_arrive_cluster_if(lane < 2 && (!EVEN || has_pv), sk.bar + lane_off);
                    mbar_arrive_if(lane == 0 && last, bars + B_AEMPTY + 8 * ((ti - 1) & 1));
                    float r0, r1, x0 = n0, x1 = n1;
#pragma unroll 1
                    for (int mask = diag, redone = 0;; mask = 0, redone = 1) {
                        if (mask | shifted) {
                            if (mask) causal_mask(s, thr, wg);
                            if (shifted) shift_rows(s, x0, x1);
                        }
                        exp_pack(pout, s, r0, r1);
                        if (!__any_sync(0xffffffffu, fmaxf(r0, r1) >= SUM_LIMIT || (EVEN && fresh && !(lane & 3) && !(fminf(s[0], s[2]) >= -REF_RANGE))) || redone) break;
                        row_max(s, x0, x1);
                        if (!(EVEN && fresh)) { x0 = fmaxf(x0, 0.f); x1 = fmaxf(x1, 0.f); }
                        float a0 = ex2(-x0), a1 = ex2(-x1);
                        n0 += x0; n1 += x1;
                        shifted = 1;
                        if (EVEN && fresh) { a0 = 1.f; a1 = 1.f; }
                        l0 *= a0; l1 *= a1;
                        wgmma_wait<0>();
                        fence_regs(o);
#pragma unroll
                        for (int q = 0; q < 16; q++) { o[4 * q] *= a0; o[4 * q + 1] *= a0; o[4 * q + 2] *= a1; o[4 * q + 3] *= a1; }
                    }
                    l0 += r0; l1 += r1;
                    wgmma_wait<0>();
                    fence_regs(o);
                    fence_regs(pin);
                    mbar_arrive_cluster_if(lane < 2, sv.bar + lane_off);
                };
                auto copy_p = [&]() {
#pragma unroll
                    for (int j = 0; j < 32; j++) pa[j] = __float_as_uint(__uint_as_float(pb[j]) + __uint_as_float(prm.zero));
                };
                int rem = 0;
                mbar_spin(bars + B_AFULL + 8 * (ti & 1), (ti >> 1) & 1);
                while (true) {
                    const bool fresh = rem == 0;
                    if (fresh) {
                        if (has_pv) {
                            const int seen = __shfl_sync(0xffffffffu, peek, 0);
                            if (seen >= 0) {
                                mbar_arrive_cluster_if(lane == 0, bars0 + B_IEMPTY + 8 * (qn % QDEPTH));
                                qn++;
                                it = seen & 0xffff;
                            } else {
                                it = take_item();
                            }
                            if (item_row(cur) < 2 || item_type(it) != T_ATTN) break;
                            if (seen & 0x10000) mbar_spin(bars + B_AFULL + 8 * (ti & 1), (ti >> 1) & 1);
                        }
                        cur = it;
                        qoff = (ti & 1) * 2048;
                    }
                    const bool last = fresh ? item_row(cur) == 0 : rem == 1;
                    step(std::true_type(), pa, pb, fresh, item_asc(cur) ? last : fresh, last);
                    first = fresh;
                    if (fresh) {
                        pending = has_pv; has_pv = 1;
                        if (!pending) { kvn -= 2; align(); kvn += 2; slot[0].par ^= 1; slot[1].par ^= 1; }
                        else scale_o();
                        rem = item_row(cur);
                        if (rem == 0) {
                            copy_p();
                            continue;
                        }
                    } else if (--rem == 0) {
                        copy_p();
                        const Slot t0 = slot[0], t1 = slot[1];
                        slot[0] = slot[2]; slot[1] = slot[3]; slot[2] = t0; slot[3] = t1;
                        continue;
                    }
                    step(std::false_type(), pb, pa, false, item_asc(cur) && rem == 1, rem == 1);
                    pending = 0; first = 0;
                    rem--;
                }
                const uint32_t skip = item_asc(cur) & ~item_row(cur) & 1;
                kvn += skip;
                const bool end = item_type(it) == T_END;
#pragma unroll 1
                for (int pass = pending ? 0 : 1; pass < 2; pass++) {
                    if (pass) {
                        kv_wait(kvn);
                        pv_gemm(o, pa, dV + (kvn & 3) * 2048, !first);
                        scales();
                        stage_acquire(0); stage_acquire(1);
                        if (end) it = take_item();
                        wgmma_wait<0>();
                        fence_regs(o);
                        kv_release(kvn);
                        kvn += 1 + skip;
                        scale_o();
                    }
                    pack_o(pb);
                    write_blocks(std::integral_constant<int, 8>(), 0, pb);
                    publish_pair();
                }
                if (end) break;
            }
        }
        if (item_type(it) == T_OUT) {
            float acc[128];
            const uint32_t dB = make_desc(sb + 16384, 8192);
            mbar_spin(bars + B_GFULL, gph);
            wgmma_fence();
            wgmma_ss_n256_tb_init(acc, full_desc(dA), full_desc(dB));
#pragma unroll
            for (int kk = 1; kk < 4; kk++) wgmma_ss_n256_tb(acc, full_desc(dA) + 2 * kk, full_desc(dB) + 128 * kk, 1);
            wgmma_commit();
            uint32_t ln;
            asm volatile("mov.u32 %0, %%laneid;" : "=r"(ln));
            const uint32_t slot = (it & 127) * 32768 + (wg * 128 + wq * 32 + ln) * 16;
            char* const mine = (char*)g_part + slot;
            int k = 1, nk = 80;
            do {
                if (k == K_MEET - 5) {
#pragma unroll
                    for (int j = 0; j < 8; j++) st_b128(mine + j * 4096, 0, 0, 0, 0);
                    __syncwarp();
                }
                if (k == K_SPLIT) nk = take_item() & 127;
                gemm_step(acc, dB, k);
            } while (k < nk);
            float lo[64];
            uint32_t pk[32];
            char* const other = (char*)g_part + (slot ^ (16 * 32768));
            auto fetch_other = [&]() {
#pragma unroll
                for (int j = 0; j < 8; j++) ld_b128(other + j * 4096, pk[4 * j], pk[4 * j + 1], pk[4 * j + 2], pk[4 * j + 3]);
            };
            auto triple = [&](auto first) {
                const uint32_t s0 = k & 3, s1 = (k + 1) & 3, o0 = s0 * (GST_BYTES >> 4), o1 = s1 * (GST_BYTES >> 4);
                wgmma_wait<0>();
                mbar_arrive_cluster_if(ln < (decltype(first)::value ? 2 : 4), bars_lane + B_GEMPTY + 8 * ((k - 1 - (ln >> 1)) & 3));
                mbar_spin(bars + B_GFULL + 8 * s0, gph);
                gph ^= s0 == 3;
                wgmma_fence();
#pragma unroll
                for (int kk = 0; kk < 4; kk++) {
                    if (decltype(first)::value && kk == 0) wgmma_ss_n128_tb_init(lo, full_desc(dA + o0), full_desc(dB + o0));
                    else wgmma_ss_n128_tb(lo, full_desc(dA + o0) + 2 * kk, full_desc(dB + o0) + 128 * kk, 1);
                }
                mbar_spin(bars + B_GFULL + 8 * s1, gph);
                gph ^= s1 == 3;
                wgmma_fence();
#pragma unroll
                for (int kk = 0; kk < 4; kk++) wgmma_ss_n128_tb(lo, full_desc(dA + o0 + 2048) + 2 * kk, full_desc(dB + o1 + 1024) + 128 * kk, 1);
#pragma unroll
                for (int kk = 0; kk < 4; kk++) wgmma_ss_n128_tb(lo, full_desc(dA + o1) + 2 * kk, full_desc(dB + o1) + 128 * kk, 1);
                wgmma_commit();
                k += 2;
            };
            triple(std::true_type());
            fence_regs(acc);
#pragma unroll
            for (int j = 0; j < 8; j++) {
                uint32_t v[4];
#pragma unroll
                for (int i = 0; i < 4; i++) v[i] = pack_bf16(acc[64 + 8 * j + 2 * i], acc[65 + 8 * j + 2 * i]);
                if (j == 4) triple(std::false_type());
                st_b128(mine + j * 4096, ~v[0], v[1], v[2], v[3]);
            }
            triple(std::false_type());
            while (true) {
                fetch_other();
                bool miss = false;
#pragma unroll
                for (int j = 0; j < 8; j++) miss |= pk[4 * j] == 0;
                if (!__any_sync(0xffffffffu, miss)) break;
                while (__any_sync(0xffffffffu, pk[28] == 0)) ld_b128(other + 7 * 4096, pk[28], pk[29], pk[30], pk[31]);
            }
#pragma unroll
            for (int j = 0; j < 32; j++) {
                const uint32_t v = j & 3 ? pk[j] : ~pk[j];
                acc[2 * j] += __uint_as_float(v << 16); acc[2 * j + 1] += __uint_as_float(v & 0xffff0000u);
                asm volatile("" : "+f"(acc[2 * j]), "+f"(acc[2 * j + 1]) :: "memory");
            }
            stage_acquire(0); stage_acquire(1);
            wgmma_wait<0>();
            fence_regs(lo);
            mbar_arrive_cluster_if(ln < 4, bars_lane + B_GEMPTY + 8 * ((k - 1 - (ln >> 1)) & 3));
#pragma unroll
            for (int j = 0; j < 32; j++)
                pk[j] = pack_bf16(acc[2 * j] + lo[2 * j], acc[2 * j + 1] + lo[2 * j + 1]);
            write_blocks(std::integral_constant<int, 8>(), 0, pk);
            __syncwarp();
            uint4* dst = (uint4*)((char*)prm.out + (uint32_t)((item_row(it) * 128 + wg * 64 + wq * 16 + (ln >> 4)) * 2048 + item_col(it) * 256 + (ln & 15) * 16));
#pragma unroll
            for (int j = 0; j < 8; j++) {
                const int r = 2 * j + (ln >> 4);
                uint4 v;
                asm volatile("ld.shared.v4.u32 {%0, %1, %2, %3}, [%4];" : "=r"(v.x), "=r"(v.y), "=r"(v.z), "=r"(v.w)
                             : "r"(stg + wq * 2048 + r * 128 + (ln & 8) * 1024 + (((ln & 7) ^ (r & 7)) << 4)) : "memory");
                dst[j * 256] = v;
            }
        }
    }
}

typedef CUresult (*EncodeFn)(CUtensorMap*, CUtensorMapDataType, cuuint32_t, void*, const cuuint64_t*, const cuuint64_t*,
                             const cuuint32_t*, const cuuint32_t*, CUtensorMapInterleave, CUtensorMapSwizzle,
                             CUtensorMapL2promotion, CUtensorMapFloatOOBfill);

void encode3(EncodeFn fn, CUtensorMap* m, const void* ptr, uint64_t d0, uint64_t d1, uint64_t d2, uint64_t s1, uint64_t s2,
             uint32_t b0, uint32_t b1, uint32_t b2) {
    cuuint64_t dims[3] = {d0, d1, d2};
    cuuint64_t strides[2] = {s1, s2};
    cuuint32_t box[3] = {b0, b1, b2};
    cuuint32_t es[3] = {1, 1, 1};
    fn(m, CU_TENSOR_MAP_DATA_TYPE_BFLOAT16, 3, const_cast<void*>(ptr), dims, strides, box, es, CU_TENSOR_MAP_INTERLEAVE_NONE,
       CU_TENSOR_MAP_SWIZZLE_128B, CU_TENSOR_MAP_L2_PROMOTION_NONE, CU_TENSOR_MAP_FLOAT_OOB_FILL_NONE);
}
void map_act(EncodeFn fn, CUtensorMap* m, const void* p, int rows, int cols, int box_rows) {
    encode3(fn, m, p, cols, rows, 1, (uint64_t)cols * 2, (uint64_t)cols * rows * 2, 64, box_rows, 1);
}
void map_wgt(EncodeFn fn, CUtensorMap* m, const void* p, int K, int N) {
    encode3(fn, m, p, 64, K, N / 64, (uint64_t)N * 2, 128, 64, 64, 2);
}

void build_schedule(Params& p) {
    int n = 0;
    auto add = [&](int type, int col, int row) { p.items[n++] = (uint16_t)(type << 13 | col << 4 | row); };
    auto add_qkv = [&](int c) {
        for (int m = 0; m < 8; m++) add(T_Q, c, m);
        for (int m = 0; m < 8; m++) add(T_K, c, m);
        for (int m = 0; m < 8; m++) add(T_V, c, m);
    };
    int ldist = 200, ldist2 = 260, lstep = 8, beta = 26, tail = 32, late = 6, early = 8, epos = 100;
    int order[16] = {6, 7, 8, 9, 10, 11, 12, 13, 14, 15, 5, 4, 3, 2, 1, 0};
    uint16_t proj[480];
    for (int m = 0; m < 8; m++) for (int c = 0; c < 12; c++) add(T_B, c, m);
    for (int c = 0; c < 16; c++) add_qkv(c);
    for (int i = 0; i < 480; i++) proj[i] = p.items[i];
    n = 0;
    for (int i = 0, l = 0; i < 480; i++) {
        p.items[n++] = proj[i];
        for (; l < 64 && i >= (l < 40 ? ldist + lstep * l / 8 : ldist2 + lstep * (l - 40) / 8); l++) add(T_LOCAL, l & 3, l >> 2);
    }
    const int a0 = n;
    for (int key = 0; key < 4000; key++)
        for (int r = 0; r < 32; r++)
            for (int j = 7; j >= 0; j--)
                if ((j ? (7 - j) * 40 + r * beta : 3999) == key) add(T_ATTN, 2 * order[r >> 1] + (r & 1), j);
    int t0 = n;
    for (int work = 0; work < 32 * 136 * tail / 100;) work += 4 * (p.items[--t0] & 15) + 3;
    for (int i = t0 + 1; i < n; i++)
        for (int j = i; j > t0 && (p.items[j] & 15) > (p.items[j - 1] & 15); j--) { const uint16_t t = p.items[j]; p.items[j] = p.items[j - 1]; p.items[j - 1] = t; }
    for (int r = early - 1; r >= 0; r--) {
        const uint16_t t = p.items[n - 32 + early - 1];
        for (int j = n - 32 + early - 1; j > n - epos; j--) p.items[j] = p.items[j - 1];
        p.items[n - epos] = t;
    }
    for (int moved = 0; moved < 2 && late >= 0; moved++)
        for (int i = a0; i < n; i++)
            if (p.items[i] == (T_ATTN << 13 | (2 * order[15] + moved) << 4 | late)) {
                for (int j = i; j + 1 < n; j++) p.items[j] = p.items[j + 1];
                p.items[n - 1] = (uint16_t)(T_ATTN << 13 | (2 * order[15] + moved) << 4 | late);
                break;
            }
    for (int s = 0, lo = 0, hi = WIDE - 1; s < 80; s++) {
        const int r = s / 2, g = r < 8 ? 32 + r : 2 * order[r / 2 - 4] + (r & 1);
        p.ostep[s >= WIDE ? s : r & 1 ? hi-- : lo++] = (uint8_t)(2 * g + (s & 1));
    }
}

void build_params(Params& p, void* const* d_in, void* d_out) {
    void* fnp = nullptr;
    cudaDriverEntryPointQueryResult qr;
    cudaGetDriverEntryPoint("cuTensorMapEncodeTiled", &fnp, cudaEnableDefault, &qr);
    EncodeFn fn = (EncodeFn)fnp;
    void* scr = nullptr;
    cudaGetSymbolAddress(&scr, g_scr);
    map_act(fn, &p.m[M_X], d_in[0], SEQ, 1024, 128);
    map_act(fn, &p.m[M_C], d_in[1], SEQ, 512, 128);
    map_wgt(fn, &p.m[M_WQ], d_in[2], 1024, 4096);
    map_wgt(fn, &p.m[M_WUK], d_in[3], 512, 4096);
    map_wgt(fn, &p.m[M_WUV], d_in[4], 512, 4096);
    map_wgt(fn, &p.m[M_WO], d_in[5], 4096, 1024);
    map_wgt(fn, &p.m[M_WQKV], d_in[7], 1024, 3072);
    map_wgt(fn, &p.m[M_WOB], d_in[8], 1024, 1024);
    encode3(fn, &p.m[M_SCR_LD], scr, 128, SEQ, G_TOTAL, 256, (uint64_t)SEQ * 256, 64, 128, 1);
    encode3(fn, &p.m[M_SCR_LOC], scr, 256, SEQ / 2, G_TOTAL, 512, (uint64_t)SEQ * 256, 64, 72, 1);
    encode3(fn, &p.m[M_SCR_LOQ], scr, 256, SEQ / 2, G_TOTAL, 512, (uint64_t)SEQ * 256, 64, 64, 1);
    encode3(fn, &p.m[M_SCR_ST], scr, 128, SEQ, G_TOTAL, 256, (uint64_t)SEQ * 256, 64, 64, 1);
    p.x = (const __nv_bfloat16*)d_in[0];
    p.gate_w = (const __nv_bfloat16*)d_in[9];
    p.zero = 0;
    p.wo = (const char*)d_in[5];
    p.out = (__nv_bfloat16*)d_out;
    build_schedule(p);
}

}

extern "C" void kernel_launch(void* const* d_in, const int* in_sizes, int n_in, void* d_out, int out_size) {
    (void)in_sizes; (void)n_in; (void)out_size;
    Params p;
    build_params(p, d_in, d_out);
    cudaFuncSetAttribute(fused_kernel, cudaFuncAttributeMaxDynamicSharedMemorySize, SM_TOTAL);
    fused_kernel<<<NCTA, 384, SM_TOTAL>>>(p);
}
```

```cpp
#include <cuda_runtime.h>
#include <cuda_bf16.h>
#include <cuda.h>
#include <stddef.h>
#include <stdint.h>
#include <type_traits>

namespace {

constexpr int SEQ = 2048;
constexpr int G_Q = 0, G_K = 32, G_V = 64, G_B = 96, G_CTX = G_Q, G_LOC = G_B, G_TOTAL = 120;

__device__ __align__(1024) __nv_bfloat16 g_scr[(size_t)G_TOTAL * SEQ * 128];
__device__ __align__(128) float g_gate[SEQ];

__device__ __forceinline__ uint32_t smem_u32(const void* p) { return (uint32_t)__cvta_generic_to_shared(p); }
__device__ __forceinline__ bool elect_one() {
    uint32_t p;
    asm volatile("{\n.reg .pred P;\nelect.sync _|P, 0xffffffff;\nselp.u32 %0, 1, 0, P;\n}\n" : "=r"(p));
    return p != 0;
}
__device__ __forceinline__ void mbar_init(uint32_t bar, uint32_t count) {
    asm volatile("mbarrier.init.shared::cta.b64 [%0], %1;" :: "r"(bar), "r"(count) : "memory");
}
__device__ __forceinline__ void mbar_expect_tx(uint32_t bar, uint32_t bytes) {
    asm volatile("mbarrier.arrive.expect_tx.shared::cta.b64 _, [%0], %1;" :: "r"(bar), "r"(bytes) : "memory");
}
__device__ __forceinline__ uint32_t cluster_rank() { uint32_t r; asm("mov.u32 %0, %%cluster_ctarank;" : "=r"(r)); return r; }
__device__ __forceinline__ uint32_t map_cta(uint32_t addr, uint32_t cta) {
    uint32_t r; asm("mapa.shared::cluster.u32 %0, %1, %2;" : "=r"(r) : "r"(addr), "r"(cta)); return r;
}
__device__ __forceinline__ void mbar_arrive_cluster_if(bool pred, uint32_t cluster_bar) {
    asm volatile("{\n.reg .pred P;\nsetp.ne.u32 P, %1, 0;\n@P mbarrier.arrive.shared::cluster.b64 _, [%0];\n}\n"
                 :: "r"(cluster_bar), "r"((uint32_t)pred) : "memory");
}
__device__ __forceinline__ void mbar_arrive_cluster_n_if(bool pred, uint32_t cluster_bar, uint32_t count) {
    asm volatile("{\n.reg .pred P;\nsetp.ne.u32 P, %1, 0;\n@P mbarrier.arrive.shared::cluster.b64 _, [%0], %2;\n}\n"
                 :: "r"(cluster_bar), "r"((uint32_t)pred), "r"(count) : "memory");
}
__device__ __forceinline__ void mbar_arrive_if(bool pred, uint32_t bar) {
    asm volatile("{\n.reg .pred P;\nsetp.ne.u32 P, %1, 0;\n@P mbarrier.arrive.shared::cta.b64 _, [%0];\n}\n"
                 :: "r"(bar), "r"((uint32_t)pred) : "memory");
}
__device__ __forceinline__ bool mbar_test(uint32_t bar, uint32_t parity) {
    uint32_t ok;
    asm volatile("{\n.reg .pred P;\nmbarrier.test_wait.parity.shared::cta.b64 P, [%1], %2;\nselp.u32 %0, 1, 0, P;\n}\n"
                 : "=r"(ok) : "r"(bar), "r"(parity) : "memory");
    return ok != 0;
}
__device__ __forceinline__ void mbar_wait(uint32_t bar, uint32_t parity) {
    asm volatile("{\n.reg .pred P;\n.reg .u32 c;\n"
                 "mov.u32 c, 0;\n"
                 "SPIN:\n"
                 "mbarrier.try_wait.parity.shared::cta.b64 P, [%0], %1;\n"
                 "@P bra DONE;\n"
                 "add.u32 c, c, 1;\n"
                 "setp.lt.u32 P, c, 4194304;\n"
                 "@P bra SPIN;\n"
                 "trap;\n"
                 "DONE:\n}\n" :: "r"(bar), "r"(parity) : "memory");
}
__device__ __forceinline__ void mbar_spin(uint32_t bar, uint32_t parity) {
    asm volatile("{\n.reg .pred P;\n"
                 "SPIN:\n"
                 "mbarrier.try_wait.parity.shared::cta.b64 P, [%0], %1;\n"
                 "@!P bra SPIN;\n}\n" :: "r"(bar), "r"(parity) : "memory");
}
__device__ __forceinline__ void bar_sync(int id, int n) { asm volatile("bar.sync %0, %1;" :: "r"(id), "r"(n) : "memory"); }
__device__ __forceinline__ void bar_arrive(int id, int n) { asm volatile("bar.arrive %0, %1;" :: "r"(id), "r"(n) : "memory"); }
__device__ __forceinline__ void fence_proxy_async_smem() { asm volatile("fence.proxy.async.shared::cta;" ::: "memory"); }
__device__ __forceinline__ void tma_load_3d(uint32_t dst, const CUtensorMap* map, uint32_t bar, int c0, int c1, int c2) {
    asm volatile("cp.async.bulk.tensor.3d.shared::cluster.global.mbarrier::complete_tx::bytes [%0], [%1, {%3, %4, %5}], [%2];"
                 :: "r"(dst), "l"(map), "r"(bar), "r"(c0), "r"(c1), "r"(c2) : "memory");
}
__device__ __forceinline__ void warp_expect_tx(uint32_t bar, uint32_t bytes) {
    asm volatile("{\n.reg .pred P;\nelect.sync _|P, 0xffffffff;\n@P mbarrier.arrive.expect_tx.shared::cta.b64 _, [%0], %1;\n}\n"
                 :: "r"(bar), "r"(bytes) : "memory");
}
constexpr uint64_t EVICT_FIRST = 0x12F0000000000000ull;
__device__ __forceinline__ void warp_tma_load(uint32_t dst, const CUtensorMap* map, uint32_t bar, int c0, int c1, int c2, bool stream) {
    if (stream)
        asm volatile("{\n.reg .pred P;\nelect.sync _|P, 0xffffffff;\n"
                     "@P cp.async.bulk.tensor.3d.shared::cluster.global.mbarrier::complete_tx::bytes.L2::cache_hint"
                     " [%0], [%1, {%3, %4, %5}], [%2], %6;\n}\n"
                     :: "r"(dst), "l"(map), "r"(bar), "r"(c0), "r"(c1), "r"(c2), "l"(EVICT_FIRST) : "memory");
    else
        asm volatile("{\n.reg .pred P;\nelect.sync _|P, 0xffffffff;\n"
                     "@P cp.async.bulk.tensor.3d.shared::cluster.global.mbarrier::complete_tx::bytes [%0], [%1, {%3, %4, %5}], [%2];\n}\n"
                     :: "r"(dst), "l"(map), "r"(bar), "r"(c0), "r"(c1), "r"(c2) : "memory");
}
__device__ __forceinline__ void warp_tma_load_pair(uint32_t dst, const CUtensorMap* map, uint32_t bar, int c0, int c1, int c2, bool stream) {
    if (stream)
        asm volatile("{\n.reg .pred P;\nelect.sync _|P, 0xffffffff;\n"
                     "@P cp.async.bulk.tensor.3d.shared::cluster.global.mbarrier::complete_tx::bytes.multicast::cluster.L2::cache_hint"
                     " [%0], [%1, {%3, %4, %5}], [%2], %6, %7;\n}\n"
                     :: "r"(dst), "l"(map), "r"(bar), "r"(c0), "r"(c1), "r"(c2), "h"((uint16_t)3), "l"(EVICT_FIRST) : "memory");
    else
        asm volatile("{\n.reg .pred P;\nelect.sync _|P, 0xffffffff;\n"
                     "@P cp.async.bulk.tensor.3d.shared::cluster.global.mbarrier::complete_tx::bytes.multicast::cluster"
                     " [%0], [%1, {%3, %4, %5}], [%2], %6;\n}\n"
                     :: "r"(dst), "l"(map), "r"(bar), "r"(c0), "r"(c1), "r"(c2), "h"((uint16_t)3) : "memory");
}
__device__ __forceinline__ void warp_bulk_load(uint32_t dst, const void* src, uint32_t bytes, uint32_t bar) {
    asm volatile("{\n.reg .pred P;\nelect.sync _|P, 0xffffffff;\n"
                 "@P cp.async.bulk.shared::cluster.global.mbarrier::complete_tx::bytes [%0], [%1], %2, [%3];\n}\n"
                 :: "r"(dst), "l"(src), "r"(bytes), "r"(bar) : "memory");
}
__device__ __forceinline__ void warp_tma_store(const CUtensorMap* map, uint32_t src, int c0, int c1, int c2, bool stream) {
    if (stream)
        asm volatile("{\n.reg .pred P;\nelect.sync _|P, 0xffffffff;\n"
                     "@P cp.async.bulk.tensor.3d.global.shared::cta.bulk_group.L2::cache_hint [%0, {%2, %3, %4}], [%1], %5;\n}\n"
                     :: "l"(map), "r"(src), "r"(c0), "r"(c1), "r"(c2), "l"(EVICT_FIRST) : "memory");
    else
        asm volatile("{\n.reg .pred P;\nelect.sync _|P, 0xffffffff;\n"
                     "@P cp.async.bulk.tensor.3d.global.shared::cta.bulk_group [%0, {%2, %3, %4}], [%1];\n}\n"
                     :: "l"(map), "r"(src), "r"(c0), "r"(c1), "r"(c2) : "memory");
}
__device__ __forceinline__ void warp_bulk_store(void* dst, uint32_t src, uint32_t bytes) {
    asm volatile("{\n.reg .pred P;\nelect.sync _|P, 0xffffffff;\n"
                 "@P cp.async.bulk.global.shared::cta.bulk_group [%0], [%1], %2;\n}\n" :: "l"(dst), "r"(src), "r"(bytes) : "memory");
}
__device__ __forceinline__ void warp_prefetch(const void* src, uint32_t bytes) {
    asm volatile("{\n.reg .pred P;\nelect.sync _|P, 0xffffffff;\n@P cp.async.bulk.prefetch.L2.global [%0], %1;\n}\n" :: "l"(src), "r"(bytes) : "memory");
}
__device__ __forceinline__ void bulk_commit() { asm volatile("cp.async.bulk.commit_group;" ::: "memory"); }
template <int N> __device__ __forceinline__ void bulk_wait_read() { asm volatile("cp.async.bulk.wait_group.read %0;" :: "n"(N) : "memory"); }
template <int N> __device__ __forceinline__ void bulk_wait() { asm volatile("cp.async.bulk.wait_group %0;" :: "n"(N) : "memory"); }
__device__ __forceinline__ void wgmma_fence() { asm volatile("wgmma.fence.sync.aligned;" ::: "memory"); }
__device__ __forceinline__ void wgmma_commit() { asm volatile("wgmma.commit_group.sync.aligned;" ::: "memory"); }
template <int N> __device__ __forceinline__ void wgmma_wait() { asm volatile("wgmma.wait_group.sync.aligned %0;" :: "n"(N) : "memory"); }
template <int N> __device__ __forceinline__ void fence_regs(float (&d)[N]) {
#pragma unroll
    for (int i = 0; i < N; i++) asm volatile("" : "+f"(d[i]) :: "memory");
}
template <int N> __device__ __forceinline__ void fence_regs(uint32_t (&d)[N]) {
#pragma unroll
    for (int i = 0; i < N; i++) asm volatile("" : "+r"(d[i]) :: "memory");
}
template <int N> __device__ __forceinline__ void reg_dec() { asm volatile("setmaxnreg.dec.sync.aligned.u32 %0;" :: "n"(N)); }
template <int N> __device__ __forceinline__ void reg_inc() { asm volatile("setmaxnreg.inc.sync.aligned.u32 %0;" :: "n"(N)); }
__device__ __forceinline__ uint32_t pack_bf16(float lo, float hi) {
    uint32_t r; asm("cvt.rn.bf16x2.f32 %0, %1, %2;" : "=r"(r) : "f"(hi), "f"(lo)); return r;
}
__device__ __forceinline__ void stmatrix_x4(uint32_t addr, uint32_t r0, uint32_t r1, uint32_t r2, uint32_t r3) {
    asm volatile("stmatrix.sync.aligned.m8n8.x4.shared.b16 [%0], {%1, %2, %3, %4};"
                 :: "r"(addr), "r"(r0), "r"(r1), "r"(r2), "r"(r3) : "memory");
}
__device__ __forceinline__ float ex2(float x) { float y; asm("ex2.approx.ftz.f32 %0, %1;" : "=f"(y) : "f"(x)); return y; }

constexpr uint32_t DESC_HI = (1024 >> 4) | (1u << 30);
__device__ __forceinline__ uint32_t make_desc(uint32_t addr, uint32_t lbo) {
    uint32_t lo = ((addr & 0x3FFFF) >> 4) | ((lbo >> 4) << 16);
    asm volatile("" : "+r"(lo));
    return lo;
}
__device__ __forceinline__ uint64_t full_desc(uint32_t lo) {
    uint64_t d; asm("mov.b64 %0, {%1, %2};" : "=l"(d) : "r"(lo), "r"(DESC_HI)); return d;
}

__device__ __forceinline__ void wgmma_ss_n256_tb_init(float (&d)[128], uint64_t da, uint64_t db) {
    asm volatile("{\n.reg .pred p;\n"
        "setp.ne.b32 p, 0, 0;\n"
        "wgmma.mma_async.sync.aligned.m64n256k16.f32.bf16.bf16 "
        "{%0, %1, %2, %3, %4, %5, %6, %7, %8, %9, %10, %11, %12, %13, %14, %15, %16, %17, %18, %19, %20, "
        "%21, %22, %23, %24, %25, %26, %27, %28, %29, %30, %31, %32, %33, %34, %35, %36, %37, %38, %39, %40, "
        "%41, %42, %43, %44, %45, %46, %47, %48, %49, %50, %51, %52, %53, %54, %55, %56, %57, %58, %59, %60, "
        "%61, %62, %63, %64, %65, %66, %67, %68, %69, %70, %71, %72, %73, %74, %75, %76, %77, %78, %79, %80, "
        "%81, %82, %83, %84, %85, %86, %87, %88, %89, %90, %91, %92, %93, %94, %95, %96, %97, %98, %99, "
        "%100, %101, %102, %103, %104, %105, %106, %107, %108, %109, %110, %111, %112, %113, %114, %115, "
        "%116, %117, %118, %119, %120, %121, %122, %123, %124, %125, %126, %127},"
        " %128, %129, p, 1, 1, 0, 1;\n}\n"
        : "=f"(d[0]), "=f"(d[1]), "=f"(d[2]), "=f"(d[3]), "=f"(d[4]), "=f"(d[5]), "=f"(d[6]), "=f"(d[7]),
        "=f"(d[8]), "=f"(d[9]), "=f"(d[10]), "=f"(d[11]), "=f"(d[12]), "=f"(d[13]), "=f"(d[14]), "=f"(d[15]),
        "=f"(d[16]), "=f"(d[17]), "=f"(d[18]), "=f"(d[19]), "=f"(d[20]), "=f"(d[21]), "=f"(d[22]),
        "=f"(d[23]), "=f"(d[24]), "=f"(d[25]), "=f"(d[26]), "=f"(d[27]), "=f"(d[28]), "=f"(d[29]),
        "=f"(d[30]), "=f"(d[31]), "=f"(d[32]), "=f"(d[33]), "=f"(d[34]), "=f"(d[35]), "=f"(d[36]),
        "=f"(d[37]), "=f"(d[38]), "=f"(d[39]), "=f"(d[40]), "=f"(d[41]), "=f"(d[42]), "=f"(d[43]),
        "=f"(d[44]), "=f"(d[45]), "=f"(d[46]), "=f"(d[47]), "=f"(d[48]), "=f"(d[49]), "=f"(d[50]),
        "=f"(d[51]), "=f"(d[52]), "=f"(d[53]), "=f"(d[54]), "=f"(d[55]), "=f"(d[56]), "=f"(d[57]),
        "=f"(d[58]), "=f"(d[59]), "=f"(d[60]), "=f"(d[61]), "=f"(d[62]), "=f"(d[63]), "=f"(d[64]),
        "=f"(d[65]), "=f"(d[66]), "=f"(d[67]), "=f"(d[68]), "=f"(d[69]), "=f"(d[70]), "=f"(d[71]),
        "=f"(d[72]), "=f"(d[73]), "=f"(d[74]), "=f"(d[75]), "=f"(d[76]), "=f"(d[77]), "=f"(d[78]),
        "=f"(d[79]), "=f"(d[80]), "=f"(d[81]), "=f"(d[82]), "=f"(d[83]), "=f"(d[84]), "=f"(d[85]),
        "=f"(d[86]), "=f"(d[87]), "=f"(d[88]), "=f"(d[89]), "=f"(d[90]), "=f"(d[91]), "=f"(d[92]),
        "=f"(d[93]), "=f"(d[94]), "=f"(d[95]), "=f"(d[96]), "=f"(d[97]), "=f"(d[98]), "=f"(d[99]),
        "=f"(d[100]), "=f"(d[101]), "=f"(d[102]), "=f"(d[103]), "=f"(d[104]), "=f"(d[105]), "=f"(d[106]),
        "=f"(d[107]), "=f"(d[108]), "=f"(d[109]), "=f"(d[110]), "=f"(d[111]), "=f"(d[112]), "=f"(d[113]),
        "=f"(d[114]), "=f"(d[115]), "=f"(d[116]), "=f"(d[117]), "=f"(d[118]), "=f"(d[119]), "=f"(d[120]),
        "=f"(d[121]), "=f"(d[122]), "=f"(d[123]), "=f"(d[124]), "=f"(d[125]), "=f"(d[126]), "=f"(d[127])
        : "l"(da), "l"(db));
}
__device__ __forceinline__ void wgmma_ss_n256_tb(float (&d)[128], uint64_t da, uint64_t db, int scale_d) {
    asm volatile("{\n.reg .pred p;\n"
        "setp.ne.b32 p, %130, 0;\n"
        "wgmma.mma_async.sync.aligned.m64n256k16.f32.bf16.bf16 "
        "{%0, %1, %2, %3, %4, %5, %6, %7, %8, %9, %10, %11, %12, %13, %14, %15, %16, %17, %18, %19, %20, "
        "%21, %22, %23, %24, %25, %26, %27, %28, %29, %30, %31, %32, %33, %34, %35, %36, %37, %38, %39, %40, "
        "%41, %42, %43, %44, %45, %46, %47, %48, %49, %50, %51, %52, %53, %54, %55, %56, %57, %58, %59, %60, "
        "%61, %62, %63, %64, %65, %66, %67, %68, %69, %70, %71, %72, %73, %74, %75, %76, %77, %78, %79, %80, "
        "%81, %82, %83, %84, %85, %86, %87, %88, %89, %90, %91, %92, %93, %94, %95, %96, %97, %98, %99, "
        "%100, %101, %102, %103, %104, %105, %106, %107, %108, %109, %110, %111, %112, %113, %114, %115, "
        "%116, %117, %118, %119, %120, %121, %122, %123, %124, %125, %126, %127},"
        " %128, %129, p, 1, 1, 0, 1;\n}\n"
        : "+f"(d[0]), "+f"(d[1]), "+f"(d[2]), "+f"(d[3]), "+f"(d[4]), "+f"(d[5]), "+f"(d[6]), "+f"(d[7]),
        "+f"(d[8]), "+f"(d[9]), "+f"(d[10]), "+f"(d[11]), "+f"(d[12]), "+f"(d[13]), "+f"(d[14]), "+f"(d[15]),
        "+f"(d[16]), "+f"(d[17]), "+f"(d[18]), "+f"(d[19]), "+f"(d[20]), "+f"(d[21]), "+f"(d[22]),
        "+f"(d[23]), "+f"(d[24]), "+f"(d[25]), "+f"(d[26]), "+f"(d[27]), "+f"(d[28]), "+f"(d[29]),
        "+f"(d[30]), "+f"(d[31]), "+f"(d[32]), "+f"(d[33]), "+f"(d[34]), "+f"(d[35]), "+f"(d[36]),
        "+f"(d[37]), "+f"(d[38]), "+f"(d[39]), "+f"(d[40]), "+f"(d[41]), "+f"(d[42]), "+f"(d[43]),
        "+f"(d[44]), "+f"(d[45]), "+f"(d[46]), "+f"(d[47]), "+f"(d[48]), "+f"(d[49]), "+f"(d[50]),
        "+f"(d[51]), "+f"(d[52]), "+f"(d[53]), "+f"(d[54]), "+f"(d[55]), "+f"(d[56]), "+f"(d[57]),
        "+f"(d[58]), "+f"(d[59]), "+f"(d[60]), "+f"(d[61]), "+f"(d[62]), "+f"(d[63]), "+f"(d[64]),
        "+f"(d[65]), "+f"(d[66]), "+f"(d[67]), "+f"(d[68]), "+f"(d[69]), "+f"(d[70]), "+f"(d[71]),
        "+f"(d[72]), "+f"(d[73]), "+f"(d[74]), "+f"(d[75]), "+f"(d[76]), "+f"(d[77]), "+f"(d[78]),
        "+f"(d[79]), "+f"(d[80]), "+f"(d[81]), "+f"(d[82]), "+f"(d[83]), "+f"(d[84]), "+f"(d[85]),
        "+f"(d[86]), "+f"(d[87]), "+f"(d[88]), "+f"(d[89]), "+f"(d[90]), "+f"(d[91]), "+f"(d[92]),
        "+f"(d[93]), "+f"(d[94]), "+f"(d[95]), "+f"(d[96]), "+f"(d[97]), "+f"(d[98]), "+f"(d[99]),
        "+f"(d[100]), "+f"(d[101]), "+f"(d[102]), "+f"(d[103]), "+f"(d[104]), "+f"(d[105]), "+f"(d[106]),
        "+f"(d[107]), "+f"(d[108]), "+f"(d[109]), "+f"(d[110]), "+f"(d[111]), "+f"(d[112]), "+f"(d[113]),
        "+f"(d[114]), "+f"(d[115]), "+f"(d[116]), "+f"(d[117]), "+f"(d[118]), "+f"(d[119]), "+f"(d[120]),
        "+f"(d[121]), "+f"(d[122]), "+f"(d[123]), "+f"(d[124]), "+f"(d[125]), "+f"(d[126]), "+f"(d[127])
        : "l"(da), "l"(db), "r"(scale_d));
}
__device__ __forceinline__ void wgmma_ss_n128(float (&d)[64], uint64_t da, uint64_t db, int scale_d) {
    asm volatile("{\n.reg .pred p;\n"
        "setp.ne.b32 p, %66, 0;\n"
        "wgmma.mma_async.sync.aligned.m64n128k16.f32.bf16.bf16 "
        "{%0, %1, %2, %3, %4, %5, %6, %7, %8, %9, %10, %11, %12, %13, %14, %15, %16, %17, %18, %19, %20, "
        "%21, %22, %23, %24, %25, %26, %27, %28, %29, %30, %31, %32, %33, %34, %35, %36, %37, %38, %39, %40, "
        "%41, %42, %43, %44, %45, %46, %47, %48, %49, %50, %51, %52, %53, %54, %55, %56, %57, %58, %59, %60, "
        "%61, %62, %63},"
        " %64, %65, p, 1, 1, 0, 0;\n}\n"
        : "+f"(d[0]), "+f"(d[1]), "+f"(d[2]), "+f"(d[3]), "+f"(d[4]), "+f"(d[5]), "+f"(d[6]), "+f"(d[7]),
        "+f"(d[8]), "+f"(d[9]), "+f"(d[10]), "+f"(d[11]), "+f"(d[12]), "+f"(d[13]), "+f"(d[14]), "+f"(d[15]),
        "+f"(d[16]), "+f"(d[17]), "+f"(d[18]), "+f"(d[19]), "+f"(d[20]), "+f"(d[21]), "+f"(d[22]),
        "+f"(d[23]), "+f"(d[24]), "+f"(d[25]), "+f"(d[26]), "+f"(d[27]), "+f"(d[28]), "+f"(d[29]),
        "+f"(d[30]), "+f"(d[31]), "+f"(d[32]), "+f"(d[33]), "+f"(d[34]), "+f"(d[35]), "+f"(d[36]),
        "+f"(d[37]), "+f"(d[38]), "+f"(d[39]), "+f"(d[40]), "+f"(d[41]), "+f"(d[42]), "+f"(d[43]),
        "+f"(d[44]), "+f"(d[45]), "+f"(d[46]), "+f"(d[47]), "+f"(d[48]), "+f"(d[49]), "+f"(d[50]),
        "+f"(d[51]), "+f"(d[52]), "+f"(d[53]), "+f"(d[54]), "+f"(d[55]), "+f"(d[56]), "+f"(d[57]),
        "+f"(d[58]), "+f"(d[59]), "+f"(d[60]), "+f"(d[61]), "+f"(d[62]), "+f"(d[63])
        : "l"(da), "l"(db), "r"(scale_d));
}
__device__ __forceinline__ void wgmma_rs_n128_tb(float (&d)[64], uint32_t a0, uint32_t a1, uint32_t a2, uint32_t a3, uint64_t db, int scale_d) {
    asm volatile("{\n.reg .pred p;\n"
        "setp.ne.b32 p, %69, 0;\n"
        "wgmma.mma_async.sync.aligned.m64n128k16.f32.bf16.bf16 "
        "{%0, %1, %2, %3, %4, %5, %6, %7, %8, %9, %10, %11, %12, %13, %14, %15, %16, %17, %18, %19, %20, "
        "%21, %22, %23, %24, %25, %26, %27, %28, %29, %30, %31, %32, %33, %34, %35, %36, %37, %38, %39, %40, "
        "%41, %42, %43, %44, %45, %46, %47, %48, %49, %50, %51, %52, %53, %54, %55, %56, %57, %58, %59, %60, "
        "%61, %62, %63},"
        " {%64, %65, %66, %67}, %68, p, 1, 1, 1;\n}\n"
        : "+f"(d[0]), "+f"(d[1]), "+f"(d[2]), "+f"(d[3]), "+f"(d[4]), "+f"(d[5]), "+f"(d[6]), "+f"(d[7]),
        "+f"(d[8]), "+f"(d[9]), "+f"(d[10]), "+f"(d[11]), "+f"(d[12]), "+f"(d[13]), "+f"(d[14]), "+f"(d[15]),
        "+f"(d[16]), "+f"(d[17]), "+f"(d[18]), "+f"(d[19]), "+f"(d[20]), "+f"(d[21]), "+f"(d[22]),
        "+f"(d[23]), "+f"(d[24]), "+f"(d[25]), "+f"(d[26]), "+f"(d[27]), "+f"(d[28]), "+f"(d[29]),
        "+f"(d[30]), "+f"(d[31]), "+f"(d[32]), "+f"(d[33]), "+f"(d[34]), "+f"(d[35]), "+f"(d[36]),
        "+f"(d[37]), "+f"(d[38]), "+f"(d[39]), "+f"(d[40]), "+f"(d[41]), "+f"(d[42]), "+f"(d[43]),
        "+f"(d[44]), "+f"(d[45]), "+f"(d[46]), "+f"(d[47]), "+f"(d[48]), "+f"(d[49]), "+f"(d[50]),
        "+f"(d[51]), "+f"(d[52]), "+f"(d[53]), "+f"(d[54]), "+f"(d[55]), "+f"(d[56]), "+f"(d[57]),
        "+f"(d[58]), "+f"(d[59]), "+f"(d[60]), "+f"(d[61]), "+f"(d[62]), "+f"(d[63])
        : "r"(a0), "r"(a1), "r"(a2), "r"(a3), "l"(db), "r"(scale_d));
}
__device__ __forceinline__ void wgmma_ss_n128_tb_init(float (&d)[64], uint64_t da, uint64_t db) {
    asm volatile("{\n.reg .pred p;\n"
        "setp.ne.b32 p, 0, 0;\n"
        "wgmma.mma_async.sync.aligned.m64n128k16.f32.bf16.bf16 "
        "{%0, %1, %2, %3, %4, %5, %6, %7, %8, %9, %10, %11, %12, %13, %14, %15, %16, %17, %18, %19, %20, "
        "%21, %22, %23, %24, %25, %26, %27, %28, %29, %30, %31, %32, %33, %34, %35, %36, %37, %38, %39, %40, "
        "%41, %42, %43, %44, %45, %46, %47, %48, %49, %50, %51, %52, %53, %54, %55, %56, %57, %58, %59, %60, "
        "%61, %62, %63},"
        " %64, %65, p, 1, 1, 0, 1;\n}\n"
        : "=f"(d[0]), "=f"(d[1]), "=f"(d[2]), "=f"(d[3]), "=f"(d[4]), "=f"(d[5]), "=f"(d[6]), "=f"(d[7]),
        "=f"(d[8]), "=f"(d[9]), "=f"(d[10]), "=f"(d[11]), "=f"(d[12]), "=f"(d[13]), "=f"(d[14]), "=f"(d[15]),
        "=f"(d[16]), "=f"(d[17]), "=f"(d[18]), "=f"(d[19]), "=f"(d[20]), "=f"(d[21]), "=f"(d[22]),
        "=f"(d[23]), "=f"(d[24]), "=f"(d[25]), "=f"(d[26]), "=f"(d[27]), "=f"(d[28]), "=f"(d[29]),
        "=f"(d[30]), "=f"(d[31]), "=f"(d[32]), "=f"(d[33]), "=f"(d[34]), "=f"(d[35]), "=f"(d[36]),
        "=f"(d[37]), "=f"(d[38]), "=f"(d[39]), "=f"(d[40]), "=f"(d[41]), "=f"(d[42]), "=f"(d[43]),
        "=f"(d[44]), "=f"(d[45]), "=f"(d[46]), "=f"(d[47]), "=f"(d[48]), "=f"(d[49]), "=f"(d[50]),
        "=f"(d[51]), "=f"(d[52]), "=f"(d[53]), "=f"(d[54]), "=f"(d[55]), "=f"(d[56]), "=f"(d[57]),
        "=f"(d[58]), "=f"(d[59]), "=f"(d[60]), "=f"(d[61]), "=f"(d[62]), "=f"(d[63])
        : "l"(da), "l"(db));
}
__device__ __forceinline__ void wgmma_ss_n128_tb(float (&d)[64], uint64_t da, uint64_t db, int scale_d) {
    asm volatile("{\n.reg .pred p;\n"
        "setp.ne.b32 p, %66, 0;\n"
        "wgmma.mma_async.sync.aligned.m64n128k16.f32.bf16.bf16 "
        "{%0, %1, %2, %3, %4, %5, %6, %7, %8, %9, %10, %11, %12, %13, %14, %15, %16, %17, %18, %19, %20, "
        "%21, %22, %23, %24, %25, %26, %27, %28, %29, %30, %31, %32, %33, %34, %35, %36, %37, %38, %39, %40, "
        "%41, %42, %43, %44, %45, %46, %47, %48, %49, %50, %51, %52, %53, %54, %55, %56, %57, %58, %59, %60, "
        "%61, %62, %63},"
        " %64, %65, p, 1, 1, 0, 1;\n}\n"
        : "+f"(d[0]), "+f"(d[1]), "+f"(d[2]), "+f"(d[3]), "+f"(d[4]), "+f"(d[5]), "+f"(d[6]), "+f"(d[7]),
        "+f"(d[8]), "+f"(d[9]), "+f"(d[10]), "+f"(d[11]), "+f"(d[12]), "+f"(d[13]), "+f"(d[14]), "+f"(d[15]),
        "+f"(d[16]), "+f"(d[17]), "+f"(d[18]), "+f"(d[19]), "+f"(d[20]), "+f"(d[21]), "+f"(d[22]),
        "+f"(d[23]), "+f"(d[24]), "+f"(d[25]), "+f"(d[26]), "+f"(d[27]), "+f"(d[28]), "+f"(d[29]),
        "+f"(d[30]), "+f"(d[31]), "+f"(d[32]), "+f"(d[33]), "+f"(d[34]), "+f"(d[35]), "+f"(d[36]),
        "+f"(d[37]), "+f"(d[38]), "+f"(d[39]), "+f"(d[40]), "+f"(d[41]), "+f"(d[42]), "+f"(d[43]),
        "+f"(d[44]), "+f"(d[45]), "+f"(d[46]), "+f"(d[47]), "+f"(d[48]), "+f"(d[49]), "+f"(d[50]),
        "+f"(d[51]), "+f"(d[52]), "+f"(d[53]), "+f"(d[54]), "+f"(d[55]), "+f"(d[56]), "+f"(d[57]),
        "+f"(d[58]), "+f"(d[59]), "+f"(d[60]), "+f"(d[61]), "+f"(d[62]), "+f"(d[63])
        : "l"(da), "l"(db), "r"(scale_d));
}

enum { M_X = 0, M_C, M_WQ, M_WUK, M_WUV, M_WQKV, M_WO, M_WOB, M_SCR_LD, M_SCR_LOC, M_SCR_LOQ, M_SCR_ST, M_COUNT };
enum { T_Q = 0, T_K, T_V, T_B, T_OUT, T_LOCAL, T_ATTN, T_END };
constexpr int NCTA = 132, NPAIR = NCTA / 2;
constexpr int NITEMS = 480 + 64 + 256;
constexpr int TRIPLES = 3, WIDE = 80 - 3 * TRIPLES;
struct Params {
    CUtensorMap m[M_COUNT];
    const __nv_bfloat16* x;
    const __nv_bfloat16* gate_w;
    const char* wo;
    __nv_bfloat16* out;
    uint32_t zero;
    uint16_t items[NITEMS];
    uint8_t ostep[80];
};
__device__ __forceinline__ int item_type(int it) { return it >> 13; }
__device__ __forceinline__ int item_row(int it) { return it & 15; }
__device__ __forceinline__ int item_col(int it) { return (it >> 4) & 31; }
__device__ __forceinline__ int item_asc(int it) { return (it >> 9) & 1; }
constexpr int ITEM_READY = 1 << 10;

struct __align__(128) Sync {
    unsigned long long count[4];
    __align__(128) unsigned long long ctx[16];
    unsigned next, next_out, done;
    __align__(128) unsigned step[32][2];
    unsigned split[32];
};
__device__ Sync g_sync;
__device__ uint4 g_part[128][8][256];

constexpr uint32_t GST_BYTES = 49152, SM_KV = 65536, SM_STAGING = 196608, SM_BARS = SM_STAGING + 32768;
constexpr uint32_t B_GFULL = 0, B_GEMPTY = 32, B_AFULL = 64, B_AEMPTY = 112, B_SFULL = 160, B_SEMPTY = 192,
                   B_IFULL = 224, B_IEMPTY = 288, B_XFREE = 352, B_WANT = 384, B_HALF = 416,
                   SM_ORDY = 448, SM_QUEUE = 456, B_ALT = 488, B_QFREE = 504, SM_GATE = 512, SM_TOTAL = SM_BARS + 1536;
constexpr int QDEPTH = 8;
constexpr int FIRST_PAIR = 6;
constexpr int K_MEET = 14, K_SPLIT = 26;
constexpr int K_FETCH = 20;
constexpr uint32_t LOC_PLANE = 72 * 128;
constexpr float SM_SCALE = 0.08838834764831845f * 1.4426950408889634f;
constexpr float LOC_SCALE = 0.17677669529663687f * 1.4426950408889634f;
constexpr float SUM_LIMIT = 1152921504606846976.f;
constexpr float REF_RANGE = 32.f;

__device__ __forceinline__ unsigned ld_acquire(const unsigned* p) {
    unsigned v; asm volatile("ld.acquire.gpu.global.u32 %0, [%1];" : "=r"(v) : "l"(p) : "memory"); return v;
}
__device__ __forceinline__ unsigned long long ld_acquire(const unsigned long long* p) {
    unsigned long long v; asm volatile("ld.acquire.gpu.global.u64 %0, [%1];" : "=l"(v) : "l"(p) : "memory"); return v;
}
__device__ __forceinline__ void st_b128(void* p, uint32_t a, uint32_t b, uint32_t c, uint32_t d) {
    asm volatile("{\n.reg .b128 v;\n.reg .b64 lo, hi;\nmov.b64 lo, {%1, %2};\nmov.b64 hi, {%3, %4};\nmov.b128 v, {lo, hi};\n"
                 "st.relaxed.gpu.global.b128 [%0], v;\n}\n" :: "l"(p), "r"(a), "r"(b), "r"(c), "r"(d) : "memory");
}
__device__ __forceinline__ void ld_b128(const void* p, uint32_t& a, uint32_t& b, uint32_t& c, uint32_t& d) {
    asm volatile("{\n.reg .b128 v;\n.reg .b64 lo, hi;\nld.relaxed.gpu.global.b128 v, [%4];\nmov.b128 {lo, hi}, v;\n"
                 "mov.b64 {%0, %1}, lo;\nmov.b64 {%2, %3}, hi;\n}\n" : "=r"(a), "=r"(b), "=r"(c), "=r"(d) : "l"(p) : "memory");
}
__device__ __forceinline__ void spin_guard(unsigned& n) {
    asm volatile("{\n.reg .pred P;\nadd.u32 %0, %0, 1;\nsetp.gt.u32 P, %0, 16777216;\n@P trap;\n}\n" : "+r"(n));
    if (n > 1) __nanosleep(100);
}
__device__ __forceinline__ void red_add(unsigned long long* p, unsigned long long v) {
    asm volatile("red.release.gpu.global.add.u64 [%0], %1;" :: "l"(p), "l"(v) : "memory");
}
__device__ __forceinline__ float rcp(float x) { float y; asm("rcp.approx.ftz.f32 %0, %1;" : "=f"(y) : "f"(x)); return y; }
__device__ __forceinline__ float lds_f32(uint32_t addr) {
    float v; asm volatile("ld.shared.f32 %0, [%1];" : "=f"(v) : "r"(addr) : "memory"); return v;
}
__device__ __forceinline__ void ldsm_x4(uint32_t (&r)[4], uint32_t addr) {
    asm volatile("ldmatrix.sync.aligned.m8n8.x4.shared.b16 {%0, %1, %2, %3}, [%4];"
                 : "=r"(r[0]), "=r"(r[1]), "=r"(r[2]), "=r"(r[3]) : "r"(addr) : "memory");
}
__device__ __forceinline__ void ldsm_x4_t(uint32_t (&r)[4], uint32_t addr) {
    asm volatile("ldmatrix.sync.aligned.m8n8.x4.trans.shared.b16 {%0, %1, %2, %3}, [%4];"
                 : "=r"(r[0]), "=r"(r[1]), "=r"(r[2]), "=r"(r[3]) : "r"(addr) : "memory");
}
__device__ __forceinline__ void mma_k16(float (&d)[4], const uint32_t (&a)[4], uint32_t b0, uint32_t b1) {
    asm("mma.sync.aligned.m16n8k16.row.col.f32.bf16.bf16.f32 {%0,%1,%2,%3}, {%4,%5,%6,%7}, {%8,%9}, {%0,%1,%2,%3};"
        : "+f"(d[0]), "+f"(d[1]), "+f"(d[2]), "+f"(d[3]) : "r"(a[0]), "r"(a[1]), "r"(a[2]), "r"(a[3]), "r"(b0), "r"(b1));
}
__device__ __forceinline__ void mma_k16_init(float (&d)[4], const uint32_t (&a)[4], uint32_t b0, uint32_t b1) {
    asm("{\n.reg .f32 z;\nmov.f32 z, 0f00000000;\n"
        "mma.sync.aligned.m16n8k16.row.col.f32.bf16.bf16.f32 {%0,%1,%2,%3}, {%4,%5,%6,%7}, {%8,%9}, {z,z,z,z};\n}\n"
        : "=f"(d[0]), "=f"(d[1]), "=f"(d[2]), "=f"(d[3]) : "r"(a[0]), "r"(a[1]), "r"(a[2]), "r"(a[3]), "r"(b0), "r"(b1));
}
__device__ __forceinline__ void mma_k8(float (&d)[4], uint32_t a0, uint32_t a1, uint32_t b0) {
    asm("mma.sync.aligned.m16n8k8.row.col.f32.bf16.bf16.f32 {%0,%1,%2,%3}, {%4,%5}, {%6}, {%0,%1,%2,%3};"
        : "+f"(d[0]), "+f"(d[1]), "+f"(d[2]), "+f"(d[3]) : "r"(a0), "r"(a1), "r"(b0));
}
template <typename T, int N> __device__ __forceinline__ void zero_regs(T (&d)[N]) {
#pragma unroll
    for (int i = 0; i < N; i++) d[i] = 0;
}
__device__ __forceinline__ float quad_max(float v) {
    v = fmaxf(v, __shfl_xor_sync(0xffffffffu, v, 1));
    return fmaxf(v, __shfl_xor_sync(0xffffffffu, v, 2));
}
__device__ __forceinline__ float quad_sum(float v) {
    v += __shfl_xor_sync(0xffffffffu, v, 1);
    return v + __shfl_xor_sync(0xffffffffu, v, 2);
}

__device__ __forceinline__ void qk_gemm(float (&s)[64], uint32_t q_lo, uint32_t k_lo) {
    const uint64_t dq = full_desc(q_lo), dk = full_desc(k_lo);
    fence_regs(s);
    wgmma_fence();
#pragma unroll
    for (int kk = 0; kk < 8; kk++) {
        const uint32_t o = (kk >> 2) * 1024 + (kk & 3) * 2;
        wgmma_ss_n128(s, dq + o, dk + o, kk != 0);
    }
    wgmma_commit();
}
__device__ __forceinline__ void pv_gemm(float (&o)[64], uint32_t (&p)[32], uint32_t v_lo, int accumulate) {
    const uint64_t dv = full_desc(v_lo);
    fence_regs(o);
    fence_regs(p);
    wgmma_fence();
#pragma unroll
    for (int kk = 0; kk < 8; kk++)
        wgmma_rs_n128_tb(o, p[4 * kk], p[4 * kk + 1], p[4 * kk + 2], p[4 * kk + 3], dv + kk * 128, kk != 0 || accumulate);
    wgmma_commit();
}
__device__ __forceinline__ void row_max(const float (&s)[64], float& x0, float& x1) {
    float z0 = fmaxf(s[0], s[1]), z1 = fmaxf(s[2], s[3]);
    x0 = fmaxf(s[4], s[5]); x1 = fmaxf(s[6], s[7]);
#pragma unroll
    for (int j = 2; j < 16; j += 2) {
        z0 = fmaxf(z0, fmaxf(s[4 * j], s[4 * j + 1]));
        z1 = fmaxf(z1, fmaxf(s[4 * j + 2], s[4 * j + 3]));
        x0 = fmaxf(x0, fmaxf(s[4 * j + 4], s[4 * j + 5]));
        x1 = fmaxf(x1, fmaxf(s[4 * j + 6], s[4 * j + 7]));
    }
    x0 = quad_max(fmaxf(x0, z0)); x1 = quad_max(fmaxf(x1, z1));
}
__device__ __forceinline__ void exp_pack(uint32_t (&p)[32], const float (&s)[64], float& r0, float& r1) {
#pragma unroll
    for (int j = 0; j < 16; j++) {
        const float e0 = ex2(s[4 * j]), e1 = ex2(s[4 * j + 1]), e2 = ex2(s[4 * j + 2]), e3 = ex2(s[4 * j + 3]);
        if (j == 0) { r0 = e0 + e1; r1 = e2 + e3; }
        else { r0 += e0 + e1; r1 += e2 + e3; }
        p[2 * j] = pack_bf16(e0, e1);
        p[2 * j + 1] = pack_bf16(e2, e3);
    }
}
__device__ __forceinline__ void shift_rows(float (&s)[64], float d0, float d1) {
#pragma unroll
    for (int j = 0; j < 16; j++) { s[4 * j] -= d0; s[4 * j + 1] -= d0; s[4 * j + 2] -= d1; s[4 * j + 3] -= d1; }
}
constexpr float MASKED = -3e38f;
template <int J0>
__device__ __forceinline__ void mask_triangle(float (&s)[64], float thr) {
#pragma unroll
    for (int j = 0; j < 16; j++) {
        const float m = __saturatef((float)(8 * (j >> 1) + (j & 1)) - thr);
        const int i = 4 * (J0 + (j >> 1)) + (j & 1);
        s[i] = fmaf(m, MASKED, s[i]);
        if (j < 14) s[i + 6] = fmaf(m, MASKED, s[i + 6]);
    }
}
__device__ __forceinline__ void causal_mask(float (&s)[64], float thr, int wg) {
    asm volatile("" : "+f"(thr));
    if (wg == 0) {
        mask_triangle<0>(s, thr);
#pragma unroll
        for (int j = 32; j < 64; j++) s[j] += MASKED;
    } else {
        mask_triangle<8>(s, thr);
    }
}

__global__ void __cluster_dims__(2, 1, 1) __launch_bounds__(384, 1) fused_kernel(const __grid_constant__ Params prm) {
    extern __shared__ __align__(1024) uint8_t smem[];
    const uint32_t sb = smem_u32(smem), bars = sb + SM_BARS;
    const int warp = __shfl_sync(0xffffffffu, threadIdx.x >> 5, 0), lane = threadIdx.x & 31;

    const uint32_t rank = cluster_rank();
    const uint32_t bars0 = map_cta(bars, 0), bars_peer = map_cta(bars, rank ^ 1);

    auto first_item = [&]() -> int {
        uint32_t pair = blockIdx.x >> 1;
        asm volatile("" : "+r"(pair));
        return prm.items[pair] + item_row(prm.items[pair]) + rank;
    };
    if (threadIdx.x == 256) {
        for (int k = 0; k < 4; k++) mbar_init(bars + B_GFULL + 8 * k, 1);
        asm volatile("fence.mbarrier_init.release.cluster;" ::: "memory");
        fence_proxy_async_smem();
    }
    if (threadIdx.x == 128) {
        for (int i = 0; i < 4; i++) { mbar_init(bars + B_GEMPTY + 8 * i, 16); mbar_init(bars + B_XFREE + 8 * i, 1); }
        for (int i = 0; i < 6; i++) { mbar_init(bars + B_AFULL + 8 * i, 1); mbar_init(bars + B_AEMPTY + 8 * i, i < 2 ? 8 : 16); }
        for (int i = 0; i < 4; i++) { mbar_init(bars + B_SFULL + 8 * i, 4); mbar_init(bars + B_SEMPTY + 8 * i, 1); }
        for (int i = 0; i < QDEPTH; i++) { mbar_init(bars + B_IFULL + 8 * i, 1); mbar_init(bars + B_IEMPTY + 8 * i, 23); }
        mbar_init(bars + B_WANT, 2);
        for (int i = 0; i < 4; i++) mbar_init(bars + B_HALF + 8 * i, 1);
        mbar_init(bars + B_ALT, 4); mbar_init(bars + B_ALT + 8, 4); mbar_init(bars + B_QFREE, 2);
        asm volatile("st.shared.u64 [%0], 0;" :: "r"(bars + SM_ORDY) : "memory");
        asm volatile("fence.mbarrier_init.release.cluster;\nfence.acq_rel.cta;" ::: "memory");
    }
    __syncwarp();
    asm volatile("barrier.cluster.arrive.relaxed.aligned;" ::: "memory");
    if (threadIdx.x == 256) {
        const int first_it = first_item();
#pragma unroll 1
        for (int k = 0; k < 4; k++) {
            const uint32_t dst = sb + k * GST_BYTES, fb = bars + B_GFULL + 8 * k;
            mbar_expect_tx(fb, GST_BYTES);
            tma_load_3d(dst, &prm.m[M_X], fb, k * 64, item_row(first_it) * 128, 0);
            tma_load_3d(dst + 16384, &prm.m[M_WQKV], fb, 0, k * 64, item_col(first_it) * 4);
            tma_load_3d(dst + 32768, &prm.m[M_WQKV], fb, 0, k * 64, item_col(first_it) * 4 + 2);
        }
    }
    __syncwarp();
    asm volatile("barrier.cluster.wait.acquire.aligned;" ::: "memory");

    uint32_t qn = 0;
    auto next_item = [&](bool releaser, bool bounded = true) -> int {
        const uint32_t slot = qn % QDEPTH;
        if (bounded) mbar_wait(bars + B_IFULL + 8 * slot, (qn / QDEPTH) & 1);
        else mbar_spin(bars + B_IFULL + 8 * slot, (qn / QDEPTH) & 1);
        uint32_t it;
        asm volatile("ld.shared.u32 %0, [%1];" : "=r"(it) : "r"(bars + SM_QUEUE + 4 * slot) : "memory");
        mbar_arrive_cluster_if(releaser, bars0 + B_IEMPTY + 8 * slot);
        qn++;
        return it;
    };

    if (warp < 4) {
        reg_dec<40>();
        if (warp == 0) {
            {
                uint32_t gph = 0;
                const uint32_t prank = __shfl_sync(0xffffffffu, rank, 0);
                auto request = [&]() { mbar_arrive_cluster_if(lane == 0, bars0 + B_WANT); };
                auto take_item = [&]() -> int { return __shfl_sync(0xffffffffu, next_item(lane == 0), 0); };
                auto inputs_seen = [&](uint32_t word, unsigned& n) -> uint32_t {
                    uint32_t v;
                    spin_guard(n);
                    asm volatile("ld.acquire.cta.shared.u32 %0, [%1];" : "=r"(v) : "r"(bars + SM_ORDY + 4 * word) : "memory");
                    return __shfl_sync(0xffffffffu, v, 0);
                };
                uint32_t oneed = 0;
                auto wait_inputs = [&](int it) {
                    if (it & ITEM_READY) return;
                    oneed += 256;
                    for (unsigned n = 0; inputs_seen(1, n) < oneed;) {}
                };
                int nxt = first_item();
                for (int k0 = 4; item_type(nxt) <= T_LOCAL; k0 = 0) {
                    const int type = item_type(nxt), m = item_row(nxt), c = item_col(nxt);
                    if (type == T_LOCAL) {
                        wait_inputs(nxt);
                        request();
#pragma unroll 1
                        for (uint32_t st = 0; st < 4; st++) {
                            mbar_wait(bars + B_GEMPTY + 8 * st, gph);
                            const uint32_t dst = sb + st * GST_BYTES, fb = bars + B_GFULL + 8 * st;
                            warp_expect_tx(fb, st == 0 ? 32768 + 512 : st == 3 ? 0 : 4 * LOC_PLANE);
                            if (st == 3) break;
                            if (st == 0) warp_bulk_load(dst + 4 * LOC_PLANE, &g_gate[m * 128], 512, fb);
#pragma unroll 1
                            for (int i = 0; i < 4; i++)
                                warp_tma_load(dst + i * LOC_PLANE, &prm.m[st ? M_SCR_LOC : M_SCR_LOQ], fb, i * 64, m * 64 - (st ? 8 : 0), G_B + 8 * st + c, true);
                        }
                        gph ^= 1;
                    } else {
                        const int nk = type == T_K || type == T_V ? 8 : 16;
                        const CUtensorMap* ma = &prm.m[nk == 8 ? M_C : M_X];
                        const CUtensorMap* mb = &prm.m[M_WQ + type];
#pragma unroll 1
                        for (int k = k0; k < nk; k++) {
                            if (k == nk - 3) request();
                            const uint32_t st = k & 3, dst = sb + st * GST_BYTES, fb = bars + B_GFULL + 8 * st;
                            mbar_wait(bars + B_GEMPTY + 8 * st, gph);
                            warp_expect_tx(fb, GST_BYTES);
                            warp_tma_load(dst, ma, fb, k * 64, m * 128, 0, c == 15 && type != T_K);
                            warp_tma_load_pair(dst + 16384 + prank * 16384, mb, fb, 0, k * 64, c * 4 + 2 * prank, type != T_B || m >= 14);
                            if (st == 3) gph ^= 1;
                        }
                    }
                    nxt = take_item();
                }
                uint32_t kv = 0, kvph = 1;
                uint32_t qc = 0;
                auto a_parity = [&](uint32_t b) { return b < 2 ? (((qc + 1 - b) >> 1) & 1) ^ 1 : kvph ^ (b - 2 < kv); };
                const CUtensorMap* tile_map = &prm.m[M_SCR_LD];
                asm volatile("" : "+l"(tile_map));
                {
                    bool need_g = true, more = true;
                    int pv_grp = -1, pv_row = 0;
                    int pv_shared = 0;
                    bool peer_longer = false;
                    int m = 0, c = 0, asc = 0, nu = 0, uend = 0, ureq = -1, ufetch = 0;
#pragma unroll 1
                    for (int u = 0;; u++) {
                        if (u == ufetch) {
                            if (qc) nxt = take_item();
                            if (item_type(nxt) == T_ATTN) {
                                wait_inputs(nxt);
                                const uint32_t b = qc & 1, dst = sb + b * 32768, fb = bars + B_AFULL + 8 * b, row = item_row(nxt) * 128;
                                mbar_wait(bars + (qc == 0 ? B_GEMPTY : qc == 1 ? B_QFREE : B_AEMPTY + 8 * b), qc == 0 ? gph : qc == 1 ? 0 : a_parity(b));
                                warp_expect_tx(fb, 32768 + 512);
                                warp_tma_load(dst, tile_map, fb, 0, row, G_Q + item_col(nxt), false);
                                warp_tma_load(dst + 16384, tile_map, fb, 64, row, G_Q + item_col(nxt), false);
                                warp_bulk_load(bars + SM_GATE + b * 512, &g_gate[row], 512, fb);
                                qc++;
                            }
                        }
                        if (u == uend) {
                            if (!more) break;
                            more = item_type(nxt) == T_ATTN;
                            m = item_row(nxt); c = item_col(nxt); asc = item_asc(nxt);
                            nu = more ? 2 * m + 2 : 0;
                            uend = nu + ((more ? m < 2 : pv_grp >= 0) ? 3 : 0);
                            ureq = 2 * max(m - 2 - (asc & m), 0);
                            ufetch = !more ? -1 : m ? 2 * m : uend;
                            u = -1;
                            continue;
                        }
                        int grp = pv_grp, row = pv_row;
                        int shared = pv_shared;
                        if (u >= nu) {
                            if (u == nu + 1) pv_grp = -1;
                            else if (peer_longer) { grp = -1; shared = 0; }
                            else continue;
                        } else {
                            const int j = asc ? u >> 1 : m - (u >> 1);
                            if (u & 1) {
                                pv_grp = G_V + c; pv_row = j * 128; pv_shared = (m | 1) - j;
                                peer_longer = asc & ~m & 1;
                                if (u == nu - 1 && (m & 1) && item_type(nxt) == T_END) mbar_arrive_cluster_n_if(lane == 0, bars0 + B_WANT, 2);
                                if (grp < 0) continue;
                            } else {
                                if (u == ureq) request();
                                grp = G_K + c; row = j * 128; shared = (m | 1) - j;
                            }
                        }
                        uint32_t fb = bars + B_AFULL + 16 + 8 * kv, mine = sb + SM_KV + kv * 32768 + prank * 16384;
                        int c_mine = prank * 64;
                        asm volatile("" : "+r"(mine), "+r"(fb), "+r"(row), "+r"(grp), "+r"(c_mine));
                        mbar_wait(need_g ? bars + B_GEMPTY + 8 + 8 * kv : fb + B_AEMPTY - B_AFULL, need_g ? gph : kvph);
                        warp_expect_tx(fb, grp < 0 ? 0 : 32768);
                        if (shared) {
                            warp_tma_load_pair(mine, tile_map, fb, c_mine, row, grp, shared == 1);
                        } else if (grp >= 0) {
                            warp_tma_load(mine, tile_map, fb, c_mine, row, grp, true);
                            warp_tma_load(mine + 16384 - prank * 32768, tile_map, fb, 64 - c_mine, row, grp, true);
                        } else {
                            mbar_arrive_cluster_n_if(lane < 2, map_cta(fb, lane & 1) + B_AEMPTY - B_AFULL, 8);
                        }
                        if (kv == 2) need_g = false;
                        if (++kv == 4) { kv = 0; kvph ^= 1; }
                    }
                }
                if (!qc) request();
                const int it = take_item();
                int nk = 0;
                if (item_type(it) == T_OUT) {
                    const int m = item_row(it), c = item_col(it), half = c & 1;
                    nk = 80;
                    for (int k = 0; k < nk; k++) {
                        if (k == K_SPLIT) nk = 2 * TRIPLES + (take_item() & 127);
                        const int kn = k + 2 * TRIPLES - nk, first = kn >= 0 && !(kn & 1);
                        const int s = kn >= 0 ? WIDE + (3 * kn + 1) / 2 : half ? WIDE - 1 - k : k;
                        const uint32_t sa = prm.ostep[s], sa2 = prm.ostep[s + first], sw = prm.ostep[s - (kn >= 0 && !first ? prank : 0)];
                        const uint32_t need = 1u << (sa >> 1 & 31) | 1u << (sa2 >> 1 & 31);
                        for (unsigned n = 0; need & ~inputs_seen(sa >> 6, n);) {}
                        const uint32_t st = k & 3;
                        uint32_t dst = sb + st * GST_BYTES, fb = bars + B_GFULL + 8 * st;
                        uint32_t dstb = dst + 16384 + (first ? 0 : prank * 16384), skipb = first && (kn >> 1 & 1) != prank;
                        int a0 = (sa & 1) * 64, a1 = m * 128, a2 = (sa >> 1) + (sa < 64 ? G_CTX : G_LOC - 32);
                        int b1 = (sw & 63) * 64, b2 = (c >> 1) * 4 + 2 * (kn >= 0 ? half : half ^ prank);
                        const CUtensorMap* mb = &prm.m[sw >= 64 ? M_WOB : M_WO];
                        asm volatile("" : "+r"(dst), "+r"(fb), "+r"(dstb), "+r"(skipb), "+r"(a0), "+r"(a1), "+r"(a2), "+r"(b1), "+r"(b2), "+l"(mb));
                        if (k < 4) {
#pragma unroll 1
                            for (uint32_t i = 0, b = (3 * st) >> 1; i < 3; i++, b++) mbar_wait(bars + (i == 2 ? B_QFREE : B_AEMPTY + 8 * b), i == 2 ? 0 : a_parity(b));
                            mbar_arrive_cluster_if(lane == 0, bars_peer + B_XFREE + 8 * st);
                            mbar_wait(bars + B_XFREE + 8 * st, 0);
                        }
                        mbar_wait(bars + B_GEMPTY + 8 * st, gph);
                        warp_expect_tx(fb, GST_BYTES);
                        warp_tma_load(dst, tile_map, fb, a0, a1, a2, true);
                        if (!skipb) warp_tma_load_pair(dstb, mb, fb, 0, b1, b2, false);
                        if (first) warp_tma_load(dst + 32768, tile_map, fb, (sa2 & 1) * 64, a1, G_CTX + (sa2 >> 1), true);
                        if (k < K_SPLIT && lane == 0 && !prank)
                            asm volatile("st.relaxed.gpu.global.u32 [%0], %1;" :: "l"(&g_sync.step[0][0] + m * 4 + c), "r"(k) : "memory");
                        if (k == K_MEET) request();
                        if ((uint32_t)(k - K_FETCH) < (3 * TRIPLES + 1) / 2) {
                            const uint32_t g = prm.ostep[79 - 2 * (k - K_FETCH)] >> 1;
                            warp_prefetch((const char*)g_scr + (uint32_t)((G_CTX + g) * (SEQ * 256) + m * 32768 + c * 4096), 4096);
                            warp_prefetch(prm.wo + (uint32_t)(g * 262144 + (m * 8 + c) * 2048), 2048);
                        }
                        if (st == 3) gph ^= 1;
                    }
                    for (unsigned n = 0; ~inputs_seen(0, n) || inputs_seen(1, n) != 255;) {}
                }
#pragma unroll 1
                for (uint32_t st = 0; st < 4; st++) { mbar_wait(bars + B_GEMPTY + 8 * st, gph ^ (st < (nk & 3))); mbar_wait(bars + B_AEMPTY + 16 + 8 * st, a_parity(2 + st)); }
                unsigned left = 0;
                if (lane == 0) asm volatile("atom.relaxed.gpu.global.add.u32 %0, [%1], 1;" : "=r"(left) : "l"(&g_sync.done) : "memory");
                if (__shfl_sync(0xffffffffu, left, 0) == NCTA - 1)
#pragma unroll 1
                    for (uint32_t i = lane * 8; i < sizeof(Sync); i += 256) *(unsigned long long*)((char*)&g_sync + i) = 0;
            }
        } else if (warp <= 2) {
            if (blockIdx.x < SEQ / 16) {
                const uint32_t r0 = 16 * blockIdx.x + 8 * (warp - 1), gbuf = bars + SM_GATE + 4 * (r0 & 15);
                float z[4];
#pragma unroll 1
                for (uint32_t i = 0; i < 8; i++) {
                    const uint32_t off = (i & 3) * 512 + lane * 16;
                    const uint4* xp = (const uint4*)((const char*)prm.x + ((r0 + (i & 4)) * 2048 + off));
                    const uint4 wv = __ldg((const uint4*)((const char*)prm.gate_w + off));
                    uint4 xv[4];
#pragma unroll
                    for (int r = 0; r < 4; r++) { xv[r] = __ldg(xp + r * 128); if (!(i & 3)) z[r] = 0.f; }
                    const uint32_t ws[4] = {wv.x, wv.y, wv.z, wv.w};
#pragma unroll
                    for (int e = 0; e < 4; e++)
#pragma unroll
                        for (int r = 0; r < 4; r++) {
                            const uint32_t xs = e == 0 ? xv[r].x : e == 1 ? xv[r].y : e == 2 ? xv[r].z : xv[r].w;
                            z[r] = fmaf(__uint_as_float(xs << 16), __uint_as_float(ws[e] << 16), z[r]);
                            z[r] = fmaf(__uint_as_float(xs & 0xffff0000u), __uint_as_float(ws[e] & 0xffff0000u), z[r]);
                        }
                    if ((i & 3) == 3) {
#pragma unroll
                        for (int o = 16; o > 0; o >>= 1)
#pragma unroll
                            for (int r = 0; r < 4; r++) z[r] += __shfl_xor_sync(0xffffffffu, z[r], o);
                        const float zr = lane & 2 ? (lane & 1 ? z[3] : z[2]) : (lane & 1 ? z[1] : z[0]);
                        asm volatile("st.shared.f32 [%0], %1;" :: "r"(gbuf + 4 * ((i & 4) + (lane & 3))), "f"(1.f / (1.f + __expf(-zr))) : "memory");
                    }
                }
                fence_proxy_async_smem();
                __syncwarp();
                warp_bulk_store((char*)g_gate + 4 * r0, gbuf, 32);
                bulk_commit();
                bulk_wait<0>();
                __syncwarp();
                if (lane == 0) red_add(&g_sync.count[3], 1);
            }
            __syncwarp();
            {
                const int w = warp - 1;
                uint32_t sph = 0, nann = 0;
                int unsent = 0, nunsent = 0;
                bool urgent = false;
                auto announce = [&]() {
                    if (!urgent) return;
                    bulk_wait<0>();
                    __syncwarp();
                    const uint32_t hb = bars + B_HALF + 8 * (nann & 3);
                    if (w == 0) {
                        mbar_arrive_if(lane == 0, hb);
                    } else {
                        mbar_wait(hb, (nann >> 2) & 1);
                        const uint32_t type = item_type(unsent), m = item_row(unsent), c = item_col(unsent);
                        const uint32_t word = type < T_B ? c >> 3 : type == T_B ? 2 : offsetof(Sync, ctx) / 8 + m;
                        const uint32_t bit = type < T_B ? 8 * (c & 7) : type == T_B ? 4 * m : type == T_LOCAL ? 32 + c : c;
                        if (lane < nunsent) red_add((unsigned long long*)((char*)&g_sync + 8 * word), 1ull << bit);
                        __syncwarp();
                    }
                    nann++;
                    nunsent = 0; urgent = false;
                };
                int held = first_item(), it;
                bool qfree = false;
                do {
                    if (!__all_sync(0xffffffffu, mbar_test(bars + B_IFULL + 8 * (qn % QDEPTH), (qn / QDEPTH) & 1))) announce();
                    it = __shfl_sync(0xffffffffu, next_item(lane == 0), 0);
                    const int itype = item_type(it);
                    const bool keep_held = itype == T_LOCAL && (item_type(held) != T_B || (it & ITEM_READY));
                    if (itype >= T_ATTN && held < 0) {
                        urgent = nunsent;
                        mbar_arrive_if(lane == 0 && !qfree, bars + B_QFREE);
                        qfree = true;
                    }
#pragma unroll 1
                    for (int pass = held < 0 || keep_held; pass < 2; pass++) {
                        if (pass && (itype < T_OUT || itype == T_END)) break;
                        const int cur = pass ? it : held, type = item_type(cur), m = item_row(cur), c = item_col(cur);
                        const bool local = type == T_LOCAL;
                        const int grp = pass ? (local ? G_LOC : G_CTX) + c : type * 32 + 2 * c;
#pragma unroll 1
                        for (int i = 0; i < 4 - 2 * pass; i++) {
                            const int b = i & 1;
                            const bool alt = i >= 2 && itype == T_ATTN;
                            const uint32_t full = bars + (alt ? B_ALT + 8 * w : B_SFULL + 16 * w + 8 * b), par = alt ? 0 : sph;
                            if (i == 3 - 2 * pass || !__all_sync(0xffffffffu, mbar_test(full, par))) announce();
                            mbar_wait(full, par);
                            fence_proxy_async_smem();
                            warp_tma_store(&prm.m[local ? M_SCR_LOQ : M_SCR_ST], sb + (alt ? 32768 : SM_STAGING) + w * 16384 + b * 8192,
                                         local ? b * 128 + w * 64 : b * 64, local ? m * 64 : m * 128 + w * 64, grp + (i >> 1), local || (type < T_B && c < FIRST_PAIR));
                            bulk_commit();
                            bulk_wait_read<0>();
                            __syncwarp();
                            mbar_arrive_if(lane == 0 && !alt, bars + B_SEMPTY + 16 * w + 8 * b);
                            sph ^= b & !alt;
                        }
                        mbar_arrive_if(lane == 0 && !qfree && itype >= T_ATTN, bars + B_QFREE);
                        qfree |= itype >= T_ATTN;
                        if (lane == nunsent) unsent = cur;
                        nunsent++;
                        urgent = nunsent == 32 || !local;
                    }
                    if (!keep_held) held = itype < T_OUT ? it : -1;
                } while (item_type(it) != T_END);
                announce();
                if (item_type(next_item(lane == 0)) == T_OUT) next_item(lane == 0);
            }
        } else {
            if (elect_one()) {
                uint32_t ordy = 0;
                unsigned long long cnt_lo = 0, cnt_hi = 0;
                int late = 0;
                auto refresh = [&]() {
                    if (!late && cnt_lo == 0xccccccccccccccccull && cnt_hi == SEQ / 8) late = 1;
                    asm volatile("ld.acquire.gpu.global.v2.u64 {%0, %1}, [%2];" : "=l"(cnt_lo), "=l"(cnt_hi) : "l"(late ? &g_sync.count[0] : &g_sync.count[2]) : "memory");
                };
                auto inputs_ready = [&](int it) -> bool {
                    const int m = item_row(it), c = item_col(it);
                    if (item_type(it) == T_ATTN) return late && ((c < 16 ? cnt_lo : cnt_hi) >> (4 * (c & 14)) & 255) == 48;
                    return late || (cnt_hi == SEQ / 8 && (cnt_lo >> (4 * m) & 15) == 12 && (cnt_lo >> (4 * max(m - 1, 0)) & 15) == 12);
                };
                auto publish = [&](int it, int step) {
                    const uint32_t slot = qn % QDEPTH;
                    mbar_wait(bars + B_IEMPTY + 8 * slot, ((qn / QDEPTH) & 1) ^ 1);
                    for (uint32_t r = 0; r < 2; r++) {
                        const uint32_t rb = map_cta(bars, r);
                        asm volatile("mbarrier.arrive.expect_tx.shared::cluster.b64 _, [%0], 4;" :: "r"(rb + B_IFULL + 8 * slot) : "memory");
                        asm volatile("st.async.shared::cluster.mbarrier::complete_tx::bytes.u32 [%0], %1, [%2];"
                                     :: "r"(rb + SM_QUEUE + 4 * slot), "r"(it + r * step), "r"(rb + B_IFULL + 8 * slot) : "memory");
                    }
                    qn++;
                };
                int asc = 1;
                int it;
                do {
                    if (rank == 0) {
                        mbar_wait(bars + B_WANT, qn & 1);
                        unsigned i;
                        asm volatile("atom.relaxed.gpu.global.add.u32 %0, [%1], 1;" : "=r"(i) : "l"(&g_sync.next) : "memory");
                        if (cnt_lo != 0x3030303030303030ull || cnt_hi != cnt_lo) refresh();
                        i += NPAIR;
                        const int pit = i < NITEMS ? prm.items[i] : T_END << 13, type = item_type(pit);
                        int step = type == T_LOCAL ? 16 : 1;
                        it = pit + (pit & (step == 1 ? 15 : 0x1f0));
                        if (type == T_ATTN) {
                            if (!asc) { it += 1; step = -1; }
                            it |= asc << 9;
                        }
                        asc = type != T_ATTN || item_row(pit) == 0 || !asc;
                        if (inputs_ready(it)) it |= ITEM_READY;
                        publish(it, step);
                    } else {
                        it = next_item(true);
                    }
                    if ((item_type(it) == T_ATTN || item_type(it) == T_LOCAL) && !(it & ITEM_READY)) {
                        unsigned n = 0;
                        while (!inputs_ready(it)) { refresh(); spin_guard(n); }
                        asm volatile("st.release.cta.shared.u32 [%0], %1;" :: "r"(bars + SM_ORDY + 4), "r"(ordy += 256) : "memory");
                    }
                } while (item_type(it) != T_END);
                if (rank == 0) {
                    mbar_wait(bars + B_WANT, qn & 1);
                    const unsigned i = atomicAdd(&g_sync.next_out, 1u), t = i < 32 ? 31 - i : i - 32;
                    it = i < 64 ? T_OUT << 13 | ((t & 3) * 2 + (i >> 5)) << 4 | (t >> 2) * 2 : T_END << 13;
                    publish(it, 1);
                } else {
                    it = next_item(true);
                }
                if (item_type(it) == T_OUT) {
                    const uint32_t m = item_row(it), half = item_col(it) & 1, tile = m * 2 + (item_col(it) >> 1);
                    unsigned* split = (unsigned*)((char*)g_sync.split + 4 * tile);
                    unsigned long long rdy = 0;
                    int state = rank ? 2 : 0;
                    for (unsigned n = 0; rdy != 0xffffffffffull || state < 2; spin_guard(n)) {
                        if (rdy != 0xffffffffffull) {
                            rdy = ld_acquire((const unsigned long long*)((char*)g_sync.ctx + 8 * m));
                            asm volatile("st.release.cta.shared.u64 [%0], %1;" :: "r"(bars + SM_ORDY), "l"(rdy) : "memory");
                        }
                        unsigned steps = 0;
                        if (state == 1) {
                            steps = ld_acquire(split);
                        } else if (state == 0 && mbar_test(bars + B_WANT, qn & 1)) {
                            state = 1;
                            unsigned seen;
                            asm volatile("atom.acq_rel.gpu.global.exch.b32 %0, [%1], 1;" : "=r"(seen) : "l"(split) : "memory");
                            if (seen) {
                                const unsigned long long v = ld_acquire((const unsigned long long*)((char*)g_sync.step + 8 * tile));
                                const int d = (int)(v >> 32) - (int)v;
                                steps = (WIDE + min(max(half ? d : -d, K_MEET - K_SPLIT), K_SPLIT - K_MEET)) >> 1;
                                atomicExch(split, WIDE - steps);
                            }
                        }
                        if (steps > 1) { publish(T_END << 13 | steps, 0); state = 2; }
                    }
                    if (rank) next_item(true);
                }
                #pragma unroll 1
                for (uint32_t n = qn; n < qn + QDEPTH && rank == 0; n++) mbar_wait(bars + B_IEMPTY + 8 * (n % QDEPTH), ((n / QDEPTH) & 1) ^ 1);
            }
        }
    } else {
        reg_inc<232>();
        const int wg = (warp >> 2) - 1, wq = warp & 3;
        uint32_t gph = 0;
        uint32_t kvn = 0;
        const uint32_t dA = make_desc(sb + wg * 8192, 16);
        uint32_t ti = 0;
        uint32_t sph = 1;
        const uint32_t stg = sb + SM_STAGING + wg * 16384;
        const uint32_t stg_lane = stg + (wq * 16 + (lane & 15)) * 128 + (((lane >> 4) ^ (lane & 7)) << 4);
        auto write_blocks = [&](auto n, uint32_t off, const uint32_t* v) {
            uint32_t a = stg_lane;
            asm volatile("" : "+r"(a));
            a += off;
#pragma unroll
            for (int j = 0; j < decltype(n)::value; j++)
                stmatrix_x4((a ^ (32 * (j & 3))) + (j >> 2) * 8192, v[4 * j], v[4 * j + 1], v[4 * j + 2], v[4 * j + 3]);
        };
        auto release = [&](uint32_t bar) { mbar_arrive_if(lane == 0, bars + bar); };
        const uint32_t bars_lane = map_cta(bars, lane & 1);
        auto release_stage = [&](uint32_t st) { mbar_arrive_cluster_if(lane < 2, bars_lane + B_GEMPTY + 8 * st); };
        auto take_item = [&]() -> int {
            return __shfl_sync(0xffffffffu, next_item(lane == 0, false), 0);
        };
        auto stage_acquire = [&](int b) { mbar_spin(bars + B_SEMPTY + 16 * wg + 8 * b, sph); };
        auto stage_publish = [&](int b) {
            __syncwarp();
            release(B_SFULL + 16 * wg + 8 * b);
        };
        auto stage_chunk = [&](int b, const uint32_t* v) {
            stage_acquire(b);
            write_blocks(std::integral_constant<int, 4>(), b * 8192, v);
            stage_publish(b);
            if (b) sph ^= 1;
        };
        auto publish_pair = [&]() {
            __syncwarp();
            mbar_arrive_if(lane < 2, bars + B_SFULL + 16 * wg + 8 * lane);
            sph ^= 1;
        };
        auto gemm_step = [&](float (&acc)[128], uint32_t dB, int& k) {
            const uint32_t st = k & 3;
            wgmma_wait<0>();
            release_stage((k - 1) & 3);
            mbar_spin(bars + B_GFULL + 8 * st, gph);
            const uint64_t da = full_desc(dA + st * (GST_BYTES >> 4)), db = full_desc(dB + st * (GST_BYTES >> 4));
            wgmma_fence();
#pragma unroll
            for (int kk = 0; kk < 4; kk++) wgmma_ss_n256_tb(acc, da + 2 * kk, db + 128 * kk, 1);
            wgmma_commit();
            gph ^= st == 3;
            k++;
        };
        if (wg == 1) bar_arrive(1, 256);
        int it = first_item();
        while (true) {
            if (item_type(it) <= T_LOCAL) {
                float acc[128];
                uint32_t pk[64];
                bool pending = false;
                bool held_b = false;
                zero_regs(pk);
                const uint32_t dB = make_desc(sb + 16384, 8192);
                do {
                    const int type = item_type(it);
                    if (type == T_LOCAL) {
                        int ln = lane;
                        asm volatile("" : "+r"(ln));
                        const int g = ln >> 2, t = ln & 3, par = wq & 1;
                        const uint32_t hc = (wq >> 1) * 4, pl = sb + (par * 2 + wg) * LOC_PLANE;
                        const uint32_t a16 = (ln & 15) * 128 + (((hc + (ln >> 4)) ^ (ln & 7)) << 4), a8 = (ln & 7) * 128 + (((hc + (ln >> 3)) ^ (ln & 7)) << 4);
                        const bool first0 = 2 * t > g, first1 = 2 * t + 1 > g;
                        const uint32_t fmask = (first0 ? 0xffffu : 0u) | (first1 ? 0xffff0000u : 0u);
                        const bool edge = item_row(it) == 0;
                        uint32_t q[4][2][4], kf[9][4], vf[9][4];
                        float w[8];
                        mbar_spin(bars + B_GFULL, gph);
#pragma unroll
                        for (int u = 0; u < 4; u++) { ldsm_x4(q[u][0], pl + u * 2048 + a16); ldsm_x4(q[u][1], pl + u * 2048 + (a16 ^ 32)); }
#pragma unroll
                        for (int j = 0; j < 8; j++) w[j] = lds_f32(sb + 4 * LOC_PLANE + 4 * (2 * g + par) + 64 * j);
                        __syncwarp();
                        release_stage(0);
                        mbar_spin(bars + B_GFULL + 8, gph);
#pragma unroll
                        for (int n = 0; n < 9; n++) ldsm_x4(kf[n], pl + GST_BYTES + n * 1024 + a8);
                        __syncwarp();
                        release_stage(1);
                        float s[8][2];
#pragma unroll
                        for (int u = 0; u < 4; u++) {
                            float d[3][4];
#pragma unroll
                            for (int nt = 0; nt < 3; nt++) {
                                mma_k16_init(d[nt], q[u][0], kf[2 * u + nt][0], kf[2 * u + nt][1]);
                                mma_k16(d[nt], q[u][1], kf[2 * u + nt][2], kf[2 * u + nt][3]);
                            }
                            if (u == 0 && edge) { d[0][0] = -INFINITY; d[0][1] = -INFINITY; }
                            s[2 * u][0] = first0 ? d[0][0] : d[1][0]; s[2 * u][1] = first1 ? d[0][1] : d[1][1];
                            s[2 * u + 1][0] = first0 ? d[1][2] : d[2][2]; s[2 * u + 1][1] = first1 ? d[1][3] : d[2][3];
                        }
                        mbar_spin(bars + B_GFULL + 16, gph);
#pragma unroll
                        for (int u = 0; u < 4; u++) { ldsm_x4_t(vf[2 * u], pl + 2 * GST_BYTES + u * 2048 + a16); ldsm_x4_t(vf[2 * u + 1], pl + 2 * GST_BYTES + u * 2048 + (a16 ^ 32)); }
                        ldsm_x4_t(vf[8], pl + 2 * GST_BYTES + 8192 + a8);
                        __syncwarp();
                        release_stage(2);
                        float x[8];
#pragma unroll
                        for (int j = 0; j < 8; j++) x[j] = fmaxf(s[j][0], s[j][1]);
#pragma unroll
                        for (int o = 1; o < 4; o *= 2)
#pragma unroll
                            for (int j = 0; j < 8; j++) x[j] = fmaxf(x[j], __shfl_xor_sync(0xffffffffu, x[j], o));
#pragma unroll
                        for (int j = 0; j < 8; j++) {
                            const float n = x[j] * -LOC_SCALE;
                            s[j][0] = ex2(fmaf(s[j][0], LOC_SCALE, n)); s[j][1] = ex2(fmaf(s[j][1], LOC_SCALE, n));
                            x[j] = s[j][0] + s[j][1];
                        }
#pragma unroll
                        for (int o = 1; o < 4; o *= 2)
#pragma unroll
                            for (int j = 0; j < 8; j++) x[j] += __shfl_xor_sync(0xffffffffu, x[j], o);
                        mbar_spin(bars + B_GFULL + 24, gph);
                        release_stage(3);
                        it = take_item();
                        uint32_t ob[4][8];
#pragma unroll
                        for (int u = 0; u < 4; u++) {
                            const float r0 = rcp(x[2 * u]), r1 = rcp(x[2 * u + 1]), f0 = fmaf(-w[2 * u], r0, r0), f1 = fmaf(-w[2 * u + 1], r1, r1);
                            const uint32_t p0 = pack_bf16(s[2 * u][0] * f0, s[2 * u][1] * f0), p1 = pack_bf16(s[2 * u + 1][0] * f1, s[2 * u + 1][1] * f1);
                            const uint32_t pa[4] = {p0 & fmask, 0, p0 & ~fmask, p1 & fmask};
#pragma unroll
                            for (int c = 0; c < 4; c++) {
                                float ol[4];
                                mma_k16_init(ol, pa, vf[2 * u + (c >> 1)][2 * (c & 1)], vf[2 * u + (c >> 1)][2 * (c & 1) + 1]);
                                mma_k8(ol, 0, p1 & ~fmask, u < 3 ? vf[2 * u + 2 + (c >> 1)][2 * (c & 1)] : vf[8][c]);
                                ob[u][2 * c] = pack_bf16(ol[0], ol[1]);
                                ob[u][2 * c + 1] = pack_bf16(ol[2], ol[3]);
                            }
                        }
                        stage_acquire(0); stage_acquire(1);
#pragma unroll
                        for (int u = 0; u < 4; u++) {
                            stmatrix_x4(stg + par * 8192 + u * 2048 + a16, ob[u][0], ob[u][1], ob[u][2], ob[u][3]);
                            stmatrix_x4(stg + par * 8192 + u * 2048 + (a16 ^ 32), ob[u][4], ob[u][5], ob[u][6], ob[u][7]);
                        }
                        publish_pair();
                        bar_sync(4, 256);
                        gph ^= 1;
                        continue;
                    }
                    mbar_spin(bars + B_GFULL, gph);
                    bool more;
                    do {
                        wgmma_fence();
                        wgmma_ss_n256_tb_init(acc, full_desc(dA), full_desc(dB));
#pragma unroll
                        for (int kk = 1; kk < 4; kk++) wgmma_ss_n256_tb(acc, full_desc(dA) + 2 * kk, full_desc(dB) + 128 * kk, 1);
                        wgmma_commit();
                        const int nk = item_type(it) == T_K || item_type(it) == T_V ? 8 : 16;
                        int k = 1;
                        do {
                            if (pending) {
                                const int kf = k - 1 - wg;
                                if (kf == 0) stage_chunk(0, pk);
                                else if (kf == 1) stage_chunk(1, pk + 16);
                                else if (kf == 3) stage_chunk(0, pk + 32);
                                else if (kf == 4) stage_chunk(1, pk + 48);
                            }
                            gemm_step(acc, dB, k);
                        } while (k < nk);
                        held_b = item_type(it) == T_B;
                        const bool is_q = item_type(it) == T_Q;
                        it = take_item();
                        more = item_type(it) < T_LOCAL;
                        if (more) mbar_spin(bars + B_GFULL, gph);
                        wgmma_wait<0>();
                        fence_regs(acc);
                        release_stage(3);
                        if (is_q) {
#pragma unroll
                            for (int j = 0; j < 128; j++) acc[j] *= SM_SCALE;
                        }
#pragma unroll
                        for (int j = 0; j < 64; j++) pk[j] = pack_bf16(acc[2 * j], acc[2 * j + 1]);
                        pending = true;
                    } while (more);
                } while (item_type(it) < T_LOCAL || (item_type(it) == T_LOCAL && (!held_b || (it & ITEM_READY))));
                if (pending) {
                    stage_acquire(0); stage_acquire(1);
                    write_blocks(std::integral_constant<int, 8>(), 0, pk);
                    const bool borrow = item_type(it) == T_ATTN;
                    if (borrow) {
                        mbar_spin(bars + B_GEMPTY, gph ^ 1); mbar_spin(bars + B_GEMPTY + 8, gph ^ 1);
                    } else {
                        publish_pair();
                        stage_acquire(0); stage_acquire(1);
                    }
                    write_blocks(std::integral_constant<int, 8>(), borrow ? 32768 - SM_STAGING : 0, pk + 32);
                    publish_pair();
                    mbar_arrive_if(lane == 0 && borrow, bars + B_ALT + 8 * wg);
                }
                if (item_type(it) == T_END) { it = take_item(); break; }
            } else {
                float o[64], s[64];
                uint32_t pa[32], pb[32];
                zero_regs(o); zero_regs(s); zero_regs(pa);
                float n0 = 0.f, n1 = 0.f;
                int shifted = 0;
                float l0 = 1.f, l1 = 1.f, f0 = 0.f, f1 = 0.f, g0 = 0.f, g1 = 0.f;
                uint32_t has_pv = 0;
                int first = 0;
                int pending = 0;
                const uint32_t dK = make_desc(sb + SM_KV, 16), dV = make_desc(sb + SM_KV, 16384);
                const uint32_t lane_off = bars_lane - bars + B_AEMPTY - B_AFULL;
                int cur = 0;
                uint32_t qoff = 0;
                const int row = wg * 64 + wq * 16 + (lane >> 2);
                const float thr = (row & 63) - (lane & 3) * 2;
                int peek = 0;
                auto kv_wait = [&](uint32_t n) { mbar_spin(bars + B_AFULL + 16 + 8 * (n & 3), (n >> 2) & 1); };
                auto kv_release = [&](uint32_t n) { mbar_arrive_cluster_if(lane < 2, bars_lane + B_AEMPTY + 16 + 8 * (n & 3)); };
                struct Slot { uint32_t bar, par, off; } slot[4];
                auto align = [&]() {
#pragma unroll
                    for (uint32_t i = 0; i < 4; i++) {
                        const uint32_t n = kvn + (i == 1 ? has_pv : i);
                        slot[i].bar = bars + B_AFULL + 16 + 8 * (n & 3); slot[i].par = (n >> 2) & 1; slot[i].off = (n & 3) * 2048;
                    }
                };
                align();
                auto scale_o = [&]() {
#pragma unroll
                    for (int j = 0; j < 16; j++) { o[4 * j] *= f0; o[4 * j + 1] *= f0; o[4 * j + 2] *= f1; o[4 * j + 3] *= f1; }
                };
                auto pack_o = [&](uint32_t (&v)[32]) {
#pragma unroll
                    for (int j = 0; j < 32; j++) v[j] = pack_bf16(o[2 * j], o[2 * j + 1]);
                };
                auto scales = [&]() { f0 = g0 * rcp(quad_sum(l0)); f1 = g1 * rcp(quad_sum(l1)); };
                auto step = [&](auto even, uint32_t (&pin)[32], uint32_t (&pout)[32], bool fresh, bool diag, bool last) {
                    constexpr bool EVEN = decltype(even)::value;
                    Slot& sk = slot[EVEN ? 0 : 2];
                    Slot& sv = slot[EVEN ? 1 : 3];
                    kvn += EVEN ? 1 + has_pv : 2;
                    mbar_spin(sk.bar, sk.par);
                    bar_sync(1 + wg, 256);
                    qk_gemm(s, dA + qoff, dK + sk.off);
                    if (EVEN && fresh) {
                        scales();
                        g0 = lds_f32(bars + SM_GATE + (ti & 1) * 512 + 4 * row); g1 = lds_f32(bars + SM_GATE + (ti & 1) * 512 + 4 * row + 32);
                        ti++;
                        n0 = 0.f; n1 = 0.f; l0 = 0.f; l1 = 0.f;
                        shifted = 0;
                        if (has_pv) { stage_acquire(0); stage_acquire(1); }
                    }
                    if (!EVEN && pending) {
                        pack_o(pout);
                        write_blocks(std::integral_constant<int, 8>(), 0, pout);
                        publish_pair();
                    }
                    if (last)
                        asm volatile("{\n.reg .pred P, Q;\n"
                                     "mbarrier.test_wait.parity.shared::cta.b64 Q, [%1], %2;\n"
                                     "mbarrier.test_wait.parity.shared::cta.b64 P, [%3], %4;\n"
                                     "ld.shared.u32 %0, [%5];\n"
                                     "@!Q or.b32 %0, %0, 0x10000;\n"
                                     "@!P mov.u32 %0, -1;\n}\n"
                                     : "=r"(peek) : "r"(bars + B_AFULL + 8 * (ti & 1)), "r"((ti >> 1) & 1), "r"(bars + B_IFULL + 8 * (qn % QDEPTH)),
                                       "r"((qn / QDEPTH) & 1), "r"(bars + SM_QUEUE + 4 * (qn % QDEPTH)) : "memory");
                    mbar_spin(sv.bar, sv.par);
                    pv_gemm(o, pin, dV + sv.off, EVEN || !first);
                    bar_arrive(2 - wg, 256);
                    sk.par ^= 1; sv.par ^= 1;
                    wgmma_wait<1>();
                    fence_regs(s);
                    mbar_arrive_cluster_if(lane < 2 && (!EVEN || has_pv), sk.bar + lane_off);
                    mbar_arrive_if(lane == 0 && last, bars + B_AEMPTY + 8 * ((ti - 1) & 1));
                    float r0, r1, x0 = n0, x1 = n1;
#pragma unroll 1
                    for (int mask = diag, redone = 0;; mask = 0, redone = 1) {
                        if (mask | shifted) {
                            if (mask) causal_mask(s, thr, wg);
                            if (shifted) shift_rows(s, x0, x1);
                        }
                        exp_pack(pout, s, r0, r1);
                        if (!__any_sync(0xffffffffu, fmaxf(r0, r1) >= SUM_LIMIT || (EVEN && fresh && !(lane & 3) && !(fminf(s[0], s[2]) >= -REF_RANGE))) || redone) break;
                        row_max(s, x0, x1);
                        if (!(EVEN && fresh)) { x0 = fmaxf(x0, 0.f); x1 = fmaxf(x1, 0.f); }
                        float a0 = ex2(-x0), a1 = ex2(-x1);
                        n0 += x0; n1 += x1;
                        shifted = 1;
                        if (EVEN && fresh) { a0 = 1.f; a1 = 1.f; }
                        l0 *= a0; l1 *= a1;
                        wgmma_wait<0>();
                        fence_regs(o);
#pragma unroll
                        for (int q = 0; q < 16; q++) { o[4 * q] *= a0; o[4 * q + 1] *= a0; o[4 * q + 2] *= a1; o[4 * q + 3] *= a1; }
                    }
                    l0 += r0; l1 += r1;
                    wgmma_wait<0>();
                    fence_regs(o);
                    fence_regs(pin);
                    mbar_arrive_cluster_if(lane < 2, sv.bar + lane_off);
                };
                auto copy_p = [&]() {
#pragma unroll
                    for (int j = 0; j < 32; j++) pa[j] = __float_as_uint(__uint_as_float(pb[j]) + __uint_as_float(prm.zero));
                };
                int rem = 0;
                mbar_spin(bars + B_AFULL + 8 * (ti & 1), (ti >> 1) & 1);
                while (true) {
                    const bool fresh = rem == 0;
                    if (fresh) {
                        if (has_pv) {
                            const int seen = __shfl_sync(0xffffffffu, peek, 0);
                            if (seen >= 0) {
                                mbar_arrive_cluster_if(lane == 0, bars0 + B_IEMPTY + 8 * (qn % QDEPTH));
                                qn++;
                                it = seen & 0xffff;
                            } else {
                                it = take_item();
                            }
                            if (item_row(cur) < 2 || item_type(it) != T_ATTN) break;
                            if (seen & 0x10000) mbar_spin(bars + B_AFULL + 8 * (ti & 1), (ti >> 1) & 1);
                        }
                        cur = it;
                        qoff = (ti & 1) * 2048;
                    }
                    const bool last = fresh ? item_row(cur) == 0 : rem == 1;
                    step(std::true_type(), pa, pb, fresh, item_asc(cur) ? last : fresh, last);
                    first = fresh;
                    if (fresh) {
                        pending = has_pv; has_pv = 1;
                        if (!pending) { kvn -= 2; align(); kvn += 2; slot[0].par ^= 1; slot[1].par ^= 1; }
                        else scale_o();
                        rem = item_row(cur);
                        if (rem == 0) {
                            copy_p();
                            continue;
                        }
                    } else if (--rem == 0) {
                        copy_p();
                        const Slot t0 = slot[0], t1 = slot[1];
                        slot[0] = slot[2]; slot[1] = slot[3]; slot[2] = t0; slot[3] = t1;
                        continue;
                    }
                    step(std::false_type(), pb, pa, false, item_asc(cur) && rem == 1, rem == 1);
                    pending = 0; first = 0;
                    rem--;
                }
                const uint32_t skip = item_asc(cur) & ~item_row(cur) & 1;
                kvn += skip;
                const bool end = item_type(it) == T_END;
#pragma unroll 1
                for (int pass = pending ? 0 : 1; pass < 2; pass++) {
                    if (pass) {
                        kv_wait(kvn);
                        pv_gemm(o, pa, dV + (kvn & 3) * 2048, !first);
                        scales();
                        stage_acquire(0); stage_acquire(1);
                        if (end) it = take_item();
                        wgmma_wait<0>();
                        fence_regs(o);
                        kv_release(kvn);
                        kvn += 1 + skip;
                        scale_o();
                    }
                    pack_o(pb);
                    write_blocks(std::integral_constant<int, 8>(), 0, pb);
                    publish_pair();
                }
                if (end) break;
            }
        }
        if (item_type(it) == T_OUT) {
            float acc[128];
            const uint32_t dB = make_desc(sb + 16384, 8192);
            mbar_spin(bars + B_GFULL, gph);
            wgmma_fence();
            wgmma_ss_n256_tb_init(acc, full_desc(dA), full_desc(dB));
#pragma unroll
            for (int kk = 1; kk < 4; kk++) wgmma_ss_n256_tb(acc, full_desc(dA) + 2 * kk, full_desc(dB) + 128 * kk, 1);
            wgmma_commit();
            uint32_t ln;
            asm volatile("mov.u32 %0, %%laneid;" : "=r"(ln));
            const uint32_t slot = (it & 127) * 32768 + (wg * 128 + wq * 32 + ln) * 16;
            char* const mine = (char*)g_part + slot;
            int k = 1, nk = 80;
            do {
                if (k == K_MEET - 5) {
#pragma unroll
                    for (int j = 0; j < 8; j++) st_b128(mine + j * 4096, 0, 0, 0, 0);
                    __syncwarp();
                }
                if (k == K_SPLIT) nk = take_item() & 127;
                gemm_step(acc, dB, k);
            } while (k < nk);
            float lo[64];
            uint32_t pk[32];
            char* const other = (char*)g_part + (slot ^ (16 * 32768));
            auto fetch_other = [&]() {
#pragma unroll
                for (int j = 0; j < 8; j++) ld_b128(other + j * 4096, pk[4 * j], pk[4 * j + 1], pk[4 * j + 2], pk[4 * j + 3]);
            };
            auto triple = [&](auto first) {
                const uint32_t s0 = k & 3, s1 = (k + 1) & 3, o0 = s0 * (GST_BYTES >> 4), o1 = s1 * (GST_BYTES >> 4);
                wgmma_wait<0>();
                mbar_arrive_cluster_if(ln < (decltype(first)::value ? 2 : 4), bars_lane + B_GEMPTY + 8 * ((k - 1 - (ln >> 1)) & 3));
                mbar_spin(bars + B_GFULL + 8 * s0, gph);
                gph ^= s0 == 3;
                wgmma_fence();
#pragma unroll
                for (int kk = 0; kk < 4; kk++) {
                    if (decltype(first)::value && kk == 0) wgmma_ss_n128_tb_init(lo, full_desc(dA + o0), full_desc(dB + o0));
                    else wgmma_ss_n128_tb(lo, full_desc(dA + o0) + 2 * kk, full_desc(dB + o0) + 128 * kk, 1);
                }
                mbar_spin(bars + B_GFULL + 8 * s1, gph);
                gph ^= s1 == 3;
                wgmma_fence();
#pragma unroll
                for (int kk = 0; kk < 4; kk++) wgmma_ss_n128_tb(lo, full_desc(dA + o0 + 2048) + 2 * kk, full_desc(dB + o1 + 1024) + 128 * kk, 1);
#pragma unroll
                for (int kk = 0; kk < 4; kk++) wgmma_ss_n128_tb(lo, full_desc(dA + o1) + 2 * kk, full_desc(dB + o1) + 128 * kk, 1);
                wgmma_commit();
                k += 2;
            };
            triple(std::true_type());
            fence_regs(acc);
#pragma unroll
            for (int j = 0; j < 8; j++) {
                uint32_t v[4];
#pragma unroll
                for (int i = 0; i < 4; i++) v[i] = pack_bf16(acc[64 + 8 * j + 2 * i], acc[65 + 8 * j + 2 * i]);
                if (j == 4) triple(std::false_type());
                st_b128(mine + j * 4096, ~v[0], v[1], v[2], v[3]);
            }
            triple(std::false_type());
            while (true) {
                fetch_other();
                bool miss = false;
#pragma unroll
                for (int j = 0; j < 8; j++) miss |= pk[4 * j] == 0;
                if (!__any_sync(0xffffffffu, miss)) break;
                while (__any_sync(0xffffffffu, pk[28] == 0)) ld_b128(other + 7 * 4096, pk[28], pk[29], pk[30], pk[31]);
            }
#pragma unroll
            for (int j = 0; j < 32; j++) {
                const uint32_t v = j & 3 ? pk[j] : ~pk[j];
                acc[2 * j] += __uint_as_float(v << 16); acc[2 * j + 1] += __uint_as_float(v & 0xffff0000u);
                asm volatile("" : "+f"(acc[2 * j]), "+f"(acc[2 * j + 1]) :: "memory");
            }
            stage_acquire(0); stage_acquire(1);
            wgmma_wait<0>();
            fence_regs(lo);
            mbar_arrive_cluster_if(ln < 4, bars_lane + B_GEMPTY + 8 * ((k - 1 - (ln >> 1)) & 3));
#pragma unroll
            for (int j = 0; j < 32; j++)
                pk[j] = pack_bf16(acc[2 * j] + lo[2 * j], acc[2 * j + 1] + lo[2 * j + 1]);
            write_blocks(std::integral_constant<int, 8>(), 0, pk);
            __syncwarp();
            uint4* dst = (uint4*)((char*)prm.out + (uint32_t)((item_row(it) * 128 + wg * 64 + wq * 16 + (ln >> 4)) * 2048 + item_col(it) * 256 + (ln & 15) * 16));
#pragma unroll
            for (int j = 0; j < 8; j++) {
                const int r = 2 * j + (ln >> 4);
                uint4 v;
                asm volatile("ld.shared.v4.u32 {%0, %1, %2, %3}, [%4];" : "=r"(v.x), "=r"(v.y), "=r"(v.z), "=r"(v.w)
                             : "r"(stg + wq * 2048 + r * 128 + (ln & 8) * 1024 + (((ln & 7) ^ (r & 7)) << 4)) : "memory");
                dst[j * 256] = v;
            }
        }
    }
}

typedef CUresult (*EncodeFn)(CUtensorMap*, CUtensorMapDataType, cuuint32_t, void*, const cuuint64_t*, const cuuint64_t*,
                             const cuuint32_t*, const cuuint32_t*, CUtensorMapInterleave, CUtensorMapSwizzle,
                             CUtensorMapL2promotion, CUtensorMapFloatOOBfill);

void encode3(EncodeFn fn, CUtensorMap* m, const void* ptr, uint64_t d0, uint64_t d1, uint64_t d2, uint64_t s1, uint64_t s2,
             uint32_t b0, uint32_t b1, uint32_t b2) {
    cuuint64_t dims[3] = {d0, d1, d2};
    cuuint64_t strides[2] = {s1, s2};
    cuuint32_t box[3] = {b0, b1, b2};
    cuuint32_t es[3] = {1, 1, 1};
    fn(m, CU_TENSOR_MAP_DATA_TYPE_BFLOAT16, 3, const_cast<void*>(ptr), dims, strides, box, es, CU_TENSOR_MAP_INTERLEAVE_NONE,
       CU_TENSOR_MAP_SWIZZLE_128B, CU_TENSOR_MAP_L2_PROMOTION_NONE, CU_TENSOR_MAP_FLOAT_OOB_FILL_NONE);
}
void map_act(EncodeFn fn, CUtensorMap* m, const void* p, int rows, int cols, int box_rows) {
    encode3(fn, m, p, cols, rows, 1, (uint64_t)cols * 2, (uint64_t)cols * rows * 2, 64, box_rows, 1);
}
void map_wgt(EncodeFn fn, CUtensorMap* m, const void* p, int K, int N) {
    encode3(fn, m, p, 64, K, N / 64, (uint64_t)N * 2, 128, 64, 64, 2);
}

void build_schedule(Params& p) {
    int n = 0;
    auto add = [&](int type, int col, int row) { p.items[n++] = (uint16_t)(type << 13 | col << 4 | row); };
    auto add_qkv = [&](int c) {
        for (int m = 0; m < 8; m++) add(T_Q, c, m);
        for (int m = 0; m < 8; m++) add(T_K, c, m);
        for (int m = 0; m < 8; m++) add(T_V, c, m);
    };
    int ldist = 200, ldist2 = 260, lstep = 8, beta = 26, tail = 32, late = 6, early = 8, epos = 100;
    int order[16] = {6, 7, 8, 9, 10, 11, 12, 13, 14, 15, 5, 4, 3, 2, 1, 0};
    uint16_t proj[480];
    for (int m = 0; m < 8; m++) for (int c = 0; c < 12; c++) add(T_B, c, m);
    for (int c = 0; c < 16; c++) add_qkv(c);
    for (int i = 0; i < 480; i++) proj[i] = p.items[i];
    n = 0;
    for (int i = 0, l = 0; i < 480; i++) {
        p.items[n++] = proj[i];
        for (; l < 64 && i >= (l < 40 ? ldist + lstep * l / 8 : ldist2 + lstep * (l - 40) / 8); l++) add(T_LOCAL, l & 3, l >> 2);
    }
    const int a0 = n;
    for (int key = 0; key < 4000; key++)
        for (int r = 0; r < 32; r++)
            for (int j = 7; j >= 0; j--)
                if ((j ? (7 - j) * 40 + r * beta : 3999) == key) add(T_ATTN, 2 * order[r >> 1] + (r & 1), j);
    int t0 = n;
    for (int work = 0; work < 32 * 136 * tail / 100;) work += 4 * (p.items[--t0] & 15) + 3;
    for (int i = t0 + 1; i < n; i++)
        for (int j = i; j > t0 && (p.items[j] & 15) > (p.items[j - 1] & 15); j--) { const uint16_t t = p.items[j]; p.items[j] = p.items[j - 1]; p.items[j - 1] = t; }
    for (int r = early - 1; r >= 0; r--) {
        const uint16_t t = p.items[n - 32 + early - 1];
        for (int j = n - 32 + early - 1; j > n - epos; j--) p.items[j] = p.items[j - 1];
        p.items[n - epos] = t;
    }
    for (int moved = 0; moved < 2 && late >= 0; moved++)
        for (int i = a0; i < n; i++)
            if (p.items[i] == (T_ATTN << 13 | (2 * order[15] + moved) << 4 | late)) {
                for (int j = i; j + 1 < n; j++) p.items[j] = p.items[j + 1];
                p.items[n - 1] = (uint16_t)(T_ATTN << 13 | (2 * order[15] + moved) << 4 | late);
                break;
            }
    for (int s = 0, lo = 0, hi = WIDE - 1; s < 80; s++) {
        const int r = s / 2, g = r < 8 ? 32 + r : 2 * order[r / 2 - 4] + (r & 1);
        p.ostep[s >= WIDE ? s : r & 1 ? hi-- : lo++] = (uint8_t)(2 * g + (s & 1));
    }
}

void build_params(Params& p, void* const* d_in, void* d_out) {
    void* fnp = nullptr;
    cudaDriverEntryPointQueryResult qr;
    cudaGetDriverEntryPoint("cuTensorMapEncodeTiled", &fnp, cudaEnableDefault, &qr);
    EncodeFn fn = (EncodeFn)fnp;
    void* scr = nullptr;
    cudaGetSymbolAddress(&scr, g_scr);
    map_act(fn, &p.m[M_X], d_in[0], SEQ, 1024, 128);
    map_act(fn, &p.m[M_C], d_in[1], SEQ, 512, 128);
    map_wgt(fn, &p.m[M_WQ], d_in[2], 1024, 4096);
    map_wgt(fn, &p.m[M_WUK], d_in[3], 512, 4096);
    map_wgt(fn, &p.m[M_WUV], d_in[4], 512, 4096);
    map_wgt(fn, &p.m[M_WO], d_in[5], 4096, 1024);
    map_wgt(fn, &p.m[M_WQKV], d_in[7], 1024, 3072);
    map_wgt(fn, &p.m[M_WOB], d_in[8], 1024, 1024);
    encode3(fn, &p.m[M_SCR_LD], scr, 128, SEQ, G_TOTAL, 256, (uint64_t)SEQ * 256, 64, 128, 1);
    encode3(fn, &p.m[M_SCR_LOC], scr, 256, SEQ / 2, G_TOTAL, 512, (uint64_t)SEQ * 256, 64, 72, 1);
    encode3(fn, &p.m[M_SCR_LOQ], scr, 256, SEQ / 2, G_TOTAL, 512, (uint64_t)SEQ * 256, 64, 64, 1);
    encode3(fn, &p.m[M_SCR_ST], scr, 128, SEQ, G_TOTAL, 256, (uint64_t)SEQ * 256, 64, 64, 1);
    p.x = (const __nv_bfloat16*)d_in[0];
    p.gate_w = (const __nv_bfloat16*)d_in[9];
    p.zero = 0;
    p.wo = (const char*)d_in[5];
    p.out = (__nv_bfloat16*)d_out;
    build_schedule(p);
}

}

extern "C" void kernel_launch(void* const* d_in, const int* in_sizes, int n_in, void* d_out, int out_size) {
    (void)in_sizes; (void)n_in; (void)out_size;
    Params p;
    build_params(p, d_in, d_out);
    cudaFuncSetAttribute(fused_kernel, cudaFuncAttributeMaxDynamicSharedMemorySize, SM_TOTAL);
    fused_kernel<<<NCTA, 384, SM_TOTAL>>>(p);
}
```

```cpp
#include <cuda_runtime.h>
#include <cuda_bf16.h>
#include <cuda.h>
#include <stddef.h>
#include <stdint.h>
#include <type_traits>

namespace {

constexpr int SEQ = 2048;
constexpr int G_Q = 0, G_K = 32, G_V = 64, G_B = 96, G_CTX = G_Q, G_LOC = G_B, G_TOTAL = 120;

__device__ __align__(1024) __nv_bfloat16 g_scr[(size_t)G_TOTAL * SEQ * 128];
__device__ __align__(128) float g_gate[SEQ];

__device__ __forceinline__ uint32_t smem_u32(const void* p) { return (uint32_t)__cvta_generic_to_shared(p); }
__device__ __forceinline__ bool elect_one() {
    uint32_t p;
    asm volatile("{\n.reg .pred P;\nelect.sync _|P, 0xffffffff;\nselp.u32 %0, 1, 0, P;\n}\n" : "=r"(p));
    return p != 0;
}
__device__ __forceinline__ void mbar_init(uint32_t bar, uint32_t count) {
    asm volatile("mbarrier.init.shared::cta.b64 [%0], %1;" :: "r"(bar), "r"(count) : "memory");
}
__device__ __forceinline__ uint32_t cluster_rank() { uint32_t r; asm("mov.u32 %0, %%cluster_ctarank;" : "=r"(r)); return r; }
__device__ __forceinline__ uint32_t map_cta(uint32_t addr, uint32_t cta) {
    uint32_t r; asm("mapa.shared::cluster.u32 %0, %1, %2;" : "=r"(r) : "r"(addr), "r"(cta)); return r;
}
__device__ __forceinline__ void mbar_arrive_cluster_if(bool pred, uint32_t cluster_bar) {
    asm volatile("{\n.reg .pred P;\nsetp.ne.u32 P, %1, 0;\n@P mbarrier.arrive.shared::cluster.b64 _, [%0];\n}\n"
                 :: "r"(cluster_bar), "r"((uint32_t)pred) : "memory");
}
__device__ __forceinline__ void mbar_arrive_cluster_n_if(bool pred, uint32_t cluster_bar, uint32_t count) {
    asm volatile("{\n.reg .pred P;\nsetp.ne.u32 P, %1, 0;\n@P mbarrier.arrive.shared::cluster.b64 _, [%0], %2;\n}\n"
                 :: "r"(cluster_bar), "r"((uint32_t)pred), "r"(count) : "memory");
}
__device__ __forceinline__ void mbar_arrive_if(bool pred, uint32_t bar) {
    asm volatile("{\n.reg .pred P;\nsetp.ne.u32 P, %1, 0;\n@P mbarrier.arrive.shared::cta.b64 _, [%0];\n}\n"
                 :: "r"(bar), "r"((uint32_t)pred) : "memory");
}
__device__ __forceinline__ bool mbar_test(uint32_t bar, uint32_t parity) {
    uint32_t ok;
    asm volatile("{\n.reg .pred P;\nmbarrier.test_wait.parity.shared::cta.b64 P, [%1], %2;\nselp.u32 %0, 1, 0, P;\n}\n"
                 : "=r"(ok) : "r"(bar), "r"(parity) : "memory");
    return ok != 0;
}
__device__ __forceinline__ void mbar_wait(uint32_t bar, uint32_t parity) {
    asm volatile("{\n.reg .pred P;\n.reg .u32 c;\n"
                 "mov.u32 c, 0;\n"
                 "SPIN:\n"
                 "mbarrier.try_wait.parity.shared::cta.b64 P, [%0], %1;\n"
                 "@P bra DONE;\n"
                 "add.u32 c, c, 1;\n"
                 "setp.lt.u32 P, c, 4194304;\n"
                 "@P bra SPIN;\n"
                 "trap;\n"
                 "DONE:\n}\n" :: "r"(bar), "r"(parity) : "memory");
}
__device__ __forceinline__ void mbar_spin(uint32_t bar, uint32_t parity) {
    asm volatile("{\n.reg .pred P;\n"
                 "SPIN:\n"
                 "mbarrier.try_wait.parity.shared::cta.b64 P, [%0], %1;\n"
                 "@!P bra SPIN;\n}\n" :: "r"(bar), "r"(parity) : "memory");
}
__device__ __forceinline__ void bar_sync(int id, int n) { asm volatile("bar.sync %0, %1;" :: "r"(id), "r"(n) : "memory"); }
__device__ __forceinline__ void bar_arrive(int id, int n) { asm volatile("bar.arrive %0, %1;" :: "r"(id), "r"(n) : "memory"); }
__device__ __forceinline__ void fence_proxy_async_smem() { asm volatile("fence.proxy.async.shared::cta;" ::: "memory"); }
__device__ __forceinline__ void warp_expect_tx(uint32_t bar, uint32_t bytes) {
    asm volatile("{\n.reg .pred P;\nelect.sync _|P, 0xffffffff;\n@P mbarrier.arrive.expect_tx.shared::cta.b64 _, [%0], %1;\n}\n"
                 :: "r"(bar), "r"(bytes) : "memory");
}
constexpr uint64_t EVICT_FIRST = 0x12F0000000000000ull;
__device__ __forceinline__ void warp_tma_load(uint32_t dst, const CUtensorMap* map, uint32_t bar, int c0, int c1, int c2, bool stream) {
    if (stream)
        asm volatile("{\n.reg .pred P;\nelect.sync _|P, 0xffffffff;\n"
                     "@P cp.async.bulk.tensor.3d.shared::cluster.global.mbarrier::complete_tx::bytes.L2::cache_hint"
                     " [%0], [%1, {%3, %4, %5}], [%2], %6;\n}\n"
                     :: "r"(dst), "l"(map), "r"(bar), "r"(c0), "r"(c1), "r"(c2), "l"(EVICT_FIRST) : "memory");
    else
        asm volatile("{\n.reg .pred P;\nelect.sync _|P, 0xffffffff;\n"
                     "@P cp.async.bulk.tensor.3d.shared::cluster.global.mbarrier::complete_tx::bytes [%0], [%1, {%3, %4, %5}], [%2];\n}\n"
                     :: "r"(dst), "l"(map), "r"(bar), "r"(c0), "r"(c1), "r"(c2) : "memory");
}
__device__ __forceinline__ void warp_tma_load_pair(uint32_t dst, const CUtensorMap* map, uint32_t bar, int c0, int c1, int c2, bool stream) {
    if (stream)
        asm volatile("{\n.reg .pred P;\nelect.sync _|P, 0xffffffff;\n"
                     "@P cp.async.bulk.tensor.3d.shared::cluster.global.mbarrier::complete_tx::bytes.multicast::cluster.L2::cache_hint"
                     " [%0], [%1, {%3, %4, %5}], [%2], %6, %7;\n}\n"
                     :: "r"(dst), "l"(map), "r"(bar), "r"(c0), "r"(c1), "r"(c2), "h"((uint16_t)3), "l"(EVICT_FIRST) : "memory");
    else
        asm volatile("{\n.reg .pred P;\nelect.sync _|P, 0xffffffff;\n"
                     "@P cp.async.bulk.tensor.3d.shared::cluster.global.mbarrier::complete_tx::bytes.multicast::cluster"
                     " [%0], [%1, {%3, %4, %5}], [%2], %6;\n}\n"
                     :: "r"(dst), "l"(map), "r"(bar), "r"(c0), "r"(c1), "r"(c2), "h"((uint16_t)3) : "memory");
}
__device__ __forceinline__ void warp_bulk_load(uint32_t dst, const void* src, uint32_t bytes, uint32_t bar) {
    asm volatile("{\n.reg .pred P;\nelect.sync _|P, 0xffffffff;\n"
                 "@P cp.async.bulk.shared::cluster.global.mbarrier::complete_tx::bytes [%0], [%1], %2, [%3];\n}\n"
                 :: "r"(dst), "l"(src), "r"(bytes), "r"(bar) : "memory");
}
__device__ __forceinline__ void warp_tma_store(const CUtensorMap* map, uint32_t src, int c0, int c1, int c2, bool stream) {
    if (stream)
        asm volatile("{\n.reg .pred P;\nelect.sync _|P, 0xffffffff;\n"
                     "@P cp.async.bulk.tensor.3d.global.shared::cta.bulk_group.L2::cache_hint [%0, {%2, %3, %4}], [%1], %5;\n}\n"
                     :: "l"(map), "r"(src), "r"(c0), "r"(c1), "r"(c2), "l"(EVICT_FIRST) : "memory");
    else
        asm volatile("{\n.reg .pred P;\nelect.sync _|P, 0xffffffff;\n"
                     "@P cp.async.bulk.tensor.3d.global.shared::cta.bulk_group [%0, {%2, %3, %4}], [%1];\n}\n"
                     :: "l"(map), "r"(src), "r"(c0), "r"(c1), "r"(c2) : "memory");
}
__device__ __forceinline__ void warp_bulk_store(void* dst, uint32_t src, uint32_t bytes) {
    asm volatile("{\n.reg .pred P;\nelect.sync _|P, 0xffffffff;\n"
                 "@P cp.async.bulk.global.shared::cta.bulk_group [%0], [%1], %2;\n}\n" :: "l"(dst), "r"(src), "r"(bytes) : "memory");
}
__device__ __forceinline__ void warp_prefetch(const void* src, uint32_t bytes) {
    asm volatile("{\n.reg .pred P;\nelect.sync _|P, 0xffffffff;\n@P cp.async.bulk.prefetch.L2.global [%0], %1;\n}\n" :: "l"(src), "r"(bytes) : "memory");
}
__device__ __forceinline__ void bulk_commit() { asm volatile("cp.async.bulk.commit_group;" ::: "memory"); }
template <int N> __device__ __forceinline__ void bulk_wait_read() { asm volatile("cp.async.bulk.wait_group.read %0;" :: "n"(N) : "memory"); }
template <int N> __device__ __forceinline__ void bulk_wait() { asm volatile("cp.async.bulk.wait_group %0;" :: "n"(N) : "memory"); }
__device__ __forceinline__ void wgmma_fence() { asm volatile("wgmma.fence.sync.aligned;" ::: "memory"); }
__device__ __forceinline__ void wgmma_commit() { asm volatile("wgmma.commit_group.sync.aligned;" ::: "memory"); }
template <int N> __device__ __forceinline__ void wgmma_wait() { asm volatile("wgmma.wait_group.sync.aligned %0;" :: "n"(N) : "memory"); }
template <int N> __device__ __forceinline__ void fence_regs(float (&d)[N]) {
#pragma unroll
    for (int i = 0; i < N; i++) asm volatile("" : "+f"(d[i]) :: "memory");
}
template <int N> __device__ __forceinline__ void fence_regs(uint32_t (&d)[N]) {
#pragma unroll
    for (int i = 0; i < N; i++) asm volatile("" : "+r"(d[i]) :: "memory");
}
template <int N> __device__ __forceinline__ void reg_dec() { asm volatile("setmaxnreg.dec.sync.aligned.u32 %0;" :: "n"(N)); }
template <int N> __device__ __forceinline__ void reg_inc() { asm volatile("setmaxnreg.inc.sync.aligned.u32 %0;" :: "n"(N)); }
__device__ __forceinline__ uint32_t pack_bf16(float lo, float hi) {
    uint32_t r; asm("cvt.rn.bf16x2.f32 %0, %1, %2;" : "=r"(r) : "f"(hi), "f"(lo)); return r;
}
__device__ __forceinline__ void stmatrix_x4(uint32_t addr, uint32_t r0, uint32_t r1, uint32_t r2, uint32_t r3) {
    asm volatile("stmatrix.sync.aligned.m8n8.x4.shared.b16 [%0], {%1, %2, %3, %4};"
                 :: "r"(addr), "r"(r0), "r"(r1), "r"(r2), "r"(r3) : "memory");
}
__device__ __forceinline__ float ex2(float x) { float y; asm("ex2.approx.ftz.f32 %0, %1;" : "=f"(y) : "f"(x)); return y; }

constexpr uint32_t DESC_HI = (1024 >> 4) | (1u << 30);
__device__ __forceinline__ uint32_t make_desc(uint32_t addr, uint32_t lbo) {
    uint32_t lo = ((addr & 0x3FFFF) >> 4) | ((lbo >> 4) << 16);
    asm volatile("" : "+r"(lo));
    return lo;
}
__device__ __forceinline__ uint64_t full_desc(uint32_t lo) {
    uint64_t d; asm("mov.b64 %0, {%1, %2};" : "=l"(d) : "r"(lo), "r"(DESC_HI)); return d;
}

__device__ __forceinline__ void wgmma_ss_n256_tb_init(float (&d)[128], uint64_t da, uint64_t db) {
    asm volatile("{\n.reg .pred p;\n"
        "setp.ne.b32 p, 0, 0;\n"
        "wgmma.mma_async.sync.aligned.m64n256k16.f32.bf16.bf16 "
        "{%0, %1, %2, %3, %4, %5, %6, %7, %8, %9, %10, %11, %12, %13, %14, %15, %16, %17, %18, %19, %20, "
        "%21, %22, %23, %24, %25, %26, %27, %28, %29, %30, %31, %32, %33, %34, %35, %36, %37, %38, %39, %40, "
        "%41, %42, %43, %44, %45, %46, %47, %48, %49, %50, %51, %52, %53, %54, %55, %56, %57, %58, %59, %60, "
        "%61, %62, %63, %64, %65, %66, %67, %68, %69, %70, %71, %72, %73, %74, %75, %76, %77, %78, %79, %80, "
        "%81, %82, %83, %84, %85, %86, %87, %88, %89, %90, %91, %92, %93, %94, %95, %96, %97, %98, %99, "
        "%100, %101, %102, %103, %104, %105, %106, %107, %108, %109, %110, %111, %112, %113, %114, %115, "
        "%116, %117, %118, %119, %120, %121, %122, %123, %124, %125, %126, %127},"
        " %128, %129, p, 1, 1, 0, 1;\n}\n"
        : "=f"(d[0]), "=f"(d[1]), "=f"(d[2]), "=f"(d[3]), "=f"(d[4]), "=f"(d[5]), "=f"(d[6]), "=f"(d[7]),
        "=f"(d[8]), "=f"(d[9]), "=f"(d[10]), "=f"(d[11]), "=f"(d[12]), "=f"(d[13]), "=f"(d[14]), "=f"(d[15]),
        "=f"(d[16]), "=f"(d[17]), "=f"(d[18]), "=f"(d[19]), "=f"(d[20]), "=f"(d[21]), "=f"(d[22]),
        "=f"(d[23]), "=f"(d[24]), "=f"(d[25]), "=f"(d[26]), "=f"(d[27]), "=f"(d[28]), "=f"(d[29]),
        "=f"(d[30]), "=f"(d[31]), "=f"(d[32]), "=f"(d[33]), "=f"(d[34]), "=f"(d[35]), "=f"(d[36]),
        "=f"(d[37]), "=f"(d[38]), "=f"(d[39]), "=f"(d[40]), "=f"(d[41]), "=f"(d[42]), "=f"(d[43]),
        "=f"(d[44]), "=f"(d[45]), "=f"(d[46]), "=f"(d[47]), "=f"(d[48]), "=f"(d[49]), "=f"(d[50]),
        "=f"(d[51]), "=f"(d[52]), "=f"(d[53]), "=f"(d[54]), "=f"(d[55]), "=f"(d[56]), "=f"(d[57]),
        "=f"(d[58]), "=f"(d[59]), "=f"(d[60]), "=f"(d[61]), "=f"(d[62]), "=f"(d[63]), "=f"(d[64]),
        "=f"(d[65]), "=f"(d[66]), "=f"(d[67]), "=f"(d[68]), "=f"(d[69]), "=f"(d[70]), "=f"(d[71]),
        "=f"(d[72]), "=f"(d[73]), "=f"(d[74]), "=f"(d[75]), "=f"(d[76]), "=f"(d[77]), "=f"(d[78]),
        "=f"(d[79]), "=f"(d[80]), "=f"(d[81]), "=f"(d[82]), "=f"(d[83]), "=f"(d[84]), "=f"(d[85]),
        "=f"(d[86]), "=f"(d[87]), "=f"(d[88]), "=f"(d[89]), "=f"(d[90]), "=f"(d[91]), "=f"(d[92]),
        "=f"(d[93]), "=f"(d[94]), "=f"(d[95]), "=f"(d[96]), "=f"(d[97]), "=f"(d[98]), "=f"(d[99]),
        "=f"(d[100]), "=f"(d[101]), "=f"(d[102]), "=f"(d[103]), "=f"(d[104]), "=f"(d[105]), "=f"(d[106]),
        "=f"(d[107]), "=f"(d[108]), "=f"(d[109]), "=f"(d[110]), "=f"(d[111]), "=f"(d[112]), "=f"(d[113]),
        "=f"(d[114]), "=f"(d[115]), "=f"(d[116]), "=f"(d[117]), "=f"(d[118]), "=f"(d[119]), "=f"(d[120]),
        "=f"(d[121]), "=f"(d[122]), "=f"(d[123]), "=f"(d[124]), "=f"(d[125]), "=f"(d[126]), "=f"(d[127])
        : "l"(da), "l"(db));
}
__device__ __forceinline__ void wgmma_ss_n256_tb(float (&d)[128], uint64_t da, uint64_t db, int scale_d) {
    asm volatile("{\n.reg .pred p;\n"
        "setp.ne.b32 p, %130, 0;\n"
        "wgmma.mma_async.sync.aligned.m64n256k16.f32.bf16.bf16 "
        "{%0, %1, %2, %3, %4, %5, %6, %7, %8, %9, %10, %11, %12, %13, %14, %15, %16, %17, %18, %19, %20, "
        "%21, %22, %23, %24, %25, %26, %27, %28, %29, %30, %31, %32, %33, %34, %35, %36, %37, %38, %39, %40, "
        "%41, %42, %43, %44, %45, %46, %47, %48, %49, %50, %51, %52, %53, %54, %55, %56, %57, %58, %59, %60, "
        "%61, %62, %63, %64, %65, %66, %67, %68, %69, %70, %71, %72, %73, %74, %75, %76, %77, %78, %79, %80, "
        "%81, %82, %83, %84, %85, %86, %87, %88, %89, %90, %91, %92, %93, %94, %95, %96, %97, %98, %99, "
        "%100, %101, %102, %103, %104, %105, %106, %107, %108, %109, %110, %111, %112, %113, %114, %115, "
        "%116, %117, %118, %119, %120, %121, %122, %123, %124, %125, %126, %127},"
        " %128, %129, p, 1, 1, 0, 1;\n}\n"
        : "+f"(d[0]), "+f"(d[1]), "+f"(d[2]), "+f"(d[3]), "+f"(d[4]), "+f"(d[5]), "+f"(d[6]), "+f"(d[7]),
        "+f"(d[8]), "+f"(d[9]), "+f"(d[10]), "+f"(d[11]), "+f"(d[12]), "+f"(d[13]), "+f"(d[14]), "+f"(d[15]),
        "+f"(d[16]), "+f"(d[17]), "+f"(d[18]), "+f"(d[19]), "+f"(d[20]), "+f"(d[21]), "+f"(d[22]),
        "+f"(d[23]), "+f"(d[24]), "+f"(d[25]), "+f"(d[26]), "+f"(d[27]), "+f"(d[28]), "+f"(d[29]),
        "+f"(d[30]), "+f"(d[31]), "+f"(d[32]), "+f"(d[33]), "+f"(d[34]), "+f"(d[35]), "+f"(d[36]),
        "+f"(d[37]), "+f"(d[38]), "+f"(d[39]), "+f"(d[40]), "+f"(d[41]), "+f"(d[42]), "+f"(d[43]),
        "+f"(d[44]), "+f"(d[45]), "+f"(d[46]), "+f"(d[47]), "+f"(d[48]), "+f"(d[49]), "+f"(d[50]),
        "+f"(d[51]), "+f"(d[52]), "+f"(d[53]), "+f"(d[54]), "+f"(d[55]), "+f"(d[56]), "+f"(d[57]),
        "+f"(d[58]), "+f"(d[59]), "+f"(d[60]), "+f"(d[61]), "+f"(d[62]), "+f"(d[63]), "+f"(d[64]),
        "+f"(d[65]), "+f"(d[66]), "+f"(d[67]), "+f"(d[68]), "+f"(d[69]), "+f"(d[70]), "+f"(d[71]),
        "+f"(d[72]), "+f"(d[73]), "+f"(d[74]), "+f"(d[75]), "+f"(d[76]), "+f"(d[77]), "+f"(d[78]),
        "+f"(d[79]), "+f"(d[80]), "+f"(d[81]), "+f"(d[82]), "+f"(d[83]), "+f"(d[84]), "+f"(d[85]),
        "+f"(d[86]), "+f"(d[87]), "+f"(d[88]), "+f"(d[89]), "+f"(d[90]), "+f"(d[91]), "+f"(d[92]),
        "+f"(d[93]), "+f"(d[94]), "+f"(d[95]), "+f"(d[96]), "+f"(d[97]), "+f"(d[98]), "+f"(d[99]),
        "+f"(d[100]), "+f"(d[101]), "+f"(d[102]), "+f"(d[103]), "+f"(d[104]), "+f"(d[105]), "+f"(d[106]),
        "+f"(d[107]), "+f"(d[108]), "+f"(d[109]), "+f"(d[110]), "+f"(d[111]), "+f"(d[112]), "+f"(d[113]),
        "+f"(d[114]), "+f"(d[115]), "+f"(d[116]), "+f"(d[117]), "+f"(d[118]), "+f"(d[119]), "+f"(d[120]),
        "+f"(d[121]), "+f"(d[122]), "+f"(d[123]), "+f"(d[124]), "+f"(d[125]), "+f"(d[126]), "+f"(d[127])
        : "l"(da), "l"(db), "r"(scale_d));
}
__device__ __forceinline__ void wgmma_ss_n128(float (&d)[64], uint64_t da, uint64_t db, int scale_d) {
    asm volatile("{\n.reg .pred p;\n"
        "setp.ne.b32 p, %66, 0;\n"
        "wgmma.mma_async.sync.aligned.m64n128k16.f32.bf16.bf16 "
        "{%0, %1, %2, %3, %4, %5, %6, %7, %8, %9, %10, %11, %12, %13, %14, %15, %16, %17, %18, %19, %20, "
        "%21, %22, %23, %24, %25, %26, %27, %28, %29, %30, %31, %32, %33, %34, %35, %36, %37, %38, %39, %40, "
        "%41, %42, %43, %44, %45, %46, %47, %48, %49, %50, %51, %52, %53, %54, %55, %56, %57, %58, %59, %60, "
        "%61, %62, %63},"
        " %64, %65, p, 1, 1, 0, 0;\n}\n"
        : "+f"(d[0]), "+f"(d[1]), "+f"(d[2]), "+f"(d[3]), "+f"(d[4]), "+f"(d[5]), "+f"(d[6]), "+f"(d[7]),
        "+f"(d[8]), "+f"(d[9]), "+f"(d[10]), "+f"(d[11]), "+f"(d[12]), "+f"(d[13]), "+f"(d[14]), "+f"(d[15]),
        "+f"(d[16]), "+f"(d[17]), "+f"(d[18]), "+f"(d[19]), "+f"(d[20]), "+f"(d[21]), "+f"(d[22]),
        "+f"(d[23]), "+f"(d[24]), "+f"(d[25]), "+f"(d[26]), "+f"(d[27]), "+f"(d[28]), "+f"(d[29]),
        "+f"(d[30]), "+f"(d[31]), "+f"(d[32]), "+f"(d[33]), "+f"(d[34]), "+f"(d[35]), "+f"(d[36]),
        "+f"(d[37]), "+f"(d[38]), "+f"(d[39]), "+f"(d[40]), "+f"(d[41]), "+f"(d[42]), "+f"(d[43]),
        "+f"(d[44]), "+f"(d[45]), "+f"(d[46]), "+f"(d[47]), "+f"(d[48]), "+f"(d[49]), "+f"(d[50]),
        "+f"(d[51]), "+f"(d[52]), "+f"(d[53]), "+f"(d[54]), "+f"(d[55]), "+f"(d[56]), "+f"(d[57]),
        "+f"(d[58]), "+f"(d[59]), "+f"(d[60]), "+f"(d[61]), "+f"(d[62]), "+f"(d[63])
        : "l"(da), "l"(db), "r"(scale_d));
}
__device__ __forceinline__ void wgmma_rs_n128_tb(float (&d)[64], uint32_t a0, uint32_t a1, uint32_t a2, uint32_t a3, uint64_t db, int scale_d) {
    asm volatile("{\n.reg .pred p;\n"
        "setp.ne.b32 p, %69, 0;\n"
        "wgmma.mma_async.sync.aligned.m64n128k16.f32.bf16.bf16 "
        "{%0, %1, %2, %3, %4, %5, %6, %7, %8, %9, %10, %11, %12, %13, %14, %15, %16, %17, %18, %19, %20, "
        "%21, %22, %23, %24, %25, %26, %27, %28, %29, %30, %31, %32, %33, %34, %35, %36, %37, %38, %39, %40, "
        "%41, %42, %43, %44, %45, %46, %47, %48, %49, %50, %51, %52, %53, %54, %55, %56, %57, %58, %59, %60, "
        "%61, %62, %63},"
        " {%64, %65, %66, %67}, %68, p, 1, 1, 1;\n}\n"
        : "+f"(d[0]), "+f"(d[1]), "+f"(d[2]), "+f"(d[3]), "+f"(d[4]), "+f"(d[5]), "+f"(d[6]), "+f"(d[7]),
        "+f"(d[8]), "+f"(d[9]), "+f"(d[10]), "+f"(d[11]), "+f"(d[12]), "+f"(d[13]), "+f"(d[14]), "+f"(d[15]),
        "+f"(d[16]), "+f"(d[17]), "+f"(d[18]), "+f"(d[19]), "+f"(d[20]), "+f"(d[21]), "+f"(d[22]),
        "+f"(d[23]), "+f"(d[24]), "+f"(d[25]), "+f"(d[26]), "+f"(d[27]), "+f"(d[28]), "+f"(d[29]),
        "+f"(d[30]), "+f"(d[31]), "+f"(d[32]), "+f"(d[33]), "+f"(d[34]), "+f"(d[35]), "+f"(d[36]),
        "+f"(d[37]), "+f"(d[38]), "+f"(d[39]), "+f"(d[40]), "+f"(d[41]), "+f"(d[42]), "+f"(d[43]),
        "+f"(d[44]), "+f"(d[45]), "+f"(d[46]), "+f"(d[47]), "+f"(d[48]), "+f"(d[49]), "+f"(d[50]),
        "+f"(d[51]), "+f"(d[52]), "+f"(d[53]), "+f"(d[54]), "+f"(d[55]), "+f"(d[56]), "+f"(d[57]),
        "+f"(d[58]), "+f"(d[59]), "+f"(d[60]), "+f"(d[61]), "+f"(d[62]), "+f"(d[63])
        : "r"(a0), "r"(a1), "r"(a2), "r"(a3), "l"(db), "r"(scale_d));
}
__device__ __forceinline__ void wgmma_ss_n128_tb_init(float (&d)[64], uint64_t da, uint64_t db) {
    asm volatile("{\n.reg .pred p;\n"
        "setp.ne.b32 p, 0, 0;\n"
        "wgmma.mma_async.sync.aligned.m64n128k16.f32.bf16.bf16 "
        "{%0, %1, %2, %3, %4, %5, %6, %7, %8, %9, %10, %11, %12, %13, %14, %15, %16, %17, %18, %19, %20, "
        "%21, %22, %23, %24, %25, %26, %27, %28, %29, %30, %31, %32, %33, %34, %35, %36, %37, %38, %39, %40, "
        "%41, %42, %43, %44, %45, %46, %47, %48, %49, %50, %51, %52, %53, %54, %55, %56, %57, %58, %59, %60, "
        "%61, %62, %63},"
        " %64, %65, p, 1, 1, 0, 1;\n}\n"
        : "=f"(d[0]), "=f"(d[1]), "=f"(d[2]), "=f"(d[3]), "=f"(d[4]), "=f"(d[5]), "=f"(d[6]), "=f"(d[7]),
        "=f"(d[8]), "=f"(d[9]), "=f"(d[10]), "=f"(d[11]), "=f"(d[12]), "=f"(d[13]), "=f"(d[14]), "=f"(d[15]),
        "=f"(d[16]), "=f"(d[17]), "=f"(d[18]), "=f"(d[19]), "=f"(d[20]), "=f"(d[21]), "=f"(d[22]),
        "=f"(d[23]), "=f"(d[24]), "=f"(d[25]), "=f"(d[26]), "=f"(d[27]), "=f"(d[28]), "=f"(d[29]),
        "=f"(d[30]), "=f"(d[31]), "=f"(d[32]), "=f"(d[33]), "=f"(d[34]), "=f"(d[35]), "=f"(d[36]),
        "=f"(d[37]), "=f"(d[38]), "=f"(d[39]), "=f"(d[40]), "=f"(d[41]), "=f"(d[42]), "=f"(d[43]),
        "=f"(d[44]), "=f"(d[45]), "=f"(d[46]), "=f"(d[47]), "=f"(d[48]), "=f"(d[49]), "=f"(d[50]),
        "=f"(d[51]), "=f"(d[52]), "=f"(d[53]), "=f"(d[54]), "=f"(d[55]), "=f"(d[56]), "=f"(d[57]),
        "=f"(d[58]), "=f"(d[59]), "=f"(d[60]), "=f"(d[61]), "=f"(d[62]), "=f"(d[63])
        : "l"(da), "l"(db));
}
__device__ __forceinline__ void wgmma_ss_n128_tb(float (&d)[64], uint64_t da, uint64_t db, int scale_d) {
    asm volatile("{\n.reg .pred p;\n"
        "setp.ne.b32 p, %66, 0;\n"
        "wgmma.mma_async.sync.aligned.m64n128k16.f32.bf16.bf16 "
        "{%0, %1, %2, %3, %4, %5, %6, %7, %8, %9, %10, %11, %12, %13, %14, %15, %16, %17, %18, %19, %20, "
        "%21, %22, %23, %24, %25, %26, %27, %28, %29, %30, %31, %32, %33, %34, %35, %36, %37, %38, %39, %40, "
        "%41, %42, %43, %44, %45, %46, %47, %48, %49, %50, %51, %52, %53, %54, %55, %56, %57, %58, %59, %60, "
        "%61, %62, %63},"
        " %64, %65, p, 1, 1, 0, 1;\n}\n"
        : "+f"(d[0]), "+f"(d[1]), "+f"(d[2]), "+f"(d[3]), "+f"(d[4]), "+f"(d[5]), "+f"(d[6]), "+f"(d[7]),
        "+f"(d[8]), "+f"(d[9]), "+f"(d[10]), "+f"(d[11]), "+f"(d[12]), "+f"(d[13]), "+f"(d[14]), "+f"(d[15]),
        "+f"(d[16]), "+f"(d[17]), "+f"(d[18]), "+f"(d[19]), "+f"(d[20]), "+f"(d[21]), "+f"(d[22]),
        "+f"(d[23]), "+f"(d[24]), "+f"(d[25]), "+f"(d[26]), "+f"(d[27]), "+f"(d[28]), "+f"(d[29]),
        "+f"(d[30]), "+f"(d[31]), "+f"(d[32]), "+f"(d[33]), "+f"(d[34]), "+f"(d[35]), "+f"(d[36]),
        "+f"(d[37]), "+f"(d[38]), "+f"(d[39]), "+f"(d[40]), "+f"(d[41]), "+f"(d[42]), "+f"(d[43]),
        "+f"(d[44]), "+f"(d[45]), "+f"(d[46]), "+f"(d[47]), "+f"(d[48]), "+f"(d[49]), "+f"(d[50]),
        "+f"(d[51]), "+f"(d[52]), "+f"(d[53]), "+f"(d[54]), "+f"(d[55]), "+f"(d[56]), "+f"(d[57]),
        "+f"(d[58]), "+f"(d[59]), "+f"(d[60]), "+f"(d[61]), "+f"(d[62]), "+f"(d[63])
        : "l"(da), "l"(db), "r"(scale_d));
}

enum { M_X = 0, M_C, M_WQ, M_WUK, M_WUV, M_WQKV, M_WO, M_WOB, M_SCR_LD, M_SCR_LOC, M_SCR_LOQ, M_SCR_ST, M_COUNT };
enum { T_Q = 0, T_K, T_V, T_B, T_OUT, T_LOCAL, T_ATTN, T_END };
constexpr int NCTA = 132, NPAIR = NCTA / 2;
constexpr int NITEMS = 480 + 64 + 256;
constexpr int TRIPLES = 3, WIDE = 80 - 3 * TRIPLES;
struct Params {
    CUtensorMap m[M_COUNT];
    const __nv_bfloat16* x;
    const __nv_bfloat16* gate_w;
    const char* wo;
    __nv_bfloat16* out;
    uint32_t zero;
    uint16_t items[NITEMS];
    uint8_t ostep[80];
};
__device__ __forceinline__ int item_type(int it) { return it >> 13; }
__device__ __forceinline__ int item_row(int it) { return it & 15; }
__device__ __forceinline__ int item_col(int it) { return (it >> 4) & 31; }
__device__ __forceinline__ int item_asc(int it) { return (it >> 9) & 1; }
constexpr int ITEM_READY = 1 << 10;

struct __align__(128) Sync {
    unsigned long long count[4];
    __align__(128) unsigned long long ctx[16];
    unsigned next, next_out, done;
    __align__(128) unsigned step[32][2];
    unsigned split[32];
};
__device__ Sync g_sync;
__device__ uint4 g_part[128][8][256];

constexpr uint32_t GST_BYTES = 49152, SM_KV = 65536, SM_STAGING = 196608, SM_BARS = SM_STAGING + 32768;
constexpr uint32_t B_GFULL = 0, B_GEMPTY = 32, B_AFULL = 64, B_AEMPTY = 112, B_SFULL = 160, B_SEMPTY = 192,
                   B_IFULL = 224, B_IEMPTY = 288, B_XFREE = 352, B_WANT = 384, B_HALF = 416,
                   SM_ORDY = 448, SM_QUEUE = 456, B_ALT = 488, B_QFREE = 504, SM_GATE = 512, SM_TOTAL = SM_BARS + 1536;
constexpr int QDEPTH = 8;
constexpr int FIRST_PAIR = 6;
constexpr int K_MEET = 14, K_SPLIT = 26;
constexpr int K_FETCH = 20;
constexpr uint32_t LOC_PLANE = 72 * 128;
constexpr float SM_SCALE = 0.08838834764831845f * 1.4426950408889634f;
constexpr float LOC_SCALE = 0.17677669529663687f * 1.4426950408889634f;
constexpr float SUM_LIMIT = 1152921504606846976.f;
constexpr float REF_RANGE = 32.f;

__device__ __forceinline__ unsigned ld_acquire(const unsigned* p) {
    unsigned v; asm volatile("ld.acquire.gpu.global.u32 %0, [%1];" : "=r"(v) : "l"(p) : "memory"); return v;
}
__device__ __forceinline__ unsigned long long ld_acquire(const unsigned long long* p) {
    unsigned long long v; asm volatile("ld.acquire.gpu.global.u64 %0, [%1];" : "=l"(v) : "l"(p) : "memory"); return v;
}
__device__ __forceinline__ void st_b128(void* p, uint32_t a, uint32_t b, uint32_t c, uint32_t d) {
    asm volatile("{\n.reg .b128 v;\n.reg .b64 lo, hi;\nmov.b64 lo, {%1, %2};\nmov.b64 hi, {%3, %4};\nmov.b128 v, {lo, hi};\n"
                 "st.relaxed.gpu.global.b128 [%0], v;\n}\n" :: "l"(p), "r"(a), "r"(b), "r"(c), "r"(d) : "memory");
}
__device__ __forceinline__ void ld_b128(const void* p, uint32_t& a, uint32_t& b, uint32_t& c, uint32_t& d) {
    asm volatile("{\n.reg .b128 v;\n.reg .b64 lo, hi;\nld.relaxed.gpu.global.b128 v, [%4];\nmov.b128 {lo, hi}, v;\n"
                 "mov.b64 {%0, %1}, lo;\nmov.b64 {%2, %3}, hi;\n}\n" : "=r"(a), "=r"(b), "=r"(c), "=r"(d) : "l"(p) : "memory");
}
__device__ __forceinline__ void spin_guard(unsigned& n) {
    asm volatile("{\n.reg .pred P;\nadd.u32 %0, %0, 1;\nsetp.gt.u32 P, %0, 16777216;\n@P trap;\n}\n" : "+r"(n));
    if (n > 1) __nanosleep(100);
}
__device__ __forceinline__ void red_add(unsigned long long* p, unsigned long long v) {
    asm volatile("red.release.gpu.global.add.u64 [%0], %1;" :: "l"(p), "l"(v) : "memory");
}
__device__ __forceinline__ float rcp(float x) { float y; asm("rcp.approx.ftz.f32 %0, %1;" : "=f"(y) : "f"(x)); return y; }
__device__ __forceinline__ float lds_f32(uint32_t addr) {
    float v; asm volatile("ld.shared.f32 %0, [%1];" : "=f"(v) : "r"(addr) : "memory"); return v;
}
__device__ __forceinline__ void ldsm_x4(uint32_t (&r)[4], uint32_t addr) {
    asm volatile("ldmatrix.sync.aligned.m8n8.x4.shared.b16 {%0, %1, %2, %3}, [%4];"
                 : "=r"(r[0]), "=r"(r[1]), "=r"(r[2]), "=r"(r[3]) : "r"(addr) : "memory");
}
__device__ __forceinline__ void ldsm_x4_t(uint32_t (&r)[4], uint32_t addr) {
    asm volatile("ldmatrix.sync.aligned.m8n8.x4.trans.shared.b16 {%0, %1, %2, %3}, [%4];"
                 : "=r"(r[0]), "=r"(r[1]), "=r"(r[2]), "=r"(r[3]) : "r"(addr) : "memory");
}
__device__ __forceinline__ void mma_k16(float (&d)[4], const uint32_t (&a)[4], uint32_t b0, uint32_t b1) {
    asm("mma.sync.aligned.m16n8k16.row.col.f32.bf16.bf16.f32 {%0,%1,%2,%3}, {%4,%5,%6,%7}, {%8,%9}, {%0,%1,%2,%3};"
        : "+f"(d[0]), "+f"(d[1]), "+f"(d[2]), "+f"(d[3]) : "r"(a[0]), "r"(a[1]), "r"(a[2]), "r"(a[3]), "r"(b0), "r"(b1));
}
__device__ __forceinline__ void mma_k16_init(float (&d)[4], const uint32_t (&a)[4], uint32_t b0, uint32_t b1) {
    asm("{\n.reg .f32 z;\nmov.f32 z, 0f00000000;\n"
        "mma.sync.aligned.m16n8k16.row.col.f32.bf16.bf16.f32 {%0,%1,%2,%3}, {%4,%5,%6,%7}, {%8,%9}, {z,z,z,z};\n}\n"
        : "=f"(d[0]), "=f"(d[1]), "=f"(d[2]), "=f"(d[3]) : "r"(a[0]), "r"(a[1]), "r"(a[2]), "r"(a[3]), "r"(b0), "r"(b1));
}
__device__ __forceinline__ void mma_k8(float (&d)[4], uint32_t a0, uint32_t a1, uint32_t b0) {
    asm("mma.sync.aligned.m16n8k8.row.col.f32.bf16.bf16.f32 {%0,%1,%2,%3}, {%4,%5}, {%6}, {%0,%1,%2,%3};"
        : "+f"(d[0]), "+f"(d[1]), "+f"(d[2]), "+f"(d[3]) : "r"(a0), "r"(a1), "r"(b0));
}
template <typename T, int N> __device__ __forceinline__ void zero_regs(T (&d)[N]) {
#pragma unroll
    for (int i = 0; i < N; i++) d[i] = 0;
}
__device__ __forceinline__ float quad_max(float v) {
    v = fmaxf(v, __shfl_xor_sync(0xffffffffu, v, 1));
    return fmaxf(v, __shfl_xor_sync(0xffffffffu, v, 2));
}
__device__ __forceinline__ float quad_sum(float v) {
    v += __shfl_xor_sync(0xffffffffu, v, 1);
    return v + __shfl_xor_sync(0xffffffffu, v, 2);
}

__device__ __forceinline__ void qk_gemm(float (&s)[64], uint32_t q_lo, uint32_t k_lo) {
    const uint64_t dq = full_desc(q_lo), dk = full_desc(k_lo);
    fence_regs(s);
    wgmma_fence();
#pragma unroll
    for (int kk = 0; kk < 8; kk++) {
        const uint32_t o = (kk >> 2) * 1024 + (kk & 3) * 2;
        wgmma_ss_n128(s, dq + o, dk + o, kk != 0);
    }
    wgmma_commit();
}
__device__ __forceinline__ void pv_gemm(float (&o)[64], uint32_t (&p)[32], uint32_t v_lo, int accumulate) {
    const uint64_t dv = full_desc(v_lo);
    fence_regs(o);
    fence_regs(p);
    wgmma_fence();
#pragma unroll
    for (int kk = 0; kk < 8; kk++)
        wgmma_rs_n128_tb(o, p[4 * kk], p[4 * kk + 1], p[4 * kk + 2], p[4 * kk + 3], dv + kk * 128, kk != 0 || accumulate);
    wgmma_commit();
}
__device__ __forceinline__ void row_max(const float (&s)[64], float& x0, float& x1) {
    float z0 = fmaxf(s[0], s[1]), z1 = fmaxf(s[2], s[3]);
    x0 = fmaxf(s[4], s[5]); x1 = fmaxf(s[6], s[7]);
#pragma unroll
    for (int j = 2; j < 16; j += 2) {
        z0 = fmaxf(z0, fmaxf(s[4 * j], s[4 * j + 1]));
        z1 = fmaxf(z1, fmaxf(s[4 * j + 2], s[4 * j + 3]));
        x0 = fmaxf(x0, fmaxf(s[4 * j + 4], s[4 * j + 5]));
        x1 = fmaxf(x1, fmaxf(s[4 * j + 6], s[4 * j + 7]));
    }
    x0 = quad_max(fmaxf(x0, z0)); x1 = quad_max(fmaxf(x1, z1));
}
__device__ __forceinline__ void exp_pack(uint32_t (&p)[32], const float (&s)[64], float& r0, float& r1) {
#pragma unroll
    for (int j = 0; j < 16; j++) {
        const float e0 = ex2(s[4 * j]), e1 = ex2(s[4 * j + 1]), e2 = ex2(s[4 * j + 2]), e3 = ex2(s[4 * j + 3]);
        if (j == 0) { r0 = e0 + e1; r1 = e2 + e3; }
        else { r0 += e0 + e1; r1 += e2 + e3; }
        p[2 * j] = pack_bf16(e0, e1);
        p[2 * j + 1] = pack_bf16(e2, e3);
    }
}
__device__ __forceinline__ void shift_rows(float (&s)[64], float d0, float d1) {
#pragma unroll
    for (int j = 0; j < 16; j++) { s[4 * j] -= d0; s[4 * j + 1] -= d0; s[4 * j + 2] -= d1; s[4 * j + 3] -= d1; }
}
constexpr float MASKED = -3e38f;
template <int J0>
__device__ __forceinline__ void mask_triangle(float (&s)[64], float thr) {
#pragma unroll
    for (int j = 0; j < 16; j++) {
        const float m = __saturatef((float)(8 * (j >> 1) + (j & 1)) - thr);
        const int i = 4 * (J0 + (j >> 1)) + (j & 1);
        s[i] = fmaf(m, MASKED, s[i]);
        if (j < 14) s[i + 6] = fmaf(m, MASKED, s[i + 6]);
    }
}
__device__ __forceinline__ void causal_mask(float (&s)[64], float thr, int wg) {
    asm volatile("" : "+f"(thr));
    if (wg == 0) {
        mask_triangle<0>(s, thr);
#pragma unroll
        for (int j = 32; j < 64; j++) s[j] += MASKED;
    } else {
        mask_triangle<8>(s, thr);
    }
}

__global__ void __cluster_dims__(2, 1, 1) __launch_bounds__(384, 1) fused_kernel(const __grid_constant__ Params prm) {
    extern __shared__ __align__(1024) uint8_t smem[];
    const uint32_t sb = smem_u32(smem), bars = sb + SM_BARS;
    const int warp = __shfl_sync(0xffffffffu, threadIdx.x >> 5, 0), lane = threadIdx.x & 31;

    const uint32_t rank = cluster_rank();
    const uint32_t bars0 = map_cta(bars, 0), bars_peer = map_cta(bars, rank ^ 1);

    auto first_item = [&]() -> int {
        uint32_t pair = blockIdx.x >> 1;
        asm volatile("" : "+r"(pair));
        const uint32_t m = pair * 43 >> 9;
        return T_B << 13 | (pair - 12 * m) << 4 | (2 * m + rank);
    };
    if (warp == 0) {
        if (elect_one()) {
            for (int k = 0; k < 4; k++) mbar_init(bars + B_GFULL + 8 * k, 1);
            asm volatile("fence.mbarrier_init.release.cluster;" ::: "memory");
            fence_proxy_async_smem();
        }
        __syncwarp();
        const int first_it = __shfl_sync(0xffffffffu, first_item(), 0);
        asm volatile("barrier.cluster.arrive.relaxed.aligned;" ::: "memory");
#pragma unroll
        for (int k = 0; k < 2; k++) {
            const uint32_t dst = sb + k * GST_BYTES, fb = bars + B_GFULL + 8 * k;
            warp_expect_tx(fb, GST_BYTES);
            warp_tma_load(dst + 16384, &prm.m[M_WQKV], fb, 0, k * 64, item_col(first_it) * 4, false);
            warp_tma_load(dst, &prm.m[M_X], fb, k * 64, item_row(first_it) * 128, 0, false);
            warp_tma_load(dst + 32768, &prm.m[M_WQKV], fb, 0, k * 64, item_col(first_it) * 4 + 2, false);
        }
    }
    if (threadIdx.x == 32) {
        for (int i = 0; i < 4; i++) { mbar_init(bars + B_GEMPTY + 8 * i, 16); mbar_init(bars + B_XFREE + 8 * i, 1); }
        for (int i = 0; i < 6; i++) { mbar_init(bars + B_AFULL + 8 * i, 1); mbar_init(bars + B_AEMPTY + 8 * i, i < 2 ? 8 : 16); }
        for (int i = 0; i < 4; i++) { mbar_init(bars + B_SFULL + 8 * i, 4); mbar_init(bars + B_SEMPTY + 8 * i, 1); }
        for (int i = 0; i < QDEPTH; i++) { mbar_init(bars + B_IFULL + 8 * i, 1); mbar_init(bars + B_IEMPTY + 8 * i, 23); }
        mbar_init(bars + B_WANT, 2);
        for (int i = 0; i < 4; i++) mbar_init(bars + B_HALF + 8 * i, 1);
        mbar_init(bars + B_ALT, 4); mbar_init(bars + B_ALT + 8, 4); mbar_init(bars + B_QFREE, 2);
        asm volatile("st.shared.u64 [%0], 0;" :: "r"(bars + SM_ORDY) : "memory");
        asm volatile("fence.mbarrier_init.release.cluster;\nfence.acq_rel.cta;" ::: "memory");
    }
    __syncwarp();
    if (warp != 0) asm volatile("barrier.cluster.arrive.relaxed.aligned;" ::: "memory");
    asm volatile("barrier.cluster.wait.acquire.aligned;" ::: "memory");

    uint32_t qn = 0;
    auto next_item = [&](bool releaser, bool bounded = true) -> int {
        const uint32_t slot = qn % QDEPTH;
        if (bounded) mbar_wait(bars + B_IFULL + 8 * slot, (qn / QDEPTH) & 1);
        else mbar_spin(bars + B_IFULL + 8 * slot, (qn / QDEPTH) & 1);
        uint32_t it;
        asm volatile("ld.shared.u32 %0, [%1];" : "=r"(it) : "r"(bars + SM_QUEUE + 4 * slot) : "memory");
        mbar_arrive_cluster_if(releaser, bars0 + B_IEMPTY + 8 * slot);
        qn++;
        return it;
    };

    if (warp < 4) {
        reg_dec<40>();
        if (warp == 0) {
            {
                uint32_t gph = 1;
                const uint32_t prank = __shfl_sync(0xffffffffu, rank, 0);
                auto request = [&]() { mbar_arrive_cluster_if(lane == 0, bars0 + B_WANT); };
                auto take_item = [&]() -> int { return __shfl_sync(0xffffffffu, next_item(lane == 0), 0); };
                auto inputs_seen = [&](uint32_t word, unsigned& n) -> uint32_t {
                    uint32_t v;
                    spin_guard(n);
                    asm volatile("ld.acquire.cta.shared.u32 %0, [%1];" : "=r"(v) : "r"(bars + SM_ORDY + 4 * word) : "memory");
                    return __shfl_sync(0xffffffffu, v, 0);
                };
                uint32_t oneed = 0;
                auto wait_inputs = [&](int it) {
                    if (it & ITEM_READY) return;
                    oneed += 256;
                    for (unsigned n = 0; inputs_seen(1, n) < oneed;) {}
                };
                int nxt = first_item();
                for (int k0 = 2; item_type(nxt) <= T_LOCAL; k0 = 0) {
                    const int type = item_type(nxt), m = item_row(nxt), c = item_col(nxt);
                    if (type == T_LOCAL) {
                        wait_inputs(nxt);
                        request();
#pragma unroll 1
                        for (uint32_t st = 0; st < 4; st++) {
                            mbar_wait(bars + B_GEMPTY + 8 * st, gph);
                            const uint32_t dst = sb + st * GST_BYTES, fb = bars + B_GFULL + 8 * st;
                            warp_expect_tx(fb, st == 0 ? 32768 + 512 : st == 3 ? 0 : 4 * LOC_PLANE);
                            if (st == 3) break;
                            if (st == 0) warp_bulk_load(dst + 4 * LOC_PLANE, &g_gate[m * 128], 512, fb);
#pragma unroll 1
                            for (int i = 0; i < 4; i++)
                                warp_tma_load(dst + i * LOC_PLANE, &prm.m[st ? M_SCR_LOC : M_SCR_LOQ], fb, i * 64, m * 64 - (st ? 8 : 0), G_B + 8 * st + c, true);
                        }
                        gph ^= 1;
                    } else {
                        const int nk = type == T_K || type == T_V ? 8 : 16;
                        const CUtensorMap* ma = &prm.m[nk == 8 ? M_C : M_X];
                        const CUtensorMap* mb = &prm.m[M_WQ + type];
#pragma unroll 1
                        for (int k = k0; k < nk; k++) {
                            if (k == nk - 3) request();
                            const uint32_t st = k & 3, dst = sb + st * GST_BYTES, fb = bars + B_GFULL + 8 * st;
                            mbar_wait(bars + B_GEMPTY + 8 * st, gph);
                            warp_expect_tx(fb, GST_BYTES);
                            warp_tma_load(dst, ma, fb, k * 64, m * 128, 0, c == 15 && type != T_K);
                            warp_tma_load_pair(dst + 16384 + prank * 16384, mb, fb, 0, k * 64, c * 4 + 2 * prank, type != T_B || m >= 14);
                            if (st == 3) gph ^= 1;
                        }
                    }
                    nxt = take_item();
                }
                uint32_t kv = 0, kvph = 1;
                uint32_t qc = 0;
                auto a_parity = [&](uint32_t b) { return b < 2 ? (((qc + 1 - b) >> 1) & 1) ^ 1 : kvph ^ (b - 2 < kv); };
                const CUtensorMap* tile_map = &prm.m[M_SCR_LD];
                asm volatile("" : "+l"(tile_map));
                {
                    bool need_g = true, more = true;
                    int pv_grp = -1, pv_row = 0;
                    int pv_shared = 0;
                    bool peer_longer = false;
                    int m = 0, c = 0, asc = 0, nu = 0, uend = 0, ureq = -1, ufetch = 0;
#pragma unroll 1
                    for (int u = 0;; u++) {
                        if (u == ufetch) {
                            if (qc) nxt = take_item();
                            if (item_type(nxt) == T_ATTN) {
                                wait_inputs(nxt);
                                const uint32_t b = qc & 1, dst = sb + b * 32768, fb = bars + B_AFULL + 8 * b, row = item_row(nxt) * 128;
                                mbar_wait(bars + (qc == 0 ? B_GEMPTY : qc == 1 ? B_QFREE : B_AEMPTY + 8 * b), qc == 0 ? gph : qc == 1 ? 0 : a_parity(b));
                                warp_expect_tx(fb, 32768 + 512);
                                warp_tma_load(dst, tile_map, fb, 0, row, G_Q + item_col(nxt), false);
                                warp_tma_load(dst + 16384, tile_map, fb, 64, row, G_Q + item_col(nxt), false);
                                warp_bulk_load(bars + SM_GATE + b * 512, &g_gate[row], 512, fb);
                                qc++;
                            }
                        }
                        if (u == uend) {
                            if (!more) break;
                            more = item_type(nxt) == T_ATTN;
                            m = item_row(nxt); c = item_col(nxt); asc = item_asc(nxt);
                            nu = more ? 2 * m + 2 : 0;
                            uend = nu + ((more ? m < 2 : pv_grp >= 0) ? 3 : 0);
                            ureq = 2 * max(m - 2 - (asc & m), 0);
                            ufetch = !more ? -1 : m ? 2 * m : uend;
                            u = -1;
                            continue;
                        }
                        int grp = pv_grp, row = pv_row;
                        int shared = pv_shared;
                        if (u >= nu) {
                            if (u == nu + 1) pv_grp = -1;
                            else if (peer_longer) { grp = -1; shared = 0; }
                            else continue;
                        } else {
                            const int j = asc ? u >> 1 : m - (u >> 1);
                            if (u & 1) {
                                pv_grp = G_V + c; pv_row = j * 128; pv_shared = (m | 1) - j;
                                peer_longer = asc & ~m & 1;
                                if (u == nu - 1 && (m & 1) && item_type(nxt) == T_END) mbar_arrive_cluster_n_if(lane == 0, bars0 + B_WANT, 2);
                                if (grp < 0) continue;
                            } else {
                                if (u == ureq) request();
                                grp = G_K + c; row = j * 128; shared = (m | 1) - j;
                            }
                        }
                        uint32_t fb = bars + B_AFULL + 16 + 8 * kv, mine = sb + SM_KV + kv * 32768 + prank * 16384;
                        int c_mine = prank * 64;
                        asm volatile("" : "+r"(mine), "+r"(fb), "+r"(row), "+r"(grp), "+r"(c_mine));
                        mbar_wait(need_g ? bars + B_GEMPTY + 8 + 8 * kv : fb + B_AEMPTY - B_AFULL, need_g ? gph : kvph);
                        warp_expect_tx(fb, grp < 0 ? 0 : 32768);
                        if (shared) {
                            warp_tma_load_pair(mine, tile_map, fb, c_mine, row, grp, shared == 1);
                        } else if (grp >= 0) {
                            warp_tma_load(mine, tile_map, fb, c_mine, row, grp, true);
                            warp_tma_load(mine + 16384 - prank * 32768, tile_map, fb, 64 - c_mine, row, grp, true);
                        } else {
                            mbar_arrive_cluster_n_if(lane < 2, map_cta(fb, lane & 1) + B_AEMPTY - B_AFULL, 8);
                        }
                        if (kv == 2) need_g = false;
                        if (++kv == 4) { kv = 0; kvph ^= 1; }
                    }
                }
                if (!qc) request();
                const int it = take_item();
                int nk = 0;
                if (item_type(it) == T_OUT) {
                    const int m = item_row(it), c = item_col(it), half = c & 1;
                    nk = 80;
                    for (int k = 0; k < nk; k++) {
                        if (k == K_SPLIT) nk = 2 * TRIPLES + (take_item() & 127);
                        const int kn = k + 2 * TRIPLES - nk, first = kn >= 0 && !(kn & 1);
                        const int s = kn >= 0 ? WIDE + (3 * kn + 1) / 2 : half ? WIDE - 1 - k : k;
                        const uint32_t sa = prm.ostep[s], sa2 = prm.ostep[s + first], sw = prm.ostep[s - (kn >= 0 && !first ? prank : 0)];
                        const uint32_t need = 1u << (sa >> 1 & 31) | 1u << (sa2 >> 1 & 31);
                        for (unsigned n = 0; need & ~inputs_seen(sa >> 6, n);) {}
                        const uint32_t st = k & 3;
                        uint32_t dst = sb + st * GST_BYTES, fb = bars + B_GFULL + 8 * st;
                        uint32_t dstb = dst + 16384 + (first ? 0 : prank * 16384), skipb = first && (kn >> 1 & 1) != prank;
                        int a0 = (sa & 1) * 64, a1 = m * 128, a2 = (sa >> 1) + (sa < 64 ? G_CTX : G_LOC - 32);
                        int b1 = (sw & 63) * 64, b2 = (c >> 1) * 4 + 2 * (kn >= 0 ? half : half ^ prank);
                        const CUtensorMap* mb = &prm.m[sw >= 64 ? M_WOB : M_WO];
                        asm volatile("" : "+r"(dst), "+r"(fb), "+r"(dstb), "+r"(skipb), "+r"(a0), "+r"(a1), "+r"(a2), "+r"(b1), "+r"(b2), "+l"(mb));
                        if (k < 4) {
#pragma unroll 1
                            for (uint32_t i = 0, b = (3 * st) >> 1; i < 3; i++, b++) mbar_wait(bars + (i == 2 ? B_QFREE : B_AEMPTY + 8 * b), i == 2 ? 0 : a_parity(b));
                            mbar_arrive_cluster_if(lane == 0, bars_peer + B_XFREE + 8 * st);
                            mbar_wait(bars + B_XFREE + 8 * st, 0);
                        }
                        mbar_wait(bars + B_GEMPTY + 8 * st, gph);
                        warp_expect_tx(fb, GST_BYTES);
                        warp_tma_load(dst, tile_map, fb, a0, a1, a2, true);
                        if (!skipb) warp_tma_load_pair(dstb, mb, fb, 0, b1, b2, false);
                        if (first) warp_tma_load(dst + 32768, tile_map, fb, (sa2 & 1) * 64, a1, G_CTX + (sa2 >> 1), true);
                        if (k < K_SPLIT && lane == 0 && !prank)
                            asm volatile("st.relaxed.gpu.global.u32 [%0], %1;" :: "l"(&g_sync.step[0][0] + m * 4 + c), "r"(k) : "memory");
                        if (k == K_MEET) request();
                        if ((uint32_t)(k - K_FETCH) < (3 * TRIPLES + 1) / 2) {
                            const uint32_t g = prm.ostep[79 - 2 * (k - K_FETCH)] >> 1;
                            warp_prefetch((const char*)g_scr + (uint32_t)((G_CTX + g) * (SEQ * 256) + m * 32768 + c * 4096), 4096);
                            warp_prefetch(prm.wo + (uint32_t)(g * 262144 + (m * 8 + c) * 2048), 2048);
                        }
                        if (st == 3) gph ^= 1;
                    }
                    for (unsigned n = 0; ~inputs_seen(0, n) || inputs_seen(1, n) != 255;) {}
                }
#pragma unroll 1
                for (uint32_t st = 0; st < 4; st++) { mbar_wait(bars + B_GEMPTY + 8 * st, gph ^ (st < (nk & 3))); mbar_wait(bars + B_AEMPTY + 16 + 8 * st, a_parity(2 + st)); }
                unsigned left = 0;
                if (lane == 0) asm volatile("atom.relaxed.gpu.global.add.u32 %0, [%1], 1;" : "=r"(left) : "l"(&g_sync.done) : "memory");
                if (__shfl_sync(0xffffffffu, left, 0) == NCTA - 1)
#pragma unroll 1
                    for (uint32_t i = lane * 8; i < sizeof(Sync); i += 256) *(unsigned long long*)((char*)&g_sync + i) = 0;
            }
        } else if (warp <= 2) {
            if (blockIdx.x < SEQ / 16) {
                const uint32_t r0 = 16 * blockIdx.x + 8 * (warp - 1), gbuf = bars + SM_GATE + 4 * (r0 & 15);
                float z[4];
                mbar_wait(bars + B_GFULL + 24, 0);
#pragma unroll 1
                for (uint32_t i = 0; i < 8; i++) {
                    const uint32_t off = (i & 3) * 512 + lane * 16;
                    const uint4* xp = (const uint4*)((const char*)prm.x + ((r0 + (i & 4)) * 2048 + off));
                    const uint4 wv = __ldg((const uint4*)((const char*)prm.gate_w + off));
                    uint4 xv[4];
#pragma unroll
                    for (int r = 0; r < 4; r++) { xv[r] = __ldg(xp + r * 128); if (!(i & 3)) z[r] = 0.f; }
                    const uint32_t ws[4] = {wv.x, wv.y, wv.z, wv.w};
#pragma unroll
                    for (int e = 0; e < 4; e++)
#pragma unroll
                        for (int r = 0; r < 4; r++) {
                            const uint32_t xs = e == 0 ? xv[r].x : e == 1 ? xv[r].y : e == 2 ? xv[r].z : xv[r].w;
                            z[r] = fmaf(__uint_as_float(xs << 16), __uint_as_float(ws[e] << 16), z[r]);
                            z[r] = fmaf(__uint_as_float(xs & 0xffff0000u), __uint_as_float(ws[e] & 0xffff0000u), z[r]);
                        }
                    if ((i & 3) == 3) {
#pragma unroll
                        for (int o = 16; o > 0; o >>= 1)
#pragma unroll
                            for (int r = 0; r < 4; r++) z[r] += __shfl_xor_sync(0xffffffffu, z[r], o);
                        const float zr = lane & 2 ? (lane & 1 ? z[3] : z[2]) : (lane & 1 ? z[1] : z[0]);
                        asm volatile("st.shared.f32 [%0], %1;" :: "r"(gbuf + 4 * ((i & 4) + (lane & 3))), "f"(1.f / (1.f + __expf(-zr))) : "memory");
                    }
                }
                fence_proxy_async_smem();
                __syncwarp();
                warp_bulk_store((char*)g_gate + 4 * r0, gbuf, 32);
                bulk_commit();
                bulk_wait<0>();
                __syncwarp();
                if (lane == 0) red_add(&g_sync.count[3], 1);
            }
            __syncwarp();
            {
                const int w = warp - 1;
                uint32_t sph = 0, nann = 0;
                int unsent = 0, nunsent = 0;
                bool urgent = false;
                auto announce = [&]() {
                    if (!urgent) return;
                    bulk_wait<0>();
                    __syncwarp();
                    const uint32_t hb = bars + B_HALF + 8 * (nann & 3);
                    if (w == 0) {
                        mbar_arrive_if(lane == 0, hb);
                    } else {
                        mbar_wait(hb, (nann >> 2) & 1);
                        const uint32_t type = item_type(unsent), m = item_row(unsent), c = item_col(unsent);
                        const uint32_t word = type < T_B ? c >> 3 : type == T_B ? 2 : offsetof(Sync, ctx) / 8 + m;
                        const uint32_t bit = type < T_B ? 8 * (c & 7) : type == T_B ? 4 * m : type == T_LOCAL ? 32 + c : c;
                        if (lane < nunsent) red_add((unsigned long long*)((char*)&g_sync + 8 * word), 1ull << bit);
                        __syncwarp();
                    }
                    nann++;
                    nunsent = 0; urgent = false;
                };
                int held = first_item(), it;
                bool qfree = false;
                do {
                    if (!__all_sync(0xffffffffu, mbar_test(bars + B_IFULL + 8 * (qn % QDEPTH), (qn / QDEPTH) & 1))) announce();
                    it = __shfl_sync(0xffffffffu, next_item(lane == 0), 0);
                    const int itype = item_type(it);
                    const bool keep_held = itype == T_LOCAL && (item_type(held) != T_B || (it & ITEM_READY));
                    if (itype >= T_ATTN && held < 0) {
                        urgent = nunsent;
                        mbar_arrive_if(lane == 0 && !qfree, bars + B_QFREE);
                        qfree = true;
                    }
#pragma unroll 1
                    for (int pass = held < 0 || keep_held; pass < 2; pass++) {
                        if (pass && (itype < T_OUT || itype == T_END)) break;
                        const int cur = pass ? it : held, type = item_type(cur), m = item_row(cur), c = item_col(cur);
                        const bool local = type == T_LOCAL;
                        const int grp = pass ? (local ? G_LOC : G_CTX) + c : type * 32 + 2 * c;
#pragma unroll 1
                        for (int i = 0; i < 4 - 2 * pass; i++) {
                            const int b = i & 1;
                            const bool alt = i >= 2 && itype == T_ATTN;
                            const uint32_t full = bars + (alt ? B_ALT + 8 * w : B_SFULL + 16 * w + 8 * b), par = alt ? 0 : sph;
                            if (i == 3 - 2 * pass || !__all_sync(0xffffffffu, mbar_test(full, par))) announce();
                            mbar_wait(full, par);
                            fence_proxy_async_smem();
                            warp_tma_store(&prm.m[local ? M_SCR_LOQ : M_SCR_ST], sb + (alt ? 32768 : SM_STAGING) + w * 16384 + b * 8192,
                                         local ? b * 128 + w * 64 : b * 64, local ? m * 64 : m * 128 + w * 64, grp + (i >> 1), local || (type < T_B && c < FIRST_PAIR));
                            bulk_commit();
                            bulk_wait_read<0>();
                            __syncwarp();
                            mbar_arrive_if(lane == 0 && !alt, bars + B_SEMPTY + 16 * w + 8 * b);
                            sph ^= b & !alt;
                        }
                        mbar_arrive_if(lane == 0 && !qfree && itype >= T_ATTN, bars + B_QFREE);
                        qfree |= itype >= T_ATTN;
                        if (lane == nunsent) unsent = cur;
                        nunsent++;
                        urgent = nunsent == 32 || !local;
                    }
                    if (!keep_held) held = itype < T_OUT ? it : -1;
                } while (item_type(it) != T_END);
                announce();
                if (item_type(next_item(lane == 0)) == T_OUT) next_item(lane == 0);
            }
        } else {
            if (elect_one()) {
                uint32_t ordy = 0;
                unsigned long long cnt_lo = 0, cnt_hi = 0;
                int late = 0;
                auto refresh = [&]() {
                    if (!late && cnt_lo == 0xccccccccccccccccull && cnt_hi == SEQ / 8) late = 1;
                    asm volatile("ld.acquire.gpu.global.v2.u64 {%0, %1}, [%2];" : "=l"(cnt_lo), "=l"(cnt_hi) : "l"(late ? &g_sync.count[0] : &g_sync.count[2]) : "memory");
                };
                auto inputs_ready = [&](int it) -> bool {
                    const int m = item_row(it), c = item_col(it);
                    if (item_type(it) == T_ATTN) return late && ((c < 16 ? cnt_lo : cnt_hi) >> (4 * (c & 14)) & 255) == 48;
                    return late || (cnt_hi == SEQ / 8 && (cnt_lo >> (4 * m) & 15) == 12 && (cnt_lo >> (4 * max(m - 1, 0)) & 15) == 12);
                };
                auto publish = [&](int it, int step) {
                    const uint32_t slot = qn % QDEPTH;
                    mbar_wait(bars + B_IEMPTY + 8 * slot, ((qn / QDEPTH) & 1) ^ 1);
                    for (uint32_t r = 0; r < 2; r++) {
                        const uint32_t rb = map_cta(bars, r);
                        asm volatile("mbarrier.arrive.expect_tx.shared::cluster.b64 _, [%0], 4;" :: "r"(rb + B_IFULL + 8 * slot) : "memory");
                        asm volatile("st.async.shared::cluster.mbarrier::complete_tx::bytes.u32 [%0], %1, [%2];"
                                     :: "r"(rb + SM_QUEUE + 4 * slot), "r"(it + r * step), "r"(rb + B_IFULL + 8 * slot) : "memory");
                    }
                    qn++;
                };
                int asc = 1;
                int it;
                do {
                    if (rank == 0) {
                        mbar_wait(bars + B_WANT, qn & 1);
                        unsigned i;
                        asm volatile("atom.relaxed.gpu.global.add.u32 %0, [%1], 1;" : "=r"(i) : "l"(&g_sync.next) : "memory");
                        if (cnt_lo != 0x3030303030303030ull || cnt_hi != cnt_lo) refresh();
                        i += NPAIR;
                        const int pit = i < NITEMS ? prm.items[i] : T_END << 13, type = item_type(pit);
                        int step = type == T_LOCAL ? 16 : 1;
                        it = pit + (pit & (step == 1 ? 15 : 0x1f0));
                        if (type == T_ATTN) {
                            if (!asc) { it += 1; step = -1; }
                            it |= asc << 9;
                        }
                        asc = type != T_ATTN || item_row(pit) == 0 || !asc;
                        if (inputs_ready(it)) it |= ITEM_READY;
                        publish(it, step);
                    } else {
                        it = next_item(true);
                    }
                    if ((item_type(it) == T_ATTN || item_type(it) == T_LOCAL) && !(it & ITEM_READY)) {
                        unsigned n = 0;
                        while (!inputs_ready(it)) { refresh(); spin_guard(n); }
                        asm volatile("st.release.cta.shared.u32 [%0], %1;" :: "r"(bars + SM_ORDY + 4), "r"(ordy += 256) : "memory");
                    }
                } while (item_type(it) != T_END);
                if (rank == 0) {
                    mbar_wait(bars + B_WANT, qn & 1);
                    const unsigned i = atomicAdd(&g_sync.next_out, 1u), t = i < 32 ? 31 - i : i - 32;
                    it = i < 64 ? T_OUT << 13 | ((t & 3) * 2 + (i >> 5)) << 4 | (t >> 2) * 2 : T_END << 13;
                    publish(it, 1);
                } else {
                    it = next_item(true);
                }
                if (item_type(it) == T_OUT) {
                    const uint32_t m = item_row(it), half = item_col(it) & 1, tile = m * 2 + (item_col(it) >> 1);
                    unsigned* split = (unsigned*)((char*)g_sync.split + 4 * tile);
                    unsigned long long rdy = 0;
                    int state = rank ? 2 : 0;
                    for (unsigned n = 0; rdy != 0xffffffffffull || state < 2; spin_guard(n)) {
                        if (rdy != 0xffffffffffull) {
                            rdy = ld_acquire((const unsigned long long*)((char*)g_sync.ctx + 8 * m));
                            asm volatile("st.release.cta.shared.u64 [%0], %1;" :: "r"(bars + SM_ORDY), "l"(rdy) : "memory");
                        }
                        unsigned steps = 0;
                        if (state == 1) {
                            steps = ld_acquire(split);
                        } else if (state == 0 && mbar_test(bars + B_WANT, qn & 1)) {
                            state = 1;
                            unsigned seen;
                            asm volatile("atom.acq_rel.gpu.global.exch.b32 %0, [%1], 1;" : "=r"(seen) : "l"(split) : "memory");
                            if (seen) {
                                const unsigned long long v = ld_acquire((const unsigned long long*)((char*)g_sync.step + 8 * tile));
                                const int d = (int)(v >> 32) - (int)v;
                                steps = (WIDE + min(max(half ? d : -d, K_MEET - K_SPLIT), K_SPLIT - K_MEET)) >> 1;
                                atomicExch(split, WIDE - steps);
                            }
                        }
                        if (steps > 1) { publish(T_END << 13 | steps, 0); state = 2; }
                    }
                    if (rank) next_item(true);
                }
                #pragma unroll 1
                for (uint32_t n = qn; n < qn + QDEPTH && rank == 0; n++) mbar_wait(bars + B_IEMPTY + 8 * (n % QDEPTH), ((n / QDEPTH) & 1) ^ 1);
            }
        }
    } else {
        reg_inc<232>();
        const int wg = (warp >> 2) - 1, wq = warp & 3;
        uint32_t gph = 0;
        uint32_t kvn = 0;
        const uint32_t dA = make_desc(sb + wg * 8192, 16);
        uint32_t ti = 0;
        uint32_t sph = 1;
        const uint32_t stg = sb + SM_STAGING + wg * 16384;
        const uint32_t stg_lane = stg + (wq * 16 + (lane & 15)) * 128 + (((lane >> 4) ^ (lane & 7)) << 4);
        auto write_blocks = [&](auto n, uint32_t off, const uint32_t* v) {
            uint32_t a = stg_lane;
            asm volatile("" : "+r"(a));
            a += off;
#pragma unroll
            for (int j = 0; j < decltype(n)::value; j++)
                stmatrix_x4((a ^ (32 * (j & 3))) + (j >> 2) * 8192, v[4 * j], v[4 * j + 1], v[4 * j + 2], v[4 * j + 3]);
        };
        auto release = [&](uint32_t bar) { mbar_arrive_if(lane == 0, bars + bar); };
        const uint32_t bars_lane = map_cta(bars, lane & 1);
        auto release_stage = [&](uint32_t st) { mbar_arrive_cluster_if(lane < 2, bars_lane + B_GEMPTY + 8 * st); };
        auto take_item = [&]() -> int {
            return __shfl_sync(0xffffffffu, next_item(lane == 0, false), 0);
        };
        auto stage_acquire = [&](int b) { mbar_spin(bars + B_SEMPTY + 16 * wg + 8 * b, sph); };
        auto stage_publish = [&](int b) {
            __syncwarp();
            release(B_SFULL + 16 * wg + 8 * b);
        };
        auto stage_chunk = [&](int b, const uint32_t* v) {
            stage_acquire(b);
            write_blocks(std::integral_constant<int, 4>(), b * 8192, v);
            stage_publish(b);
            if (b) sph ^= 1;
        };
        auto publish_pair = [&]() {
            __syncwarp();
            mbar_arrive_if(lane < 2, bars + B_SFULL + 16 * wg + 8 * lane);
            sph ^= 1;
        };
        auto gemm_step = [&](float (&acc)[128], uint32_t dB, int& k) {
            const uint32_t st = k & 3;
            wgmma_wait<0>();
            release_stage((k - 1) & 3);
            mbar_spin(bars + B_GFULL + 8 * st, gph);
            const uint64_t da = full_desc(dA + st * (GST_BYTES >> 4)), db = full_desc(dB + st * (GST_BYTES >> 4));
            wgmma_fence();
#pragma unroll
            for (int kk = 0; kk < 4; kk++) wgmma_ss_n256_tb(acc, da + 2 * kk, db + 128 * kk, 1);
            wgmma_commit();
            gph ^= st == 3;
            k++;
        };
        if (wg == 1) bar_arrive(1, 256);
        int it = first_item();
        while (true) {
            if (item_type(it) <= T_LOCAL) {
                float acc[128];
                uint32_t pk[64];
                bool pending = false;
                bool held_b = false;
                zero_regs(pk);
                const uint32_t dB = make_desc(sb + 16384, 8192);
                do {
                    const int type = item_type(it);
                    if (type == T_LOCAL) {
                        int ln = lane;
                        asm volatile("" : "+r"(ln));
                        const int g = ln >> 2, t = ln & 3, par = wq & 1;
                        const uint32_t hc = (wq >> 1) * 4, pl = sb + (par * 2 + wg) * LOC_PLANE;
                        const uint32_t a16 = (ln & 15) * 128 + (((hc + (ln >> 4)) ^ (ln & 7)) << 4), a8 = (ln & 7) * 128 + (((hc + (ln >> 3)) ^ (ln & 7)) << 4);
                        const bool first0 = 2 * t > g, first1 = 2 * t + 1 > g;
                        const uint32_t fmask = (first0 ? 0xffffu : 0u) | (first1 ? 0xffff0000u : 0u);
                        const bool edge = item_row(it) == 0;
                        uint32_t q[4][2][4], kf[9][4], vf[9][4];
                        float w[8];
                        mbar_spin(bars + B_GFULL, gph);
#pragma unroll
                        for (int u = 0; u < 4; u++) { ldsm_x4(q[u][0], pl + u * 2048 + a16); ldsm_x4(q[u][1], pl + u * 2048 + (a16 ^ 32)); }
#pragma unroll
                        for (int j = 0; j < 8; j++) w[j] = lds_f32(sb + 4 * LOC_PLANE + 4 * (2 * g + par) + 64 * j);
                        __syncwarp();
                        release_stage(0);
                        mbar_spin(bars + B_GFULL + 8, gph);
#pragma unroll
                        for (int n = 0; n < 9; n++) ldsm_x4(kf[n], pl + GST_BYTES + n * 1024 + a8);
                        __syncwarp();
                        release_stage(1);
                        float s[8][2];
#pragma unroll
                        for (int u = 0; u < 4; u++) {
                            float d[3][4];
#pragma unroll
                            for (int nt = 0; nt < 3; nt++) {
                                mma_k16_init(d[nt], q[u][0], kf[2 * u + nt][0], kf[2 * u + nt][1]);
                                mma_k16(d[nt], q[u][1], kf[2 * u + nt][2], kf[2 * u + nt][3]);
                            }
                            if (u == 0 && edge) { d[0][0] = -INFINITY; d[0][1] = -INFINITY; }
                            s[2 * u][0] = first0 ? d[0][0] : d[1][0]; s[2 * u][1] = first1 ? d[0][1] : d[1][1];
                            s[2 * u + 1][0] = first0 ? d[1][2] : d[2][2]; s[2 * u + 1][1] = first1 ? d[1][3] : d[2][3];
                        }
                        mbar_spin(bars + B_GFULL + 16, gph);
#pragma unroll
                        for (int u = 0; u < 4; u++) { ldsm_x4_t(vf[2 * u], pl + 2 * GST_BYTES + u * 2048 + a16); ldsm_x4_t(vf[2 * u + 1], pl + 2 * GST_BYTES + u * 2048 + (a16 ^ 32)); }
                        ldsm_x4_t(vf[8], pl + 2 * GST_BYTES + 8192 + a8);
                        __syncwarp();
                        release_stage(2);
                        float x[8];
#pragma unroll
                        for (int j = 0; j < 8; j++) x[j] = fmaxf(s[j][0], s[j][1]);
#pragma unroll
                        for (int o = 1; o < 4; o *= 2)
#pragma unroll
                            for (int j = 0; j < 8; j++) x[j] = fmaxf(x[j], __shfl_xor_sync(0xffffffffu, x[j], o));
#pragma unroll
                        for (int j = 0; j < 8; j++) {
                            const float n = x[j] * -LOC_SCALE;
                            s[j][0] = ex2(fmaf(s[j][0], LOC_SCALE, n)); s[j][1] = ex2(fmaf(s[j][1], LOC_SCALE, n));
                            x[j] = s[j][0] + s[j][1];
                        }
#pragma unroll
                        for (int o = 1; o < 4; o *= 2)
#pragma unroll
                            for (int j = 0; j < 8; j++) x[j] += __shfl_xor_sync(0xffffffffu, x[j], o);
                        mbar_spin(bars + B_GFULL + 24, gph);
                        release_stage(3);
                        it = take_item();
                        uint32_t ob[4][8];
#pragma unroll
                        for (int u = 0; u < 4; u++) {
                            const float r0 = rcp(x[2 * u]), r1 = rcp(x[2 * u + 1]), f0 = fmaf(-w[2 * u], r0, r0), f1 = fmaf(-w[2 * u + 1], r1, r1);
                            const uint32_t p0 = pack_bf16(s[2 * u][0] * f0, s[2 * u][1] * f0), p1 = pack_bf16(s[2 * u + 1][0] * f1, s[2 * u + 1][1] * f1);
                            const uint32_t pa[4] = {p0 & fmask, 0, p0 & ~fmask, p1 & fmask};
#pragma unroll
                            for (int c = 0; c < 4; c++) {
                                float ol[4];
                                mma_k16_init(ol, pa, vf[2 * u + (c >> 1)][2 * (c & 1)], vf[2 * u + (c >> 1)][2 * (c & 1) + 1]);
                                mma_k8(ol, 0, p1 & ~fmask, u < 3 ? vf[2 * u + 2 + (c >> 1)][2 * (c & 1)] : vf[8][c]);
                                ob[u][2 * c] = pack_bf16(ol[0], ol[1]);
                                ob[u][2 * c + 1] = pack_bf16(ol[2], ol[3]);
                            }
                        }
                        stage_acquire(0); stage_acquire(1);
#pragma unroll
                        for (int u = 0; u < 4; u++) {
                            stmatrix_x4(stg + par * 8192 + u * 2048 + a16, ob[u][0], ob[u][1], ob[u][2], ob[u][3]);
                            stmatrix_x4(stg + par * 8192 + u * 2048 + (a16 ^ 32), ob[u][4], ob[u][5], ob[u][6], ob[u][7]);
                        }
                        publish_pair();
                        bar_sync(4, 256);
                        gph ^= 1;
                        continue;
                    }
                    mbar_spin(bars + B_GFULL, gph);
                    bool more;
                    do {
                        wgmma_fence();
                        wgmma_ss_n256_tb_init(acc, full_desc(dA), full_desc(dB));
#pragma unroll
                        for (int kk = 1; kk < 4; kk++) wgmma_ss_n256_tb(acc, full_desc(dA) + 2 * kk, full_desc(dB) + 128 * kk, 1);
                        wgmma_commit();
                        const int nk = item_type(it) == T_K || item_type(it) == T_V ? 8 : 16;
                        int k = 1;
                        do {
                            if (pending) {
                                const int kf = k - 1 - wg;
                                if (kf == 0) stage_chunk(0, pk);
                                else if (kf == 1) stage_chunk(1, pk + 16);
                                else if (kf == 3) stage_chunk(0, pk + 32);
                                else if (kf == 4) stage_chunk(1, pk + 48);
                            }
                            gemm_step(acc, dB, k);
                        } while (k < nk);
                        held_b = item_type(it) == T_B;
                        const bool is_q = item_type(it) == T_Q;
                        it = take_item();
                        more = item_type(it) < T_LOCAL;
                        if (more) mbar_spin(bars + B_GFULL, gph);
                        wgmma_wait<0>();
                        fence_regs(acc);
                        release_stage(3);
                        if (is_q) {
#pragma unroll
                            for (int j = 0; j < 128; j++) acc[j] *= SM_SCALE;
                        }
#pragma unroll
                        for (int j = 0; j < 64; j++) pk[j] = pack_bf16(acc[2 * j], acc[2 * j + 1]);
                        pending = true;
                    } while (more);
                } while (item_type(it) < T_LOCAL || (item_type(it) == T_LOCAL && (!held_b || (it & ITEM_READY))));
                if (pending) {
                    stage_acquire(0); stage_acquire(1);
                    write_blocks(std::integral_constant<int, 8>(), 0, pk);
                    const bool borrow = item_type(it) == T_ATTN;
                    if (borrow) {
                        mbar_spin(bars + B_GEMPTY, gph ^ 1); mbar_spin(bars + B_GEMPTY + 8, gph ^ 1);
                    } else {
                        publish_pair();
                        stage_acquire(0); stage_acquire(1);
                    }
                    write_blocks(std::integral_constant<int, 8>(), borrow ? 32768 - SM_STAGING : 0, pk + 32);
                    publish_pair();
                    mbar_arrive_if(lane == 0 && borrow, bars + B_ALT + 8 * wg);
                }
                if (item_type(it) == T_END) { it = take_item(); break; }
            } else {
                float o[64], s[64];
                uint32_t pa[32], pb[32];
                zero_regs(o); zero_regs(s); zero_regs(pa);
                float n0 = 0.f, n1 = 0.f;
                int shifted = 0;
                float l0 = 1.f, l1 = 1.f, f0 = 0.f, f1 = 0.f, g0 = 0.f, g1 = 0.f;
                uint32_t has_pv = 0;
                int first = 0;
                int pending = 0;
                const uint32_t dK = make_desc(sb + SM_KV, 16), dV = make_desc(sb + SM_KV, 16384);
                const uint32_t lane_off = bars_lane - bars + B_AEMPTY - B_AFULL;
                int cur = 0;
                uint32_t qoff = 0;
                const int row = wg * 64 + wq * 16 + (lane >> 2);
                const float thr = (row & 63) - (lane & 3) * 2;
                int peek = 0;
                auto kv_wait = [&](uint32_t n) { mbar_spin(bars + B_AFULL + 16 + 8 * (n & 3), (n >> 2) & 1); };
                auto kv_release = [&](uint32_t n) { mbar_arrive_cluster_if(lane < 2, bars_lane + B_AEMPTY + 16 + 8 * (n & 3)); };
                struct Slot { uint32_t bar, par, off; } slot[4];
                auto align = [&]() {
#pragma unroll
                    for (uint32_t i = 0; i < 4; i++) {
                        const uint32_t n = kvn + (i == 1 ? has_pv : i);
                        slot[i].bar = bars + B_AFULL + 16 + 8 * (n & 3); slot[i].par = (n >> 2) & 1; slot[i].off = (n & 3) * 2048;
                    }
                };
                align();
                auto scale_o = [&]() {
#pragma unroll
                    for (int j = 0; j < 16; j++) { o[4 * j] *= f0; o[4 * j + 1] *= f0; o[4 * j + 2] *= f1; o[4 * j + 3] *= f1; }
                };
                auto pack_o = [&](uint32_t (&v)[32]) {
#pragma unroll
                    for (int j = 0; j < 32; j++) v[j] = pack_bf16(o[2 * j], o[2 * j + 1]);
                };
                auto scales = [&]() { f0 = g0 * rcp(quad_sum(l0)); f1 = g1 * rcp(quad_sum(l1)); };
                auto step = [&](auto even, uint32_t (&pin)[32], uint32_t (&pout)[32], bool fresh, bool diag, bool last) {
                    constexpr bool EVEN = decltype(even)::value;
                    Slot& sk = slot[EVEN ? 0 : 2];
                    Slot& sv = slot[EVEN ? 1 : 3];
                    kvn += EVEN ? 1 + has_pv : 2;
                    mbar_spin(sk.bar, sk.par);
                    bar_sync(1 + wg, 256);
                    qk_gemm(s, dA + qoff, dK + sk.off);
                    if (EVEN && fresh) {
                        scales();
                        g0 = lds_f32(bars + SM_GATE + (ti & 1) * 512 + 4 * row); g1 = lds_f32(bars + SM_GATE + (ti & 1) * 512 + 4 * row + 32);
                        ti++;
                        n0 = 0.f; n1 = 0.f; l0 = 0.f; l1 = 0.f;
                        shifted = 0;
                        if (has_pv) { stage_acquire(0); stage_acquire(1); }
                    }
                    if (!EVEN && pending) {
                        pack_o(pout);
                        write_blocks(std::integral_constant<int, 8>(), 0, pout);
                        publish_pair();
                    }
                    if (last)
                        asm volatile("{\n.reg .pred P, Q;\n"
                                     "mbarrier.test_wait.parity.shared::cta.b64 Q, [%1], %2;\n"
                                     "mbarrier.test_wait.parity.shared::cta.b64 P, [%3], %4;\n"
                                     "ld.shared.u32 %0, [%5];\n"
                                     "@!Q or.b32 %0, %0, 0x10000;\n"
                                     "@!P mov.u32 %0, -1;\n}\n"
                                     : "=r"(peek) : "r"(bars + B_AFULL + 8 * (ti & 1)), "r"((ti >> 1) & 1), "r"(bars + B_IFULL + 8 * (qn % QDEPTH)),
                                       "r"((qn / QDEPTH) & 1), "r"(bars + SM_QUEUE + 4 * (qn % QDEPTH)) : "memory");
                    mbar_spin(sv.bar, sv.par);
                    pv_gemm(o, pin, dV + sv.off, EVEN || !first);
                    bar_arrive(2 - wg, 256);
                    sk.par ^= 1; sv.par ^= 1;
                    wgmma_wait<1>();
                    fence_regs(s);
                    mbar_arrive_cluster_if(lane < 2 && (!EVEN || has_pv), sk.bar + lane_off);
                    mbar_arrive_if(lane == 0 && last, bars + B_AEMPTY + 8 * ((ti - 1) & 1));
                    float r0, r1, x0 = n0, x1 = n1;
#pragma unroll 1
                    for (int mask = diag, redone = 0;; mask = 0, redone = 1) {
                        if (mask | shifted) {
                            if (mask) causal_mask(s, thr, wg);
                            if (shifted) shift_rows(s, x0, x1);
                        }
                        exp_pack(pout, s, r0, r1);
                        if (!__any_sync(0xffffffffu, fmaxf(r0, r1) >= SUM_LIMIT || (EVEN && fresh && !(lane & 3) && !(fminf(s[0], s[2]) >= -REF_RANGE))) || redone) break;
                        row_max(s, x0, x1);
                        if (!(EVEN && fresh)) { x0 = fmaxf(x0, 0.f); x1 = fmaxf(x1, 0.f); }
                        float a0 = ex2(-x0), a1 = ex2(-x1);
                        n0 += x0; n1 += x1;
                        shifted = 1;
                        if (EVEN && fresh) { a0 = 1.f; a1 = 1.f; }
                        l0 *= a0; l1 *= a1;
                        wgmma_wait<0>();
                        fence_regs(o);
#pragma unroll
                        for (int q = 0; q < 16; q++) { o[4 * q] *= a0; o[4 * q + 1] *= a0; o[4 * q + 2] *= a1; o[4 * q + 3] *= a1; }
                    }
                    l0 += r0; l1 += r1;
                    wgmma_wait<0>();
                    fence_regs(o);
                    fence_regs(pin);
                    mbar_arrive_cluster_if(lane < 2, sv.bar + lane_off);
                };
                auto copy_p = [&]() {
#pragma unroll
                    for (int j = 0; j < 32; j++) pa[j] = __float_as_uint(__uint_as_float(pb[j]) + __uint_as_float(prm.zero));
                };
                int rem = 0;
                mbar_spin(bars + B_AFULL + 8 * (ti & 1), (ti >> 1) & 1);
                while (true) {
                    const bool fresh = rem == 0;
                    if (fresh) {
                        if (has_pv) {
                            const int seen = __shfl_sync(0xffffffffu, peek, 0);
                            if (seen >= 0) {
                                mbar_arrive_cluster_if(lane == 0, bars0 + B_IEMPTY + 8 * (qn % QDEPTH));
                                qn++;
                                it = seen & 0xffff;
                            } else {
                                it = take_item();
                            }
                            if (item_row(cur) < 2 || item_type(it) != T_ATTN) break;
                            if (seen & 0x10000) mbar_spin(bars + B_AFULL + 8 * (ti & 1), (ti >> 1) & 1);
                        }
                        cur = it;
                        qoff = (ti & 1) * 2048;
                    }
                    const bool last = fresh ? item_row(cur) == 0 : rem == 1;
                    step(std::true_type(), pa, pb, fresh, item_asc(cur) ? last : fresh, last);
                    first = fresh;
                    if (fresh) {
                        pending = has_pv; has_pv = 1;
                        if (!pending) { kvn -= 2; align(); kvn += 2; slot[0].par ^= 1; slot[1].par ^= 1; }
                        else scale_o();
                        rem = item_row(cur);
                        if (rem == 0) {
                            copy_p();
                            continue;
                        }
                    } else if (--rem == 0) {
                        copy_p();
                        const Slot t0 = slot[0], t1 = slot[1];
                        slot[0] = slot[2]; slot[1] = slot[3]; slot[2] = t0; slot[3] = t1;
                        continue;
                    }
                    step(std::false_type(), pb, pa, false, item_asc(cur) && rem == 1, rem == 1);
                    pending = 0; first = 0;
                    rem--;
                }
                const uint32_t skip = item_asc(cur) & ~item_row(cur) & 1;
                kvn += skip;
                const bool end = item_type(it) == T_END;
#pragma unroll 1
                for (int pass = pending ? 0 : 1; pass < 2; pass++) {
                    if (pass) {
                        kv_wait(kvn);
                        pv_gemm(o, pa, dV + (kvn & 3) * 2048, !first);
                        scales();
                        stage_acquire(0); stage_acquire(1);
                        if (end) it = take_item();
                        wgmma_wait<0>();
                        fence_regs(o);
                        kv_release(kvn);
                        kvn += 1 + skip;
                        scale_o();
                    }
                    pack_o(pb);
                    write_blocks(std::integral_constant<int, 8>(), 0, pb);
                    publish_pair();
                }
                if (end) break;
            }
        }
        if (item_type(it) == T_OUT) {
            float acc[128];
            const uint32_t dB = make_desc(sb + 16384, 8192);
            mbar_spin(bars + B_GFULL, gph);
            wgmma_fence();
            wgmma_ss_n256_tb_init(acc, full_desc(dA), full_desc(dB));
#pragma unroll
            for (int kk = 1; kk < 4; kk++) wgmma_ss_n256_tb(acc, full_desc(dA) + 2 * kk, full_desc(dB) + 128 * kk, 1);
            wgmma_commit();
            uint32_t ln;
            asm volatile("mov.u32 %0, %%laneid;" : "=r"(ln));
            const uint32_t slot = (it & 127) * 32768 + (wg * 128 + wq * 32 + ln) * 16;
            char* const mine = (char*)g_part + slot;
            int k = 1, nk = 80;
            do {
                if (k == K_MEET - 5) {
#pragma unroll
                    for (int j = 0; j < 8; j++) st_b128(mine + j * 4096, 0, 0, 0, 0);
                    __syncwarp();
                }
                if (k == K_SPLIT) nk = take_item() & 127;
                gemm_step(acc, dB, k);
            } while (k < nk);
            float lo[64];
            uint32_t pk[32];
            char* const other = (char*)g_part + (slot ^ (16 * 32768));
            auto fetch_other = [&]() {
#pragma unroll
                for (int j = 0; j < 8; j++) ld_b128(other + j * 4096, pk[4 * j], pk[4 * j + 1], pk[4 * j + 2], pk[4 * j + 3]);
            };
            auto triple = [&](auto first) {
                const uint32_t s0 = k & 3, s1 = (k + 1) & 3, o0 = s0 * (GST_BYTES >> 4), o1 = s1 * (GST_BYTES >> 4);
                wgmma_wait<0>();
                mbar_arrive_cluster_if(ln < (decltype(first)::value ? 2 : 4), bars_lane + B_GEMPTY + 8 * ((k - 1 - (ln >> 1)) & 3));
                mbar_spin(bars + B_GFULL + 8 * s0, gph);
                gph ^= s0 == 3;
                wgmma_fence();
#pragma unroll
                for (int kk = 0; kk < 4; kk++) {
                    if (decltype(first)::value && kk == 0) wgmma_ss_n128_tb_init(lo, full_desc(dA + o0), full_desc(dB + o0));
                    else wgmma_ss_n128_tb(lo, full_desc(dA + o0) + 2 * kk, full_desc(dB + o0) + 128 * kk, 1);
                }
                mbar_spin(bars + B_GFULL + 8 * s1, gph);
                gph ^= s1 == 3;
                wgmma_fence();
#pragma unroll
                for (int kk = 0; kk < 4; kk++) wgmma_ss_n128_tb(lo, full_desc(dA + o0 + 2048) + 2 * kk, full_desc(dB + o1 + 1024) + 128 * kk, 1);
#pragma unroll
                for (int kk = 0; kk < 4; kk++) wgmma_ss_n128_tb(lo, full_desc(dA + o1) + 2 * kk, full_desc(dB + o1) + 128 * kk, 1);
                wgmma_commit();
                k += 2;
            };
            triple(std::true_type());
            fence_regs(acc);
#pragma unroll
            for (int j = 0; j < 8; j++) {
                uint32_t v[4];
#pragma unroll
                for (int i = 0; i < 4; i++) v[i] = pack_bf16(acc[64 + 8 * j + 2 * i], acc[65 + 8 * j + 2 * i]);
                if (j == 4) triple(std::false_type());
                st_b128(mine + j * 4096, ~v[0], v[1], v[2], v[3]);
            }
            triple(std::false_type());
            while (true) {
                fetch_other();
                bool miss = false;
#pragma unroll
                for (int j = 0; j < 8; j++) miss |= pk[4 * j] == 0;
                if (!__any_sync(0xffffffffu, miss)) break;
                while (__any_sync(0xffffffffu, pk[28] == 0)) ld_b128(other + 7 * 4096, pk[28], pk[29], pk[30], pk[31]);
            }
#pragma unroll
            for (int j = 0; j < 32; j++) {
                const uint32_t v = j & 3 ? pk[j] : ~pk[j];
                acc[2 * j] += __uint_as_float(v << 16); acc[2 * j + 1] += __uint_as_float(v & 0xffff0000u);
                asm volatile("" : "+f"(acc[2 * j]), "+f"(acc[2 * j + 1]) :: "memory");
            }
            stage_acquire(0); stage_acquire(1);
            wgmma_wait<0>();
            fence_regs(lo);
            mbar_arrive_cluster_if(ln < 4, bars_lane + B_GEMPTY + 8 * ((k - 1 - (ln >> 1)) & 3));
#pragma unroll
            for (int j = 0; j < 32; j++)
                pk[j] = pack_bf16(acc[2 * j] + lo[2 * j], acc[2 * j + 1] + lo[2 * j + 1]);
            write_blocks(std::integral_constant<int, 8>(), 0, pk);
            __syncwarp();
            uint4* dst = (uint4*)((char*)prm.out + (uint32_t)((item_row(it) * 128 + wg * 64 + wq * 16 + (ln >> 4)) * 2048 + item_col(it) * 256 + (ln & 15) * 16));
#pragma unroll
            for (int j = 0; j < 8; j++) {
                const int r = 2 * j + (ln >> 4);
                uint4 v;
                asm volatile("ld.shared.v4.u32 {%0, %1, %2, %3}, [%4];" : "=r"(v.x), "=r"(v.y), "=r"(v.z), "=r"(v.w)
                             : "r"(stg + wq * 2048 + r * 128 + (ln & 8) * 1024 + (((ln & 7) ^ (r & 7)) << 4)) : "memory");
                dst[j * 256] = v;
            }
        }
    }
}

typedef CUresult (*EncodeFn)(CUtensorMap*, CUtensorMapDataType, cuuint32_t, void*, const cuuint64_t*, const cuuint64_t*,
                             const cuuint32_t*, const cuuint32_t*, CUtensorMapInterleave, CUtensorMapSwizzle,
                             CUtensorMapL2promotion, CUtensorMapFloatOOBfill);

void encode3(EncodeFn fn, CUtensorMap* m, const void* ptr, uint64_t d0, uint64_t d1, uint64_t d2, uint64_t s1, uint64_t s2,
             uint32_t b0, uint32_t b1, uint32_t b2) {
    cuuint64_t dims[3] = {d0, d1, d2};
    cuuint64_t strides[2] = {s1, s2};
    cuuint32_t box[3] = {b0, b1, b2};
    cuuint32_t es[3] = {1, 1, 1};
    fn(m, CU_TENSOR_MAP_DATA_TYPE_BFLOAT16, 3, const_cast<void*>(ptr), dims, strides, box, es, CU_TENSOR_MAP_INTERLEAVE_NONE,
       CU_TENSOR_MAP_SWIZZLE_128B, CU_TENSOR_MAP_L2_PROMOTION_NONE, CU_TENSOR_MAP_FLOAT_OOB_FILL_NONE);
}
void map_act(EncodeFn fn, CUtensorMap* m, const void* p, int rows, int cols, int box_rows) {
    encode3(fn, m, p, cols, rows, 1, (uint64_t)cols * 2, (uint64_t)cols * rows * 2, 64, box_rows, 1);
}
void map_wgt(EncodeFn fn, CUtensorMap* m, const void* p, int K, int N) {
    encode3(fn, m, p, 64, K, N / 64, (uint64_t)N * 2, 128, 64, 64, 2);
}

void build_schedule(Params& p) {
    int n = 0;
    auto add = [&](int type, int col, int row) { p.items[n++] = (uint16_t)(type << 13 | col << 4 | row); };
    auto add_qkv = [&](int c) {
        for (int m = 0; m < 8; m++) add(T_Q, c, m);
        for (int m = 0; m < 8; m++) add(T_K, c, m);
        for (int m = 0; m < 8; m++) add(T_V, c, m);
    };
    int ldist = 200, ldist2 = 260, lstep = 8, beta = 26, tail = 32, late = 6, early = 8, epos = 100;
    int order[16] = {6, 7, 8, 9, 10, 11, 12, 13, 14, 15, 5, 4, 3, 2, 1, 0};
    uint16_t proj[480];
    for (int m = 0; m < 8; m++) for (int c = 0; c < 12; c++) add(T_B, c, m);
    for (int c = 0; c < 16; c++) add_qkv(c);
    for (int i = 0; i < 480; i++) proj[i] = p.items[i];
    n = 0;
    for (int i = 0, l = 0; i < 480; i++) {
        p.items[n++] = proj[i];
        for (; l < 64 && i >= (l < 40 ? ldist + lstep * l / 8 : ldist2 + lstep * (l - 40) / 8); l++) add(T_LOCAL, l & 3, l >> 2);
    }
    const int a0 = n;
    for (int key = 0; key < 4000; key++)
        for (int r = 0; r < 32; r++)
            for (int j = 7; j >= 0; j--)
                if ((j ? (7 - j) * 40 + r * beta : 3999) == key) add(T_ATTN, 2 * order[r >> 1] + (r & 1), j);
    int t0 = n;
    for (int work = 0; work < 32 * 136 * tail / 100;) work += 4 * (p.items[--t0] & 15) + 3;
    for (int i = t0 + 1; i < n; i++)
        for (int j = i; j > t0 && (p.items[j] & 15) > (p.items[j - 1] & 15); j--) { const uint16_t t = p.items[j]; p.items[j] = p.items[j - 1]; p.items[j - 1] = t; }
    for (int r = early - 1; r >= 0; r--) {
        const uint16_t t = p.items[n - 32 + early - 1];
        for (int j = n - 32 + early - 1; j > n - epos; j--) p.items[j] = p.items[j - 1];
        p.items[n - epos] = t;
    }
    for (int moved = 0; moved < 2 && late >= 0; moved++)
        for (int i = a0; i < n; i++)
            if (p.items[i] == (T_ATTN << 13 | (2 * order[15] + moved) << 4 | late)) {
                for (int j = i; j + 1 < n; j++) p.items[j] = p.items[j + 1];
                p.items[n - 1] = (uint16_t)(T_ATTN << 13 | (2 * order[15] + moved) << 4 | late);
                break;
            }
    for (int s = 0, lo = 0, hi = WIDE - 1; s < 80; s++) {
        const int r = s / 2, g = r < 8 ? 32 + r : 2 * order[r / 2 - 4] + (r & 1);
        p.ostep[s >= WIDE ? s : r & 1 ? hi-- : lo++] = (uint8_t)(2 * g + (s & 1));
    }
}

void build_params(Params& p, void* const* d_in, void* d_out) {
    void* fnp = nullptr;
    cudaDriverEntryPointQueryResult qr;
    cudaGetDriverEntryPoint("cuTensorMapEncodeTiled", &fnp, cudaEnableDefault, &qr);
    EncodeFn fn = (EncodeFn)fnp;
    void* scr = nullptr;
    cudaGetSymbolAddress(&scr, g_scr);
    map_act(fn, &p.m[M_X], d_in[0], SEQ, 1024, 128);
    map_act(fn, &p.m[M_C], d_in[1], SEQ, 512, 128);
    map_wgt(fn, &p.m[M_WQ], d_in[2], 1024, 4096);
    map_wgt(fn, &p.m[M_WUK], d_in[3], 512, 4096);
    map_wgt(fn, &p.m[M_WUV], d_in[4], 512, 4096);
    map_wgt(fn, &p.m[M_WO], d_in[5], 4096, 1024);
    map_wgt(fn, &p.m[M_WQKV], d_in[7], 1024, 3072);
    map_wgt(fn, &p.m[M_WOB], d_in[8], 1024, 1024);
    encode3(fn, &p.m[M_SCR_LD], scr, 128, SEQ, G_TOTAL, 256, (uint64_t)SEQ * 256, 64, 128, 1);
    encode3(fn, &p.m[M_SCR_LOC], scr, 256, SEQ / 2, G_TOTAL, 512, (uint64_t)SEQ * 256, 64, 72, 1);
    encode3(fn, &p.m[M_SCR_LOQ], scr, 256, SEQ / 2, G_TOTAL, 512, (uint64_t)SEQ * 256, 64, 64, 1);
    encode3(fn, &p.m[M_SCR_ST], scr, 128, SEQ, G_TOTAL, 256, (uint64_t)SEQ * 256, 64, 64, 1);
    p.x = (const __nv_bfloat16*)d_in[0];
    p.gate_w = (const __nv_bfloat16*)d_in[9];
    p.zero = 0;
    p.wo = (const char*)d_in[5];
    p.out = (__nv_bfloat16*)d_out;
    build_schedule(p);
}

}

extern "C" void kernel_launch(void* const* d_in, const int* in_sizes, int n_in, void* d_out, int out_size) {
    (void)in_sizes; (void)n_in; (void)out_size;
    Params p;
    build_params(p, d_in, d_out);
    cudaFuncSetAttribute(fused_kernel, cudaFuncAttributeMaxDynamicSharedMemorySize, SM_TOTAL);
    fused_kernel<<<NCTA, 384, SM_TOTAL>>>(p);
}
```

```cpp
#include <cuda_runtime.h>
#include <cuda_bf16.h>
#include <cuda.h>
#include <stddef.h>
#include <stdint.h>
#include <type_traits>

namespace {

constexpr int SEQ = 2048;
constexpr int G_Q = 0, G_K = 32, G_V = 64, G_B = 96, G_CTX = G_Q, G_LOC = G_B, G_TOTAL = 120;

__device__ __align__(1024) __nv_bfloat16 g_scr[(size_t)G_TOTAL * SEQ * 128];
__device__ __align__(128) float g_gate[SEQ];

__device__ __forceinline__ uint32_t smem_u32(const void* p) { return (uint32_t)__cvta_generic_to_shared(p); }
__device__ __forceinline__ bool elect_one() {
    uint32_t p;
    asm volatile("{\n.reg .pred P;\nelect.sync _|P, 0xffffffff;\nselp.u32 %0, 1, 0, P;\n}\n" : "=r"(p));
    return p != 0;
}
__device__ __forceinline__ void mbar_init(uint32_t bar, uint32_t count) {
    asm volatile("mbarrier.init.shared::cta.b64 [%0], %1;" :: "r"(bar), "r"(count) : "memory");
}
__device__ __forceinline__ uint32_t cluster_rank() { uint32_t r; asm("mov.u32 %0, %%cluster_ctarank;" : "=r"(r)); return r; }
__device__ __forceinline__ uint32_t map_cta(uint32_t addr, uint32_t cta) {
    uint32_t r; asm("mapa.shared::cluster.u32 %0, %1, %2;" : "=r"(r) : "r"(addr), "r"(cta)); return r;
}
__device__ __forceinline__ void mbar_arrive_cluster_if(bool pred, uint32_t cluster_bar) {
    asm volatile("{\n.reg .pred P;\nsetp.ne.u32 P, %1, 0;\n@P mbarrier.arrive.shared::cluster.b64 _, [%0];\n}\n"
                 :: "r"(cluster_bar), "r"((uint32_t)pred) : "memory");
}
__device__ __forceinline__ void mbar_arrive_cluster_n_if(bool pred, uint32_t cluster_bar, uint32_t count) {
    asm volatile("{\n.reg .pred P;\nsetp.ne.u32 P, %1, 0;\n@P mbarrier.arrive.shared::cluster.b64 _, [%0], %2;\n}\n"
                 :: "r"(cluster_bar), "r"((uint32_t)pred), "r"(count) : "memory");
}
__device__ __forceinline__ void mbar_arrive_if(bool pred, uint32_t bar) {
    asm volatile("{\n.reg .pred P;\nsetp.ne.u32 P, %1, 0;\n@P mbarrier.arrive.shared::cta.b64 _, [%0];\n}\n"
                 :: "r"(bar), "r"((uint32_t)pred) : "memory");
}
__device__ __forceinline__ bool mbar_test(uint32_t bar, uint32_t parity) {
    uint32_t ok;
    asm volatile("{\n.reg .pred P;\nmbarrier.test_wait.parity.shared::cta.b64 P, [%1], %2;\nselp.u32 %0, 1, 0, P;\n}\n"
                 : "=r"(ok) : "r"(bar), "r"(parity) : "memory");
    return ok != 0;
}
__device__ __forceinline__ void mbar_wait(uint32_t bar, uint32_t parity) {
    asm volatile("{\n.reg .pred P;\n.reg .u32 c;\n"
                 "mov.u32 c, 0;\n"
                 "SPIN:\n"
                 "mbarrier.try_wait.parity.shared::cta.b64 P, [%0], %1;\n"
                 "@P bra DONE;\n"
                 "add.u32 c, c, 1;\n"
                 "setp.lt.u32 P, c, 4194304;\n"
                 "@P bra SPIN;\n"
                 "trap;\n"
                 "DONE:\n}\n" :: "r"(bar), "r"(parity) : "memory");
}
__device__ __forceinline__ void mbar_spin(uint32_t bar, uint32_t parity) {
    asm volatile("{\n.reg .pred P;\n"
                 "SPIN:\n"
                 "mbarrier.try_wait.parity.shared::cta.b64 P, [%0], %1;\n"
                 "@!P bra SPIN;\n}\n" :: "r"(bar), "r"(parity) : "memory");
}
__device__ __forceinline__ void bar_sync(int id, int n) { asm volatile("bar.sync %0, %1;" :: "r"(id), "r"(n) : "memory"); }
__device__ __forceinline__ void bar_arrive(int id, int n) { asm volatile("bar.arrive %0, %1;" :: "r"(id), "r"(n) : "memory"); }
__device__ __forceinline__ void fence_proxy_async_smem() { asm volatile("fence.proxy.async.shared::cta;" ::: "memory"); }
__device__ __forceinline__ void warp_expect_tx(uint32_t bar, uint32_t bytes) {
    asm volatile("{\n.reg .pred P;\nelect.sync _|P, 0xffffffff;\n@P mbarrier.arrive.expect_tx.shared::cta.b64 _, [%0], %1;\n}\n"
                 :: "r"(bar), "r"(bytes) : "memory");
}
constexpr uint64_t EVICT_FIRST = 0x12F0000000000000ull;
__device__ __forceinline__ void warp_tma_load(uint32_t dst, const CUtensorMap* map, uint32_t bar, int c0, int c1, int c2, bool stream) {
    if (stream)
        asm volatile("{\n.reg .pred P;\nelect.sync _|P, 0xffffffff;\n"
                     "@P cp.async.bulk.tensor.3d.shared::cluster.global.mbarrier::complete_tx::bytes.L2::cache_hint"
                     " [%0], [%1, {%3, %4, %5}], [%2], %6;\n}\n"
                     :: "r"(dst), "l"(map), "r"(bar), "r"(c0), "r"(c1), "r"(c2), "l"(EVICT_FIRST) : "memory");
    else
        asm volatile("{\n.reg .pred P;\nelect.sync _|P, 0xffffffff;\n"
                     "@P cp.async.bulk.tensor.3d.shared::cluster.global.mbarrier::complete_tx::bytes [%0], [%1, {%3, %4, %5}], [%2];\n}\n"
                     :: "r"(dst), "l"(map), "r"(bar), "r"(c0), "r"(c1), "r"(c2) : "memory");
}
__device__ __forceinline__ void warp_tma_load_pair(uint32_t dst, const CUtensorMap* map, uint32_t bar, int c0, int c1, int c2, bool stream) {
    if (stream)
        asm volatile("{\n.reg .pred P;\nelect.sync _|P, 0xffffffff;\n"
                     "@P cp.async.bulk.tensor.3d.shared::cluster.global.mbarrier::complete_tx::bytes.multicast::cluster.L2::cache_hint"
                     " [%0], [%1, {%3, %4, %5}], [%2], %6, %7;\n}\n"
                     :: "r"(dst), "l"(map), "r"(bar), "r"(c0), "r"(c1), "r"(c2), "h"((uint16_t)3), "l"(EVICT_FIRST) : "memory");
    else
        asm volatile("{\n.reg .pred P;\nelect.sync _|P, 0xffffffff;\n"
                     "@P cp.async.bulk.tensor.3d.shared::cluster.global.mbarrier::complete_tx::bytes.multicast::cluster"
                     " [%0], [%1, {%3, %4, %5}], [%2], %6;\n}\n"
                     :: "r"(dst), "l"(map), "r"(bar), "r"(c0), "r"(c1), "r"(c2), "h"((uint16_t)3) : "memory");
}
__device__ __forceinline__ void warp_bulk_load(uint32_t dst, const void* src, uint32_t bytes, uint32_t bar) {
    asm volatile("{\n.reg .pred P;\nelect.sync _|P, 0xffffffff;\n"
                 "@P cp.async.bulk.shared::cluster.global.mbarrier::complete_tx::bytes [%0], [%1], %2, [%3];\n}\n"
                 :: "r"(dst), "l"(src), "r"(bytes), "r"(bar) : "memory");
}
__device__ __forceinline__ void warp_tma_store(const CUtensorMap* map, uint32_t src, int c0, int c1, int c2, bool stream) {
    if (stream)
        asm volatile("{\n.reg .pred P;\nelect.sync _|P, 0xffffffff;\n"
                     "@P cp.async.bulk.tensor.3d.global.shared::cta.bulk_group.L2::cache_hint [%0, {%2, %3, %4}], [%1], %5;\n}\n"
                     :: "l"(map), "r"(src), "r"(c0), "r"(c1), "r"(c2), "l"(EVICT_FIRST) : "memory");
    else
        asm volatile("{\n.reg .pred P;\nelect.sync _|P, 0xffffffff;\n"
                     "@P cp.async.bulk.tensor.3d.global.shared::cta.bulk_group [%0, {%2, %3, %4}], [%1];\n}\n"
                     :: "l"(map), "r"(src), "r"(c0), "r"(c1), "r"(c2) : "memory");
}
__device__ __forceinline__ void warp_bulk_store(void* dst, uint32_t src, uint32_t bytes) {
    asm volatile("{\n.reg .pred P;\nelect.sync _|P, 0xffffffff;\n"
                 "@P cp.async.bulk.global.shared::cta.bulk_group [%0], [%1], %2;\n}\n" :: "l"(dst), "r"(src), "r"(bytes) : "memory");
}
__device__ __forceinline__ void warp_prefetch(const void* src, uint32_t bytes) {
    asm volatile("{\n.reg .pred P;\nelect.sync _|P, 0xffffffff;\n@P cp.async.bulk.prefetch.L2.global [%0], %1;\n}\n" :: "l"(src), "r"(bytes) : "memory");
}
__device__ __forceinline__ void bulk_commit() { asm volatile("cp.async.bulk.commit_group;" ::: "memory"); }
template <int N> __device__ __forceinline__ void bulk_wait_read() { asm volatile("cp.async.bulk.wait_group.read %0;" :: "n"(N) : "memory"); }
template <int N> __device__ __forceinline__ void bulk_wait() { asm volatile("cp.async.bulk.wait_group %0;" :: "n"(N) : "memory"); }
__device__ __forceinline__ void wgmma_fence() { asm volatile("wgmma.fence.sync.aligned;" ::: "memory"); }
__device__ __forceinline__ void wgmma_commit() { asm volatile("wgmma.commit_group.sync.aligned;" ::: "memory"); }
template <int N> __device__ __forceinline__ void wgmma_wait() { asm volatile("wgmma.wait_group.sync.aligned %0;" :: "n"(N) : "memory"); }
template <int N> __device__ __forceinline__ void fence_regs(float (&d)[N]) {
#pragma unroll
    for (int i = 0; i < N; i++) asm volatile("" : "+f"(d[i]) :: "memory");
}
template <int N> __device__ __forceinline__ void fence_regs(uint32_t (&d)[N]) {
#pragma unroll
    for (int i = 0; i < N; i++) asm volatile("" : "+r"(d[i]) :: "memory");
}
template <int N> __device__ __forceinline__ void reg_dec() { asm volatile("setmaxnreg.dec.sync.aligned.u32 %0;" :: "n"(N)); }
template <int N> __device__ __forceinline__ void reg_inc() { asm volatile("setmaxnreg.inc.sync.aligned.u32 %0;" :: "n"(N)); }
__device__ __forceinline__ uint32_t pack_bf16(float lo, float hi) {
    uint32_t r; asm("cvt.rn.bf16x2.f32 %0, %1, %2;" : "=r"(r) : "f"(hi), "f"(lo)); return r;
}
__device__ __forceinline__ void stmatrix_x4(uint32_t addr, uint32_t r0, uint32_t r1, uint32_t r2, uint32_t r3) {
    asm volatile("stmatrix.sync.aligned.m8n8.x4.shared.b16 [%0], {%1, %2, %3, %4};"
                 :: "r"(addr), "r"(r0), "r"(r1), "r"(r2), "r"(r3) : "memory");
}
__device__ __forceinline__ float ex2(float x) { float y; asm("ex2.approx.ftz.f32 %0, %1;" : "=f"(y) : "f"(x)); return y; }

constexpr uint32_t DESC_HI = (1024 >> 4) | (1u << 30);
__device__ __forceinline__ uint32_t make_desc(uint32_t addr, uint32_t lbo) {
    uint32_t lo = ((addr & 0x3FFFF) >> 4) | ((lbo >> 4) << 16);
    asm volatile("" : "+r"(lo));
    return lo;
}
__device__ __forceinline__ uint64_t full_desc(uint32_t lo) {
    uint64_t d; asm("mov.b64 %0, {%1, %2};" : "=l"(d) : "r"(lo), "r"(DESC_HI)); return d;
}

__device__ __forceinline__ void wgmma_ss_n256_tb_init(float (&d)[128], uint64_t da, uint64_t db) {
    asm volatile("{\n.reg .pred p;\n"
        "setp.ne.b32 p, 0, 0;\n"
        "wgmma.mma_async.sync.aligned.m64n256k16.f32.bf16.bf16 "
        "{%0, %1, %2, %3, %4, %5, %6, %7, %8, %9, %10, %11, %12, %13, %14, %15, %16, %17, %18, %19, %20, "
        "%21, %22, %23, %24, %25, %26, %27, %28, %29, %30, %31, %32, %33, %34, %35, %36, %37, %38, %39, %40, "
        "%41, %42, %43, %44, %45, %46, %47, %48, %49, %50, %51, %52, %53, %54, %55, %56, %57, %58, %59, %60, "
        "%61, %62, %63, %64, %65, %66, %67, %68, %69, %70, %71, %72, %73, %74, %75, %76, %77, %78, %79, %80, "
        "%81, %82, %83, %84, %85, %86, %87, %88, %89, %90, %91, %92, %93, %94, %95, %96, %97, %98, %99, "
        "%100, %101, %102, %103, %104, %105, %106, %107, %108, %109, %110, %111, %112, %113, %114, %115, "
        "%116, %117, %118, %119, %120, %121, %122, %123, %124, %125, %126, %127},"
        " %128, %129, p, 1, 1, 0, 1;\n}\n"
        : "=f"(d[0]), "=f"(d[1]), "=f"(d[2]), "=f"(d[3]), "=f"(d[4]), "=f"(d[5]), "=f"(d[6]), "=f"(d[7]),
        "=f"(d[8]), "=f"(d[9]), "=f"(d[10]), "=f"(d[11]), "=f"(d[12]), "=f"(d[13]), "=f"(d[14]), "=f"(d[15]),
        "=f"(d[16]), "=f"(d[17]), "=f"(d[18]), "=f"(d[19]), "=f"(d[20]), "=f"(d[21]), "=f"(d[22]),
        "=f"(d[23]), "=f"(d[24]), "=f"(d[25]), "=f"(d[26]), "=f"(d[27]), "=f"(d[28]), "=f"(d[29]),
        "=f"(d[30]), "=f"(d[31]), "=f"(d[32]), "=f"(d[33]), "=f"(d[34]), "=f"(d[35]), "=f"(d[36]),
        "=f"(d[37]), "=f"(d[38]), "=f"(d[39]), "=f"(d[40]), "=f"(d[41]), "=f"(d[42]), "=f"(d[43]),
        "=f"(d[44]), "=f"(d[45]), "=f"(d[46]), "=f"(d[47]), "=f"(d[48]), "=f"(d[49]), "=f"(d[50]),
        "=f"(d[51]), "=f"(d[52]), "=f"(d[53]), "=f"(d[54]), "=f"(d[55]), "=f"(d[56]), "=f"(d[57]),
        "=f"(d[58]), "=f"(d[59]), "=f"(d[60]), "=f"(d[61]), "=f"(d[62]), "=f"(d[63]), "=f"(d[64]),
        "=f"(d[65]), "=f"(d[66]), "=f"(d[67]), "=f"(d[68]), "=f"(d[69]), "=f"(d[70]), "=f"(d[71]),
        "=f"(d[72]), "=f"(d[73]), "=f"(d[74]), "=f"(d[75]), "=f"(d[76]), "=f"(d[77]), "=f"(d[78]),
        "=f"(d[79]), "=f"(d[80]), "=f"(d[81]), "=f"(d[82]), "=f"(d[83]), "=f"(d[84]), "=f"(d[85]),
        "=f"(d[86]), "=f"(d[87]), "=f"(d[88]), "=f"(d[89]), "=f"(d[90]), "=f"(d[91]), "=f"(d[92]),
        "=f"(d[93]), "=f"(d[94]), "=f"(d[95]), "=f"(d[96]), "=f"(d[97]), "=f"(d[98]), "=f"(d[99]),
        "=f"(d[100]), "=f"(d[101]), "=f"(d[102]), "=f"(d[103]), "=f"(d[104]), "=f"(d[105]), "=f"(d[106]),
        "=f"(d[107]), "=f"(d[108]), "=f"(d[109]), "=f"(d[110]), "=f"(d[111]), "=f"(d[112]), "=f"(d[113]),
        "=f"(d[114]), "=f"(d[115]), "=f"(d[116]), "=f"(d[117]), "=f"(d[118]), "=f"(d[119]), "=f"(d[120]),
        "=f"(d[121]), "=f"(d[122]), "=f"(d[123]), "=f"(d[124]), "=f"(d[125]), "=f"(d[126]), "=f"(d[127])
        : "l"(da), "l"(db));
}
__device__ __forceinline__ void wgmma_ss_n256_tb(float (&d)[128], uint64_t da, uint64_t db, int scale_d) {
    asm volatile("{\n.reg .pred p;\n"
        "setp.ne.b32 p, %130, 0;\n"
        "wgmma.mma_async.sync.aligned.m64n256k16.f32.bf16.bf16 "
        "{%0, %1, %2, %3, %4, %5, %6, %7, %8, %9, %10, %11, %12, %13, %14, %15, %16, %17, %18, %19, %20, "
        "%21, %22, %23, %24, %25, %26, %27, %28, %29, %30, %31, %32, %33, %34, %35, %36, %37, %38, %39, %40, "
        "%41, %42, %43, %44, %45, %46, %47, %48, %49, %50, %51, %52, %53, %54, %55, %56, %57, %58, %59, %60, "
        "%61, %62, %63, %64, %65, %66, %67, %68, %69, %70, %71, %72, %73, %74, %75, %76, %77, %78, %79, %80, "
        "%81, %82, %83, %84, %85, %86, %87, %88, %89, %90, %91, %92, %93, %94, %95, %96, %97, %98, %99, "
        "%100, %101, %102, %103, %104, %105, %106, %107, %108, %109, %110, %111, %112, %113, %114, %115, "
        "%116, %117, %118, %119, %120, %121, %122, %123, %124, %125, %126, %127},"
        " %128, %129, p, 1, 1, 0, 1;\n}\n"
        : "+f"(d[0]), "+f"(d[1]), "+f"(d[2]), "+f"(d[3]), "+f"(d[4]), "+f"(d[5]), "+f"(d[6]), "+f"(d[7]),
        "+f"(d[8]), "+f"(d[9]), "+f"(d[10]), "+f"(d[11]), "+f"(d[12]), "+f"(d[13]), "+f"(d[14]), "+f"(d[15]),
        "+f"(d[16]), "+f"(d[17]), "+f"(d[18]), "+f"(d[19]), "+f"(d[20]), "+f"(d[21]), "+f"(d[22]),
        "+f"(d[23]), "+f"(d[24]), "+f"(d[25]), "+f"(d[26]), "+f"(d[27]), "+f"(d[28]), "+f"(d[29]),
        "+f"(d[30]), "+f"(d[31]), "+f"(d[32]), "+f"(d[33]), "+f"(d[34]), "+f"(d[35]), "+f"(d[36]),
        "+f"(d[37]), "+f"(d[38]), "+f"(d[39]), "+f"(d[40]), "+f"(d[41]), "+f"(d[42]), "+f"(d[43]),
        "+f"(d[44]), "+f"(d[45]), "+f"(d[46]), "+f"(d[47]), "+f"(d[48]), "+f"(d[49]), "+f"(d[50]),
        "+f"(d[51]), "+f"(d[52]), "+f"(d[53]), "+f"(d[54]), "+f"(d[55]), "+f"(d[56]), "+f"(d[57]),
        "+f"(d[58]), "+f"(d[59]), "+f"(d[60]), "+f"(d[61]), "+f"(d[62]), "+f"(d[63]), "+f"(d[64]),
        "+f"(d[65]), "+f"(d[66]), "+f"(d[67]), "+f"(d[68]), "+f"(d[69]), "+f"(d[70]), "+f"(d[71]),
        "+f"(d[72]), "+f"(d[73]), "+f"(d[74]), "+f"(d[75]), "+f"(d[76]), "+f"(d[77]), "+f"(d[78]),
        "+f"(d[79]), "+f"(d[80]), "+f"(d[81]), "+f"(d[82]), "+f"(d[83]), "+f"(d[84]), "+f"(d[85]),
        "+f"(d[86]), "+f"(d[87]), "+f"(d[88]), "+f"(d[89]), "+f"(d[90]), "+f"(d[91]), "+f"(d[92]),
        "+f"(d[93]), "+f"(d[94]), "+f"(d[95]), "+f"(d[96]), "+f"(d[97]), "+f"(d[98]), "+f"(d[99]),
        "+f"(d[100]), "+f"(d[101]), "+f"(d[102]), "+f"(d[103]), "+f"(d[104]), "+f"(d[105]), "+f"(d[106]),
        "+f"(d[107]), "+f"(d[108]), "+f"(d[109]), "+f"(d[110]), "+f"(d[111]), "+f"(d[112]), "+f"(d[113]),
        "+f"(d[114]), "+f"(d[115]), "+f"(d[116]), "+f"(d[117]), "+f"(d[118]), "+f"(d[119]), "+f"(d[120]),
        "+f"(d[121]), "+f"(d[122]), "+f"(d[123]), "+f"(d[124]), "+f"(d[125]), "+f"(d[126]), "+f"(d[127])
        : "l"(da), "l"(db), "r"(scale_d));
}
__device__ __forceinline__ void wgmma_ss_n128(float (&d)[64], uint64_t da, uint64_t db, int scale_d) {
    asm volatile("{\n.reg .pred p;\n"
        "setp.ne.b32 p, %66, 0;\n"
        "wgmma.mma_async.sync.aligned.m64n128k16.f32.bf16.bf16 "
        "{%0, %1, %2, %3, %4, %5, %6, %7, %8, %9, %10, %11, %12, %13, %14, %15, %16, %17, %18, %19, %20, "
        "%21, %22, %23, %24, %25, %26, %27, %28, %29, %30, %31, %32, %33, %34, %35, %36, %37, %38, %39, %40, "
        "%41, %42, %43, %44, %45, %46, %47, %48, %49, %50, %51, %52, %53, %54, %55, %56, %57, %58, %59, %60, "
        "%61, %62, %63},"
        " %64, %65, p, 1, 1, 0, 0;\n}\n"
        : "+f"(d[0]), "+f"(d[1]), "+f"(d[2]), "+f"(d[3]), "+f"(d[4]), "+f"(d[5]), "+f"(d[6]), "+f"(d[7]),
        "+f"(d[8]), "+f"(d[9]), "+f"(d[10]), "+f"(d[11]), "+f"(d[12]), "+f"(d[13]), "+f"(d[14]), "+f"(d[15]),
        "+f"(d[16]), "+f"(d[17]), "+f"(d[18]), "+f"(d[19]), "+f"(d[20]), "+f"(d[21]), "+f"(d[22]),
        "+f"(d[23]), "+f"(d[24]), "+f"(d[25]), "+f"(d[26]), "+f"(d[27]), "+f"(d[28]), "+f"(d[29]),
        "+f"(d[30]), "+f"(d[31]), "+f"(d[32]), "+f"(d[33]), "+f"(d[34]), "+f"(d[35]), "+f"(d[36]),
        "+f"(d[37]), "+f"(d[38]), "+f"(d[39]), "+f"(d[40]), "+f"(d[41]), "+f"(d[42]), "+f"(d[43]),
        "+f"(d[44]), "+f"(d[45]), "+f"(d[46]), "+f"(d[47]), "+f"(d[48]), "+f"(d[49]), "+f"(d[50]),
        "+f"(d[51]), "+f"(d[52]), "+f"(d[53]), "+f"(d[54]), "+f"(d[55]), "+f"(d[56]), "+f"(d[57]),
        "+f"(d[58]), "+f"(d[59]), "+f"(d[60]), "+f"(d[61]), "+f"(d[62]), "+f"(d[63])
        : "l"(da), "l"(db), "r"(scale_d));
}
__device__ __forceinline__ void wgmma_rs_n128_tb(float (&d)[64], uint32_t a0, uint32_t a1, uint32_t a2, uint32_t a3, uint64_t db, int scale_d) {
    asm volatile("{\n.reg .pred p;\n"
        "setp.ne.b32 p, %69, 0;\n"
        "wgmma.mma_async.sync.aligned.m64n128k16.f32.bf16.bf16 "
        "{%0, %1, %2, %3, %4, %5, %6, %7, %8, %9, %10, %11, %12, %13, %14, %15, %16, %17, %18, %19, %20, "
        "%21, %22, %23, %24, %25, %26, %27, %28, %29, %30, %31, %32, %33, %34, %35, %36, %37, %38, %39, %40, "
        "%41, %42, %43, %44, %45, %46, %47, %48, %49, %50, %51, %52, %53, %54, %55, %56, %57, %58, %59, %60, "
        "%61, %62, %63},"
        " {%64, %65, %66, %67}, %68, p, 1, 1, 1;\n}\n"
        : "+f"(d[0]), "+f"(d[1]), "+f"(d[2]), "+f"(d[3]), "+f"(d[4]), "+f"(d[5]), "+f"(d[6]), "+f"(d[7]),
        "+f"(d[8]), "+f"(d[9]), "+f"(d[10]), "+f"(d[11]), "+f"(d[12]), "+f"(d[13]), "+f"(d[14]), "+f"(d[15]),
        "+f"(d[16]), "+f"(d[17]), "+f"(d[18]), "+f"(d[19]), "+f"(d[20]), "+f"(d[21]), "+f"(d[22]),
        "+f"(d[23]), "+f"(d[24]), "+f"(d[25]), "+f"(d[26]), "+f"(d[27]), "+f"(d[28]), "+f"(d[29]),
        "+f"(d[30]), "+f"(d[31]), "+f"(d[32]), "+f"(d[33]), "+f"(d[34]), "+f"(d[35]), "+f"(d[36]),
        "+f"(d[37]), "+f"(d[38]), "+f"(d[39]), "+f"(d[40]), "+f"(d[41]), "+f"(d[42]), "+f"(d[43]),
        "+f"(d[44]), "+f"(d[45]), "+f"(d[46]), "+f"(d[47]), "+f"(d[48]), "+f"(d[49]), "+f"(d[50]),
        "+f"(d[51]), "+f"(d[52]), "+f"(d[53]), "+f"(d[54]), "+f"(d[55]), "+f"(d[56]), "+f"(d[57]),
        "+f"(d[58]), "+f"(d[59]), "+f"(d[60]), "+f"(d[61]), "+f"(d[62]), "+f"(d[63])
        : "r"(a0), "r"(a1), "r"(a2), "r"(a3), "l"(db), "r"(scale_d));
}
__device__ __forceinline__ void wgmma_ss_n128_tb_init(float (&d)[64], uint64_t da, uint64_t db) {
    asm volatile("{\n.reg .pred p;\n"
        "setp.ne.b32 p, 0, 0;\n"
        "wgmma.mma_async.sync.aligned.m64n128k16.f32.bf16.bf16 "
        "{%0, %1, %2, %3, %4, %5, %6, %7, %8, %9, %10, %11, %12, %13, %14, %15, %16, %17, %18, %19, %20, "
        "%21, %22, %23, %24, %25, %26, %27, %28, %29, %30, %31, %32, %33, %34, %35, %36, %37, %38, %39, %40, "
        "%41, %42, %43, %44, %45, %46, %47, %48, %49, %50, %51, %52, %53, %54, %55, %56, %57, %58, %59, %60, "
        "%61, %62, %63},"
        " %64, %65, p, 1, 1, 0, 1;\n}\n"
        : "=f"(d[0]), "=f"(d[1]), "=f"(d[2]), "=f"(d[3]), "=f"(d[4]), "=f"(d[5]), "=f"(d[6]), "=f"(d[7]),
        "=f"(d[8]), "=f"(d[9]), "=f"(d[10]), "=f"(d[11]), "=f"(d[12]), "=f"(d[13]), "=f"(d[14]), "=f"(d[15]),
        "=f"(d[16]), "=f"(d[17]), "=f"(d[18]), "=f"(d[19]), "=f"(d[20]), "=f"(d[21]), "=f"(d[22]),
        "=f"(d[23]), "=f"(d[24]), "=f"(d[25]), "=f"(d[26]), "=f"(d[27]), "=f"(d[28]), "=f"(d[29]),
        "=f"(d[30]), "=f"(d[31]), "=f"(d[32]), "=f"(d[33]), "=f"(d[34]), "=f"(d[35]), "=f"(d[36]),
        "=f"(d[37]), "=f"(d[38]), "=f"(d[39]), "=f"(d[40]), "=f"(d[41]), "=f"(d[42]), "=f"(d[43]),
        "=f"(d[44]), "=f"(d[45]), "=f"(d[46]), "=f"(d[47]), "=f"(d[48]), "=f"(d[49]), "=f"(d[50]),
        "=f"(d[51]), "=f"(d[52]), "=f"(d[53]), "=f"(d[54]), "=f"(d[55]), "=f"(d[56]), "=f"(d[57]),
        "=f"(d[58]), "=f"(d[59]), "=f"(d[60]), "=f"(d[61]), "=f"(d[62]), "=f"(d[63])
        : "l"(da), "l"(db));
}
__device__ __forceinline__ void wgmma_ss_n128_tb(float (&d)[64], uint64_t da, uint64_t db, int scale_d) {
    asm volatile("{\n.reg .pred p;\n"
        "setp.ne.b32 p, %66, 0;\n"
        "wgmma.mma_async.sync.aligned.m64n128k16.f32.bf16.bf16 "
        "{%0, %1, %2, %3, %4, %5, %6, %7, %8, %9, %10, %11, %12, %13, %14, %15, %16, %17, %18, %19, %20, "
        "%21, %22, %23, %24, %25, %26, %27, %28, %29, %30, %31, %32, %33, %34, %35, %36, %37, %38, %39, %40, "
        "%41, %42, %43, %44, %45, %46, %47, %48, %49, %50, %51, %52, %53, %54, %55, %56, %57, %58, %59, %60, "
        "%61, %62, %63},"
        " %64, %65, p, 1, 1, 0, 1;\n}\n"
        : "+f"(d[0]), "+f"(d[1]), "+f"(d[2]), "+f"(d[3]), "+f"(d[4]), "+f"(d[5]), "+f"(d[6]), "+f"(d[7]),
        "+f"(d[8]), "+f"(d[9]), "+f"(d[10]), "+f"(d[11]), "+f"(d[12]), "+f"(d[13]), "+f"(d[14]), "+f"(d[15]),
        "+f"(d[16]), "+f"(d[17]), "+f"(d[18]), "+f"(d[19]), "+f"(d[20]), "+f"(d[21]), "+f"(d[22]),
        "+f"(d[23]), "+f"(d[24]), "+f"(d[25]), "+f"(d[26]), "+f"(d[27]), "+f"(d[28]), "+f"(d[29]),
        "+f"(d[30]), "+f"(d[31]), "+f"(d[32]), "+f"(d[33]), "+f"(d[34]), "+f"(d[35]), "+f"(d[36]),
        "+f"(d[37]), "+f"(d[38]), "+f"(d[39]), "+f"(d[40]), "+f"(d[41]), "+f"(d[42]), "+f"(d[43]),
        "+f"(d[44]), "+f"(d[45]), "+f"(d[46]), "+f"(d[47]), "+f"(d[48]), "+f"(d[49]), "+f"(d[50]),
        "+f"(d[51]), "+f"(d[52]), "+f"(d[53]), "+f"(d[54]), "+f"(d[55]), "+f"(d[56]), "+f"(d[57]),
        "+f"(d[58]), "+f"(d[59]), "+f"(d[60]), "+f"(d[61]), "+f"(d[62]), "+f"(d[63])
        : "l"(da), "l"(db), "r"(scale_d));
}

enum { M_X = 0, M_C, M_WQ, M_WUK, M_WUV, M_WQKV, M_WO, M_WOB, M_SCR_LD, M_SCR_LOC, M_SCR_LOQ, M_SCR_ST, M_COUNT };
enum { T_Q = 0, T_K, T_V, T_B, T_OUT, T_LOCAL, T_ATTN, T_END };
constexpr int NCTA = 132, NPAIR = NCTA / 2;
constexpr int NITEMS = 480 + 64 + 256;
constexpr int TRIPLES = 3, WIDE = 80 - 3 * TRIPLES;
struct Params {
    CUtensorMap m[M_COUNT];
    const __nv_bfloat16* x;
    const __nv_bfloat16* gate_w;
    const char* wo;
    __nv_bfloat16* out;
    uint32_t zero;
    uint16_t items[NITEMS];
    uint8_t ostep[80];
};
__device__ __forceinline__ int item_type(int it) { return it >> 13; }
__device__ __forceinline__ int item_row(int it) { return it & 15; }
__device__ __forceinline__ int item_col(int it) { return (it >> 4) & 31; }
__device__ __forceinline__ int item_asc(int it) { return (it >> 9) & 1; }
constexpr int ITEM_READY = 1 << 10;

struct __align__(128) Sync {
    unsigned long long count[4];
    __align__(128) unsigned long long ctx[16];
    unsigned next, next_out, done;
    __align__(128) unsigned step[32][2];
    unsigned split[32];
};
__device__ Sync g_sync;
__device__ uint4 g_part[128][8][256];

constexpr uint32_t GST_BYTES = 49152, SM_KV = 65536, SM_STAGING = 196608, SM_BARS = SM_STAGING + 32768;
constexpr uint32_t B_GFULL = 0, B_GEMPTY = 32, B_AFULL = 64, B_AEMPTY = 112, B_SFULL = 160, B_SEMPTY = 192,
                   B_IFULL = 224, B_IEMPTY = 288, B_XFREE = 352, B_WANT = 384, B_MEET = 392, B_HALF = 416,
                   SM_ORDY = 448, SM_QUEUE = 456, B_ALT = 488, B_QFREE = 504, SM_GATE = 512, SM_TOTAL = SM_BARS + 1536;
constexpr int QDEPTH = 8;
constexpr int FIRST_PAIR = 6;
constexpr int K_MEET = 12, K_SPLIT = 26;
constexpr int K_FETCH = 20;
constexpr uint32_t LOC_PLANE = 72 * 128;
constexpr float SM_SCALE = 0.08838834764831845f * 1.4426950408889634f;
constexpr float LOC_SCALE = 0.17677669529663687f * 1.4426950408889634f;
constexpr float SUM_LIMIT = 1152921504606846976.f;
constexpr float REF_RANGE = 32.f;

__device__ __forceinline__ unsigned ld_acquire(const unsigned* p) {
    unsigned v; asm volatile("ld.acquire.gpu.global.u32 %0, [%1];" : "=r"(v) : "l"(p) : "memory"); return v;
}
__device__ __forceinline__ unsigned long long ld_acquire(const unsigned long long* p) {
    unsigned long long v; asm volatile("ld.acquire.gpu.global.u64 %0, [%1];" : "=l"(v) : "l"(p) : "memory"); return v;
}
__device__ __forceinline__ void st_b128(void* p, uint32_t a, uint32_t b, uint32_t c, uint32_t d) {
    asm volatile("{\n.reg .b128 v;\n.reg .b64 lo, hi;\nmov.b64 lo, {%1, %2};\nmov.b64 hi, {%3, %4};\nmov.b128 v, {lo, hi};\n"
                 "st.relaxed.gpu.global.b128 [%0], v;\n}\n" :: "l"(p), "r"(a), "r"(b), "r"(c), "r"(d) : "memory");
}
__device__ __forceinline__ void ld_b128(const void* p, uint32_t& a, uint32_t& b, uint32_t& c, uint32_t& d) {
    asm volatile("{\n.reg .b128 v;\n.reg .b64 lo, hi;\nld.relaxed.gpu.global.b128 v, [%4];\nmov.b128 {lo, hi}, v;\n"
                 "mov.b64 {%0, %1}, lo;\nmov.b64 {%2, %3}, hi;\n}\n" : "=r"(a), "=r"(b), "=r"(c), "=r"(d) : "l"(p) : "memory");
}
__device__ __forceinline__ void spin_guard(unsigned& n) {
    asm volatile("{\n.reg .pred P;\nadd.u32 %0, %0, 1;\nsetp.gt.u32 P, %0, 16777216;\n@P trap;\n}\n" : "+r"(n));
    if (n > 1) __nanosleep(100);
}
__device__ __forceinline__ void red_add(unsigned long long* p, unsigned long long v) {
    asm volatile("red.release.gpu.global.add.u64 [%0], %1;" :: "l"(p), "l"(v) : "memory");
}
__device__ __forceinline__ float rcp(float x) { float y; asm("rcp.approx.ftz.f32 %0, %1;" : "=f"(y) : "f"(x)); return y; }
__device__ __forceinline__ float lds_f32(uint32_t addr) {
    float v; asm volatile("ld.shared.f32 %0, [%1];" : "=f"(v) : "r"(addr) : "memory"); return v;
}
__device__ __forceinline__ void ldsm_x4(uint32_t (&r)[4], uint32_t addr) {
    asm volatile("ldmatrix.sync.aligned.m8n8.x4.shared.b16 {%0, %1, %2, %3}, [%4];"
                 : "=r"(r[0]), "=r"(r[1]), "=r"(r[2]), "=r"(r[3]) : "r"(addr) : "memory");
}
__device__ __forceinline__ void ldsm_x4_t(uint32_t (&r)[4], uint32_t addr) {
    asm volatile("ldmatrix.sync.aligned.m8n8.x4.trans.shared.b16 {%0, %1, %2, %3}, [%4];"
                 : "=r"(r[0]), "=r"(r[1]), "=r"(r[2]), "=r"(r[3]) : "r"(addr) : "memory");
}
__device__ __forceinline__ void mma_k16(float (&d)[4], const uint32_t (&a)[4], uint32_t b0, uint32_t b1) {
    asm("mma.sync.aligned.m16n8k16.row.col.f32.bf16.bf16.f32 {%0,%1,%2,%3}, {%4,%5,%6,%7}, {%8,%9}, {%0,%1,%2,%3};"
        : "+f"(d[0]), "+f"(d[1]), "+f"(d[2]), "+f"(d[3]) : "r"(a[0]), "r"(a[1]), "r"(a[2]), "r"(a[3]), "r"(b0), "r"(b1));
}
__device__ __forceinline__ void mma_k16_init(float (&d)[4], const uint32_t (&a)[4], uint32_t b0, uint32_t b1) {
    asm("{\n.reg .f32 z;\nmov.f32 z, 0f00000000;\n"
        "mma.sync.aligned.m16n8k16.row.col.f32.bf16.bf16.f32 {%0,%1,%2,%3}, {%4,%5,%6,%7}, {%8,%9}, {z,z,z,z};\n}\n"
        : "=f"(d[0]), "=f"(d[1]), "=f"(d[2]), "=f"(d[3]) : "r"(a[0]), "r"(a[1]), "r"(a[2]), "r"(a[3]), "r"(b0), "r"(b1));
}
__device__ __forceinline__ void mma_k8(float (&d)[4], uint32_t a0, uint32_t a1, uint32_t b0) {
    asm("mma.sync.aligned.m16n8k8.row.col.f32.bf16.bf16.f32 {%0,%1,%2,%3}, {%4,%5}, {%6}, {%0,%1,%2,%3};"
        : "+f"(d[0]), "+f"(d[1]), "+f"(d[2]), "+f"(d[3]) : "r"(a0), "r"(a1), "r"(b0));
}
template <typename T, int N> __device__ __forceinline__ void zero_regs(T (&d)[N]) {
#pragma unroll
    for (int i = 0; i < N; i++) d[i] = 0;
}
__device__ __forceinline__ float quad_max(float v) {
    v = fmaxf(v, __shfl_xor_sync(0xffffffffu, v, 1));
    return fmaxf(v, __shfl_xor_sync(0xffffffffu, v, 2));
}
__device__ __forceinline__ float quad_sum(float v) {
    v += __shfl_xor_sync(0xffffffffu, v, 1);
    return v + __shfl_xor_sync(0xffffffffu, v, 2);
}

__device__ __forceinline__ void qk_gemm(float (&s)[64], uint32_t q_lo, uint32_t k_lo) {
    const uint64_t dq = full_desc(q_lo), dk = full_desc(k_lo);
    fence_regs(s);
    wgmma_fence();
#pragma unroll
    for (int kk = 0; kk < 8; kk++) {
        const uint32_t o = (kk >> 2) * 1024 + (kk & 3) * 2;
        wgmma_ss_n128(s, dq + o, dk + o, kk != 0);
    }
    wgmma_commit();
}
__device__ __forceinline__ void pv_gemm(float (&o)[64], uint32_t (&p)[32], uint32_t v_lo, int accumulate) {
    const uint64_t dv = full_desc(v_lo);
    fence_regs(o);
    fence_regs(p);
    wgmma_fence();
#pragma unroll
    for (int kk = 0; kk < 8; kk++)
        wgmma_rs_n128_tb(o, p[4 * kk], p[4 * kk + 1], p[4 * kk + 2], p[4 * kk + 3], dv + kk * 128, kk != 0 || accumulate);
    wgmma_commit();
}
__device__ __forceinline__ void row_max(const float (&s)[64], float& x0, float& x1) {
    float z0 = fmaxf(s[0], s[1]), z1 = fmaxf(s[2], s[3]);
    x0 = fmaxf(s[4], s[5]); x1 = fmaxf(s[6], s[7]);
#pragma unroll
    for (int j = 2; j < 16; j += 2) {
        z0 = fmaxf(z0, fmaxf(s[4 * j], s[4 * j + 1]));
        z1 = fmaxf(z1, fmaxf(s[4 * j + 2], s[4 * j + 3]));
        x0 = fmaxf(x0, fmaxf(s[4 * j + 4], s[4 * j + 5]));
        x1 = fmaxf(x1, fmaxf(s[4 * j + 6], s[4 * j + 7]));
    }
    x0 = quad_max(fmaxf(x0, z0)); x1 = quad_max(fmaxf(x1, z1));
}
__device__ __forceinline__ void exp_pack(uint32_t (&p)[32], const float (&s)[64], float& r0, float& r1) {
#pragma unroll
    for (int j = 0; j < 16; j++) {
        const float e0 = ex2(s[4 * j]), e1 = ex2(s[4 * j + 1]), e2 = ex2(s[4 * j + 2]), e3 = ex2(s[4 * j + 3]);
        if (j == 0) { r0 = e0 + e1; r1 = e2 + e3; }
        else { r0 += e0 + e1; r1 += e2 + e3; }
        p[2 * j] = pack_bf16(e0, e1);
        p[2 * j + 1] = pack_bf16(e2, e3);
    }
}
__device__ __forceinline__ void shift_rows(float (&s)[64], float d0, float d1) {
#pragma unroll
    for (int j = 0; j < 16; j++) { s[4 * j] -= d0; s[4 * j + 1] -= d0; s[4 * j + 2] -= d1; s[4 * j + 3] -= d1; }
}
constexpr float MASKED = -3e38f;
template <int J0>
__device__ __forceinline__ void mask_triangle(float (&s)[64], float thr) {
#pragma unroll
    for (int j = 0; j < 16; j++) {
        const float m = __saturatef((float)(8 * (j >> 1) + (j & 1)) - thr);
        const int i = 4 * (J0 + (j >> 1)) + (j & 1);
        s[i] = fmaf(m, MASKED, s[i]);
        if (j < 14) s[i + 6] = fmaf(m, MASKED, s[i + 6]);
    }
}
__device__ __forceinline__ void causal_mask(float (&s)[64], float thr, int wg) {
    asm volatile("" : "+f"(thr));
    if (wg == 0) {
        mask_triangle<0>(s, thr);
#pragma unroll
        for (int j = 32; j < 64; j++) s[j] += MASKED;
    } else {
        mask_triangle<8>(s, thr);
    }
}

__global__ void __cluster_dims__(2, 1, 1) __launch_bounds__(384, 1) fused_kernel(const __grid_constant__ Params prm) {
    extern __shared__ __align__(1024) uint8_t smem[];
    const uint32_t sb = smem_u32(smem), bars = sb + SM_BARS;
    const int warp = __shfl_sync(0xffffffffu, threadIdx.x >> 5, 0), lane = threadIdx.x & 31;

    const uint32_t rank = cluster_rank();
    const uint32_t bars0 = map_cta(bars, 0), bars_peer = map_cta(bars, rank ^ 1);

    auto first_item = [&]() -> int {
        uint32_t pair = blockIdx.x >> 1;
        asm volatile("" : "+r"(pair));
        const uint32_t m = pair * 43 >> 9;
        return T_B << 13 | (pair - 12 * m) << 4 | (2 * m + rank);
    };
    if (warp == 0) {
        if (elect_one()) {
            for (int k = 0; k < 4; k++) mbar_init(bars + B_GFULL + 8 * k, 1);
            asm volatile("fence.mbarrier_init.release.cluster;" ::: "memory");
            fence_proxy_async_smem();
        }
        __syncwarp();
        const int first_it = __shfl_sync(0xffffffffu, first_item(), 0);
        asm volatile("barrier.cluster.arrive.relaxed.aligned;" ::: "memory");
#pragma unroll
        for (int k = 0; k < 2; k++) {
            const uint32_t dst = sb + k * GST_BYTES, fb = bars + B_GFULL + 8 * k;
            warp_expect_tx(fb, GST_BYTES);
            warp_tma_load(dst + 16384, &prm.m[M_WQKV], fb, 0, k * 64, item_col(first_it) * 4, false);
            warp_tma_load(dst, &prm.m[M_X], fb, k * 64, item_row(first_it) * 128, 0, false);
            warp_tma_load(dst + 32768, &prm.m[M_WQKV], fb, 0, k * 64, item_col(first_it) * 4 + 2, false);
        }
    }
    if (threadIdx.x == 32) {
        for (int i = 0; i < 4; i++) { mbar_init(bars + B_GEMPTY + 8 * i, 16); mbar_init(bars + B_XFREE + 8 * i, 1); }
        for (int i = 0; i < 6; i++) { mbar_init(bars + B_AFULL + 8 * i, 1); mbar_init(bars + B_AEMPTY + 8 * i, i < 2 ? 8 : 16); }
        for (int i = 0; i < 4; i++) { mbar_init(bars + B_SFULL + 8 * i, 4); mbar_init(bars + B_SEMPTY + 8 * i, 1); }
        for (int i = 0; i < QDEPTH; i++) { mbar_init(bars + B_IFULL + 8 * i, 1); mbar_init(bars + B_IEMPTY + 8 * i, 23); }
        mbar_init(bars + B_WANT, 2); mbar_init(bars + B_MEET, 1);
        for (int i = 0; i < 4; i++) mbar_init(bars + B_HALF + 8 * i, 1);
        mbar_init(bars + B_ALT, 4); mbar_init(bars + B_ALT + 8, 4); mbar_init(bars + B_QFREE, 2);
        asm volatile("st.shared.u64 [%0], 0;" :: "r"(bars + SM_ORDY) : "memory");
        asm volatile("fence.mbarrier_init.release.cluster;\nfence.acq_rel.cta;" ::: "memory");
    }
    __syncwarp();
    if (warp != 0) asm volatile("barrier.cluster.arrive.relaxed.aligned;" ::: "memory");
    asm volatile("barrier.cluster.wait.acquire.aligned;" ::: "memory");

    uint32_t qn = 0;
    auto next_item = [&](bool releaser, bool bounded = true) -> int {
        const uint32_t slot = qn % QDEPTH;
        if (bounded) mbar_wait(bars + B_IFULL + 8 * slot, (qn / QDEPTH) & 1);
        else mbar_spin(bars + B_IFULL + 8 * slot, (qn / QDEPTH) & 1);
        uint32_t it;
        asm volatile("ld.shared.u32 %0, [%1];" : "=r"(it) : "r"(bars + SM_QUEUE + 4 * slot) : "memory");
        mbar_arrive_cluster_if(releaser, bars0 + B_IEMPTY + 8 * slot);
        qn++;
        return it;
    };

    if (warp < 4) {
        reg_dec<40>();
        if (warp == 0) {
            {
                uint32_t gph = 1;
                const uint32_t prank = __shfl_sync(0xffffffffu, rank, 0);
                auto request = [&]() { mbar_arrive_cluster_if(lane == 0, bars0 + B_WANT); };
                auto take_item = [&]() -> int { return __shfl_sync(0xffffffffu, next_item(lane == 0), 0); };
                auto inputs_seen = [&](uint32_t word, unsigned& n) -> uint32_t {
                    uint32_t v;
                    spin_guard(n);
                    asm volatile("ld.acquire.cta.shared.u32 %0, [%1];" : "=r"(v) : "r"(bars + SM_ORDY + 4 * word) : "memory");
                    return __shfl_sync(0xffffffffu, v, 0);
                };
                uint32_t oneed = 0;
                auto wait_inputs = [&](int it) {
                    if (it & ITEM_READY) return;
                    oneed += 256;
                    for (unsigned n = 0; inputs_seen(1, n) < oneed;) {}
                };
                int nxt = first_item();
                for (int k0 = 2; item_type(nxt) <= T_LOCAL; k0 = 0) {
                    const int type = item_type(nxt), m = item_row(nxt), c = item_col(nxt);
                    if (type == T_LOCAL) {
                        wait_inputs(nxt);
                        request();
#pragma unroll 1
                        for (uint32_t st = 0; st < 4; st++) {
                            mbar_wait(bars + B_GEMPTY + 8 * st, gph);
                            const uint32_t dst = sb + st * GST_BYTES, fb = bars + B_GFULL + 8 * st;
                            warp_expect_tx(fb, st == 0 ? 32768 + 512 : st == 3 ? 0 : 4 * LOC_PLANE);
                            if (st == 3) break;
                            if (st == 0) warp_bulk_load(dst + 4 * LOC_PLANE, &g_gate[m * 128], 512, fb);
#pragma unroll 1
                            for (int i = 0; i < 4; i++)
                                warp_tma_load(dst + i * LOC_PLANE, &prm.m[st ? M_SCR_LOC : M_SCR_LOQ], fb, i * 64, m * 64 - (st ? 8 : 0), G_B + 8 * st + c, true);
                        }
                        gph ^= 1;
                    } else {
                        const int nk = type == T_K || type == T_V ? 8 : 16;
                        const CUtensorMap* ma = &prm.m[nk == 8 ? M_C : M_X];
                        const CUtensorMap* mb = &prm.m[M_WQ + type];
#pragma unroll 1
                        for (int k = k0; k < nk; k++) {
                            if (k == nk - 3) request();
                            const uint32_t st = k & 3, dst = sb + st * GST_BYTES, fb = bars + B_GFULL + 8 * st;
                            mbar_wait(bars + B_GEMPTY + 8 * st, gph);
                            warp_expect_tx(fb, GST_BYTES);
                            warp_tma_load(dst, ma, fb, k * 64, m * 128, 0, c == 15 && type != T_K);
                            warp_tma_load_pair(dst + 16384 + prank * 16384, mb, fb, 0, k * 64, c * 4 + 2 * prank, type != T_B || m >= 14);
                            if (st == 3) gph ^= 1;
                        }
                    }
                    nxt = take_item();
                }
                uint32_t kv = 0, kvph = 1;
                uint32_t qc = 0;
                auto a_parity = [&](uint32_t b) { return b < 2 ? (((qc + 1 - b) >> 1) & 1) ^ 1 : kvph ^ (b - 2 < kv); };
                const CUtensorMap* tile_map = &prm.m[M_SCR_LD];
                asm volatile("" : "+l"(tile_map));
                {
                    bool need_g = true, more = true;
                    int pv_grp = -1, pv_row = 0;
                    int pv_shared = 0;
                    bool peer_longer = false;
                    int m = 0, c = 0, asc = 0, nu = 0, uend = 0, ureq = -1, ufetch = 0;
#pragma unroll 1
                    for (int u = 0;; u++) {
                        if (u == ufetch) {
                            if (qc) nxt = take_item();
                            if (item_type(nxt) == T_ATTN) {
                                wait_inputs(nxt);
                                const uint32_t b = qc & 1, dst = sb + b * 32768, fb = bars + B_AFULL + 8 * b, row = item_row(nxt) * 128;
                                mbar_wait(bars + (qc == 0 ? B_GEMPTY : qc == 1 ? B_QFREE : B_AEMPTY + 8 * b), qc == 0 ? gph : qc == 1 ? 0 : a_parity(b));
                                warp_expect_tx(fb, 32768 + 512);
                                warp_tma_load(dst, tile_map, fb, 0, row, G_Q + item_col(nxt), false);
                                warp_tma_load(dst + 16384, tile_map, fb, 64, row, G_Q + item_col(nxt), false);
                                warp_bulk_load(bars + SM_GATE + b * 512, &g_gate[row], 512, fb);
                                qc++;
                            }
                        }
                        if (u == uend) {
                            if (!more) break;
                            more = item_type(nxt) == T_ATTN;
                            m = item_row(nxt); c = item_col(nxt); asc = item_asc(nxt);
                            nu = more ? 2 * m + 2 : 0;
                            uend = nu + ((more ? m < 2 : pv_grp >= 0) ? 3 : 0);
                            ureq = 2 * max(m - 2 - (asc & m), 0);
                            ufetch = !more ? -1 : m ? 2 * m : uend;
                            u = -1;
                            continue;
                        }
                        int grp = pv_grp, row = pv_row;
                        int shared = pv_shared;
                        if (u >= nu) {
                            if (u == nu + 1) pv_grp = -1;
                            else if (peer_longer) { grp = -1; shared = 0; }
                            else continue;
                        } else {
                            const int j = asc ? u >> 1 : m - (u >> 1);
                            if (u & 1) {
                                pv_grp = G_V + c; pv_row = j * 128; pv_shared = (m | 1) - j;
                                peer_longer = asc & ~m & 1;
                                if (u == nu - 1 && (m & 1) && item_type(nxt) == T_END) mbar_arrive_cluster_n_if(lane == 0, bars0 + B_WANT, 2);
                                if (grp < 0) continue;
                            } else {
                                if (u == ureq) request();
                                grp = G_K + c; row = j * 128; shared = (m | 1) - j;
                            }
                        }
                        uint32_t fb = bars + B_AFULL + 16 + 8 * kv, mine = sb + SM_KV + kv * 32768 + prank * 16384;
                        int c_mine = prank * 64;
                        asm volatile("" : "+r"(mine), "+r"(fb), "+r"(row), "+r"(grp), "+r"(c_mine));
                        mbar_wait(need_g ? bars + B_GEMPTY + 8 + 8 * kv : fb + B_AEMPTY - B_AFULL, need_g ? gph : kvph);
                        warp_expect_tx(fb, grp < 0 ? 0 : 32768);
                        if (shared) {
                            warp_tma_load_pair(mine, tile_map, fb, c_mine, row, grp, shared == 1);
                        } else if (grp >= 0) {
                            warp_tma_load(mine, tile_map, fb, c_mine, row, grp, true);
                            warp_tma_load(mine + 16384 - prank * 32768, tile_map, fb, 64 - c_mine, row, grp, true);
                        } else {
                            mbar_arrive_cluster_n_if(lane < 2, map_cta(fb, lane & 1) + B_AEMPTY - B_AFULL, 8);
                        }
                        if (kv == 2) need_g = false;
                        if (++kv == 4) { kv = 0; kvph ^= 1; }
                    }
                }
                if (!qc) request();
                const int it = take_item();
                int nk = 0;
                if (item_type(it) == T_OUT) {
                    const int m = item_row(it), c = item_col(it), half = c & 1;
                    nk = 80;
                    for (int k = 0; k < nk; k++) {
                        if (k == K_SPLIT) nk = 2 * TRIPLES + (take_item() & 127);
                        const int kn = k + 2 * TRIPLES - nk, first = kn >= 0 && !(kn & 1);
                        const int s = kn >= 0 ? WIDE + (3 * kn + 1) / 2 : half ? WIDE - 1 - k : k;
                        const uint32_t sa = prm.ostep[s], sa2 = prm.ostep[s + first], sw = prm.ostep[s - (kn >= 0 && !first ? prank : 0)];
                        const uint32_t need = 1u << (sa >> 1 & 31) | 1u << (sa2 >> 1 & 31);
                        for (unsigned n = 0; need & ~inputs_seen(sa >> 6, n);) {}
                        const uint32_t st = k & 3;
                        uint32_t dst = sb + st * GST_BYTES, fb = bars + B_GFULL + 8 * st;
                        uint32_t dstb = dst + 16384 + (first ? 0 : prank * 16384), skipb = first && (kn >> 1 & 1) != prank;
                        int a0 = (sa & 1) * 64, a1 = m * 128, a2 = (sa >> 1) + (sa < 64 ? G_CTX : G_LOC - 32);
                        int b1 = (sw & 63) * 64, b2 = (c >> 1) * 4 + 2 * (kn >= 0 ? half : half ^ prank);
                        const CUtensorMap* mb = &prm.m[sw >= 64 ? M_WOB : M_WO];
                        asm volatile("" : "+r"(dst), "+r"(fb), "+r"(dstb), "+r"(skipb), "+r"(a0), "+r"(a1), "+r"(a2), "+r"(b1), "+r"(b2), "+l"(mb));
                        if (k < 4) {
#pragma unroll 1
                            for (uint32_t i = 0, b = (3 * st) >> 1; i < 3; i++, b++) mbar_wait(bars + (i == 2 ? B_QFREE : B_AEMPTY + 8 * b), i == 2 ? 0 : a_parity(b));
                            mbar_arrive_cluster_if(lane == 0, bars_peer + B_XFREE + 8 * st);
                            mbar_wait(bars + B_XFREE + 8 * st, 0);
                        }
                        mbar_wait(bars + B_GEMPTY + 8 * st, gph);
                        warp_expect_tx(fb, GST_BYTES);
                        warp_tma_load(dst, tile_map, fb, a0, a1, a2, true);
                        if (!skipb) warp_tma_load_pair(dstb, mb, fb, 0, b1, b2, false);
                        if (first) warp_tma_load(dst + 32768, tile_map, fb, (sa2 & 1) * 64, a1, G_CTX + (sa2 >> 1), true);
                        if (k < K_SPLIT && lane == 0 && !prank)
                            asm volatile("st.relaxed.gpu.global.u32 [%0], %1;" :: "l"(&g_sync.step[0][0] + m * 4 + c), "r"(k) : "memory");
                        mbar_arrive_if(k == K_MEET && lane == 0, bars + B_MEET);
                        if ((uint32_t)(k - K_FETCH) < (3 * TRIPLES + 1) / 2) {
                            const uint32_t g = prm.ostep[79 - 2 * (k - K_FETCH)] >> 1;
                            warp_prefetch((const char*)g_scr + (uint32_t)((G_CTX + g) * (SEQ * 256) + m * 32768 + c * 4096), 4096);
                            warp_prefetch(prm.wo + (uint32_t)(g * 262144 + (m * 8 + c) * 2048), 2048);
                        }
                        if (st == 3) gph ^= 1;
                    }
                    for (unsigned n = 0; ~inputs_seen(0, n) || inputs_seen(1, n) != 255;) {}
                }
#pragma unroll 1
                for (uint32_t st = 0; st < 4; st++) { mbar_wait(bars + B_GEMPTY + 8 * st, gph ^ (st < (nk & 3))); mbar_wait(bars + B_AEMPTY + 16 + 8 * st, a_parity(2 + st)); }
                unsigned left = 0;
                if (lane == 0) asm volatile("atom.relaxed.gpu.global.add.u32 %0, [%1], 1;" : "=r"(left) : "l"(&g_sync.done) : "memory");
                if (__shfl_sync(0xffffffffu, left, 0) == NCTA - 1)
#pragma unroll 1
                    for (uint32_t i = lane * 8; i < sizeof(Sync); i += 256) *(unsigned long long*)((char*)&g_sync + i) = 0;
            }
        } else if (warp <= 2) {
            if (blockIdx.x < SEQ / 16) {
                const uint32_t r0 = 16 * blockIdx.x + 8 * (warp - 1), gbuf = bars + SM_GATE + 4 * (r0 & 15);
                float z[4];
                mbar_wait(bars + B_GFULL + 24, 0);
#pragma unroll 1
                for (uint32_t i = 0; i < 8; i++) {
                    const uint32_t off = (i & 3) * 512 + lane * 16;
                    const uint4* xp = (const uint4*)((const char*)prm.x + ((r0 + (i & 4)) * 2048 + off));
                    const uint4 wv = __ldg((const uint4*)((const char*)prm.gate_w + off));
                    uint4 xv[4];
#pragma unroll
                    for (int r = 0; r < 4; r++) { xv[r] = __ldg(xp + r * 128); if (!(i & 3)) z[r] = 0.f; }
                    const uint32_t ws[4] = {wv.x, wv.y, wv.z, wv.w};
#pragma unroll
                    for (int e = 0; e < 4; e++)
#pragma unroll
                        for (int r = 0; r < 4; r++) {
                            const uint32_t xs = e == 0 ? xv[r].x : e == 1 ? xv[r].y : e == 2 ? xv[r].z : xv[r].w;
                            z[r] = fmaf(__uint_as_float(xs << 16), __uint_as_float(ws[e] << 16), z[r]);
                            z[r] = fmaf(__uint_as_float(xs & 0xffff0000u), __uint_as_float(ws[e] & 0xffff0000u), z[r]);
                        }
                    if ((i & 3) == 3) {
#pragma unroll
                        for (int o = 16; o > 0; o >>= 1)
#pragma unroll
                            for (int r = 0; r < 4; r++) z[r] += __shfl_xor_sync(0xffffffffu, z[r], o);
                        const float zr = lane & 2 ? (lane & 1 ? z[3] : z[2]) : (lane & 1 ? z[1] : z[0]);
                        asm volatile("st.shared.f32 [%0], %1;" :: "r"(gbuf + 4 * ((i & 4) + (lane & 3))), "f"(1.f / (1.f + __expf(-zr))) : "memory");
                    }
                }
                fence_proxy_async_smem();
                __syncwarp();
                warp_bulk_store((char*)g_gate + 4 * r0, gbuf, 32);
                bulk_commit();
                bulk_wait<0>();
                __syncwarp();
                if (lane == 0) red_add(&g_sync.count[3], 1);
            }
            __syncwarp();
            {
                const int w = warp - 1;
                uint32_t sph = 0, nann = 0;
                int unsent = 0, nunsent = 0;
                bool urgent = false;
                auto announce = [&]() {
                    if (!urgent) return;
                    bulk_wait<0>();
                    __syncwarp();
                    const uint32_t hb = bars + B_HALF + 8 * (nann & 3);
                    if (w == 0) {
                        mbar_arrive_if(lane == 0, hb);
                    } else {
                        mbar_wait(hb, (nann >> 2) & 1);
                        const uint32_t type = item_type(unsent), m = item_row(unsent), c = item_col(unsent);
                        const uint32_t word = type < T_B ? c >> 3 : type == T_B ? 2 : offsetof(Sync, ctx) / 8 + m;
                        const uint32_t bit = type < T_B ? 8 * (c & 7) : type == T_B ? 4 * m : type == T_LOCAL ? 32 + c : c;
                        if (lane < nunsent) red_add((unsigned long long*)((char*)&g_sync + 8 * word), 1ull << bit);
                        __syncwarp();
                    }
                    nann++;
                    nunsent = 0; urgent = false;
                };
                int held = first_item(), it;
                bool qfree = false;
                do {
                    if (!__all_sync(0xffffffffu, mbar_test(bars + B_IFULL + 8 * (qn % QDEPTH), (qn / QDEPTH) & 1))) announce();
                    it = __shfl_sync(0xffffffffu, next_item(lane == 0), 0);
                    const int itype = item_type(it);
                    const bool keep_held = itype == T_LOCAL && (item_type(held) != T_B || (it & ITEM_READY));
                    if (itype >= T_ATTN && held < 0) {
                        urgent = nunsent;
                        mbar_arrive_if(lane == 0 && !qfree, bars + B_QFREE);
                        qfree = true;
                    }
#pragma unroll 1
                    for (int pass = held < 0 || keep_held; pass < 2; pass++) {
                        if (pass && (itype < T_OUT || itype == T_END)) break;
                        const int cur = pass ? it : held, type = item_type(cur), m = item_row(cur), c = item_col(cur);
                        const bool local = type == T_LOCAL;
                        const int grp = pass ? (local ? G_LOC : G_CTX) + c : type * 32 + 2 * c;
#pragma unroll 1
                        for (int i = 0; i < 4 - 2 * pass; i++) {
                            const int b = i & 1;
                            const bool alt = i >= 2 && itype == T_ATTN;
                            const uint32_t full = bars + (alt ? B_ALT + 8 * w : B_SFULL + 16 * w + 8 * b), par = alt ? 0 : sph;
                            if (i == 3 - 2 * pass || !__all_sync(0xffffffffu, mbar_test(full, par))) announce();
                            mbar_wait(full, par);
                            fence_proxy_async_smem();
                            warp_tma_store(&prm.m[local ? M_SCR_LOQ : M_SCR_ST], sb + (alt ? 32768 : SM_STAGING) + w * 16384 + b * 8192,
                                         local ? b * 128 + w * 64 : b * 64, local ? m * 64 : m * 128 + w * 64, grp + (i >> 1), local || (type < T_B && c < FIRST_PAIR));
                            bulk_commit();
                            bulk_wait_read<0>();
                            __syncwarp();
                            mbar_arrive_if(lane == 0 && !alt, bars + B_SEMPTY + 16 * w + 8 * b);
                            sph ^= b & !alt;
                        }
                        mbar_arrive_if(lane == 0 && !qfree && itype >= T_ATTN, bars + B_QFREE);
                        qfree |= itype >= T_ATTN;
                        if (lane == nunsent) unsent = cur;
                        nunsent++;
                        urgent = nunsent == 32 || !local;
                    }
                    if (!keep_held) held = itype < T_OUT ? it : -1;
                } while (item_type(it) != T_END);
                announce();
                if (item_type(next_item(lane == 0)) == T_OUT) {
                    if (w) {
                        mbar_wait(bars + B_MEET, 0);
                        asm volatile("fence.acq_rel.gpu;" ::: "memory");
                        mbar_arrive_cluster_if(lane == 0, bars0 + B_WANT);
                    }
                    next_item(lane == 0);
                }
            }
        } else {
            if (elect_one()) {
                uint32_t ordy = 0;
                unsigned long long cnt_lo = 0, cnt_hi = 0;
                int late = 0;
                auto refresh = [&]() {
                    if (!late && cnt_lo == 0xccccccccccccccccull && cnt_hi == SEQ / 8) late = 1;
                    asm volatile("ld.acquire.gpu.global.v2.u64 {%0, %1}, [%2];" : "=l"(cnt_lo), "=l"(cnt_hi) : "l"(late ? &g_sync.count[0] : &g_sync.count[2]) : "memory");
                };
                auto inputs_ready = [&](int it) -> bool {
                    const int m = item_row(it), c = item_col(it);
                    if (item_type(it) == T_ATTN) return late && ((c < 16 ? cnt_lo : cnt_hi) >> (4 * (c & 14)) & 255) == 48;
                    return late || (cnt_hi == SEQ / 8 && (cnt_lo >> (4 * m) & 15) == 12 && (cnt_lo >> (4 * max(m - 1, 0)) & 15) == 12);
                };
                auto publish = [&](int it, int step) {
                    const uint32_t slot = qn % QDEPTH;
                    mbar_wait(bars + B_IEMPTY + 8 * slot, ((qn / QDEPTH) & 1) ^ 1);
                    for (uint32_t r = 0; r < 2; r++) {
                        const uint32_t rb = map_cta(bars, r);
                        asm volatile("mbarrier.arrive.expect_tx.shared::cluster.b64 _, [%0], 4;" :: "r"(rb + B_IFULL + 8 * slot) : "memory");
                        asm volatile("st.async.shared::cluster.mbarrier::complete_tx::bytes.u32 [%0], %1, [%2];"
                                     :: "r"(rb + SM_QUEUE + 4 * slot), "r"(it + r * step), "r"(rb + B_IFULL + 8 * slot) : "memory");
                    }
                    qn++;
                };
                int asc = 1;
                int it;
                do {
                    if (rank == 0) {
                        mbar_wait(bars + B_WANT, qn & 1);
                        unsigned i;
                        asm volatile("atom.relaxed.gpu.global.add.u32 %0, [%1], 1;" : "=r"(i) : "l"(&g_sync.next) : "memory");
                        if (cnt_lo != 0x3030303030303030ull || cnt_hi != cnt_lo) refresh();
                        i += NPAIR;
                        const int pit = i < NITEMS ? prm.items[i] : T_END << 13, type = item_type(pit);
                        int step = type == T_LOCAL ? 16 : 1;
                        it = pit + (pit & (step == 1 ? 15 : 0x1f0));
                        if (type == T_ATTN) {
                            if (!asc) { it += 1; step = -1; }
                            it |= asc << 9;
                        }
                        asc = type != T_ATTN || item_row(pit) == 0 || !asc;
                        if (inputs_ready(it)) it |= ITEM_READY;
                        publish(it, step);
                    } else {
                        it = next_item(true);
                    }
                    if ((item_type(it) == T_ATTN || item_type(it) == T_LOCAL) && !(it & ITEM_READY)) {
                        unsigned n = 0;
                        while (!inputs_ready(it)) { refresh(); spin_guard(n); }
                        asm volatile("st.release.cta.shared.u32 [%0], %1;" :: "r"(bars + SM_ORDY + 4), "r"(ordy += 256) : "memory");
                    }
                } while (item_type(it) != T_END);
                if (rank == 0) {
                    mbar_wait(bars + B_WANT, qn & 1);
                    const unsigned i = atomicAdd(&g_sync.next_out, 1u), t = i < 32 ? 31 - i : i - 32;
                    it = i < 64 ? T_OUT << 13 | ((t & 3) * 2 + (i >> 5)) << 4 | (t >> 2) * 2 : T_END << 13;
                    publish(it, 1);
                } else {
                    it = next_item(true);
                }
                if (item_type(it) == T_OUT) {
                    const uint32_t m = item_row(it), half = item_col(it) & 1, tile = m * 2 + (item_col(it) >> 1);
                    unsigned* split = (unsigned*)((char*)g_sync.split + 4 * tile);
                    unsigned long long rdy = 0;
                    int state = rank ? 2 : 0;
                    for (unsigned n = 0; rdy != 0xffffffffffull || state < 2; spin_guard(n)) {
                        if (rdy != 0xffffffffffull) {
                            rdy = ld_acquire((const unsigned long long*)((char*)g_sync.ctx + 8 * m));
                            asm volatile("st.release.cta.shared.u64 [%0], %1;" :: "r"(bars + SM_ORDY), "l"(rdy) : "memory");
                        }
                        unsigned steps = 0;
                        if (state == 1) {
                            steps = ld_acquire(split);
                        } else if (state == 0 && mbar_test(bars + B_WANT, qn & 1)) {
                            state = 1;
                            unsigned seen;
                            asm volatile("atom.acq_rel.gpu.global.exch.b32 %0, [%1], 1;" : "=r"(seen) : "l"(split) : "memory");
                            if (seen) {
                                const unsigned long long v = ld_acquire((const unsigned long long*)((char*)g_sync.step + 8 * tile));
                                const int d = (int)(v >> 32) - (int)v;
                                steps = (WIDE + min(max(half ? d : -d, -12), 12)) >> 1;
                                atomicExch(split, WIDE - steps);
                            }
                        }
                        if (steps > 1) { publish(T_END << 13 | steps, 0); state = 2; }
                    }
                    if (rank) next_item(true);
                }
                #pragma unroll 1
                for (uint32_t n = qn; n < qn + QDEPTH && rank == 0; n++) mbar_wait(bars + B_IEMPTY + 8 * (n % QDEPTH), ((n / QDEPTH) & 1) ^ 1);
            }
        }
    } else {
        reg_inc<232>();
        const int wg = (warp >> 2) - 1, wq = warp & 3;
        uint32_t gph = 0;
        uint32_t kvn = 0;
        const uint32_t dA = make_desc(sb + wg * 8192, 16);
        uint32_t ti = 0;
        uint32_t sph = 1;
        const uint32_t stg = sb + SM_STAGING + wg * 16384;
        const uint32_t stg_lane = stg + (wq * 16 + (lane & 15)) * 128 + (((lane >> 4) ^ (lane & 7)) << 4);
        auto write_blocks = [&](auto n, uint32_t off, const uint32_t* v) {
            uint32_t a = stg_lane;
            asm volatile("" : "+r"(a));
            a += off;
#pragma unroll
            for (int j = 0; j < decltype(n)::value; j++)
                stmatrix_x4((a ^ (32 * (j & 3))) + (j >> 2) * 8192, v[4 * j], v[4 * j + 1], v[4 * j + 2], v[4 * j + 3]);
        };
        auto release = [&](uint32_t bar) { mbar_arrive_if(lane == 0, bars + bar); };
        const uint32_t bars_lane = map_cta(bars, lane & 1);
        auto release_stage = [&](uint32_t st) { mbar_arrive_cluster_if(lane < 2, bars_lane + B_GEMPTY + 8 * st); };
        auto take_item = [&]() -> int {
            return __shfl_sync(0xffffffffu, next_item(lane == 0, false), 0);
        };
        auto stage_acquire = [&](int b) { mbar_spin(bars + B_SEMPTY + 16 * wg + 8 * b, sph); };
        auto stage_publish = [&](int b) {
            __syncwarp();
            release(B_SFULL + 16 * wg + 8 * b);
        };
        auto stage_chunk = [&](int b, const uint32_t* v) {
            stage_acquire(b);
            write_blocks(std::integral_constant<int, 4>(), b * 8192, v);
            stage_publish(b);
            if (b) sph ^= 1;
        };
        auto publish_pair = [&]() {
            __syncwarp();
            mbar_arrive_if(lane < 2, bars + B_SFULL + 16 * wg + 8 * lane);
            sph ^= 1;
        };
        auto gemm_step = [&](float (&acc)[128], uint32_t dB, int& k) {
            const uint32_t st = k & 3;
            wgmma_wait<0>();
            release_stage((k - 1) & 3);
            mbar_spin(bars + B_GFULL + 8 * st, gph);
            const uint64_t da = full_desc(dA + st * (GST_BYTES >> 4)), db = full_desc(dB + st * (GST_BYTES >> 4));
            wgmma_fence();
#pragma unroll
            for (int kk = 0; kk < 4; kk++) wgmma_ss_n256_tb(acc, da + 2 * kk, db + 128 * kk, 1);
            wgmma_commit();
            gph ^= st == 3;
            k++;
        };
        if (wg == 1) bar_arrive(1, 256);
        int it = first_item();
        while (true) {
            if (item_type(it) <= T_LOCAL) {
                float acc[128];
                uint32_t pk[64];
                bool pending = false;
                bool held_b = false;
                zero_regs(pk);
                const uint32_t dB = make_desc(sb + 16384, 8192);
                do {
                    const int type = item_type(it);
                    if (type == T_LOCAL) {
                        int ln = lane;
                        asm volatile("" : "+r"(ln));
                        const int g = ln >> 2, t = ln & 3, par = wq & 1;
                        const uint32_t hc = (wq >> 1) * 4, pl = sb + (par * 2 + wg) * LOC_PLANE;
                        const uint32_t a16 = (ln & 15) * 128 + (((hc + (ln >> 4)) ^ (ln & 7)) << 4), a8 = (ln & 7) * 128 + (((hc + (ln >> 3)) ^ (ln & 7)) << 4);
                        const bool first0 = 2 * t > g, first1 = 2 * t + 1 > g;
                        const uint32_t fmask = (first0 ? 0xffffu : 0u) | (first1 ? 0xffff0000u : 0u);
                        const bool edge = item_row(it) == 0;
                        uint32_t q[4][2][4], kf[9][4], vf[9][4];
                        float w[8];
                        mbar_spin(bars + B_GFULL, gph);
#pragma unroll
                        for (int u = 0; u < 4; u++) { ldsm_x4(q[u][0], pl + u * 2048 + a16); ldsm_x4(q[u][1], pl + u * 2048 + (a16 ^ 32)); }
#pragma unroll
                        for (int j = 0; j < 8; j++) w[j] = lds_f32(sb + 4 * LOC_PLANE + 4 * (2 * g + par) + 64 * j);
                        __syncwarp();
                        release_stage(0);
                        mbar_spin(bars + B_GFULL + 8, gph);
#pragma unroll
                        for (int n = 0; n < 9; n++) ldsm_x4(kf[n], pl + GST_BYTES + n * 1024 + a8);
                        __syncwarp();
                        release_stage(1);
                        float s[8][2];
#pragma unroll
                        for (int u = 0; u < 4; u++) {
                            float d[3][4];
#pragma unroll
                            for (int nt = 0; nt < 3; nt++) {
                                mma_k16_init(d[nt], q[u][0], kf[2 * u + nt][0], kf[2 * u + nt][1]);
                                mma_k16(d[nt], q[u][1], kf[2 * u + nt][2], kf[2 * u + nt][3]);
                            }
                            if (u == 0 && edge) { d[0][0] = -INFINITY; d[0][1] = -INFINITY; }
                            s[2 * u][0] = first0 ? d[0][0] : d[1][0]; s[2 * u][1] = first1 ? d[0][1] : d[1][1];
                            s[2 * u + 1][0] = first0 ? d[1][2] : d[2][2]; s[2 * u + 1][1] = first1 ? d[1][3] : d[2][3];
                        }
                        mbar_spin(bars + B_GFULL + 16, gph);
#pragma unroll
                        for (int u = 0; u < 4; u++) { ldsm_x4_t(vf[2 * u], pl + 2 * GST_BYTES + u * 2048 + a16); ldsm_x4_t(vf[2 * u + 1], pl + 2 * GST_BYTES + u * 2048 + (a16 ^ 32)); }
                        ldsm_x4_t(vf[8], pl + 2 * GST_BYTES + 8192 + a8);
                        __syncwarp();
                        release_stage(2);
                        float x[8];
#pragma unroll
                        for (int j = 0; j < 8; j++) x[j] = fmaxf(s[j][0], s[j][1]);
#pragma unroll
                        for (int o = 1; o < 4; o *= 2)
#pragma unroll
                            for (int j = 0; j < 8; j++) x[j] = fmaxf(x[j], __shfl_xor_sync(0xffffffffu, x[j], o));
#pragma unroll
                        for (int j = 0; j < 8; j++) {
                            const float n = x[j] * -LOC_SCALE;
                            s[j][0] = ex2(fmaf(s[j][0], LOC_SCALE, n)); s[j][1] = ex2(fmaf(s[j][1], LOC_SCALE, n));
                            x[j] = s[j][0] + s[j][1];
                        }
#pragma unroll
                        for (int o = 1; o < 4; o *= 2)
#pragma unroll
                            for (int j = 0; j < 8; j++) x[j] += __shfl_xor_sync(0xffffffffu, x[j], o);
                        mbar_spin(bars + B_GFULL + 24, gph);
                        release_stage(3);
                        it = take_item();
                        uint32_t ob[4][8];
#pragma unroll
                        for (int u = 0; u < 4; u++) {
                            const float r0 = rcp(x[2 * u]), r1 = rcp(x[2 * u + 1]), f0 = fmaf(-w[2 * u], r0, r0), f1 = fmaf(-w[2 * u + 1], r1, r1);
                            const uint32_t p0 = pack_bf16(s[2 * u][0] * f0, s[2 * u][1] * f0), p1 = pack_bf16(s[2 * u + 1][0] * f1, s[2 * u + 1][1] * f1);
                            const uint32_t pa[4] = {p0 & fmask, 0, p0 & ~fmask, p1 & fmask};
#pragma unroll
                            for (int c = 0; c < 4; c++) {
                                float ol[4];
                                mma_k16_init(ol, pa, vf[2 * u + (c >> 1)][2 * (c & 1)], vf[2 * u + (c >> 1)][2 * (c & 1) + 1]);
                                mma_k8(ol, 0, p1 & ~fmask, u < 3 ? vf[2 * u + 2 + (c >> 1)][2 * (c & 1)] : vf[8][c]);
                                ob[u][2 * c] = pack_bf16(ol[0], ol[1]);
                                ob[u][2 * c + 1] = pack_bf16(ol[2], ol[3]);
                            }
                        }
                        stage_acquire(0); stage_acquire(1);
#pragma unroll
                        for (int u = 0; u < 4; u++) {
                            stmatrix_x4(stg + par * 8192 + u * 2048 + a16, ob[u][0], ob[u][1], ob[u][2], ob[u][3]);
                            stmatrix_x4(stg + par * 8192 + u * 2048 + (a16 ^ 32), ob[u][4], ob[u][5], ob[u][6], ob[u][7]);
                        }
                        publish_pair();
                        bar_sync(4, 256);
                        gph ^= 1;
                        continue;
                    }
                    mbar_spin(bars + B_GFULL, gph);
                    bool more;
                    do {
                        wgmma_fence();
                        wgmma_ss_n256_tb_init(acc, full_desc(dA), full_desc(dB));
#pragma unroll
                        for (int kk = 1; kk < 4; kk++) wgmma_ss_n256_tb(acc, full_desc(dA) + 2 * kk, full_desc(dB) + 128 * kk, 1);
                        wgmma_commit();
                        const int nk = item_type(it) == T_K || item_type(it) == T_V ? 8 : 16;
                        int k = 1;
                        do {
                            if (pending) {
                                const int kf = k - 1 - wg;
                                if (kf == 0) stage_chunk(0, pk);
                                else if (kf == 1) stage_chunk(1, pk + 16);
                                else if (kf == 3) stage_chunk(0, pk + 32);
                                else if (kf == 4) stage_chunk(1, pk + 48);
                            }
                            gemm_step(acc, dB, k);
                        } while (k < nk);
                        held_b = item_type(it) == T_B;
                        const bool is_q = item_type(it) == T_Q;
                        it = take_item();
                        more = item_type(it) < T_LOCAL;
                        if (more) mbar_spin(bars + B_GFULL, gph);
                        wgmma_wait<0>();
                        fence_regs(acc);
                        release_stage(3);
                        if (is_q) {
#pragma unroll
                            for (int j = 0; j < 128; j++) acc[j] *= SM_SCALE;
                        }
#pragma unroll
                        for (int j = 0; j < 64; j++) pk[j] = pack_bf16(acc[2 * j], acc[2 * j + 1]);
                        pending = true;
                    } while (more);
                } while (item_type(it) < T_LOCAL || (item_type(it) == T_LOCAL && (!held_b || (it & ITEM_READY))));
                if (pending) {
                    stage_acquire(0); stage_acquire(1);
                    write_blocks(std::integral_constant<int, 8>(), 0, pk);
                    const bool borrow = item_type(it) == T_ATTN;
                    if (borrow) {
                        mbar_spin(bars + B_GEMPTY, gph ^ 1); mbar_spin(bars + B_GEMPTY + 8, gph ^ 1);
                    } else {
                        publish_pair();
                        stage_acquire(0); stage_acquire(1);
                    }
                    write_blocks(std::integral_constant<int, 8>(), borrow ? 32768 - SM_STAGING : 0, pk + 32);
                    publish_pair();
                    mbar_arrive_if(lane == 0 && borrow, bars + B_ALT + 8 * wg);
                }
                if (item_type(it) == T_END) { it = take_item(); break; }
            } else {
                float o[64], s[64];
                uint32_t pa[32], pb[32];
                zero_regs(o); zero_regs(s); zero_regs(pa);
                float n0 = 0.f, n1 = 0.f;
                int shifted = 0;
                float l0 = 1.f, l1 = 1.f, f0 = 0.f, f1 = 0.f, g0 = 0.f, g1 = 0.f;
                uint32_t has_pv = 0;
                int first = 0;
                int pending = 0;
                const uint32_t dK = make_desc(sb + SM_KV, 16), dV = make_desc(sb + SM_KV, 16384);
                const uint32_t lane_off = bars_lane - bars + B_AEMPTY - B_AFULL;
                int cur = 0;
                uint32_t qoff = 0;
                const int row = wg * 64 + wq * 16 + (lane >> 2);
                const float thr = (row & 63) - (lane & 3) * 2;
                int peek = 0;
                auto kv_wait = [&](uint32_t n) { mbar_spin(bars + B_AFULL + 16 + 8 * (n & 3), (n >> 2) & 1); };
                auto kv_release = [&](uint32_t n) { mbar_arrive_cluster_if(lane < 2, bars_lane + B_AEMPTY + 16 + 8 * (n & 3)); };
                struct Slot { uint32_t bar, par, off; } slot[4];
                auto align = [&]() {
#pragma unroll
                    for (uint32_t i = 0; i < 4; i++) {
                        const uint32_t n = kvn + (i == 1 ? has_pv : i);
                        slot[i].bar = bars + B_AFULL + 16 + 8 * (n & 3); slot[i].par = (n >> 2) & 1; slot[i].off = (n & 3) * 2048;
                    }
                };
                align();
                auto scale_o = [&]() {
#pragma unroll
                    for (int j = 0; j < 16; j++) { o[4 * j] *= f0; o[4 * j + 1] *= f0; o[4 * j + 2] *= f1; o[4 * j + 3] *= f1; }
                };
                auto pack_o = [&](uint32_t (&v)[32]) {
#pragma unroll
                    for (int j = 0; j < 32; j++) v[j] = pack_bf16(o[2 * j], o[2 * j + 1]);
                };
                auto scales = [&]() { f0 = g0 * rcp(quad_sum(l0)); f1 = g1 * rcp(quad_sum(l1)); };
                auto step = [&](auto even, uint32_t (&pin)[32], uint32_t (&pout)[32], bool fresh, bool diag, bool last) {
                    constexpr bool EVEN = decltype(even)::value;
                    Slot& sk = slot[EVEN ? 0 : 2];
                    Slot& sv = slot[EVEN ? 1 : 3];
                    kvn += EVEN ? 1 + has_pv : 2;
                    mbar_spin(sk.bar, sk.par);
                    bar_sync(1 + wg, 256);
                    qk_gemm(s, dA + qoff, dK + sk.off);
                    if (EVEN && fresh) {
                        scales();
                        g0 = lds_f32(bars + SM_GATE + (ti & 1) * 512 + 4 * row); g1 = lds_f32(bars + SM_GATE + (ti & 1) * 512 + 4 * row + 32);
                        ti++;
                        n0 = 0.f; n1 = 0.f; l0 = 0.f; l1 = 0.f;
                        shifted = 0;
                        if (has_pv) { stage_acquire(0); stage_acquire(1); }
                    }
                    if (!EVEN && pending) {
                        pack_o(pout);
                        write_blocks(std::integral_constant<int, 8>(), 0, pout);
                        publish_pair();
                    }
                    if (last)
                        asm volatile("{\n.reg .pred P, Q;\n"
                                     "mbarrier.test_wait.parity.shared::cta.b64 Q, [%1], %2;\n"
                                     "mbarrier.test_wait.parity.shared::cta.b64 P, [%3], %4;\n"
                                     "ld.shared.u32 %0, [%5];\n"
                                     "@!Q or.b32 %0, %0, 0x10000;\n"
                                     "@!P mov.u32 %0, -1;\n}\n"
                                     : "=r"(peek) : "r"(bars + B_AFULL + 8 * (ti & 1)), "r"((ti >> 1) & 1), "r"(bars + B_IFULL + 8 * (qn % QDEPTH)),
                                       "r"((qn / QDEPTH) & 1), "r"(bars + SM_QUEUE + 4 * (qn % QDEPTH)) : "memory");
                    mbar_spin(sv.bar, sv.par);
                    pv_gemm(o, pin, dV + sv.off, EVEN || !first);
                    bar_arrive(2 - wg, 256);
                    sk.par ^= 1; sv.par ^= 1;
                    wgmma_wait<1>();
                    fence_regs(s);
                    mbar_arrive_cluster_if(lane < 2 && (!EVEN || has_pv), sk.bar + lane_off);
                    mbar_arrive_if(lane == 0 && last, bars + B_AEMPTY + 8 * ((ti - 1) & 1));
                    float r0, r1, x0 = n0, x1 = n1;
#pragma unroll 1
                    for (int mask = diag, redone = 0;; mask = 0, redone = 1) {
                        if (mask | shifted) {
                            if (mask) causal_mask(s, thr, wg);
                            if (shifted) shift_rows(s, x0, x1);
                        }
                        exp_pack(pout, s, r0, r1);
                        if (!__any_sync(0xffffffffu, fmaxf(r0, r1) >= SUM_LIMIT || (EVEN && fresh && !(lane & 3) && !(fminf(s[0], s[2]) >= -REF_RANGE))) || redone) break;
                        row_max(s, x0, x1);
                        if (!(EVEN && fresh)) { x0 = fmaxf(x0, 0.f); x1 = fmaxf(x1, 0.f); }
                        float a0 = ex2(-x0), a1 = ex2(-x1);
                        n0 += x0; n1 += x1;
                        shifted = 1;
                        if (EVEN && fresh) { a0 = 1.f; a1 = 1.f; }
                        l0 *= a0; l1 *= a1;
                        wgmma_wait<0>();
                        fence_regs(o);
#pragma unroll
                        for (int q = 0; q < 16; q++) { o[4 * q] *= a0; o[4 * q + 1] *= a0; o[4 * q + 2] *= a1; o[4 * q + 3] *= a1; }
                    }
                    l0 += r0; l1 += r1;
                    wgmma_wait<0>();
                    fence_regs(o);
                    fence_regs(pin);
                    mbar_arrive_cluster_if(lane < 2, sv.bar + lane_off);
                };
                auto copy_p = [&]() {
#pragma unroll
                    for (int j = 0; j < 32; j++) pa[j] = __float_as_uint(__uint_as_float(pb[j]) + __uint_as_float(prm.zero));
                };
                int rem = 0;
                mbar_spin(bars + B_AFULL + 8 * (ti & 1), (ti >> 1) & 1);
                while (true) {
                    const bool fresh = rem == 0;
                    if (fresh) {
                        if (has_pv) {
                            const int seen = __shfl_sync(0xffffffffu, peek, 0);
                            if (seen >= 0) {
                                mbar_arrive_cluster_if(lane == 0, bars0 + B_IEMPTY + 8 * (qn % QDEPTH));
                                qn++;
                                it = seen & 0xffff;
                            } else {
                                it = take_item();
                            }
                            if (item_row(cur) < 2 || item_type(it) != T_ATTN) break;
                            if (seen & 0x10000) mbar_spin(bars + B_AFULL + 8 * (ti & 1), (ti >> 1) & 1);
                        }
                        cur = it;
                        qoff = (ti & 1) * 2048;
                    }
                    const bool last = fresh ? item_row(cur) == 0 : rem == 1;
                    step(std::true_type(), pa, pb, fresh, item_asc(cur) ? last : fresh, last);
                    first = fresh;
                    if (fresh) {
                        pending = has_pv; has_pv = 1;
                        if (!pending) { kvn -= 2; align(); kvn += 2; slot[0].par ^= 1; slot[1].par ^= 1; }
                        else scale_o();
                        rem = item_row(cur);
                        if (rem == 0) {
                            copy_p();
                            continue;
                        }
                    } else if (--rem == 0) {
                        copy_p();
                        const Slot t0 = slot[0], t1 = slot[1];
                        slot[0] = slot[2]; slot[1] = slot[3]; slot[2] = t0; slot[3] = t1;
                        continue;
                    }
                    step(std::false_type(), pb, pa, false, item_asc(cur) && rem == 1, rem == 1);
                    pending = 0; first = 0;
                    rem--;
                }
                const uint32_t skip = item_asc(cur) & ~item_row(cur) & 1;
                kvn += skip;
                const bool end = item_type(it) == T_END;
#pragma unroll 1
                for (int pass = pending ? 0 : 1; pass < 2; pass++) {
                    if (pass) {
                        kv_wait(kvn);
                        pv_gemm(o, pa, dV + (kvn & 3) * 2048, !first);
                        scales();
                        stage_acquire(0); stage_acquire(1);
                        if (end) it = take_item();
                        wgmma_wait<0>();
                        fence_regs(o);
                        kv_release(kvn);
                        kvn += 1 + skip;
                        scale_o();
                    }
                    pack_o(pb);
                    write_blocks(std::integral_constant<int, 8>(), 0, pb);
                    publish_pair();
                }
                if (end) break;
            }
        }
        if (item_type(it) == T_OUT) {
            float acc[128];
            const uint32_t dB = make_desc(sb + 16384, 8192);
            mbar_spin(bars + B_GFULL, gph);
            wgmma_fence();
            wgmma_ss_n256_tb_init(acc, full_desc(dA), full_desc(dB));
#pragma unroll
            for (int kk = 1; kk < 4; kk++) wgmma_ss_n256_tb(acc, full_desc(dA) + 2 * kk, full_desc(dB) + 128 * kk, 1);
            wgmma_commit();
            uint32_t ln;
            asm volatile("mov.u32 %0, %%laneid;" : "=r"(ln));
            const uint32_t slot = (it & 127) * 32768 + (wg * 128 + wq * 32 + ln) * 16;
            char* const mine = (char*)g_part + slot;
            int k = 1, nk = 80;
            do {
                if (k == K_MEET - 5) {
#pragma unroll
                    for (int j = 0; j < 8; j++) st_b128(mine + j * 4096, 0, 0, 0, 0);
                    __syncwarp();
                }
                if (k == K_SPLIT) nk = take_item() & 127;
                gemm_step(acc, dB, k);
            } while (k < nk);
            float lo[64];
            auto triple = [&](auto first) {
                const uint32_t s0 = k & 3, s1 = (k + 1) & 3, o0 = s0 * (GST_BYTES >> 4), o1 = s1 * (GST_BYTES >> 4);
                wgmma_wait<0>();
                mbar_arrive_cluster_if(ln < (decltype(first)::value ? 2 : 4), bars_lane + B_GEMPTY + 8 * ((k - 1 - (ln >> 1)) & 3));
                mbar_spin(bars + B_GFULL + 8 * s0, gph);
                gph ^= s0 == 3;
                wgmma_fence();
#pragma unroll
                for (int kk = 0; kk < 4; kk++) {
                    if (decltype(first)::value && kk == 0) wgmma_ss_n128_tb_init(lo, full_desc(dA + o0), full_desc(dB + o0));
                    else wgmma_ss_n128_tb(lo, full_desc(dA + o0) + 2 * kk, full_desc(dB + o0) + 128 * kk, 1);
                }
                mbar_spin(bars + B_GFULL + 8 * s1, gph);
                gph ^= s1 == 3;
                wgmma_fence();
#pragma unroll
                for (int kk = 0; kk < 4; kk++) wgmma_ss_n128_tb(lo, full_desc(dA + o0 + 2048) + 2 * kk, full_desc(dB + o1 + 1024) + 128 * kk, 1);
#pragma unroll
                for (int kk = 0; kk < 4; kk++) wgmma_ss_n128_tb(lo, full_desc(dA + o1) + 2 * kk, full_desc(dB + o1) + 128 * kk, 1);
                wgmma_commit();
                k += 2;
            };
            triple(std::true_type());
            fence_regs(acc);
#pragma unroll
            for (int j = 0; j < 8; j++) {
                uint32_t v[4];
#pragma unroll
                for (int i = 0; i < 4; i++) v[i] = pack_bf16(acc[64 + 8 * j + 2 * i], acc[65 + 8 * j + 2 * i]);
                if (j == 4) triple(std::false_type());
                st_b128(mine + j * 4096, ~v[0], v[1], v[2], v[3]);
            }
            triple(std::false_type());
            uint32_t pk[32];
            char* const other = (char*)g_part + (slot ^ (16 * 32768));
            while (true) {
#pragma unroll
                for (int j = 0; j < 8; j++) ld_b128(other + j * 4096, pk[4 * j], pk[4 * j + 1], pk[4 * j + 2], pk[4 * j + 3]);
                bool miss = false;
#pragma unroll
                for (int j = 0; j < 8; j++) miss |= pk[4 * j] == 0;
                if (!__any_sync(0xffffffffu, miss)) break;
                while (__any_sync(0xffffffffu, pk[28] == 0)) ld_b128(other + 7 * 4096, pk[28], pk[29], pk[30], pk[31]);
            }
#pragma unroll
            for (int j = 0; j < 32; j++) {
                const uint32_t v = j & 3 ? pk[j] : ~pk[j];
                acc[2 * j] += __uint_as_float(v << 16); acc[2 * j + 1] += __uint_as_float(v & 0xffff0000u);
                asm volatile("" : "+f"(acc[2 * j]), "+f"(acc[2 * j + 1]) :: "memory");
            }
            stage_acquire(0); stage_acquire(1);
            wgmma_wait<0>();
            fence_regs(lo);
            mbar_arrive_cluster_if(ln < 4, bars_lane + B_GEMPTY + 8 * ((k - 1 - (ln >> 1)) & 3));
#pragma unroll
            for (int j = 0; j < 32; j++)
                pk[j] = pack_bf16(acc[2 * j] + lo[2 * j], acc[2 * j + 1] + lo[2 * j + 1]);
            write_blocks(std::integral_constant<int, 8>(), 0, pk);
            __syncwarp();
            uint4* dst = (uint4*)((char*)prm.out + (uint32_t)((item_row(it) * 128 + wg * 64 + wq * 16 + (ln >> 4)) * 2048 + item_col(it) * 256 + (ln & 15) * 16));
#pragma unroll
            for (int j = 0; j < 8; j++) {
                const int r = 2 * j + (ln >> 4);
                uint4 v;
                asm volatile("ld.shared.v4.u32 {%0, %1, %2, %3}, [%4];" : "=r"(v.x), "=r"(v.y), "=r"(v.z), "=r"(v.w)
                             : "r"(stg + wq * 2048 + r * 128 + (ln & 8) * 1024 + (((ln & 7) ^ (r & 7)) << 4)) : "memory");
                dst[j * 256] = v;
            }
        }
    }
}

typedef CUresult (*EncodeFn)(CUtensorMap*, CUtensorMapDataType, cuuint32_t, void*, const cuuint64_t*, const cuuint64_t*,
                             const cuuint32_t*, const cuuint32_t*, CUtensorMapInterleave, CUtensorMapSwizzle,
                             CUtensorMapL2promotion, CUtensorMapFloatOOBfill);

void encode3(EncodeFn fn, CUtensorMap* m, const void* ptr, uint64_t d0, uint64_t d1, uint64_t d2, uint64_t s1, uint64_t s2,
             uint32_t b0, uint32_t b1, uint32_t b2) {
    cuuint64_t dims[3] = {d0, d1, d2};
    cuuint64_t strides[2] = {s1, s2};
    cuuint32_t box[3] = {b0, b1, b2};
    cuuint32_t es[3] = {1, 1, 1};
    fn(m, CU_TENSOR_MAP_DATA_TYPE_BFLOAT16, 3, const_cast<void*>(ptr), dims, strides, box, es, CU_TENSOR_MAP_INTERLEAVE_NONE,
       CU_TENSOR_MAP_SWIZZLE_128B, CU_TENSOR_MAP_L2_PROMOTION_NONE, CU_TENSOR_MAP_FLOAT_OOB_FILL_NONE);
}
void map_act(EncodeFn fn, CUtensorMap* m, const void* p, int rows, int cols, int box_rows) {
    encode3(fn, m, p, cols, rows, 1, (uint64_t)cols * 2, (uint64_t)cols * rows * 2, 64, box_rows, 1);
}
void map_wgt(EncodeFn fn, CUtensorMap* m, const void* p, int K, int N) {
    encode3(fn, m, p, 64, K, N / 64, (uint64_t)N * 2, 128, 64, 64, 2);
}

void build_schedule(Params& p) {
    int n = 0;
    auto add = [&](int type, int col, int row) { p.items[n++] = (uint16_t)(type << 13 | col << 4 | row); };
    auto add_qkv = [&](int c) {
        for (int m = 0; m < 8; m++) add(T_Q, c, m);
        for (int m = 0; m < 8; m++) add(T_K, c, m);
        for (int m = 0; m < 8; m++) add(T_V, c, m);
    };
    int ldist = 200, ldist2 = 260, lstep = 8, beta = 26, tail = 32, late = 6, early = 8, epos = 100;
    int order[16] = {6, 7, 8, 9, 10, 11, 12, 13, 14, 15, 5, 4, 3, 2, 1, 0};
    uint16_t proj[480];
    for (int m = 0; m < 8; m++) for (int c = 0; c < 12; c++) add(T_B, c, m);
    for (int c = 0; c < 16; c++) add_qkv(c);
    for (int i = 0; i < 480; i++) proj[i] = p.items[i];
    n = 0;
    for (int i = 0, l = 0; i < 480; i++) {
        p.items[n++] = proj[i];
        for (; l < 64 && i >= (l < 40 ? ldist + lstep * l / 8 : ldist2 + lstep * (l - 40) / 8); l++) add(T_LOCAL, l & 3, l >> 2);
    }
    const int a0 = n;
    for (int key = 0; key < 4000; key++)
        for (int r = 0; r < 32; r++)
            for (int j = 7; j >= 0; j--)
                if ((j ? (7 - j) * 40 + r * beta : 3999) == key) add(T_ATTN, 2 * order[r >> 1] + (r & 1), j);
    int t0 = n;
    for (int work = 0; work < 32 * 136 * tail / 100;) work += 4 * (p.items[--t0] & 15) + 3;
    for (int i = t0 + 1; i < n; i++)
        for (int j = i; j > t0 && (p.items[j] & 15) > (p.items[j - 1] & 15); j--) { const uint16_t t = p.items[j]; p.items[j] = p.items[j - 1]; p.items[j - 1] = t; }
    for (int r = early - 1; r >= 0; r--) {
        const uint16_t t = p.items[n - 32 + early - 1];
        for (int j = n - 32 + early - 1; j > n - epos; j--) p.items[j] = p.items[j - 1];
        p.items[n - epos] = t;
    }
    for (int moved = 0; moved < 2 && late >= 0; moved++)
        for (int i = a0; i < n; i++)
            if (p.items[i] == (T_ATTN << 13 | (2 * order[15] + moved) << 4 | late)) {
                for (int j = i; j + 1 < n; j++) p.items[j] = p.items[j + 1];
                p.items[n - 1] = (uint16_t)(T_ATTN << 13 | (2 * order[15] + moved) << 4 | late);
                break;
            }
    for (int s = 0, lo = 0, hi = WIDE - 1; s < 80; s++) {
        const int r = s / 2, g = r < 8 ? 32 + r : 2 * order[r / 2 - 4] + (r & 1);
        p.ostep[s >= WIDE ? s : r & 1 ? hi-- : lo++] = (uint8_t)(2 * g + (s & 1));
    }
}

void build_params(Params& p, void* const* d_in, void* d_out) {
    void* fnp = nullptr;
    cudaDriverEntryPointQueryResult qr;
    cudaGetDriverEntryPoint("cuTensorMapEncodeTiled", &fnp, cudaEnableDefault, &qr);
    EncodeFn fn = (EncodeFn)fnp;
    void* scr = nullptr;
    cudaGetSymbolAddress(&scr, g_scr);
    map_act(fn, &p.m[M_X], d_in[0], SEQ, 1024, 128);
    map_act(fn, &p.m[M_C], d_in[1], SEQ, 512, 128);
    map_wgt(fn, &p.m[M_WQ], d_in[2], 1024, 4096);
    map_wgt(fn, &p.m[M_WUK], d_in[3], 512, 4096);
    map_wgt(fn, &p.m[M_WUV], d_in[4], 512, 4096);
    map_wgt(fn, &p.m[M_WO], d_in[5], 4096, 1024);
    map_wgt(fn, &p.m[M_WQKV], d_in[7], 1024, 3072);
    map_wgt(fn, &p.m[M_WOB], d_in[8], 1024, 1024);
    encode3(fn, &p.m[M_SCR_LD], scr, 128, SEQ, G_TOTAL, 256, (uint64_t)SEQ * 256, 64, 128, 1);
    encode3(fn, &p.m[M_SCR_LOC], scr, 256, SEQ / 2, G_TOTAL, 512, (uint64_t)SEQ * 256, 64, 72, 1);
    encode3(fn, &p.m[M_SCR_LOQ], scr, 256, SEQ / 2, G_TOTAL, 512, (uint64_t)SEQ * 256, 64, 64, 1);
    encode3(fn, &p.m[M_SCR_ST], scr, 128, SEQ, G_TOTAL, 256, (uint64_t)SEQ * 256, 64, 64, 1);
    p.x = (const __nv_bfloat16*)d_in[0];
    p.gate_w = (const __nv_bfloat16*)d_in[9];
    p.zero = 0;
    p.wo = (const char*)d_in[5];
    p.out = (__nv_bfloat16*)d_out;
    build_schedule(p);
}

}

extern "C" void kernel_launch(void* const* d_in, const int* in_sizes, int n_in, void* d_out, int out_size) {
    (void)in_sizes; (void)n_in; (void)out_size;
    Params p;
    build_params(p, d_in, d_out);
    cudaFuncSetAttribute(fused_kernel, cudaFuncAttributeMaxDynamicSharedMemorySize, SM_TOTAL);
    fused_kernel<<<NCTA, 384, SM_TOTAL>>>(p);
}
```

```cpp
#include <cuda_runtime.h>
#include <cuda_bf16.h>
#include <cuda.h>
#include <stddef.h>
#include <stdint.h>
#include <type_traits>

namespace {

constexpr int SEQ = 2048;
constexpr int G_Q = 0, G_K = 32, G_V = 64, G_B = 96, G_CTX = G_Q, G_LOC = G_B, G_TOTAL = 120;

__device__ __align__(1024) __nv_bfloat16 g_scr[(size_t)G_TOTAL * SEQ * 128];
__device__ __align__(128) float g_gate[SEQ];

__device__ __forceinline__ uint32_t smem_u32(const void* p) { return (uint32_t)__cvta_generic_to_shared(p); }
__device__ __forceinline__ bool elect_one() {
    uint32_t p;
    asm volatile("{\n.reg .pred P;\nelect.sync _|P, 0xffffffff;\nselp.u32 %0, 1, 0, P;\n}\n" : "=r"(p));
    return p != 0;
}
__device__ __forceinline__ void mbar_init(uint32_t bar, uint32_t count) {
    asm volatile("mbarrier.init.shared::cta.b64 [%0], %1;" :: "r"(bar), "r"(count) : "memory");
}
__device__ __forceinline__ uint32_t cluster_rank() { uint32_t r; asm("mov.u32 %0, %%cluster_ctarank;" : "=r"(r)); return r; }
__device__ __forceinline__ uint32_t map_cta(uint32_t addr, uint32_t cta) {
    uint32_t r; asm("mapa.shared::cluster.u32 %0, %1, %2;" : "=r"(r) : "r"(addr), "r"(cta)); return r;
}
__device__ __forceinline__ void mbar_arrive_cluster_if(bool pred, uint32_t cluster_bar) {
    asm volatile("{\n.reg .pred P;\nsetp.ne.u32 P, %1, 0;\n@P mbarrier.arrive.shared::cluster.b64 _, [%0];\n}\n"
                 :: "r"(cluster_bar), "r"((uint32_t)pred) : "memory");
}
__device__ __forceinline__ void mbar_arrive_cluster_n_if(bool pred, uint32_t cluster_bar, uint32_t count) {
    asm volatile("{\n.reg .pred P;\nsetp.ne.u32 P, %1, 0;\n@P mbarrier.arrive.shared::cluster.b64 _, [%0], %2;\n}\n"
                 :: "r"(cluster_bar), "r"((uint32_t)pred), "r"(count) : "memory");
}
__device__ __forceinline__ void mbar_arrive_if(bool pred, uint32_t bar) {
    asm volatile("{\n.reg .pred P;\nsetp.ne.u32 P, %1, 0;\n@P mbarrier.arrive.shared::cta.b64 _, [%0];\n}\n"
                 :: "r"(bar), "r"((uint32_t)pred) : "memory");
}
__device__ __forceinline__ bool mbar_test(uint32_t bar, uint32_t parity) {
    uint32_t ok;
    asm volatile("{\n.reg .pred P;\nmbarrier.test_wait.parity.shared::cta.b64 P, [%1], %2;\nselp.u32 %0, 1, 0, P;\n}\n"
                 : "=r"(ok) : "r"(bar), "r"(parity) : "memory");
    return ok != 0;
}
__device__ __forceinline__ void mbar_wait(uint32_t bar, uint32_t parity) {
    asm volatile("{\n.reg .pred P;\n.reg .u32 c;\n"
                 "mov.u32 c, 0;\n"
                 "SPIN:\n"
                 "mbarrier.try_wait.parity.shared::cta.b64 P, [%0], %1;\n"
                 "@P bra DONE;\n"
                 "add.u32 c, c, 1;\n"
                 "setp.lt.u32 P, c, 4194304;\n"
                 "@P bra SPIN;\n"
                 "trap;\n"
                 "DONE:\n}\n" :: "r"(bar), "r"(parity) : "memory");
}
__device__ __forceinline__ void mbar_spin(uint32_t bar, uint32_t parity) {
    asm volatile("{\n.reg .pred P;\n"
                 "SPIN:\n"
                 "mbarrier.try_wait.parity.shared::cta.b64 P, [%0], %1;\n"
                 "@!P bra SPIN;\n}\n" :: "r"(bar), "r"(parity) : "memory");
}
__device__ __forceinline__ void bar_sync(int id, int n) { asm volatile("bar.sync %0, %1;" :: "r"(id), "r"(n) : "memory"); }
__device__ __forceinline__ void bar_arrive(int id, int n) { asm volatile("bar.arrive %0, %1;" :: "r"(id), "r"(n) : "memory"); }
__device__ __forceinline__ void fence_proxy_async_smem() { asm volatile("fence.proxy.async.shared::cta;" ::: "memory"); }
__device__ __forceinline__ void warp_expect_tx(uint32_t bar, uint32_t bytes) {
    asm volatile("{\n.reg .pred P;\nelect.sync _|P, 0xffffffff;\n@P mbarrier.arrive.expect_tx.shared::cta.b64 _, [%0], %1;\n}\n"
                 :: "r"(bar), "r"(bytes) : "memory");
}
constexpr uint64_t EVICT_FIRST = 0x12F0000000000000ull;
__device__ __forceinline__ void warp_tma_load(uint32_t dst, const CUtensorMap* map, uint32_t bar, int c0, int c1, int c2, bool stream) {
    if (stream)
        asm volatile("{\n.reg .pred P;\nelect.sync _|P, 0xffffffff;\n"
                     "@P cp.async.bulk.tensor.3d.shared::cluster.global.mbarrier::complete_tx::bytes.L2::cache_hint"
                     " [%0], [%1, {%3, %4, %5}], [%2], %6;\n}\n"
                     :: "r"(dst), "l"(map), "r"(bar), "r"(c0), "r"(c1), "r"(c2), "l"(EVICT_FIRST) : "memory");
    else
        asm volatile("{\n.reg .pred P;\nelect.sync _|P, 0xffffffff;\n"
                     "@P cp.async.bulk.tensor.3d.shared::cluster.global.mbarrier::complete_tx::bytes [%0], [%1, {%3, %4, %5}], [%2];\n}\n"
                     :: "r"(dst), "l"(map), "r"(bar), "r"(c0), "r"(c1), "r"(c2) : "memory");
}
__device__ __forceinline__ void warp_tma_load_pair(uint32_t dst, const CUtensorMap* map, uint32_t bar, int c0, int c1, int c2, bool stream) {
    if (stream)
        asm volatile("{\n.reg .pred P;\nelect.sync _|P, 0xffffffff;\n"
                     "@P cp.async.bulk.tensor.3d.shared::cluster.global.mbarrier::complete_tx::bytes.multicast::cluster.L2::cache_hint"
                     " [%0], [%1, {%3, %4, %5}], [%2], %6, %7;\n}\n"
                     :: "r"(dst), "l"(map), "r"(bar), "r"(c0), "r"(c1), "r"(c2), "h"((uint16_t)3), "l"(EVICT_FIRST) : "memory");
    else
        asm volatile("{\n.reg .pred P;\nelect.sync _|P, 0xffffffff;\n"
                     "@P cp.async.bulk.tensor.3d.shared::cluster.global.mbarrier::complete_tx::bytes.multicast::cluster"
                     " [%0], [%1, {%3, %4, %5}], [%2], %6;\n}\n"
                     :: "r"(dst), "l"(map), "r"(bar), "r"(c0), "r"(c1), "r"(c2), "h"((uint16_t)3) : "memory");
}
__device__ __forceinline__ void warp_bulk_load(uint32_t dst, const void* src, uint32_t bytes, uint32_t bar) {
    asm volatile("{\n.reg .pred P;\nelect.sync _|P, 0xffffffff;\n"
                 "@P cp.async.bulk.shared::cluster.global.mbarrier::complete_tx::bytes [%0], [%1], %2, [%3];\n}\n"
                 :: "r"(dst), "l"(src), "r"(bytes), "r"(bar) : "memory");
}
__device__ __forceinline__ void warp_tma_store(const CUtensorMap* map, uint32_t src, int c0, int c1, int c2, bool stream) {
    if (stream)
        asm volatile("{\n.reg .pred P;\nelect.sync _|P, 0xffffffff;\n"
                     "@P cp.async.bulk.tensor.3d.global.shared::cta.bulk_group.L2::cache_hint [%0, {%2, %3, %4}], [%1], %5;\n}\n"
                     :: "l"(map), "r"(src), "r"(c0), "r"(c1), "r"(c2), "l"(EVICT_FIRST) : "memory");
    else
        asm volatile("{\n.reg .pred P;\nelect.sync _|P, 0xffffffff;\n"
                     "@P cp.async.bulk.tensor.3d.global.shared::cta.bulk_group [%0, {%2, %3, %4}], [%1];\n}\n"
                     :: "l"(map), "r"(src), "r"(c0), "r"(c1), "r"(c2) : "memory");
}
__device__ __forceinline__ void warp_bulk_store(void* dst, uint32_t src, uint32_t bytes) {
    asm volatile("{\n.reg .pred P;\nelect.sync _|P, 0xffffffff;\n"
                 "@P cp.async.bulk.global.shared::cta.bulk_group [%0], [%1], %2;\n}\n" :: "l"(dst), "r"(src), "r"(bytes) : "memory");
}
__device__ __forceinline__ void warp_prefetch(const void* src, uint32_t bytes) {
    asm volatile("{\n.reg .pred P;\nelect.sync _|P, 0xffffffff;\n@P cp.async.bulk.prefetch.L2.global [%0], %1;\n}\n" :: "l"(src), "r"(bytes) : "memory");
}
__device__ __forceinline__ void bulk_commit() { asm volatile("cp.async.bulk.commit_group;" ::: "memory"); }
template <int N> __device__ __forceinline__ void bulk_wait_read() { asm volatile("cp.async.bulk.wait_group.read %0;" :: "n"(N) : "memory"); }
template <int N> __device__ __forceinline__ void bulk_wait() { asm volatile("cp.async.bulk.wait_group %0;" :: "n"(N) : "memory"); }
__device__ __forceinline__ void wgmma_fence() { asm volatile("wgmma.fence.sync.aligned;" ::: "memory"); }
__device__ __forceinline__ void wgmma_commit() { asm volatile("wgmma.commit_group.sync.aligned;" ::: "memory"); }
template <int N> __device__ __forceinline__ void wgmma_wait() { asm volatile("wgmma.wait_group.sync.aligned %0;" :: "n"(N) : "memory"); }
template <int N> __device__ __forceinline__ void fence_regs(float (&d)[N]) {
#pragma unroll
    for (int i = 0; i < N; i++) asm volatile("" : "+f"(d[i]) :: "memory");
}
template <int N> __device__ __forceinline__ void fence_regs(uint32_t (&d)[N]) {
#pragma unroll
    for (int i = 0; i < N; i++) asm volatile("" : "+r"(d[i]) :: "memory");
}
template <int N> __device__ __forceinline__ void reg_dec() { asm volatile("setmaxnreg.dec.sync.aligned.u32 %0;" :: "n"(N)); }
template <int N> __device__ __forceinline__ void reg_inc() { asm volatile("setmaxnreg.inc.sync.aligned.u32 %0;" :: "n"(N)); }
__device__ __forceinline__ uint32_t pack_bf16(float lo, float hi) {
    uint32_t r; asm("cvt.rn.bf16x2.f32 %0, %1, %2;" : "=r"(r) : "f"(hi), "f"(lo)); return r;
}
__device__ __forceinline__ void stmatrix_x4(uint32_t addr, uint32_t r0, uint32_t r1, uint32_t r2, uint32_t r3) {
    asm volatile("stmatrix.sync.aligned.m8n8.x4.shared.b16 [%0], {%1, %2, %3, %4};"
                 :: "r"(addr), "r"(r0), "r"(r1), "r"(r2), "r"(r3) : "memory");
}
__device__ __forceinline__ float ex2(float x) { float y; asm("ex2.approx.ftz.f32 %0, %1;" : "=f"(y) : "f"(x)); return y; }

constexpr uint32_t DESC_HI = (1024 >> 4) | (1u << 30);
__device__ __forceinline__ uint32_t make_desc(uint32_t addr, uint32_t lbo) {
    uint32_t lo = ((addr & 0x3FFFF) >> 4) | ((lbo >> 4) << 16);
    asm volatile("" : "+r"(lo));
    return lo;
}
__device__ __forceinline__ uint64_t full_desc(uint32_t lo) {
    uint64_t d; asm("mov.b64 %0, {%1, %2};" : "=l"(d) : "r"(lo), "r"(DESC_HI)); return d;
}

__device__ __forceinline__ void wgmma_ss_n256_tb_init(float (&d)[128], uint64_t da, uint64_t db) {
    asm volatile("{\n.reg .pred p;\n"
        "setp.ne.b32 p, 0, 0;\n"
        "wgmma.mma_async.sync.aligned.m64n256k16.f32.bf16.bf16 "
        "{%0, %1, %2, %3, %4, %5, %6, %7, %8, %9, %10, %11, %12, %13, %14, %15, %16, %17, %18, %19, %20, "
        "%21, %22, %23, %24, %25, %26, %27, %28, %29, %30, %31, %32, %33, %34, %35, %36, %37, %38, %39, %40, "
        "%41, %42, %43, %44, %45, %46, %47, %48, %49, %50, %51, %52, %53, %54, %55, %56, %57, %58, %59, %60, "
        "%61, %62, %63, %64, %65, %66, %67, %68, %69, %70, %71, %72, %73, %74, %75, %76, %77, %78, %79, %80, "
        "%81, %82, %83, %84, %85, %86, %87, %88, %89, %90, %91, %92, %93, %94, %95, %96, %97, %98, %99, "
        "%100, %101, %102, %103, %104, %105, %106, %107, %108, %109, %110, %111, %112, %113, %114, %115, "
        "%116, %117, %118, %119, %120, %121, %122, %123, %124, %125, %126, %127},"
        " %128, %129, p, 1, 1, 0, 1;\n}\n"
        : "=f"(d[0]), "=f"(d[1]), "=f"(d[2]), "=f"(d[3]), "=f"(d[4]), "=f"(d[5]), "=f"(d[6]), "=f"(d[7]),
        "=f"(d[8]), "=f"(d[9]), "=f"(d[10]), "=f"(d[11]), "=f"(d[12]), "=f"(d[13]), "=f"(d[14]), "=f"(d[15]),
        "=f"(d[16]), "=f"(d[17]), "=f"(d[18]), "=f"(d[19]), "=f"(d[20]), "=f"(d[21]), "=f"(d[22]),
        "=f"(d[23]), "=f"(d[24]), "=f"(d[25]), "=f"(d[26]), "=f"(d[27]), "=f"(d[28]), "=f"(d[29]),
        "=f"(d[30]), "=f"(d[31]), "=f"(d[32]), "=f"(d[33]), "=f"(d[34]), "=f"(d[35]), "=f"(d[36]),
        "=f"(d[37]), "=f"(d[38]), "=f"(d[39]), "=f"(d[40]), "=f"(d[41]), "=f"(d[42]), "=f"(d[43]),
        "=f"(d[44]), "=f"(d[45]), "=f"(d[46]), "=f"(d[47]), "=f"(d[48]), "=f"(d[49]), "=f"(d[50]),
        "=f"(d[51]), "=f"(d[52]), "=f"(d[53]), "=f"(d[54]), "=f"(d[55]), "=f"(d[56]), "=f"(d[57]),
        "=f"(d[58]), "=f"(d[59]), "=f"(d[60]), "=f"(d[61]), "=f"(d[62]), "=f"(d[63]), "=f"(d[64]),
        "=f"(d[65]), "=f"(d[66]), "=f"(d[67]), "=f"(d[68]), "=f"(d[69]), "=f"(d[70]), "=f"(d[71]),
        "=f"(d[72]), "=f"(d[73]), "=f"(d[74]), "=f"(d[75]), "=f"(d[76]), "=f"(d[77]), "=f"(d[78]),
        "=f"(d[79]), "=f"(d[80]), "=f"(d[81]), "=f"(d[82]), "=f"(d[83]), "=f"(d[84]), "=f"(d[85]),
        "=f"(d[86]), "=f"(d[87]), "=f"(d[88]), "=f"(d[89]), "=f"(d[90]), "=f"(d[91]), "=f"(d[92]),
        "=f"(d[93]), "=f"(d[94]), "=f"(d[95]), "=f"(d[96]), "=f"(d[97]), "=f"(d[98]), "=f"(d[99]),
        "=f"(d[100]), "=f"(d[101]), "=f"(d[102]), "=f"(d[103]), "=f"(d[104]), "=f"(d[105]), "=f"(d[106]),
        "=f"(d[107]), "=f"(d[108]), "=f"(d[109]), "=f"(d[110]), "=f"(d[111]), "=f"(d[112]), "=f"(d[113]),
        "=f"(d[114]), "=f"(d[115]), "=f"(d[116]), "=f"(d[117]), "=f"(d[118]), "=f"(d[119]), "=f"(d[120]),
        "=f"(d[121]), "=f"(d[122]), "=f"(d[123]), "=f"(d[124]), "=f"(d[125]), "=f"(d[126]), "=f"(d[127])
        : "l"(da), "l"(db));
}
__device__ __forceinline__ void wgmma_ss_n256_tb(float (&d)[128], uint64_t da, uint64_t db, int scale_d) {
    asm volatile("{\n.reg .pred p;\n"
        "setp.ne.b32 p, %130, 0;\n"
        "wgmma.mma_async.sync.aligned.m64n256k16.f32.bf16.bf16 "
        "{%0, %1, %2, %3, %4, %5, %6, %7, %8, %9, %10, %11, %12, %13, %14, %15, %16, %17, %18, %19, %20, "
        "%21, %22, %23, %24, %25, %26, %27, %28, %29, %30, %31, %32, %33, %34, %35, %36, %37, %38, %39, %40, "
        "%41, %42, %43, %44, %45, %46, %47, %48, %49, %50, %51, %52, %53, %54, %55, %56, %57, %58, %59, %60, "
        "%61, %62, %63, %64, %65, %66, %67, %68, %69, %70, %71, %72, %73, %74, %75, %76, %77, %78, %79, %80, "
        "%81, %82, %83, %84, %85, %86, %87, %88, %89, %90, %91, %92, %93, %94, %95, %96, %97, %98, %99, "
        "%100, %101, %102, %103, %104, %105, %106, %107, %108, %109, %110, %111, %112, %113, %114, %115, "
        "%116, %117, %118, %119, %120, %121, %122, %123, %124, %125, %126, %127},"
        " %128, %129, p, 1, 1, 0, 1;\n}\n"
        : "+f"(d[0]), "+f"(d[1]), "+f"(d[2]), "+f"(d[3]), "+f"(d[4]), "+f"(d[5]), "+f"(d[6]), "+f"(d[7]),
        "+f"(d[8]), "+f"(d[9]), "+f"(d[10]), "+f"(d[11]), "+f"(d[12]), "+f"(d[13]), "+f"(d[14]), "+f"(d[15]),
        "+f"(d[16]), "+f"(d[17]), "+f"(d[18]), "+f"(d[19]), "+f"(d[20]), "+f"(d[21]), "+f"(d[22]),
        "+f"(d[23]), "+f"(d[24]), "+f"(d[25]), "+f"(d[26]), "+f"(d[27]), "+f"(d[28]), "+f"(d[29]),
        "+f"(d[30]), "+f"(d[31]), "+f"(d[32]), "+f"(d[33]), "+f"(d[34]), "+f"(d[35]), "+f"(d[36]),
        "+f"(d[37]), "+f"(d[38]), "+f"(d[39]), "+f"(d[40]), "+f"(d[41]), "+f"(d[42]), "+f"(d[43]),
        "+f"(d[44]), "+f"(d[45]), "+f"(d[46]), "+f"(d[47]), "+f"(d[48]), "+f"(d[49]), "+f"(d[50]),
        "+f"(d[51]), "+f"(d[52]), "+f"(d[53]), "+f"(d[54]), "+f"(d[55]), "+f"(d[56]), "+f"(d[57]),
        "+f"(d[58]), "+f"(d[59]), "+f"(d[60]), "+f"(d[61]), "+f"(d[62]), "+f"(d[63]), "+f"(d[64]),
        "+f"(d[65]), "+f"(d[66]), "+f"(d[67]), "+f"(d[68]), "+f"(d[69]), "+f"(d[70]), "+f"(d[71]),
        "+f"(d[72]), "+f"(d[73]), "+f"(d[74]), "+f"(d[75]), "+f"(d[76]), "+f"(d[77]), "+f"(d[78]),
        "+f"(d[79]), "+f"(d[80]), "+f"(d[81]), "+f"(d[82]), "+f"(d[83]), "+f"(d[84]), "+f"(d[85]),
        "+f"(d[86]), "+f"(d[87]), "+f"(d[88]), "+f"(d[89]), "+f"(d[90]), "+f"(d[91]), "+f"(d[92]),
        "+f"(d[93]), "+f"(d[94]), "+f"(d[95]), "+f"(d[96]), "+f"(d[97]), "+f"(d[98]), "+f"(d[99]),
        "+f"(d[100]), "+f"(d[101]), "+f"(d[102]), "+f"(d[103]), "+f"(d[104]), "+f"(d[105]), "+f"(d[106]),
        "+f"(d[107]), "+f"(d[108]), "+f"(d[109]), "+f"(d[110]), "+f"(d[111]), "+f"(d[112]), "+f"(d[113]),
        "+f"(d[114]), "+f"(d[115]), "+f"(d[116]), "+f"(d[117]), "+f"(d[118]), "+f"(d[119]), "+f"(d[120]),
        "+f"(d[121]), "+f"(d[122]), "+f"(d[123]), "+f"(d[124]), "+f"(d[125]), "+f"(d[126]), "+f"(d[127])
        : "l"(da), "l"(db), "r"(scale_d));
}
__device__ __forceinline__ void wgmma_ss_n128(float (&d)[64], uint64_t da, uint64_t db, int scale_d) {
    asm volatile("{\n.reg .pred p;\n"
        "setp.ne.b32 p, %66, 0;\n"
        "wgmma.mma_async.sync.aligned.m64n128k16.f32.bf16.bf16 "
        "{%0, %1, %2, %3, %4, %5, %6, %7, %8, %9, %10, %11, %12, %13, %14, %15, %16, %17, %18, %19, %20, "
        "%21, %22, %23, %24, %25, %26, %27, %28, %29, %30, %31, %32, %33, %34, %35, %36, %37, %38, %39, %40, "
        "%41, %42, %43, %44, %45, %46, %47, %48, %49, %50, %51, %52, %53, %54, %55, %56, %57, %58, %59, %60, "
        "%61, %62, %63},"
        " %64, %65, p, 1, 1, 0, 0;\n}\n"
        : "+f"(d[0]), "+f"(d[1]), "+f"(d[2]), "+f"(d[3]), "+f"(d[4]), "+f"(d[5]), "+f"(d[6]), "+f"(d[7]),
        "+f"(d[8]), "+f"(d[9]), "+f"(d[10]), "+f"(d[11]), "+f"(d[12]), "+f"(d[13]), "+f"(d[14]), "+f"(d[15]),
        "+f"(d[16]), "+f"(d[17]), "+f"(d[18]), "+f"(d[19]), "+f"(d[20]), "+f"(d[21]), "+f"(d[22]),
        "+f"(d[23]), "+f"(d[24]), "+f"(d[25]), "+f"(d[26]), "+f"(d[27]), "+f"(d[28]), "+f"(d[29]),
        "+f"(d[30]), "+f"(d[31]), "+f"(d[32]), "+f"(d[33]), "+f"(d[34]), "+f"(d[35]), "+f"(d[36]),
        "+f"(d[37]), "+f"(d[38]), "+f"(d[39]), "+f"(d[40]), "+f"(d[41]), "+f"(d[42]), "+f"(d[43]),
        "+f"(d[44]), "+f"(d[45]), "+f"(d[46]), "+f"(d[47]), "+f"(d[48]), "+f"(d[49]), "+f"(d[50]),
        "+f"(d[51]), "+f"(d[52]), "+f"(d[53]), "+f"(d[54]), "+f"(d[55]), "+f"(d[56]), "+f"(d[57]),
        "+f"(d[58]), "+f"(d[59]), "+f"(d[60]), "+f"(d[61]), "+f"(d[62]), "+f"(d[63])
        : "l"(da), "l"(db), "r"(scale_d));
}
__device__ __forceinline__ void wgmma_rs_n128_tb(float (&d)[64], uint32_t a0, uint32_t a1, uint32_t a2, uint32_t a3, uint64_t db, int scale_d) {
    asm volatile("{\n.reg .pred p;\n"
        "setp.ne.b32 p, %69, 0;\n"
        "wgmma.mma_async.sync.aligned.m64n128k16.f32.bf16.bf16 "
        "{%0, %1, %2, %3, %4, %5, %6, %7, %8, %9, %10, %11, %12, %13, %14, %15, %16, %17, %18, %19, %20, "
        "%21, %22, %23, %24, %25, %26, %27, %28, %29, %30, %31, %32, %33, %34, %35, %36, %37, %38, %39, %40, "
        "%41, %42, %43, %44, %45, %46, %47, %48, %49, %50, %51, %52, %53, %54, %55, %56, %57, %58, %59, %60, "
        "%61, %62, %63},"
        " {%64, %65, %66, %67}, %68, p, 1, 1, 1;\n}\n"
        : "+f"(d[0]), "+f"(d[1]), "+f"(d[2]), "+f"(d[3]), "+f"(d[4]), "+f"(d[5]), "+f"(d[6]), "+f"(d[7]),
        "+f"(d[8]), "+f"(d[9]), "+f"(d[10]), "+f"(d[11]), "+f"(d[12]), "+f"(d[13]), "+f"(d[14]), "+f"(d[15]),
        "+f"(d[16]), "+f"(d[17]), "+f"(d[18]), "+f"(d[19]), "+f"(d[20]), "+f"(d[21]), "+f"(d[22]),
        "+f"(d[23]), "+f"(d[24]), "+f"(d[25]), "+f"(d[26]), "+f"(d[27]), "+f"(d[28]), "+f"(d[29]),
        "+f"(d[30]), "+f"(d[31]), "+f"(d[32]), "+f"(d[33]), "+f"(d[34]), "+f"(d[35]), "+f"(d[36]),
        "+f"(d[37]), "+f"(d[38]), "+f"(d[39]), "+f"(d[40]), "+f"(d[41]), "+f"(d[42]), "+f"(d[43]),
        "+f"(d[44]), "+f"(d[45]), "+f"(d[46]), "+f"(d[47]), "+f"(d[48]), "+f"(d[49]), "+f"(d[50]),
        "+f"(d[51]), "+f"(d[52]), "+f"(d[53]), "+f"(d[54]), "+f"(d[55]), "+f"(d[56]), "+f"(d[57]),
        "+f"(d[58]), "+f"(d[59]), "+f"(d[60]), "+f"(d[61]), "+f"(d[62]), "+f"(d[63])
        : "r"(a0), "r"(a1), "r"(a2), "r"(a3), "l"(db), "r"(scale_d));
}
__device__ __forceinline__ void wgmma_ss_n128_tb_init(float (&d)[64], uint64_t da, uint64_t db) {
    asm volatile("{\n.reg .pred p;\n"
        "setp.ne.b32 p, 0, 0;\n"
        "wgmma.mma_async.sync.aligned.m64n128k16.f32.bf16.bf16 "
        "{%0, %1, %2, %3, %4, %5, %6, %7, %8, %9, %10, %11, %12, %13, %14, %15, %16, %17, %18, %19, %20, "
        "%21, %22, %23, %24, %25, %26, %27, %28, %29, %30, %31, %32, %33, %34, %35, %36, %37, %38, %39, %40, "
        "%41, %42, %43, %44, %45, %46, %47, %48, %49, %50, %51, %52, %53, %54, %55, %56, %57, %58, %59, %60, "
        "%61, %62, %63},"
        " %64, %65, p, 1, 1, 0, 1;\n}\n"
        : "=f"(d[0]), "=f"(d[1]), "=f"(d[2]), "=f"(d[3]), "=f"(d[4]), "=f"(d[5]), "=f"(d[6]), "=f"(d[7]),
        "=f"(d[8]), "=f"(d[9]), "=f"(d[10]), "=f"(d[11]), "=f"(d[12]), "=f"(d[13]), "=f"(d[14]), "=f"(d[15]),
        "=f"(d[16]), "=f"(d[17]), "=f"(d[18]), "=f"(d[19]), "=f"(d[20]), "=f"(d[21]), "=f"(d[22]),
        "=f"(d[23]), "=f"(d[24]), "=f"(d[25]), "=f"(d[26]), "=f"(d[27]), "=f"(d[28]), "=f"(d[29]),
        "=f"(d[30]), "=f"(d[31]), "=f"(d[32]), "=f"(d[33]), "=f"(d[34]), "=f"(d[35]), "=f"(d[36]),
        "=f"(d[37]), "=f"(d[38]), "=f"(d[39]), "=f"(d[40]), "=f"(d[41]), "=f"(d[42]), "=f"(d[43]),
        "=f"(d[44]), "=f"(d[45]), "=f"(d[46]), "=f"(d[47]), "=f"(d[48]), "=f"(d[49]), "=f"(d[50]),
        "=f"(d[51]), "=f"(d[52]), "=f"(d[53]), "=f"(d[54]), "=f"(d[55]), "=f"(d[56]), "=f"(d[57]),
        "=f"(d[58]), "=f"(d[59]), "=f"(d[60]), "=f"(d[61]), "=f"(d[62]), "=f"(d[63])
        : "l"(da), "l"(db));
}
__device__ __forceinline__ void wgmma_ss_n128_tb(float (&d)[64], uint64_t da, uint64_t db, int scale_d) {
    asm volatile("{\n.reg .pred p;\n"
        "setp.ne.b32 p, %66, 0;\n"
        "wgmma.mma_async.sync.aligned.m64n128k16.f32.bf16.bf16 "
        "{%0, %1, %2, %3, %4, %5, %6, %7, %8, %9, %10, %11, %12, %13, %14, %15, %16, %17, %18, %19, %20, "
        "%21, %22, %23, %24, %25, %26, %27, %28, %29, %30, %31, %32, %33, %34, %35, %36, %37, %38, %39, %40, "
        "%41, %42, %43, %44, %45, %46, %47, %48, %49, %50, %51, %52, %53, %54, %55, %56, %57, %58, %59, %60, "
        "%61, %62, %63},"
        " %64, %65, p, 1, 1, 0, 1;\n}\n"
        : "+f"(d[0]), "+f"(d[1]), "+f"(d[2]), "+f"(d[3]), "+f"(d[4]), "+f"(d[5]), "+f"(d[6]), "+f"(d[7]),
        "+f"(d[8]), "+f"(d[9]), "+f"(d[10]), "+f"(d[11]), "+f"(d[12]), "+f"(d[13]), "+f"(d[14]), "+f"(d[15]),
        "+f"(d[16]), "+f"(d[17]), "+f"(d[18]), "+f"(d[19]), "+f"(d[20]), "+f"(d[21]), "+f"(d[22]),
        "+f"(d[23]), "+f"(d[24]), "+f"(d[25]), "+f"(d[26]), "+f"(d[27]), "+f"(d[28]), "+f"(d[29]),
        "+f"(d[30]), "+f"(d[31]), "+f"(d[32]), "+f"(d[33]), "+f"(d[34]), "+f"(d[35]), "+f"(d[36]),
        "+f"(d[37]), "+f"(d[38]), "+f"(d[39]), "+f"(d[40]), "+f"(d[41]), "+f"(d[42]), "+f"(d[43]),
        "+f"(d[44]), "+f"(d[45]), "+f"(d[46]), "+f"(d[47]), "+f"(d[48]), "+f"(d[49]), "+f"(d[50]),
        "+f"(d[51]), "+f"(d[52]), "+f"(d[53]), "+f"(d[54]), "+f"(d[55]), "+f"(d[56]), "+f"(d[57]),
        "+f"(d[58]), "+f"(d[59]), "+f"(d[60]), "+f"(d[61]), "+f"(d[62]), "+f"(d[63])
        : "l"(da), "l"(db), "r"(scale_d));
}

enum { M_X = 0, M_C, M_WQ, M_WUK, M_WUV, M_WQKV, M_WO, M_WOB, M_SCR_LD, M_SCR_LOC, M_SCR_LOQ, M_SCR_ST, M_COUNT };
enum { T_Q = 0, T_K, T_V, T_B, T_OUT, T_LOCAL, T_ATTN, T_END };
constexpr int NCTA = 132, NPAIR = NCTA / 2;
constexpr int NITEMS = 480 + 64 + 256;
constexpr int TRIPLES = 3, WIDE = 80 - 3 * TRIPLES;
struct Params {
    CUtensorMap m[M_COUNT];
    const __nv_bfloat16* x;
    const __nv_bfloat16* gate_w;
    const char* wo;
    __nv_bfloat16* out;
    uint32_t zero;
    uint16_t items[NITEMS];
    uint8_t ostep[80];
};
__device__ __forceinline__ int item_type(int it) { return it >> 13; }
__device__ __forceinline__ int item_row(int it) { return it & 15; }
__device__ __forceinline__ int item_col(int it) { return (it >> 4) & 31; }
__device__ __forceinline__ int item_asc(int it) { return (it >> 9) & 1; }
constexpr int ITEM_READY = 1 << 10;

struct __align__(128) Sync {
    unsigned long long count[4];
    __align__(128) unsigned long long ctx[16];
    unsigned next, next_out, done;
    __align__(128) unsigned step[32][2];
    unsigned split[32];
};
__device__ Sync g_sync;
__device__ uint4 g_part[128][8][256];

constexpr uint32_t GST_BYTES = 49152, SM_KV = 65536, SM_STAGING = 196608, SM_BARS = SM_STAGING + 32768;
constexpr uint32_t B_GFULL = 0, B_GEMPTY = 32, B_AFULL = 64, B_AEMPTY = 112, B_SFULL = 160, B_SEMPTY = 192,
                   B_IFULL = 224, B_IEMPTY = 288, B_XFREE = 352, B_WANT = 384, B_MEET = 392, B_HALF = 416,
                   SM_ORDY = 448, SM_QUEUE = 456, B_ALT = 488, B_QFREE = 504, SM_GATE = 512, SM_TOTAL = SM_BARS + 1536;
constexpr int QDEPTH = 8;
constexpr int FIRST_PAIR = 6;
constexpr int K_MEET = 12, K_SPLIT = 26;
constexpr int K_FETCH = 20;
constexpr uint32_t LOC_PLANE = 72 * 128;
constexpr float LOC_SCALE = 0.17677669529663687f * 1.4426950408889634f;
constexpr float SUM_LIMIT = 1152921504606846976.f;
constexpr float REF_RANGE = 32.f;

__device__ __forceinline__ unsigned ld_acquire(const unsigned* p) {
    unsigned v; asm volatile("ld.acquire.gpu.global.u32 %0, [%1];" : "=r"(v) : "l"(p) : "memory"); return v;
}
__device__ __forceinline__ unsigned long long ld_acquire(const unsigned long long* p) {
    unsigned long long v; asm volatile("ld.acquire.gpu.global.u64 %0, [%1];" : "=l"(v) : "l"(p) : "memory"); return v;
}
__device__ __forceinline__ void st_b128(void* p, uint32_t a, uint32_t b, uint32_t c, uint32_t d) {
    asm volatile("{\n.reg .b128 v;\n.reg .b64 lo, hi;\nmov.b64 lo, {%1, %2};\nmov.b64 hi, {%3, %4};\nmov.b128 v, {lo, hi};\n"
                 "st.relaxed.gpu.global.b128 [%0], v;\n}\n" :: "l"(p), "r"(a), "r"(b), "r"(c), "r"(d) : "memory");
}
__device__ __forceinline__ void ld_b128(const void* p, uint32_t& a, uint32_t& b, uint32_t& c, uint32_t& d) {
    asm volatile("{\n.reg .b128 v;\n.reg .b64 lo, hi;\nld.relaxed.gpu.global.b128 v, [%4];\nmov.b128 {lo, hi}, v;\n"
                 "mov.b64 {%0, %1}, lo;\nmov.b64 {%2, %3}, hi;\n}\n" : "=r"(a), "=r"(b), "=r"(c), "=r"(d) : "l"(p) : "memory");
}
__device__ __forceinline__ void spin_guard(unsigned& n) {
    asm volatile("{\n.reg .pred P;\nadd.u32 %0, %0, 1;\nsetp.gt.u32 P, %0, 16777216;\n@P trap;\n}\n" : "+r"(n));
    if (n > 1) __nanosleep(100);
}
__device__ __forceinline__ void red_add(unsigned long long* p, unsigned long long v) {
    asm volatile("red.release.gpu.global.add.u64 [%0], %1;" :: "l"(p), "l"(v) : "memory");
}
__device__ __forceinline__ float rcp(float x) { float y; asm("rcp.approx.ftz.f32 %0, %1;" : "=f"(y) : "f"(x)); return y; }
__device__ __forceinline__ float lds_f32(uint32_t addr) {
    float v; asm volatile("ld.shared.f32 %0, [%1];" : "=f"(v) : "r"(addr) : "memory"); return v;
}
__device__ __forceinline__ void ldsm_x4(uint32_t (&r)[4], uint32_t addr) {
    asm volatile("ldmatrix.sync.aligned.m8n8.x4.shared.b16 {%0, %1, %2, %3}, [%4];"
                 : "=r"(r[0]), "=r"(r[1]), "=r"(r[2]), "=r"(r[3]) : "r"(addr) : "memory");
}
__device__ __forceinline__ void ldsm_x4_t(uint32_t (&r)[4], uint32_t addr) {
    asm volatile("ldmatrix.sync.aligned.m8n8.x4.trans.shared.b16 {%0, %1, %2, %3}, [%4];"
                 : "=r"(r[0]), "=r"(r[1]), "=r"(r[2]), "=r"(r[3]) : "r"(addr) : "memory");
}
__device__ __forceinline__ void mma_k16(float (&d)[4], const uint32_t (&a)[4], uint32_t b0, uint32_t b1) {
    asm("mma.sync.aligned.m16n8k16.row.col.f32.bf16.bf16.f32 {%0,%1,%2,%3}, {%4,%5,%6,%7}, {%8,%9}, {%0,%1,%2,%3};"
        : "+f"(d[0]), "+f"(d[1]), "+f"(d[2]), "+f"(d[3]) : "r"(a[0]), "r"(a[1]), "r"(a[2]), "r"(a[3]), "r"(b0), "r"(b1));
}
__device__ __forceinline__ void mma_k16_init(float (&d)[4], const uint32_t (&a)[4], uint32_t b0, uint32_t b1) {
    asm("{\n.reg .f32 z;\nmov.f32 z, 0f00000000;\n"
        "mma.sync.aligned.m16n8k16.row.col.f32.bf16.bf16.f32 {%0,%1,%2,%3}, {%4,%5,%6,%7}, {%8,%9}, {z,z,z,z};\n}\n"
        : "=f"(d[0]), "=f"(d[1]), "=f"(d[2]), "=f"(d[3]) : "r"(a[0]), "r"(a[1]), "r"(a[2]), "r"(a[3]), "r"(b0), "r"(b1));
}
__device__ __forceinline__ void mma_k8(float (&d)[4], uint32_t a0, uint32_t a1, uint32_t b0) {
    asm("mma.sync.aligned.m16n8k8.row.col.f32.bf16.bf16.f32 {%0,%1,%2,%3}, {%4,%5}, {%6}, {%0,%1,%2,%3};"
        : "+f"(d[0]), "+f"(d[1]), "+f"(d[2]), "+f"(d[3]) : "r"(a0), "r"(a1), "r"(b0));
}
template <typename T, int N> __device__ __forceinline__ void zero_regs(T (&d)[N]) {
#pragma unroll
    for (int i = 0; i < N; i++) d[i] = 0;
}
__device__ __forceinline__ float quad_max(float v) {
    v = fmaxf(v, __shfl_xor_sync(0xffffffffu, v, 1));
    return fmaxf(v, __shfl_xor_sync(0xffffffffu, v, 2));
}
__device__ __forceinline__ float quad_sum(float v) {
    v += __shfl_xor_sync(0xffffffffu, v, 1);
    return v + __shfl_xor_sync(0xffffffffu, v, 2);
}

__device__ __forceinline__ void qk_gemm(float (&s)[64], uint32_t q_lo, uint32_t k_lo) {
    const uint64_t dq = full_desc(q_lo), dk = full_desc(k_lo);
    fence_regs(s);
    wgmma_fence();
#pragma unroll
    for (int kk = 0; kk < 8; kk++) {
        const uint32_t o = (kk >> 2) * 1024 + (kk & 3) * 2;
        wgmma_ss_n128(s, dq + o, dk + o, kk != 0);
    }
    wgmma_commit();
}
__device__ __forceinline__ void pv_gemm(float (&o)[64], uint32_t (&p)[32], uint32_t v_lo, int accumulate) {
    const uint64_t dv = full_desc(v_lo);
    fence_regs(o);
    fence_regs(p);
    wgmma_fence();
#pragma unroll
    for (int kk = 0; kk < 8; kk++)
        wgmma_rs_n128_tb(o, p[4 * kk], p[4 * kk + 1], p[4 * kk + 2], p[4 * kk + 3], dv + kk * 128, kk != 0 || accumulate);
    wgmma_commit();
}
__device__ __forceinline__ void row_max(const float (&s)[64], float& x0, float& x1) {
    float z0 = fmaxf(s[0], s[1]), z1 = fmaxf(s[2], s[3]);
    x0 = fmaxf(s[4], s[5]); x1 = fmaxf(s[6], s[7]);
#pragma unroll
    for (int j = 2; j < 16; j += 2) {
        z0 = fmaxf(z0, fmaxf(s[4 * j], s[4 * j + 1]));
        z1 = fmaxf(z1, fmaxf(s[4 * j + 2], s[4 * j + 3]));
        x0 = fmaxf(x0, fmaxf(s[4 * j + 4], s[4 * j + 5]));
        x1 = fmaxf(x1, fmaxf(s[4 * j + 6], s[4 * j + 7]));
    }
    x0 = quad_max(fmaxf(x0, z0)); x1 = quad_max(fmaxf(x1, z1));
}
__device__ __forceinline__ void exp_pack(uint32_t (&p)[32], const float (&s)[64], float& r0, float& r1) {
#pragma unroll
    for (int j = 0; j < 16; j++) {
        const float e0 = ex2(s[4 * j]), e1 = ex2(s[4 * j + 1]), e2 = ex2(s[4 * j + 2]), e3 = ex2(s[4 * j + 3]);
        if (j == 0) { r0 = e0 + e1; r1 = e2 + e3; }
        else { r0 += e0 + e1; r1 += e2 + e3; }
        p[2 * j] = pack_bf16(e0, e1);
        p[2 * j + 1] = pack_bf16(e2, e3);
    }
}
__device__ __forceinline__ void shift_rows(float (&s)[64], float d0, float d1) {
#pragma unroll
    for (int j = 0; j < 16; j++) { s[4 * j] -= d0; s[4 * j + 1] -= d0; s[4 * j + 2] -= d1; s[4 * j + 3] -= d1; }
}
constexpr float MASKED = -3e38f;
template <int J0>
__device__ __forceinline__ void mask_triangle(float (&s)[64], float thr) {
#pragma unroll
    for (int j = 0; j < 16; j++) {
        const float m = __saturatef((float)(8 * (j >> 1) + (j & 1)) - thr);
        const int i = 4 * (J0 + (j >> 1)) + (j & 1);
        s[i] = fmaf(m, MASKED, s[i]);
        if (j < 14) s[i + 6] = fmaf(m, MASKED, s[i + 6]);
    }
}
__device__ __forceinline__ void causal_mask(float (&s)[64], float thr, int wg) {
    asm volatile("" : "+f"(thr));
    if (wg == 0) {
        mask_triangle<0>(s, thr);
#pragma unroll
        for (int j = 32; j < 64; j++) s[j] += MASKED;
    } else {
        mask_triangle<8>(s, thr);
    }
}

__global__ void __cluster_dims__(2, 1, 1) __launch_bounds__(384, 1) fused_kernel(const __grid_constant__ Params prm) {
    extern __shared__ __align__(1024) uint8_t smem[];
    const uint32_t sb = smem_u32(smem), bars = sb + SM_BARS;
    const int warp = __shfl_sync(0xffffffffu, threadIdx.x >> 5, 0), lane = threadIdx.x & 31;

    const uint32_t rank = cluster_rank();
    const uint32_t bars0 = map_cta(bars, 0), bars_peer = map_cta(bars, rank ^ 1);

    auto first_item = [&]() -> int {
        uint32_t pair = blockIdx.x >> 1;
        asm volatile("" : "+r"(pair));
        const uint32_t m = pair * 43 >> 9;
        return T_B << 13 | (pair - 12 * m) << 4 | (2 * m + rank);
    };
    if (warp == 0) {
        if (elect_one()) {
            for (int k = 0; k < 4; k++) mbar_init(bars + B_GFULL + 8 * k, 1);
            asm volatile("fence.mbarrier_init.release.cluster;" ::: "memory");
            fence_proxy_async_smem();
        }
        __syncwarp();
        const int first_it = __shfl_sync(0xffffffffu, first_item(), 0);
        asm volatile("barrier.cluster.arrive.relaxed.aligned;" ::: "memory");
#pragma unroll
        for (int k = 0; k < 2; k++) {
            const uint32_t dst = sb + k * GST_BYTES, fb = bars + B_GFULL + 8 * k;
            warp_expect_tx(fb, GST_BYTES);
            warp_tma_load(dst + 16384, &prm.m[M_WQKV], fb, 0, k * 64, item_col(first_it) * 4, false);
            warp_tma_load(dst, &prm.m[M_X], fb, k * 64, item_row(first_it) * 128, 0, false);
            warp_tma_load(dst + 32768, &prm.m[M_WQKV], fb, 0, k * 64, item_col(first_it) * 4 + 2, false);
        }
    }
    if (threadIdx.x == 32) {
        for (int i = 0; i < 4; i++) { mbar_init(bars + B_GEMPTY + 8 * i, 16); mbar_init(bars + B_XFREE + 8 * i, 1); }
        for (int i = 0; i < 6; i++) { mbar_init(bars + B_AFULL + 8 * i, 1); mbar_init(bars + B_AEMPTY + 8 * i, i < 2 ? 8 : 16); }
        for (int i = 0; i < 4; i++) { mbar_init(bars + B_SFULL + 8 * i, 4); mbar_init(bars + B_SEMPTY + 8 * i, 1); }
        for (int i = 0; i < QDEPTH; i++) { mbar_init(bars + B_IFULL + 8 * i, 1); mbar_init(bars + B_IEMPTY + 8 * i, 23); }
        mbar_init(bars + B_WANT, 2); mbar_init(bars + B_MEET, 1);
        for (int i = 0; i < 4; i++) mbar_init(bars + B_HALF + 8 * i, 1);
        mbar_init(bars + B_ALT, 4); mbar_init(bars + B_ALT + 8, 4); mbar_init(bars + B_QFREE, 2);
        asm volatile("st.shared.u64 [%0], 0;" :: "r"(bars + SM_ORDY) : "memory");
        asm volatile("fence.mbarrier_init.release.cluster;\nfence.acq_rel.cta;" ::: "memory");
    }
    __syncwarp();
    if (warp != 0) asm volatile("barrier.cluster.arrive.relaxed.aligned;" ::: "memory");
    asm volatile("barrier.cluster.wait.acquire.aligned;" ::: "memory");

    uint32_t qn = 0;
    auto next_item = [&](bool releaser, bool bounded = true) -> int {
        const uint32_t slot = qn % QDEPTH;
        if (bounded) mbar_wait(bars + B_IFULL + 8 * slot, (qn / QDEPTH) & 1);
        else mbar_spin(bars + B_IFULL + 8 * slot, (qn / QDEPTH) & 1);
        uint32_t it;
        asm volatile("ld.shared.u32 %0, [%1];" : "=r"(it) : "r"(bars + SM_QUEUE + 4 * slot) : "memory");
        mbar_arrive_cluster_if(releaser, bars0 + B_IEMPTY + 8 * slot);
        qn++;
        return it;
    };

    if (warp < 4) {
        reg_dec<40>();
        if (warp == 0) {
            {
                uint32_t gph = 1;
                const uint32_t prank = __shfl_sync(0xffffffffu, rank, 0);
                auto request = [&]() { mbar_arrive_cluster_if(lane == 0, bars0 + B_WANT); };
                auto take_item = [&]() -> int { return __shfl_sync(0xffffffffu, next_item(lane == 0), 0); };
                auto inputs_seen = [&](uint32_t word, unsigned& n) -> uint32_t {
                    uint32_t v;
                    spin_guard(n);
                    asm volatile("ld.acquire.cta.shared.u32 %0, [%1];" : "=r"(v) : "r"(bars + SM_ORDY + 4 * word) : "memory");
                    return __shfl_sync(0xffffffffu, v, 0);
                };
                uint32_t oneed = 0;
                auto wait_inputs = [&](int it) {
                    if (it & ITEM_READY) return;
                    oneed += 256;
                    for (unsigned n = 0; inputs_seen(1, n) < oneed;) {}
                };
                int nxt = first_item();
                for (int k0 = 2; item_type(nxt) <= T_LOCAL; k0 = 0) {
                    const int type = item_type(nxt), m = item_row(nxt), c = item_col(nxt);
                    if (type == T_LOCAL) {
                        wait_inputs(nxt);
                        request();
#pragma unroll 1
                        for (uint32_t st = 0; st < 4; st++) {
                            mbar_wait(bars + B_GEMPTY + 8 * st, gph);
                            const uint32_t dst = sb + st * GST_BYTES, fb = bars + B_GFULL + 8 * st;
                            warp_expect_tx(fb, st == 0 ? 32768 + 512 : st == 3 ? 0 : 4 * LOC_PLANE);
                            if (st == 3) break;
                            if (st == 0) warp_bulk_load(dst + 4 * LOC_PLANE, &g_gate[m * 128], 512, fb);
#pragma unroll 1
                            for (int i = 0; i < 4; i++)
                                warp_tma_load(dst + i * LOC_PLANE, &prm.m[st ? M_SCR_LOC : M_SCR_LOQ], fb, i * 64, m * 64 - (st ? 8 : 0), G_B + 8 * st + c, true);
                        }
                        gph ^= 1;
                    } else {
                        const int nk = type == T_K || type == T_V ? 8 : 16;
                        const CUtensorMap* ma = &prm.m[nk == 8 ? M_C : M_X];
                        const CUtensorMap* mb = &prm.m[M_WQ + type];
#pragma unroll 1
                        for (int k = k0; k < nk; k++) {
                            if (k == nk - 3) request();
                            const uint32_t st = k & 3, dst = sb + st * GST_BYTES, fb = bars + B_GFULL + 8 * st;
                            mbar_wait(bars + B_GEMPTY + 8 * st, gph);
                            warp_expect_tx(fb, GST_BYTES);
                            warp_tma_load(dst, ma, fb, k * 64, m * 128, 0, c == 15 && type != T_K);
                            warp_tma_load_pair(dst + 16384 + prank * 16384, mb, fb, 0, k * 64, c * 4 + 2 * prank, type != T_B || m >= 14);
                            if (st == 3) gph ^= 1;
                        }
                    }
                    nxt = take_item();
                }
                uint32_t kv = 0, kvph = 1;
                uint32_t qc = 0;
                auto a_parity = [&](uint32_t b) { return b < 2 ? (((qc + 1 - b) >> 1) & 1) ^ 1 : kvph ^ (b - 2 < kv); };
                const CUtensorMap* tile_map = &prm.m[M_SCR_LD];
                asm volatile("" : "+l"(tile_map));
                {
                    bool need_g = true, more = true;
                    int pv_grp = -1, pv_row = 0;
                    int pv_shared = 0;
                    bool peer_longer = false;
                    int m = 0, c = 0, asc = 0, nu = 0, uend = 0, ureq = -1, ufetch = 0;
#pragma unroll 1
                    for (int u = 0;; u++) {
                        if (u == ufetch) {
                            if (qc) nxt = take_item();
                            if (item_type(nxt) == T_ATTN) {
                                wait_inputs(nxt);
                                const uint32_t b = qc & 1, dst = sb + b * 32768, fb = bars + B_AFULL + 8 * b, row = item_row(nxt) * 128;
                                mbar_wait(bars + (qc == 0 ? B_GEMPTY : qc == 1 ? B_QFREE : B_AEMPTY + 8 * b), qc == 0 ? gph : qc == 1 ? 0 : a_parity(b));
                                warp_expect_tx(fb, 32768 + 512);
                                warp_tma_load(dst, tile_map, fb, 0, row, G_Q + item_col(nxt), false);
                                warp_tma_load(dst + 16384, tile_map, fb, 64, row, G_Q + item_col(nxt), false);
                                warp_bulk_load(bars + SM_GATE + b * 512, &g_gate[row], 512, fb);
                                qc++;
                            }
                        }
                        if (u == uend) {
                            if (!more) break;
                            more = item_type(nxt) == T_ATTN;
                            m = item_row(nxt); c = item_col(nxt); asc = item_asc(nxt);
                            nu = more ? 2 * m + 2 : 0;
                            uend = nu + ((more ? m < 2 : pv_grp >= 0) ? 3 : 0);
                            ureq = 2 * max(m - 2 - (asc & m), 0);
                            ufetch = !more ? -1 : m ? 2 * m : uend;
                            u = -1;
                            continue;
                        }
                        int grp = pv_grp, row = pv_row;
                        int shared = pv_shared;
                        if (u >= nu) {
                            if (u == nu + 1) pv_grp = -1;
                            else if (peer_longer) { grp = -1; shared = 0; }
                            else continue;
                        } else {
                            const int j = asc ? u >> 1 : m - (u >> 1);
                            if (u & 1) {
                                pv_grp = G_V + c; pv_row = j * 128; pv_shared = (m | 1) - j;
                                peer_longer = asc & ~m & 1;
                                if (u == nu - 1 && (m & 1) && item_type(nxt) == T_END) mbar_arrive_cluster_n_if(lane == 0, bars0 + B_WANT, 2);
                                if (grp < 0) continue;
                            } else {
                                if (u == ureq) request();
                                grp = G_K + c; row = j * 128; shared = (m | 1) - j;
                            }
                        }
                        uint32_t fb = bars + B_AFULL + 16 + 8 * kv, mine = sb + SM_KV + kv * 32768 + prank * 16384;
                        int c_mine = prank * 64;
                        asm volatile("" : "+r"(mine), "+r"(fb), "+r"(row), "+r"(grp), "+r"(c_mine));
                        mbar_wait(need_g ? bars + B_GEMPTY + 8 + 8 * kv : fb + B_AEMPTY - B_AFULL, need_g ? gph : kvph);
                        warp_expect_tx(fb, grp < 0 ? 0 : 32768);
                        if (shared) {
                            warp_tma_load_pair(mine, tile_map, fb, c_mine, row, grp, shared == 1);
                        } else if (grp >= 0) {
                            warp_tma_load(mine, tile_map, fb, c_mine, row, grp, true);
                            warp_tma_load(mine + 16384 - prank * 32768, tile_map, fb, 64 - c_mine, row, grp, true);
                        } else {
                            mbar_arrive_cluster_n_if(lane < 2, map_cta(fb, lane & 1) + B_AEMPTY - B_AFULL, 8);
                        }
                        if (kv == 2) need_g = false;
                        if (++kv == 4) { kv = 0; kvph ^= 1; }
                    }
                }
                if (!qc) request();
                const int it = take_item();
                int nk = 0;
                if (item_type(it) == T_OUT) {
                    const int m = item_row(it), c = item_col(it), half = c & 1;
                    nk = 80;
                    for (int k = 0; k < nk; k++) {
                        if (k == K_SPLIT) nk = 2 * TRIPLES + (take_item() & 127);
                        const int kn = k + 2 * TRIPLES - nk, first = kn >= 0 && !(kn & 1);
                        const int s = kn >= 0 ? WIDE + (3 * kn + 1) / 2 : half ? WIDE - 1 - k : k;
                        const uint32_t sa = prm.ostep[s], sa2 = prm.ostep[s + first], sw = prm.ostep[s - (kn >= 0 && !first ? prank : 0)];
                        const uint32_t need = 1u << (sa >> 1 & 31) | 1u << (sa2 >> 1 & 31);
                        for (unsigned n = 0; need & ~inputs_seen(sa >> 6, n);) {}
                        const uint32_t st = k & 3;
                        uint32_t dst = sb + st * GST_BYTES, fb = bars + B_GFULL + 8 * st;
                        uint32_t dstb = dst + 16384 + (first ? 0 : prank * 16384), skipb = first && (kn >> 1 & 1) != prank;
                        int a0 = (sa & 1) * 64, a1 = m * 128, a2 = (sa >> 1) + (sa < 64 ? G_CTX : G_LOC - 32);
                        int b1 = (sw & 63) * 64, b2 = (c >> 1) * 4 + 2 * (kn >= 0 ? half : half ^ prank);
                        const CUtensorMap* mb = &prm.m[sw >= 64 ? M_WOB : M_WO];
                        asm volatile("" : "+r"(dst), "+r"(fb), "+r"(dstb), "+r"(skipb), "+r"(a0), "+r"(a1), "+r"(a2), "+r"(b1), "+r"(b2), "+l"(mb));
                        if (k < 4) {
#pragma unroll 1
                            for (uint32_t i = 0, b = (3 * st) >> 1; i < 3; i++, b++) mbar_wait(bars + (i == 2 ? B_QFREE : B_AEMPTY + 8 * b), i == 2 ? 0 : a_parity(b));
                            mbar_arrive_cluster_if(lane == 0, bars_peer + B_XFREE + 8 * st);
                            mbar_wait(bars + B_XFREE + 8 * st, 0);
                        }
                        mbar_wait(bars + B_GEMPTY + 8 * st, gph);
                        warp_expect_tx(fb, GST_BYTES);
                        warp_tma_load(dst, tile_map, fb, a0, a1, a2, true);
                        if (!skipb) warp_tma_load_pair(dstb, mb, fb, 0, b1, b2, false);
                        if (first) warp_tma_load(dst + 32768, tile_map, fb, (sa2 & 1) * 64, a1, G_CTX + (sa2 >> 1), true);
                        if (k < K_SPLIT && lane == 0 && !prank)
                            asm volatile("st.relaxed.gpu.global.u32 [%0], %1;" :: "l"(&g_sync.step[0][0] + m * 4 + c), "r"(k) : "memory");
                        mbar_arrive_if(k == K_MEET && lane == 0, bars + B_MEET);
                        if ((uint32_t)(k - K_FETCH) < (3 * TRIPLES + 1) / 2) {
                            const uint32_t g = prm.ostep[79 - 2 * (k - K_FETCH)] >> 1;
                            warp_prefetch((const char*)g_scr + (uint32_t)((G_CTX + g) * (SEQ * 256) + m * 32768 + c * 4096), 4096);
                            warp_prefetch(prm.wo + (uint32_t)(g * 262144 + (m * 8 + c) * 2048), 2048);
                        }
                        if (st == 3) gph ^= 1;
                    }
                    for (unsigned n = 0; ~inputs_seen(0, n) || inputs_seen(1, n) != 255;) {}
                }
#pragma unroll 1
                for (uint32_t st = 0; st < 4; st++) { mbar_wait(bars + B_GEMPTY + 8 * st, gph ^ (st < (nk & 3))); mbar_wait(bars + B_AEMPTY + 16 + 8 * st, a_parity(2 + st)); }
                unsigned left = 0;
                if (lane == 0) asm volatile("atom.relaxed.gpu.global.add.u32 %0, [%1], 1;" : "=r"(left) : "l"(&g_sync.done) : "memory");
                if (__shfl_sync(0xffffffffu, left, 0) == NCTA - 1)
#pragma unroll 1
                    for (uint32_t i = lane * 8; i < sizeof(Sync); i += 256) *(unsigned long long*)((char*)&g_sync + i) = 0;
            }
        } else if (warp <= 2) {
            if (blockIdx.x < SEQ / 16) {
                const uint32_t r0 = 16 * blockIdx.x + 8 * (warp - 1), gbuf = bars + SM_GATE + 4 * (r0 & 15);
                float z[4];
                mbar_wait(bars + B_GFULL + 24, 0);
#pragma unroll 1
                for (uint32_t i = 0; i < 8; i++) {
                    const uint32_t off = (i & 3) * 512 + lane * 16;
                    const uint4* xp = (const uint4*)((const char*)prm.x + ((r0 + (i & 4)) * 2048 + off));
                    const uint4 wv = __ldg((const uint4*)((const char*)prm.gate_w + off));
                    uint4 xv[4];
#pragma unroll
                    for (int r = 0; r < 4; r++) { xv[r] = __ldg(xp + r * 128); if (!(i & 3)) z[r] = 0.f; }
                    const uint32_t ws[4] = {wv.x, wv.y, wv.z, wv.w};
#pragma unroll
                    for (int e = 0; e < 4; e++)
#pragma unroll
                        for (int r = 0; r < 4; r++) {
                            const uint32_t xs = e == 0 ? xv[r].x : e == 1 ? xv[r].y : e == 2 ? xv[r].z : xv[r].w;
                            z[r] = fmaf(__uint_as_float(xs << 16), __uint_as_float(ws[e] << 16), z[r]);
                            z[r] = fmaf(__uint_as_float(xs & 0xffff0000u), __uint_as_float(ws[e] & 0xffff0000u), z[r]);
                        }
                    if ((i & 3) == 3) {
#pragma unroll
                        for (int o = 16; o > 0; o >>= 1)
#pragma unroll
                            for (int r = 0; r < 4; r++) z[r] += __shfl_xor_sync(0xffffffffu, z[r], o);
                        const float zr = lane & 2 ? (lane & 1 ? z[3] : z[2]) : (lane & 1 ? z[1] : z[0]);
                        asm volatile("st.shared.f32 [%0], %1;" :: "r"(gbuf + 4 * ((i & 4) + (lane & 3))), "f"(1.f / (1.f + __expf(-zr))) : "memory");
                    }
                }
                fence_proxy_async_smem();
                __syncwarp();
                warp_bulk_store((char*)g_gate + 4 * r0, gbuf, 32);
                bulk_commit();
                bulk_wait<0>();
                __syncwarp();
                if (lane == 0) red_add(&g_sync.count[3], 1);
            }
            __syncwarp();
            {
                const int w = warp - 1;
                uint32_t sph = 0, nann = 0;
                int unsent = 0, nunsent = 0;
                bool urgent = false;
                auto announce = [&]() {
                    if (!urgent) return;
                    bulk_wait<0>();
                    __syncwarp();
                    const uint32_t hb = bars + B_HALF + 8 * (nann & 3);
                    if (w == 0) {
                        mbar_arrive_if(lane == 0, hb);
                    } else {
                        mbar_wait(hb, (nann >> 2) & 1);
                        const uint32_t type = item_type(unsent), m = item_row(unsent), c = item_col(unsent);
                        const uint32_t word = type < T_B ? c >> 3 : type == T_B ? 2 : offsetof(Sync, ctx) / 8 + m;
                        const uint32_t bit = type < T_B ? 8 * (c & 7) : type == T_B ? 4 * m : type == T_LOCAL ? 32 + c : c;
                        if (lane < nunsent) red_add((unsigned long long*)((char*)&g_sync + 8 * word), 1ull << bit);
                        __syncwarp();
                    }
                    nann++;
                    nunsent = 0; urgent = false;
                };
                int held = first_item(), it;
                bool qfree = false;
                do {
                    if (!__all_sync(0xffffffffu, mbar_test(bars + B_IFULL + 8 * (qn % QDEPTH), (qn / QDEPTH) & 1))) announce();
                    it = __shfl_sync(0xffffffffu, next_item(lane == 0), 0);
                    const int itype = item_type(it);
                    const bool keep_held = itype == T_LOCAL && (item_type(held) != T_B || (it & ITEM_READY));
                    if (itype >= T_ATTN && held < 0) {
                        urgent = nunsent;
                        mbar_arrive_if(lane == 0 && !qfree, bars + B_QFREE);
                        qfree = true;
                    }
#pragma unroll 1
                    for (int pass = held < 0 || keep_held; pass < 2; pass++) {
                        if (pass && (itype < T_OUT || itype == T_END)) break;
                        const int cur = pass ? it : held, type = item_type(cur), m = item_row(cur), c = item_col(cur);
                        const bool local = type == T_LOCAL;
                        const int grp = pass ? (local ? G_LOC : G_CTX) + c : type * 32 + 2 * c;
#pragma unroll 1
                        for (int i = 0; i < 4 - 2 * pass; i++) {
                            const int b = i & 1;
                            const bool alt = i >= 2 && itype == T_ATTN;
                            const uint32_t full = bars + (alt ? B_ALT + 8 * w : B_SFULL + 16 * w + 8 * b), par = alt ? 0 : sph;
                            if (i == 3 - 2 * pass || !__all_sync(0xffffffffu, mbar_test(full, par))) announce();
                            mbar_wait(full, par);
                            fence_proxy_async_smem();
                            warp_tma_store(&prm.m[local ? M_SCR_LOQ : M_SCR_ST], sb + (alt ? 32768 : SM_STAGING) + w * 16384 + b * 8192,
                                         local ? b * 128 + w * 64 : b * 64, local ? m * 64 : m * 128 + w * 64, grp + (i >> 1), local || (type < T_B && c < FIRST_PAIR));
                            bulk_commit();
                            bulk_wait_read<0>();
                            __syncwarp();
                            mbar_arrive_if(lane == 0 && !alt, bars + B_SEMPTY + 16 * w + 8 * b);
                            sph ^= b & !alt;
                        }
                        mbar_arrive_if(lane == 0 && !qfree && itype >= T_ATTN, bars + B_QFREE);
                        qfree |= itype >= T_ATTN;
                        if (lane == nunsent) unsent = cur;
                        nunsent++;
                        urgent = nunsent == 32 || !local;
                    }
                    if (!keep_held) held = itype < T_OUT ? it : -1;
                } while (item_type(it) != T_END);
                announce();
                if (item_type(next_item(lane == 0)) == T_OUT) {
                    if (w) {
                        mbar_wait(bars + B_MEET, 0);
                        asm volatile("fence.acq_rel.gpu;" ::: "memory");
                        mbar_arrive_cluster_if(lane == 0, bars0 + B_WANT);
                    }
                    next_item(lane == 0);
                }
            }
        } else {
            if (elect_one()) {
                uint32_t ordy = 0;
                unsigned long long cnt_lo = 0, cnt_hi = 0;
                int late = 0;
                auto refresh = [&]() {
                    if (!late && cnt_lo == 0xccccccccccccccccull && cnt_hi == SEQ / 8) late = 1;
                    asm volatile("ld.acquire.gpu.global.v2.u64 {%0, %1}, [%2];" : "=l"(cnt_lo), "=l"(cnt_hi) : "l"(late ? &g_sync.count[0] : &g_sync.count[2]) : "memory");
                };
                auto inputs_ready = [&](int it) -> bool {
                    const int m = item_row(it), c = item_col(it);
                    if (item_type(it) == T_ATTN) return late && ((c < 16 ? cnt_lo : cnt_hi) >> (4 * (c & 14)) & 255) == 48;
                    return late || (cnt_hi == SEQ / 8 && (cnt_lo >> (4 * m) & 15) == 12 && (cnt_lo >> (4 * max(m - 1, 0)) & 15) == 12);
                };
                auto publish = [&](int it, int step) {
                    const uint32_t slot = qn % QDEPTH;
                    mbar_wait(bars + B_IEMPTY + 8 * slot, ((qn / QDEPTH) & 1) ^ 1);
                    for (uint32_t r = 0; r < 2; r++) {
                        const uint32_t rb = map_cta(bars, r);
                        asm volatile("mbarrier.arrive.expect_tx.shared::cluster.b64 _, [%0], 4;" :: "r"(rb + B_IFULL + 8 * slot) : "memory");
                        asm volatile("st.async.shared::cluster.mbarrier::complete_tx::bytes.u32 [%0], %1, [%2];"
                                     :: "r"(rb + SM_QUEUE + 4 * slot), "r"(it + r * step), "r"(rb + B_IFULL + 8 * slot) : "memory");
                    }
                    qn++;
                };
                int asc = 1;
                int it;
                do {
                    if (rank == 0) {
                        mbar_wait(bars + B_WANT, qn & 1);
                        unsigned i;
                        asm volatile("atom.relaxed.gpu.global.add.u32 %0, [%1], 1;" : "=r"(i) : "l"(&g_sync.next) : "memory");
                        if (cnt_lo != 0x3030303030303030ull || cnt_hi != cnt_lo) refresh();
                        i += NPAIR;
                        const int pit = i < NITEMS ? prm.items[i] : T_END << 13, type = item_type(pit);
                        int step = type == T_LOCAL ? 16 : 1;
                        it = pit + (pit & (step == 1 ? 15 : 0x1f0));
                        if (type == T_ATTN) {
                            if (!asc) { it += 1; step = -1; }
                            it |= asc << 9;
                        }
                        asc = type != T_ATTN || item_row(pit) == 0 || !asc;
                        if (inputs_ready(it)) it |= ITEM_READY;
                        publish(it, step);
                    } else {
                        it = next_item(true);
                    }
                    if ((item_type(it) == T_ATTN || item_type(it) == T_LOCAL) && !(it & ITEM_READY)) {
                        unsigned n = 0;
                        while (!inputs_ready(it)) { refresh(); spin_guard(n); }
                        asm volatile("st.release.cta.shared.u32 [%0], %1;" :: "r"(bars + SM_ORDY + 4), "r"(ordy += 256) : "memory");
                    }
                } while (item_type(it) != T_END);
                if (rank == 0) {
                    mbar_wait(bars + B_WANT, qn & 1);
                    const unsigned i = atomicAdd(&g_sync.next_out, 1u), t = i < 32 ? 31 - i : i - 32;
                    it = i < 64 ? T_OUT << 13 | ((t & 3) * 2 + (i >> 5)) << 4 | (t >> 2) * 2 : T_END << 13;
                    publish(it, 1);
                } else {
                    it = next_item(true);
                }
                if (item_type(it) == T_OUT) {
                    const uint32_t m = item_row(it), half = item_col(it) & 1, tile = m * 2 + (item_col(it) >> 1);
                    unsigned* split = (unsigned*)((char*)g_sync.split + 4 * tile);
                    unsigned long long rdy = 0;
                    int state = rank ? 2 : 0;
                    for (unsigned n = 0; rdy != 0xffffffffffull || state < 2; spin_guard(n)) {
                        if (rdy != 0xffffffffffull) {
                            rdy = ld_acquire((const unsigned long long*)((char*)g_sync.ctx + 8 * m));
                            asm volatile("st.release.cta.shared.u64 [%0], %1;" :: "r"(bars + SM_ORDY), "l"(rdy) : "memory");
                        }
                        unsigned steps = 0;
                        if (state == 1) {
                            steps = ld_acquire(split);
                        } else if (state == 0 && mbar_test(bars + B_WANT, qn & 1)) {
                            state = 1;
                            unsigned seen;
                            asm volatile("atom.acq_rel.gpu.global.exch.b32 %0, [%1], 1;" : "=r"(seen) : "l"(split) : "memory");
                            if (seen) {
                                const unsigned long long v = ld_acquire((const unsigned long long*)((char*)g_sync.step + 8 * tile));
                                const int d = (int)(v >> 32) - (int)v;
                                steps = (WIDE + min(max(half ? d : -d, -12), 12)) >> 1;
                                atomicExch(split, WIDE - steps);
                            }
                        }
                        if (steps > 1) { publish(T_END << 13 | steps, 0); state = 2; }
                    }
                    if (rank) next_item(true);
                }
                #pragma unroll 1
                for (uint32_t n = qn; n < qn + QDEPTH && rank == 0; n++) mbar_wait(bars + B_IEMPTY + 8 * (n % QDEPTH), ((n / QDEPTH) & 1) ^ 1);
            }
        }
    } else {
        reg_inc<232>();
        const int wg = (warp >> 2) - 1, wq = warp & 3;
        uint32_t gph = 0;
        uint32_t kvn = 0;
        const uint32_t dA = make_desc(sb + wg * 8192, 16);
        uint32_t ti = 0;
        uint32_t sph = 1;
        const uint32_t stg = sb + SM_STAGING + wg * 16384;
        const uint32_t stg_lane = stg + (wq * 16 + (lane & 15)) * 128 + (((lane >> 4) ^ (lane & 7)) << 4);
        auto write_blocks = [&](auto n, uint32_t off, const uint32_t* v) {
            uint32_t a = stg_lane;
            asm volatile("" : "+r"(a));
            a += off;
#pragma unroll
            for (int j = 0; j < decltype(n)::value; j++)
                stmatrix_x4((a ^ (32 * (j & 3))) + (j >> 2) * 8192, v[4 * j], v[4 * j + 1], v[4 * j + 2], v[4 * j + 3]);
        };
        auto release = [&](uint32_t bar) { mbar_arrive_if(lane == 0, bars + bar); };
        const uint32_t bars_lane = map_cta(bars, lane & 1);
        auto release_stage = [&](uint32_t st) { mbar_arrive_cluster_if(lane < 2, bars_lane + B_GEMPTY + 8 * st); };
        auto take_item = [&]() -> int {
            return __shfl_sync(0xffffffffu, next_item(lane == 0, false), 0);
        };
        auto stage_acquire = [&](int b) { mbar_spin(bars + B_SEMPTY + 16 * wg + 8 * b, sph); };
        auto stage_publish = [&](int b) {
            __syncwarp();
            release(B_SFULL + 16 * wg + 8 * b);
        };
        auto stage_chunk = [&](int b, const uint32_t* v) {
            stage_acquire(b);
            write_blocks(std::integral_constant<int, 4>(), b * 8192, v);
            stage_publish(b);
            if (b) sph ^= 1;
        };
        auto publish_pair = [&]() {
            __syncwarp();
            mbar_arrive_if(lane < 2, bars + B_SFULL + 16 * wg + 8 * lane);
            sph ^= 1;
        };
        auto gemm_step = [&](float (&acc)[128], uint32_t dB, int& k) {
            const uint32_t st = k & 3;
            wgmma_wait<0>();
            release_stage((k - 1) & 3);
            mbar_spin(bars + B_GFULL + 8 * st, gph);
            const uint64_t da = full_desc(dA + st * (GST_BYTES >> 4)), db = full_desc(dB + st * (GST_BYTES >> 4));
            wgmma_fence();
#pragma unroll
            for (int kk = 0; kk < 4; kk++) wgmma_ss_n256_tb(acc, da + 2 * kk, db + 128 * kk, 1);
            wgmma_commit();
            gph ^= st == 3;
            k++;
        };
        if (wg == 1) bar_arrive(1, 256);
        int it = first_item();
        while (true) {
            if (item_type(it) <= T_LOCAL) {
                float acc[128];
                uint32_t pk[64];
                bool pending = false;
                int held = T_END;
                auto scale_q = [&](int j0, int n) {
                    if (held != T_Q) return;
#pragma unroll
                    for (int j = j0; j < j0 + n; j++)
                        asm("{\n.reg .b32 t;\nmul.rn.bf16x2 t, %0, %2;\nfma.rn.bf16x2 %0, %0, %1, t;\n}\n" : "+r"(pk[j]) : "r"(0x3e033e03u), "r"(0xb9d8b9d8u));
                };
                zero_regs(pk);
                const uint32_t dB = make_desc(sb + 16384, 8192);
                do {
                    const int type = item_type(it);
                    if (type == T_LOCAL) {
                        int ln = lane;
                        asm volatile("" : "+r"(ln));
                        const int g = ln >> 2, t = ln & 3, par = wq & 1;
                        const uint32_t hc = (wq >> 1) * 4, pl = sb + (par * 2 + wg) * LOC_PLANE;
                        const uint32_t a16 = (ln & 15) * 128 + (((hc + (ln >> 4)) ^ (ln & 7)) << 4), a8 = (ln & 7) * 128 + (((hc + (ln >> 3)) ^ (ln & 7)) << 4);
                        const bool first0 = 2 * t > g, first1 = 2 * t + 1 > g;
                        const uint32_t fmask = (first0 ? 0xffffu : 0u) | (first1 ? 0xffff0000u : 0u);
                        const bool edge = item_row(it) == 0;
                        uint32_t q[4][2][4], kf[9][4], vf[9][4];
                        float w[8];
                        mbar_spin(bars + B_GFULL, gph);
#pragma unroll
                        for (int u = 0; u < 4; u++) { ldsm_x4(q[u][0], pl + u * 2048 + a16); ldsm_x4(q[u][1], pl + u * 2048 + (a16 ^ 32)); }
#pragma unroll
                        for (int j = 0; j < 8; j++) w[j] = lds_f32(sb + 4 * LOC_PLANE + 4 * (2 * g + par) + 64 * j);
                        __syncwarp();
                        release_stage(0);
                        mbar_spin(bars + B_GFULL + 8, gph);
#pragma unroll
                        for (int n = 0; n < 9; n++) ldsm_x4(kf[n], pl + GST_BYTES + n * 1024 + a8);
                        __syncwarp();
                        release_stage(1);
                        float s[8][2];
#pragma unroll
                        for (int u = 0; u < 4; u++) {
                            float d[3][4];
#pragma unroll
                            for (int nt = 0; nt < 3; nt++) {
                                mma_k16_init(d[nt], q[u][0], kf[2 * u + nt][0], kf[2 * u + nt][1]);
                                mma_k16(d[nt], q[u][1], kf[2 * u + nt][2], kf[2 * u + nt][3]);
                            }
                            if (u == 0 && edge) { d[0][0] = -INFINITY; d[0][1] = -INFINITY; }
                            s[2 * u][0] = first0 ? d[0][0] : d[1][0]; s[2 * u][1] = first1 ? d[0][1] : d[1][1];
                            s[2 * u + 1][0] = first0 ? d[1][2] : d[2][2]; s[2 * u + 1][1] = first1 ? d[1][3] : d[2][3];
                        }
                        mbar_spin(bars + B_GFULL + 16, gph);
#pragma unroll
                        for (int u = 0; u < 4; u++) { ldsm_x4_t(vf[2 * u], pl + 2 * GST_BYTES + u * 2048 + a16); ldsm_x4_t(vf[2 * u + 1], pl + 2 * GST_BYTES + u * 2048 + (a16 ^ 32)); }
                        ldsm_x4_t(vf[8], pl + 2 * GST_BYTES + 8192 + a8);
                        __syncwarp();
                        release_stage(2);
                        float x[8];
#pragma unroll
                        for (int j = 0; j < 8; j++) x[j] = fmaxf(s[j][0], s[j][1]);
#pragma unroll
                        for (int o = 1; o < 4; o *= 2)
#pragma unroll
                            for (int j = 0; j < 8; j++) x[j] = fmaxf(x[j], __shfl_xor_sync(0xffffffffu, x[j], o));
#pragma unroll
                        for (int j = 0; j < 8; j++) {
                            const float n = x[j] * -LOC_SCALE;
                            s[j][0] = ex2(fmaf(s[j][0], LOC_SCALE, n)); s[j][1] = ex2(fmaf(s[j][1], LOC_SCALE, n));
                            x[j] = s[j][0] + s[j][1];
                        }
#pragma unroll
                        for (int o = 1; o < 4; o *= 2)
#pragma unroll
                            for (int j = 0; j < 8; j++) x[j] += __shfl_xor_sync(0xffffffffu, x[j], o);
                        mbar_spin(bars + B_GFULL + 24, gph);
                        release_stage(3);
                        it = take_item();
                        uint32_t ob[4][8];
#pragma unroll
                        for (int u = 0; u < 4; u++) {
                            const float r0 = rcp(x[2 * u]), r1 = rcp(x[2 * u + 1]), f0 = fmaf(-w[2 * u], r0, r0), f1 = fmaf(-w[2 * u + 1], r1, r1);
                            const uint32_t p0 = pack_bf16(s[2 * u][0] * f0, s[2 * u][1] * f0), p1 = pack_bf16(s[2 * u + 1][0] * f1, s[2 * u + 1][1] * f1);
                            const uint32_t pa[4] = {p0 & fmask, 0, p0 & ~fmask, p1 & fmask};
#pragma unroll
                            for (int c = 0; c < 4; c++) {
                                float ol[4];
                                mma_k16_init(ol, pa, vf[2 * u + (c >> 1)][2 * (c & 1)], vf[2 * u + (c >> 1)][2 * (c & 1) + 1]);
                                mma_k8(ol, 0, p1 & ~fmask, u < 3 ? vf[2 * u + 2 + (c >> 1)][2 * (c & 1)] : vf[8][c]);
                                ob[u][2 * c] = pack_bf16(ol[0], ol[1]);
                                ob[u][2 * c + 1] = pack_bf16(ol[2], ol[3]);
                            }
                        }
                        stage_acquire(0); stage_acquire(1);
#pragma unroll
                        for (int u = 0; u < 4; u++) {
                            stmatrix_x4(stg + par * 8192 + u * 2048 + a16, ob[u][0], ob[u][1], ob[u][2], ob[u][3]);
                            stmatrix_x4(stg + par * 8192 + u * 2048 + (a16 ^ 32), ob[u][4], ob[u][5], ob[u][6], ob[u][7]);
                        }
                        publish_pair();
                        bar_sync(4, 256);
                        gph ^= 1;
                        continue;
                    }
                    mbar_spin(bars + B_GFULL, gph);
                    bool more;
                    do {
                        wgmma_fence();
                        wgmma_ss_n256_tb_init(acc, full_desc(dA), full_desc(dB));
#pragma unroll
                        for (int kk = 1; kk < 4; kk++) wgmma_ss_n256_tb(acc, full_desc(dA) + 2 * kk, full_desc(dB) + 128 * kk, 1);
                        wgmma_commit();
                        const int nk = item_type(it) == T_K || item_type(it) == T_V ? 8 : 16;
                        int k = 1;
                        do {
                            if (pending) {
                                const int kf = k - 1 - wg;
                                if (kf == 0) { scale_q(0, 16); stage_chunk(0, pk); }
                                else if (kf == 1) { scale_q(16, 16); stage_chunk(1, pk + 16); }
                                else if (kf == 3) { scale_q(32, 16); stage_chunk(0, pk + 32); }
                                else if (kf == 4) { scale_q(48, 16); stage_chunk(1, pk + 48); }
                            }
                            gemm_step(acc, dB, k);
                        } while (k < nk);
                        held = item_type(it);
                        it = take_item();
                        more = item_type(it) < T_LOCAL;
                        if (more) mbar_spin(bars + B_GFULL, gph);
                        wgmma_wait<0>();
                        fence_regs(acc);
                        release_stage(3);
#pragma unroll
                        for (int j = 0; j < 64; j++) pk[j] = pack_bf16(acc[2 * j], acc[2 * j + 1]);
                        pending = true;
                    } while (more);
                } while (item_type(it) < T_LOCAL || (item_type(it) == T_LOCAL && (held != T_B || (it & ITEM_READY))));
                if (pending) {
                    scale_q(0, 64);
                    stage_acquire(0); stage_acquire(1);
                    write_blocks(std::integral_constant<int, 8>(), 0, pk);
                    const bool borrow = item_type(it) == T_ATTN;
                    if (borrow) {
                        mbar_spin(bars + B_GEMPTY, gph ^ 1); mbar_spin(bars + B_GEMPTY + 8, gph ^ 1);
                    } else {
                        publish_pair();
                        stage_acquire(0); stage_acquire(1);
                    }
                    write_blocks(std::integral_constant<int, 8>(), borrow ? 32768 - SM_STAGING : 0, pk + 32);
                    publish_pair();
                    mbar_arrive_if(lane == 0 && borrow, bars + B_ALT + 8 * wg);
                }
                if (item_type(it) == T_END) { it = take_item(); break; }
            } else {
                float o[64], s[64];
                uint32_t pa[32], pb[32];
                zero_regs(o); zero_regs(s); zero_regs(pa);
                float n0 = 0.f, n1 = 0.f;
                int shifted = 0;
                float l0 = 1.f, l1 = 1.f, f0 = 0.f, f1 = 0.f, g0 = 0.f, g1 = 0.f;
                uint32_t has_pv = 0;
                int first = 0;
                int pending = 0;
                const uint32_t dK = make_desc(sb + SM_KV, 16), dV = make_desc(sb + SM_KV, 16384);
                const uint32_t lane_off = bars_lane - bars + B_AEMPTY - B_AFULL;
                int cur = 0;
                uint32_t qoff = 0;
                const int row = wg * 64 + wq * 16 + (lane >> 2);
                const float thr = (row & 63) - (lane & 3) * 2;
                int peek = 0;
                auto kv_wait = [&](uint32_t n) { mbar_spin(bars + B_AFULL + 16 + 8 * (n & 3), (n >> 2) & 1); };
                auto kv_release = [&](uint32_t n) { mbar_arrive_cluster_if(lane < 2, bars_lane + B_AEMPTY + 16 + 8 * (n & 3)); };
                struct Slot { uint32_t bar, par, off; } slot[4];
                auto align = [&]() {
#pragma unroll
                    for (uint32_t i = 0; i < 4; i++) {
                        const uint32_t n = kvn + (i == 1 ? has_pv : i);
                        slot[i].bar = bars + B_AFULL + 16 + 8 * (n & 3); slot[i].par = (n >> 2) & 1; slot[i].off = (n & 3) * 2048;
                    }
                };
                align();
                auto scale_o = [&]() {
#pragma unroll
                    for (int j = 0; j < 16; j++) { o[4 * j] *= f0; o[4 * j + 1] *= f0; o[4 * j + 2] *= f1; o[4 * j + 3] *= f1; }
                };
                auto pack_o = [&](uint32_t (&v)[32]) {
#pragma unroll
                    for (int j = 0; j < 32; j++) v[j] = pack_bf16(o[2 * j], o[2 * j + 1]);
                };
                auto scales = [&]() { f0 = g0 * rcp(quad_sum(l0)); f1 = g1 * rcp(quad_sum(l1)); };
                auto step = [&](auto even, uint32_t (&pin)[32], uint32_t (&pout)[32], bool fresh, bool diag, bool last) {
                    constexpr bool EVEN = decltype(even)::value;
                    Slot& sk = slot[EVEN ? 0 : 2];
                    Slot& sv = slot[EVEN ? 1 : 3];
                    kvn += EVEN ? 1 + has_pv : 2;
                    mbar_spin(sk.bar, sk.par);
                    bar_sync(1 + wg, 256);
                    qk_gemm(s, dA + qoff, dK + sk.off);
                    if (EVEN && fresh) {
                        scales();
                        g0 = lds_f32(bars + SM_GATE + (ti & 1) * 512 + 4 * row); g1 = lds_f32(bars + SM_GATE + (ti & 1) * 512 + 4 * row + 32);
                        ti++;
                        n0 = 0.f; n1 = 0.f; l0 = 0.f; l1 = 0.f;
                        shifted = 0;
                        if (has_pv) { stage_acquire(0); stage_acquire(1); }
                    }
                    if (!EVEN && pending) {
                        pack_o(pout);
                        write_blocks(std::integral_constant<int, 8>(), 0, pout);
                        publish_pair();
                    }
                    if (last)
                        asm volatile("{\n.reg .pred P, Q;\n"
                                     "mbarrier.test_wait.parity.shared::cta.b64 Q, [%1], %2;\n"
                                     "mbarrier.test_wait.parity.shared::cta.b64 P, [%3], %4;\n"
                                     "ld.shared.u32 %0, [%5];\n"
                                     "@!Q or.b32 %0, %0, 0x10000;\n"
                                     "@!P mov.u32 %0, -1;\n}\n"
                                     : "=r"(peek) : "r"(bars + B_AFULL + 8 * (ti & 1)), "r"((ti >> 1) & 1), "r"(bars + B_IFULL + 8 * (qn % QDEPTH)),
                                       "r"((qn / QDEPTH) & 1), "r"(bars + SM_QUEUE + 4 * (qn % QDEPTH)) : "memory");
                    mbar_spin(sv.bar, sv.par);
                    pv_gemm(o, pin, dV + sv.off, EVEN || !first);
                    bar_arrive(2 - wg, 256);
                    sk.par ^= 1; sv.par ^= 1;
                    wgmma_wait<1>();
                    fence_regs(s);
                    mbar_arrive_cluster_if(lane < 2 && (!EVEN || has_pv), sk.bar + lane_off);
                    mbar_arrive_if(lane == 0 && last, bars + B_AEMPTY + 8 * ((ti - 1) & 1));
                    float r0, r1, x0 = n0, x1 = n1;
#pragma unroll 1
                    for (int mask = diag, redone = 0;; mask = 0, redone = 1) {
                        if (mask | shifted) {
                            if (mask) causal_mask(s, thr, wg);
                            if (shifted) shift_rows(s, x0, x1);
                        }
                        exp_pack(pout, s, r0, r1);
                        if (!__any_sync(0xffffffffu, fmaxf(r0, r1) >= SUM_LIMIT || (EVEN && fresh && !(lane & 3) && !(fminf(s[0], s[2]) >= -REF_RANGE))) || redone) break;
                        row_max(s, x0, x1);
                        if (!(EVEN && fresh)) { x0 = fmaxf(x0, 0.f); x1 = fmaxf(x1, 0.f); }
                        float a0 = ex2(-x0), a1 = ex2(-x1);
                        n0 += x0; n1 += x1;
                        shifted = 1;
                        if (EVEN && fresh) { a0 = 1.f; a1 = 1.f; }
                        l0 *= a0; l1 *= a1;
                        wgmma_wait<0>();
                        fence_regs(o);
#pragma unroll
                        for (int q = 0; q < 16; q++) { o[4 * q] *= a0; o[4 * q + 1] *= a0; o[4 * q + 2] *= a1; o[4 * q + 3] *= a1; }
                    }
                    l0 += r0; l1 += r1;
                    wgmma_wait<0>();
                    fence_regs(o);
                    fence_regs(pin);
                    mbar_arrive_cluster_if(lane < 2, sv.bar + lane_off);
                };
                auto copy_p = [&]() {
#pragma unroll
                    for (int j = 0; j < 32; j++) pa[j] = __float_as_uint(__uint_as_float(pb[j]) + __uint_as_float(prm.zero));
                };
                int rem = 0;
                mbar_spin(bars + B_AFULL + 8 * (ti & 1), (ti >> 1) & 1);
                while (true) {
                    const bool fresh = rem == 0;
                    if (fresh) {
                        if (has_pv) {
                            const int seen = __shfl_sync(0xffffffffu, peek, 0);
                            if (seen >= 0) {
                                mbar_arrive_cluster_if(lane == 0, bars0 + B_IEMPTY + 8 * (qn % QDEPTH));
                                qn++;
                                it = seen & 0xffff;
                            } else {
                                it = take_item();
                            }
                            if (item_row(cur) < 2 || item_type(it) != T_ATTN) break;
                            if (seen & 0x10000) mbar_spin(bars + B_AFULL + 8 * (ti & 1), (ti >> 1) & 1);
                        }
                        cur = it;
                        qoff = (ti & 1) * 2048;
                    }
                    const bool last = fresh ? item_row(cur) == 0 : rem == 1;
                    step(std::true_type(), pa, pb, fresh, item_asc(cur) ? last : fresh, last);
                    first = fresh;
                    if (fresh) {
                        pending = has_pv; has_pv = 1;
                        if (!pending) { kvn -= 2; align(); kvn += 2; slot[0].par ^= 1; slot[1].par ^= 1; }
                        else scale_o();
                        rem = item_row(cur);
                        if (rem == 0) {
                            copy_p();
                            continue;
                        }
                    } else if (--rem == 0) {
                        copy_p();
                        const Slot t0 = slot[0], t1 = slot[1];
                        slot[0] = slot[2]; slot[1] = slot[3]; slot[2] = t0; slot[3] = t1;
                        continue;
                    }
                    step(std::false_type(), pb, pa, false, item_asc(cur) && rem == 1, rem == 1);
                    pending = 0; first = 0;
                    rem--;
                }
                const uint32_t skip = item_asc(cur) & ~item_row(cur) & 1;
                kvn += skip;
                const bool end = item_type(it) == T_END;
#pragma unroll 1
                for (int pass = pending ? 0 : 1; pass < 2; pass++) {
                    if (pass) {
                        kv_wait(kvn);
                        pv_gemm(o, pa, dV + (kvn & 3) * 2048, !first);
                        scales();
                        stage_acquire(0); stage_acquire(1);
                        if (end) it = take_item();
                        wgmma_wait<0>();
                        fence_regs(o);
                        kv_release(kvn);
                        kvn += 1 + skip;
                        scale_o();
                    }
                    pack_o(pb);
                    write_blocks(std::integral_constant<int, 8>(), 0, pb);
                    publish_pair();
                }
                if (end) break;
            }
        }
        if (item_type(it) == T_OUT) {
            float acc[128];
            const uint32_t dB = make_desc(sb + 16384, 8192);
            mbar_spin(bars + B_GFULL, gph);
            wgmma_fence();
            wgmma_ss_n256_tb_init(acc, full_desc(dA), full_desc(dB));
#pragma unroll
            for (int kk = 1; kk < 4; kk++) wgmma_ss_n256_tb(acc, full_desc(dA) + 2 * kk, full_desc(dB) + 128 * kk, 1);
            wgmma_commit();
            uint32_t ln;
            asm volatile("mov.u32 %0, %%laneid;" : "=r"(ln));
            const uint32_t slot = (it & 127) * 32768 + (wg * 128 + wq * 32 + ln) * 16;
            char* const mine = (char*)g_part + slot;
            int k = 1, nk = 80;
            do {
                if (k == K_MEET - 5) {
#pragma unroll
                    for (int j = 0; j < 8; j++) st_b128(mine + j * 4096, 0, 0, 0, 0);
                    __syncwarp();
                }
                if (k == K_SPLIT) nk = take_item() & 127;
                gemm_step(acc, dB, k);
            } while (k < nk);
            float lo[64];
            auto triple = [&](auto first) {
                const uint32_t s0 = k & 3, s1 = (k + 1) & 3, o0 = s0 * (GST_BYTES >> 4), o1 = s1 * (GST_BYTES >> 4);
                wgmma_wait<0>();
                mbar_arrive_cluster_if(ln < (decltype(first)::value ? 2 : 4), bars_lane + B_GEMPTY + 8 * ((k - 1 - (ln >> 1)) & 3));
                mbar_spin(bars + B_GFULL + 8 * s0, gph);
                gph ^= s0 == 3;
                wgmma_fence();
#pragma unroll
                for (int kk = 0; kk < 4; kk++) {
                    if (decltype(first)::value && kk == 0) wgmma_ss_n128_tb_init(lo, full_desc(dA + o0), full_desc(dB + o0));
                    else wgmma_ss_n128_tb(lo, full_desc(dA + o0) + 2 * kk, full_desc(dB + o0) + 128 * kk, 1);
                }
                mbar_spin(bars + B_GFULL + 8 * s1, gph);
                gph ^= s1 == 3;
                wgmma_fence();
#pragma unroll
                for (int kk = 0; kk < 4; kk++) wgmma_ss_n128_tb(lo, full_desc(dA + o0 + 2048) + 2 * kk, full_desc(dB + o1 + 1024) + 128 * kk, 1);
#pragma unroll
                for (int kk = 0; kk < 4; kk++) wgmma_ss_n128_tb(lo, full_desc(dA + o1) + 2 * kk, full_desc(dB + o1) + 128 * kk, 1);
                wgmma_commit();
                k += 2;
            };
            triple(std::true_type());
            fence_regs(acc);
#pragma unroll
            for (int j = 0; j < 8; j++) {
                uint32_t v[4];
#pragma unroll
                for (int i = 0; i < 4; i++) v[i] = pack_bf16(acc[64 + 8 * j + 2 * i], acc[65 + 8 * j + 2 * i]);
                if (j == 4) triple(std::false_type());
                st_b128(mine + j * 4096, ~v[0], v[1], v[2], v[3]);
            }
            triple(std::false_type());
            uint32_t pk[32];
            char* const other = (char*)g_part + (slot ^ (16 * 32768));
            while (true) {
#pragma unroll
                for (int j = 0; j < 8; j++) ld_b128(other + j * 4096, pk[4 * j], pk[4 * j + 1], pk[4 * j + 2], pk[4 * j + 3]);
                bool miss = false;
#pragma unroll
                for (int j = 0; j < 8; j++) miss |= pk[4 * j] == 0;
                if (!__any_sync(0xffffffffu, miss)) break;
                while (__any_sync(0xffffffffu, pk[28] == 0)) ld_b128(other + 7 * 4096, pk[28], pk[29], pk[30], pk[31]);
            }
#pragma unroll
            for (int j = 0; j < 32; j++) {
                const uint32_t v = j & 3 ? pk[j] : ~pk[j];
                acc[2 * j] += __uint_as_float(v << 16); acc[2 * j + 1] += __uint_as_float(v & 0xffff0000u);
                asm volatile("" : "+f"(acc[2 * j]), "+f"(acc[2 * j + 1]) :: "memory");
            }
            stage_acquire(0); stage_acquire(1);
            wgmma_wait<0>();
            fence_regs(lo);
            mbar_arrive_cluster_if(ln < 4, bars_lane + B_GEMPTY + 8 * ((k - 1 - (ln >> 1)) & 3));
#pragma unroll
            for (int j = 0; j < 32; j++)
                pk[j] = pack_bf16(acc[2 * j] + lo[2 * j], acc[2 * j + 1] + lo[2 * j + 1]);
            write_blocks(std::integral_constant<int, 8>(), 0, pk);
            __syncwarp();
            uint4* dst = (uint4*)((char*)prm.out + (uint32_t)((item_row(it) * 128 + wg * 64 + wq * 16 + (ln >> 4)) * 2048 + item_col(it) * 256 + (ln & 15) * 16));
#pragma unroll
            for (int j = 0; j < 8; j++) {
                const int r = 2 * j + (ln >> 4);
                uint4 v;
                asm volatile("ld.shared.v4.u32 {%0, %1, %2, %3}, [%4];" : "=r"(v.x), "=r"(v.y), "=r"(v.z), "=r"(v.w)
                             : "r"(stg + wq * 2048 + r * 128 + (ln & 8) * 1024 + (((ln & 7) ^ (r & 7)) << 4)) : "memory");
                dst[j * 256] = v;
            }
        }
    }
}

typedef CUresult (*EncodeFn)(CUtensorMap*, CUtensorMapDataType, cuuint32_t, void*, const cuuint64_t*, const cuuint64_t*,
                             const cuuint32_t*, const cuuint32_t*, CUtensorMapInterleave, CUtensorMapSwizzle,
                             CUtensorMapL2promotion, CUtensorMapFloatOOBfill);

void encode3(EncodeFn fn, CUtensorMap* m, const void* ptr, uint64_t d0, uint64_t d1, uint64_t d2, uint64_t s1, uint64_t s2,
             uint32_t b0, uint32_t b1, uint32_t b2) {
    cuuint64_t dims[3] = {d0, d1, d2};
    cuuint64_t strides[2] = {s1, s2};
    cuuint32_t box[3] = {b0, b1, b2};
    cuuint32_t es[3] = {1, 1, 1};
    fn(m, CU_TENSOR_MAP_DATA_TYPE_BFLOAT16, 3, const_cast<void*>(ptr), dims, strides, box, es, CU_TENSOR_MAP_INTERLEAVE_NONE,
       CU_TENSOR_MAP_SWIZZLE_128B, CU_TENSOR_MAP_L2_PROMOTION_NONE, CU_TENSOR_MAP_FLOAT_OOB_FILL_NONE);
}
void map_act(EncodeFn fn, CUtensorMap* m, const void* p, int rows, int cols, int box_rows) {
    encode3(fn, m, p, cols, rows, 1, (uint64_t)cols * 2, (uint64_t)cols * rows * 2, 64, box_rows, 1);
}
void map_wgt(EncodeFn fn, CUtensorMap* m, const void* p, int K, int N) {
    encode3(fn, m, p, 64, K, N / 64, (uint64_t)N * 2, 128, 64, 64, 2);
}

void build_schedule(Params& p) {
    int n = 0;
    auto add = [&](int type, int col, int row) { p.items[n++] = (uint16_t)(type << 13 | col << 4 | row); };
    auto add_qkv = [&](int c) {
        for (int m = 0; m < 8; m++) add(T_Q, c, m);
        for (int m = 0; m < 8; m++) add(T_K, c, m);
        for (int m = 0; m < 8; m++) add(T_V, c, m);
    };
    int ldist = 200, ldist2 = 260, lstep = 8, beta = 26, tail = 32, late = 6, early = 8, epos = 100;
    int order[16] = {6, 7, 8, 9, 10, 11, 12, 13, 14, 15, 5, 4, 3, 2, 1, 0};
    uint16_t proj[480];
    for (int m = 0; m < 8; m++) for (int c = 0; c < 12; c++) add(T_B, c, m);
    for (int c = 0; c < 16; c++) add_qkv(c);
    for (int i = 0; i < 480; i++) proj[i] = p.items[i];
    n = 0;
    for (int i = 0, l = 0; i < 480; i++) {
        p.items[n++] = proj[i];
        for (; l < 64 && i >= (l < 40 ? ldist + lstep * l / 8 : ldist2 + lstep * (l - 40) / 8); l++) add(T_LOCAL, l & 3, l >> 2);
    }
    const int a0 = n;
    for (int key = 0; key < 4000; key++)
        for (int r = 0; r < 32; r++)
            for (int j = 7; j >= 0; j--)
                if ((j ? (7 - j) * 40 + r * beta : 3999) == key) add(T_ATTN, 2 * order[r >> 1] + (r & 1), j);
    int t0 = n;
    for (int work = 0; work < 32 * 136 * tail / 100;) work += 4 * (p.items[--t0] & 15) + 3;
    for (int i = t0 + 1; i < n; i++)
        for (int j = i; j > t0 && (p.items[j] & 15) > (p.items[j - 1] & 15); j--) { const uint16_t t = p.items[j]; p.items[j] = p.items[j - 1]; p.items[j - 1] = t; }
    for (int r = early - 1; r >= 0; r--) {
        const uint16_t t = p.items[n - 32 + early - 1];
        for (int j = n - 32 + early - 1; j > n - epos; j--) p.items[j] = p.items[j - 1];
        p.items[n - epos] = t;
    }
    for (int moved = 0; moved < 2 && late >= 0; moved++)
        for (int i = a0; i < n; i++)
            if (p.items[i] == (T_ATTN << 13 | (2 * order[15] + moved) << 4 | late)) {
                for (int j = i; j + 1 < n; j++) p.items[j] = p.items[j + 1];
                p.items[n - 1] = (uint16_t)(T_ATTN << 13 | (2 * order[15] + moved) << 4 | late);
                break;
            }
    for (int s = 0, lo = 0, hi = WIDE - 1; s < 80; s++) {
        const int r = s / 2, g = r < 8 ? 32 + r : 2 * order[r / 2 - 4] + (r & 1);
        p.ostep[s >= WIDE ? s : r & 1 ? hi-- : lo++] = (uint8_t)(2 * g + (s & 1));
    }
}

void build_params(Params& p, void* const* d_in, void* d_out) {
    void* fnp = nullptr;
    cudaDriverEntryPointQueryResult qr;
    cudaGetDriverEntryPoint("cuTensorMapEncodeTiled", &fnp, cudaEnableDefault, &qr);
    EncodeFn fn = (EncodeFn)fnp;
    void* scr = nullptr;
    cudaGetSymbolAddress(&scr, g_scr);
    map_act(fn, &p.m[M_X], d_in[0], SEQ, 1024, 128);
    map_act(fn, &p.m[M_C], d_in[1], SEQ, 512, 128);
    map_wgt(fn, &p.m[M_WQ], d_in[2], 1024, 4096);
    map_wgt(fn, &p.m[M_WUK], d_in[3], 512, 4096);
    map_wgt(fn, &p.m[M_WUV], d_in[4], 512, 4096);
    map_wgt(fn, &p.m[M_WO], d_in[5], 4096, 1024);
    map_wgt(fn, &p.m[M_WQKV], d_in[7], 1024, 3072);
    map_wgt(fn, &p.m[M_WOB], d_in[8], 1024, 1024);
    encode3(fn, &p.m[M_SCR_LD], scr, 128, SEQ, G_TOTAL, 256, (uint64_t)SEQ * 256, 64, 128, 1);
    encode3(fn, &p.m[M_SCR_LOC], scr, 256, SEQ / 2, G_TOTAL, 512, (uint64_t)SEQ * 256, 64, 72, 1);
    encode3(fn, &p.m[M_SCR_LOQ], scr, 256, SEQ / 2, G_TOTAL, 512, (uint64_t)SEQ * 256, 64, 64, 1);
    encode3(fn, &p.m[M_SCR_ST], scr, 128, SEQ, G_TOTAL, 256, (uint64_t)SEQ * 256, 64, 64, 1);
    p.x = (const __nv_bfloat16*)d_in[0];
    p.gate_w = (const __nv_bfloat16*)d_in[9];
    p.zero = 0;
    p.wo = (const char*)d_in[5];
    p.out = (__nv_bfloat16*)d_out;
    build_schedule(p);
}

}

extern "C" void kernel_launch(void* const* d_in, const int* in_sizes, int n_in, void* d_out, int out_size) {
    (void)in_sizes; (void)n_in; (void)out_size;
    Params p;
    build_params(p, d_in, d_out);
    cudaFuncSetAttribute(fused_kernel, cudaFuncAttributeMaxDynamicSharedMemorySize, SM_TOTAL);
    fused_kernel<<<NCTA, 384, SM_TOTAL>>>(p);
}
```

```cpp
#include <cuda_runtime.h>
#include <cuda_bf16.h>
#include <cuda.h>
#include <stddef.h>
#include <stdint.h>
#include <type_traits>

namespace {

constexpr int SEQ = 2048;
constexpr int G_Q = 0, G_K = 32, G_V = 64, G_B = 96, G_CTX = G_Q, G_LOC = G_B, G_TOTAL = 120;

__device__ __align__(1024) __nv_bfloat16 g_scr[(size_t)G_TOTAL * SEQ * 128];
__device__ __align__(128) float g_gate[SEQ];

__device__ __forceinline__ uint32_t smem_u32(const void* p) { return (uint32_t)__cvta_generic_to_shared(p); }
__device__ __forceinline__ bool elect_one() {
    uint32_t p;
    asm volatile("{\n.reg .pred P;\nelect.sync _|P, 0xffffffff;\nselp.u32 %0, 1, 0, P;\n}\n" : "=r"(p));
    return p != 0;
}
__device__ __forceinline__ void mbar_init(uint32_t bar, uint32_t count) {
    asm volatile("mbarrier.init.shared::cta.b64 [%0], %1;" :: "r"(bar), "r"(count) : "memory");
}
__device__ __forceinline__ uint32_t cluster_rank() { uint32_t r; asm("mov.u32 %0, %%cluster_ctarank;" : "=r"(r)); return r; }
__device__ __forceinline__ uint32_t map_cta(uint32_t addr, uint32_t cta) {
    uint32_t r; asm("mapa.shared::cluster.u32 %0, %1, %2;" : "=r"(r) : "r"(addr), "r"(cta)); return r;
}
__device__ __forceinline__ void mbar_arrive_cluster_if(bool pred, uint32_t cluster_bar) {
    asm volatile("{\n.reg .pred P;\nsetp.ne.u32 P, %1, 0;\n@P mbarrier.arrive.shared::cluster.b64 _, [%0];\n}\n"
                 :: "r"(cluster_bar), "r"((uint32_t)pred) : "memory");
}
__device__ __forceinline__ void mbar_arrive_cluster_n_if(bool pred, uint32_t cluster_bar, uint32_t count) {
    asm volatile("{\n.reg .pred P;\nsetp.ne.u32 P, %1, 0;\n@P mbarrier.arrive.shared::cluster.b64 _, [%0], %2;\n}\n"
                 :: "r"(cluster_bar), "r"((uint32_t)pred), "r"(count) : "memory");
}
__device__ __forceinline__ void mbar_arrive_if(bool pred, uint32_t bar) {
    asm volatile("{\n.reg .pred P;\nsetp.ne.u32 P, %1, 0;\n@P mbarrier.arrive.shared::cta.b64 _, [%0];\n}\n"
                 :: "r"(bar), "r"((uint32_t)pred) : "memory");
}
__device__ __forceinline__ bool mbar_test(uint32_t bar, uint32_t parity) {
    uint32_t ok;
    asm volatile("{\n.reg .pred P;\nmbarrier.test_wait.parity.shared::cta.b64 P, [%1], %2;\nselp.u32 %0, 1, 0, P;\n}\n"
                 : "=r"(ok) : "r"(bar), "r"(parity) : "memory");
    return ok != 0;
}
__device__ __forceinline__ void mbar_wait(uint32_t bar, uint32_t parity) {
    asm volatile("{\n.reg .pred P;\n.reg .u32 c;\n"
                 "mov.u32 c, 0;\n"
                 "SPIN:\n"
                 "mbarrier.try_wait.parity.shared::cta.b64 P, [%0], %1;\n"
                 "@P bra DONE;\n"
                 "add.u32 c, c, 1;\n"
                 "setp.lt.u32 P, c, 4194304;\n"
                 "@P bra SPIN;\n"
                 "trap;\n"
                 "DONE:\n}\n" :: "r"(bar), "r"(parity) : "memory");
}
__device__ __forceinline__ void mbar_spin(uint32_t bar, uint32_t parity) {
    asm volatile("{\n.reg .pred P;\n"
                 "SPIN:\n"
                 "mbarrier.try_wait.parity.shared::cta.b64 P, [%0], %1;\n"
                 "@!P bra SPIN;\n}\n" :: "r"(bar), "r"(parity) : "memory");
}
__device__ __forceinline__ void bar_sync(int id, int n) { asm volatile("bar.sync %0, %1;" :: "r"(id), "r"(n) : "memory"); }
__device__ __forceinline__ void bar_arrive(int id, int n) { asm volatile("bar.arrive %0, %1;" :: "r"(id), "r"(n) : "memory"); }
__device__ __forceinline__ void fence_proxy_async_smem() { asm volatile("fence.proxy.async.shared::cta;" ::: "memory"); }
__device__ __forceinline__ void warp_expect_tx(uint32_t bar, uint32_t bytes) {
    asm volatile("{\n.reg .pred P;\nelect.sync _|P, 0xffffffff;\n@P mbarrier.arrive.expect_tx.shared::cta.b64 _, [%0], %1;\n}\n"
                 :: "r"(bar), "r"(bytes) : "memory");
}
constexpr uint64_t EVICT_FIRST = 0x12F0000000000000ull;
__device__ __forceinline__ void warp_tma_load(uint32_t dst, const CUtensorMap* map, uint32_t bar, int c0, int c1, int c2, bool stream) {
    if (stream)
        asm volatile("{\n.reg .pred P;\nelect.sync _|P, 0xffffffff;\n"
                     "@P cp.async.bulk.tensor.3d.shared::cluster.global.mbarrier::complete_tx::bytes.L2::cache_hint"
                     " [%0], [%1, {%3, %4, %5}], [%2], %6;\n}\n"
                     :: "r"(dst), "l"(map), "r"(bar), "r"(c0), "r"(c1), "r"(c2), "l"(EVICT_FIRST) : "memory");
    else
        asm volatile("{\n.reg .pred P;\nelect.sync _|P, 0xffffffff;\n"
                     "@P cp.async.bulk.tensor.3d.shared::cluster.global.mbarrier::complete_tx::bytes [%0], [%1, {%3, %4, %5}], [%2];\n}\n"
                     :: "r"(dst), "l"(map), "r"(bar), "r"(c0), "r"(c1), "r"(c2) : "memory");
}
__device__ __forceinline__ void warp_tma_load_pair(uint32_t dst, const CUtensorMap* map, uint32_t bar, int c0, int c1, int c2, bool stream) {
    if (stream)
        asm volatile("{\n.reg .pred P;\nelect.sync _|P, 0xffffffff;\n"
                     "@P cp.async.bulk.tensor.3d.shared::cluster.global.mbarrier::complete_tx::bytes.multicast::cluster.L2::cache_hint"
                     " [%0], [%1, {%3, %4, %5}], [%2], %6, %7;\n}\n"
                     :: "r"(dst), "l"(map), "r"(bar), "r"(c0), "r"(c1), "r"(c2), "h"((uint16_t)3), "l"(EVICT_FIRST) : "memory");
    else
        asm volatile("{\n.reg .pred P;\nelect.sync _|P, 0xffffffff;\n"
                     "@P cp.async.bulk.tensor.3d.shared::cluster.global.mbarrier::complete_tx::bytes.multicast::cluster"
                     " [%0], [%1, {%3, %4, %5}], [%2], %6;\n}\n"
                     :: "r"(dst), "l"(map), "r"(bar), "r"(c0), "r"(c1), "r"(c2), "h"((uint16_t)3) : "memory");
}
__device__ __forceinline__ void warp_bulk_load(uint32_t dst, const void* src, uint32_t bytes, uint32_t bar) {
    asm volatile("{\n.reg .pred P;\nelect.sync _|P, 0xffffffff;\n"
                 "@P cp.async.bulk.shared::cluster.global.mbarrier::complete_tx::bytes [%0], [%1], %2, [%3];\n}\n"
                 :: "r"(dst), "l"(src), "r"(bytes), "r"(bar) : "memory");
}
__device__ __forceinline__ void warp_tma_store(const CUtensorMap* map, uint32_t src, int c0, int c1, int c2, bool stream) {
    if (stream)
        asm volatile("{\n.reg .pred P;\nelect.sync _|P, 0xffffffff;\n"
                     "@P cp.async.bulk.tensor.3d.global.shared::cta.bulk_group.L2::cache_hint [%0, {%2, %3, %4}], [%1], %5;\n}\n"
                     :: "l"(map), "r"(src), "r"(c0), "r"(c1), "r"(c2), "l"(EVICT_FIRST) : "memory");
    else
        asm volatile("{\n.reg .pred P;\nelect.sync _|P, 0xffffffff;\n"
                     "@P cp.async.bulk.tensor.3d.global.shared::cta.bulk_group [%0, {%2, %3, %4}], [%1];\n}\n"
                     :: "l"(map), "r"(src), "r"(c0), "r"(c1), "r"(c2) : "memory");
}
__device__ __forceinline__ void warp_bulk_store(void* dst, uint32_t src, uint32_t bytes) {
    asm volatile("{\n.reg .pred P;\nelect.sync _|P, 0xffffffff;\n"
                 "@P cp.async.bulk.global.shared::cta.bulk_group [%0], [%1], %2;\n}\n" :: "l"(dst), "r"(src), "r"(bytes) : "memory");
}
__device__ __forceinline__ void warp_prefetch(const void* src, uint32_t bytes) {
    asm volatile("{\n.reg .pred P;\nelect.sync _|P, 0xffffffff;\n@P cp.async.bulk.prefetch.L2.global [%0], %1;\n}\n" :: "l"(src), "r"(bytes) : "memory");
}
__device__ __forceinline__ void bulk_commit() { asm volatile("cp.async.bulk.commit_group;" ::: "memory"); }
template <int N> __device__ __forceinline__ void bulk_wait_read() { asm volatile("cp.async.bulk.wait_group.read %0;" :: "n"(N) : "memory"); }
template <int N> __device__ __forceinline__ void bulk_wait() { asm volatile("cp.async.bulk.wait_group %0;" :: "n"(N) : "memory"); }
__device__ __forceinline__ void wgmma_fence() { asm volatile("wgmma.fence.sync.aligned;" ::: "memory"); }
__device__ __forceinline__ void wgmma_commit() { asm volatile("wgmma.commit_group.sync.aligned;" ::: "memory"); }
template <int N> __device__ __forceinline__ void wgmma_wait() { asm volatile("wgmma.wait_group.sync.aligned %0;" :: "n"(N) : "memory"); }
template <int N> __device__ __forceinline__ void fence_regs(float (&d)[N]) {
#pragma unroll
    for (int i = 0; i < N; i++) asm volatile("" : "+f"(d[i]) :: "memory");
}
template <int N> __device__ __forceinline__ void fence_regs(uint32_t (&d)[N]) {
#pragma unroll
    for (int i = 0; i < N; i++) asm volatile("" : "+r"(d[i]) :: "memory");
}
template <int N> __device__ __forceinline__ void reg_dec() { asm volatile("setmaxnreg.dec.sync.aligned.u32 %0;" :: "n"(N)); }
template <int N> __device__ __forceinline__ void reg_inc() { asm volatile("setmaxnreg.inc.sync.aligned.u32 %0;" :: "n"(N)); }
__device__ __forceinline__ uint32_t pack_bf16(float lo, float hi) {
    uint32_t r; asm("cvt.rn.bf16x2.f32 %0, %1, %2;" : "=r"(r) : "f"(hi), "f"(lo)); return r;
}
__device__ __forceinline__ void stmatrix_x4(uint32_t addr, uint32_t r0, uint32_t r1, uint32_t r2, uint32_t r3) {
    asm volatile("stmatrix.sync.aligned.m8n8.x4.shared.b16 [%0], {%1, %2, %3, %4};"
                 :: "r"(addr), "r"(r0), "r"(r1), "r"(r2), "r"(r3) : "memory");
}
__device__ __forceinline__ float ex2(float x) { float y; asm("ex2.approx.ftz.f32 %0, %1;" : "=f"(y) : "f"(x)); return y; }

constexpr uint32_t DESC_HI = (1024 >> 4) | (1u << 30);
__device__ __forceinline__ uint32_t make_desc(uint32_t addr, uint32_t lbo) {
    uint32_t lo = ((addr & 0x3FFFF) >> 4) | ((lbo >> 4) << 16);
    asm volatile("" : "+r"(lo));
    return lo;
}
__device__ __forceinline__ uint64_t full_desc(uint32_t lo) {
    uint64_t d; asm("mov.b64 %0, {%1, %2};" : "=l"(d) : "r"(lo), "r"(DESC_HI)); return d;
}

__device__ __forceinline__ void wgmma_ss_n256_tb_init(float (&d)[128], uint64_t da, uint64_t db) {
    asm volatile("{\n.reg .pred p;\n"
        "setp.ne.b32 p, 0, 0;\n"
        "wgmma.mma_async.sync.aligned.m64n256k16.f32.bf16.bf16 "
        "{%0, %1, %2, %3, %4, %5, %6, %7, %8, %9, %10, %11, %12, %13, %14, %15, %16, %17, %18, %19, %20, "
        "%21, %22, %23, %24, %25, %26, %27, %28, %29, %30, %31, %32, %33, %34, %35, %36, %37, %38, %39, %40, "
        "%41, %42, %43, %44, %45, %46, %47, %48, %49, %50, %51, %52, %53, %54, %55, %56, %57, %58, %59, %60, "
        "%61, %62, %63, %64, %65, %66, %67, %68, %69, %70, %71, %72, %73, %74, %75, %76, %77, %78, %79, %80, "
        "%81, %82, %83, %84, %85, %86, %87, %88, %89, %90, %91, %92, %93, %94, %95, %96, %97, %98, %99, "
        "%100, %101, %102, %103, %104, %105, %106, %107, %108, %109, %110, %111, %112, %113, %114, %115, "
        "%116, %117, %118, %119, %120, %121, %122, %123, %124, %125, %126, %127},"
        " %128, %129, p, 1, 1, 0, 1;\n}\n"
        : "=f"(d[0]), "=f"(d[1]), "=f"(d[2]), "=f"(d[3]), "=f"(d[4]), "=f"(d[5]), "=f"(d[6]), "=f"(d[7]),
        "=f"(d[8]), "=f"(d[9]), "=f"(d[10]), "=f"(d[11]), "=f"(d[12]), "=f"(d[13]), "=f"(d[14]), "=f"(d[15]),
        "=f"(d[16]), "=f"(d[17]), "=f"(d[18]), "=f"(d[19]), "=f"(d[20]), "=f"(d[21]), "=f"(d[22]),
        "=f"(d[23]), "=f"(d[24]), "=f"(d[25]), "=f"(d[26]), "=f"(d[27]), "=f"(d[28]), "=f"(d[29]),
        "=f"(d[30]), "=f"(d[31]), "=f"(d[32]), "=f"(d[33]), "=f"(d[34]), "=f"(d[35]), "=f"(d[36]),
        "=f"(d[37]), "=f"(d[38]), "=f"(d[39]), "=f"(d[40]), "=f"(d[41]), "=f"(d[42]), "=f"(d[43]),
        "=f"(d[44]), "=f"(d[45]), "=f"(d[46]), "=f"(d[47]), "=f"(d[48]), "=f"(d[49]), "=f"(d[50]),
        "=f"(d[51]), "=f"(d[52]), "=f"(d[53]), "=f"(d[54]), "=f"(d[55]), "=f"(d[56]), "=f"(d[57]),
        "=f"(d[58]), "=f"(d[59]), "=f"(d[60]), "=f"(d[61]), "=f"(d[62]), "=f"(d[63]), "=f"(d[64]),
        "=f"(d[65]), "=f"(d[66]), "=f"(d[67]), "=f"(d[68]), "=f"(d[69]), "=f"(d[70]), "=f"(d[71]),
        "=f"(d[72]), "=f"(d[73]), "=f"(d[74]), "=f"(d[75]), "=f"(d[76]), "=f"(d[77]), "=f"(d[78]),
        "=f"(d[79]), "=f"(d[80]), "=f"(d[81]), "=f"(d[82]), "=f"(d[83]), "=f"(d[84]), "=f"(d[85]),
        "=f"(d[86]), "=f"(d[87]), "=f"(d[88]), "=f"(d[89]), "=f"(d[90]), "=f"(d[91]), "=f"(d[92]),
        "=f"(d[93]), "=f"(d[94]), "=f"(d[95]), "=f"(d[96]), "=f"(d[97]), "=f"(d[98]), "=f"(d[99]),
        "=f"(d[100]), "=f"(d[101]), "=f"(d[102]), "=f"(d[103]), "=f"(d[104]), "=f"(d[105]), "=f"(d[106]),
        "=f"(d[107]), "=f"(d[108]), "=f"(d[109]), "=f"(d[110]), "=f"(d[111]), "=f"(d[112]), "=f"(d[113]),
        "=f"(d[114]), "=f"(d[115]), "=f"(d[116]), "=f"(d[117]), "=f"(d[118]), "=f"(d[119]), "=f"(d[120]),
        "=f"(d[121]), "=f"(d[122]), "=f"(d[123]), "=f"(d[124]), "=f"(d[125]), "=f"(d[126]), "=f"(d[127])
        : "l"(da), "l"(db));
}
__device__ __forceinline__ void wgmma_ss_n256_tb(float (&d)[128], uint64_t da, uint64_t db, int scale_d) {
    asm volatile("{\n.reg .pred p;\n"
        "setp.ne.b32 p, %130, 0;\n"
        "wgmma.mma_async.sync.aligned.m64n256k16.f32.bf16.bf16 "
        "{%0, %1, %2, %3, %4, %5, %6, %7, %8, %9, %10, %11, %12, %13, %14, %15, %16, %17, %18, %19, %20, "
        "%21, %22, %23, %24, %25, %26, %27, %28, %29, %30, %31, %32, %33, %34, %35, %36, %37, %38, %39, %40, "
        "%41, %42, %43, %44, %45, %46, %47, %48, %49, %50, %51, %52, %53, %54, %55, %56, %57, %58, %59, %60, "
        "%61, %62, %63, %64, %65, %66, %67, %68, %69, %70, %71, %72, %73, %74, %75, %76, %77, %78, %79, %80, "
        "%81, %82, %83, %84, %85, %86, %87, %88, %89, %90, %91, %92, %93, %94, %95, %96, %97, %98, %99, "
        "%100, %101, %102, %103, %104, %105, %106, %107, %108, %109, %110, %111, %112, %113, %114, %115, "
        "%116, %117, %118, %119, %120, %121, %122, %123, %124, %125, %126, %127},"
        " %128, %129, p, 1, 1, 0, 1;\n}\n"
        : "+f"(d[0]), "+f"(d[1]), "+f"(d[2]), "+f"(d[3]), "+f"(d[4]), "+f"(d[5]), "+f"(d[6]), "+f"(d[7]),
        "+f"(d[8]), "+f"(d[9]), "+f"(d[10]), "+f"(d[11]), "+f"(d[12]), "+f"(d[13]), "+f"(d[14]), "+f"(d[15]),
        "+f"(d[16]), "+f"(d[17]), "+f"(d[18]), "+f"(d[19]), "+f"(d[20]), "+f"(d[21]), "+f"(d[22]),
        "+f"(d[23]), "+f"(d[24]), "+f"(d[25]), "+f"(d[26]), "+f"(d[27]), "+f"(d[28]), "+f"(d[29]),
        "+f"(d[30]), "+f"(d[31]), "+f"(d[32]), "+f"(d[33]), "+f"(d[34]), "+f"(d[35]), "+f"(d[36]),
        "+f"(d[37]), "+f"(d[38]), "+f"(d[39]), "+f"(d[40]), "+f"(d[41]), "+f"(d[42]), "+f"(d[43]),
        "+f"(d[44]), "+f"(d[45]), "+f"(d[46]), "+f"(d[47]), "+f"(d[48]), "+f"(d[49]), "+f"(d[50]),
        "+f"(d[51]), "+f"(d[52]), "+f"(d[53]), "+f"(d[54]), "+f"(d[55]), "+f"(d[56]), "+f"(d[57]),
        "+f"(d[58]), "+f"(d[59]), "+f"(d[60]), "+f"(d[61]), "+f"(d[62]), "+f"(d[63]), "+f"(d[64]),
        "+f"(d[65]), "+f"(d[66]), "+f"(d[67]), "+f"(d[68]), "+f"(d[69]), "+f"(d[70]), "+f"(d[71]),
        "+f"(d[72]), "+f"(d[73]), "+f"(d[74]), "+f"(d[75]), "+f"(d[76]), "+f"(d[77]), "+f"(d[78]),
        "+f"(d[79]), "+f"(d[80]), "+f"(d[81]), "+f"(d[82]), "+f"(d[83]), "+f"(d[84]), "+f"(d[85]),
        "+f"(d[86]), "+f"(d[87]), "+f"(d[88]), "+f"(d[89]), "+f"(d[90]), "+f"(d[91]), "+f"(d[92]),
        "+f"(d[93]), "+f"(d[94]), "+f"(d[95]), "+f"(d[96]), "+f"(d[97]), "+f"(d[98]), "+f"(d[99]),
        "+f"(d[100]), "+f"(d[101]), "+f"(d[102]), "+f"(d[103]), "+f"(d[104]), "+f"(d[105]), "+f"(d[106]),
        "+f"(d[107]), "+f"(d[108]), "+f"(d[109]), "+f"(d[110]), "+f"(d[111]), "+f"(d[112]), "+f"(d[113]),
        "+f"(d[114]), "+f"(d[115]), "+f"(d[116]), "+f"(d[117]), "+f"(d[118]), "+f"(d[119]), "+f"(d[120]),
        "+f"(d[121]), "+f"(d[122]), "+f"(d[123]), "+f"(d[124]), "+f"(d[125]), "+f"(d[126]), "+f"(d[127])
        : "l"(da), "l"(db), "r"(scale_d));
}
__device__ __forceinline__ void wgmma_ss_n128(float (&d)[64], uint64_t da, uint64_t db, int scale_d) {
    asm volatile("{\n.reg .pred p;\n"
        "setp.ne.b32 p, %66, 0;\n"
        "wgmma.mma_async.sync.aligned.m64n128k16.f32.bf16.bf16 "
        "{%0, %1, %2, %3, %4, %5, %6, %7, %8, %9, %10, %11, %12, %13, %14, %15, %16, %17, %18, %19, %20, "
        "%21, %22, %23, %24, %25, %26, %27, %28, %29, %30, %31, %32, %33, %34, %35, %36, %37, %38, %39, %40, "
        "%41, %42, %43, %44, %45, %46, %47, %48, %49, %50, %51, %52, %53, %54, %55, %56, %57, %58, %59, %60, "
        "%61, %62, %63},"
        " %64, %65, p, 1, 1, 0, 0;\n}\n"
        : "+f"(d[0]), "+f"(d[1]), "+f"(d[2]), "+f"(d[3]), "+f"(d[4]), "+f"(d[5]), "+f"(d[6]), "+f"(d[7]),
        "+f"(d[8]), "+f"(d[9]), "+f"(d[10]), "+f"(d[11]), "+f"(d[12]), "+f"(d[13]), "+f"(d[14]), "+f"(d[15]),
        "+f"(d[16]), "+f"(d[17]), "+f"(d[18]), "+f"(d[19]), "+f"(d[20]), "+f"(d[21]), "+f"(d[22]),
        "+f"(d[23]), "+f"(d[24]), "+f"(d[25]), "+f"(d[26]), "+f"(d[27]), "+f"(d[28]), "+f"(d[29]),
        "+f"(d[30]), "+f"(d[31]), "+f"(d[32]), "+f"(d[33]), "+f"(d[34]), "+f"(d[35]), "+f"(d[36]),
        "+f"(d[37]), "+f"(d[38]), "+f"(d[39]), "+f"(d[40]), "+f"(d[41]), "+f"(d[42]), "+f"(d[43]),
        "+f"(d[44]), "+f"(d[45]), "+f"(d[46]), "+f"(d[47]), "+f"(d[48]), "+f"(d[49]), "+f"(d[50]),
        "+f"(d[51]), "+f"(d[52]), "+f"(d[53]), "+f"(d[54]), "+f"(d[55]), "+f"(d[56]), "+f"(d[57]),
        "+f"(d[58]), "+f"(d[59]), "+f"(d[60]), "+f"(d[61]), "+f"(d[62]), "+f"(d[63])
        : "l"(da), "l"(db), "r"(scale_d));
}
__device__ __forceinline__ void wgmma_rs_n128_tb(float (&d)[64], uint32_t a0, uint32_t a1, uint32_t a2, uint32_t a3, uint64_t db, int scale_d) {
    asm volatile("{\n.reg .pred p;\n"
        "setp.ne.b32 p, %69, 0;\n"
        "wgmma.mma_async.sync.aligned.m64n128k16.f32.bf16.bf16 "
        "{%0, %1, %2, %3, %4, %5, %6, %7, %8, %9, %10, %11, %12, %13, %14, %15, %16, %17, %18, %19, %20, "
        "%21, %22, %23, %24, %25, %26, %27, %28, %29, %30, %31, %32, %33, %34, %35, %36, %37, %38, %39, %40, "
        "%41, %42, %43, %44, %45, %46, %47, %48, %49, %50, %51, %52, %53, %54, %55, %56, %57, %58, %59, %60, "
        "%61, %62, %63},"
        " {%64, %65, %66, %67}, %68, p, 1, 1, 1;\n}\n"
        : "+f"(d[0]), "+f"(d[1]), "+f"(d[2]), "+f"(d[3]), "+f"(d[4]), "+f"(d[5]), "+f"(d[6]), "+f"(d[7]),
        "+f"(d[8]), "+f"(d[9]), "+f"(d[10]), "+f"(d[11]), "+f"(d[12]), "+f"(d[13]), "+f"(d[14]), "+f"(d[15]),
        "+f"(d[16]), "+f"(d[17]), "+f"(d[18]), "+f"(d[19]), "+f"(d[20]), "+f"(d[21]), "+f"(d[22]),
        "+f"(d[23]), "+f"(d[24]), "+f"(d[25]), "+f"(d[26]), "+f"(d[27]), "+f"(d[28]), "+f"(d[29]),
        "+f"(d[30]), "+f"(d[31]), "+f"(d[32]), "+f"(d[33]), "+f"(d[34]), "+f"(d[35]), "+f"(d[36]),
        "+f"(d[37]), "+f"(d[38]), "+f"(d[39]), "+f"(d[40]), "+f"(d[41]), "+f"(d[42]), "+f"(d[43]),
        "+f"(d[44]), "+f"(d[45]), "+f"(d[46]), "+f"(d[47]), "+f"(d[48]), "+f"(d[49]), "+f"(d[50]),
        "+f"(d[51]), "+f"(d[52]), "+f"(d[53]), "+f"(d[54]), "+f"(d[55]), "+f"(d[56]), "+f"(d[57]),
        "+f"(d[58]), "+f"(d[59]), "+f"(d[60]), "+f"(d[61]), "+f"(d[62]), "+f"(d[63])
        : "r"(a0), "r"(a1), "r"(a2), "r"(a3), "l"(db), "r"(scale_d));
}
__device__ __forceinline__ void wgmma_ss_n128_tb_init(float (&d)[64], uint64_t da, uint64_t db) {
    asm volatile("{\n.reg .pred p;\n"
        "setp.ne.b32 p, 0, 0;\n"
        "wgmma.mma_async.sync.aligned.m64n128k16.f32.bf16.bf16 "
        "{%0, %1, %2, %3, %4, %5, %6, %7, %8, %9, %10, %11, %12, %13, %14, %15, %16, %17, %18, %19, %20, "
        "%21, %22, %23, %24, %25, %26, %27, %28, %29, %30, %31, %32, %33, %34, %35, %36, %37, %38, %39, %40, "
        "%41, %42, %43, %44, %45, %46, %47, %48, %49, %50, %51, %52, %53, %54, %55, %56, %57, %58, %59, %60, "
        "%61, %62, %63},"
        " %64, %65, p, 1, 1, 0, 1;\n}\n"
        : "=f"(d[0]), "=f"(d[1]), "=f"(d[2]), "=f"(d[3]), "=f"(d[4]), "=f"(d[5]), "=f"(d[6]), "=f"(d[7]),
        "=f"(d[8]), "=f"(d[9]), "=f"(d[10]), "=f"(d[11]), "=f"(d[12]), "=f"(d[13]), "=f"(d[14]), "=f"(d[15]),
        "=f"(d[16]), "=f"(d[17]), "=f"(d[18]), "=f"(d[19]), "=f"(d[20]), "=f"(d[21]), "=f"(d[22]),
        "=f"(d[23]), "=f"(d[24]), "=f"(d[25]), "=f"(d[26]), "=f"(d[27]), "=f"(d[28]), "=f"(d[29]),
        "=f"(d[30]), "=f"(d[31]), "=f"(d[32]), "=f"(d[33]), "=f"(d[34]), "=f"(d[35]), "=f"(d[36]),
        "=f"(d[37]), "=f"(d[38]), "=f"(d[39]), "=f"(d[40]), "=f"(d[41]), "=f"(d[42]), "=f"(d[43]),
        "=f"(d[44]), "=f"(d[45]), "=f"(d[46]), "=f"(d[47]), "=f"(d[48]), "=f"(d[49]), "=f"(d[50]),
        "=f"(d[51]), "=f"(d[52]), "=f"(d[53]), "=f"(d[54]), "=f"(d[55]), "=f"(d[56]), "=f"(d[57]),
        "=f"(d[58]), "=f"(d[59]), "=f"(d[60]), "=f"(d[61]), "=f"(d[62]), "=f"(d[63])
        : "l"(da), "l"(db));
}
__device__ __forceinline__ void wgmma_ss_n128_tb(float (&d)[64], uint64_t da, uint64_t db, int scale_d) {
    asm volatile("{\n.reg .pred p;\n"
        "setp.ne.b32 p, %66, 0;\n"
        "wgmma.mma_async.sync.aligned.m64n128k16.f32.bf16.bf16 "
        "{%0, %1, %2, %3, %4, %5, %6, %7, %8, %9, %10, %11, %12, %13, %14, %15, %16, %17, %18, %19, %20, "
        "%21, %22, %23, %24, %25, %26, %27, %28, %29, %30, %31, %32, %33, %34, %35, %36, %37, %38, %39, %40, "
        "%41, %42, %43, %44, %45, %46, %47, %48, %49, %50, %51, %52, %53, %54, %55, %56, %57, %58, %59, %60, "
        "%61, %62, %63},"
        " %64, %65, p, 1, 1, 0, 1;\n}\n"
        : "+f"(d[0]), "+f"(d[1]), "+f"(d[2]), "+f"(d[3]), "+f"(d[4]), "+f"(d[5]), "+f"(d[6]), "+f"(d[7]),
        "+f"(d[8]), "+f"(d[9]), "+f"(d[10]), "+f"(d[11]), "+f"(d[12]), "+f"(d[13]), "+f"(d[14]), "+f"(d[15]),
        "+f"(d[16]), "+f"(d[17]), "+f"(d[18]), "+f"(d[19]), "+f"(d[20]), "+f"(d[21]), "+f"(d[22]),
        "+f"(d[23]), "+f"(d[24]), "+f"(d[25]), "+f"(d[26]), "+f"(d[27]), "+f"(d[28]), "+f"(d[29]),
        "+f"(d[30]), "+f"(d[31]), "+f"(d[32]), "+f"(d[33]), "+f"(d[34]), "+f"(d[35]), "+f"(d[36]),
        "+f"(d[37]), "+f"(d[38]), "+f"(d[39]), "+f"(d[40]), "+f"(d[41]), "+f"(d[42]), "+f"(d[43]),
        "+f"(d[44]), "+f"(d[45]), "+f"(d[46]), "+f"(d[47]), "+f"(d[48]), "+f"(d[49]), "+f"(d[50]),
        "+f"(d[51]), "+f"(d[52]), "+f"(d[53]), "+f"(d[54]), "+f"(d[55]), "+f"(d[56]), "+f"(d[57]),
        "+f"(d[58]), "+f"(d[59]), "+f"(d[60]), "+f"(d[61]), "+f"(d[62]), "+f"(d[63])
        : "l"(da), "l"(db), "r"(scale_d));
}

enum { M_X = 0, M_C, M_WQ, M_WUK, M_WUV, M_WQKV, M_WO, M_WOB, M_SCR_LD, M_SCR_LOC, M_SCR_LOQ, M_SCR_ST, M_COUNT };
enum { T_Q = 0, T_K, T_V, T_B, T_OUT, T_LOCAL, T_ATTN, T_END };
constexpr int NCTA = 132;
constexpr int NITEMS = 256;
constexpr int TRIPLES = 3, WIDE = 80 - 3 * TRIPLES;
struct Params {
    CUtensorMap m[M_COUNT];
    const __nv_bfloat16* x;
    const __nv_bfloat16* gate_w;
    const char* wo;
    __nv_bfloat16* out;
    uint32_t zero;
    uint16_t plan[10][16];
    uint16_t items[NITEMS];
    uint8_t ostep[80];
};
__device__ __forceinline__ int item_type(int it) { return it >> 13; }
__device__ __forceinline__ int item_row(int it) { return it & 15; }
__device__ __forceinline__ int item_col(int it) { return (it >> 4) & 31; }
__device__ __forceinline__ int item_asc(int it) { return (it >> 9) & 1; }
constexpr int ITEM_READY = 1 << 10;

struct __align__(128) Sync {
    unsigned long long count[4];
    __align__(128) unsigned long long ctx[16];
    unsigned next, next_out, done;
    __align__(128) unsigned step[32][2];
    unsigned split[32];
};
__device__ Sync g_sync;
__device__ uint4 g_part[128][8][256];

constexpr uint32_t GST_BYTES = 49152, SM_KV = 65536, SM_STAGING = 196608, SM_BARS = SM_STAGING + 32768;
constexpr uint32_t B_GFULL = 0, B_GEMPTY = 32, B_AFULL = 64, B_AEMPTY = 112, B_SFULL = 160, B_SEMPTY = 192,
                   B_IFULL = 224, B_IEMPTY = 288, B_XFREE = 352, B_WANT = 384, B_MEET = 392, B_HALF = 416,
                   SM_ORDY = 448, SM_QUEUE = 456, B_ALT = 488, B_QFREE = 504, SM_GATE = 512, SM_TOTAL = SM_BARS + 1536;
constexpr int QDEPTH = 8;
constexpr int FIRST_PAIR = 6;
constexpr int K_MEET = 12, K_SPLIT = 26;
constexpr int K_FETCH = 20;
constexpr uint32_t LOC_PLANE = 72 * 128;
constexpr float LOC_SCALE = 0.17677669529663687f * 1.4426950408889634f;
constexpr float SUM_LIMIT = 1152921504606846976.f;
constexpr float REF_RANGE = 32.f;

__device__ __forceinline__ unsigned ld_acquire(const unsigned* p) {
    unsigned v; asm volatile("ld.acquire.gpu.global.u32 %0, [%1];" : "=r"(v) : "l"(p) : "memory"); return v;
}
__device__ __forceinline__ unsigned long long ld_acquire(const unsigned long long* p) {
    unsigned long long v; asm volatile("ld.acquire.gpu.global.u64 %0, [%1];" : "=l"(v) : "l"(p) : "memory"); return v;
}
__device__ __forceinline__ void st_b128(void* p, uint32_t a, uint32_t b, uint32_t c, uint32_t d) {
    asm volatile("{\n.reg .b128 v;\n.reg .b64 lo, hi;\nmov.b64 lo, {%1, %2};\nmov.b64 hi, {%3, %4};\nmov.b128 v, {lo, hi};\n"
                 "st.relaxed.gpu.global.b128 [%0], v;\n}\n" :: "l"(p), "r"(a), "r"(b), "r"(c), "r"(d) : "memory");
}
__device__ __forceinline__ void ld_b128(const void* p, uint32_t& a, uint32_t& b, uint32_t& c, uint32_t& d) {
    asm volatile("{\n.reg .b128 v;\n.reg .b64 lo, hi;\nld.relaxed.gpu.global.b128 v, [%4];\nmov.b128 {lo, hi}, v;\n"
                 "mov.b64 {%0, %1}, lo;\nmov.b64 {%2, %3}, hi;\n}\n" : "=r"(a), "=r"(b), "=r"(c), "=r"(d) : "l"(p) : "memory");
}
__device__ __forceinline__ void spin_guard(unsigned& n) {
    asm volatile("{\n.reg .pred P;\nadd.u32 %0, %0, 1;\nsetp.gt.u32 P, %0, 16777216;\n@P trap;\n}\n" : "+r"(n));
    if (n > 1) __nanosleep(100);
}
__device__ __forceinline__ void red_add(unsigned long long* p, unsigned long long v) {
    asm volatile("red.release.gpu.global.add.u64 [%0], %1;" :: "l"(p), "l"(v) : "memory");
}
__device__ __forceinline__ float rcp(float x) { float y; asm("rcp.approx.ftz.f32 %0, %1;" : "=f"(y) : "f"(x)); return y; }
__device__ __forceinline__ float lds_f32(uint32_t addr) {
    float v; asm volatile("ld.shared.f32 %0, [%1];" : "=f"(v) : "r"(addr) : "memory"); return v;
}
__device__ __forceinline__ void ldsm_x4(uint32_t (&r)[4], uint32_t addr) {
    asm volatile("ldmatrix.sync.aligned.m8n8.x4.shared.b16 {%0, %1, %2, %3}, [%4];"
                 : "=r"(r[0]), "=r"(r[1]), "=r"(r[2]), "=r"(r[3]) : "r"(addr) : "memory");
}
__device__ __forceinline__ void ldsm_x4_t(uint32_t (&r)[4], uint32_t addr) {
    asm volatile("ldmatrix.sync.aligned.m8n8.x4.trans.shared.b16 {%0, %1, %2, %3}, [%4];"
                 : "=r"(r[0]), "=r"(r[1]), "=r"(r[2]), "=r"(r[3]) : "r"(addr) : "memory");
}
__device__ __forceinline__ void mma_k16(float (&d)[4], const uint32_t (&a)[4], uint32_t b0, uint32_t b1) {
    asm("mma.sync.aligned.m16n8k16.row.col.f32.bf16.bf16.f32 {%0,%1,%2,%3}, {%4,%5,%6,%7}, {%8,%9}, {%0,%1,%2,%3};"
        : "+f"(d[0]), "+f"(d[1]), "+f"(d[2]), "+f"(d[3]) : "r"(a[0]), "r"(a[1]), "r"(a[2]), "r"(a[3]), "r"(b0), "r"(b1));
}
__device__ __forceinline__ void mma_k16_init(float (&d)[4], const uint32_t (&a)[4], uint32_t b0, uint32_t b1) {
    asm("{\n.reg .f32 z;\nmov.f32 z, 0f00000000;\n"
        "mma.sync.aligned.m16n8k16.row.col.f32.bf16.bf16.f32 {%0,%1,%2,%3}, {%4,%5,%6,%7}, {%8,%9}, {z,z,z,z};\n}\n"
        : "=f"(d[0]), "=f"(d[1]), "=f"(d[2]), "=f"(d[3]) : "r"(a[0]), "r"(a[1]), "r"(a[2]), "r"(a[3]), "r"(b0), "r"(b1));
}
__device__ __forceinline__ void mma_k8(float (&d)[4], uint32_t a0, uint32_t a1, uint32_t b0) {
    asm("mma.sync.aligned.m16n8k8.row.col.f32.bf16.bf16.f32 {%0,%1,%2,%3}, {%4,%5}, {%6}, {%0,%1,%2,%3};"
        : "+f"(d[0]), "+f"(d[1]), "+f"(d[2]), "+f"(d[3]) : "r"(a0), "r"(a1), "r"(b0));
}
template <typename T, int N> __device__ __forceinline__ void zero_regs(T (&d)[N]) {
#pragma unroll
    for (int i = 0; i < N; i++) d[i] = 0;
}
__device__ __forceinline__ float quad_max(float v) {
    v = fmaxf(v, __shfl_xor_sync(0xffffffffu, v, 1));
    return fmaxf(v, __shfl_xor_sync(0xffffffffu, v, 2));
}
__device__ __forceinline__ float quad_sum(float v) {
    v += __shfl_xor_sync(0xffffffffu, v, 1);
    return v + __shfl_xor_sync(0xffffffffu, v, 2);
}

__device__ __forceinline__ void qk_gemm(float (&s)[64], uint32_t q_lo, uint32_t k_lo) {
    const uint64_t dq = full_desc(q_lo), dk = full_desc(k_lo);
    fence_regs(s);
    wgmma_fence();
#pragma unroll
    for (int kk = 0; kk < 8; kk++) {
        const uint32_t o = (kk >> 2) * 1024 + (kk & 3) * 2;
        wgmma_ss_n128(s, dq + o, dk + o, kk != 0);
    }
    wgmma_commit();
}
__device__ __forceinline__ void pv_gemm(float (&o)[64], uint32_t (&p)[32], uint32_t v_lo, int accumulate) {
    const uint64_t dv = full_desc(v_lo);
    fence_regs(o);
    fence_regs(p);
    wgmma_fence();
#pragma unroll
    for (int kk = 0; kk < 8; kk++)
        wgmma_rs_n128_tb(o, p[4 * kk], p[4 * kk + 1], p[4 * kk + 2], p[4 * kk + 3], dv + kk * 128, kk != 0 || accumulate);
    wgmma_commit();
}
__device__ __forceinline__ void row_max(const float (&s)[64], float& x0, float& x1) {
    float z0 = fmaxf(s[0], s[1]), z1 = fmaxf(s[2], s[3]);
    x0 = fmaxf(s[4], s[5]); x1 = fmaxf(s[6], s[7]);
#pragma unroll
    for (int j = 2; j < 16; j += 2) {
        z0 = fmaxf(z0, fmaxf(s[4 * j], s[4 * j + 1]));
        z1 = fmaxf(z1, fmaxf(s[4 * j + 2], s[4 * j + 3]));
        x0 = fmaxf(x0, fmaxf(s[4 * j + 4], s[4 * j + 5]));
        x1 = fmaxf(x1, fmaxf(s[4 * j + 6], s[4 * j + 7]));
    }
    x0 = quad_max(fmaxf(x0, z0)); x1 = quad_max(fmaxf(x1, z1));
}
__device__ __forceinline__ void exp_pack(uint32_t (&p)[32], const float (&s)[64], float& r0, float& r1) {
#pragma unroll
    for (int j = 0; j < 16; j++) {
        const float e0 = ex2(s[4 * j]), e1 = ex2(s[4 * j + 1]), e2 = ex2(s[4 * j + 2]), e3 = ex2(s[4 * j + 3]);
        if (j == 0) { r0 = e0 + e1; r1 = e2 + e3; }
        else { r0 += e0 + e1; r1 += e2 + e3; }
        p[2 * j] = pack_bf16(e0, e1);
        p[2 * j + 1] = pack_bf16(e2, e3);
    }
}
__device__ __forceinline__ void shift_rows(float (&s)[64], float d0, float d1) {
#pragma unroll
    for (int j = 0; j < 16; j++) { s[4 * j] -= d0; s[4 * j + 1] -= d0; s[4 * j + 2] -= d1; s[4 * j + 3] -= d1; }
}
constexpr float MASKED = -3e38f;
template <int J0>
__device__ __forceinline__ void mask_triangle(float (&s)[64], float thr) {
#pragma unroll
    for (int j = 0; j < 16; j++) {
        const float m = __saturatef((float)(8 * (j >> 1) + (j & 1)) - thr);
        const int i = 4 * (J0 + (j >> 1)) + (j & 1);
        s[i] = fmaf(m, MASKED, s[i]);
        if (j < 14) s[i + 6] = fmaf(m, MASKED, s[i + 6]);
    }
}
__device__ __forceinline__ void causal_mask(float (&s)[64], float thr, int wg) {
    asm volatile("" : "+f"(thr));
    if (wg == 0) {
        mask_triangle<0>(s, thr);
#pragma unroll
        for (int j = 32; j < 64; j++) s[j] += MASKED;
    } else {
        mask_triangle<8>(s, thr);
    }
}

__global__ void __cluster_dims__(2, 1, 1) __launch_bounds__(384, 1) fused_kernel(const __grid_constant__ Params prm) {
    extern __shared__ __align__(1024) uint8_t smem[];
    const uint32_t sb = smem_u32(smem), bars = sb + SM_BARS;
    const int warp = __shfl_sync(0xffffffffu, threadIdx.x >> 5, 0), lane = threadIdx.x & 31;

    const uint32_t rank = cluster_rank();
    const uint32_t bars0 = map_cta(bars, 0), bars_peer = map_cta(bars, rank ^ 1);

    auto plan_index = [&]() -> uint32_t {
        uint32_t p = blockIdx.x >> 1;
        asm volatile("" : "+r"(p));
        const uint32_t r = (p - 36) * 37 >> 8;
        return p < 4 ? 60 + p : p < 36 ? (p - 4 & 7) * 8 + (p - 4 >> 3) : p < 64 ? (p - 36 - 7 * r) * 8 + 4 + r : p;
    };
    auto first_item = [&]() -> int {
        const uint32_t pair = plan_index();
        const uint32_t slot = pair & 7, c = slot * 11 >> 5;
        return pair < 64 ? T_B << 13 | (4 * slot - 11 * c) << 4 | (2 * (pair >> 3) + rank) : T_K << 13 | (8 * slot + rank);
    };
    if (warp == 0) {
        if (elect_one()) {
            for (int k = 0; k < 4; k++) mbar_init(bars + B_GFULL + 8 * k, 1);
            asm volatile("fence.mbarrier_init.release.cluster;" ::: "memory");
            fence_proxy_async_smem();
        }
        __syncwarp();
        const int first_it = __shfl_sync(0xffffffffu, first_item(), 0);
        asm volatile("barrier.cluster.arrive.relaxed.aligned;" ::: "memory");
        const CUtensorMap* ma = &prm.m[item_type(first_it) == T_K ? M_C : M_X];
        const CUtensorMap* mb = &prm.m[M_WQ + item_type(first_it)];
#pragma unroll
        for (int k = 0; k < 2; k++) {
            const uint32_t dst = sb + k * GST_BYTES, fb = bars + B_GFULL + 8 * k;
            warp_expect_tx(fb, GST_BYTES);
            warp_tma_load(dst + 16384, mb, fb, 0, k * 64, item_col(first_it) * 4, true);
            warp_tma_load(dst, ma, fb, k * 64, item_row(first_it) * 128, 0, false);
            warp_tma_load(dst + 32768, mb, fb, 0, k * 64, item_col(first_it) * 4 + 2, true);
        }
    }
    if (threadIdx.x == 32) {
        for (int i = 0; i < 4; i++) { mbar_init(bars + B_GEMPTY + 8 * i, 16); mbar_init(bars + B_XFREE + 8 * i, 1); }
        for (int i = 0; i < 6; i++) { mbar_init(bars + B_AFULL + 8 * i, 1); mbar_init(bars + B_AEMPTY + 8 * i, i < 2 ? 8 : 16); }
        for (int i = 0; i < 4; i++) { mbar_init(bars + B_SFULL + 8 * i, 4); mbar_init(bars + B_SEMPTY + 8 * i, 1); }
        for (int i = 0; i < QDEPTH; i++) { mbar_init(bars + B_IFULL + 8 * i, 1); mbar_init(bars + B_IEMPTY + 8 * i, 23); }
        mbar_init(bars + B_WANT, 2); mbar_init(bars + B_MEET, 1);
        for (int i = 0; i < 4; i++) mbar_init(bars + B_HALF + 8 * i, 1);
        mbar_init(bars + B_ALT, 4); mbar_init(bars + B_ALT + 8, 4); mbar_init(bars + B_QFREE, 2);
        asm volatile("st.shared.u64 [%0], 0;" :: "r"(bars + SM_ORDY) : "memory");
        asm volatile("fence.mbarrier_init.release.cluster;\nfence.acq_rel.cta;" ::: "memory");
    }
    __syncwarp();
    if (warp != 0) asm volatile("barrier.cluster.arrive.relaxed.aligned;" ::: "memory");
    asm volatile("barrier.cluster.wait.acquire.aligned;" ::: "memory");

    uint32_t qn = 0;
    auto next_item = [&](bool releaser, bool bounded = true) -> int {
        const uint32_t slot = qn % QDEPTH;
        if (bounded) mbar_wait(bars + B_IFULL + 8 * slot, (qn / QDEPTH) & 1);
        else mbar_spin(bars + B_IFULL + 8 * slot, (qn / QDEPTH) & 1);
        uint32_t it;
        asm volatile("ld.shared.u32 %0, [%1];" : "=r"(it) : "r"(bars + SM_QUEUE + 4 * slot) : "memory");
        mbar_arrive_cluster_if(releaser, bars0 + B_IEMPTY + 8 * slot);
        qn++;
        return it;
    };

    if (warp < 4) {
        reg_dec<40>();
        if (warp == 0) {
            {
                uint32_t gph = 1;
                const uint32_t prank = __shfl_sync(0xffffffffu, rank, 0);
                auto request = [&]() { mbar_arrive_cluster_if(lane == 0, bars0 + B_WANT); };
                auto take_item = [&]() -> int { return __shfl_sync(0xffffffffu, next_item(lane == 0), 0); };
                auto inputs_seen = [&](uint32_t word, unsigned& n) -> uint32_t {
                    uint32_t v;
                    spin_guard(n);
                    asm volatile("ld.acquire.cta.shared.u32 %0, [%1];" : "=r"(v) : "r"(bars + SM_ORDY + 4 * word) : "memory");
                    return __shfl_sync(0xffffffffu, v, 0);
                };
                uint32_t oneed = 0;
                auto wait_inputs = [&](int it) {
                    if (it & ITEM_READY) return;
                    oneed += 256;
                    for (unsigned n = 0; inputs_seen(1, n) < oneed;) {}
                };
                int nxt = first_item(), ring = -1, rot = 0;
                for (int k0 = 2; item_type(nxt) <= T_LOCAL; k0 = 0) {
                    const int type = item_type(nxt), m = item_row(nxt), c = item_col(nxt);
                    if (type == T_LOCAL) {
                        wait_inputs(nxt);
                        request();
#pragma unroll 1
                        for (uint32_t st = 0; st < 4; st++) {
                            mbar_wait(bars + B_GEMPTY + 8 * st, gph);
                            const uint32_t dst = sb + st * GST_BYTES, fb = bars + B_GFULL + 8 * st;
                            warp_expect_tx(fb, st == 0 ? 32768 + 512 : st == 3 ? 0 : 4 * LOC_PLANE);
                            if (st == 3) break;
                            if (st == 0) warp_bulk_load(dst + 4 * LOC_PLANE, &g_gate[m * 128], 512, fb);
#pragma unroll 1
                            for (int i = 0; i < 4; i++)
                                warp_tma_load(dst + i * LOC_PLANE, &prm.m[st ? M_SCR_LOC : M_SCR_LOQ], fb, i * 64, m * 64 - (st ? 8 : 0), G_B + 8 * st + c, true);
                        }
                        gph ^= 1;
                        ring = -1;
                    } else {
                        const int nk = type == T_K || type == T_V ? 8 : 16, kept = ring == m + 16 * nk ? 4 : 0;
                        ring = m + 16 * nk;
                        rot = kept ? rot - 4 : 0;
                        const CUtensorMap* ma = &prm.m[nk == 8 ? M_C : M_X];
                        const CUtensorMap* mb = &prm.m[M_WQ + type];
#pragma unroll 1
                        for (int k = k0; k < nk; k++) {
                            if (k == nk - 3) request();
                            const uint32_t st = k & 3, dst = sb + st * GST_BYTES, fb = bars + B_GFULL + 8 * st;
                            const int kc = ((k + rot) & (nk - 1)) * 64;
                            mbar_wait(bars + B_GEMPTY + 8 * st, gph);
                            warp_expect_tx(fb, k < kept ? 32768 : GST_BYTES);
                            if (k >= kept) warp_tma_load(dst, ma, fb, kc, m * 128, 0, c == 15 && type != T_K);
                            warp_tma_load_pair(dst + 16384 + prank * 16384, mb, fb, 0, kc, c * 4 + 2 * prank, true);
                            if (st == 3) gph ^= 1;
                        }
                    }
                    nxt = take_item();
                }
                uint32_t kv = 0, kvph = 1;
                uint32_t qc = 0;
                auto a_parity = [&](uint32_t b) { return b < 2 ? (((qc + 1 - b) >> 1) & 1) ^ 1 : kvph ^ (b - 2 < kv); };
                const CUtensorMap* tile_map = &prm.m[M_SCR_LD];
                asm volatile("" : "+l"(tile_map));
                {
                    bool need_g = true, more = true;
                    int pv_grp = -1, pv_row = 0;
                    int pv_shared = 0;
                    bool peer_longer = false;
                    int m = 0, c = 0, asc = 0, nu = 0, uend = 0, ureq = -1, ufetch = 0;
#pragma unroll 1
                    for (int u = 0;; u++) {
                        if (u == ufetch) {
                            if (qc) nxt = take_item();
                            if (item_type(nxt) == T_ATTN) {
                                wait_inputs(nxt);
                                const uint32_t b = qc & 1, dst = sb + b * 32768, fb = bars + B_AFULL + 8 * b, row = item_row(nxt) * 128;
                                mbar_wait(bars + (qc == 0 ? B_GEMPTY : qc == 1 ? B_QFREE : B_AEMPTY + 8 * b), qc == 0 ? gph : qc == 1 ? 0 : a_parity(b));
                                warp_expect_tx(fb, 32768 + 512);
                                warp_tma_load(dst, tile_map, fb, 0, row, G_Q + item_col(nxt), false);
                                warp_tma_load(dst + 16384, tile_map, fb, 64, row, G_Q + item_col(nxt), false);
                                warp_bulk_load(bars + SM_GATE + b * 512, &g_gate[row], 512, fb);
                                qc++;
                            }
                        }
                        if (u == uend) {
                            if (!more) break;
                            more = item_type(nxt) == T_ATTN;
                            m = item_row(nxt); c = item_col(nxt); asc = item_asc(nxt);
                            nu = more ? 2 * m + 2 : 0;
                            uend = nu + ((more ? m < 2 : pv_grp >= 0) ? 3 : 0);
                            ureq = 2 * max(m - 2 - (asc & m), 0);
                            ufetch = !more ? -1 : m ? 2 * m : uend;
                            u = -1;
                            continue;
                        }
                        int grp = pv_grp, row = pv_row;
                        int shared = pv_shared;
                        if (u >= nu) {
                            if (u == nu + 1) pv_grp = -1;
                            else if (peer_longer) { grp = -1; shared = 0; }
                            else continue;
                        } else {
                            const int j = asc ? u >> 1 : m - (u >> 1);
                            if (u & 1) {
                                pv_grp = G_V + c; pv_row = j * 128; pv_shared = (m | 1) - j;
                                peer_longer = asc & ~m & 1;
                                if (u == nu - 1 && (m & 1) && item_type(nxt) == T_END) mbar_arrive_cluster_n_if(lane == 0, bars0 + B_WANT, 2);
                                if (grp < 0) continue;
                            } else {
                                if (u == ureq) request();
                                grp = G_K + c; row = j * 128; shared = (m | 1) - j;
                            }
                        }
                        uint32_t fb = bars + B_AFULL + 16 + 8 * kv, mine = sb + SM_KV + kv * 32768 + prank * 16384;
                        int c_mine = prank * 64;
                        asm volatile("" : "+r"(mine), "+r"(fb), "+r"(row), "+r"(grp), "+r"(c_mine));
                        mbar_wait(need_g ? bars + B_GEMPTY + 8 + 8 * kv : fb + B_AEMPTY - B_AFULL, need_g ? gph : kvph);
                        warp_expect_tx(fb, grp < 0 ? 0 : 32768);
                        if (shared) {
                            warp_tma_load_pair(mine, tile_map, fb, c_mine, row, grp, shared == 1);
                        } else if (grp >= 0) {
                            warp_tma_load(mine, tile_map, fb, c_mine, row, grp, true);
                            warp_tma_load(mine + 16384 - prank * 32768, tile_map, fb, 64 - c_mine, row, grp, true);
                        } else {
                            mbar_arrive_cluster_n_if(lane < 2, map_cta(fb, lane & 1) + B_AEMPTY - B_AFULL, 8);
                        }
                        if (kv == 2) need_g = false;
                        if (++kv == 4) { kv = 0; kvph ^= 1; }
                    }
                }
                if (!qc) request();
                const int it = take_item();
                int nk = 0;
                if (item_type(it) == T_OUT) {
                    const int m = item_row(it), c = item_col(it), half = c & 1;
                    nk = 80;
                    for (int k = 0; k < nk; k++) {
                        if (k == K_SPLIT) nk = 2 * TRIPLES + (take_item() & 127);
                        const int kn = k + 2 * TRIPLES - nk, first = kn >= 0 && !(kn & 1);
                        const int s = kn >= 0 ? WIDE + (3 * kn + 1) / 2 : half ? WIDE - 1 - k : k;
                        const uint32_t sa = prm.ostep[s], sa2 = prm.ostep[s + first], sw = prm.ostep[s - (kn >= 0 && !first ? prank : 0)];
                        const uint32_t need = 1u << (sa >> 1 & 31) | 1u << (sa2 >> 1 & 31);
                        for (unsigned n = 0; need & ~inputs_seen(sa >> 6, n);) {}
                        const uint32_t st = k & 3;
                        uint32_t dst = sb + st * GST_BYTES, fb = bars + B_GFULL + 8 * st;
                        uint32_t dstb = dst + 16384 + (first ? 0 : prank * 16384), skipb = first && (kn >> 1 & 1) != prank;
                        int a0 = (sa & 1) * 64, a1 = m * 128, a2 = (sa >> 1) + (sa < 64 ? G_CTX : G_LOC - 32);
                        int b1 = (sw & 63) * 64, b2 = (c >> 1) * 4 + 2 * (kn >= 0 ? half : half ^ prank);
                        const CUtensorMap* mb = &prm.m[sw >= 64 ? M_WOB : M_WO];
                        asm volatile("" : "+r"(dst), "+r"(fb), "+r"(dstb), "+r"(skipb), "+r"(a0), "+r"(a1), "+r"(a2), "+r"(b1), "+r"(b2), "+l"(mb));
                        if (k < 4) {
#pragma unroll 1
                            for (uint32_t i = 0, b = (3 * st) >> 1; i < 3; i++, b++) mbar_wait(bars + (i == 2 ? B_QFREE : B_AEMPTY + 8 * b), i == 2 ? 0 : a_parity(b));
                            mbar_arrive_cluster_if(lane == 0, bars_peer + B_XFREE + 8 * st);
                            mbar_wait(bars + B_XFREE + 8 * st, 0);
                        }
                        mbar_wait(bars + B_GEMPTY + 8 * st, gph);
                        warp_expect_tx(fb, GST_BYTES);
                        warp_tma_load(dst, tile_map, fb, a0, a1, a2, true);
                        if (!skipb) warp_tma_load_pair(dstb, mb, fb, 0, b1, b2, false);
                        if (first) warp_tma_load(dst + 32768, tile_map, fb, (sa2 & 1) * 64, a1, G_CTX + (sa2 >> 1), true);
                        if (k < K_SPLIT && lane == 0 && !prank)
                            asm volatile("st.relaxed.gpu.global.u32 [%0], %1;" :: "l"(&g_sync.step[0][0] + m * 4 + c), "r"(k) : "memory");
                        mbar_arrive_if(k == K_MEET && lane == 0, bars + B_MEET);
                        if ((uint32_t)(k - K_FETCH) < (3 * TRIPLES + 1) / 2) {
                            const uint32_t g = prm.ostep[79 - 2 * (k - K_FETCH)] >> 1;
                            warp_prefetch((const char*)g_scr + (uint32_t)((G_CTX + g) * (SEQ * 256) + m * 32768 + c * 4096), 4096);
                            warp_prefetch(prm.wo + (uint32_t)(g * 262144 + (m * 8 + c) * 2048), 2048);
                        }
                        if (st == 3) gph ^= 1;
                    }
                    for (unsigned n = 0; ~inputs_seen(0, n) || inputs_seen(1, n) != 255;) {}
                }
#pragma unroll 1
                for (uint32_t st = 0; st < 4; st++) { mbar_wait(bars + B_GEMPTY + 8 * st, gph ^ (st < (nk & 3))); mbar_wait(bars + B_AEMPTY + 16 + 8 * st, a_parity(2 + st)); }
                unsigned left = 0;
                if (lane == 0) asm volatile("atom.relaxed.gpu.global.add.u32 %0, [%1], 1;" : "=r"(left) : "l"(&g_sync.done) : "memory");
                if (__shfl_sync(0xffffffffu, left, 0) == NCTA - 1)
#pragma unroll 1
                    for (uint32_t i = lane * 8; i < sizeof(Sync); i += 256) *(unsigned long long*)((char*)&g_sync + i) = 0;
            }
        } else if (warp <= 2) {
            if (blockIdx.x < SEQ / 16) {
                const uint32_t r0 = 16 * blockIdx.x + 8 * (warp - 1), gbuf = bars + SM_GATE + 4 * (r0 & 15);
                float z[4];
                mbar_wait(bars + B_GFULL + 24, 0);
#pragma unroll 1
                for (uint32_t i = 0; i < 8; i++) {
                    const uint32_t off = (i & 3) * 512 + lane * 16;
                    const uint4* xp = (const uint4*)((const char*)prm.x + ((r0 + (i & 4)) * 2048 + off));
                    const uint4 wv = __ldg((const uint4*)((const char*)prm.gate_w + off));
                    uint4 xv[4];
#pragma unroll
                    for (int r = 0; r < 4; r++) { xv[r] = __ldg(xp + r * 128); if (!(i & 3)) z[r] = 0.f; }
                    const uint32_t ws[4] = {wv.x, wv.y, wv.z, wv.w};
#pragma unroll
                    for (int e = 0; e < 4; e++)
#pragma unroll
                        for (int r = 0; r < 4; r++) {
                            const uint32_t xs = e == 0 ? xv[r].x : e == 1 ? xv[r].y : e == 2 ? xv[r].z : xv[r].w;
                            z[r] = fmaf(__uint_as_float(xs << 16), __uint_as_float(ws[e] << 16), z[r]);
                            z[r] = fmaf(__uint_as_float(xs & 0xffff0000u), __uint_as_float(ws[e] & 0xffff0000u), z[r]);
                        }
                    if ((i & 3) == 3) {
#pragma unroll
                        for (int o = 16; o > 0; o >>= 1)
#pragma unroll
                            for (int r = 0; r < 4; r++) z[r] += __shfl_xor_sync(0xffffffffu, z[r], o);
                        const float zr = lane & 2 ? (lane & 1 ? z[3] : z[2]) : (lane & 1 ? z[1] : z[0]);
                        asm volatile("st.shared.f32 [%0], %1;" :: "r"(gbuf + 4 * ((i & 4) + (lane & 3))), "f"(1.f / (1.f + __expf(-zr))) : "memory");
                    }
                }
                fence_proxy_async_smem();
                __syncwarp();
                warp_bulk_store((char*)g_gate + 4 * r0, gbuf, 32);
                bulk_commit();
                bulk_wait<0>();
                __syncwarp();
                if (lane == 0) red_add(&g_sync.count[3], 1);
            }
            __syncwarp();
            {
                const int w = warp - 1;
                uint32_t sph = 0, nann = 0;
                int unsent = 0, nunsent = 0;
                bool urgent = false;
                auto announce = [&]() {
                    if (!urgent) return;
                    bulk_wait<0>();
                    __syncwarp();
                    const uint32_t hb = bars + B_HALF + 8 * (nann & 3);
                    if (w == 0) {
                        mbar_arrive_if(lane == 0, hb);
                    } else {
                        mbar_wait(hb, (nann >> 2) & 1);
                        const uint32_t type = item_type(unsent), m = item_row(unsent), c = item_col(unsent);
                        const uint32_t word = type < T_B ? c >> 3 : type == T_B ? 2 : offsetof(Sync, ctx) / 8 + m;
                        const uint32_t bit = type < T_B ? 8 * (c & 7) : type == T_B ? 8 * (c & 3) : type == T_LOCAL ? 32 + c : c;
                        if (lane < nunsent) red_add((unsigned long long*)((char*)&g_sync + 8 * word), 1ull << bit);
                        __syncwarp();
                    }
                    nann++;
                    nunsent = 0; urgent = false;
                };
                int held = first_item(), it;
                bool qfree = false;
                do {
                    if (!__all_sync(0xffffffffu, mbar_test(bars + B_IFULL + 8 * (qn % QDEPTH), (qn / QDEPTH) & 1))) announce();
                    it = __shfl_sync(0xffffffffu, next_item(lane == 0), 0);
                    const int itype = item_type(it);
                    const bool keep_held = itype == T_LOCAL;
                    if (itype >= T_ATTN && held < 0) {
                        urgent = nunsent;
                        mbar_arrive_if(lane == 0 && !qfree, bars + B_QFREE);
                        qfree = true;
                    }
#pragma unroll 1
                    for (int pass = held < 0 || keep_held; pass < 2; pass++) {
                        if (pass && (itype < T_OUT || itype == T_END)) break;
                        const int cur = pass ? it : held, type = item_type(cur), m = item_row(cur), c = item_col(cur);
                        const bool local = type == T_LOCAL;
                        const int grp = pass ? (local ? G_LOC : G_CTX) + c : type * 32 + 2 * c;
#pragma unroll 1
                        for (int i = 0; i < 4 - 2 * pass; i++) {
                            const int b = i & 1;
                            const bool alt = i >= 2 && itype == T_ATTN;
                            const uint32_t full = bars + (alt ? B_ALT + 8 * w : B_SFULL + 16 * w + 8 * b), par = alt ? 0 : sph;
                            if (i == 3 - 2 * pass || !__all_sync(0xffffffffu, mbar_test(full, par))) announce();
                            mbar_wait(full, par);
                            fence_proxy_async_smem();
                            warp_tma_store(&prm.m[local ? M_SCR_LOQ : M_SCR_ST], sb + (alt ? 32768 : SM_STAGING) + w * 16384 + b * 8192,
                                         local ? b * 128 + w * 64 : b * 64, local ? m * 64 : m * 128 + w * 64, grp + (i >> 1), local || (type < T_B && c < FIRST_PAIR));
                            bulk_commit();
                            bulk_wait_read<0>();
                            __syncwarp();
                            mbar_arrive_if(lane == 0 && !alt, bars + B_SEMPTY + 16 * w + 8 * b);
                            sph ^= b & !alt;
                        }
                        mbar_arrive_if(lane == 0 && !qfree && itype >= T_ATTN, bars + B_QFREE);
                        qfree |= itype >= T_ATTN;
                        if (lane == nunsent) unsent = cur;
                        nunsent++;
                        urgent = nunsent == 32 || !local;
                    }
                    if (!keep_held) held = itype < T_OUT ? it : -1;
                } while (item_type(it) != T_END);
                announce();
                if (item_type(next_item(lane == 0)) == T_OUT) {
                    if (w) {
                        mbar_wait(bars + B_MEET, 0);
                        asm volatile("fence.acq_rel.gpu;" ::: "memory");
                        mbar_arrive_cluster_if(lane == 0, bars0 + B_WANT);
                    }
                    next_item(lane == 0);
                }
            }
        } else {
            if (elect_one()) {
                uint32_t ordy = 0;
                unsigned long long cnt_lo = 0, cnt_hi = 0;
                int late = 0;
                auto refresh = [&]() {
                    if (!late && cnt_lo == 0x30303030 && cnt_hi == SEQ / 8) late = 1;
                    asm volatile("ld.acquire.gpu.global.v2.u64 {%0, %1}, [%2];" : "=l"(cnt_lo), "=l"(cnt_hi) : "l"(late ? &g_sync.count[0] : &g_sync.count[2]) : "memory");
                };
                auto inputs_ready = [&](int it) -> bool {
                    const int c = item_col(it);
                    if (item_type(it) == T_ATTN) return late && ((c < 16 ? cnt_lo : cnt_hi) >> (4 * (c & 14)) & 255) == 48;
                    return late || (cnt_hi == SEQ / 8 && (cnt_lo >> (4 * (c & 6)) & 255) == 48);
                };
                auto publish = [&](int it, int step) {
                    const uint32_t slot = qn % QDEPTH;
                    mbar_wait(bars + B_IEMPTY + 8 * slot, ((qn / QDEPTH) & 1) ^ 1);
                    for (uint32_t r = 0; r < 2; r++) {
                        const uint32_t rb = map_cta(bars, r);
                        asm volatile("mbarrier.arrive.expect_tx.shared::cluster.b64 _, [%0], 4;" :: "r"(rb + B_IFULL + 8 * slot) : "memory");
                        asm volatile("st.async.shared::cluster.mbarrier::complete_tx::bytes.u32 [%0], %1, [%2];"
                                     :: "r"(rb + SM_QUEUE + 4 * slot), "r"(it + r * step), "r"(rb + B_IFULL + 8 * slot) : "memory");
                    }
                    qn++;
                };
                int asc = 1;
                int it;
                do {
                    if (rank == 0) {
                        mbar_wait(bars + B_WANT, qn & 1);
                        const uint32_t pair = plan_index();
                        int pit = prm.plan[pair < 64 ? pair & 7 : pair - 56][min(qn + 1, 15u)];
                        unsigned i;
                        const bool planned = item_type(pit) != T_END;
                        if (!planned) asm volatile("atom.relaxed.gpu.global.add.u32 %0, [%1], 1;" : "=r"(i) : "l"(&g_sync.next) : "memory");
                        if (cnt_lo != 0x3030303030303030ull || cnt_hi != cnt_lo) refresh();
                        if (planned) pit += (pair >> 3 & 7) << (item_type(pit) == T_LOCAL);
                        else if (i < NITEMS) pit = prm.items[i];
                        const int type = item_type(pit);
                        int step = type == T_LOCAL ? 16 : 1;
                        it = pit + (pit & (step == 1 ? 15 : 0x1f0));
                        if (type == T_ATTN) {
                            if (!asc) { it += 1; step = -1; }
                            it |= asc << 9;
                        }
                        asc = type != T_ATTN || item_row(pit) == 0 || !asc;
                        if (inputs_ready(it)) it |= ITEM_READY;
                        publish(it, step);
                    } else {
                        it = next_item(true);
                    }
                    if ((item_type(it) == T_ATTN || item_type(it) == T_LOCAL) && !(it & ITEM_READY)) {
                        unsigned n = 0;
                        while (!inputs_ready(it)) { refresh(); spin_guard(n); }
                        asm volatile("st.release.cta.shared.u32 [%0], %1;" :: "r"(bars + SM_ORDY + 4), "r"(ordy += 256) : "memory");
                    }
                } while (item_type(it) != T_END);
                if (rank == 0) {
                    mbar_wait(bars + B_WANT, qn & 1);
                    const unsigned i = atomicAdd(&g_sync.next_out, 1u), t = i < 32 ? 31 - i : i - 32;
                    it = i < 64 ? T_OUT << 13 | ((t & 3) * 2 + (i >> 5)) << 4 | (t >> 2) * 2 : T_END << 13;
                    publish(it, 1);
                } else {
                    it = next_item(true);
                }
                if (item_type(it) == T_OUT) {
                    const uint32_t m = item_row(it), half = item_col(it) & 1, tile = m * 2 + (item_col(it) >> 1);
                    unsigned* split = (unsigned*)((char*)g_sync.split + 4 * tile);
                    unsigned long long rdy = 0;
                    int state = rank ? 2 : 0;
                    for (unsigned n = 0; rdy != 0xffffffffffull || state < 2; spin_guard(n)) {
                        if (rdy != 0xffffffffffull) {
                            rdy = ld_acquire((const unsigned long long*)((char*)g_sync.ctx + 8 * m));
                            asm volatile("st.release.cta.shared.u64 [%0], %1;" :: "r"(bars + SM_ORDY), "l"(rdy) : "memory");
                        }
                        unsigned steps = 0;
                        if (state == 1) {
                            steps = ld_acquire(split);
                        } else if (state == 0 && mbar_test(bars + B_WANT, qn & 1)) {
                            state = 1;
                            unsigned seen;
                            asm volatile("atom.acq_rel.gpu.global.exch.b32 %0, [%1], 1;" : "=r"(seen) : "l"(split) : "memory");
                            if (seen) {
                                const unsigned long long v = ld_acquire((const unsigned long long*)((char*)g_sync.step + 8 * tile));
                                const int d = (int)(v >> 32) - (int)v;
                                steps = (WIDE + min(max(half ? d : -d, -12), 12)) >> 1;
                                atomicExch(split, WIDE - steps);
                            }
                        }
                        if (steps > 1) { publish(T_END << 13 | steps, 0); state = 2; }
                    }
                    if (rank) next_item(true);
                }
                #pragma unroll 1
                for (uint32_t n = qn; n < qn + QDEPTH && rank == 0; n++) mbar_wait(bars + B_IEMPTY + 8 * (n % QDEPTH), ((n / QDEPTH) & 1) ^ 1);
            }
        }
    } else {
        reg_inc<232>();
        const int wg = (warp >> 2) - 1, wq = warp & 3;
        uint32_t gph = 0;
        uint32_t kvn = 0;
        const uint32_t dA = make_desc(sb + wg * 8192, 16);
        uint32_t ti = 0;
        uint32_t sph = 1;
        const uint32_t stg = sb + SM_STAGING + wg * 16384;
        const uint32_t stg_lane = stg + (wq * 16 + (lane & 15)) * 128 + (((lane >> 4) ^ (lane & 7)) << 4);
        auto write_blocks = [&](auto n, uint32_t off, const uint32_t* v) {
            uint32_t a = stg_lane;
            asm volatile("" : "+r"(a));
            a += off;
#pragma unroll
            for (int j = 0; j < decltype(n)::value; j++)
                stmatrix_x4((a ^ (32 * (j & 3))) + (j >> 2) * 8192, v[4 * j], v[4 * j + 1], v[4 * j + 2], v[4 * j + 3]);
        };
        auto release = [&](uint32_t bar) { mbar_arrive_if(lane == 0, bars + bar); };
        const uint32_t bars_lane = map_cta(bars, lane & 1);
        auto release_stage = [&](uint32_t st) { mbar_arrive_cluster_if(lane < 2, bars_lane + B_GEMPTY + 8 * st); };
        auto take_item = [&]() -> int {
            return __shfl_sync(0xffffffffu, next_item(lane == 0, false), 0);
        };
        auto stage_acquire = [&](int b) { mbar_spin(bars + B_SEMPTY + 16 * wg + 8 * b, sph); };
        auto stage_publish = [&](int b) {
            __syncwarp();
            release(B_SFULL + 16 * wg + 8 * b);
        };
        auto stage_chunk = [&](int b, const uint32_t* v) {
            stage_acquire(b);
            write_blocks(std::integral_constant<int, 4>(), b * 8192, v);
            stage_publish(b);
            if (b) sph ^= 1;
        };
        auto publish_pair = [&]() {
            __syncwarp();
            mbar_arrive_if(lane < 2, bars + B_SFULL + 16 * wg + 8 * lane);
            sph ^= 1;
        };
        auto gemm_step = [&](float (&acc)[128], uint32_t dB, int& k) {
            const uint32_t st = k & 3;
            wgmma_wait<0>();
            release_stage((k - 1) & 3);
            mbar_spin(bars + B_GFULL + 8 * st, gph);
            const uint64_t da = full_desc(dA + st * (GST_BYTES >> 4)), db = full_desc(dB + st * (GST_BYTES >> 4));
            wgmma_fence();
#pragma unroll
            for (int kk = 0; kk < 4; kk++) wgmma_ss_n256_tb(acc, da + 2 * kk, db + 128 * kk, 1);
            wgmma_commit();
            gph ^= st == 3;
            k++;
        };
        if (wg == 1) bar_arrive(1, 256);
        int it = first_item();
        while (true) {
            if (item_type(it) <= T_LOCAL) {
                float acc[128];
                uint32_t pk[64];
                bool pending = false;
                int held = T_END;
                auto scale_q = [&](int j0, int n) {
                    if (held != T_Q) return;
#pragma unroll
                    for (int j = j0; j < j0 + n; j++)
                        asm("{\n.reg .b32 t;\nmul.rn.bf16x2 t, %0, %2;\nfma.rn.bf16x2 %0, %0, %1, t;\n}\n" : "+r"(pk[j]) : "r"(0x3e033e03u), "r"(0xb9d8b9d8u));
                };
                zero_regs(pk);
                const uint32_t dB = make_desc(sb + 16384, 8192);
                do {
                    const int type = item_type(it);
                    if (type == T_LOCAL) {
                        int ln = lane;
                        asm volatile("" : "+r"(ln));
                        const int g = ln >> 2, t = ln & 3, par = wq & 1;
                        const uint32_t hc = (wq >> 1) * 4, pl = sb + (par * 2 + wg) * LOC_PLANE;
                        const uint32_t a16 = (ln & 15) * 128 + (((hc + (ln >> 4)) ^ (ln & 7)) << 4), a8 = (ln & 7) * 128 + (((hc + (ln >> 3)) ^ (ln & 7)) << 4);
                        const bool first0 = 2 * t > g, first1 = 2 * t + 1 > g;
                        const uint32_t fmask = (first0 ? 0xffffu : 0u) | (first1 ? 0xffff0000u : 0u);
                        const bool edge = item_row(it) == 0;
                        uint32_t q[4][2][4], kf[9][4], vf[9][4];
                        float w[8];
                        mbar_spin(bars + B_GFULL, gph);
#pragma unroll
                        for (int u = 0; u < 4; u++) { ldsm_x4(q[u][0], pl + u * 2048 + a16); ldsm_x4(q[u][1], pl + u * 2048 + (a16 ^ 32)); }
#pragma unroll
                        for (int j = 0; j < 8; j++) w[j] = lds_f32(sb + 4 * LOC_PLANE + 4 * (2 * g + par) + 64 * j);
                        __syncwarp();
                        release_stage(0);
                        mbar_spin(bars + B_GFULL + 8, gph);
#pragma unroll
                        for (int n = 0; n < 9; n++) ldsm_x4(kf[n], pl + GST_BYTES + n * 1024 + a8);
                        __syncwarp();
                        release_stage(1);
                        float s[8][2];
#pragma unroll
                        for (int u = 0; u < 4; u++) {
                            float d[3][4];
#pragma unroll
                            for (int nt = 0; nt < 3; nt++) {
                                mma_k16_init(d[nt], q[u][0], kf[2 * u + nt][0], kf[2 * u + nt][1]);
                                mma_k16(d[nt], q[u][1], kf[2 * u + nt][2], kf[2 * u + nt][3]);
                            }
                            if (u == 0 && edge) { d[0][0] = -INFINITY; d[0][1] = -INFINITY; }
                            s[2 * u][0] = first0 ? d[0][0] : d[1][0]; s[2 * u][1] = first1 ? d[0][1] : d[1][1];
                            s[2 * u + 1][0] = first0 ? d[1][2] : d[2][2]; s[2 * u + 1][1] = first1 ? d[1][3] : d[2][3];
                        }
                        mbar_spin(bars + B_GFULL + 16, gph);
#pragma unroll
                        for (int u = 0; u < 4; u++) { ldsm_x4_t(vf[2 * u], pl + 2 * GST_BYTES + u * 2048 + a16); ldsm_x4_t(vf[2 * u + 1], pl + 2 * GST_BYTES + u * 2048 + (a16 ^ 32)); }
                        ldsm_x4_t(vf[8], pl + 2 * GST_BYTES + 8192 + a8);
                        __syncwarp();
                        release_stage(2);
                        float x[8];
#pragma unroll
                        for (int j = 0; j < 8; j++) x[j] = fmaxf(s[j][0], s[j][1]);
#pragma unroll
                        for (int o = 1; o < 4; o *= 2)
#pragma unroll
                            for (int j = 0; j < 8; j++) x[j] = fmaxf(x[j], __shfl_xor_sync(0xffffffffu, x[j], o));
#pragma unroll
                        for (int j = 0; j < 8; j++) {
                            const float n = x[j] * -LOC_SCALE;
                            s[j][0] = ex2(fmaf(s[j][0], LOC_SCALE, n)); s[j][1] = ex2(fmaf(s[j][1], LOC_SCALE, n));
                            x[j] = s[j][0] + s[j][1];
                        }
#pragma unroll
                        for (int o = 1; o < 4; o *= 2)
#pragma unroll
                            for (int j = 0; j < 8; j++) x[j] += __shfl_xor_sync(0xffffffffu, x[j], o);
                        mbar_spin(bars + B_GFULL + 24, gph);
                        release_stage(3);
                        it = take_item();
                        uint32_t ob[4][8];
#pragma unroll
                        for (int u = 0; u < 4; u++) {
                            const float r0 = rcp(x[2 * u]), r1 = rcp(x[2 * u + 1]), f0 = fmaf(-w[2 * u], r0, r0), f1 = fmaf(-w[2 * u + 1], r1, r1);
                            const uint32_t p0 = pack_bf16(s[2 * u][0] * f0, s[2 * u][1] * f0), p1 = pack_bf16(s[2 * u + 1][0] * f1, s[2 * u + 1][1] * f1);
                            const uint32_t pa[4] = {p0 & fmask, 0, p0 & ~fmask, p1 & fmask};
#pragma unroll
                            for (int c = 0; c < 4; c++) {
                                float ol[4];
                                mma_k16_init(ol, pa, vf[2 * u + (c >> 1)][2 * (c & 1)], vf[2 * u + (c >> 1)][2 * (c & 1) + 1]);
                                mma_k8(ol, 0, p1 & ~fmask, u < 3 ? vf[2 * u + 2 + (c >> 1)][2 * (c & 1)] : vf[8][c]);
                                ob[u][2 * c] = pack_bf16(ol[0], ol[1]);
                                ob[u][2 * c + 1] = pack_bf16(ol[2], ol[3]);
                            }
                        }
                        stage_acquire(0); stage_acquire(1);
#pragma unroll
                        for (int u = 0; u < 4; u++) {
                            stmatrix_x4(stg + par * 8192 + u * 2048 + a16, ob[u][0], ob[u][1], ob[u][2], ob[u][3]);
                            stmatrix_x4(stg + par * 8192 + u * 2048 + (a16 ^ 32), ob[u][4], ob[u][5], ob[u][6], ob[u][7]);
                        }
                        publish_pair();
                        bar_sync(4, 256);
                        gph ^= 1;
                        continue;
                    }
                    mbar_spin(bars + B_GFULL, gph);
                    bool more;
                    do {
                        wgmma_fence();
                        wgmma_ss_n256_tb_init(acc, full_desc(dA), full_desc(dB));
#pragma unroll
                        for (int kk = 1; kk < 4; kk++) wgmma_ss_n256_tb(acc, full_desc(dA) + 2 * kk, full_desc(dB) + 128 * kk, 1);
                        wgmma_commit();
                        const int nk = item_type(it) == T_K || item_type(it) == T_V ? 8 : 16;
                        int k = 1;
                        do {
                            if (pending) {
                                const int kf = k - 1 - wg;
                                if (kf == 0) { scale_q(0, 16); stage_chunk(0, pk); }
                                else if (kf == 1) { scale_q(16, 16); stage_chunk(1, pk + 16); }
                                else if (kf == 3) { scale_q(32, 16); stage_chunk(0, pk + 32); }
                                else if (kf == 4) { scale_q(48, 16); stage_chunk(1, pk + 48); }
                            }
                            gemm_step(acc, dB, k);
                        } while (k < nk);
                        held = item_type(it);
                        it = take_item();
                        more = item_type(it) < T_LOCAL;
                        if (more) mbar_spin(bars + B_GFULL, gph);
                        wgmma_wait<0>();
                        fence_regs(acc);
                        release_stage(3);
#pragma unroll
                        for (int j = 0; j < 64; j++) pk[j] = pack_bf16(acc[2 * j], acc[2 * j + 1]);
                        pending = true;
                    } while (more);
                } while (item_type(it) <= T_LOCAL);
                if (pending) {
                    scale_q(0, 64);
                    stage_acquire(0); stage_acquire(1);
                    write_blocks(std::integral_constant<int, 8>(), 0, pk);
                    const bool borrow = item_type(it) == T_ATTN;
                    if (borrow) {
                        mbar_spin(bars + B_GEMPTY, gph ^ 1); mbar_spin(bars + B_GEMPTY + 8, gph ^ 1);
                    } else {
                        publish_pair();
                        stage_acquire(0); stage_acquire(1);
                    }
                    write_blocks(std::integral_constant<int, 8>(), borrow ? 32768 - SM_STAGING : 0, pk + 32);
                    publish_pair();
                    mbar_arrive_if(lane == 0 && borrow, bars + B_ALT + 8 * wg);
                }
                if (item_type(it) == T_END) { it = take_item(); break; }
            } else {
                float o[64], s[64];
                uint32_t pa[32], pb[32];
                zero_regs(o); zero_regs(s); zero_regs(pa);
                float n0 = 0.f, n1 = 0.f;
                int shifted = 0;
                float l0 = 1.f, l1 = 1.f, f0 = 0.f, f1 = 0.f, g0 = 0.f, g1 = 0.f;
                uint32_t has_pv = 0;
                int first = 0;
                int pending = 0;
                const uint32_t dK = make_desc(sb + SM_KV, 16), dV = make_desc(sb + SM_KV, 16384);
                const uint32_t lane_off = bars_lane - bars + B_AEMPTY - B_AFULL;
                int cur = 0;
                uint32_t qoff = 0;
                const int row = wg * 64 + wq * 16 + (lane >> 2);
                const float thr = (row & 63) - (lane & 3) * 2;
                int peek = 0;
                auto kv_wait = [&](uint32_t n) { mbar_spin(bars + B_AFULL + 16 + 8 * (n & 3), (n >> 2) & 1); };
                auto kv_release = [&](uint32_t n) { mbar_arrive_cluster_if(lane < 2, bars_lane + B_AEMPTY + 16 + 8 * (n & 3)); };
                struct Slot { uint32_t bar, par, off; } slot[4];
                auto align = [&]() {
#pragma unroll
                    for (uint32_t i = 0; i < 4; i++) {
                        const uint32_t n = kvn + (i == 1 ? has_pv : i);
                        slot[i].bar = bars + B_AFULL + 16 + 8 * (n & 3); slot[i].par = (n >> 2) & 1; slot[i].off = (n & 3) * 2048;
                    }
                };
                align();
                auto scale_o = [&]() {
#pragma unroll
                    for (int j = 0; j < 16; j++) { o[4 * j] *= f0; o[4 * j + 1] *= f0; o[4 * j + 2] *= f1; o[4 * j + 3] *= f1; }
                };
                auto pack_o = [&](uint32_t (&v)[32]) {
#pragma unroll
                    for (int j = 0; j < 32; j++) v[j] = pack_bf16(o[2 * j], o[2 * j + 1]);
                };
                auto scales = [&]() { f0 = g0 * rcp(quad_sum(l0)); f1 = g1 * rcp(quad_sum(l1)); };
                auto step = [&](auto even, uint32_t (&pin)[32], uint32_t (&pout)[32], bool fresh, bool diag, bool last) {
                    constexpr bool EVEN = decltype(even)::value;
                    Slot& sk = slot[EVEN ? 0 : 2];
                    Slot& sv = slot[EVEN ? 1 : 3];
                    kvn += EVEN ? 1 + has_pv : 2;
                    mbar_spin(sk.bar, sk.par);
                    bar_sync(1 + wg, 256);
                    qk_gemm(s, dA + qoff, dK + sk.off);
                    if (EVEN && fresh) {
                        scales();
                        g0 = lds_f32(bars + SM_GATE + (ti & 1) * 512 + 4 * row); g1 = lds_f32(bars + SM_GATE + (ti & 1) * 512 + 4 * row + 32);
                        ti++;
                        n0 = 0.f; n1 = 0.f; l0 = 0.f; l1 = 0.f;
                        shifted = 0;
                        if (has_pv) { stage_acquire(0); stage_acquire(1); }
                    }
                    if (!EVEN && pending) {
                        pack_o(pout);
                        write_blocks(std::integral_constant<int, 8>(), 0, pout);
                        publish_pair();
                    }
                    if (last)
                        asm volatile("{\n.reg .pred P, Q;\n"
                                     "mbarrier.test_wait.parity.shared::cta.b64 Q, [%1], %2;\n"
                                     "mbarrier.test_wait.parity.shared::cta.b64 P, [%3], %4;\n"
                                     "ld.shared.u32 %0, [%5];\n"
                                     "@!Q or.b32 %0, %0, 0x10000;\n"
                                     "@!P mov.u32 %0, -1;\n}\n"
                                     : "=r"(peek) : "r"(bars + B_AFULL + 8 * (ti & 1)), "r"((ti >> 1) & 1), "r"(bars + B_IFULL + 8 * (qn % QDEPTH)),
                                       "r"((qn / QDEPTH) & 1), "r"(bars + SM_QUEUE + 4 * (qn % QDEPTH)) : "memory");
                    mbar_spin(sv.bar, sv.par);
                    pv_gemm(o, pin, dV + sv.off, EVEN || !first);
                    bar_arrive(2 - wg, 256);
                    sk.par ^= 1; sv.par ^= 1;
                    wgmma_wait<1>();
                    fence_regs(s);
                    mbar_arrive_cluster_if(lane < 2 && (!EVEN || has_pv), sk.bar + lane_off);
                    mbar_arrive_if(lane == 0 && last, bars + B_AEMPTY + 8 * ((ti - 1) & 1));
                    float r0, r1, x0 = n0, x1 = n1;
#pragma unroll 1
                    for (int mask = diag, redone = 0;; mask = 0, redone = 1) {
                        if (mask | shifted) {
                            if (mask) causal_mask(s, thr, wg);
                            if (shifted) shift_rows(s, x0, x1);
                        }
                        exp_pack(pout, s, r0, r1);
                        if (!__any_sync(0xffffffffu, fmaxf(r0, r1) >= SUM_LIMIT || (EVEN && fresh && !(lane & 3) && !(fminf(s[0], s[2]) >= -REF_RANGE))) || redone) break;
                        row_max(s, x0, x1);
                        if (!(EVEN && fresh)) { x0 = fmaxf(x0, 0.f); x1 = fmaxf(x1, 0.f); }
                        float a0 = ex2(-x0), a1 = ex2(-x1);
                        n0 += x0; n1 += x1;
                        shifted = 1;
                        if (EVEN && fresh) { a0 = 1.f; a1 = 1.f; }
                        l0 *= a0; l1 *= a1;
                        wgmma_wait<0>();
                        fence_regs(o);
#pragma unroll
                        for (int q = 0; q < 16; q++) { o[4 * q] *= a0; o[4 * q + 1] *= a0; o[4 * q + 2] *= a1; o[4 * q + 3] *= a1; }
                    }
                    l0 += r0; l1 += r1;
                    wgmma_wait<0>();
                    fence_regs(o);
                    fence_regs(pin);
                    mbar_arrive_cluster_if(lane < 2, sv.bar + lane_off);
                };
                auto copy_p = [&]() {
#pragma unroll
                    for (int j = 0; j < 32; j++) pa[j] = __float_as_uint(__uint_as_float(pb[j]) + __uint_as_float(prm.zero));
                };
                int rem = 0;
                mbar_spin(bars + B_AFULL + 8 * (ti & 1), (ti >> 1) & 1);
                while (true) {
                    const bool fresh = rem == 0;
                    if (fresh) {
                        if (has_pv) {
                            const int seen = __shfl_sync(0xffffffffu, peek, 0);
                            if (seen >= 0) {
                                mbar_arrive_cluster_if(lane == 0, bars0 + B_IEMPTY + 8 * (qn % QDEPTH));
                                qn++;
                                it = seen & 0xffff;
                            } else {
                                it = take_item();
                            }
                            if (item_row(cur) < 2 || item_type(it) != T_ATTN) break;
                            if (seen & 0x10000) mbar_spin(bars + B_AFULL + 8 * (ti & 1), (ti >> 1) & 1);
                        }
                        cur = it;
                        qoff = (ti & 1) * 2048;
                    }
                    const bool last = fresh ? item_row(cur) == 0 : rem == 1;
                    step(std::true_type(), pa, pb, fresh, item_asc(cur) ? last : fresh, last);
                    first = fresh;
                    if (fresh) {
                        pending = has_pv; has_pv = 1;
                        if (!pending) { kvn -= 2; align(); kvn += 2; slot[0].par ^= 1; slot[1].par ^= 1; }
                        else scale_o();
                        rem = item_row(cur);
                        if (rem == 0) {
                            copy_p();
                            continue;
                        }
                    } else if (--rem == 0) {
                        copy_p();
                        const Slot t0 = slot[0], t1 = slot[1];
                        slot[0] = slot[2]; slot[1] = slot[3]; slot[2] = t0; slot[3] = t1;
                        continue;
                    }
                    step(std::false_type(), pb, pa, false, item_asc(cur) && rem == 1, rem == 1);
                    pending = 0; first = 0;
                    rem--;
                }
                const uint32_t skip = item_asc(cur) & ~item_row(cur) & 1;
                kvn += skip;
                const bool end = item_type(it) == T_END;
#pragma unroll 1
                for (int pass = pending ? 0 : 1; pass < 2; pass++) {
                    if (pass) {
                        kv_wait(kvn);
                        pv_gemm(o, pa, dV + (kvn & 3) * 2048, !first);
                        scales();
                        stage_acquire(0); stage_acquire(1);
                        if (end) it = take_item();
                        wgmma_wait<0>();
                        fence_regs(o);
                        kv_release(kvn);
                        kvn += 1 + skip;
                        scale_o();
                    }
                    pack_o(pb);
                    write_blocks(std::integral_constant<int, 8>(), 0, pb);
                    publish_pair();
                }
                if (end) break;
            }
        }
        if (item_type(it) == T_OUT) {
            float acc[128];
            const uint32_t dB = make_desc(sb + 16384, 8192);
            mbar_spin(bars + B_GFULL, gph);
            wgmma_fence();
            wgmma_ss_n256_tb_init(acc, full_desc(dA), full_desc(dB));
#pragma unroll
            for (int kk = 1; kk < 4; kk++) wgmma_ss_n256_tb(acc, full_desc(dA) + 2 * kk, full_desc(dB) + 128 * kk, 1);
            wgmma_commit();
            uint32_t ln;
            asm volatile("mov.u32 %0, %%laneid;" : "=r"(ln));
            const uint32_t slot = (it & 127) * 32768 + (wg * 128 + wq * 32 + ln) * 16;
            char* const mine = (char*)g_part + slot;
            int k = 1, nk = 80;
            do {
                if (k == K_MEET - 5) {
#pragma unroll
                    for (int j = 0; j < 8; j++) st_b128(mine + j * 4096, 0, 0, 0, 0);
                    __syncwarp();
                }
                if (k == K_SPLIT) nk = take_item() & 127;
                gemm_step(acc, dB, k);
            } while (k < nk);
            float lo[64];
            auto triple = [&](auto first) {
                const uint32_t s0 = k & 3, s1 = (k + 1) & 3, o0 = s0 * (GST_BYTES >> 4), o1 = s1 * (GST_BYTES >> 4);
                wgmma_wait<0>();
                mbar_arrive_cluster_if(ln < (decltype(first)::value ? 2 : 4), bars_lane + B_GEMPTY + 8 * ((k - 1 - (ln >> 1)) & 3));
                mbar_spin(bars + B_GFULL + 8 * s0, gph);
                gph ^= s0 == 3;
                wgmma_fence();
#pragma unroll
                for (int kk = 0; kk < 4; kk++) {
                    if (decltype(first)::value && kk == 0) wgmma_ss_n128_tb_init(lo, full_desc(dA + o0), full_desc(dB + o0));
                    else wgmma_ss_n128_tb(lo, full_desc(dA + o0) + 2 * kk, full_desc(dB + o0) + 128 * kk, 1);
                }
                mbar_spin(bars + B_GFULL + 8 * s1, gph);
                gph ^= s1 == 3;
                wgmma_fence();
#pragma unroll
                for (int kk = 0; kk < 4; kk++) wgmma_ss_n128_tb(lo, full_desc(dA + o0 + 2048) + 2 * kk, full_desc(dB + o1 + 1024) + 128 * kk, 1);
#pragma unroll
                for (int kk = 0; kk < 4; kk++) wgmma_ss_n128_tb(lo, full_desc(dA + o1) + 2 * kk, full_desc(dB + o1) + 128 * kk, 1);
                wgmma_commit();
                k += 2;
            };
            triple(std::true_type());
            fence_regs(acc);
#pragma unroll
            for (int j = 0; j < 8; j++) {
                uint32_t v[4];
#pragma unroll
                for (int i = 0; i < 4; i++) v[i] = pack_bf16(acc[64 + 8 * j + 2 * i], acc[65 + 8 * j + 2 * i]);
                if (j == 4) triple(std::false_type());
                st_b128(mine + j * 4096, ~v[0], v[1], v[2], v[3]);
            }
            triple(std::false_type());
            uint32_t pk[32];
            char* const other = (char*)g_part + (slot ^ (16 * 32768));
            while (true) {
#pragma unroll
                for (int j = 0; j < 8; j++) ld_b128(other + j * 4096, pk[4 * j], pk[4 * j + 1], pk[4 * j + 2], pk[4 * j + 3]);
                bool miss = false;
#pragma unroll
                for (int j = 0; j < 8; j++) miss |= pk[4 * j] == 0;
                if (!__any_sync(0xffffffffu, miss)) break;
                while (__any_sync(0xffffffffu, pk[28] == 0)) ld_b128(other + 7 * 4096, pk[28], pk[29], pk[30], pk[31]);
            }
#pragma unroll
            for (int j = 0; j < 32; j++) {
                const uint32_t v = j & 3 ? pk[j] : ~pk[j];
                acc[2 * j] += __uint_as_float(v << 16); acc[2 * j + 1] += __uint_as_float(v & 0xffff0000u);
                asm volatile("" : "+f"(acc[2 * j]), "+f"(acc[2 * j + 1]) :: "memory");
            }
            stage_acquire(0); stage_acquire(1);
            wgmma_wait<0>();
            fence_regs(lo);
            mbar_arrive_cluster_if(ln < 4, bars_lane + B_GEMPTY + 8 * ((k - 1 - (ln >> 1)) & 3));
#pragma unroll
            for (int j = 0; j < 32; j++)
                pk[j] = pack_bf16(acc[2 * j] + lo[2 * j], acc[2 * j + 1] + lo[2 * j + 1]);
            write_blocks(std::integral_constant<int, 8>(), 0, pk);
            __syncwarp();
            uint4* dst = (uint4*)((char*)prm.out + (uint32_t)((item_row(it) * 128 + wg * 64 + wq * 16 + (ln >> 4)) * 2048 + item_col(it) * 256 + (ln & 15) * 16));
#pragma unroll
            for (int j = 0; j < 8; j++) {
                const int r = 2 * j + (ln >> 4);
                uint4 v;
                asm volatile("ld.shared.v4.u32 {%0, %1, %2, %3}, [%4];" : "=r"(v.x), "=r"(v.y), "=r"(v.z), "=r"(v.w)
                             : "r"(stg + wq * 2048 + r * 128 + (ln & 8) * 1024 + (((ln & 7) ^ (r & 7)) << 4)) : "memory");
                dst[j * 256] = v;
            }
        }
    }
}

typedef CUresult (*EncodeFn)(CUtensorMap*, CUtensorMapDataType, cuuint32_t, void*, const cuuint64_t*, const cuuint64_t*,
                             const cuuint32_t*, const cuuint32_t*, CUtensorMapInterleave, CUtensorMapSwizzle,
                             CUtensorMapL2promotion, CUtensorMapFloatOOBfill);

void encode3(EncodeFn fn, CUtensorMap* m, const void* ptr, uint64_t d0, uint64_t d1, uint64_t d2, uint64_t s1, uint64_t s2,
             uint32_t b0, uint32_t b1, uint32_t b2) {
    cuuint64_t dims[3] = {d0, d1, d2};
    cuuint64_t strides[2] = {s1, s2};
    cuuint32_t box[3] = {b0, b1, b2};
    cuuint32_t es[3] = {1, 1, 1};
    fn(m, CU_TENSOR_MAP_DATA_TYPE_BFLOAT16, 3, const_cast<void*>(ptr), dims, strides, box, es, CU_TENSOR_MAP_INTERLEAVE_NONE,
       CU_TENSOR_MAP_SWIZZLE_128B, CU_TENSOR_MAP_L2_PROMOTION_NONE, CU_TENSOR_MAP_FLOAT_OOB_FILL_NONE);
}
void map_act(EncodeFn fn, CUtensorMap* m, const void* p, int rows, int cols, int box_rows) {
    encode3(fn, m, p, cols, rows, 1, (uint64_t)cols * 2, (uint64_t)cols * rows * 2, 64, box_rows, 1);
}
void map_wgt(EncodeFn fn, CUtensorMap* m, const void* p, int K, int N) {
    encode3(fn, m, p, 64, K, N / 64, (uint64_t)N * 2, 128, 64, 64, 2);
}

void build_schedule(Params& p) {
    int n = 0;
    auto add = [&](int type, int col, int row) { p.items[n++] = (uint16_t)(type << 13 | col << 4 | row); };
    int beta = 26, tail = 32, late = 6, early = 8, epos = 100;
    int order[16] = {6, 7, 8, 9, 10, 11, 12, 13, 14, 15, 5, 4, 3, 2, 1, 0};
    const char* plans = "xxcccccx,xxcccccx,xxxxx,xxcxlxx,xxlcclxcc,xxlcccccc,xxlxlccccc,xxlxlxccc";
    const char* pos[8];
    int len[8] = {}, start[8] = {};
    for (int s = 0; s < 8; s++) { pos[s] = plans; while (*plans && *plans++ != ',') {} }
    for (int i = 0; i < 160; i++) p.plan[i / 16][i % 16] = T_END << 13;
    for (int nx = 0, nc = 3, nl = 0; nx + nc + nl < 28 + 32 + 8;) {
        int s = -1;
        for (int i = 0; i < 8; i++) if (*pos[i] > ',' && (s < 0 || start[i] < start[s])) s = i;
        const char kind = *pos[s]++;
        int it;
        if (kind == 'x') { it = nx < 12 ? T_B << 13 | (nx % 3 * 4 + nx / 3) << 4 : T_Q << 13 | (nx - 12) << 4; nx++; }
        else if (kind == 'c') { it = (T_K + (nc & 1)) << 13 | nc / 2 << 4; nc++; }
        else { it = T_LOCAL << 13 | nl / 2 << 4 | (nl & 1); nl++; }
        p.plan[s][len[s]++] = (uint16_t)it;
        start[s] += kind == 'x' ? 48 : kind == 'c' ? 24 : 8;
    }
    for (int i = 0; i < 24; i++) p.plan[8 + i / 12][i % 12] = (uint16_t)((T_K + (i % 3 & 1)) << 13 | i % 3 / 2 << 4 | i / 3);
    const int a0 = n;
    for (int key = 0; key < 4000; key++)
        for (int r = 0; r < 32; r++)
            for (int j = 7; j >= 0; j--)
                if ((j ? (7 - j) * 40 + r * beta : 3999) == key) add(T_ATTN, 2 * order[r >> 1] + (r & 1), j);
    int t0 = n;
    for (int work = 0; work < 32 * 136 * tail / 100;) work += 4 * (p.items[--t0] & 15) + 3;
    for (int i = t0 + 1; i < n; i++)
        for (int j = i; j > t0 && (p.items[j] & 15) > (p.items[j - 1] & 15); j--) { const uint16_t t = p.items[j]; p.items[j] = p.items[j - 1]; p.items[j - 1] = t; }
    for (int r = early - 1; r >= 0; r--) {
        const uint16_t t = p.items[n - 32 + early - 1];
        for (int j = n - 32 + early - 1; j > n - epos; j--) p.items[j] = p.items[j - 1];
        p.items[n - epos] = t;
    }
    for (int moved = 0; moved < 2 && late >= 0; moved++)
        for (int i = a0; i < n; i++)
            if (p.items[i] == (T_ATTN << 13 | (2 * order[15] + moved) << 4 | late)) {
                for (int j = i; j + 1 < n; j++) p.items[j] = p.items[j + 1];
                p.items[n - 1] = (uint16_t)(T_ATTN << 13 | (2 * order[15] + moved) << 4 | late);
                break;
            }
    for (int s = 0, lo = 0, hi = WIDE - 1; s < 80; s++) {
        const int r = s / 2, g = r < 8 ? 32 + r : 2 * order[r / 2 - 4] + (r & 1);
        p.ostep[s >= WIDE ? s : r & 1 ? hi-- : lo++] = (uint8_t)(2 * g + (s & 1));
    }
}

void build_params(Params& p, void* const* d_in, void* d_out) {
    void* fnp = nullptr;
    cudaDriverEntryPointQueryResult qr;
    cudaGetDriverEntryPoint("cuTensorMapEncodeTiled", &fnp, cudaEnableDefault, &qr);
    EncodeFn fn = (EncodeFn)fnp;
    void* scr = nullptr;
    cudaGetSymbolAddress(&scr, g_scr);
    map_act(fn, &p.m[M_X], d_in[0], SEQ, 1024, 128);
    map_act(fn, &p.m[M_C], d_in[1], SEQ, 512, 128);
    map_wgt(fn, &p.m[M_WQ], d_in[2], 1024, 4096);
    map_wgt(fn, &p.m[M_WUK], d_in[3], 512, 4096);
    map_wgt(fn, &p.m[M_WUV], d_in[4], 512, 4096);
    map_wgt(fn, &p.m[M_WO], d_in[5], 4096, 1024);
    map_wgt(fn, &p.m[M_WQKV], d_in[7], 1024, 3072);
    map_wgt(fn, &p.m[M_WOB], d_in[8], 1024, 1024);
    encode3(fn, &p.m[M_SCR_LD], scr, 128, SEQ, G_TOTAL, 256, (uint64_t)SEQ * 256, 64, 128, 1);
    encode3(fn, &p.m[M_SCR_LOC], scr, 256, SEQ / 2, G_TOTAL, 512, (uint64_t)SEQ * 256, 64, 72, 1);
    encode3(fn, &p.m[M_SCR_LOQ], scr, 256, SEQ / 2, G_TOTAL, 512, (uint64_t)SEQ * 256, 64, 64, 1);
    encode3(fn, &p.m[M_SCR_ST], scr, 128, SEQ, G_TOTAL, 256, (uint64_t)SEQ * 256, 64, 64, 1);
    p.x = (const __nv_bfloat16*)d_in[0];
    p.gate_w = (const __nv_bfloat16*)d_in[9];
    p.zero = 0;
    p.wo = (const char*)d_in[5];
    p.out = (__nv_bfloat16*)d_out;
    build_schedule(p);
}

}

extern "C" void kernel_launch(void* const* d_in, const int* in_sizes, int n_in, void* d_out, int out_size) {
    (void)in_sizes; (void)n_in; (void)out_size;
    Params p;
    build_params(p, d_in, d_out);
    cudaFuncSetAttribute(fused_kernel, cudaFuncAttributeMaxDynamicSharedMemorySize, SM_TOTAL);
    fused_kernel<<<NCTA, 384, SM_TOTAL>>>(p);
}
```

```cpp
#include <cuda_runtime.h>
#include <cuda_bf16.h>
#include <cuda.h>
#include <stddef.h>
#include <stdint.h>
#include <type_traits>

namespace {

constexpr int SEQ = 2048;
constexpr int G_Q = 0, G_K = 32, G_V = 64, G_B = 96, G_CTX = G_Q, G_LOC = G_B, G_TOTAL = 120;

__device__ __align__(1024) __nv_bfloat16 g_scr[(size_t)G_TOTAL * SEQ * 128];
__device__ __align__(128) float g_gate[SEQ];

__device__ __forceinline__ uint32_t smem_u32(const void* p) { return (uint32_t)__cvta_generic_to_shared(p); }
__device__ __forceinline__ bool elect_one() {
    uint32_t p;
    asm volatile("{\n.reg .pred P;\nelect.sync _|P, 0xffffffff;\nselp.u32 %0, 1, 0, P;\n}\n" : "=r"(p));
    return p != 0;
}
__device__ __forceinline__ void mbar_init(uint32_t bar, uint32_t count) {
    asm volatile("mbarrier.init.shared::cta.b64 [%0], %1;" :: "r"(bar), "r"(count) : "memory");
}
__device__ __forceinline__ uint32_t cluster_rank() { uint32_t r; asm("mov.u32 %0, %%cluster_ctarank;" : "=r"(r)); return r; }
__device__ __forceinline__ uint32_t map_cta(uint32_t addr, uint32_t cta) {
    uint32_t r; asm("mapa.shared::cluster.u32 %0, %1, %2;" : "=r"(r) : "r"(addr), "r"(cta)); return r;
}
__device__ __forceinline__ void mbar_arrive_cluster_if(bool pred, uint32_t cluster_bar) {
    asm volatile("{\n.reg .pred P;\nsetp.ne.u32 P, %1, 0;\n@P mbarrier.arrive.shared::cluster.b64 _, [%0];\n}\n"
                 :: "r"(cluster_bar), "r"((uint32_t)pred) : "memory");
}
__device__ __forceinline__ void mbar_arrive_cluster_n_if(bool pred, uint32_t cluster_bar, uint32_t count) {
    asm volatile("{\n.reg .pred P;\nsetp.ne.u32 P, %1, 0;\n@P mbarrier.arrive.shared::cluster.b64 _, [%0], %2;\n}\n"
                 :: "r"(cluster_bar), "r"((uint32_t)pred), "r"(count) : "memory");
}
__device__ __forceinline__ void mbar_arrive_if(bool pred, uint32_t bar) {
    asm volatile("{\n.reg .pred P;\nsetp.ne.u32 P, %1, 0;\n@P mbarrier.arrive.shared::cta.b64 _, [%0];\n}\n"
                 :: "r"(bar), "r"((uint32_t)pred) : "memory");
}
__device__ __forceinline__ bool mbar_test(uint32_t bar, uint32_t parity) {
    uint32_t ok;
    asm volatile("{\n.reg .pred P;\nmbarrier.test_wait.parity.shared::cta.b64 P, [%1], %2;\nselp.u32 %0, 1, 0, P;\n}\n"
                 : "=r"(ok) : "r"(bar), "r"(parity) : "memory");
    return ok != 0;
}
__device__ __forceinline__ void mbar_wait(uint32_t bar, uint32_t parity) {
    asm volatile("{\n.reg .pred P;\n.reg .u32 c;\n"
                 "mov.u32 c, 0;\n"
                 "SPIN:\n"
                 "mbarrier.try_wait.parity.shared::cta.b64 P, [%0], %1;\n"
                 "@P bra DONE;\n"
                 "add.u32 c, c, 1;\n"
                 "setp.lt.u32 P, c, 4194304;\n"
                 "@P bra SPIN;\n"
                 "trap;\n"
                 "DONE:\n}\n" :: "r"(bar), "r"(parity) : "memory");
}
__device__ __forceinline__ void mbar_spin(uint32_t bar, uint32_t parity) {
    asm volatile("{\n.reg .pred P;\n"
                 "SPIN:\n"
                 "mbarrier.try_wait.parity.shared::cta.b64 P, [%0], %1;\n"
                 "@!P bra SPIN;\n}\n" :: "r"(bar), "r"(parity) : "memory");
}
__device__ __forceinline__ void bar_sync(int id, int n) { asm volatile("bar.sync %0, %1;" :: "r"(id), "r"(n) : "memory"); }
__device__ __forceinline__ void bar_arrive(int id, int n) { asm volatile("bar.arrive %0, %1;" :: "r"(id), "r"(n) : "memory"); }
__device__ __forceinline__ void fence_proxy_async_smem() { asm volatile("fence.proxy.async.shared::cta;" ::: "memory"); }
__device__ __forceinline__ void warp_expect_tx(uint32_t bar, uint32_t bytes) {
    asm volatile("{\n.reg .pred P;\nelect.sync _|P, 0xffffffff;\n@P mbarrier.arrive.expect_tx.shared::cta.b64 _, [%0], %1;\n}\n"
                 :: "r"(bar), "r"(bytes) : "memory");
}
constexpr uint64_t EVICT_FIRST = 0x12F0000000000000ull;
__device__ __forceinline__ void warp_tma_load(uint32_t dst, const CUtensorMap* map, uint32_t bar, int c0, int c1, int c2, bool stream) {
    if (stream)
        asm volatile("{\n.reg .pred P;\nelect.sync _|P, 0xffffffff;\n"
                     "@P cp.async.bulk.tensor.3d.shared::cluster.global.mbarrier::complete_tx::bytes.L2::cache_hint"
                     " [%0], [%1, {%3, %4, %5}], [%2], %6;\n}\n"
                     :: "r"(dst), "l"(map), "r"(bar), "r"(c0), "r"(c1), "r"(c2), "l"(EVICT_FIRST) : "memory");
    else
        asm volatile("{\n.reg .pred P;\nelect.sync _|P, 0xffffffff;\n"
                     "@P cp.async.bulk.tensor.3d.shared::cluster.global.mbarrier::complete_tx::bytes [%0], [%1, {%3, %4, %5}], [%2];\n}\n"
                     :: "r"(dst), "l"(map), "r"(bar), "r"(c0), "r"(c1), "r"(c2) : "memory");
}
__device__ __forceinline__ void warp_tma_load_pair(uint32_t dst, const CUtensorMap* map, uint32_t bar, int c0, int c1, int c2, bool stream) {
    if (stream)
        asm volatile("{\n.reg .pred P;\nelect.sync _|P, 0xffffffff;\n"
                     "@P cp.async.bulk.tensor.3d.shared::cluster.global.mbarrier::complete_tx::bytes.multicast::cluster.L2::cache_hint"
                     " [%0], [%1, {%3, %4, %5}], [%2], %6, %7;\n}\n"
                     :: "r"(dst), "l"(map), "r"(bar), "r"(c0), "r"(c1), "r"(c2), "h"((uint16_t)3), "l"(EVICT_FIRST) : "memory");
    else
        asm volatile("{\n.reg .pred P;\nelect.sync _|P, 0xffffffff;\n"
                     "@P cp.async.bulk.tensor.3d.shared::cluster.global.mbarrier::complete_tx::bytes.multicast::cluster"
                     " [%0], [%1, {%3, %4, %5}], [%2], %6;\n}\n"
                     :: "r"(dst), "l"(map), "r"(bar), "r"(c0), "r"(c1), "r"(c2), "h"((uint16_t)3) : "memory");
}
__device__ __forceinline__ void warp_bulk_load(uint32_t dst, const void* src, uint32_t bytes, uint32_t bar) {
    asm volatile("{\n.reg .pred P;\nelect.sync _|P, 0xffffffff;\n"
                 "@P cp.async.bulk.shared::cluster.global.mbarrier::complete_tx::bytes [%0], [%1], %2, [%3];\n}\n"
                 :: "r"(dst), "l"(src), "r"(bytes), "r"(bar) : "memory");
}
__device__ __forceinline__ void warp_tma_store(const CUtensorMap* map, uint32_t src, int c0, int c1, int c2, bool stream) {
    if (stream)
        asm volatile("{\n.reg .pred P;\nelect.sync _|P, 0xffffffff;\n"
                     "@P cp.async.bulk.tensor.3d.global.shared::cta.bulk_group.L2::cache_hint [%0, {%2, %3, %4}], [%1], %5;\n}\n"
                     :: "l"(map), "r"(src), "r"(c0), "r"(c1), "r"(c2), "l"(EVICT_FIRST) : "memory");
    else
        asm volatile("{\n.reg .pred P;\nelect.sync _|P, 0xffffffff;\n"
                     "@P cp.async.bulk.tensor.3d.global.shared::cta.bulk_group [%0, {%2, %3, %4}], [%1];\n}\n"
                     :: "l"(map), "r"(src), "r"(c0), "r"(c1), "r"(c2) : "memory");
}
__device__ __forceinline__ void warp_tma_add(const CUtensorMap* map, uint32_t src, int c0, int c1, int c2) {
    asm volatile("{\n.reg .pred P;\nelect.sync _|P, 0xffffffff;\n"
                 "@P cp.reduce.async.bulk.tensor.3d.global.shared::cta.add.tile.bulk_group [%0, {%2, %3, %4}], [%1];\n}\n"
                 :: "l"(map), "r"(src), "r"(c0), "r"(c1), "r"(c2) : "memory");
}
__device__ __forceinline__ void warp_bulk_store(void* dst, uint32_t src, uint32_t bytes) {
    asm volatile("{\n.reg .pred P;\nelect.sync _|P, 0xffffffff;\n"
                 "@P cp.async.bulk.global.shared::cta.bulk_group [%0], [%1], %2;\n}\n" :: "l"(dst), "r"(src), "r"(bytes) : "memory");
}
__device__ __forceinline__ void warp_prefetch(const void* src, uint32_t bytes) {
    asm volatile("{\n.reg .pred P;\nelect.sync _|P, 0xffffffff;\n@P cp.async.bulk.prefetch.L2.global [%0], %1;\n}\n" :: "l"(src), "r"(bytes) : "memory");
}
__device__ __forceinline__ void bulk_commit() { asm volatile("cp.async.bulk.commit_group;" ::: "memory"); }
template <int N> __device__ __forceinline__ void bulk_wait_read() { asm volatile("cp.async.bulk.wait_group.read %0;" :: "n"(N) : "memory"); }
template <int N> __device__ __forceinline__ void bulk_wait() { asm volatile("cp.async.bulk.wait_group %0;" :: "n"(N) : "memory"); }
__device__ __forceinline__ void wgmma_fence() { asm volatile("wgmma.fence.sync.aligned;" ::: "memory"); }
__device__ __forceinline__ void wgmma_commit() { asm volatile("wgmma.commit_group.sync.aligned;" ::: "memory"); }
template <int N> __device__ __forceinline__ void wgmma_wait() { asm volatile("wgmma.wait_group.sync.aligned %0;" :: "n"(N) : "memory"); }
template <int N> __device__ __forceinline__ void fence_regs(float (&d)[N]) {
#pragma unroll
    for (int i = 0; i < N; i++) asm volatile("" : "+f"(d[i]) :: "memory");
}
template <int N> __device__ __forceinline__ void fence_regs(uint32_t (&d)[N]) {
#pragma unroll
    for (int i = 0; i < N; i++) asm volatile("" : "+r"(d[i]) :: "memory");
}
template <int N> __device__ __forceinline__ void reg_dec() { asm volatile("setmaxnreg.dec.sync.aligned.u32 %0;" :: "n"(N)); }
template <int N> __device__ __forceinline__ void reg_inc() { asm volatile("setmaxnreg.inc.sync.aligned.u32 %0;" :: "n"(N)); }
__device__ __forceinline__ uint32_t pack_bf16(float lo, float hi) {
    uint32_t r; asm("cvt.rn.bf16x2.f32 %0, %1, %2;" : "=r"(r) : "f"(hi), "f"(lo)); return r;
}
__device__ __forceinline__ void stmatrix_x4(uint32_t addr, uint32_t r0, uint32_t r1, uint32_t r2, uint32_t r3) {
    asm volatile("stmatrix.sync.aligned.m8n8.x4.shared.b16 [%0], {%1, %2, %3, %4};"
                 :: "r"(addr), "r"(r0), "r"(r1), "r"(r2), "r"(r3) : "memory");
}
__device__ __forceinline__ float ex2(float x) { float y; asm("ex2.approx.ftz.f32 %0, %1;" : "=f"(y) : "f"(x)); return y; }

constexpr uint32_t DESC_HI = (1024 >> 4) | (1u << 30);
__device__ __forceinline__ uint32_t make_desc(uint32_t addr, uint32_t lbo) {
    uint32_t lo = ((addr & 0x3FFFF) >> 4) | ((lbo >> 4) << 16);
    asm volatile("" : "+r"(lo));
    return lo;
}
__device__ __forceinline__ uint64_t full_desc(uint32_t lo) {
    uint64_t d; asm("mov.b64 %0, {%1, %2};" : "=l"(d) : "r"(lo), "r"(DESC_HI)); return d;
}

__device__ __forceinline__ void wgmma_ss_n256_tb_init(float (&d)[128], uint64_t da, uint64_t db) {
    asm volatile("{\n.reg .pred p;\n"
        "setp.ne.b32 p, 0, 0;\n"
        "wgmma.mma_async.sync.aligned.m64n256k16.f32.bf16.bf16 "
        "{%0, %1, %2, %3, %4, %5, %6, %7, %8, %9, %10, %11, %12, %13, %14, %15, %16, %17, %18, %19, %20, "
        "%21, %22, %23, %24, %25, %26, %27, %28, %29, %30, %31, %32, %33, %34, %35, %36, %37, %38, %39, %40, "
        "%41, %42, %43, %44, %45, %46, %47, %48, %49, %50, %51, %52, %53, %54, %55, %56, %57, %58, %59, %60, "
        "%61, %62, %63, %64, %65, %66, %67, %68, %69, %70, %71, %72, %73, %74, %75, %76, %77, %78, %79, %80, "
        "%81, %82, %83, %84, %85, %86, %87, %88, %89, %90, %91, %92, %93, %94, %95, %96, %97, %98, %99, "
        "%100, %101, %102, %103, %104, %105, %106, %107, %108, %109, %110, %111, %112, %113, %114, %115, "
        "%116, %117, %118, %119, %120, %121, %122, %123, %124, %125, %126, %127},"
        " %128, %129, p, 1, 1, 0, 1;\n}\n"
        : "=f"(d[0]), "=f"(d[1]), "=f"(d[2]), "=f"(d[3]), "=f"(d[4]), "=f"(d[5]), "=f"(d[6]), "=f"(d[7]),
        "=f"(d[8]), "=f"(d[9]), "=f"(d[10]), "=f"(d[11]), "=f"(d[12]), "=f"(d[13]), "=f"(d[14]), "=f"(d[15]),
        "=f"(d[16]), "=f"(d[17]), "=f"(d[18]), "=f"(d[19]), "=f"(d[20]), "=f"(d[21]), "=f"(d[22]),
        "=f"(d[23]), "=f"(d[24]), "=f"(d[25]), "=f"(d[26]), "=f"(d[27]), "=f"(d[28]), "=f"(d[29]),
        "=f"(d[30]), "=f"(d[31]), "=f"(d[32]), "=f"(d[33]), "=f"(d[34]), "=f"(d[35]), "=f"(d[36]),
        "=f"(d[37]), "=f"(d[38]), "=f"(d[39]), "=f"(d[40]), "=f"(d[41]), "=f"(d[42]), "=f"(d[43]),
        "=f"(d[44]), "=f"(d[45]), "=f"(d[46]), "=f"(d[47]), "=f"(d[48]), "=f"(d[49]), "=f"(d[50]),
        "=f"(d[51]), "=f"(d[52]), "=f"(d[53]), "=f"(d[54]), "=f"(d[55]), "=f"(d[56]), "=f"(d[57]),
        "=f"(d[58]), "=f"(d[59]), "=f"(d[60]), "=f"(d[61]), "=f"(d[62]), "=f"(d[63]), "=f"(d[64]),
        "=f"(d[65]), "=f"(d[66]), "=f"(d[67]), "=f"(d[68]), "=f"(d[69]), "=f"(d[70]), "=f"(d[71]),
        "=f"(d[72]), "=f"(d[73]), "=f"(d[74]), "=f"(d[75]), "=f"(d[76]), "=f"(d[77]), "=f"(d[78]),
        "=f"(d[79]), "=f"(d[80]), "=f"(d[81]), "=f"(d[82]), "=f"(d[83]), "=f"(d[84]), "=f"(d[85]),
        "=f"(d[86]), "=f"(d[87]), "=f"(d[88]), "=f"(d[89]), "=f"(d[90]), "=f"(d[91]), "=f"(d[92]),
        "=f"(d[93]), "=f"(d[94]), "=f"(d[95]), "=f"(d[96]), "=f"(d[97]), "=f"(d[98]), "=f"(d[99]),
        "=f"(d[100]), "=f"(d[101]), "=f"(d[102]), "=f"(d[103]), "=f"(d[104]), "=f"(d[105]), "=f"(d[106]),
        "=f"(d[107]), "=f"(d[108]), "=f"(d[109]), "=f"(d[110]), "=f"(d[111]), "=f"(d[112]), "=f"(d[113]),
        "=f"(d[114]), "=f"(d[115]), "=f"(d[116]), "=f"(d[117]), "=f"(d[118]), "=f"(d[119]), "=f"(d[120]),
        "=f"(d[121]), "=f"(d[122]), "=f"(d[123]), "=f"(d[124]), "=f"(d[125]), "=f"(d[126]), "=f"(d[127])
        : "l"(da), "l"(db));
}
__device__ __forceinline__ void wgmma_ss_n256_tb(float (&d)[128], uint64_t da, uint64_t db, int scale_d) {
    asm volatile("{\n.reg .pred p;\n"
        "setp.ne.b32 p, %130, 0;\n"
        "wgmma.mma_async.sync.aligned.m64n256k16.f32.bf16.bf16 "
        "{%0, %1, %2, %3, %4, %5, %6, %7, %8, %9, %10, %11, %12, %13, %14, %15, %16, %17, %18, %19, %20, "
        "%21, %22, %23, %24, %25, %26, %27, %28, %29, %30, %31, %32, %33, %34, %35, %36, %37, %38, %39, %40, "
        "%41, %42, %43, %44, %45, %46, %47, %48, %49, %50, %51, %52, %53, %54, %55, %56, %57, %58, %59, %60, "
        "%61, %62, %63, %64, %65, %66, %67, %68, %69, %70, %71, %72, %73, %74, %75, %76, %77, %78, %79, %80, "
        "%81, %82, %83, %84, %85, %86, %87, %88, %89, %90, %91, %92, %93, %94, %95, %96, %97, %98, %99, "
        "%100, %101, %102, %103, %104, %105, %106, %107, %108, %109, %110, %111, %112, %113, %114, %115, "
        "%116, %117, %118, %119, %120, %121, %122, %123, %124, %125, %126, %127},"
        " %128, %129, p, 1, 1, 0, 1;\n}\n"
        : "+f"(d[0]), "+f"(d[1]), "+f"(d[2]), "+f"(d[3]), "+f"(d[4]), "+f"(d[5]), "+f"(d[6]), "+f"(d[7]),
        "+f"(d[8]), "+f"(d[9]), "+f"(d[10]), "+f"(d[11]), "+f"(d[12]), "+f"(d[13]), "+f"(d[14]), "+f"(d[15]),
        "+f"(d[16]), "+f"(d[17]), "+f"(d[18]), "+f"(d[19]), "+f"(d[20]), "+f"(d[21]), "+f"(d[22]),
        "+f"(d[23]), "+f"(d[24]), "+f"(d[25]), "+f"(d[26]), "+f"(d[27]), "+f"(d[28]), "+f"(d[29]),
        "+f"(d[30]), "+f"(d[31]), "+f"(d[32]), "+f"(d[33]), "+f"(d[34]), "+f"(d[35]), "+f"(d[36]),
        "+f"(d[37]), "+f"(d[38]), "+f"(d[39]), "+f"(d[40]), "+f"(d[41]), "+f"(d[42]), "+f"(d[43]),
        "+f"(d[44]), "+f"(d[45]), "+f"(d[46]), "+f"(d[47]), "+f"(d[48]), "+f"(d[49]), "+f"(d[50]),
        "+f"(d[51]), "+f"(d[52]), "+f"(d[53]), "+f"(d[54]), "+f"(d[55]), "+f"(d[56]), "+f"(d[57]),
        "+f"(d[58]), "+f"(d[59]), "+f"(d[60]), "+f"(d[61]), "+f"(d[62]), "+f"(d[63]), "+f"(d[64]),
        "+f"(d[65]), "+f"(d[66]), "+f"(d[67]), "+f"(d[68]), "+f"(d[69]), "+f"(d[70]), "+f"(d[71]),
        "+f"(d[72]), "+f"(d[73]), "+f"(d[74]), "+f"(d[75]), "+f"(d[76]), "+f"(d[77]), "+f"(d[78]),
        "+f"(d[79]), "+f"(d[80]), "+f"(d[81]), "+f"(d[82]), "+f"(d[83]), "+f"(d[84]), "+f"(d[85]),
        "+f"(d[86]), "+f"(d[87]), "+f"(d[88]), "+f"(d[89]), "+f"(d[90]), "+f"(d[91]), "+f"(d[92]),
        "+f"(d[93]), "+f"(d[94]), "+f"(d[95]), "+f"(d[96]), "+f"(d[97]), "+f"(d[98]), "+f"(d[99]),
        "+f"(d[100]), "+f"(d[101]), "+f"(d[102]), "+f"(d[103]), "+f"(d[104]), "+f"(d[105]), "+f"(d[106]),
        "+f"(d[107]), "+f"(d[108]), "+f"(d[109]), "+f"(d[110]), "+f"(d[111]), "+f"(d[112]), "+f"(d[113]),
        "+f"(d[114]), "+f"(d[115]), "+f"(d[116]), "+f"(d[117]), "+f"(d[118]), "+f"(d[119]), "+f"(d[120]),
        "+f"(d[121]), "+f"(d[122]), "+f"(d[123]), "+f"(d[124]), "+f"(d[125]), "+f"(d[126]), "+f"(d[127])
        : "l"(da), "l"(db), "r"(scale_d));
}
__device__ __forceinline__ void wgmma_ss_n128(float (&d)[64], uint64_t da, uint64_t db, int scale_d) {
    asm volatile("{\n.reg .pred p;\n"
        "setp.ne.b32 p, %66, 0;\n"
        "wgmma.mma_async.sync.aligned.m64n128k16.f32.bf16.bf16 "
        "{%0, %1, %2, %3, %4, %5, %6, %7, %8, %9, %10, %11, %12, %13, %14, %15, %16, %17, %18, %19, %20, "
        "%21, %22, %23, %24, %25, %26, %27, %28, %29, %30, %31, %32, %33, %34, %35, %36, %37, %38, %39, %40, "
        "%41, %42, %43, %44, %45, %46, %47, %48, %49, %50, %51, %52, %53, %54, %55, %56, %57, %58, %59, %60, "
        "%61, %62, %63},"
        " %64, %65, p, 1, 1, 0, 0;\n}\n"
        : "+f"(d[0]), "+f"(d[1]), "+f"(d[2]), "+f"(d[3]), "+f"(d[4]), "+f"(d[5]), "+f"(d[6]), "+f"(d[7]),
        "+f"(d[8]), "+f"(d[9]), "+f"(d[10]), "+f"(d[11]), "+f"(d[12]), "+f"(d[13]), "+f"(d[14]), "+f"(d[15]),
        "+f"(d[16]), "+f"(d[17]), "+f"(d[18]), "+f"(d[19]), "+f"(d[20]), "+f"(d[21]), "+f"(d[22]),
        "+f"(d[23]), "+f"(d[24]), "+f"(d[25]), "+f"(d[26]), "+f"(d[27]), "+f"(d[28]), "+f"(d[29]),
        "+f"(d[30]), "+f"(d[31]), "+f"(d[32]), "+f"(d[33]), "+f"(d[34]), "+f"(d[35]), "+f"(d[36]),
        "+f"(d[37]), "+f"(d[38]), "+f"(d[39]), "+f"(d[40]), "+f"(d[41]), "+f"(d[42]), "+f"(d[43]),
        "+f"(d[44]), "+f"(d[45]), "+f"(d[46]), "+f"(d[47]), "+f"(d[48]), "+f"(d[49]), "+f"(d[50]),
        "+f"(d[51]), "+f"(d[52]), "+f"(d[53]), "+f"(d[54]), "+f"(d[55]), "+f"(d[56]), "+f"(d[57]),
        "+f"(d[58]), "+f"(d[59]), "+f"(d[60]), "+f"(d[61]), "+f"(d[62]), "+f"(d[63])
        : "l"(da), "l"(db), "r"(scale_d));
}
__device__ __forceinline__ void wgmma_rs_n128_tb(float (&d)[64], uint32_t a0, uint32_t a1, uint32_t a2, uint32_t a3, uint64_t db, int scale_d) {
    asm volatile("{\n.reg .pred p;\n"
        "setp.ne.b32 p, %69, 0;\n"
        "wgmma.mma_async.sync.aligned.m64n128k16.f32.bf16.bf16 "
        "{%0, %1, %2, %3, %4, %5, %6, %7, %8, %9, %10, %11, %12, %13, %14, %15, %16, %17, %18, %19, %20, "
        "%21, %22, %23, %24, %25, %26, %27, %28, %29, %30, %31, %32, %33, %34, %35, %36, %37, %38, %39, %40, "
        "%41, %42, %43, %44, %45, %46, %47, %48, %49, %50, %51, %52, %53, %54, %55, %56, %57, %58, %59, %60, "
        "%61, %62, %63},"
        " {%64, %65, %66, %67}, %68, p, 1, 1, 1;\n}\n"
        : "+f"(d[0]), "+f"(d[1]), "+f"(d[2]), "+f"(d[3]), "+f"(d[4]), "+f"(d[5]), "+f"(d[6]), "+f"(d[7]),
        "+f"(d[8]), "+f"(d[9]), "+f"(d[10]), "+f"(d[11]), "+f"(d[12]), "+f"(d[13]), "+f"(d[14]), "+f"(d[15]),
        "+f"(d[16]), "+f"(d[17]), "+f"(d[18]), "+f"(d[19]), "+f"(d[20]), "+f"(d[21]), "+f"(d[22]),
        "+f"(d[23]), "+f"(d[24]), "+f"(d[25]), "+f"(d[26]), "+f"(d[27]), "+f"(d[28]), "+f"(d[29]),
        "+f"(d[30]), "+f"(d[31]), "+f"(d[32]), "+f"(d[33]), "+f"(d[34]), "+f"(d[35]), "+f"(d[36]),
        "+f"(d[37]), "+f"(d[38]), "+f"(d[39]), "+f"(d[40]), "+f"(d[41]), "+f"(d[42]), "+f"(d[43]),
        "+f"(d[44]), "+f"(d[45]), "+f"(d[46]), "+f"(d[47]), "+f"(d[48]), "+f"(d[49]), "+f"(d[50]),
        "+f"(d[51]), "+f"(d[52]), "+f"(d[53]), "+f"(d[54]), "+f"(d[55]), "+f"(d[56]), "+f"(d[57]),
        "+f"(d[58]), "+f"(d[59]), "+f"(d[60]), "+f"(d[61]), "+f"(d[62]), "+f"(d[63])
        : "r"(a0), "r"(a1), "r"(a2), "r"(a3), "l"(db), "r"(scale_d));
}
__device__ __forceinline__ void wgmma_ss_n128_tb_init(float (&d)[64], uint64_t da, uint64_t db) {
    asm volatile("{\n.reg .pred p;\n"
        "setp.ne.b32 p, 0, 0;\n"
        "wgmma.mma_async.sync.aligned.m64n128k16.f32.bf16.bf16 "
        "{%0, %1, %2, %3, %4, %5, %6, %7, %8, %9, %10, %11, %12, %13, %14, %15, %16, %17, %18, %19, %20, "
        "%21, %22, %23, %24, %25, %26, %27, %28, %29, %30, %31, %32, %33, %34, %35, %36, %37, %38, %39, %40, "
        "%41, %42, %43, %44, %45, %46, %47, %48, %49, %50, %51, %52, %53, %54, %55, %56, %57, %58, %59, %60, "
        "%61, %62, %63},"
        " %64, %65, p, 1, 1, 0, 1;\n}\n"
        : "=f"(d[0]), "=f"(d[1]), "=f"(d[2]), "=f"(d[3]), "=f"(d[4]), "=f"(d[5]), "=f"(d[6]), "=f"(d[7]),
        "=f"(d[8]), "=f"(d[9]), "=f"(d[10]), "=f"(d[11]), "=f"(d[12]), "=f"(d[13]), "=f"(d[14]), "=f"(d[15]),
        "=f"(d[16]), "=f"(d[17]), "=f"(d[18]), "=f"(d[19]), "=f"(d[20]), "=f"(d[21]), "=f"(d[22]),
        "=f"(d[23]), "=f"(d[24]), "=f"(d[25]), "=f"(d[26]), "=f"(d[27]), "=f"(d[28]), "=f"(d[29]),
        "=f"(d[30]), "=f"(d[31]), "=f"(d[32]), "=f"(d[33]), "=f"(d[34]), "=f"(d[35]), "=f"(d[36]),
        "=f"(d[37]), "=f"(d[38]), "=f"(d[39]), "=f"(d[40]), "=f"(d[41]), "=f"(d[42]), "=f"(d[43]),
        "=f"(d[44]), "=f"(d[45]), "=f"(d[46]), "=f"(d[47]), "=f"(d[48]), "=f"(d[49]), "=f"(d[50]),
        "=f"(d[51]), "=f"(d[52]), "=f"(d[53]), "=f"(d[54]), "=f"(d[55]), "=f"(d[56]), "=f"(d[57]),
        "=f"(d[58]), "=f"(d[59]), "=f"(d[60]), "=f"(d[61]), "=f"(d[62]), "=f"(d[63])
        : "l"(da), "l"(db));
}
__device__ __forceinline__ void wgmma_ss_n128_tb(float (&d)[64], uint64_t da, uint64_t db, int scale_d) {
    asm volatile("{\n.reg .pred p;\n"
        "setp.ne.b32 p, %66, 0;\n"
        "wgmma.mma_async.sync.aligned.m64n128k16.f32.bf16.bf16 "
        "{%0, %1, %2, %3, %4, %5, %6, %7, %8, %9, %10, %11, %12, %13, %14, %15, %16, %17, %18, %19, %20, "
        "%21, %22, %23, %24, %25, %26, %27, %28, %29, %30, %31, %32, %33, %34, %35, %36, %37, %38, %39, %40, "
        "%41, %42, %43, %44, %45, %46, %47, %48, %49, %50, %51, %52, %53, %54, %55, %56, %57, %58, %59, %60, "
        "%61, %62, %63},"
        " %64, %65, p, 1, 1, 0, 1;\n}\n"
        : "+f"(d[0]), "+f"(d[1]), "+f"(d[2]), "+f"(d[3]), "+f"(d[4]), "+f"(d[5]), "+f"(d[6]), "+f"(d[7]),
        "+f"(d[8]), "+f"(d[9]), "+f"(d[10]), "+f"(d[11]), "+f"(d[12]), "+f"(d[13]), "+f"(d[14]), "+f"(d[15]),
        "+f"(d[16]), "+f"(d[17]), "+f"(d[18]), "+f"(d[19]), "+f"(d[20]), "+f"(d[21]), "+f"(d[22]),
        "+f"(d[23]), "+f"(d[24]), "+f"(d[25]), "+f"(d[26]), "+f"(d[27]), "+f"(d[28]), "+f"(d[29]),
        "+f"(d[30]), "+f"(d[31]), "+f"(d[32]), "+f"(d[33]), "+f"(d[34]), "+f"(d[35]), "+f"(d[36]),
        "+f"(d[37]), "+f"(d[38]), "+f"(d[39]), "+f"(d[40]), "+f"(d[41]), "+f"(d[42]), "+f"(d[43]),
        "+f"(d[44]), "+f"(d[45]), "+f"(d[46]), "+f"(d[47]), "+f"(d[48]), "+f"(d[49]), "+f"(d[50]),
        "+f"(d[51]), "+f"(d[52]), "+f"(d[53]), "+f"(d[54]), "+f"(d[55]), "+f"(d[56]), "+f"(d[57]),
        "+f"(d[58]), "+f"(d[59]), "+f"(d[60]), "+f"(d[61]), "+f"(d[62]), "+f"(d[63])
        : "l"(da), "l"(db), "r"(scale_d));
}

enum { M_X = 0, M_C, M_WQ, M_WUK, M_WUV, M_WQKV, M_WO, M_WOB, M_SCR_LD, M_SCR_LOC, M_SCR_LOQ, M_SCR_ST, M_OUT, M_COUNT };
enum { T_Q = 0, T_K, T_V, T_B, T_OUT, T_LOCAL, T_ATTN, T_END };
constexpr int NCTA = 132;
constexpr int NITEMS = 256;
constexpr int TRIPLES = 2, WIDE = 80 - 3 * TRIPLES;
struct Params {
    CUtensorMap m[M_COUNT];
    const __nv_bfloat16* x;
    const __nv_bfloat16* gate_w;
    const char* wo;
    __nv_bfloat16* out;
    uint32_t zero;
    uint16_t plan[10][16];
    uint16_t items[NITEMS];
    uint8_t ostep[80];
};
__device__ __forceinline__ int item_type(int it) { return it >> 13; }
__device__ __forceinline__ int item_row(int it) { return it & 15; }
__device__ __forceinline__ int item_col(int it) { return (it >> 4) & 31; }
__device__ __forceinline__ int item_asc(int it) { return (it >> 9) & 1; }
constexpr int ITEM_READY = 1 << 10;

struct __align__(128) Sync {
    unsigned long long count[4];
    __align__(128) unsigned long long ctx[16];
    unsigned next, next_out, done;
    __align__(128) unsigned step[32][2];
    unsigned split[32];
};
__device__ Sync g_sync;

constexpr uint32_t GST_BYTES = 49152, SM_KV = 65536, SM_STAGING = 196608, SM_BARS = SM_STAGING + 32768;
constexpr uint32_t B_GFULL = 0, B_GEMPTY = 32, B_AFULL = 64, B_AEMPTY = 112, B_SFULL = 160, B_SEMPTY = 192,
                   B_IFULL = 224, B_IEMPTY = 288, B_XFREE = 352, B_WANT = 384, B_MEET = 392, B_HALF = 416,
                   SM_ORDY = 448, SM_QUEUE = 456, B_ALT = 488, B_QFREE = 504, SM_GATE = 512, SM_TOTAL = SM_BARS + 1536;
constexpr int QDEPTH = 8;
constexpr int FIRST_PAIR = 6;
#define KM 16
#define KFE 20
constexpr int K_MEET = KM, K_SPLIT = 30;
constexpr int K_FETCH = KFE;
constexpr uint32_t LOC_PLANE = 72 * 128;
constexpr float LOC_SCALE = 0.17677669529663687f * 1.4426950408889634f;
constexpr float SUM_LIMIT = 1152921504606846976.f;
constexpr float REF_RANGE = 32.f;

__device__ __forceinline__ unsigned ld_acquire(const unsigned* p) {
    unsigned v; asm volatile("ld.acquire.gpu.global.u32 %0, [%1];" : "=r"(v) : "l"(p) : "memory"); return v;
}
__device__ __forceinline__ unsigned long long ld_acquire(const unsigned long long* p) {
    unsigned long long v; asm volatile("ld.acquire.gpu.global.u64 %0, [%1];" : "=l"(v) : "l"(p) : "memory"); return v;
}
__device__ __forceinline__ void spin_guard(unsigned& n) {
    asm volatile("{\n.reg .pred P;\nadd.u32 %0, %0, 1;\nsetp.gt.u32 P, %0, 16777216;\n@P trap;\n}\n" : "+r"(n));
    if (n > 1) __nanosleep(100);
}
__device__ __forceinline__ void red_add(unsigned long long* p, unsigned long long v) {
    asm volatile("red.release.gpu.global.add.u64 [%0], %1;" :: "l"(p), "l"(v) : "memory");
}
__device__ __forceinline__ float rcp(float x) { float y; asm("rcp.approx.ftz.f32 %0, %1;" : "=f"(y) : "f"(x)); return y; }
__device__ __forceinline__ float lds_f32(uint32_t addr) {
    float v; asm volatile("ld.shared.f32 %0, [%1];" : "=f"(v) : "r"(addr) : "memory"); return v;
}
__device__ __forceinline__ void ldsm_x4(uint32_t (&r)[4], uint32_t addr) {
    asm volatile("ldmatrix.sync.aligned.m8n8.x4.shared.b16 {%0, %1, %2, %3}, [%4];"
                 : "=r"(r[0]), "=r"(r[1]), "=r"(r[2]), "=r"(r[3]) : "r"(addr) : "memory");
}
__device__ __forceinline__ void ldsm_x4_t(uint32_t (&r)[4], uint32_t addr) {
    asm volatile("ldmatrix.sync.aligned.m8n8.x4.trans.shared.b16 {%0, %1, %2, %3}, [%4];"
                 : "=r"(r[0]), "=r"(r[1]), "=r"(r[2]), "=r"(r[3]) : "r"(addr) : "memory");
}
__device__ __forceinline__ void mma_k16(float (&d)[4], const uint32_t (&a)[4], uint32_t b0, uint32_t b1) {
    asm("mma.sync.aligned.m16n8k16.row.col.f32.bf16.bf16.f32 {%0,%1,%2,%3}, {%4,%5,%6,%7}, {%8,%9}, {%0,%1,%2,%3};"
        : "+f"(d[0]), "+f"(d[1]), "+f"(d[2]), "+f"(d[3]) : "r"(a[0]), "r"(a[1]), "r"(a[2]), "r"(a[3]), "r"(b0), "r"(b1));
}
__device__ __forceinline__ void mma_k16_init(float (&d)[4], const uint32_t (&a)[4], uint32_t b0, uint32_t b1) {
    asm("{\n.reg .f32 z;\nmov.f32 z, 0f00000000;\n"
        "mma.sync.aligned.m16n8k16.row.col.f32.bf16.bf16.f32 {%0,%1,%2,%3}, {%4,%5,%6,%7}, {%8,%9}, {z,z,z,z};\n}\n"
        : "=f"(d[0]), "=f"(d[1]), "=f"(d[2]), "=f"(d[3]) : "r"(a[0]), "r"(a[1]), "r"(a[2]), "r"(a[3]), "r"(b0), "r"(b1));
}
__device__ __forceinline__ void mma_k8(float (&d)[4], uint32_t a0, uint32_t a1, uint32_t b0) {
    asm("mma.sync.aligned.m16n8k8.row.col.f32.bf16.bf16.f32 {%0,%1,%2,%3}, {%4,%5}, {%6}, {%0,%1,%2,%3};"
        : "+f"(d[0]), "+f"(d[1]), "+f"(d[2]), "+f"(d[3]) : "r"(a0), "r"(a1), "r"(b0));
}
template <typename T, int N> __device__ __forceinline__ void zero_regs(T (&d)[N]) {
#pragma unroll
    for (int i = 0; i < N; i++) d[i] = 0;
}
__device__ __forceinline__ float quad_max(float v) {
    v = fmaxf(v, __shfl_xor_sync(0xffffffffu, v, 1));
    return fmaxf(v, __shfl_xor_sync(0xffffffffu, v, 2));
}
__device__ __forceinline__ float quad_sum(float v) {
    v += __shfl_xor_sync(0xffffffffu, v, 1);
    return v + __shfl_xor_sync(0xffffffffu, v, 2);
}

__device__ __forceinline__ void qk_gemm(float (&s)[64], uint32_t q_lo, uint32_t k_lo) {
    const uint64_t dq = full_desc(q_lo), dk = full_desc(k_lo);
    fence_regs(s);
    wgmma_fence();
#pragma unroll
    for (int kk = 0; kk < 8; kk++) {
        const uint32_t o = (kk >> 2) * 1024 + (kk & 3) * 2;
        wgmma_ss_n128(s, dq + o, dk + o, kk != 0);
    }
    wgmma_commit();
}
__device__ __forceinline__ void pv_gemm(float (&o)[64], uint32_t (&p)[32], uint32_t v_lo, int accumulate) {
    const uint64_t dv = full_desc(v_lo);
    fence_regs(o);
    fence_regs(p);
    wgmma_fence();
#pragma unroll
    for (int kk = 0; kk < 8; kk++)
        wgmma_rs_n128_tb(o, p[4 * kk], p[4 * kk + 1], p[4 * kk + 2], p[4 * kk + 3], dv + kk * 128, kk != 0 || accumulate);
    wgmma_commit();
}
__device__ __forceinline__ void row_max(const float (&s)[64], float& x0, float& x1) {
    float z0 = fmaxf(s[0], s[1]), z1 = fmaxf(s[2], s[3]);
    x0 = fmaxf(s[4], s[5]); x1 = fmaxf(s[6], s[7]);
#pragma unroll
    for (int j = 2; j < 16; j += 2) {
        z0 = fmaxf(z0, fmaxf(s[4 * j], s[4 * j + 1]));
        z1 = fmaxf(z1, fmaxf(s[4 * j + 2], s[4 * j + 3]));
        x0 = fmaxf(x0, fmaxf(s[4 * j + 4], s[4 * j + 5]));
        x1 = fmaxf(x1, fmaxf(s[4 * j + 6], s[4 * j + 7]));
    }
    x0 = quad_max(fmaxf(x0, z0)); x1 = quad_max(fmaxf(x1, z1));
}
__device__ __forceinline__ void exp_pack(uint32_t (&p)[32], const float (&s)[64], float& r0, float& r1) {
#pragma unroll
    for (int j = 0; j < 16; j++) {
        const float e0 = ex2(s[4 * j]), e1 = ex2(s[4 * j + 1]), e2 = ex2(s[4 * j + 2]), e3 = ex2(s[4 * j + 3]);
        if (j == 0) { r0 = e0 + e1; r1 = e2 + e3; }
        else { r0 += e0 + e1; r1 += e2 + e3; }
        p[2 * j] = pack_bf16(e0, e1);
        p[2 * j + 1] = pack_bf16(e2, e3);
    }
}
__device__ __forceinline__ void shift_rows(float (&s)[64], float d0, float d1) {
#pragma unroll
    for (int j = 0; j < 16; j++) { s[4 * j] -= d0; s[4 * j + 1] -= d0; s[4 * j + 2] -= d1; s[4 * j + 3] -= d1; }
}
constexpr float MASKED = -3e38f;
template <int J0>
__device__ __forceinline__ void mask_triangle(float (&s)[64], float thr) {
#pragma unroll
    for (int j = 0; j < 16; j++) {
        const float m = __saturatef((float)(8 * (j >> 1) + (j & 1)) - thr);
        const int i = 4 * (J0 + (j >> 1)) + (j & 1);
        s[i] = fmaf(m, MASKED, s[i]);
        if (j < 14) s[i + 6] = fmaf(m, MASKED, s[i + 6]);
    }
}
__device__ __forceinline__ void causal_mask(float (&s)[64], float thr, int wg) {
    asm volatile("" : "+f"(thr));
    if (wg == 0) {
        mask_triangle<0>(s, thr);
#pragma unroll
        for (int j = 32; j < 64; j++) s[j] += MASKED;
    } else {
        mask_triangle<8>(s, thr);
    }
}

__global__ void __cluster_dims__(2, 1, 1) __launch_bounds__(384, 1) fused_kernel(const __grid_constant__ Params prm) {
    extern __shared__ __align__(1024) uint8_t smem[];
    const uint32_t sb = smem_u32(smem), bars = sb + SM_BARS;
    const int warp = __shfl_sync(0xffffffffu, threadIdx.x >> 5, 0), lane = threadIdx.x & 31;

    const uint32_t rank = cluster_rank();
    const uint32_t bars0 = map_cta(bars, 0), bars_peer = map_cta(bars, rank ^ 1);

    auto plan_index = [&]() -> uint32_t {
        uint32_t p = blockIdx.x >> 1;
        asm volatile("" : "+r"(p));
        const uint32_t r = (p - 36) * 37 >> 8;
        return p < 4 ? 60 + p : p < 36 ? (p - 4 & 7) * 8 + (p - 4 >> 3) : p < 64 ? (p - 36 - 7 * r) * 8 + 4 + r : p;
    };
    auto first_item = [&]() -> int {
        const uint32_t pair = plan_index();
        const uint32_t slot = pair & 7, c = slot * 11 >> 5;
        return pair < 64 ? T_B << 13 | (4 * slot - 11 * c) << 4 | (2 * (pair >> 3) + rank) : T_K << 13 | (8 * slot + rank);
    };
    if (warp == 0) {
        if (elect_one()) {
            for (int k = 0; k < 4; k++) mbar_init(bars + B_GFULL + 8 * k, 1);
            asm volatile("fence.mbarrier_init.release.cluster;" ::: "memory");
            fence_proxy_async_smem();
        }
        __syncwarp();
        const int first_it = __shfl_sync(0xffffffffu, first_item(), 0);
        asm volatile("barrier.cluster.arrive.relaxed.aligned;" ::: "memory");
        const CUtensorMap* ma = &prm.m[item_type(first_it) == T_K ? M_C : M_X];
        const CUtensorMap* mb = &prm.m[M_WQ + item_type(first_it)];
#pragma unroll
        for (int k = 0; k < 2; k++) {
            const uint32_t dst = sb + k * GST_BYTES, fb = bars + B_GFULL + 8 * k;
            warp_expect_tx(fb, GST_BYTES);
            warp_tma_load(dst + 16384, mb, fb, 0, k * 64, item_col(first_it) * 4, true);
            warp_tma_load(dst, ma, fb, k * 64, item_row(first_it) * 128, 0, false);
            warp_tma_load(dst + 32768, mb, fb, 0, k * 64, item_col(first_it) * 4 + 2, true);
        }
    }
    if (threadIdx.x == 32) {
        for (int i = 0; i < 4; i++) { mbar_init(bars + B_GEMPTY + 8 * i, 16); mbar_init(bars + B_XFREE + 8 * i, 1); }
        for (int i = 0; i < 6; i++) { mbar_init(bars + B_AFULL + 8 * i, 1); mbar_init(bars + B_AEMPTY + 8 * i, i < 2 ? 8 : 16); }
        for (int i = 0; i < 4; i++) { mbar_init(bars + B_SFULL + 8 * i, 4); mbar_init(bars + B_SEMPTY + 8 * i, 1); }
        for (int i = 0; i < QDEPTH; i++) { mbar_init(bars + B_IFULL + 8 * i, 1); mbar_init(bars + B_IEMPTY + 8 * i, 23); }
        mbar_init(bars + B_WANT, 2); mbar_init(bars + B_MEET, 1);
        for (int i = 0; i < 4; i++) mbar_init(bars + B_HALF + 8 * i, 1);
        mbar_init(bars + B_ALT, 4); mbar_init(bars + B_ALT + 8, 4); mbar_init(bars + B_QFREE, 2);
        asm volatile("st.shared.u64 [%0], 0;" :: "r"(bars + SM_ORDY) : "memory");
        asm volatile("fence.mbarrier_init.release.cluster;\nfence.acq_rel.cta;" ::: "memory");
    }
    __syncwarp();
    if (warp != 0) asm volatile("barrier.cluster.arrive.relaxed.aligned;" ::: "memory");
    asm volatile("barrier.cluster.wait.acquire.aligned;" ::: "memory");

    uint32_t qn = 0;
    auto next_item = [&](bool releaser, bool bounded = true) -> int {
        const uint32_t slot = qn % QDEPTH;
        if (bounded) mbar_wait(bars + B_IFULL + 8 * slot, (qn / QDEPTH) & 1);
        else mbar_spin(bars + B_IFULL + 8 * slot, (qn / QDEPTH) & 1);
        uint32_t it;
        asm volatile("ld.shared.u32 %0, [%1];" : "=r"(it) : "r"(bars + SM_QUEUE + 4 * slot) : "memory");
        mbar_arrive_cluster_if(releaser, bars0 + B_IEMPTY + 8 * slot);
        qn++;
        return it;
    };

    if (warp < 4) {
        reg_dec<40>();
        if (warp == 0) {
            {
                uint32_t gph = 1;
                const uint32_t prank = __shfl_sync(0xffffffffu, rank, 0);
                auto request = [&]() { mbar_arrive_cluster_if(lane == 0, bars0 + B_WANT); };
                auto take_item = [&]() -> int { return __shfl_sync(0xffffffffu, next_item(lane == 0), 0); };
                auto inputs_seen = [&](uint32_t word, unsigned& n) -> uint32_t {
                    uint32_t v;
                    spin_guard(n);
                    asm volatile("ld.acquire.cta.shared.u32 %0, [%1];" : "=r"(v) : "r"(bars + SM_ORDY + 4 * word) : "memory");
                    return __shfl_sync(0xffffffffu, v, 0);
                };
                uint32_t oneed = 0;
                auto wait_inputs = [&](int it) {
                    if (it & ITEM_READY) return;
                    oneed += 256;
                    for (unsigned n = 0; inputs_seen(1, n) < oneed;) {}
                };
                int nxt = first_item(), ring = -1, rot = 0;
                for (int k0 = 2; item_type(nxt) <= T_LOCAL; k0 = 0) {
                    const int type = item_type(nxt), m = item_row(nxt), c = item_col(nxt);
                    if (type == T_LOCAL) {
                        wait_inputs(nxt);
                        request();
#pragma unroll 1
                        for (uint32_t st = 0; st < 4; st++) {
                            mbar_wait(bars + B_GEMPTY + 8 * st, gph);
                            const uint32_t dst = sb + st * GST_BYTES, fb = bars + B_GFULL + 8 * st;
                            warp_expect_tx(fb, st == 0 ? 32768 + 512 : st == 3 ? 0 : 4 * LOC_PLANE);
                            if (st == 3) break;
                            if (st == 0) warp_bulk_load(dst + 4 * LOC_PLANE, &g_gate[m * 128], 512, fb);
#pragma unroll 1
                            for (int i = 0; i < 4; i++)
                                warp_tma_load(dst + i * LOC_PLANE, &prm.m[st ? M_SCR_LOC : M_SCR_LOQ], fb, i * 64, m * 64 - (st ? 8 : 0), G_B + 8 * st + c, true);
                        }
                        gph ^= 1;
                        ring = -1;
                    } else {
                        const int nk = type == T_K || type == T_V ? 8 : 16, kept = ring == m + 16 * nk ? 4 : 0;
                        ring = m + 16 * nk;
                        rot = kept ? rot - 4 : 0;
                        const CUtensorMap* ma = &prm.m[nk == 8 ? M_C : M_X];
                        const CUtensorMap* mb = &prm.m[M_WQ + type];
#pragma unroll 1
                        for (int k = k0; k < nk; k++) {
                            if (k == nk - 3) request();
                            const uint32_t st = k & 3, dst = sb + st * GST_BYTES, fb = bars + B_GFULL + 8 * st;
                            const int kc = ((k + rot) & (nk - 1)) * 64;
                            mbar_wait(bars + B_GEMPTY + 8 * st, gph);
                            warp_expect_tx(fb, k < kept ? 32768 : GST_BYTES);
                            if (k >= kept) warp_tma_load(dst, ma, fb, kc, m * 128, 0, c == 15 && type != T_K);
                            warp_tma_load_pair(dst + 16384 + prank * 16384, mb, fb, 0, kc, c * 4 + 2 * prank, true);
                            if (st == 3) gph ^= 1;
                        }
                    }
                    nxt = take_item();
                }
                uint32_t kv = 0, kvph = 1;
                uint32_t qc = 0;
                auto a_parity = [&](uint32_t b) { return b < 2 ? (((qc + 1 - b) >> 1) & 1) ^ 1 : kvph ^ (b - 2 < kv); };
                const CUtensorMap* tile_map = &prm.m[M_SCR_LD];
                asm volatile("" : "+l"(tile_map));
                {
                    bool need_g = true, more = true;
                    int pv_grp = -1, pv_row = 0;
                    int pv_shared = 0;
                    bool peer_longer = false;
                    int m = 0, c = 0, asc = 0, nu = 0, uend = 0, ureq = -1, ufetch = 0;
#pragma unroll 1
                    for (int u = 0;; u++) {
                        if (u == ufetch) {
                            if (qc) nxt = take_item();
                            if (item_type(nxt) == T_ATTN) {
                                wait_inputs(nxt);
                                const uint32_t b = qc & 1, dst = sb + b * 32768, fb = bars + B_AFULL + 8 * b, row = item_row(nxt) * 128;
                                mbar_wait(bars + (qc == 0 ? B_GEMPTY : qc == 1 ? B_QFREE : B_AEMPTY + 8 * b), qc == 0 ? gph : qc == 1 ? 0 : a_parity(b));
                                warp_expect_tx(fb, 32768 + 512);
                                warp_tma_load(dst, tile_map, fb, 0, row, G_Q + item_col(nxt), false);
                                warp_tma_load(dst + 16384, tile_map, fb, 64, row, G_Q + item_col(nxt), false);
                                warp_bulk_load(bars + SM_GATE + b * 512, &g_gate[row], 512, fb);
                                qc++;
                            }
                        }
                        if (u == uend) {
                            if (!more) break;
                            more = item_type(nxt) == T_ATTN;
                            m = item_row(nxt); c = item_col(nxt); asc = item_asc(nxt);
                            nu = more ? 2 * m + 2 : 0;
                            uend = nu + ((more ? m < 2 : pv_grp >= 0) ? 3 : 0);
                            ureq = 2 * max(m - 2 - (asc & m), 0);
                            ufetch = !more ? -1 : m ? 2 * m : uend;
                            u = -1;
                            continue;
                        }
                        int grp = pv_grp, row = pv_row;
                        int shared = pv_shared;
                        if (u >= nu) {
                            if (u == nu + 1) pv_grp = -1;
                            else if (peer_longer) { grp = -1; shared = 0; }
                            else continue;
                        } else {
                            const int j = asc ? u >> 1 : m - (u >> 1);
                            if (u & 1) {
                                pv_grp = G_V + c; pv_row = j * 128; pv_shared = (m | 1) - j;
                                peer_longer = asc & ~m & 1;
                                if (u == nu - 1 && (m & 1) && item_type(nxt) == T_END) mbar_arrive_cluster_n_if(lane == 0, bars0 + B_WANT, 2);
                                if (grp < 0) continue;
                            } else {
                                if (u == ureq) request();
                                grp = G_K + c; row = j * 128; shared = (m | 1) - j;
                            }
                        }
                        uint32_t fb = bars + B_AFULL + 16 + 8 * kv, mine = sb + SM_KV + kv * 32768 + prank * 16384;
                        int c_mine = prank * 64;
                        asm volatile("" : "+r"(mine), "+r"(fb), "+r"(row), "+r"(grp), "+r"(c_mine));
                        mbar_wait(need_g ? bars + B_GEMPTY + 8 + 8 * kv : fb + B_AEMPTY - B_AFULL, need_g ? gph : kvph);
                        warp_expect_tx(fb, grp < 0 ? 0 : 32768);
                        if (shared) {
                            warp_tma_load_pair(mine, tile_map, fb, c_mine, row, grp, shared == 1);
                        } else if (grp >= 0) {
                            warp_tma_load(mine, tile_map, fb, c_mine, row, grp, true);
                            warp_tma_load(mine + 16384 - prank * 32768, tile_map, fb, 64 - c_mine, row, grp, true);
                        } else {
                            mbar_arrive_cluster_n_if(lane < 2, map_cta(fb, lane & 1) + B_AEMPTY - B_AFULL, 8);
                        }
                        if (kv == 2) need_g = false;
                        if (++kv == 4) { kv = 0; kvph ^= 1; }
                    }
                }
                if (!qc) request();
                const int it = take_item();
                int nk = 0;
                if (item_type(it) == T_OUT) {
                    const int m = item_row(it), c = item_col(it), half = c & 1;
                    nk = 80;
                    for (int k = 0; k < nk; k++) {
                        if (k == K_SPLIT) nk = 2 * TRIPLES + (take_item() & 127);
                        const int kn = k + 2 * TRIPLES - nk, first = kn >= 0 && !(kn & 1);
                        const int s = kn >= 0 ? WIDE + (3 * kn + 1) / 2 : half ? WIDE - 1 - k : k;
                        const uint32_t sa = prm.ostep[s], sa2 = prm.ostep[s + first], sw = prm.ostep[s - (kn >= 0 && !first ? prank : 0)];
                        const uint32_t need = 1u << (sa >> 1 & 31) | 1u << (sa2 >> 1 & 31);
                        for (unsigned n = 0; need & ~inputs_seen(sa >> 6, n);) {}
                        const uint32_t st = k & 3;
                        uint32_t dst = sb + st * GST_BYTES, fb = bars + B_GFULL + 8 * st;
                        uint32_t dstb = dst + 16384 + (first ? 0 : prank * 16384), skipb = first && (kn >> 1 & 1) != prank;
                        int a0 = (sa & 1) * 64, a1 = m * 128, a2 = (sa >> 1) + (sa < 64 ? G_CTX : G_LOC - 32);
                        int b1 = (sw & 63) * 64, b2 = (c >> 1) * 4 + 2 * (kn >= 0 ? half : half ^ prank);
                        const CUtensorMap* mb = &prm.m[sw >= 64 ? M_WOB : M_WO];
                        asm volatile("" : "+r"(dst), "+r"(fb), "+r"(dstb), "+r"(skipb), "+r"(a0), "+r"(a1), "+r"(a2), "+r"(b1), "+r"(b2), "+l"(mb));
                        if (k < 4) {
#pragma unroll 1
                            for (uint32_t i = 0, b = (3 * st) >> 1; i < 3; i++, b++) mbar_wait(bars + (i == 2 ? B_QFREE : B_AEMPTY + 8 * b), i == 2 ? 0 : a_parity(b));
                            mbar_arrive_cluster_if(lane == 0, bars_peer + B_XFREE + 8 * st);
                            mbar_wait(bars + B_XFREE + 8 * st, 0);
                        }
                        mbar_wait(bars + B_GEMPTY + 8 * st, gph);
                        warp_expect_tx(fb, GST_BYTES);
                        warp_tma_load(dst, tile_map, fb, a0, a1, a2, true);
                        if (!skipb) warp_tma_load_pair(dstb, mb, fb, 0, b1, b2, false);
                        if (first) warp_tma_load(dst + 32768, tile_map, fb, (sa2 & 1) * 64, a1, G_CTX + (sa2 >> 1), true);
                        if (k < K_SPLIT && lane == 0 && !prank)
                            asm volatile("st.relaxed.gpu.global.u32 [%0], %1;" :: "l"(&g_sync.step[0][0] + m * 4 + c), "r"(k) : "memory");
                        mbar_arrive_if(k == K_MEET && lane == 0, bars + B_MEET);
                        if ((uint32_t)(k - K_FETCH) < (3 * TRIPLES + 1) / 2) {
                            const uint32_t g = prm.ostep[79 - 2 * (k - K_FETCH)] >> 1;
                            warp_prefetch((const char*)g_scr + (uint32_t)((G_CTX + g) * (SEQ * 256) + m * 32768 + c * 4096), 4096);
                            warp_prefetch(prm.wo + (uint32_t)(g * 262144 + (m * 8 + c) * 2048), 2048);
                        }
                        if (st == 3) gph ^= 1;
                    }
                    for (unsigned n = 0; ~inputs_seen(0, n) || inputs_seen(1, n) != 255;) {}
                }
#pragma unroll 1
                for (uint32_t st = 0; st < 4; st++) { mbar_wait(bars + B_GEMPTY + 8 * st, gph ^ (st < (nk & 3))); mbar_wait(bars + B_AEMPTY + 16 + 8 * st, a_parity(2 + st)); }
                unsigned left = 0;
                if (lane == 0) asm volatile("atom.relaxed.gpu.global.add.u32 %0, [%1], 1;" : "=r"(left) : "l"(&g_sync.done) : "memory");
                if (__shfl_sync(0xffffffffu, left, 0) == NCTA - 1)
#pragma unroll 1
                    for (uint32_t i = lane * 8; i < sizeof(Sync); i += 256) *(unsigned long long*)((char*)&g_sync + i) = 0;
            }
        } else if (warp <= 2) {
            if (blockIdx.x < SEQ / 16) {
                const uint32_t r0 = 16 * blockIdx.x + 8 * (warp - 1), gbuf = bars + SM_GATE + 4 * (r0 & 15);
                float z[4];
                mbar_wait(bars + B_GFULL + 24, 0);
#pragma unroll 1
                for (uint32_t i = 0; i < 8; i++) {
                    const uint32_t off = (i & 3) * 512 + lane * 16;
                    const uint4* xp = (const uint4*)((const char*)prm.x + ((r0 + (i & 4)) * 2048 + off));
                    const uint4 wv = __ldg((const uint4*)((const char*)prm.gate_w + off));
                    uint4 xv[4];
#pragma unroll
                    for (int r = 0; r < 4; r++) { xv[r] = __ldg(xp + r * 128); if (!(i & 3)) z[r] = 0.f; }
                    const uint32_t ws[4] = {wv.x, wv.y, wv.z, wv.w};
#pragma unroll
                    for (int e = 0; e < 4; e++)
#pragma unroll
                        for (int r = 0; r < 4; r++) {
                            const uint32_t xs = e == 0 ? xv[r].x : e == 1 ? xv[r].y : e == 2 ? xv[r].z : xv[r].w;
                            z[r] = fmaf(__uint_as_float(xs << 16), __uint_as_float(ws[e] << 16), z[r]);
                            z[r] = fmaf(__uint_as_float(xs & 0xffff0000u), __uint_as_float(ws[e] & 0xffff0000u), z[r]);
                        }
                    if ((i & 3) == 3) {
#pragma unroll
                        for (int o = 16; o > 0; o >>= 1)
#pragma unroll
                            for (int r = 0; r < 4; r++) z[r] += __shfl_xor_sync(0xffffffffu, z[r], o);
                        const float zr = lane & 2 ? (lane & 1 ? z[3] : z[2]) : (lane & 1 ? z[1] : z[0]);
                        asm volatile("st.shared.f32 [%0], %1;" :: "r"(gbuf + 4 * ((i & 4) + (lane & 3))), "f"(1.f / (1.f + __expf(-zr))) : "memory");
                    }
                }
                fence_proxy_async_smem();
                __syncwarp();
                warp_bulk_store((char*)g_gate + 4 * r0, gbuf, 32);
                bulk_commit();
                bulk_wait<0>();
                __syncwarp();
                if (lane == 0) red_add(&g_sync.count[3], 1);
            }
            __syncwarp();
            {
                const int w = warp - 1;
                uint32_t sph = 0, nann = 0;
                int unsent = 0, nunsent = 0;
                bool urgent = false;
                auto announce = [&]() {
                    if (!urgent) return;
                    bulk_wait<0>();
                    __syncwarp();
                    const uint32_t hb = bars + B_HALF + 8 * (nann & 3);
                    if (w == 0) {
                        mbar_arrive_if(lane == 0, hb);
                    } else {
                        mbar_wait(hb, (nann >> 2) & 1);
                        const uint32_t type = item_type(unsent), m = item_row(unsent), c = item_col(unsent);
                        const uint32_t word = type < T_B ? c >> 3 : type == T_B ? 2 : offsetof(Sync, ctx) / 8 + m;
                        const uint32_t bit = type < T_B ? 8 * (c & 7) : type == T_B ? 8 * (c & 3) : type == T_LOCAL ? 32 + c : c;
                        if (lane < nunsent) red_add((unsigned long long*)((char*)&g_sync + 8 * word), 1ull << bit);
                        __syncwarp();
                    }
                    nann++;
                    nunsent = 0; urgent = false;
                };
                int held = first_item(), it;
                bool qfree = false;
                do {
                    if (!__all_sync(0xffffffffu, mbar_test(bars + B_IFULL + 8 * (qn % QDEPTH), (qn / QDEPTH) & 1))) announce();
                    it = __shfl_sync(0xffffffffu, next_item(lane == 0), 0);
                    const int itype = item_type(it);
                    const bool keep_held = itype == T_LOCAL;
                    if (itype >= T_ATTN && held < 0) {
                        urgent = nunsent;
                        mbar_arrive_if(lane == 0 && !qfree, bars + B_QFREE);
                        qfree = true;
                    }
#pragma unroll 1
                    for (int pass = held < 0 || keep_held; pass < 2; pass++) {
                        if (pass && (itype < T_OUT || itype == T_END)) break;
                        const int cur = pass ? it : held, type = item_type(cur), m = item_row(cur), c = item_col(cur);
                        const bool local = type == T_LOCAL;
                        const int grp = pass ? (local ? G_LOC : G_CTX) + c : type * 32 + 2 * c;
#pragma unroll 1
                        for (int i = 0; i < 4 - 2 * pass; i++) {
                            const int b = i & 1;
                            const bool alt = i >= 2 && itype == T_ATTN;
                            const uint32_t full = bars + (alt ? B_ALT + 8 * w : B_SFULL + 16 * w + 8 * b), par = alt ? 0 : sph;
                            if (i == 3 - 2 * pass || !__all_sync(0xffffffffu, mbar_test(full, par))) announce();
                            mbar_wait(full, par);
                            fence_proxy_async_smem();
                            warp_tma_store(&prm.m[local ? M_SCR_LOQ : M_SCR_ST], sb + (alt ? 32768 : SM_STAGING) + w * 16384 + b * 8192,
                                         local ? b * 128 + w * 64 : b * 64, local ? m * 64 : m * 128 + w * 64, grp + (i >> 1), local || (type < T_B && c < FIRST_PAIR));
                            bulk_commit();
                            bulk_wait_read<0>();
                            __syncwarp();
                            mbar_arrive_if(lane == 0 && !alt, bars + B_SEMPTY + 16 * w + 8 * b);
                            sph ^= b & !alt;
                        }
                        mbar_arrive_if(lane == 0 && !qfree && itype >= T_ATTN, bars + B_QFREE);
                        qfree |= itype >= T_ATTN;
                        if (lane == nunsent) unsent = cur;
                        nunsent++;
                        urgent = nunsent == 32 || !local;
                    }
                    if (!keep_held) held = itype < T_OUT ? it : -1;
                } while (item_type(it) != T_END);
                announce();
                it = __shfl_sync(0xffffffffu, next_item(lane == 0), 0);
                if (item_type(it) == T_OUT) {
                    if (w) {
                        mbar_wait(bars + B_MEET, 0);
                        asm volatile("fence.proxy.async.global;\nfence.acq_rel.gpu;" ::: "memory");
                        mbar_arrive_cluster_if(lane == 0, bars0 + B_WANT);
                    }
                    next_item(lane == 0);
#pragma unroll 1
                    for (int i = 0; i < 4; i++) {
                        const int b = i & 1;
                        mbar_wait(bars + B_SFULL + 16 * w + 8 * b, sph ^ (i >> 1));
                        fence_proxy_async_smem();
                        warp_tma_add(&prm.m[M_OUT], sb + SM_STAGING + w * 16384 + b * 8192, (item_col(it) ^ (i < 2)) * 128 + b * 64, item_row(it) * 128 + w * 64, 0);
                        bulk_commit();
                        if (b) {
                            bulk_wait_read<0>();
                            __syncwarp();
                            mbar_arrive_if(lane < 2, bars + B_SEMPTY + 16 * w + 8 * lane);
                        }
                    }
                }
            }
        } else {
            if (elect_one()) {
                uint32_t ordy = 0;
                unsigned long long cnt_lo = 0, cnt_hi = 0;
                int late = 0;
                auto refresh = [&]() {
                    if (!late && cnt_lo == 0x30303030 && cnt_hi == SEQ / 8) late = 1;
                    asm volatile("ld.acquire.gpu.global.v2.u64 {%0, %1}, [%2];" : "=l"(cnt_lo), "=l"(cnt_hi) : "l"(late ? &g_sync.count[0] : &g_sync.count[2]) : "memory");
                };
                auto inputs_ready = [&](int it) -> bool {
                    const int c = item_col(it);
                    if (item_type(it) == T_ATTN) return late && ((c < 16 ? cnt_lo : cnt_hi) >> (4 * (c & 14)) & 255) == 48;
                    return late || (cnt_hi == SEQ / 8 && (cnt_lo >> (4 * (c & 6)) & 255) == 48);
                };
                auto publish = [&](int it, int step) {
                    const uint32_t slot = qn % QDEPTH;
                    mbar_wait(bars + B_IEMPTY + 8 * slot, ((qn / QDEPTH) & 1) ^ 1);
                    for (uint32_t r = 0; r < 2; r++) {
                        const uint32_t rb = map_cta(bars, r);
                        asm volatile("mbarrier.arrive.expect_tx.shared::cluster.b64 _, [%0], 4;" :: "r"(rb + B_IFULL + 8 * slot) : "memory");
                        asm volatile("st.async.shared::cluster.mbarrier::complete_tx::bytes.u32 [%0], %1, [%2];"
                                     :: "r"(rb + SM_QUEUE + 4 * slot), "r"(it + r * step), "r"(rb + B_IFULL + 8 * slot) : "memory");
                    }
                    qn++;
                };
                int asc = 1;
                int it;
                do {
                    if (rank == 0) {
                        mbar_wait(bars + B_WANT, qn & 1);
                        const uint32_t pair = plan_index();
                        int pit = prm.plan[pair < 64 ? pair & 7 : pair - 56][min(qn + 1, 15u)];
                        unsigned i;
                        const bool planned = item_type(pit) != T_END;
                        if (!planned) asm volatile("atom.relaxed.gpu.global.add.u32 %0, [%1], 1;" : "=r"(i) : "l"(&g_sync.next) : "memory");
                        if (cnt_lo != 0x3030303030303030ull || cnt_hi != cnt_lo) refresh();
                        if (planned) pit += (pair >> 3 & 7) << (item_type(pit) == T_LOCAL);
                        else if (i < NITEMS) pit = prm.items[i];
                        const int type = item_type(pit);
                        int step = type == T_LOCAL ? 16 : 1;
                        it = pit + (pit & (step == 1 ? 15 : 0x1f0));
                        if (type == T_ATTN) {
                            if (!asc) { it += 1; step = -1; }
                            it |= asc << 9;
                        }
                        asc = type != T_ATTN || item_row(pit) == 0 || !asc;
                        if (inputs_ready(it)) it |= ITEM_READY;
                        publish(it, step);
                    } else {
                        it = next_item(true);
                    }
                    if ((item_type(it) == T_ATTN || item_type(it) == T_LOCAL) && !(it & ITEM_READY)) {
                        unsigned n = 0;
                        while (!inputs_ready(it)) { refresh(); spin_guard(n); }
                        asm volatile("st.release.cta.shared.u32 [%0], %1;" :: "r"(bars + SM_ORDY + 4), "r"(ordy += 256) : "memory");
                    }
                } while (item_type(it) != T_END);
                if (rank == 0) {
                    mbar_wait(bars + B_WANT, qn & 1);
                    const unsigned i = atomicAdd(&g_sync.next_out, 1u), t = i < 32 ? 31 - i : i - 32;
                    it = i < 64 ? T_OUT << 13 | ((t & 3) * 2 + (i >> 5)) << 4 | (t >> 2) * 2 : T_END << 13;
                    publish(it, 1);
                } else {
                    it = next_item(true);
                }
                if (item_type(it) == T_OUT) {
                    const uint32_t m = item_row(it), half = item_col(it) & 1, tile = m * 2 + (item_col(it) >> 1);
                    unsigned* split = (unsigned*)((char*)g_sync.split + 4 * tile);
                    unsigned long long rdy = 0;
                    int state = rank ? 2 : 0;
                    for (unsigned n = 0; rdy != 0xffffffffffull || state < 2; spin_guard(n)) {
                        if (rdy != 0xffffffffffull) {
                            rdy = ld_acquire((const unsigned long long*)((char*)g_sync.ctx + 8 * m));
                            asm volatile("st.release.cta.shared.u64 [%0], %1;" :: "r"(bars + SM_ORDY), "l"(rdy) : "memory");
                        }
                        unsigned steps = 0;
                        if (state == 1) {
                            steps = ld_acquire(split);
                        } else if (state == 0 && mbar_test(bars + B_WANT, qn & 1)) {
                            state = 1;
                            unsigned seen;
                            asm volatile("atom.acq_rel.gpu.global.exch.b32 %0, [%1], 1;" : "=r"(seen) : "l"(split) : "memory");
                            if (seen) {
                                const unsigned long long v = ld_acquire((const unsigned long long*)((char*)g_sync.step + 8 * tile));
                                const int d = (int)(v >> 32) - (int)v;
                                steps = (WIDE + min(max(half ? d : -d, -12), 12)) >> 1;
                                atomicExch(split, WIDE - steps);
                            }
                        }
                        if (steps > 1) { publish(T_END << 13 | steps, 0); state = 2; }
                    }
                    if (rank) next_item(true);
                }
                #pragma unroll 1
                for (uint32_t n = qn; n < qn + QDEPTH && rank == 0; n++) mbar_wait(bars + B_IEMPTY + 8 * (n % QDEPTH), ((n / QDEPTH) & 1) ^ 1);
            }
        }
    } else {
        reg_inc<232>();
        const int wg = (warp >> 2) - 1, wq = warp & 3;
        uint32_t gph = 0;
        uint32_t kvn = 0;
        const uint32_t dA = make_desc(sb + wg * 8192, 16);
        uint32_t ti = 0;
        uint32_t sph = 1;
        const uint32_t stg = sb + SM_STAGING + wg * 16384;
        const uint32_t stg_lane = stg + (wq * 16 + (lane & 15)) * 128 + (((lane >> 4) ^ (lane & 7)) << 4);
        auto write_blocks = [&](auto n, uint32_t off, const uint32_t* v) {
            uint32_t a = stg_lane;
            asm volatile("" : "+r"(a));
            a += off;
#pragma unroll
            for (int j = 0; j < decltype(n)::value; j++)
                stmatrix_x4((a ^ (32 * (j & 3))) + (j >> 2) * 8192, v[4 * j], v[4 * j + 1], v[4 * j + 2], v[4 * j + 3]);
        };
        auto release = [&](uint32_t bar) { mbar_arrive_if(lane == 0, bars + bar); };
        const uint32_t bars_lane = map_cta(bars, lane & 1);
        auto release_stage = [&](uint32_t st) { mbar_arrive_cluster_if(lane < 2, bars_lane + B_GEMPTY + 8 * st); };
        auto take_item = [&]() -> int {
            return __shfl_sync(0xffffffffu, next_item(lane == 0, false), 0);
        };
        auto stage_acquire = [&](int b) { mbar_spin(bars + B_SEMPTY + 16 * wg + 8 * b, sph); };
        auto stage_publish = [&](int b) {
            __syncwarp();
            release(B_SFULL + 16 * wg + 8 * b);
        };
        auto stage_chunk = [&](int b, const uint32_t* v) {
            stage_acquire(b);
            write_blocks(std::integral_constant<int, 4>(), b * 8192, v);
            stage_publish(b);
            if (b) sph ^= 1;
        };
        auto publish_pair = [&]() {
            __syncwarp();
            mbar_arrive_if(lane < 2, bars + B_SFULL + 16 * wg + 8 * lane);
            sph ^= 1;
        };
        auto gemm_step = [&](float (&acc)[128], uint32_t dB, int& k) {
            const uint32_t st = k & 3;
            wgmma_wait<0>();
            release_stage((k - 1) & 3);
            mbar_spin(bars + B_GFULL + 8 * st, gph);
            const uint64_t da = full_desc(dA + st * (GST_BYTES >> 4)), db = full_desc(dB + st * (GST_BYTES >> 4));
            wgmma_fence();
#pragma unroll
            for (int kk = 0; kk < 4; kk++) wgmma_ss_n256_tb(acc, da + 2 * kk, db + 128 * kk, 1);
            wgmma_commit();
            gph ^= st == 3;
            k++;
        };
        if (wg == 1) bar_arrive(1, 256);
        int it = first_item();
        while (true) {
            if (item_type(it) <= T_LOCAL) {
                float acc[128];
                uint32_t pk[64];
                bool pending = false;
                int held = T_END;
                auto scale_q = [&](int j0, int n) {
                    if (held != T_Q) return;
#pragma unroll
                    for (int j = j0; j < j0 + n; j++)
                        asm("{\n.reg .b32 t;\nmul.rn.bf16x2 t, %0, %2;\nfma.rn.bf16x2 %0, %0, %1, t;\n}\n" : "+r"(pk[j]) : "r"(0x3e033e03u), "r"(0xb9d8b9d8u));
                };
                zero_regs(pk);
                const uint32_t dB = make_desc(sb + 16384, 8192);
                do {
                    const int type = item_type(it);
                    if (type == T_LOCAL) {
                        int ln = lane;
                        asm volatile("" : "+r"(ln));
                        const int g = ln >> 2, t = ln & 3, par = wq & 1;
                        const uint32_t hc = (wq >> 1) * 4, pl = sb + (par * 2 + wg) * LOC_PLANE;
                        const uint32_t a16 = (ln & 15) * 128 + (((hc + (ln >> 4)) ^ (ln & 7)) << 4), a8 = (ln & 7) * 128 + (((hc + (ln >> 3)) ^ (ln & 7)) << 4);
                        const bool first0 = 2 * t > g, first1 = 2 * t + 1 > g;
                        const uint32_t fmask = (first0 ? 0xffffu : 0u) | (first1 ? 0xffff0000u : 0u);
                        const bool edge = item_row(it) == 0;
                        uint32_t q[4][2][4], kf[9][4], vf[9][4];
                        float w[8];
                        mbar_spin(bars + B_GFULL, gph);
#pragma unroll
                        for (int u = 0; u < 4; u++) { ldsm_x4(q[u][0], pl + u * 2048 + a16); ldsm_x4(q[u][1], pl + u * 2048 + (a16 ^ 32)); }
#pragma unroll
                        for (int j = 0; j < 8; j++) w[j] = lds_f32(sb + 4 * LOC_PLANE + 4 * (2 * g + par) + 64 * j);
                        __syncwarp();
                        release_stage(0);
                        mbar_spin(bars + B_GFULL + 8, gph);
#pragma unroll
                        for (int n = 0; n < 9; n++) ldsm_x4(kf[n], pl + GST_BYTES + n * 1024 + a8);
                        __syncwarp();
                        release_stage(1);
                        float s[8][2];
#pragma unroll
                        for (int u = 0; u < 4; u++) {
                            float d[3][4];
#pragma unroll
                            for (int nt = 0; nt < 3; nt++) {
                                mma_k16_init(d[nt], q[u][0], kf[2 * u + nt][0], kf[2 * u + nt][1]);
                                mma_k16(d[nt], q[u][1], kf[2 * u + nt][2], kf[2 * u + nt][3]);
                            }
                            if (u == 0 && edge) { d[0][0] = -INFINITY; d[0][1] = -INFINITY; }
                            s[2 * u][0] = first0 ? d[0][0] : d[1][0]; s[2 * u][1] = first1 ? d[0][1] : d[1][1];
                            s[2 * u + 1][0] = first0 ? d[1][2] : d[2][2]; s[2 * u + 1][1] = first1 ? d[1][3] : d[2][3];
                        }
                        mbar_spin(bars + B_GFULL + 16, gph);
#pragma unroll
                        for (int u = 0; u < 4; u++) { ldsm_x4_t(vf[2 * u], pl + 2 * GST_BYTES + u * 2048 + a16); ldsm_x4_t(vf[2 * u + 1], pl + 2 * GST_BYTES + u * 2048 + (a16 ^ 32)); }
                        ldsm_x4_t(vf[8], pl + 2 * GST_BYTES + 8192 + a8);
                        __syncwarp();
                        release_stage(2);
                        float x[8];
#pragma unroll
                        for (int j = 0; j < 8; j++) x[j] = fmaxf(s[j][0], s[j][1]);
#pragma unroll
                        for (int o = 1; o < 4; o *= 2)
#pragma unroll
                            for (int j = 0; j < 8; j++) x[j] = fmaxf(x[j], __shfl_xor_sync(0xffffffffu, x[j], o));
#pragma unroll
                        for (int j = 0; j < 8; j++) {
                            const float n = x[j] * -LOC_SCALE;
                            s[j][0] = ex2(fmaf(s[j][0], LOC_SCALE, n)); s[j][1] = ex2(fmaf(s[j][1], LOC_SCALE, n));
                            x[j] = s[j][0] + s[j][1];
                        }
#pragma unroll
                        for (int o = 1; o < 4; o *= 2)
#pragma unroll
                            for (int j = 0; j < 8; j++) x[j] += __shfl_xor_sync(0xffffffffu, x[j], o);
                        mbar_spin(bars + B_GFULL + 24, gph);
                        release_stage(3);
                        it = take_item();
                        uint32_t ob[4][8];
#pragma unroll
                        for (int u = 0; u < 4; u++) {
                            const float r0 = rcp(x[2 * u]), r1 = rcp(x[2 * u + 1]), f0 = fmaf(-w[2 * u], r0, r0), f1 = fmaf(-w[2 * u + 1], r1, r1);
                            const uint32_t p0 = pack_bf16(s[2 * u][0] * f0, s[2 * u][1] * f0), p1 = pack_bf16(s[2 * u + 1][0] * f1, s[2 * u + 1][1] * f1);
                            const uint32_t pa[4] = {p0 & fmask, 0, p0 & ~fmask, p1 & fmask};
#pragma unroll
                            for (int c = 0; c < 4; c++) {
                                float ol[4];
                                mma_k16_init(ol, pa, vf[2 * u + (c >> 1)][2 * (c & 1)], vf[2 * u + (c >> 1)][2 * (c & 1) + 1]);
                                mma_k8(ol, 0, p1 & ~fmask, u < 3 ? vf[2 * u + 2 + (c >> 1)][2 * (c & 1)] : vf[8][c]);
                                ob[u][2 * c] = pack_bf16(ol[0], ol[1]);
                                ob[u][2 * c + 1] = pack_bf16(ol[2], ol[3]);
                            }
                        }
                        stage_acquire(0); stage_acquire(1);
#pragma unroll
                        for (int u = 0; u < 4; u++) {
                            stmatrix_x4(stg + par * 8192 + u * 2048 + a16, ob[u][0], ob[u][1], ob[u][2], ob[u][3]);
                            stmatrix_x4(stg + par * 8192 + u * 2048 + (a16 ^ 32), ob[u][4], ob[u][5], ob[u][6], ob[u][7]);
                        }
                        publish_pair();
                        bar_sync(4, 256);
                        gph ^= 1;
                        continue;
                    }
                    mbar_spin(bars + B_GFULL, gph);
                    bool more;
                    do {
                        wgmma_fence();
                        wgmma_ss_n256_tb_init(acc, full_desc(dA), full_desc(dB));
#pragma unroll
                        for (int kk = 1; kk < 4; kk++) wgmma_ss_n256_tb(acc, full_desc(dA) + 2 * kk, full_desc(dB) + 128 * kk, 1);
                        wgmma_commit();
                        const int nk = item_type(it) == T_K || item_type(it) == T_V ? 8 : 16;
                        int k = 1;
                        do {
                            if (pending) {
                                const int kf = k - 1 - wg;
                                if (kf == 0) { scale_q(0, 16); stage_chunk(0, pk); }
                                else if (kf == 1) { scale_q(16, 16); stage_chunk(1, pk + 16); }
                                else if (kf == 3) { scale_q(32, 16); stage_chunk(0, pk + 32); }
                                else if (kf == 4) { scale_q(48, 16); stage_chunk(1, pk + 48); }
                            }
                            gemm_step(acc, dB, k);
                        } while (k < nk);
                        held = item_type(it);
                        it = take_item();
                        more = item_type(it) < T_LOCAL;
                        if (more) mbar_spin(bars + B_GFULL, gph);
                        wgmma_wait<0>();
                        fence_regs(acc);
                        release_stage(3);
#pragma unroll
                        for (int j = 0; j < 64; j++) pk[j] = pack_bf16(acc[2 * j], acc[2 * j + 1]);
                        pending = true;
                    } while (more);
                } while (item_type(it) <= T_LOCAL);
                if (pending) {
                    scale_q(0, 64);
                    stage_acquire(0); stage_acquire(1);
                    write_blocks(std::integral_constant<int, 8>(), 0, pk);
                    const bool borrow = item_type(it) == T_ATTN;
                    if (borrow) {
                        mbar_spin(bars + B_GEMPTY, gph ^ 1); mbar_spin(bars + B_GEMPTY + 8, gph ^ 1);
                    } else {
                        publish_pair();
                        stage_acquire(0); stage_acquire(1);
                    }
                    write_blocks(std::integral_constant<int, 8>(), borrow ? 32768 - SM_STAGING : 0, pk + 32);
                    publish_pair();
                    mbar_arrive_if(lane == 0 && borrow, bars + B_ALT + 8 * wg);
                }
                if (item_type(it) == T_END) { it = take_item(); break; }
            } else {
                float o[64], s[64];
                uint32_t pa[32], pb[32];
                zero_regs(o); zero_regs(s); zero_regs(pa);
                float n0 = 0.f, n1 = 0.f;
                int shifted = 0;
                float l0 = 1.f, l1 = 1.f, f0 = 0.f, f1 = 0.f, g0 = 0.f, g1 = 0.f;
                uint32_t has_pv = 0;
                int first = 0;
                int pending = 0;
                const uint32_t dK = make_desc(sb + SM_KV, 16), dV = make_desc(sb + SM_KV, 16384);
                const uint32_t lane_off = bars_lane - bars + B_AEMPTY - B_AFULL;
                int cur = 0;
                uint32_t qoff = 0;
                const int row = wg * 64 + wq * 16 + (lane >> 2);
                const float thr = (row & 63) - (lane & 3) * 2;
                int peek = 0;
                auto kv_wait = [&](uint32_t n) { mbar_spin(bars + B_AFULL + 16 + 8 * (n & 3), (n >> 2) & 1); };
                auto kv_release = [&](uint32_t n) { mbar_arrive_cluster_if(lane < 2, bars_lane + B_AEMPTY + 16 + 8 * (n & 3)); };
                struct Slot { uint32_t bar, par, off; } slot[4];
                auto align = [&]() {
#pragma unroll
                    for (uint32_t i = 0; i < 4; i++) {
                        const uint32_t n = kvn + (i == 1 ? has_pv : i);
                        slot[i].bar = bars + B_AFULL + 16 + 8 * (n & 3); slot[i].par = (n >> 2) & 1; slot[i].off = (n & 3) * 2048;
                    }
                };
                align();
                auto scale_o = [&]() {
#pragma unroll
                    for (int j = 0; j < 16; j++) { o[4 * j] *= f0; o[4 * j + 1] *= f0; o[4 * j + 2] *= f1; o[4 * j + 3] *= f1; }
                };
                auto pack_o = [&](uint32_t (&v)[32]) {
#pragma unroll
                    for (int j = 0; j < 32; j++) v[j] = pack_bf16(o[2 * j], o[2 * j + 1]);
                };
                auto scales = [&]() { f0 = g0 * rcp(quad_sum(l0)); f1 = g1 * rcp(quad_sum(l1)); };
                auto step = [&](auto even, uint32_t (&pin)[32], uint32_t (&pout)[32], bool fresh, bool diag, bool last) {
                    constexpr bool EVEN = decltype(even)::value;
                    Slot& sk = slot[EVEN ? 0 : 2];
                    Slot& sv = slot[EVEN ? 1 : 3];
                    kvn += EVEN ? 1 + has_pv : 2;
                    mbar_spin(sk.bar, sk.par);
                    bar_sync(1 + wg, 256);
                    qk_gemm(s, dA + qoff, dK + sk.off);
                    if (EVEN && fresh) {
                        scales();
                        g0 = lds_f32(bars + SM_GATE + (ti & 1) * 512 + 4 * row); g1 = lds_f32(bars + SM_GATE + (ti & 1) * 512 + 4 * row + 32);
                        ti++;
                        n0 = 0.f; n1 = 0.f; l0 = 0.f; l1 = 0.f;
                        shifted = 0;
                        if (has_pv) { stage_acquire(0); stage_acquire(1); }
                    }
                    if (!EVEN && pending) {
                        pack_o(pout);
                        write_blocks(std::integral_constant<int, 8>(), 0, pout);
                        publish_pair();
                    }
                    if (last)
                        asm volatile("{\n.reg .pred P, Q;\n"
                                     "mbarrier.test_wait.parity.shared::cta.b64 Q, [%1], %2;\n"
                                     "mbarrier.test_wait.parity.shared::cta.b64 P, [%3], %4;\n"
                                     "ld.shared.u32 %0, [%5];\n"
                                     "@!Q or.b32 %0, %0, 0x10000;\n"
                                     "@!P mov.u32 %0, -1;\n}\n"
                                     : "=r"(peek) : "r"(bars + B_AFULL + 8 * (ti & 1)), "r"((ti >> 1) & 1), "r"(bars + B_IFULL + 8 * (qn % QDEPTH)),
                                       "r"((qn / QDEPTH) & 1), "r"(bars + SM_QUEUE + 4 * (qn % QDEPTH)) : "memory");
                    mbar_spin(sv.bar, sv.par);
                    pv_gemm(o, pin, dV + sv.off, EVEN || !first);
                    bar_arrive(2 - wg, 256);
                    sk.par ^= 1; sv.par ^= 1;
                    wgmma_wait<1>();
                    fence_regs(s);
                    mbar_arrive_cluster_if(lane < 2 && (!EVEN || has_pv), sk.bar + lane_off);
                    mbar_arrive_if(lane == 0 && last, bars + B_AEMPTY + 8 * ((ti - 1) & 1));
                    float r0, r1, x0 = n0, x1 = n1;
#pragma unroll 1
                    for (int mask = diag, redone = 0;; mask = 0, redone = 1) {
                        if (mask | shifted) {
                            if (mask) causal_mask(s, thr, wg);
                            if (shifted) shift_rows(s, x0, x1);
                        }
                        exp_pack(pout, s, r0, r1);
                        if (!__any_sync(0xffffffffu, fmaxf(r0, r1) >= SUM_LIMIT || (EVEN && fresh && !(lane & 3) && !(fminf(s[0], s[2]) >= -REF_RANGE))) || redone) break;
                        row_max(s, x0, x1);
                        if (!(EVEN && fresh)) { x0 = fmaxf(x0, 0.f); x1 = fmaxf(x1, 0.f); }
                        float a0 = ex2(-x0), a1 = ex2(-x1);
                        n0 += x0; n1 += x1;
                        shifted = 1;
                        if (EVEN && fresh) { a0 = 1.f; a1 = 1.f; }
                        l0 *= a0; l1 *= a1;
                        wgmma_wait<0>();
                        fence_regs(o);
#pragma unroll
                        for (int q = 0; q < 16; q++) { o[4 * q] *= a0; o[4 * q + 1] *= a0; o[4 * q + 2] *= a1; o[4 * q + 3] *= a1; }
                    }
                    l0 += r0; l1 += r1;
                    wgmma_wait<0>();
                    fence_regs(o);
                    fence_regs(pin);
                    mbar_arrive_cluster_if(lane < 2, sv.bar + lane_off);
                };
                auto copy_p = [&]() {
#pragma unroll
                    for (int j = 0; j < 32; j++) pa[j] = __float_as_uint(__uint_as_float(pb[j]) + __uint_as_float(prm.zero));
                };
                int rem = 0;
                mbar_spin(bars + B_AFULL + 8 * (ti & 1), (ti >> 1) & 1);
                while (true) {
                    const bool fresh = rem == 0;
                    if (fresh) {
                        if (has_pv) {
                            const int seen = __shfl_sync(0xffffffffu, peek, 0);
                            if (seen >= 0) {
                                mbar_arrive_cluster_if(lane == 0, bars0 + B_IEMPTY + 8 * (qn % QDEPTH));
                                qn++;
                                it = seen & 0xffff;
                            } else {
                                it = take_item();
                            }
                            if (item_row(cur) < 2 || item_type(it) != T_ATTN) break;
                            if (seen & 0x10000) mbar_spin(bars + B_AFULL + 8 * (ti & 1), (ti >> 1) & 1);
                        }
                        cur = it;
                        qoff = (ti & 1) * 2048;
                    }
                    const bool last = fresh ? item_row(cur) == 0 : rem == 1;
                    step(std::true_type(), pa, pb, fresh, item_asc(cur) ? last : fresh, last);
                    first = fresh;
                    if (fresh) {
                        pending = has_pv; has_pv = 1;
                        if (!pending) { kvn -= 2; align(); kvn += 2; slot[0].par ^= 1; slot[1].par ^= 1; }
                        else scale_o();
                        rem = item_row(cur);
                        if (rem == 0) {
                            copy_p();
                            continue;
                        }
                    } else if (--rem == 0) {
                        copy_p();
                        const Slot t0 = slot[0], t1 = slot[1];
                        slot[0] = slot[2]; slot[1] = slot[3]; slot[2] = t0; slot[3] = t1;
                        continue;
                    }
                    step(std::false_type(), pb, pa, false, item_asc(cur) && rem == 1, rem == 1);
                    pending = 0; first = 0;
                    rem--;
                }
                const uint32_t skip = item_asc(cur) & ~item_row(cur) & 1;
                kvn += skip;
                const bool end = item_type(it) == T_END;
#pragma unroll 1
                for (int pass = pending ? 0 : 1; pass < 2; pass++) {
                    if (pass) {
                        kv_wait(kvn);
                        pv_gemm(o, pa, dV + (kvn & 3) * 2048, !first);
                        scales();
                        stage_acquire(0); stage_acquire(1);
                        if (end) it = take_item();
                        wgmma_wait<0>();
                        fence_regs(o);
                        kv_release(kvn);
                        kvn += 1 + skip;
                        scale_o();
                    }
                    pack_o(pb);
                    write_blocks(std::integral_constant<int, 8>(), 0, pb);
                    publish_pair();
                }
                if (end) break;
            }
        }
        if (item_type(it) == T_OUT) {
            float acc[128];
            const uint32_t dB = make_desc(sb + 16384, 8192);
            mbar_spin(bars + B_GFULL, gph);
            wgmma_fence();
            wgmma_ss_n256_tb_init(acc, full_desc(dA), full_desc(dB));
#pragma unroll
            for (int kk = 1; kk < 4; kk++) wgmma_ss_n256_tb(acc, full_desc(dA) + 2 * kk, full_desc(dB) + 128 * kk, 1);
            wgmma_commit();
            uint32_t ln;
            asm volatile("mov.u32 %0, %%laneid;" : "=r"(ln));
            char* const mine = (char*)prm.out + (uint32_t)((item_row(it) * 128 + wg * 64 + wq * 16 + (ln >> 4)) * 2048 + item_col(it) * 256 + (ln & 15) * 16);
            int k = 1, nk = 80;
            do {
                if (k == K_MEET - 5) {
#pragma unroll
                    for (int j = 0; j < 8; j++) *(uint4*)(mine + j * 4096) = make_uint4(0, 0, 0, 0);
                    __syncwarp();
                }
                if (k == K_SPLIT) nk = take_item() & 127;
                gemm_step(acc, dB, k);
            } while (k < nk);
            float lo[64];
            auto triple = [&](auto first) {
                const uint32_t s0 = k & 3, s1 = (k + 1) & 3, o0 = s0 * (GST_BYTES >> 4), o1 = s1 * (GST_BYTES >> 4);
                wgmma_wait<0>();
                mbar_arrive_cluster_if(ln < (decltype(first)::value ? 2 : 4), bars_lane + B_GEMPTY + 8 * ((k - 1 - (ln >> 1)) & 3));
                mbar_spin(bars + B_GFULL + 8 * s0, gph);
                gph ^= s0 == 3;
                wgmma_fence();
#pragma unroll
                for (int kk = 0; kk < 4; kk++) {
                    if (decltype(first)::value && kk == 0) wgmma_ss_n128_tb_init(lo, full_desc(dA + o0), full_desc(dB + o0));
                    else wgmma_ss_n128_tb(lo, full_desc(dA + o0) + 2 * kk, full_desc(dB + o0) + 128 * kk, 1);
                }
                mbar_spin(bars + B_GFULL + 8 * s1, gph);
                gph ^= s1 == 3;
                wgmma_fence();
#pragma unroll
                for (int kk = 0; kk < 4; kk++) wgmma_ss_n128_tb(lo, full_desc(dA + o0 + 2048) + 2 * kk, full_desc(dB + o1 + 1024) + 128 * kk, 1);
#pragma unroll
                for (int kk = 0; kk < 4; kk++) wgmma_ss_n128_tb(lo, full_desc(dA + o1) + 2 * kk, full_desc(dB + o1) + 128 * kk, 1);
                wgmma_commit();
                k += 2;
            };
            triple(std::true_type());
            fence_regs(acc);
            uint32_t pk[32];
#pragma unroll
            for (int j = 0; j < 32; j++) pk[j] = pack_bf16(acc[64 + 2 * j], acc[65 + 2 * j]);
            stage_acquire(0); stage_acquire(1);
            write_blocks(std::integral_constant<int, 8>(), 0, pk);
            publish_pair();
            triple(std::false_type());
            stage_acquire(0); stage_acquire(1);
            wgmma_wait<0>();
            fence_regs(lo);
            mbar_arrive_cluster_if(ln < 4, bars_lane + B_GEMPTY + 8 * ((k - 1 - (ln >> 1)) & 3));
#pragma unroll
            for (int b = 0; b < 2; b++) {
#pragma unroll
                for (int j = 16 * b; j < 16 * b + 16; j++) pk[j] = pack_bf16(acc[2 * j] + lo[2 * j], acc[2 * j + 1] + lo[2 * j + 1]);
                write_blocks(std::integral_constant<int, 4>(), b * 8192, pk + 16 * b);
                stage_publish(b);
            }
        }
    }
}

typedef CUresult (*EncodeFn)(CUtensorMap*, CUtensorMapDataType, cuuint32_t, void*, const cuuint64_t*, const cuuint64_t*,
                             const cuuint32_t*, const cuuint32_t*, CUtensorMapInterleave, CUtensorMapSwizzle,
                             CUtensorMapL2promotion, CUtensorMapFloatOOBfill);

void encode3(EncodeFn fn, CUtensorMap* m, const void* ptr, uint64_t d0, uint64_t d1, uint64_t d2, uint64_t s1, uint64_t s2,
             uint32_t b0, uint32_t b1, uint32_t b2) {
    cuuint64_t dims[3] = {d0, d1, d2};
    cuuint64_t strides[2] = {s1, s2};
    cuuint32_t box[3] = {b0, b1, b2};
    cuuint32_t es[3] = {1, 1, 1};
    fn(m, CU_TENSOR_MAP_DATA_TYPE_BFLOAT16, 3, const_cast<void*>(ptr), dims, strides, box, es, CU_TENSOR_MAP_INTERLEAVE_NONE,
       CU_TENSOR_MAP_SWIZZLE_128B, CU_TENSOR_MAP_L2_PROMOTION_NONE, CU_TENSOR_MAP_FLOAT_OOB_FILL_NONE);
}
void map_act(EncodeFn fn, CUtensorMap* m, const void* p, int rows, int cols, int box_rows) {
    encode3(fn, m, p, cols, rows, 1, (uint64_t)cols * 2, (uint64_t)cols * rows * 2, 64, box_rows, 1);
}
void map_wgt(EncodeFn fn, CUtensorMap* m, const void* p, int K, int N) {
    encode3(fn, m, p, 64, K, N / 64, (uint64_t)N * 2, 128, 64, 64, 2);
}

void build_schedule(Params& p) {
    int n = 0;
    auto add = [&](int type, int col, int row) { p.items[n++] = (uint16_t)(type << 13 | col << 4 | row); };
    int beta = 26, tail = 32, late = 6, early = 8, epos = 100;
    int order[16] = {6, 7, 8, 9, 10, 11, 12, 13, 14, 15, 5, 4, 3, 2, 1, 0};
    const char* plans = "xxcccccx,xxcccccx,xxxxx,xxcxlxx,xxlcclxcc,xxlcccccc,xxlxlccccc,xxlxlxccc";
    const char* pos[8];
    int len[8] = {}, start[8] = {};
    for (int s = 0; s < 8; s++) { pos[s] = plans; while (*plans && *plans++ != ',') {} }
    for (int i = 0; i < 160; i++) p.plan[i / 16][i % 16] = T_END << 13;
    for (int nx = 0, nc = 3, nl = 0; nx + nc + nl < 28 + 32 + 8;) {
        int s = -1;
        for (int i = 0; i < 8; i++) if (*pos[i] > ',' && (s < 0 || start[i] < start[s])) s = i;
        const char kind = *pos[s]++;
        int it;
        if (kind == 'x') { it = nx < 12 ? T_B << 13 | (nx % 3 * 4 + nx / 3) << 4 : T_Q << 13 | (nx - 12) << 4; nx++; }
        else if (kind == 'c') { it = (T_K + (nc & 1)) << 13 | nc / 2 << 4; nc++; }
        else { it = T_LOCAL << 13 | nl / 2 << 4 | (nl & 1); nl++; }
        p.plan[s][len[s]++] = (uint16_t)it;
        start[s] += kind == 'x' ? 48 : kind == 'c' ? 24 : 8;
    }
    for (int i = 0; i < 24; i++) p.plan[8 + i / 12][i % 12] = (uint16_t)((T_K + (i % 3 & 1)) << 13 | i % 3 / 2 << 4 | i / 3);
    const int a0 = n;
    for (int key = 0; key < 4000; key++)
        for (int r = 0; r < 32; r++)
            for (int j = 7; j >= 0; j--)
                if ((j ? (7 - j) * 40 + r * beta : 3999) == key) add(T_ATTN, 2 * order[r >> 1] + (r & 1), j);
    int t0 = n;
    for (int work = 0; work < 32 * 136 * tail / 100;) work += 4 * (p.items[--t0] & 15) + 3;
    for (int i = t0 + 1; i < n; i++)
        for (int j = i; j > t0 && (p.items[j] & 15) > (p.items[j - 1] & 15); j--) { const uint16_t t = p.items[j]; p.items[j] = p.items[j - 1]; p.items[j - 1] = t; }
    for (int r = early - 1; r >= 0; r--) {
        const uint16_t t = p.items[n - 32 + early - 1];
        for (int j = n - 32 + early - 1; j > n - epos; j--) p.items[j] = p.items[j - 1];
        p.items[n - epos] = t;
    }
    for (int moved = 0; moved < 2 && late >= 0; moved++)
        for (int i = a0; i < n; i++)
            if (p.items[i] == (T_ATTN << 13 | (2 * order[15] + moved) << 4 | late)) {
                for (int j = i; j + 1 < n; j++) p.items[j] = p.items[j + 1];
                p.items[n - 1] = (uint16_t)(T_ATTN << 13 | (2 * order[15] + moved) << 4 | late);
                break;
            }
    for (int s = 0, lo = 0, hi = WIDE - 1; s < 80; s++) {
        const int r = s / 2, g = r < 8 ? 32 + r : 2 * order[r / 2 - 4] + (r & 1);
        p.ostep[s >= WIDE ? s : r & 1 ? hi-- : lo++] = (uint8_t)(2 * g + (s & 1));
    }
}

void build_params(Params& p, void* const* d_in, void* d_out) {
    void* fnp = nullptr;
    cudaDriverEntryPointQueryResult qr;
    cudaGetDriverEntryPoint("cuTensorMapEncodeTiled", &fnp, cudaEnableDefault, &qr);
    EncodeFn fn = (EncodeFn)fnp;
    void* scr = nullptr;
    cudaGetSymbolAddress(&scr, g_scr);
    map_act(fn, &p.m[M_X], d_in[0], SEQ, 1024, 128);
    map_act(fn, &p.m[M_C], d_in[1], SEQ, 512, 128);
    map_wgt(fn, &p.m[M_WQ], d_in[2], 1024, 4096);
    map_wgt(fn, &p.m[M_WUK], d_in[3], 512, 4096);
    map_wgt(fn, &p.m[M_WUV], d_in[4], 512, 4096);
    map_wgt(fn, &p.m[M_WO], d_in[5], 4096, 1024);
    map_wgt(fn, &p.m[M_WQKV], d_in[7], 1024, 3072);
    map_wgt(fn, &p.m[M_WOB], d_in[8], 1024, 1024);
    encode3(fn, &p.m[M_SCR_LD], scr, 128, SEQ, G_TOTAL, 256, (uint64_t)SEQ * 256, 64, 128, 1);
    encode3(fn, &p.m[M_SCR_LOC], scr, 256, SEQ / 2, G_TOTAL, 512, (uint64_t)SEQ * 256, 64, 72, 1);
    encode3(fn, &p.m[M_SCR_LOQ], scr, 256, SEQ / 2, G_TOTAL, 512, (uint64_t)SEQ * 256, 64, 64, 1);
    encode3(fn, &p.m[M_SCR_ST], scr, 128, SEQ, G_TOTAL, 256, (uint64_t)SEQ * 256, 64, 64, 1);
    map_act(fn, &p.m[M_OUT], d_out, SEQ, 1024, 64);
    p.x = (const __nv_bfloat16*)d_in[0];
    p.gate_w = (const __nv_bfloat16*)d_in[9];
    p.zero = 0;
    p.wo = (const char*)d_in[5];
    p.out = (__nv_bfloat16*)d_out;
    build_schedule(p);
}

}

extern "C" void kernel_launch(void* const* d_in, const int* in_sizes, int n_in, void* d_out, int out_size) {
    (void)in_sizes; (void)n_in; (void)out_size;
    Params p;
    build_params(p, d_in, d_out);
    cudaFuncSetAttribute(fused_kernel, cudaFuncAttributeMaxDynamicSharedMemorySize, SM_TOTAL);
    fused_kernel<<<NCTA, 384, SM_TOTAL>>>(p);
}
```

```cpp
#include <cuda_runtime.h>
#include <cuda_bf16.h>
#include <cuda.h>
#include <stddef.h>
#include <stdint.h>
#include <type_traits>

namespace {

constexpr int SEQ = 2048;
constexpr int G_Q = 0, G_K = 32, G_V = 64, G_B = 96, G_CTX = G_Q, G_LOC = G_B, G_TOTAL = 120;

__device__ __align__(1024) __nv_bfloat16 g_scr[(size_t)G_TOTAL * SEQ * 128];
__device__ __align__(128) float g_gate[SEQ];

__device__ __forceinline__ uint32_t smem_u32(const void* p) { return (uint32_t)__cvta_generic_to_shared(p); }
__device__ __forceinline__ bool elect_one() {
    uint32_t p;
    asm volatile("{\n.reg .pred P;\nelect.sync _|P, 0xffffffff;\nselp.u32 %0, 1, 0, P;\n}\n" : "=r"(p));
    return p != 0;
}
__device__ __forceinline__ void mbar_init(uint32_t bar, uint32_t count) {
    asm volatile("mbarrier.init.shared::cta.b64 [%0], %1;" :: "r"(bar), "r"(count) : "memory");
}
__device__ __forceinline__ uint32_t cluster_rank() { uint32_t r; asm("mov.u32 %0, %%cluster_ctarank;" : "=r"(r)); return r; }
__device__ __forceinline__ uint32_t map_cta(uint32_t addr, uint32_t cta) {
    uint32_t r; asm("mapa.shared::cluster.u32 %0, %1, %2;" : "=r"(r) : "r"(addr), "r"(cta)); return r;
}
__device__ __forceinline__ void mbar_arrive_cluster_if(bool pred, uint32_t cluster_bar) {
    asm volatile("{\n.reg .pred P;\nsetp.ne.u32 P, %1, 0;\n@P mbarrier.arrive.shared::cluster.b64 _, [%0];\n}\n"
                 :: "r"(cluster_bar), "r"((uint32_t)pred) : "memory");
}
__device__ __forceinline__ void mbar_arrive_cluster_n_if(bool pred, uint32_t cluster_bar, uint32_t count) {
    asm volatile("{\n.reg .pred P;\nsetp.ne.u32 P, %1, 0;\n@P mbarrier.arrive.shared::cluster.b64 _, [%0], %2;\n}\n"
                 :: "r"(cluster_bar), "r"((uint32_t)pred), "r"(count) : "memory");
}
__device__ __forceinline__ void mbar_arrive_if(bool pred, uint32_t bar) {
    asm volatile("{\n.reg .pred P;\nsetp.ne.u32 P, %1, 0;\n@P mbarrier.arrive.shared::cta.b64 _, [%0];\n}\n"
                 :: "r"(bar), "r"((uint32_t)pred) : "memory");
}
__device__ __forceinline__ bool mbar_test(uint32_t bar, uint32_t parity) {
    uint32_t ok;
    asm volatile("{\n.reg .pred P;\nmbarrier.test_wait.parity.shared::cta.b64 P, [%1], %2;\nselp.u32 %0, 1, 0, P;\n}\n"
                 : "=r"(ok) : "r"(bar), "r"(parity) : "memory");
    return ok != 0;
}
__device__ __forceinline__ void mbar_wait(uint32_t bar, uint32_t parity) {
    asm volatile("{\n.reg .pred P;\n.reg .u32 c;\n"
                 "mov.u32 c, 0;\n"
                 "SPIN:\n"
                 "mbarrier.try_wait.parity.shared::cta.b64 P, [%0], %1;\n"
                 "@P bra DONE;\n"
                 "add.u32 c, c, 1;\n"
                 "setp.lt.u32 P, c, 4194304;\n"
                 "@P bra SPIN;\n"
                 "trap;\n"
                 "DONE:\n}\n" :: "r"(bar), "r"(parity) : "memory");
}
__device__ __forceinline__ void mbar_spin(uint32_t bar, uint32_t parity) {
    asm volatile("{\n.reg .pred P;\n"
                 "SPIN:\n"
                 "mbarrier.try_wait.parity.shared::cta.b64 P, [%0], %1;\n"
                 "@!P bra SPIN;\n}\n" :: "r"(bar), "r"(parity) : "memory");
}
__device__ __forceinline__ void bar_sync(int id, int n) { asm volatile("bar.sync %0, %1;" :: "r"(id), "r"(n) : "memory"); }
__device__ __forceinline__ void bar_arrive(int id, int n) { asm volatile("bar.arrive %0, %1;" :: "r"(id), "r"(n) : "memory"); }
__device__ __forceinline__ void fence_proxy_async_smem() { asm volatile("fence.proxy.async.shared::cta;" ::: "memory"); }
__device__ __forceinline__ void warp_expect_tx(uint32_t bar, uint32_t bytes) {
    asm volatile("{\n.reg .pred P;\nelect.sync _|P, 0xffffffff;\n@P mbarrier.arrive.expect_tx.shared::cta.b64 _, [%0], %1;\n}\n"
                 :: "r"(bar), "r"(bytes) : "memory");
}
constexpr uint64_t EVICT_FIRST = 0x12F0000000000000ull;
__device__ __forceinline__ void warp_tma_load(uint32_t dst, const CUtensorMap* map, uint32_t bar, int c0, int c1, int c2, bool stream) {
    if (stream)
        asm volatile("{\n.reg .pred P;\nelect.sync _|P, 0xffffffff;\n"
                     "@P cp.async.bulk.tensor.3d.shared::cluster.global.mbarrier::complete_tx::bytes.L2::cache_hint"
                     " [%0], [%1, {%3, %4, %5}], [%2], %6;\n}\n"
                     :: "r"(dst), "l"(map), "r"(bar), "r"(c0), "r"(c1), "r"(c2), "l"(EVICT_FIRST) : "memory");
    else
        asm volatile("{\n.reg .pred P;\nelect.sync _|P, 0xffffffff;\n"
                     "@P cp.async.bulk.tensor.3d.shared::cluster.global.mbarrier::complete_tx::bytes [%0], [%1, {%3, %4, %5}], [%2];\n}\n"
                     :: "r"(dst), "l"(map), "r"(bar), "r"(c0), "r"(c1), "r"(c2) : "memory");
}
__device__ __forceinline__ void warp_tma_load_pair(uint32_t dst, const CUtensorMap* map, uint32_t bar, int c0, int c1, int c2, bool stream) {
    if (stream)
        asm volatile("{\n.reg .pred P;\nelect.sync _|P, 0xffffffff;\n"
                     "@P cp.async.bulk.tensor.3d.shared::cluster.global.mbarrier::complete_tx::bytes.multicast::cluster.L2::cache_hint"
                     " [%0], [%1, {%3, %4, %5}], [%2], %6, %7;\n}\n"
                     :: "r"(dst), "l"(map), "r"(bar), "r"(c0), "r"(c1), "r"(c2), "h"((uint16_t)3), "l"(EVICT_FIRST) : "memory");
    else
        asm volatile("{\n.reg .pred P;\nelect.sync _|P, 0xffffffff;\n"
                     "@P cp.async.bulk.tensor.3d.shared::cluster.global.mbarrier::complete_tx::bytes.multicast::cluster"
                     " [%0], [%1, {%3, %4, %5}], [%2], %6;\n}\n"
                     :: "r"(dst), "l"(map), "r"(bar), "r"(c0), "r"(c1), "r"(c2), "h"((uint16_t)3) : "memory");
}
__device__ __forceinline__ void warp_bulk_load(uint32_t dst, const void* src, uint32_t bytes, uint32_t bar) {
    asm volatile("{\n.reg .pred P;\nelect.sync _|P, 0xffffffff;\n"
                 "@P cp.async.bulk.shared::cluster.global.mbarrier::complete_tx::bytes [%0], [%1], %2, [%3];\n}\n"
                 :: "r"(dst), "l"(src), "r"(bytes), "r"(bar) : "memory");
}
__device__ __forceinline__ void warp_tma_store(const CUtensorMap* map, uint32_t src, int c0, int c1, int c2, bool stream) {
    if (stream)
        asm volatile("{\n.reg .pred P;\nelect.sync _|P, 0xffffffff;\n"
                     "@P cp.async.bulk.tensor.3d.global.shared::cta.bulk_group.L2::cache_hint [%0, {%2, %3, %4}], [%1], %5;\n}\n"
                     :: "l"(map), "r"(src), "r"(c0), "r"(c1), "r"(c2), "l"(EVICT_FIRST) : "memory");
    else
        asm volatile("{\n.reg .pred P;\nelect.sync _|P, 0xffffffff;\n"
                     "@P cp.async.bulk.tensor.3d.global.shared::cta.bulk_group [%0, {%2, %3, %4}], [%1];\n}\n"
                     :: "l"(map), "r"(src), "r"(c0), "r"(c1), "r"(c2) : "memory");
}
__device__ __forceinline__ void warp_tma_add(const CUtensorMap* map, uint32_t src, int c0, int c1, int c2) {
    asm volatile("{\n.reg .pred P;\nelect.sync _|P, 0xffffffff;\n"
                 "@P cp.reduce.async.bulk.tensor.3d.global.shared::cta.add.tile.bulk_group [%0, {%2, %3, %4}], [%1];\n}\n"
                 :: "l"(map), "r"(src), "r"(c0), "r"(c1), "r"(c2) : "memory");
}
__device__ __forceinline__ void warp_bulk_store(void* dst, uint32_t src, uint32_t bytes) {
    asm volatile("{\n.reg .pred P;\nelect.sync _|P, 0xffffffff;\n"
                 "@P cp.async.bulk.global.shared::cta.bulk_group [%0], [%1], %2;\n}\n" :: "l"(dst), "r"(src), "r"(bytes) : "memory");
}
__device__ __forceinline__ void warp_prefetch(const void* src, uint32_t bytes) {
    asm volatile("{\n.reg .pred P;\nelect.sync _|P, 0xffffffff;\n@P cp.async.bulk.prefetch.L2.global [%0], %1;\n}\n" :: "l"(src), "r"(bytes) : "memory");
}
__device__ __forceinline__ void bulk_commit() { asm volatile("cp.async.bulk.commit_group;" ::: "memory"); }
template <int N> __device__ __forceinline__ void bulk_wait_read() { asm volatile("cp.async.bulk.wait_group.read %0;" :: "n"(N) : "memory"); }
template <int N> __device__ __forceinline__ void bulk_wait() { asm volatile("cp.async.bulk.wait_group %0;" :: "n"(N) : "memory"); }
__device__ __forceinline__ void wgmma_fence() { asm volatile("wgmma.fence.sync.aligned;" ::: "memory"); }
__device__ __forceinline__ void wgmma_commit() { asm volatile("wgmma.commit_group.sync.aligned;" ::: "memory"); }
template <int N> __device__ __forceinline__ void wgmma_wait() { asm volatile("wgmma.wait_group.sync.aligned %0;" :: "n"(N) : "memory"); }
template <int N> __device__ __forceinline__ void fence_regs(float (&d)[N]) {
#pragma unroll
    for (int i = 0; i < N; i++) asm volatile("" : "+f"(d[i]) :: "memory");
}
template <int N> __device__ __forceinline__ void fence_regs(uint32_t (&d)[N]) {
#pragma unroll
    for (int i = 0; i < N; i++) asm volatile("" : "+r"(d[i]) :: "memory");
}
template <int N> __device__ __forceinline__ void reg_dec() { asm volatile("setmaxnreg.dec.sync.aligned.u32 %0;" :: "n"(N)); }
template <int N> __device__ __forceinline__ void reg_inc() { asm volatile("setmaxnreg.inc.sync.aligned.u32 %0;" :: "n"(N)); }
__device__ __forceinline__ uint32_t pack_bf16(float lo, float hi) {
    uint32_t r; asm("cvt.rn.bf16x2.f32 %0, %1, %2;" : "=r"(r) : "f"(hi), "f"(lo)); return r;
}
__device__ __forceinline__ void stmatrix_x4(uint32_t addr, uint32_t r0, uint32_t r1, uint32_t r2, uint32_t r3) {
    asm volatile("stmatrix.sync.aligned.m8n8.x4.shared.b16 [%0], {%1, %2, %3, %4};"
                 :: "r"(addr), "r"(r0), "r"(r1), "r"(r2), "r"(r3) : "memory");
}
__device__ __forceinline__ float ex2(float x) { float y; asm("ex2.approx.ftz.f32 %0, %1;" : "=f"(y) : "f"(x)); return y; }

constexpr uint32_t DESC_HI = (1024 >> 4) | (1u << 30);
__device__ __forceinline__ uint32_t make_desc(uint32_t addr, uint32_t lbo) {
    uint32_t lo = ((addr & 0x3FFFF) >> 4) | ((lbo >> 4) << 16);
    asm volatile("" : "+r"(lo));
    return lo;
}
__device__ __forceinline__ uint64_t full_desc(uint32_t lo) {
    uint64_t d; asm("mov.b64 %0, {%1, %2};" : "=l"(d) : "r"(lo), "r"(DESC_HI)); return d;
}

__device__ __forceinline__ void wgmma_ss_n256_tb_init(float (&d)[128], uint64_t da, uint64_t db) {
    asm volatile("{\n.reg .pred p;\n"
        "setp.ne.b32 p, 0, 0;\n"
        "wgmma.mma_async.sync.aligned.m64n256k16.f32.bf16.bf16 "
        "{%0, %1, %2, %3, %4, %5, %6, %7, %8, %9, %10, %11, %12, %13, %14, %15, %16, %17, %18, %19, %20, "
        "%21, %22, %23, %24, %25, %26, %27, %28, %29, %30, %31, %32, %33, %34, %35, %36, %37, %38, %39, %40, "
        "%41, %42, %43, %44, %45, %46, %47, %48, %49, %50, %51, %52, %53, %54, %55, %56, %57, %58, %59, %60, "
        "%61, %62, %63, %64, %65, %66, %67, %68, %69, %70, %71, %72, %73, %74, %75, %76, %77, %78, %79, %80, "
        "%81, %82, %83, %84, %85, %86, %87, %88, %89, %90, %91, %92, %93, %94, %95, %96, %97, %98, %99, "
        "%100, %101, %102, %103, %104, %105, %106, %107, %108, %109, %110, %111, %112, %113, %114, %115, "
        "%116, %117, %118, %119, %120, %121, %122, %123, %124, %125, %126, %127},"
        " %128, %129, p, 1, 1, 0, 1;\n}\n"
        : "=f"(d[0]), "=f"(d[1]), "=f"(d[2]), "=f"(d[3]), "=f"(d[4]), "=f"(d[5]), "=f"(d[6]), "=f"(d[7]),
        "=f"(d[8]), "=f"(d[9]), "=f"(d[10]), "=f"(d[11]), "=f"(d[12]), "=f"(d[13]), "=f"(d[14]), "=f"(d[15]),
        "=f"(d[16]), "=f"(d[17]), "=f"(d[18]), "=f"(d[19]), "=f"(d[20]), "=f"(d[21]), "=f"(d[22]),
        "=f"(d[23]), "=f"(d[24]), "=f"(d[25]), "=f"(d[26]), "=f"(d[27]), "=f"(d[28]), "=f"(d[29]),
        "=f"(d[30]), "=f"(d[31]), "=f"(d[32]), "=f"(d[33]), "=f"(d[34]), "=f"(d[35]), "=f"(d[36]),
        "=f"(d[37]), "=f"(d[38]), "=f"(d[39]), "=f"(d[40]), "=f"(d[41]), "=f"(d[42]), "=f"(d[43]),
        "=f"(d[44]), "=f"(d[45]), "=f"(d[46]), "=f"(d[47]), "=f"(d[48]), "=f"(d[49]), "=f"(d[50]),
        "=f"(d[51]), "=f"(d[52]), "=f"(d[53]), "=f"(d[54]), "=f"(d[55]), "=f"(d[56]), "=f"(d[57]),
        "=f"(d[58]), "=f"(d[59]), "=f"(d[60]), "=f"(d[61]), "=f"(d[62]), "=f"(d[63]), "=f"(d[64]),
        "=f"(d[65]), "=f"(d[66]), "=f"(d[67]), "=f"(d[68]), "=f"(d[69]), "=f"(d[70]), "=f"(d[71]),
        "=f"(d[72]), "=f"(d[73]), "=f"(d[74]), "=f"(d[75]), "=f"(d[76]), "=f"(d[77]), "=f"(d[78]),
        "=f"(d[79]), "=f"(d[80]), "=f"(d[81]), "=f"(d[82]), "=f"(d[83]), "=f"(d[84]), "=f"(d[85]),
        "=f"(d[86]), "=f"(d[87]), "=f"(d[88]), "=f"(d[89]), "=f"(d[90]), "=f"(d[91]), "=f"(d[92]),
        "=f"(d[93]), "=f"(d[94]), "=f"(d[95]), "=f"(d[96]), "=f"(d[97]), "=f"(d[98]), "=f"(d[99]),
        "=f"(d[100]), "=f"(d[101]), "=f"(d[102]), "=f"(d[103]), "=f"(d[104]), "=f"(d[105]), "=f"(d[106]),
        "=f"(d[107]), "=f"(d[108]), "=f"(d[109]), "=f"(d[110]), "=f"(d[111]), "=f"(d[112]), "=f"(d[113]),
        "=f"(d[114]), "=f"(d[115]), "=f"(d[116]), "=f"(d[117]), "=f"(d[118]), "=f"(d[119]), "=f"(d[120]),
        "=f"(d[121]), "=f"(d[122]), "=f"(d[123]), "=f"(d[124]), "=f"(d[125]), "=f"(d[126]), "=f"(d[127])
        : "l"(da), "l"(db));
}
__device__ __forceinline__ void wgmma_ss_n256_tb(float (&d)[128], uint64_t da, uint64_t db, int scale_d) {
    asm volatile("{\n.reg .pred p;\n"
        "setp.ne.b32 p, %130, 0;\n"
        "wgmma.mma_async.sync.aligned.m64n256k16.f32.bf16.bf16 "
        "{%0, %1, %2, %3, %4, %5, %6, %7, %8, %9, %10, %11, %12, %13, %14, %15, %16, %17, %18, %19, %20, "
        "%21, %22, %23, %24, %25, %26, %27, %28, %29, %30, %31, %32, %33, %34, %35, %36, %37, %38, %39, %40, "
        "%41, %42, %43, %44, %45, %46, %47, %48, %49, %50, %51, %52, %53, %54, %55, %56, %57, %58, %59, %60, "
        "%61, %62, %63, %64, %65, %66, %67, %68, %69, %70, %71, %72, %73, %74, %75, %76, %77, %78, %79, %80, "
        "%81, %82, %83, %84, %85, %86, %87, %88, %89, %90, %91, %92, %93, %94, %95, %96, %97, %98, %99, "
        "%100, %101, %102, %103, %104, %105, %106, %107, %108, %109, %110, %111, %112, %113, %114, %115, "
        "%116, %117, %118, %119, %120, %121, %122, %123, %124, %125, %126, %127},"
        " %128, %129, p, 1, 1, 0, 1;\n}\n"
        : "+f"(d[0]), "+f"(d[1]), "+f"(d[2]), "+f"(d[3]), "+f"(d[4]), "+f"(d[5]), "+f"(d[6]), "+f"(d[7]),
        "+f"(d[8]), "+f"(d[9]), "+f"(d[10]), "+f"(d[11]), "+f"(d[12]), "+f"(d[13]), "+f"(d[14]), "+f"(d[15]),
        "+f"(d[16]), "+f"(d[17]), "+f"(d[18]), "+f"(d[19]), "+f"(d[20]), "+f"(d[21]), "+f"(d[22]),
        "+f"(d[23]), "+f"(d[24]), "+f"(d[25]), "+f"(d[26]), "+f"(d[27]), "+f"(d[28]), "+f"(d[29]),
        "+f"(d[30]), "+f"(d[31]), "+f"(d[32]), "+f"(d[33]), "+f"(d[34]), "+f"(d[35]), "+f"(d[36]),
        "+f"(d[37]), "+f"(d[38]), "+f"(d[39]), "+f"(d[40]), "+f"(d[41]), "+f"(d[42]), "+f"(d[43]),
        "+f"(d[44]), "+f"(d[45]), "+f"(d[46]), "+f"(d[47]), "+f"(d[48]), "+f"(d[49]), "+f"(d[50]),
        "+f"(d[51]), "+f"(d[52]), "+f"(d[53]), "+f"(d[54]), "+f"(d[55]), "+f"(d[56]), "+f"(d[57]),
        "+f"(d[58]), "+f"(d[59]), "+f"(d[60]), "+f"(d[61]), "+f"(d[62]), "+f"(d[63]), "+f"(d[64]),
        "+f"(d[65]), "+f"(d[66]), "+f"(d[67]), "+f"(d[68]), "+f"(d[69]), "+f"(d[70]), "+f"(d[71]),
        "+f"(d[72]), "+f"(d[73]), "+f"(d[74]), "+f"(d[75]), "+f"(d[76]), "+f"(d[77]), "+f"(d[78]),
        "+f"(d[79]), "+f"(d[80]), "+f"(d[81]), "+f"(d[82]), "+f"(d[83]), "+f"(d[84]), "+f"(d[85]),
        "+f"(d[86]), "+f"(d[87]), "+f"(d[88]), "+f"(d[89]), "+f"(d[90]), "+f"(d[91]), "+f"(d[92]),
        "+f"(d[93]), "+f"(d[94]), "+f"(d[95]), "+f"(d[96]), "+f"(d[97]), "+f"(d[98]), "+f"(d[99]),
        "+f"(d[100]), "+f"(d[101]), "+f"(d[102]), "+f"(d[103]), "+f"(d[104]), "+f"(d[105]), "+f"(d[106]),
        "+f"(d[107]), "+f"(d[108]), "+f"(d[109]), "+f"(d[110]), "+f"(d[111]), "+f"(d[112]), "+f"(d[113]),
        "+f"(d[114]), "+f"(d[115]), "+f"(d[116]), "+f"(d[117]), "+f"(d[118]), "+f"(d[119]), "+f"(d[120]),
        "+f"(d[121]), "+f"(d[122]), "+f"(d[123]), "+f"(d[124]), "+f"(d[125]), "+f"(d[126]), "+f"(d[127])
        : "l"(da), "l"(db), "r"(scale_d));
}
__device__ __forceinline__ void wgmma_ss_n128(float (&d)[64], uint64_t da, uint64_t db, int scale_d) {
    asm volatile("{\n.reg .pred p;\n"
        "setp.ne.b32 p, %66, 0;\n"
        "wgmma.mma_async.sync.aligned.m64n128k16.f32.bf16.bf16 "
        "{%0, %1, %2, %3, %4, %5, %6, %7, %8, %9, %10, %11, %12, %13, %14, %15, %16, %17, %18, %19, %20, "
        "%21, %22, %23, %24, %25, %26, %27, %28, %29, %30, %31, %32, %33, %34, %35, %36, %37, %38, %39, %40, "
        "%41, %42, %43, %44, %45, %46, %47, %48, %49, %50, %51, %52, %53, %54, %55, %56, %57, %58, %59, %60, "
        "%61, %62, %63},"
        " %64, %65, p, 1, 1, 0, 0;\n}\n"
        : "+f"(d[0]), "+f"(d[1]), "+f"(d[2]), "+f"(d[3]), "+f"(d[4]), "+f"(d[5]), "+f"(d[6]), "+f"(d[7]),
        "+f"(d[8]), "+f"(d[9]), "+f"(d[10]), "+f"(d[11]), "+f"(d[12]), "+f"(d[13]), "+f"(d[14]), "+f"(d[15]),
        "+f"(d[16]), "+f"(d[17]), "+f"(d[18]), "+f"(d[19]), "+f"(d[20]), "+f"(d[21]), "+f"(d[22]),
        "+f"(d[23]), "+f"(d[24]), "+f"(d[25]), "+f"(d[26]), "+f"(d[27]), "+f"(d[28]), "+f"(d[29]),
        "+f"(d[30]), "+f"(d[31]), "+f"(d[32]), "+f"(d[33]), "+f"(d[34]), "+f"(d[35]), "+f"(d[36]),
        "+f"(d[37]), "+f"(d[38]), "+f"(d[39]), "+f"(d[40]), "+f"(d[41]), "+f"(d[42]), "+f"(d[43]),
        "+f"(d[44]), "+f"(d[45]), "+f"(d[46]), "+f"(d[47]), "+f"(d[48]), "+f"(d[49]), "+f"(d[50]),
        "+f"(d[51]), "+f"(d[52]), "+f"(d[53]), "+f"(d[54]), "+f"(d[55]), "+f"(d[56]), "+f"(d[57]),
        "+f"(d[58]), "+f"(d[59]), "+f"(d[60]), "+f"(d[61]), "+f"(d[62]), "+f"(d[63])
        : "l"(da), "l"(db), "r"(scale_d));
}
__device__ __forceinline__ void wgmma_rs_n128_tb(float (&d)[64], uint32_t a0, uint32_t a1, uint32_t a2, uint32_t a3, uint64_t db, int scale_d) {
    asm volatile("{\n.reg .pred p;\n"
        "setp.ne.b32 p, %69, 0;\n"
        "wgmma.mma_async.sync.aligned.m64n128k16.f32.bf16.bf16 "
        "{%0, %1, %2, %3, %4, %5, %6, %7, %8, %9, %10, %11, %12, %13, %14, %15, %16, %17, %18, %19, %20, "
        "%21, %22, %23, %24, %25, %26, %27, %28, %29, %30, %31, %32, %33, %34, %35, %36, %37, %38, %39, %40, "
        "%41, %42, %43, %44, %45, %46, %47, %48, %49, %50, %51, %52, %53, %54, %55, %56, %57, %58, %59, %60, "
        "%61, %62, %63},"
        " {%64, %65, %66, %67}, %68, p, 1, 1, 1;\n}\n"
        : "+f"(d[0]), "+f"(d[1]), "+f"(d[2]), "+f"(d[3]), "+f"(d[4]), "+f"(d[5]), "+f"(d[6]), "+f"(d[7]),
        "+f"(d[8]), "+f"(d[9]), "+f"(d[10]), "+f"(d[11]), "+f"(d[12]), "+f"(d[13]), "+f"(d[14]), "+f"(d[15]),
        "+f"(d[16]), "+f"(d[17]), "+f"(d[18]), "+f"(d[19]), "+f"(d[20]), "+f"(d[21]), "+f"(d[22]),
        "+f"(d[23]), "+f"(d[24]), "+f"(d[25]), "+f"(d[26]), "+f"(d[27]), "+f"(d[28]), "+f"(d[29]),
        "+f"(d[30]), "+f"(d[31]), "+f"(d[32]), "+f"(d[33]), "+f"(d[34]), "+f"(d[35]), "+f"(d[36]),
        "+f"(d[37]), "+f"(d[38]), "+f"(d[39]), "+f"(d[40]), "+f"(d[41]), "+f"(d[42]), "+f"(d[43]),
        "+f"(d[44]), "+f"(d[45]), "+f"(d[46]), "+f"(d[47]), "+f"(d[48]), "+f"(d[49]), "+f"(d[50]),
        "+f"(d[51]), "+f"(d[52]), "+f"(d[53]), "+f"(d[54]), "+f"(d[55]), "+f"(d[56]), "+f"(d[57]),
        "+f"(d[58]), "+f"(d[59]), "+f"(d[60]), "+f"(d[61]), "+f"(d[62]), "+f"(d[63])
        : "r"(a0), "r"(a1), "r"(a2), "r"(a3), "l"(db), "r"(scale_d));
}
__device__ __forceinline__ void wgmma_ss_n128_tb_init(float (&d)[64], uint64_t da, uint64_t db) {
    asm volatile("{\n.reg .pred p;\n"
        "setp.ne.b32 p, 0, 0;\n"
        "wgmma.mma_async.sync.aligned.m64n128k16.f32.bf16.bf16 "
        "{%0, %1, %2, %3, %4, %5, %6, %7, %8, %9, %10, %11, %12, %13, %14, %15, %16, %17, %18, %19, %20, "
        "%21, %22, %23, %24, %25, %26, %27, %28, %29, %30, %31, %32, %33, %34, %35, %36, %37, %38, %39, %40, "
        "%41, %42, %43, %44, %45, %46, %47, %48, %49, %50, %51, %52, %53, %54, %55, %56, %57, %58, %59, %60, "
        "%61, %62, %63},"
        " %64, %65, p, 1, 1, 0, 1;\n}\n"
        : "=f"(d[0]), "=f"(d[1]), "=f"(d[2]), "=f"(d[3]), "=f"(d[4]), "=f"(d[5]), "=f"(d[6]), "=f"(d[7]),
        "=f"(d[8]), "=f"(d[9]), "=f"(d[10]), "=f"(d[11]), "=f"(d[12]), "=f"(d[13]), "=f"(d[14]), "=f"(d[15]),
        "=f"(d[16]), "=f"(d[17]), "=f"(d[18]), "=f"(d[19]), "=f"(d[20]), "=f"(d[21]), "=f"(d[22]),
        "=f"(d[23]), "=f"(d[24]), "=f"(d[25]), "=f"(d[26]), "=f"(d[27]), "=f"(d[28]), "=f"(d[29]),
        "=f"(d[30]), "=f"(d[31]), "=f"(d[32]), "=f"(d[33]), "=f"(d[34]), "=f"(d[35]), "=f"(d[36]),
        "=f"(d[37]), "=f"(d[38]), "=f"(d[39]), "=f"(d[40]), "=f"(d[41]), "=f"(d[42]), "=f"(d[43]),
        "=f"(d[44]), "=f"(d[45]), "=f"(d[46]), "=f"(d[47]), "=f"(d[48]), "=f"(d[49]), "=f"(d[50]),
        "=f"(d[51]), "=f"(d[52]), "=f"(d[53]), "=f"(d[54]), "=f"(d[55]), "=f"(d[56]), "=f"(d[57]),
        "=f"(d[58]), "=f"(d[59]), "=f"(d[60]), "=f"(d[61]), "=f"(d[62]), "=f"(d[63])
        : "l"(da), "l"(db));
}
__device__ __forceinline__ void wgmma_ss_n128_tb(float (&d)[64], uint64_t da, uint64_t db, int scale_d) {
    asm volatile("{\n.reg .pred p;\n"
        "setp.ne.b32 p, %66, 0;\n"
        "wgmma.mma_async.sync.aligned.m64n128k16.f32.bf16.bf16 "
        "{%0, %1, %2, %3, %4, %5, %6, %7, %8, %9, %10, %11, %12, %13, %14, %15, %16, %17, %18, %19, %20, "
        "%21, %22, %23, %24, %25, %26, %27, %28, %29, %30, %31, %32, %33, %34, %35, %36, %37, %38, %39, %40, "
        "%41, %42, %43, %44, %45, %46, %47, %48, %49, %50, %51, %52, %53, %54, %55, %56, %57, %58, %59, %60, "
        "%61, %62, %63},"
        " %64, %65, p, 1, 1, 0, 1;\n}\n"
        : "+f"(d[0]), "+f"(d[1]), "+f"(d[2]), "+f"(d[3]), "+f"(d[4]), "+f"(d[5]), "+f"(d[6]), "+f"(d[7]),
        "+f"(d[8]), "+f"(d[9]), "+f"(d[10]), "+f"(d[11]), "+f"(d[12]), "+f"(d[13]), "+f"(d[14]), "+f"(d[15]),
        "+f"(d[16]), "+f"(d[17]), "+f"(d[18]), "+f"(d[19]), "+f"(d[20]), "+f"(d[21]), "+f"(d[22]),
        "+f"(d[23]), "+f"(d[24]), "+f"(d[25]), "+f"(d[26]), "+f"(d[27]), "+f"(d[28]), "+f"(d[29]),
        "+f"(d[30]), "+f"(d[31]), "+f"(d[32]), "+f"(d[33]), "+f"(d[34]), "+f"(d[35]), "+f"(d[36]),
        "+f"(d[37]), "+f"(d[38]), "+f"(d[39]), "+f"(d[40]), "+f"(d[41]), "+f"(d[42]), "+f"(d[43]),
        "+f"(d[44]), "+f"(d[45]), "+f"(d[46]), "+f"(d[47]), "+f"(d[48]), "+f"(d[49]), "+f"(d[50]),
        "+f"(d[51]), "+f"(d[52]), "+f"(d[53]), "+f"(d[54]), "+f"(d[55]), "+f"(d[56]), "+f"(d[57]),
        "+f"(d[58]), "+f"(d[59]), "+f"(d[60]), "+f"(d[61]), "+f"(d[62]), "+f"(d[63])
        : "l"(da), "l"(db), "r"(scale_d));
}

enum { M_X = 0, M_C, M_WQ, M_WUK, M_WUV, M_WQKV, M_WO, M_WOB, M_SCR_LD, M_SCR_LOC, M_SCR_LOQ, M_SCR_ST, M_OUT, M_COUNT };
enum { T_Q = 0, T_K, T_V, T_B, T_OUT, T_LOCAL, T_ATTN, T_END };
constexpr int NCTA = 132;
constexpr int NITEMS = 256;
constexpr int TRIPLES = 2, WIDE = 80 - 3 * TRIPLES;
struct Params {
    CUtensorMap m[M_COUNT];
    const __nv_bfloat16* x;
    const __nv_bfloat16* gate_w;
    const char* wo;
    __nv_bfloat16* out;
    uint32_t zero;
    uint16_t plan[10][16];
    uint16_t items[NITEMS];
    uint8_t ostep[80];
};
__device__ __forceinline__ int item_type(int it) { return it >> 13; }
__device__ __forceinline__ int item_row(int it) { return it & 15; }
__device__ __forceinline__ int item_col(int it) { return (it >> 4) & 31; }
__device__ __forceinline__ int item_asc(int it) { return (it >> 9) & 1; }
constexpr int ITEM_READY = 1 << 10;

struct __align__(128) Sync {
    unsigned long long count[4];
    __align__(128) unsigned long long ctx[16];
    unsigned next, next_out, done;
    __align__(128) unsigned step[32][2];
    unsigned split[32];
};
__device__ Sync g_sync;

constexpr uint32_t GST_BYTES = 49152, SM_KV = 65536, SM_STAGING = 196608, SM_BARS = SM_STAGING + 32768;
constexpr uint32_t B_GFULL = 0, B_GEMPTY = 32, B_AFULL = 64, B_AEMPTY = 112, B_SFULL = 160, B_SEMPTY = 192,
                   B_IFULL = 224, B_IEMPTY = 288, B_XFREE = 352, B_WANT = 384, B_MEET = 392, B_HALF = 416,
                   SM_ORDY = 448, SM_QUEUE = 456, B_ALT = 488, B_QFREE = 504, SM_GATE = 512, SM_TOTAL = SM_BARS + 1536;
constexpr int QDEPTH = 8;
constexpr int FIRST_PAIR = 6;
constexpr int K_MEET = 16, K_SPLIT = 30;
constexpr int K_FETCH = 20;
constexpr uint32_t LOC_PLANE = 72 * 128;
constexpr float LOC_SCALE = 0.17677669529663687f * 1.4426950408889634f;
constexpr float SUM_LIMIT = 1152921504606846976.f;
constexpr float REF_RANGE = 32.f;

__device__ __forceinline__ unsigned ld_acquire(const unsigned* p) {
    unsigned v; asm volatile("ld.acquire.gpu.global.u32 %0, [%1];" : "=r"(v) : "l"(p) : "memory"); return v;
}
__device__ __forceinline__ unsigned long long ld_acquire(const unsigned long long* p) {
    unsigned long long v; asm volatile("ld.acquire.gpu.global.u64 %0, [%1];" : "=l"(v) : "l"(p) : "memory"); return v;
}
__device__ __forceinline__ void spin_guard(unsigned& n) {
    asm volatile("{\n.reg .pred P;\nadd.u32 %0, %0, 1;\nsetp.gt.u32 P, %0, 16777216;\n@P trap;\n}\n" : "+r"(n));
    if (n > 1) __nanosleep(100);
}
__device__ __forceinline__ void red_add(unsigned long long* p, unsigned long long v) {
    asm volatile("red.release.gpu.global.add.u64 [%0], %1;" :: "l"(p), "l"(v) : "memory");
}
__device__ __forceinline__ float rcp(float x) { float y; asm("rcp.approx.ftz.f32 %0, %1;" : "=f"(y) : "f"(x)); return y; }
__device__ __forceinline__ float lds_f32(uint32_t addr) {
    float v; asm volatile("ld.shared.f32 %0, [%1];" : "=f"(v) : "r"(addr) : "memory"); return v;
}
__device__ __forceinline__ void ldsm_x4(uint32_t (&r)[4], uint32_t addr) {
    asm volatile("ldmatrix.sync.aligned.m8n8.x4.shared.b16 {%0, %1, %2, %3}, [%4];"
                 : "=r"(r[0]), "=r"(r[1]), "=r"(r[2]), "=r"(r[3]) : "r"(addr) : "memory");
}
__device__ __forceinline__ void ldsm_x4_t(uint32_t (&r)[4], uint32_t addr) {
    asm volatile("ldmatrix.sync.aligned.m8n8.x4.trans.shared.b16 {%0, %1, %2, %3}, [%4];"
                 : "=r"(r[0]), "=r"(r[1]), "=r"(r[2]), "=r"(r[3]) : "r"(addr) : "memory");
}
__device__ __forceinline__ void mma_k16(float (&d)[4], const uint32_t (&a)[4], uint32_t b0, uint32_t b1) {
    asm("mma.sync.aligned.m16n8k16.row.col.f32.bf16.bf16.f32 {%0,%1,%2,%3}, {%4,%5,%6,%7}, {%8,%9}, {%0,%1,%2,%3};"
        : "+f"(d[0]), "+f"(d[1]), "+f"(d[2]), "+f"(d[3]) : "r"(a[0]), "r"(a[1]), "r"(a[2]), "r"(a[3]), "r"(b0), "r"(b1));
}
__device__ __forceinline__ void mma_k16_init(float (&d)[4], const uint32_t (&a)[4], uint32_t b0, uint32_t b1) {
    asm("{\n.reg .f32 z;\nmov.f32 z, 0f00000000;\n"
        "mma.sync.aligned.m16n8k16.row.col.f32.bf16.bf16.f32 {%0,%1,%2,%3}, {%4,%5,%6,%7}, {%8,%9}, {z,z,z,z};\n}\n"
        : "=f"(d[0]), "=f"(d[1]), "=f"(d[2]), "=f"(d[3]) : "r"(a[0]), "r"(a[1]), "r"(a[2]), "r"(a[3]), "r"(b0), "r"(b1));
}
__device__ __forceinline__ void mma_k8(float (&d)[4], uint32_t a0, uint32_t a1, uint32_t b0) {
    asm("mma.sync.aligned.m16n8k8.row.col.f32.bf16.bf16.f32 {%0,%1,%2,%3}, {%4,%5}, {%6}, {%0,%1,%2,%3};"
        : "+f"(d[0]), "+f"(d[1]), "+f"(d[2]), "+f"(d[3]) : "r"(a0), "r"(a1), "r"(b0));
}
template <typename T, int N> __device__ __forceinline__ void zero_regs(T (&d)[N]) {
#pragma unroll
    for (int i = 0; i < N; i++) d[i] = 0;
}
__device__ __forceinline__ float quad_max(float v) {
    v = fmaxf(v, __shfl_xor_sync(0xffffffffu, v, 1));
    return fmaxf(v, __shfl_xor_sync(0xffffffffu, v, 2));
}
__device__ __forceinline__ float quad_sum(float v) {
    v += __shfl_xor_sync(0xffffffffu, v, 1);
    return v + __shfl_xor_sync(0xffffffffu, v, 2);
}

__device__ __forceinline__ void qk_gemm(float (&s)[64], uint32_t q_lo, uint32_t k_lo) {
    const uint64_t dq = full_desc(q_lo), dk = full_desc(k_lo);
    fence_regs(s);
    wgmma_fence();
#pragma unroll
    for (int kk = 0; kk < 8; kk++) {
        const uint32_t o = (kk >> 2) * 1024 + (kk & 3) * 2;
        wgmma_ss_n128(s, dq + o, dk + o, kk != 0);
    }
    wgmma_commit();
}
__device__ __forceinline__ void pv_gemm(float (&o)[64], uint32_t (&p)[32], uint32_t v_lo, int accumulate) {
    const uint64_t dv = full_desc(v_lo);
    fence_regs(o);
    fence_regs(p);
    wgmma_fence();
#pragma unroll
    for (int kk = 0; kk < 8; kk++)
        wgmma_rs_n128_tb(o, p[4 * kk], p[4 * kk + 1], p[4 * kk + 2], p[4 * kk + 3], dv + kk * 128, kk != 0 || accumulate);
    wgmma_commit();
}
__device__ __forceinline__ void row_max(const float (&s)[64], float& x0, float& x1) {
    float z0 = fmaxf(s[0], s[1]), z1 = fmaxf(s[2], s[3]);
    x0 = fmaxf(s[4], s[5]); x1 = fmaxf(s[6], s[7]);
#pragma unroll
    for (int j = 2; j < 16; j += 2) {
        z0 = fmaxf(z0, fmaxf(s[4 * j], s[4 * j + 1]));
        z1 = fmaxf(z1, fmaxf(s[4 * j + 2], s[4 * j + 3]));
        x0 = fmaxf(x0, fmaxf(s[4 * j + 4], s[4 * j + 5]));
        x1 = fmaxf(x1, fmaxf(s[4 * j + 6], s[4 * j + 7]));
    }
    x0 = quad_max(fmaxf(x0, z0)); x1 = quad_max(fmaxf(x1, z1));
}
__device__ __forceinline__ void exp_pack(uint32_t (&p)[32], const float (&s)[64], float& r0, float& r1) {
#pragma unroll
    for (int j = 0; j < 16; j++) {
        const float e0 = ex2(s[4 * j]), e1 = ex2(s[4 * j + 1]), e2 = ex2(s[4 * j + 2]), e3 = ex2(s[4 * j + 3]);
        if (j == 0) { r0 = e0 + e1; r1 = e2 + e3; }
        else { r0 += e0 + e1; r1 += e2 + e3; }
        p[2 * j] = pack_bf16(e0, e1);
        p[2 * j + 1] = pack_bf16(e2, e3);
    }
}
__device__ __forceinline__ void shift_rows(float (&s)[64], float d0, float d1) {
#pragma unroll
    for (int j = 0; j < 16; j++) { s[4 * j] -= d0; s[4 * j + 1] -= d0; s[4 * j + 2] -= d1; s[4 * j + 3] -= d1; }
}
constexpr float MASKED = -3e38f;
template <int J0>
__device__ __forceinline__ void mask_triangle(float (&s)[64], float thr) {
#pragma unroll
    for (int j = 0; j < 16; j++) {
        const float m = __saturatef((float)(8 * (j >> 1) + (j & 1)) - thr);
        const int i = 4 * (J0 + (j >> 1)) + (j & 1);
        s[i] = fmaf(m, MASKED, s[i]);
        if (j < 14) s[i + 6] = fmaf(m, MASKED, s[i + 6]);
    }
}
__device__ __forceinline__ void causal_mask(float (&s)[64], float thr, int wg) {
    asm volatile("" : "+f"(thr));
    if (wg == 0) {
        mask_triangle<0>(s, thr);
#pragma unroll
        for (int j = 32; j < 64; j++) s[j] += MASKED;
    } else {
        mask_triangle<8>(s, thr);
    }
}

__global__ void __cluster_dims__(2, 1, 1) __launch_bounds__(384, 1) fused_kernel(const __grid_constant__ Params prm) {
    extern __shared__ __align__(1024) uint8_t smem[];
    const uint32_t sb = smem_u32(smem), bars = sb + SM_BARS;
    const int warp = __shfl_sync(0xffffffffu, threadIdx.x >> 5, 0), lane = threadIdx.x & 31;

    const uint32_t rank = cluster_rank();
    const uint32_t bars0 = map_cta(bars, 0), bars_peer = map_cta(bars, rank ^ 1);

    auto plan_index = [&]() -> uint32_t {
        uint32_t p = blockIdx.x >> 1;
        asm volatile("" : "+r"(p));
        const uint32_t r = (p - 36) * 37 >> 8;
        return p < 4 ? 60 + p : p < 36 ? (p - 4 & 7) * 8 + (p - 4 >> 3) : p < 64 ? (p - 36 - 7 * r) * 8 + 4 + r : p;
    };
    auto first_item = [&]() -> int {
        const uint32_t pair = plan_index();
        const uint32_t slot = pair & 7, c = slot * 11 >> 5;
        return pair < 64 ? T_B << 13 | (4 * slot - 11 * c) << 4 | (2 * (pair >> 3) + rank) : T_K << 13 | (8 * slot + rank);
    };
    if (warp == 0) {
        if (elect_one()) {
            for (int k = 0; k < 4; k++) mbar_init(bars + B_GFULL + 8 * k, 1);
            asm volatile("fence.mbarrier_init.release.cluster;" ::: "memory");
            fence_proxy_async_smem();
        }
        __syncwarp();
        const int first_it = __shfl_sync(0xffffffffu, first_item(), 0);
        asm volatile("barrier.cluster.arrive.relaxed.aligned;" ::: "memory");
        const CUtensorMap* ma = &prm.m[item_type(first_it) == T_K ? M_C : M_X];
        const CUtensorMap* mb = &prm.m[M_WQ + item_type(first_it)];
#pragma unroll
        for (int k = 0; k < 2; k++) {
            const uint32_t dst = sb + k * GST_BYTES, fb = bars + B_GFULL + 8 * k;
            warp_expect_tx(fb, GST_BYTES);
            warp_tma_load(dst + 16384, mb, fb, 0, k * 64, item_col(first_it) * 4, true);
            warp_tma_load(dst, ma, fb, k * 64, item_row(first_it) * 128, 0, false);
            warp_tma_load(dst + 32768, mb, fb, 0, k * 64, item_col(first_it) * 4 + 2, true);
        }
    }
    if (threadIdx.x == 32) {
        for (int i = 0; i < 4; i++) mbar_init(bars + B_GEMPTY + 8 * i, 16);
        for (int i = 0; i < 6; i++) { mbar_init(bars + B_AFULL + 8 * i, 1); mbar_init(bars + B_AEMPTY + 8 * i, i < 2 ? 8 : 16); }
        for (int i = 0; i < 4; i++) { mbar_init(bars + B_SFULL + 8 * i, 4); mbar_init(bars + B_SEMPTY + 8 * i, 1); }
        for (int i = 0; i < QDEPTH; i++) { mbar_init(bars + B_IFULL + 8 * i, 1); mbar_init(bars + B_IEMPTY + 8 * i, 23); }
        mbar_init(bars + B_WANT, 2); mbar_init(bars + B_MEET, 1); mbar_init(bars + B_XFREE, 1);
        for (int i = 0; i < 4; i++) mbar_init(bars + B_HALF + 8 * i, 1);
        mbar_init(bars + B_ALT, 4); mbar_init(bars + B_ALT + 8, 4); mbar_init(bars + B_QFREE, 2);
        asm volatile("st.shared.u64 [%0], 0;" :: "r"(bars + SM_ORDY) : "memory");
        asm volatile("fence.mbarrier_init.release.cluster;\nfence.acq_rel.cta;" ::: "memory");
    }
    __syncwarp();
    if (warp != 0) asm volatile("barrier.cluster.arrive.relaxed.aligned;" ::: "memory");
    asm volatile("barrier.cluster.wait.acquire.aligned;" ::: "memory");

    uint32_t qn = 0;
    auto next_item = [&](bool releaser, bool bounded = true) -> int {
        const uint32_t slot = qn % QDEPTH;
        if (bounded) mbar_wait(bars + B_IFULL + 8 * slot, (qn / QDEPTH) & 1);
        else mbar_spin(bars + B_IFULL + 8 * slot, (qn / QDEPTH) & 1);
        uint32_t it;
        asm volatile("ld.shared.u32 %0, [%1];" : "=r"(it) : "r"(bars + SM_QUEUE + 4 * slot) : "memory");
        mbar_arrive_cluster_if(releaser, bars0 + B_IEMPTY + 8 * slot);
        qn++;
        return it;
    };

    if (warp < 4) {
        reg_dec<40>();
        if (warp == 0) {
            {
                uint32_t gph = 1;
                const uint32_t prank = __shfl_sync(0xffffffffu, rank, 0);
                auto request = [&]() { mbar_arrive_cluster_if(lane == 0, bars0 + B_WANT); };
                auto take_item = [&]() -> int { return __shfl_sync(0xffffffffu, next_item(lane == 0), 0); };
                auto inputs_seen = [&](uint32_t word, unsigned& n) -> uint32_t {
                    uint32_t v;
                    spin_guard(n);
                    asm volatile("ld.acquire.cta.shared.u32 %0, [%1];" : "=r"(v) : "r"(bars + SM_ORDY + 4 * word) : "memory");
                    return __shfl_sync(0xffffffffu, v, 0);
                };
                uint32_t oneed = 0;
                auto wait_inputs = [&](int it) {
                    if (it & ITEM_READY) return;
                    oneed += 256;
                    for (unsigned n = 0; inputs_seen(1, n) < oneed;) {}
                };
                int nxt = first_item(), ring = -1, rot = 0;
                for (int k0 = 2; item_type(nxt) <= T_LOCAL; k0 = 0) {
                    const int type = item_type(nxt), m = item_row(nxt), c = item_col(nxt);
                    if (type == T_LOCAL) {
                        wait_inputs(nxt);
                        request();
#pragma unroll 1
                        for (uint32_t st = 0; st < 4; st++) {
                            mbar_wait(bars + B_GEMPTY + 8 * st, gph);
                            const uint32_t dst = sb + st * GST_BYTES, fb = bars + B_GFULL + 8 * st;
                            warp_expect_tx(fb, st == 0 ? 32768 + 512 : st == 3 ? 0 : 4 * LOC_PLANE);
                            if (st == 3) break;
                            if (st == 0) warp_bulk_load(dst + 4 * LOC_PLANE, &g_gate[m * 128], 512, fb);
#pragma unroll 1
                            for (int i = 0; i < 4; i++)
                                warp_tma_load(dst + i * LOC_PLANE, &prm.m[st ? M_SCR_LOC : M_SCR_LOQ], fb, i * 64, m * 64 - (st ? 8 : 0), G_B + 8 * st + c, true);
                        }
                        gph ^= 1;
                        ring = -1;
                    } else {
                        const int nk = type == T_K || type == T_V ? 8 : 16, kept = ring == m + 16 * nk ? 4 : 0;
                        ring = m + 16 * nk;
                        rot = kept ? rot - 4 : 0;
                        const CUtensorMap* ma = &prm.m[nk == 8 ? M_C : M_X];
                        const CUtensorMap* mb = &prm.m[M_WQ + type];
#pragma unroll 1
                        for (int k = k0; k < nk; k++) {
                            if (k == nk - 3) request();
                            const uint32_t st = k & 3, dst = sb + st * GST_BYTES, fb = bars + B_GFULL + 8 * st;
                            const int kc = ((k + rot) & (nk - 1)) * 64;
                            mbar_wait(bars + B_GEMPTY + 8 * st, gph);
                            warp_expect_tx(fb, k < kept ? 32768 : GST_BYTES);
                            if (k >= kept) warp_tma_load(dst, ma, fb, kc, m * 128, 0, c == 15 && type != T_K);
                            warp_tma_load_pair(dst + 16384 + prank * 16384, mb, fb, 0, kc, c * 4 + 2 * prank, true);
                            if (st == 3) gph ^= 1;
                        }
                    }
                    nxt = take_item();
                }
                uint32_t kv = 0, kvph = 1;
                uint32_t qc = 0;
                auto a_parity = [&](uint32_t b) { return b < 2 ? (((qc + 1 - b) >> 1) & 1) ^ 1 : kvph ^ (b - 2 < kv); };
                const CUtensorMap* tile_map = &prm.m[M_SCR_LD];
                asm volatile("" : "+l"(tile_map));
                {
                    bool need_g = true, more = true;
                    int pv_grp = -1, pv_row = 0;
                    int pv_shared = 0;
                    bool peer_longer = false;
                    int m = 0, c = 0, asc = 0, nu = 0, uend = 0, ureq = -1, ufetch = 0;
#pragma unroll 1
                    for (int u = 0;; u++) {
                        if (u == ufetch) {
                            if (qc) nxt = take_item();
                            if (item_type(nxt) == T_ATTN) {
                                wait_inputs(nxt);
                                const uint32_t b = qc & 1, dst = sb + b * 32768, fb = bars + B_AFULL + 8 * b, row = item_row(nxt) * 128;
                                mbar_wait(bars + (qc == 0 ? B_GEMPTY : qc == 1 ? B_QFREE : B_AEMPTY + 8 * b), qc == 0 ? gph : qc == 1 ? 0 : a_parity(b));
                                warp_expect_tx(fb, 32768 + 512);
                                warp_tma_load(dst, tile_map, fb, 0, row, G_Q + item_col(nxt), false);
                                warp_tma_load(dst + 16384, tile_map, fb, 64, row, G_Q + item_col(nxt), false);
                                warp_bulk_load(bars + SM_GATE + b * 512, &g_gate[row], 512, fb);
                                qc++;
                            }
                        }
                        if (u == uend) {
                            if (!more) break;
                            more = item_type(nxt) == T_ATTN;
                            m = item_row(nxt); c = item_col(nxt); asc = item_asc(nxt);
                            nu = more ? 2 * m + 2 : 0;
                            uend = nu + ((more ? m < 2 : pv_grp >= 0) ? 3 : 0);
                            ureq = 2 * max(m - 2 - (asc & m), 0);
                            ufetch = !more ? -1 : m ? 2 * m : uend;
                            u = -1;
                            continue;
                        }
                        int grp = pv_grp, row = pv_row;
                        int shared = pv_shared;
                        if (u >= nu) {
                            if (u == nu + 1) pv_grp = -1;
                            else if (peer_longer) { grp = -1; shared = 0; }
                            else continue;
                        } else {
                            const int j = asc ? u >> 1 : m - (u >> 1);
                            if (u & 1) {
                                pv_grp = G_V + c; pv_row = j * 128; pv_shared = (m | 1) - j;
                                peer_longer = asc & ~m & 1;
                                if (u == nu - 1 && (m & 1) && item_type(nxt) == T_END) mbar_arrive_cluster_n_if(lane == 0, bars0 + B_WANT, 2);
                                if (grp < 0) continue;
                            } else {
                                if (u == ureq) request();
                                grp = G_K + c; row = j * 128; shared = (m | 1) - j;
                            }
                        }
                        uint32_t fb = bars + B_AFULL + 16 + 8 * kv, mine = sb + SM_KV + kv * 32768 + prank * 16384;
                        int c_mine = prank * 64;
                        asm volatile("" : "+r"(mine), "+r"(fb), "+r"(row), "+r"(grp), "+r"(c_mine));
                        mbar_wait(need_g ? bars + B_GEMPTY + 8 + 8 * kv : fb + B_AEMPTY - B_AFULL, need_g ? gph : kvph);
                        warp_expect_tx(fb, grp < 0 ? 0 : 32768);
                        if (shared) {
                            warp_tma_load_pair(mine, tile_map, fb, c_mine, row, grp, shared == 1);
                        } else if (grp >= 0) {
                            warp_tma_load(mine, tile_map, fb, c_mine, row, grp, true);
                            warp_tma_load(mine + 16384 - prank * 32768, tile_map, fb, 64 - c_mine, row, grp, true);
                        } else {
                            mbar_arrive_cluster_n_if(lane < 2, map_cta(fb, lane & 1) + B_AEMPTY - B_AFULL, 8);
                        }
                        if (kv == 2) need_g = false;
                        if (++kv == 4) { kv = 0; kvph ^= 1; }
                    }
                }
                if (!qc) request();
                const int it = take_item();
                int nk = 0;
                if (item_type(it) == T_OUT) {
                    const int m = item_row(it), c = item_col(it), half = c & 1;
                    nk = 80;
                    for (unsigned n = 0; (inputs_seen(1, n) & 255) != 255;) {}
                    mbar_wait(bars + B_GEMPTY + 24, gph);
                    mbar_wait(bars + B_QFREE, 0);
                    mbar_wait(bars + B_AEMPTY + 8 * (qc & 1), a_parity(qc & 1));
#pragma unroll 1
                    for (uint32_t k = 0; k < 4; k++) {
                        const uint32_t sa = prm.ostep[half ? WIDE - 1 - k : k], dst = sb + k * GST_BYTES, fb = bars + B_GFULL + 8 * k;
                        const uint32_t b0 = k ? 1 + k : ~qc & 1, b1 = 2 + k - (k == 1);
                        mbar_wait(bars + B_AEMPTY + 8 * b0, a_parity(b0));
                        mbar_arrive_cluster_if(lane == 0 && !k, bars_peer + B_XFREE);
                        warp_expect_tx(fb, GST_BYTES);
                        warp_tma_load(dst, tile_map, fb, (sa & 1) * 64, m * 128, G_LOC - 32 + (sa >> 1), true);
                        mbar_wait(bars + (k ? B_AEMPTY + 8 * b1 : B_XFREE), k ? kvph ^ (b1 - 2 < kv) : 0);
                        warp_tma_load_pair(dst + 16384 + prank * 16384, &prm.m[M_WOB], fb, 0, (sa & 63) * 64, (c >> 1) * 4 + 2 * (half ^ prank), false);
                    }
                    gph ^= 1;
                    uint32_t seen = 0;
                    for (int k = 4; k < nk; k++) {
                        if (k == K_SPLIT) nk = 2 * TRIPLES + (take_item() & 127);
                        const int kn = k + 2 * TRIPLES - nk, first = kn >= 0 && !(kn & 1);
                        const int s = kn >= 0 ? WIDE + (3 * kn + 1) / 2 : half ? WIDE - 1 - k : k;
                        const uint32_t sa = prm.ostep[s], sa2 = prm.ostep[s + first], sw = prm.ostep[s - (kn >= 0 && !first ? prank : 0)];
                        const uint32_t need = 1u << (sa >> 1 & 31) | 1u << (sa2 >> 1 & 31);
                        for (unsigned n = 0; sa < 64 && (need & ~seen);) seen = inputs_seen(0, n);
                        const uint32_t st = k & 3;
                        uint32_t dst = sb + st * GST_BYTES, fb = bars + B_GFULL + 8 * st;
                        uint32_t dstb = dst + 16384 + (first ? 0 : prank * 16384), skipb = first && (kn >> 1 & 1) != prank;
                        int a0 = (sa & 1) * 64, a1 = m * 128, a2 = (sa >> 1) + (sa < 64 ? G_CTX : G_LOC - 32);
                        int b1 = (sw & 63) * 64, b2 = (c >> 1) * 4 + 2 * (kn >= 0 ? half : half ^ prank);
                        const CUtensorMap* mb = &prm.m[sw >= 64 ? M_WOB : M_WO];
                        asm volatile("" : "+r"(dst), "+r"(fb), "+r"(dstb), "+r"(skipb), "+r"(a0), "+r"(a1), "+r"(a2), "+r"(b1), "+r"(b2), "+l"(mb));
                        mbar_wait(bars + B_GEMPTY + 8 * st, gph);
                        warp_expect_tx(fb, GST_BYTES);
                        warp_tma_load(dst, tile_map, fb, a0, a1, a2, true);
                        if (!skipb) warp_tma_load_pair(dstb, mb, fb, 0, b1, b2, false);
                        if (first) warp_tma_load(dst + 32768, tile_map, fb, (sa2 & 1) * 64, a1, G_CTX + (sa2 >> 1), true);
                        if (k < K_SPLIT && lane == 0 && !prank)
                            asm volatile("st.relaxed.gpu.global.u32 [%0], %1;" :: "l"(&g_sync.step[0][0] + m * 4 + c), "r"(k) : "memory");
                        mbar_arrive_if(k == K_MEET && lane == 0, bars + B_MEET);
                        if ((uint32_t)(k - K_FETCH) < (3 * TRIPLES + 1) / 2) {
                            const uint32_t g = prm.ostep[79 - 2 * (k - K_FETCH)] >> 1;
                            warp_prefetch((const char*)g_scr + (uint32_t)((G_CTX + g) * (SEQ * 256) + m * 32768 + c * 4096), 4096);
                            warp_prefetch(prm.wo + (uint32_t)(g * 262144 + (m * 8 + c) * 2048), 2048);
                        }
                        if (st == 3) gph ^= 1;
                    }
                    for (unsigned n = 0; ~inputs_seen(0, n);) {}
                }
#pragma unroll 1
                for (uint32_t st = 0; st < 4; st++) { mbar_wait(bars + B_GEMPTY + 8 * st, gph ^ (st < (nk & 3))); mbar_wait(bars + B_AEMPTY + 16 + 8 * st, a_parity(2 + st)); }
                unsigned left = 0;
                if (lane == 0) asm volatile("atom.relaxed.gpu.global.add.u32 %0, [%1], 1;" : "=r"(left) : "l"(&g_sync.done) : "memory");
                if (__shfl_sync(0xffffffffu, left, 0) == NCTA - 1)
#pragma unroll 1
                    for (uint32_t i = lane * 8; i < sizeof(Sync); i += 256) *(unsigned long long*)((char*)&g_sync + i) = 0;
            }
        } else if (warp <= 2) {
            if (blockIdx.x < SEQ / 16) {
                const uint32_t r0 = 16 * blockIdx.x + 8 * (warp - 1), gbuf = bars + SM_GATE + 4 * (r0 & 15);
                float z[4];
                mbar_wait(bars + B_GFULL + 24, 0);
#pragma unroll 1
                for (uint32_t i = 0; i < 8; i++) {
                    const uint32_t off = (i & 3) * 512 + lane * 16;
                    const uint4* xp = (const uint4*)((const char*)prm.x + ((r0 + (i & 4)) * 2048 + off));
                    const uint4 wv = __ldg((const uint4*)((const char*)prm.gate_w + off));
                    uint4 xv[4];
#pragma unroll
                    for (int r = 0; r < 4; r++) { xv[r] = __ldg(xp + r * 128); if (!(i & 3)) z[r] = 0.f; }
                    const uint32_t ws[4] = {wv.x, wv.y, wv.z, wv.w};
#pragma unroll
                    for (int e = 0; e < 4; e++)
#pragma unroll
                        for (int r = 0; r < 4; r++) {
                            const uint32_t xs = e == 0 ? xv[r].x : e == 1 ? xv[r].y : e == 2 ? xv[r].z : xv[r].w;
                            z[r] = fmaf(__uint_as_float(xs << 16), __uint_as_float(ws[e] << 16), z[r]);
                            z[r] = fmaf(__uint_as_float(xs & 0xffff0000u), __uint_as_float(ws[e] & 0xffff0000u), z[r]);
                        }
                    if ((i & 3) == 3) {
#pragma unroll
                        for (int o = 16; o > 0; o >>= 1)
#pragma unroll
                            for (int r = 0; r < 4; r++) z[r] += __shfl_xor_sync(0xffffffffu, z[r], o);
                        const float zr = lane & 2 ? (lane & 1 ? z[3] : z[2]) : (lane & 1 ? z[1] : z[0]);
                        asm volatile("st.shared.f32 [%0], %1;" :: "r"(gbuf + 4 * ((i & 4) + (lane & 3))), "f"(1.f / (1.f + __expf(-zr))) : "memory");
                    }
                }
                fence_proxy_async_smem();
                __syncwarp();
                warp_bulk_store((char*)g_gate + 4 * r0, gbuf, 32);
                bulk_commit();
                bulk_wait<0>();
                __syncwarp();
                if (lane == 0) red_add(&g_sync.count[3], 1);
            }
            __syncwarp();
            {
                const int w = warp - 1;
                uint32_t sph = 0, nann = 0;
                int unsent = 0, nunsent = 0;
                bool urgent = false;
                auto announce = [&]() {
                    if (!urgent) return;
                    bulk_wait<0>();
                    __syncwarp();
                    const uint32_t hb = bars + B_HALF + 8 * (nann & 3);
                    if (w == 0) {
                        mbar_arrive_if(lane == 0, hb);
                    } else {
                        mbar_wait(hb, (nann >> 2) & 1);
                        const uint32_t type = item_type(unsent), m = item_row(unsent), c = item_col(unsent);
                        const uint32_t word = type < T_B ? c >> 3 : type == T_B ? 2 : offsetof(Sync, ctx) / 8 + m;
                        const uint32_t bit = type < T_B ? 8 * (c & 7) : type == T_B ? 8 * (c & 3) : type == T_LOCAL ? 32 + c : c;
                        if (lane < nunsent) red_add((unsigned long long*)((char*)&g_sync + 8 * word), 1ull << bit);
                        __syncwarp();
                    }
                    nann++;
                    nunsent = 0; urgent = false;
                };
                int held = first_item(), it;
                bool qfree = false;
                do {
                    if (!__all_sync(0xffffffffu, mbar_test(bars + B_IFULL + 8 * (qn % QDEPTH), (qn / QDEPTH) & 1))) announce();
                    it = __shfl_sync(0xffffffffu, next_item(lane == 0), 0);
                    const int itype = item_type(it);
                    const bool keep_held = itype == T_LOCAL;
                    if (itype >= T_ATTN && held < 0) {
                        urgent = nunsent;
                        mbar_arrive_if(lane == 0 && !qfree, bars + B_QFREE);
                        qfree = true;
                    }
#pragma unroll 1
                    for (int pass = held < 0 || keep_held; pass < 2; pass++) {
                        if (pass && (itype < T_OUT || itype == T_END)) break;
                        const int cur = pass ? it : held, type = item_type(cur), m = item_row(cur), c = item_col(cur);
                        const bool local = type == T_LOCAL;
                        const int grp = pass ? (local ? G_LOC : G_CTX) + c : type * 32 + 2 * c;
#pragma unroll 1
                        for (int i = 0; i < 4 - 2 * pass; i++) {
                            const int b = i & 1;
                            const bool alt = i >= 2 && itype == T_ATTN;
                            const uint32_t full = bars + (alt ? B_ALT + 8 * w : B_SFULL + 16 * w + 8 * b), par = alt ? 0 : sph;
                            if (i == 3 - 2 * pass || !__all_sync(0xffffffffu, mbar_test(full, par))) announce();
                            mbar_wait(full, par);
                            fence_proxy_async_smem();
                            warp_tma_store(&prm.m[local ? M_SCR_LOQ : M_SCR_ST], sb + (alt ? 32768 : SM_STAGING) + w * 16384 + b * 8192,
                                         local ? b * 128 + w * 64 : b * 64, local ? m * 64 : m * 128 + w * 64, grp + (i >> 1), local || (type < T_B && c < FIRST_PAIR));
                            bulk_commit();
                            if (pass > b) continue;
                            bulk_wait_read<0>();
                            __syncwarp();
                            mbar_arrive_if(lane <= pass && !alt, bars + B_SEMPTY + 16 * w + 8 * (b - lane));
                            sph ^= b & !alt;
                        }
                        mbar_arrive_if(lane == 0 && !qfree && itype >= T_ATTN, bars + B_QFREE);
                        qfree |= itype >= T_ATTN;
                        if (lane == nunsent) unsent = cur;
                        nunsent++;
                        urgent = nunsent == 32 || !local;
                    }
                    if (!keep_held) held = itype < T_OUT ? it : -1;
                } while (item_type(it) != T_END);
                announce();
                it = __shfl_sync(0xffffffffu, next_item(lane == 0), 0);
                if (item_type(it) == T_OUT) {
                    if (w) {
                        mbar_wait(bars + B_MEET, 0);
                        asm volatile("fence.proxy.async.global;\nfence.acq_rel.gpu;" ::: "memory");
                        mbar_arrive_cluster_if(lane == 0, bars0 + B_WANT);
                    }
                    next_item(lane == 0);
#pragma unroll 1
                    for (int i = 0; i < 4; i++) {
                        const int b = i & 1;
                        mbar_wait(bars + B_SFULL + 16 * w + 8 * b, sph ^ (i >> 1));
                        fence_proxy_async_smem();
                        warp_tma_add(&prm.m[M_OUT], sb + SM_STAGING + w * 16384 + b * 8192, (item_col(it) ^ (i < 2)) * 128 + b * 64, item_row(it) * 128 + w * 64, 0);
                        bulk_commit();
                        if (b) {
                            bulk_wait_read<0>();
                            __syncwarp();
                            mbar_arrive_if(lane < 2, bars + B_SEMPTY + 16 * w + 8 * lane);
                        }
                    }
                }
            }
        } else {
            if (elect_one()) {
                uint32_t ordy = 0;
                unsigned long long cnt_lo = 0, cnt_hi = 0;
                int late = 0;
                auto refresh = [&]() {
                    if (!late && cnt_lo == 0x30303030 && cnt_hi == SEQ / 8) late = 1;
                    asm volatile("ld.acquire.gpu.global.v2.u64 {%0, %1}, [%2];" : "=l"(cnt_lo), "=l"(cnt_hi) : "l"(late ? &g_sync.count[0] : &g_sync.count[2]) : "memory");
                };
                auto inputs_ready = [&](int it) -> bool {
                    const int c = item_col(it);
                    if (item_type(it) == T_ATTN) return late && ((c < 16 ? cnt_lo : cnt_hi) >> (4 * (c & 14)) & 255) == 48;
                    return late || (cnt_hi == SEQ / 8 && (cnt_lo >> (4 * (c & 6)) & 255) == 48);
                };
                auto publish = [&](int it, int step) {
                    const uint32_t slot = qn % QDEPTH;
                    mbar_wait(bars + B_IEMPTY + 8 * slot, ((qn / QDEPTH) & 1) ^ 1);
                    for (uint32_t r = 0; r < 2; r++) {
                        const uint32_t rb = map_cta(bars, r);
                        asm volatile("mbarrier.arrive.expect_tx.shared::cluster.b64 _, [%0], 4;" :: "r"(rb + B_IFULL + 8 * slot) : "memory");
                        asm volatile("st.async.shared::cluster.mbarrier::complete_tx::bytes.u32 [%0], %1, [%2];"
                                     :: "r"(rb + SM_QUEUE + 4 * slot), "r"(it + r * step), "r"(rb + B_IFULL + 8 * slot) : "memory");
                    }
                    qn++;
                };
                int asc = 1;
                int it;
                do {
                    if (rank == 0) {
                        mbar_wait(bars + B_WANT, qn & 1);
                        const uint32_t pair = plan_index();
                        int pit = prm.plan[pair < 64 ? pair & 7 : pair - 56][min(qn + 1, 15u)];
                        unsigned i;
                        const bool planned = item_type(pit) != T_END;
                        if (!planned) asm volatile("atom.relaxed.gpu.global.add.u32 %0, [%1], 1;" : "=r"(i) : "l"(&g_sync.next) : "memory");
                        if (cnt_lo != 0x3030303030303030ull || cnt_hi != cnt_lo) refresh();
                        if (planned) pit += (pair >> 3 & 7) << (item_type(pit) == T_LOCAL);
                        else if (i < NITEMS) pit = prm.items[i];
                        const int type = item_type(pit);
                        int step = type == T_LOCAL ? 16 : 1;
                        it = pit + (pit & (step == 1 ? 15 : 0x1f0));
                        if (type == T_ATTN) {
                            if (!asc) { it += 1; step = -1; }
                            it |= asc << 9;
                        }
                        asc = type != T_ATTN || item_row(pit) == 0 || !asc;
                        if (inputs_ready(it)) it |= ITEM_READY;
                        publish(it, step);
                    } else {
                        it = next_item(true);
                    }
                    if ((item_type(it) == T_ATTN || item_type(it) == T_LOCAL) && !(it & ITEM_READY)) {
                        unsigned n = 0;
                        while (!inputs_ready(it)) { refresh(); spin_guard(n); }
                        asm volatile("st.release.cta.shared.u32 [%0], %1;" :: "r"(bars + SM_ORDY + 4), "r"(ordy += 256) : "memory");
                    }
                } while (item_type(it) != T_END);
                if (rank == 0) {
                    mbar_wait(bars + B_WANT, qn & 1);
                    const unsigned i = atomicAdd(&g_sync.next_out, 1u), t = i < 32 ? 31 - i : i - 32;
                    it = i < 64 ? T_OUT << 13 | ((t & 3) * 2 + (i >> 5)) << 4 | (t >> 2) * 2 : T_END << 13;
                    publish(it, 1);
                } else {
                    it = next_item(true);
                }
                if (item_type(it) == T_OUT) {
                    const uint32_t m = item_row(it), half = item_col(it) & 1, tile = m * 2 + (item_col(it) >> 1);
                    unsigned* split = (unsigned*)((char*)g_sync.split + 4 * tile);
                    unsigned long long rdy = 0;
                    int state = rank ? 2 : 0;
                    for (unsigned n = 0; rdy != 0xffffffffffull || state < 2; spin_guard(n)) {
                        if (rdy != 0xffffffffffull) {
                            rdy = ld_acquire((const unsigned long long*)((char*)g_sync.ctx + 8 * m));
                            asm volatile("st.release.cta.shared.u64 [%0], %1;" :: "r"(bars + SM_ORDY), "l"(rdy) : "memory");
                        }
                        unsigned steps = 0;
                        if (state == 1) {
                            steps = ld_acquire(split);
                        } else if (state == 0 && mbar_test(bars + B_WANT, qn & 1)) {
                            state = 1;
                            unsigned seen;
                            asm volatile("atom.acq_rel.gpu.global.exch.b32 %0, [%1], 1;" : "=r"(seen) : "l"(split) : "memory");
                            if (seen) {
                                const unsigned long long v = ld_acquire((const unsigned long long*)((char*)g_sync.step + 8 * tile));
                                const int d = (int)(v >> 32) - (int)v;
                                steps = (WIDE + min(max(half ? d : -d, -12), 12)) >> 1;
                                atomicExch(split, WIDE - steps);
                            }
                        }
                        if (steps > 1) { publish(T_END << 13 | steps, 0); state = 2; }
                    }
                    if (rank) next_item(true);
                }
                #pragma unroll 1
                for (uint32_t n = qn; n < qn + QDEPTH && rank == 0; n++) mbar_wait(bars + B_IEMPTY + 8 * (n % QDEPTH), ((n / QDEPTH) & 1) ^ 1);
            }
        }
    } else {
        reg_inc<232>();
        const int wg = (warp >> 2) - 1, wq = warp & 3;
        uint32_t gph = 0;
        uint32_t kvn = 0;
        const uint32_t dA = make_desc(sb + wg * 8192, 16);
        uint32_t ti = 0;
        uint32_t sph = 1;
        const uint32_t stg = sb + SM_STAGING + wg * 16384;
        const uint32_t stg_lane = stg + (wq * 16 + (lane & 15)) * 128 + (((lane >> 4) ^ (lane & 7)) << 4);
        auto write_blocks = [&](auto n, uint32_t off, const uint32_t* v) {
            uint32_t a = stg_lane;
            asm volatile("" : "+r"(a));
            a += off;
#pragma unroll
            for (int j = 0; j < decltype(n)::value; j++)
                stmatrix_x4((a ^ (32 * (j & 3))) + (j >> 2) * 8192, v[4 * j], v[4 * j + 1], v[4 * j + 2], v[4 * j + 3]);
        };
        auto release = [&](uint32_t bar) { mbar_arrive_if(lane == 0, bars + bar); };
        const uint32_t bars_lane = map_cta(bars, lane & 1);
        auto release_stage = [&](uint32_t st) { mbar_arrive_cluster_if(lane < 2, bars_lane + B_GEMPTY + 8 * st); };
        auto take_item = [&]() -> int {
            return __shfl_sync(0xffffffffu, next_item(lane == 0, false), 0);
        };
        auto stage_acquire = [&](int b) { mbar_spin(bars + B_SEMPTY + 16 * wg + 8 * b, sph); };
        auto stage_publish = [&](int b) {
            __syncwarp();
            release(B_SFULL + 16 * wg + 8 * b);
        };
        auto stage_chunk = [&](int b, const uint32_t* v) {
            stage_acquire(b);
            write_blocks(std::integral_constant<int, 4>(), b * 8192, v);
            stage_publish(b);
            if (b) sph ^= 1;
        };
        auto publish_pair = [&]() {
            __syncwarp();
            mbar_arrive_if(lane < 2, bars + B_SFULL + 16 * wg + 8 * lane);
            sph ^= 1;
        };
        auto gemm_step = [&](float (&acc)[128], uint32_t dB, int& k) {
            const uint32_t st = k & 3;
            wgmma_wait<0>();
            release_stage((k - 1) & 3);
            mbar_spin(bars + B_GFULL + 8 * st, gph);
            const uint64_t da = full_desc(dA + st * (GST_BYTES >> 4)), db = full_desc(dB + st * (GST_BYTES >> 4));
            wgmma_fence();
#pragma unroll
            for (int kk = 0; kk < 4; kk++) wgmma_ss_n256_tb(acc, da + 2 * kk, db + 128 * kk, 1);
            wgmma_commit();
            gph ^= st == 3;
            k++;
        };
        if (wg == 1) bar_arrive(1, 256);
        int it = first_item();
        while (true) {
            if (item_type(it) <= T_LOCAL) {
                float acc[128];
                uint32_t pk[64];
                bool pending = false;
                int held = T_END;
                auto scale_q = [&](int j0, int n) {
                    if (held != T_Q) return;
#pragma unroll
                    for (int j = j0; j < j0 + n; j++)
                        asm("{\n.reg .b32 t;\nmul.rn.bf16x2 t, %0, %2;\nfma.rn.bf16x2 %0, %0, %1, t;\n}\n" : "+r"(pk[j]) : "r"(0x3e033e03u), "r"(0xb9d8b9d8u));
                };
                zero_regs(pk);
                const uint32_t dB = make_desc(sb + 16384, 8192);
                do {
                    const int type = item_type(it);
                    if (type == T_LOCAL) {
                        int ln = lane;
                        asm volatile("" : "+r"(ln));
                        const int g = ln >> 2, t = ln & 3, par = wq & 1;
                        const uint32_t hc = (wq >> 1) * 4, pl = sb + (par * 2 + wg) * LOC_PLANE;
                        const uint32_t a16 = (ln & 15) * 128 + (((hc + (ln >> 4)) ^ (ln & 7)) << 4), a8 = (ln & 7) * 128 + (((hc + (ln >> 3)) ^ (ln & 7)) << 4);
                        const bool first0 = 2 * t > g, first1 = 2 * t + 1 > g;
                        const uint32_t fmask = (first0 ? 0xffffu : 0u) | (first1 ? 0xffff0000u : 0u);
                        const bool edge = item_row(it) == 0;
                        uint32_t q[4][2][4], kf[9][4], vf[9][4];
                        float w[8];
                        mbar_spin(bars + B_GFULL, gph);
#pragma unroll
                        for (int u = 0; u < 4; u++) { ldsm_x4(q[u][0], pl + u * 2048 + a16); ldsm_x4(q[u][1], pl + u * 2048 + (a16 ^ 32)); }
#pragma unroll
                        for (int j = 0; j < 8; j++) w[j] = lds_f32(sb + 4 * LOC_PLANE + 4 * (2 * g + par) + 64 * j);
                        __syncwarp();
                        release_stage(0);
                        mbar_spin(bars + B_GFULL + 8, gph);
#pragma unroll
                        for (int n = 0; n < 9; n++) ldsm_x4(kf[n], pl + GST_BYTES + n * 1024 + a8);
                        __syncwarp();
                        release_stage(1);
                        float s[8][2];
#pragma unroll
                        for (int u = 0; u < 4; u++) {
                            float d[3][4];
#pragma unroll
                            for (int nt = 0; nt < 3; nt++) {
                                mma_k16_init(d[nt], q[u][0], kf[2 * u + nt][0], kf[2 * u + nt][1]);
                                mma_k16(d[nt], q[u][1], kf[2 * u + nt][2], kf[2 * u + nt][3]);
                            }
                            if (u == 0 && edge) { d[0][0] = -INFINITY; d[0][1] = -INFINITY; }
                            s[2 * u][0] = first0 ? d[0][0] : d[1][0]; s[2 * u][1] = first1 ? d[0][1] : d[1][1];
                            s[2 * u + 1][0] = first0 ? d[1][2] : d[2][2]; s[2 * u + 1][1] = first1 ? d[1][3] : d[2][3];
                        }
                        mbar_spin(bars + B_GFULL + 16, gph);
#pragma unroll
                        for (int u = 0; u < 4; u++) { ldsm_x4_t(vf[2 * u], pl + 2 * GST_BYTES + u * 2048 + a16); ldsm_x4_t(vf[2 * u + 1], pl + 2 * GST_BYTES + u * 2048 + (a16 ^ 32)); }
                        ldsm_x4_t(vf[8], pl + 2 * GST_BYTES + 8192 + a8);
                        __syncwarp();
                        release_stage(2);
                        float x[8];
#pragma unroll
                        for (int j = 0; j < 8; j++) x[j] = fmaxf(s[j][0], s[j][1]);
#pragma unroll
                        for (int o = 1; o < 4; o *= 2)
#pragma unroll
                            for (int j = 0; j < 8; j++) x[j] = fmaxf(x[j], __shfl_xor_sync(0xffffffffu, x[j], o));
#pragma unroll
                        for (int j = 0; j < 8; j++) {
                            const float n = x[j] * -LOC_SCALE;
                            s[j][0] = ex2(fmaf(s[j][0], LOC_SCALE, n)); s[j][1] = ex2(fmaf(s[j][1], LOC_SCALE, n));
                            x[j] = s[j][0] + s[j][1];
                        }
#pragma unroll
                        for (int o = 1; o < 4; o *= 2)
#pragma unroll
                            for (int j = 0; j < 8; j++) x[j] += __shfl_xor_sync(0xffffffffu, x[j], o);
                        mbar_spin(bars + B_GFULL + 24, gph);
                        release_stage(3);
                        it = take_item();
                        uint32_t ob[4][8];
#pragma unroll
                        for (int u = 0; u < 4; u++) {
                            const float r0 = rcp(x[2 * u]), r1 = rcp(x[2 * u + 1]), f0 = fmaf(-w[2 * u], r0, r0), f1 = fmaf(-w[2 * u + 1], r1, r1);
                            const uint32_t p0 = pack_bf16(s[2 * u][0] * f0, s[2 * u][1] * f0), p1 = pack_bf16(s[2 * u + 1][0] * f1, s[2 * u + 1][1] * f1);
                            const uint32_t pa[4] = {p0 & fmask, 0, p0 & ~fmask, p1 & fmask};
#pragma unroll
                            for (int c = 0; c < 4; c++) {
                                float ol[4];
                                mma_k16_init(ol, pa, vf[2 * u + (c >> 1)][2 * (c & 1)], vf[2 * u + (c >> 1)][2 * (c & 1) + 1]);
                                mma_k8(ol, 0, p1 & ~fmask, u < 3 ? vf[2 * u + 2 + (c >> 1)][2 * (c & 1)] : vf[8][c]);
                                ob[u][2 * c] = pack_bf16(ol[0], ol[1]);
                                ob[u][2 * c + 1] = pack_bf16(ol[2], ol[3]);
                            }
                        }
                        stage_acquire(0); stage_acquire(1);
#pragma unroll
                        for (int u = 0; u < 4; u++) {
                            stmatrix_x4(stg + par * 8192 + u * 2048 + a16, ob[u][0], ob[u][1], ob[u][2], ob[u][3]);
                            stmatrix_x4(stg + par * 8192 + u * 2048 + (a16 ^ 32), ob[u][4], ob[u][5], ob[u][6], ob[u][7]);
                        }
                        publish_pair();
                        bar_sync(4, 256);
                        gph ^= 1;
                        continue;
                    }
                    mbar_spin(bars + B_GFULL, gph);
                    bool more;
                    do {
                        wgmma_fence();
                        wgmma_ss_n256_tb_init(acc, full_desc(dA), full_desc(dB));
#pragma unroll
                        for (int kk = 1; kk < 4; kk++) wgmma_ss_n256_tb(acc, full_desc(dA) + 2 * kk, full_desc(dB) + 128 * kk, 1);
                        wgmma_commit();
                        const int nk = item_type(it) == T_K || item_type(it) == T_V ? 8 : 16;
                        int k = 1;
                        do {
                            if (pending) {
                                const int kf = k - 1 - wg;
                                if (kf == 0) { scale_q(0, 16); stage_chunk(0, pk); }
                                else if (kf == 1) { scale_q(16, 16); stage_chunk(1, pk + 16); }
                                else if (kf == 3) { scale_q(32, 16); stage_chunk(0, pk + 32); }
                                else if (kf == 4) { scale_q(48, 16); stage_chunk(1, pk + 48); }
                            }
                            gemm_step(acc, dB, k);
                        } while (k < nk);
                        held = item_type(it);
                        it = take_item();
                        more = item_type(it) < T_LOCAL;
                        if (more) mbar_spin(bars + B_GFULL, gph);
                        wgmma_wait<0>();
                        fence_regs(acc);
                        release_stage(3);
#pragma unroll
                        for (int j = 0; j < 64; j++) pk[j] = pack_bf16(acc[2 * j], acc[2 * j + 1]);
                        pending = true;
                    } while (more);
                } while (item_type(it) <= T_LOCAL);
                if (pending) {
                    scale_q(0, 64);
                    stage_acquire(0); stage_acquire(1);
                    write_blocks(std::integral_constant<int, 8>(), 0, pk);
                    const bool borrow = item_type(it) == T_ATTN;
                    if (borrow) {
                        mbar_spin(bars + B_GEMPTY, gph ^ 1); mbar_spin(bars + B_GEMPTY + 8, gph ^ 1);
                    } else {
                        publish_pair();
                        stage_acquire(0); stage_acquire(1);
                    }
                    write_blocks(std::integral_constant<int, 8>(), borrow ? 32768 - SM_STAGING : 0, pk + 32);
                    publish_pair();
                    mbar_arrive_if(lane == 0 && borrow, bars + B_ALT + 8 * wg);
                }
                if (item_type(it) == T_END) { it = take_item(); break; }
            } else {
                float o[64], s[64];
                uint32_t pa[32], pb[32];
                zero_regs(o); zero_regs(s); zero_regs(pa);
                float n0 = 0.f, n1 = 0.f;
                int shifted = 0;
                float l0 = 1.f, l1 = 1.f, f0 = 0.f, f1 = 0.f, g0 = 0.f, g1 = 0.f;
                uint32_t has_pv = 0;
                int first = 0;
                int pending = 0;
                const uint32_t dK = make_desc(sb + SM_KV, 16), dV = make_desc(sb + SM_KV, 16384);
                const uint32_t lane_off = bars_lane - bars + B_AEMPTY - B_AFULL;
                int cur = 0;
                uint32_t qoff = 0;
                const int row = wg * 64 + wq * 16 + (lane >> 2);
                const float thr = (row & 63) - (lane & 3) * 2;
                int peek = 0;
                auto kv_wait = [&](uint32_t n) { mbar_spin(bars + B_AFULL + 16 + 8 * (n & 3), (n >> 2) & 1); };
                auto kv_release = [&](uint32_t n) { mbar_arrive_cluster_if(lane < 2, bars_lane + B_AEMPTY + 16 + 8 * (n & 3)); };
                struct Slot { uint32_t bar, par, off; } slot[4];
                auto align = [&]() {
#pragma unroll
                    for (uint32_t i = 0; i < 4; i++) {
                        const uint32_t n = kvn + (i == 1 ? has_pv : i);
                        slot[i].bar = bars + B_AFULL + 16 + 8 * (n & 3); slot[i].par = (n >> 2) & 1; slot[i].off = (n & 3) * 2048;
                    }
                };
                align();
                auto scale_o = [&]() {
#pragma unroll
                    for (int j = 0; j < 16; j++) { o[4 * j] *= f0; o[4 * j + 1] *= f0; o[4 * j + 2] *= f1; o[4 * j + 3] *= f1; }
                };
                auto pack_o = [&](uint32_t (&v)[32]) {
#pragma unroll
                    for (int j = 0; j < 32; j++) v[j] = pack_bf16(o[2 * j], o[2 * j + 1]);
                };
                auto scales = [&]() { f0 = g0 * rcp(quad_sum(l0)); f1 = g1 * rcp(quad_sum(l1)); };
                auto step = [&](auto even, uint32_t (&pin)[32], uint32_t (&pout)[32], bool fresh, bool diag, bool last) {
                    constexpr bool EVEN = decltype(even)::value;
                    Slot& sk = slot[EVEN ? 0 : 2];
                    Slot& sv = slot[EVEN ? 1 : 3];
                    kvn += EVEN ? 1 + has_pv : 2;
                    mbar_spin(sk.bar, sk.par);
                    bar_sync(1 + wg, 256);
                    qk_gemm(s, dA + qoff, dK + sk.off);
                    if (EVEN && fresh) {
                        scales();
                        g0 = lds_f32(bars + SM_GATE + (ti & 1) * 512 + 4 * row); g1 = lds_f32(bars + SM_GATE + (ti & 1) * 512 + 4 * row + 32);
                        ti++;
                        n0 = 0.f; n1 = 0.f; l0 = 0.f; l1 = 0.f;
                        shifted = 0;
                        if (has_pv) { stage_acquire(0); stage_acquire(1); }
                    }
                    if (!EVEN && pending) {
                        pack_o(pout);
                        write_blocks(std::integral_constant<int, 8>(), 0, pout);
                        publish_pair();
                    }
                    if (last)
                        asm volatile("{\n.reg .pred P, Q;\n"
                                     "mbarrier.test_wait.parity.shared::cta.b64 Q, [%1], %2;\n"
                                     "mbarrier.test_wait.parity.shared::cta.b64 P, [%3], %4;\n"
                                     "ld.shared.u32 %0, [%5];\n"
                                     "@!Q or.b32 %0, %0, 0x10000;\n"
                                     "@!P mov.u32 %0, -1;\n}\n"
                                     : "=r"(peek) : "r"(bars + B_AFULL + 8 * (ti & 1)), "r"((ti >> 1) & 1), "r"(bars + B_IFULL + 8 * (qn % QDEPTH)),
                                       "r"((qn / QDEPTH) & 1), "r"(bars + SM_QUEUE + 4 * (qn % QDEPTH)) : "memory");
                    mbar_spin(sv.bar, sv.par);
                    pv_gemm(o, pin, dV + sv.off, EVEN || !first);
                    bar_arrive(2 - wg, 256);
                    sk.par ^= 1; sv.par ^= 1;
                    wgmma_wait<1>();
                    fence_regs(s);
                    mbar_arrive_cluster_if(lane < 2 && (!EVEN || has_pv), sk.bar + lane_off);
                    mbar_arrive_if(lane == 0 && last, bars + B_AEMPTY + 8 * ((ti - 1) & 1));
                    float r0, r1, x0 = n0, x1 = n1;
#pragma unroll 1
                    for (int mask = diag, redone = 0;; mask = 0, redone = 1) {
                        if (mask | shifted) {
                            if (mask) causal_mask(s, thr, wg);
                            if (shifted) shift_rows(s, x0, x1);
                        }
                        exp_pack(pout, s, r0, r1);
                        if (!__any_sync(0xffffffffu, fmaxf(r0, r1) >= SUM_LIMIT || (EVEN && fresh && !(lane & 3) && !(fminf(s[0], s[2]) >= -REF_RANGE))) || redone) break;
                        row_max(s, x0, x1);
                        if (!(EVEN && fresh)) { x0 = fmaxf(x0, 0.f); x1 = fmaxf(x1, 0.f); }
                        float a0 = ex2(-x0), a1 = ex2(-x1);
                        n0 += x0; n1 += x1;
                        shifted = 1;
                        if (EVEN && fresh) { a0 = 1.f; a1 = 1.f; }
                        l0 *= a0; l1 *= a1;
                        wgmma_wait<0>();
                        fence_regs(o);
#pragma unroll
                        for (int q = 0; q < 16; q++) { o[4 * q] *= a0; o[4 * q + 1] *= a0; o[4 * q + 2] *= a1; o[4 * q + 3] *= a1; }
                    }
                    l0 += r0; l1 += r1;
                    wgmma_wait<0>();
                    fence_regs(o);
                    fence_regs(pin);
                    mbar_arrive_cluster_if(lane < 2, sv.bar + lane_off);
                };
                auto copy_p = [&]() {
#pragma unroll
                    for (int j = 0; j < 32; j++) pa[j] = __float_as_uint(__uint_as_float(pb[j]) + __uint_as_float(prm.zero));
                };
                int rem = 0;
                mbar_spin(bars + B_AFULL + 8 * (ti & 1), (ti >> 1) & 1);
                while (true) {
                    const bool fresh = rem == 0;
                    if (fresh) {
                        if (has_pv) {
                            const int seen = __shfl_sync(0xffffffffu, peek, 0);
                            if (seen >= 0) {
                                mbar_arrive_cluster_if(lane == 0, bars0 + B_IEMPTY + 8 * (qn % QDEPTH));
                                qn++;
                                it = seen & 0xffff;
                            } else {
                                it = take_item();
                            }
                            if (item_row(cur) < 2 || item_type(it) != T_ATTN) break;
                            if (seen & 0x10000) mbar_spin(bars + B_AFULL + 8 * (ti & 1), (ti >> 1) & 1);
                        }
                        cur = it;
                        qoff = (ti & 1) * 2048;
                    }
                    const bool last = fresh ? item_row(cur) == 0 : rem == 1;
                    step(std::true_type(), pa, pb, fresh, item_asc(cur) ? last : fresh, last);
                    first = fresh;
                    if (fresh) {
                        pending = has_pv; has_pv = 1;
                        if (!pending) { kvn -= 2; align(); kvn += 2; slot[0].par ^= 1; slot[1].par ^= 1; }
                        else scale_o();
                        rem = item_row(cur);
                        if (rem == 0) {
                            copy_p();
                            continue;
                        }
                    } else if (--rem == 0) {
                        copy_p();
                        const Slot t0 = slot[0], t1 = slot[1];
                        slot[0] = slot[2]; slot[1] = slot[3]; slot[2] = t0; slot[3] = t1;
                        continue;
                    }
                    step(std::false_type(), pb, pa, false, item_asc(cur) && rem == 1, rem == 1);
                    pending = 0; first = 0;
                    rem--;
                }
                const uint32_t skip = item_asc(cur) & ~item_row(cur) & 1;
                kvn += skip;
                const bool end = item_type(it) == T_END;
#pragma unroll 1
                for (int pass = pending ? 0 : 1; pass < 2; pass++) {
                    if (pass) {
                        kv_wait(kvn);
                        pv_gemm(o, pa, dV + (kvn & 3) * 2048, !first);
                        scales();
                        stage_acquire(0); stage_acquire(1);
                        if (end) it = take_item();
                        wgmma_wait<0>();
                        fence_regs(o);
                        kv_release(kvn);
                        kvn += 1 + skip;
                        scale_o();
                    }
                    pack_o(pb);
                    write_blocks(std::integral_constant<int, 8>(), 0, pb);
                    publish_pair();
                }
                if (end) break;
            }
        }
        if (item_type(it) == T_OUT) {
            float acc[128];
            const uint32_t dB = make_desc(sb + 16384, 8192);
            mbar_spin(bars + B_GFULL, gph);
            wgmma_fence();
            wgmma_ss_n256_tb_init(acc, full_desc(dA), full_desc(dB));
#pragma unroll
            for (int kk = 1; kk < 4; kk++) wgmma_ss_n256_tb(acc, full_desc(dA) + 2 * kk, full_desc(dB) + 128 * kk, 1);
            wgmma_commit();
            uint32_t ln;
            asm volatile("mov.u32 %0, %%laneid;" : "=r"(ln));
            char* const mine = (char*)prm.out + (uint32_t)((item_row(it) * 128 + wg * 64 + wq * 16 + (ln >> 4)) * 2048 + item_col(it) * 256 + (ln & 15) * 16);
            int k = 1, nk = 80;
            do {
                if (k == K_MEET - 5) {
#pragma unroll
                    for (int j = 0; j < 8; j++) *(uint4*)(mine + j * 4096) = make_uint4(0, 0, 0, 0);
                    __syncwarp();
                }
                if (k == K_SPLIT) nk = take_item() & 127;
                gemm_step(acc, dB, k);
            } while (k < nk);
            float lo[64];
            auto triple = [&](auto first) {
                const uint32_t s0 = k & 3, s1 = (k + 1) & 3, o0 = s0 * (GST_BYTES >> 4), o1 = s1 * (GST_BYTES >> 4);
                wgmma_wait<0>();
                mbar_arrive_cluster_if(ln < (decltype(first)::value ? 2 : 4), bars_lane + B_GEMPTY + 8 * ((k - 1 - (ln >> 1)) & 3));
                mbar_spin(bars + B_GFULL + 8 * s0, gph);
                gph ^= s0 == 3;
                wgmma_fence();
#pragma unroll
                for (int kk = 0; kk < 4; kk++) {
                    if (decltype(first)::value && kk == 0) wgmma_ss_n128_tb_init(lo, full_desc(dA + o0), full_desc(dB + o0));
                    else wgmma_ss_n128_tb(lo, full_desc(dA + o0) + 2 * kk, full_desc(dB + o0) + 128 * kk, 1);
                }
                mbar_spin(bars + B_GFULL + 8 * s1, gph);
                gph ^= s1 == 3;
                wgmma_fence();
#pragma unroll
                for (int kk = 0; kk < 4; kk++) wgmma_ss_n128_tb(lo, full_desc(dA + o0 + 2048) + 2 * kk, full_desc(dB + o1 + 1024) + 128 * kk, 1);
#pragma unroll
                for (int kk = 0; kk < 4; kk++) wgmma_ss_n128_tb(lo, full_desc(dA + o1) + 2 * kk, full_desc(dB + o1) + 128 * kk, 1);
                wgmma_commit();
                k += 2;
            };
            triple(std::true_type());
            fence_regs(acc);
            uint32_t pk[32];
#pragma unroll
            for (int j = 0; j < 32; j++) pk[j] = pack_bf16(acc[64 + 2 * j], acc[65 + 2 * j]);
            stage_acquire(0); stage_acquire(1);
            write_blocks(std::integral_constant<int, 8>(), 0, pk);
            publish_pair();
            triple(std::false_type());
            stage_acquire(0); stage_acquire(1);
            wgmma_wait<0>();
            fence_regs(lo);
            mbar_arrive_cluster_if(ln < 4, bars_lane + B_GEMPTY + 8 * ((k - 1 - (ln >> 1)) & 3));
#pragma unroll
            for (int b = 0; b < 2; b++) {
#pragma unroll
                for (int j = 16 * b; j < 16 * b + 16; j++) pk[j] = pack_bf16(acc[2 * j] + lo[2 * j], acc[2 * j + 1] + lo[2 * j + 1]);
                write_blocks(std::integral_constant<int, 4>(), b * 8192, pk + 16 * b);
                stage_publish(b);
            }
        }
    }
}

typedef CUresult (*EncodeFn)(CUtensorMap*, CUtensorMapDataType, cuuint32_t, void*, const cuuint64_t*, const cuuint64_t*,
                             const cuuint32_t*, const cuuint32_t*, CUtensorMapInterleave, CUtensorMapSwizzle,
                             CUtensorMapL2promotion, CUtensorMapFloatOOBfill);

void encode3(EncodeFn fn, CUtensorMap* m, const void* ptr, uint64_t d0, uint64_t d1, uint64_t d2, uint64_t s1, uint64_t s2,
             uint32_t b0, uint32_t b1, uint32_t b2) {
    cuuint64_t dims[3] = {d0, d1, d2};
    cuuint64_t strides[2] = {s1, s2};
    cuuint32_t box[3] = {b0, b1, b2};
    cuuint32_t es[3] = {1, 1, 1};
    fn(m, CU_TENSOR_MAP_DATA_TYPE_BFLOAT16, 3, const_cast<void*>(ptr), dims, strides, box, es, CU_TENSOR_MAP_INTERLEAVE_NONE,
       CU_TENSOR_MAP_SWIZZLE_128B, CU_TENSOR_MAP_L2_PROMOTION_NONE, CU_TENSOR_MAP_FLOAT_OOB_FILL_NONE);
}
void map_act(EncodeFn fn, CUtensorMap* m, const void* p, int rows, int cols, int box_rows) {
    encode3(fn, m, p, cols, rows, 1, (uint64_t)cols * 2, (uint64_t)cols * rows * 2, 64, box_rows, 1);
}
void map_wgt(EncodeFn fn, CUtensorMap* m, const void* p, int K, int N) {
    encode3(fn, m, p, 64, K, N / 64, (uint64_t)N * 2, 128, 64, 64, 2);
}

void build_schedule(Params& p) {
    int n = 0;
    auto add = [&](int type, int col, int row) { p.items[n++] = (uint16_t)(type << 13 | col << 4 | row); };
    int beta = 26, tail = 32, late = 6, early = 8, epos = 100;
    int order[16] = {6, 7, 8, 9, 10, 11, 12, 13, 14, 15, 5, 4, 3, 2, 1, 0};
    const char* plans = "xxcccccx,xxcccccx,xxxxx,xxcxlxx,xxlcclxcc,xxlcccccc,xxlxlccccc,xxlxlxccc";
    const char* pos[8];
    int len[8] = {}, start[8] = {};
    for (int s = 0; s < 8; s++) { pos[s] = plans; while (*plans && *plans++ != ',') {} }
    for (int i = 0; i < 160; i++) p.plan[i / 16][i % 16] = T_END << 13;
    for (int nx = 0, nc = 3, nl = 0; nx + nc + nl < 28 + 32 + 8;) {
        int s = -1;
        for (int i = 0; i < 8; i++) if (*pos[i] > ',' && (s < 0 || start[i] < start[s])) s = i;
        const char kind = *pos[s]++;
        int it;
        if (kind == 'x') { it = nx < 12 ? T_B << 13 | (nx % 3 * 4 + nx / 3) << 4 : T_Q << 13 | (nx - 12) << 4; nx++; }
        else if (kind == 'c') { it = (T_K + (nc & 1)) << 13 | nc / 2 << 4; nc++; }
        else { it = T_LOCAL << 13 | nl / 2 << 4 | (nl & 1); nl++; }
        p.plan[s][len[s]++] = (uint16_t)it;
        start[s] += kind == 'x' ? 48 : kind == 'c' ? 24 : 8;
    }
    for (int i = 0; i < 24; i++) p.plan[8 + i / 12][i % 12] = (uint16_t)((T_K + (i % 3 & 1)) << 13 | i % 3 / 2 << 4 | i / 3);
    const int a0 = n;
    for (int key = 0; key < 4000; key++)
        for (int r = 0; r < 32; r++)
            for (int j = 7; j >= 0; j--)
                if ((j ? (7 - j) * 40 + r * beta : 3999) == key) add(T_ATTN, 2 * order[r >> 1] + (r & 1), j);
    int t0 = n;
    for (int work = 0; work < 32 * 136 * tail / 100;) work += 4 * (p.items[--t0] & 15) + 3;
    for (int i = t0 + 1; i < n; i++)
        for (int j = i; j > t0 && (p.items[j] & 15) > (p.items[j - 1] & 15); j--) { const uint16_t t = p.items[j]; p.items[j] = p.items[j - 1]; p.items[j - 1] = t; }
    for (int r = early - 1; r >= 0; r--) {
        const uint16_t t = p.items[n - 32 + early - 1];
        for (int j = n - 32 + early - 1; j > n - epos; j--) p.items[j] = p.items[j - 1];
        p.items[n - epos] = t;
    }
    for (int moved = 0; moved < 2 && late >= 0; moved++)
        for (int i = a0; i < n; i++)
            if (p.items[i] == (T_ATTN << 13 | (2 * order[15] + moved) << 4 | late)) {
                for (int j = i; j + 1 < n; j++) p.items[j] = p.items[j + 1];
                p.items[n - 1] = (uint16_t)(T_ATTN << 13 | (2 * order[15] + moved) << 4 | late);
                break;
            }
    for (int s = 0, lo = 0, hi = WIDE - 1; s < 80; s++) {
        const int r = s / 2, g = r < 8 ? 32 + r : 2 * order[r / 2 - 4] + (r & 1);
        p.ostep[s >= WIDE ? s : r & 1 ? hi-- : lo++] = (uint8_t)(2 * g + (s & 1));
    }
}

void build_params(Params& p, void* const* d_in, void* d_out) {
    void* fnp = nullptr;
    cudaDriverEntryPointQueryResult qr;
    cudaGetDriverEntryPoint("cuTensorMapEncodeTiled", &fnp, cudaEnableDefault, &qr);
    EncodeFn fn = (EncodeFn)fnp;
    void* scr = nullptr;
    cudaGetSymbolAddress(&scr, g_scr);
    map_act(fn, &p.m[M_X], d_in[0], SEQ, 1024, 128);
    map_act(fn, &p.m[M_C], d_in[1], SEQ, 512, 128);
    map_wgt(fn, &p.m[M_WQ], d_in[2], 1024, 4096);
    map_wgt(fn, &p.m[M_WUK], d_in[3], 512, 4096);
    map_wgt(fn, &p.m[M_WUV], d_in[4], 512, 4096);
    map_wgt(fn, &p.m[M_WO], d_in[5], 4096, 1024);
    map_wgt(fn, &p.m[M_WQKV], d_in[7], 1024, 3072);
    map_wgt(fn, &p.m[M_WOB], d_in[8], 1024, 1024);
    encode3(fn, &p.m[M_SCR_LD], scr, 128, SEQ, G_TOTAL, 256, (uint64_t)SEQ * 256, 64, 128, 1);
    encode3(fn, &p.m[M_SCR_LOC], scr, 256, SEQ / 2, G_TOTAL, 512, (uint64_t)SEQ * 256, 64, 72, 1);
    encode3(fn, &p.m[M_SCR_LOQ], scr, 256, SEQ / 2, G_TOTAL, 512, (uint64_t)SEQ * 256, 64, 64, 1);
    encode3(fn, &p.m[M_SCR_ST], scr, 128, SEQ, G_TOTAL, 256, (uint64_t)SEQ * 256, 64, 64, 1);
    map_act(fn, &p.m[M_OUT], d_out, SEQ, 1024, 64);
    p.x = (const __nv_bfloat16*)d_in[0];
    p.gate_w = (const __nv_bfloat16*)d_in[9];
    p.zero = 0;
    p.wo = (const char*)d_in[5];
    p.out = (__nv_bfloat16*)d_out;
    build_schedule(p);
}

}

extern "C" void kernel_launch(void* const* d_in, const int* in_sizes, int n_in, void* d_out, int out_size) {
    (void)in_sizes; (void)n_in; (void)out_size;
    Params p;
    build_params(p, d_in, d_out);
    cudaFuncSetAttribute(fused_kernel, cudaFuncAttributeMaxDynamicSharedMemorySize, SM_TOTAL);
    fused_kernel<<<NCTA, 384, SM_TOTAL>>>(p);
}
```

```cpp
#include <cuda_runtime.h>
#include <cuda_bf16.h>
#include <cuda.h>
#include <stddef.h>
#include <stdint.h>
#include <type_traits>

namespace {

constexpr int SEQ = 2048;
constexpr int G_Q = 0, G_K = 32, G_V = 64, G_B = 96, G_CTX = G_Q, G_LOC = G_B, G_TOTAL = 120;

__device__ __align__(1024) __nv_bfloat16 g_scr[(size_t)G_TOTAL * SEQ * 128];
__device__ __align__(128) float g_gate[SEQ];

__device__ __forceinline__ uint32_t smem_u32(const void* p) { return (uint32_t)__cvta_generic_to_shared(p); }
__device__ __forceinline__ bool elect_one() {
    uint32_t p;
    asm volatile("{\n.reg .pred P;\nelect.sync _|P, 0xffffffff;\nselp.u32 %0, 1, 0, P;\n}\n" : "=r"(p));
    return p != 0;
}
__device__ __forceinline__ void mbar_init(uint32_t bar, uint32_t count) {
    asm volatile("mbarrier.init.shared::cta.b64 [%0], %1;" :: "r"(bar), "r"(count) : "memory");
}
__device__ __forceinline__ uint32_t cluster_rank() { uint32_t r; asm("mov.u32 %0, %%cluster_ctarank;" : "=r"(r)); return r; }
__device__ __forceinline__ uint32_t map_cta(uint32_t addr, uint32_t cta) {
    uint32_t r; asm("mapa.shared::cluster.u32 %0, %1, %2;" : "=r"(r) : "r"(addr), "r"(cta)); return r;
}
__device__ __forceinline__ void mbar_arrive_cluster_if(bool pred, uint32_t cluster_bar) {
    asm volatile("{\n.reg .pred P;\nsetp.ne.u32 P, %1, 0;\n@P mbarrier.arrive.shared::cluster.b64 _, [%0];\n}\n"
                 :: "r"(cluster_bar), "r"((uint32_t)pred) : "memory");
}
__device__ __forceinline__ void mbar_arrive_cluster_n_if(bool pred, uint32_t cluster_bar, uint32_t count) {
    asm volatile("{\n.reg .pred P;\nsetp.ne.u32 P, %1, 0;\n@P mbarrier.arrive.shared::cluster.b64 _, [%0], %2;\n}\n"
                 :: "r"(cluster_bar), "r"((uint32_t)pred), "r"(count) : "memory");
}
__device__ __forceinline__ void mbar_arrive_if(bool pred, uint32_t bar) {
    asm volatile("{\n.reg .pred P;\nsetp.ne.u32 P, %1, 0;\n@P mbarrier.arrive.shared::cta.b64 _, [%0];\n}\n"
                 :: "r"(bar), "r"((uint32_t)pred) : "memory");
}
__device__ __forceinline__ bool mbar_test(uint32_t bar, uint32_t parity) {
    uint32_t ok;
    asm volatile("{\n.reg .pred P;\nmbarrier.test_wait.parity.shared::cta.b64 P, [%1], %2;\nselp.u32 %0, 1, 0, P;\n}\n"
                 : "=r"(ok) : "r"(bar), "r"(parity) : "memory");
    return ok != 0;
}
__device__ __forceinline__ void mbar_wait(uint32_t bar, uint32_t parity) {
    asm volatile("{\n.reg .pred P;\n.reg .u32 c;\n"
                 "mov.u32 c, 0;\n"
                 "SPIN:\n"
                 "mbarrier.try_wait.parity.shared::cta.b64 P, [%0], %1;\n"
                 "@P bra DONE;\n"
                 "add.u32 c, c, 1;\n"
                 "setp.lt.u32 P, c, 4194304;\n"
                 "@P bra SPIN;\n"
                 "trap;\n"
                 "DONE:\n}\n" :: "r"(bar), "r"(parity) : "memory");
}
__device__ __forceinline__ void mbar_spin(uint32_t bar, uint32_t parity) {
    asm volatile("{\n.reg .pred P;\n"
                 "SPIN:\n"
                 "mbarrier.try_wait.parity.shared::cta.b64 P, [%0], %1;\n"
                 "@!P bra SPIN;\n}\n" :: "r"(bar), "r"(parity) : "memory");
}
__device__ __forceinline__ void bar_sync(int id, int n) { asm volatile("bar.sync %0, %1;" :: "r"(id), "r"(n) : "memory"); }
__device__ __forceinline__ void bar_arrive(int id, int n) { asm volatile("bar.arrive %0, %1;" :: "r"(id), "r"(n) : "memory"); }
__device__ __forceinline__ void fence_proxy_async_smem() { asm volatile("fence.proxy.async.shared::cta;" ::: "memory"); }
__device__ __forceinline__ void warp_expect_tx(uint32_t bar, uint32_t bytes) {
    asm volatile("{\n.reg .pred P;\nelect.sync _|P, 0xffffffff;\n@P mbarrier.arrive.expect_tx.shared::cta.b64 _, [%0], %1;\n}\n"
                 :: "r"(bar), "r"(bytes) : "memory");
}
constexpr uint64_t EVICT_FIRST = 0x12F0000000000000ull;
__device__ __forceinline__ void warp_tma_load(uint32_t dst, const CUtensorMap* map, uint32_t bar, int c0, int c1, int c2, bool stream) {
    if (stream)
        asm volatile("{\n.reg .pred P;\nelect.sync _|P, 0xffffffff;\n"
                     "@P cp.async.bulk.tensor.3d.shared::cluster.global.mbarrier::complete_tx::bytes.L2::cache_hint"
                     " [%0], [%1, {%3, %4, %5}], [%2], %6;\n}\n"
                     :: "r"(dst), "l"(map), "r"(bar), "r"(c0), "r"(c1), "r"(c2), "l"(EVICT_FIRST) : "memory");
    else
        asm volatile("{\n.reg .pred P;\nelect.sync _|P, 0xffffffff;\n"
                     "@P cp.async.bulk.tensor.3d.shared::cluster.global.mbarrier::complete_tx::bytes [%0], [%1, {%3, %4, %5}], [%2];\n}\n"
                     :: "r"(dst), "l"(map), "r"(bar), "r"(c0), "r"(c1), "r"(c2) : "memory");
}
__device__ __forceinline__ void warp_tma_load_pair(uint32_t dst, const CUtensorMap* map, uint32_t bar, int c0, int c1, int c2, bool stream) {
    if (stream)
        asm volatile("{\n.reg .pred P;\nelect.sync _|P, 0xffffffff;\n"
                     "@P cp.async.bulk.tensor.3d.shared::cluster.global.mbarrier::complete_tx::bytes.multicast::cluster.L2::cache_hint"
                     " [%0], [%1, {%3, %4, %5}], [%2], %6, %7;\n}\n"
                     :: "r"(dst), "l"(map), "r"(bar), "r"(c0), "r"(c1), "r"(c2), "h"((uint16_t)3), "l"(EVICT_FIRST) : "memory");
    else
        asm volatile("{\n.reg .pred P;\nelect.sync _|P, 0xffffffff;\n"
                     "@P cp.async.bulk.tensor.3d.shared::cluster.global.mbarrier::complete_tx::bytes.multicast::cluster"
                     " [%0], [%1, {%3, %4, %5}], [%2], %6;\n}\n"
                     :: "r"(dst), "l"(map), "r"(bar), "r"(c0), "r"(c1), "r"(c2), "h"((uint16_t)3) : "memory");
}
__device__ __forceinline__ void warp_bulk_load(uint32_t dst, const void* src, uint32_t bytes, uint32_t bar) {
    asm volatile("{\n.reg .pred P;\nelect.sync _|P, 0xffffffff;\n"
                 "@P cp.async.bulk.shared::cluster.global.mbarrier::complete_tx::bytes [%0], [%1], %2, [%3];\n}\n"
                 :: "r"(dst), "l"(src), "r"(bytes), "r"(bar) : "memory");
}
__device__ __forceinline__ void warp_tma_store(const CUtensorMap* map, uint32_t src, int c0, int c1, int c2, bool stream) {
    if (stream)
        asm volatile("{\n.reg .pred P;\nelect.sync _|P, 0xffffffff;\n"
                     "@P cp.async.bulk.tensor.3d.global.shared::cta.bulk_group.L2::cache_hint [%0, {%2, %3, %4}], [%1], %5;\n}\n"
                     :: "l"(map), "r"(src), "r"(c0), "r"(c1), "r"(c2), "l"(EVICT_FIRST) : "memory");
    else
        asm volatile("{\n.reg .pred P;\nelect.sync _|P, 0xffffffff;\n"
                     "@P cp.async.bulk.tensor.3d.global.shared::cta.bulk_group [%0, {%2, %3, %4}], [%1];\n}\n"
                     :: "l"(map), "r"(src), "r"(c0), "r"(c1), "r"(c2) : "memory");
}
__device__ __forceinline__ void warp_tma_add(const CUtensorMap* map, uint32_t src, int c0, int c1, int c2) {
    asm volatile("{\n.reg .pred P;\nelect.sync _|P, 0xffffffff;\n"
                 "@P cp.reduce.async.bulk.tensor.3d.global.shared::cta.add.tile.bulk_group [%0, {%2, %3, %4}], [%1];\n}\n"
                 :: "l"(map), "r"(src), "r"(c0), "r"(c1), "r"(c2) : "memory");
}
__device__ __forceinline__ void warp_bulk_store(void* dst, uint32_t src, uint32_t bytes) {
    asm volatile("{\n.reg .pred P;\nelect.sync _|P, 0xffffffff;\n"
                 "@P cp.async.bulk.global.shared::cta.bulk_group [%0], [%1], %2;\n}\n" :: "l"(dst), "r"(src), "r"(bytes) : "memory");
}
__device__ __forceinline__ void warp_prefetch(const void* src, uint32_t bytes) {
    asm volatile("{\n.reg .pred P;\nelect.sync _|P, 0xffffffff;\n@P cp.async.bulk.prefetch.L2.global [%0], %1;\n}\n" :: "l"(src), "r"(bytes) : "memory");
}
__device__ __forceinline__ void bulk_commit() { asm volatile("cp.async.bulk.commit_group;" ::: "memory"); }
template <int N> __device__ __forceinline__ void bulk_wait_read() { asm volatile("cp.async.bulk.wait_group.read %0;" :: "n"(N) : "memory"); }
template <int N> __device__ __forceinline__ void bulk_wait() { asm volatile("cp.async.bulk.wait_group %0;" :: "n"(N) : "memory"); }
__device__ __forceinline__ void wgmma_fence() { asm volatile("wgmma.fence.sync.aligned;" ::: "memory"); }
__device__ __forceinline__ void wgmma_commit() { asm volatile("wgmma.commit_group.sync.aligned;" ::: "memory"); }
template <int N> __device__ __forceinline__ void wgmma_wait() { asm volatile("wgmma.wait_group.sync.aligned %0;" :: "n"(N) : "memory"); }
template <int N> __device__ __forceinline__ void fence_regs(float (&d)[N]) {
#pragma unroll
    for (int i = 0; i < N; i++) asm volatile("" : "+f"(d[i]) :: "memory");
}
template <int N> __device__ __forceinline__ void fence_regs(uint32_t (&d)[N]) {
#pragma unroll
    for (int i = 0; i < N; i++) asm volatile("" : "+r"(d[i]) :: "memory");
}
template <int N> __device__ __forceinline__ void reg_dec() { asm volatile("setmaxnreg.dec.sync.aligned.u32 %0;" :: "n"(N)); }
template <int N> __device__ __forceinline__ void reg_inc() { asm volatile("setmaxnreg.inc.sync.aligned.u32 %0;" :: "n"(N)); }
__device__ __forceinline__ uint32_t pack_bf16(float lo, float hi) {
    uint32_t r; asm("cvt.rn.bf16x2.f32 %0, %1, %2;" : "=r"(r) : "f"(hi), "f"(lo)); return r;
}
__device__ __forceinline__ void stmatrix_x4(uint32_t addr, uint32_t r0, uint32_t r1, uint32_t r2, uint32_t r3) {
    asm volatile("stmatrix.sync.aligned.m8n8.x4.shared.b16 [%0], {%1, %2, %3, %4};"
                 :: "r"(addr), "r"(r0), "r"(r1), "r"(r2), "r"(r3) : "memory");
}
__device__ __forceinline__ float ex2(float x) { float y; asm("ex2.approx.ftz.f32 %0, %1;" : "=f"(y) : "f"(x)); return y; }

constexpr uint32_t DESC_HI = (1024 >> 4) | (1u << 30);
__device__ __forceinline__ uint32_t make_desc(uint32_t addr, uint32_t lbo) {
    uint32_t lo = ((addr & 0x3FFFF) >> 4) | ((lbo >> 4) << 16);
    asm volatile("" : "+r"(lo));
    return lo;
}
__device__ __forceinline__ uint64_t full_desc(uint32_t lo) {
    uint64_t d; asm("mov.b64 %0, {%1, %2};" : "=l"(d) : "r"(lo), "r"(DESC_HI)); return d;
}

__device__ __forceinline__ void wgmma_ss_n256_tb_init(float (&d)[128], uint64_t da, uint64_t db) {
    asm volatile("{\n.reg .pred p;\n"
        "setp.ne.b32 p, 0, 0;\n"
        "wgmma.mma_async.sync.aligned.m64n256k16.f32.bf16.bf16 "
        "{%0, %1, %2, %3, %4, %5, %6, %7, %8, %9, %10, %11, %12, %13, %14, %15, %16, %17, %18, %19, %20, "
        "%21, %22, %23, %24, %25, %26, %27, %28, %29, %30, %31, %32, %33, %34, %35, %36, %37, %38, %39, %40, "
        "%41, %42, %43, %44, %45, %46, %47, %48, %49, %50, %51, %52, %53, %54, %55, %56, %57, %58, %59, %60, "
        "%61, %62, %63, %64, %65, %66, %67, %68, %69, %70, %71, %72, %73, %74, %75, %76, %77, %78, %79, %80, "
        "%81, %82, %83, %84, %85, %86, %87, %88, %89, %90, %91, %92, %93, %94, %95, %96, %97, %98, %99, "
        "%100, %101, %102, %103, %104, %105, %106, %107, %108, %109, %110, %111, %112, %113, %114, %115, "
        "%116, %117, %118, %119, %120, %121, %122, %123, %124, %125, %126, %127},"
        " %128, %129, p, 1, 1, 0, 1;\n}\n"
        : "=f"(d[0]), "=f"(d[1]), "=f"(d[2]), "=f"(d[3]), "=f"(d[4]), "=f"(d[5]), "=f"(d[6]), "=f"(d[7]),
        "=f"(d[8]), "=f"(d[9]), "=f"(d[10]), "=f"(d[11]), "=f"(d[12]), "=f"(d[13]), "=f"(d[14]), "=f"(d[15]),
        "=f"(d[16]), "=f"(d[17]), "=f"(d[18]), "=f"(d[19]), "=f"(d[20]), "=f"(d[21]), "=f"(d[22]),
        "=f"(d[23]), "=f"(d[24]), "=f"(d[25]), "=f"(d[26]), "=f"(d[27]), "=f"(d[28]), "=f"(d[29]),
        "=f"(d[30]), "=f"(d[31]), "=f"(d[32]), "=f"(d[33]), "=f"(d[34]), "=f"(d[35]), "=f"(d[36]),
        "=f"(d[37]), "=f"(d[38]), "=f"(d[39]), "=f"(d[40]), "=f"(d[41]), "=f"(d[42]), "=f"(d[43]),
        "=f"(d[44]), "=f"(d[45]), "=f"(d[46]), "=f"(d[47]), "=f"(d[48]), "=f"(d[49]), "=f"(d[50]),
        "=f"(d[51]), "=f"(d[52]), "=f"(d[53]), "=f"(d[54]), "=f"(d[55]), "=f"(d[56]), "=f"(d[57]),
        "=f"(d[58]), "=f"(d[59]), "=f"(d[60]), "=f"(d[61]), "=f"(d[62]), "=f"(d[63]), "=f"(d[64]),
        "=f"(d[65]), "=f"(d[66]), "=f"(d[67]), "=f"(d[68]), "=f"(d[69]), "=f"(d[70]), "=f"(d[71]),
        "=f"(d[72]), "=f"(d[73]), "=f"(d[74]), "=f"(d[75]), "=f"(d[76]), "=f"(d[77]), "=f"(d[78]),
        "=f"(d[79]), "=f"(d[80]), "=f"(d[81]), "=f"(d[82]), "=f"(d[83]), "=f"(d[84]), "=f"(d[85]),
        "=f"(d[86]), "=f"(d[87]), "=f"(d[88]), "=f"(d[89]), "=f"(d[90]), "=f"(d[91]), "=f"(d[92]),
        "=f"(d[93]), "=f"(d[94]), "=f"(d[95]), "=f"(d[96]), "=f"(d[97]), "=f"(d[98]), "=f"(d[99]),
        "=f"(d[100]), "=f"(d[101]), "=f"(d[102]), "=f"(d[103]), "=f"(d[104]), "=f"(d[105]), "=f"(d[106]),
        "=f"(d[107]), "=f"(d[108]), "=f"(d[109]), "=f"(d[110]), "=f"(d[111]), "=f"(d[112]), "=f"(d[113]),
        "=f"(d[114]), "=f"(d[115]), "=f"(d[116]), "=f"(d[117]), "=f"(d[118]), "=f"(d[119]), "=f"(d[120]),
        "=f"(d[121]), "=f"(d[122]), "=f"(d[123]), "=f"(d[124]), "=f"(d[125]), "=f"(d[126]), "=f"(d[127])
        : "l"(da), "l"(db));
}
__device__ __forceinline__ void wgmma_ss_n256_tb(float (&d)[128], uint64_t da, uint64_t db, int scale_d) {
    asm volatile("{\n.reg .pred p;\n"
        "setp.ne.b32 p, %130, 0;\n"
        "wgmma.mma_async.sync.aligned.m64n256k16.f32.bf16.bf16 "
        "{%0, %1, %2, %3, %4, %5, %6, %7, %8, %9, %10, %11, %12, %13, %14, %15, %16, %17, %18, %19, %20, "
        "%21, %22, %23, %24, %25, %26, %27, %28, %29, %30, %31, %32, %33, %34, %35, %36, %37, %38, %39, %40, "
        "%41, %42, %43, %44, %45, %46, %47, %48, %49, %50, %51, %52, %53, %54, %55, %56, %57, %58, %59, %60, "
        "%61, %62, %63, %64, %65, %66, %67, %68, %69, %70, %71, %72, %73, %74, %75, %76, %77, %78, %79, %80, "
        "%81, %82, %83, %84, %85, %86, %87, %88, %89, %90, %91, %92, %93, %94, %95, %96, %97, %98, %99, "
        "%100, %101, %102, %103, %104, %105, %106, %107, %108, %109, %110, %111, %112, %113, %114, %115, "
        "%116, %117, %118, %119, %120, %121, %122, %123, %124, %125, %126, %127},"
        " %128, %129, p, 1, 1, 0, 1;\n}\n"
        : "+f"(d[0]), "+f"(d[1]), "+f"(d[2]), "+f"(d[3]), "+f"(d[4]), "+f"(d[5]), "+f"(d[6]), "+f"(d[7]),
        "+f"(d[8]), "+f"(d[9]), "+f"(d[10]), "+f"(d[11]), "+f"(d[12]), "+f"(d[13]), "+f"(d[14]), "+f"(d[15]),
        "+f"(d[16]), "+f"(d[17]), "+f"(d[18]), "+f"(d[19]), "+f"(d[20]), "+f"(d[21]), "+f"(d[22]),
        "+f"(d[23]), "+f"(d[24]), "+f"(d[25]), "+f"(d[26]), "+f"(d[27]), "+f"(d[28]), "+f"(d[29]),
        "+f"(d[30]), "+f"(d[31]), "+f"(d[32]), "+f"(d[33]), "+f"(d[34]), "+f"(d[35]), "+f"(d[36]),
        "+f"(d[37]), "+f"(d[38]), "+f"(d[39]), "+f"(d[40]), "+f"(d[41]), "+f"(d[42]), "+f"(d[43]),
        "+f"(d[44]), "+f"(d[45]), "+f"(d[46]), "+f"(d[47]), "+f"(d[48]), "+f"(d[49]), "+f"(d[50]),
        "+f"(d[51]), "+f"(d[52]), "+f"(d[53]), "+f"(d[54]), "+f"(d[55]), "+f"(d[56]), "+f"(d[57]),
        "+f"(d[58]), "+f"(d[59]), "+f"(d[60]), "+f"(d[61]), "+f"(d[62]), "+f"(d[63]), "+f"(d[64]),
        "+f"(d[65]), "+f"(d[66]), "+f"(d[67]), "+f"(d[68]), "+f"(d[69]), "+f"(d[70]), "+f"(d[71]),
        "+f"(d[72]), "+f"(d[73]), "+f"(d[74]), "+f"(d[75]), "+f"(d[76]), "+f"(d[77]), "+f"(d[78]),
        "+f"(d[79]), "+f"(d[80]), "+f"(d[81]), "+f"(d[82]), "+f"(d[83]), "+f"(d[84]), "+f"(d[85]),
        "+f"(d[86]), "+f"(d[87]), "+f"(d[88]), "+f"(d[89]), "+f"(d[90]), "+f"(d[91]), "+f"(d[92]),
        "+f"(d[93]), "+f"(d[94]), "+f"(d[95]), "+f"(d[96]), "+f"(d[97]), "+f"(d[98]), "+f"(d[99]),
        "+f"(d[100]), "+f"(d[101]), "+f"(d[102]), "+f"(d[103]), "+f"(d[104]), "+f"(d[105]), "+f"(d[106]),
        "+f"(d[107]), "+f"(d[108]), "+f"(d[109]), "+f"(d[110]), "+f"(d[111]), "+f"(d[112]), "+f"(d[113]),
        "+f"(d[114]), "+f"(d[115]), "+f"(d[116]), "+f"(d[117]), "+f"(d[118]), "+f"(d[119]), "+f"(d[120]),
        "+f"(d[121]), "+f"(d[122]), "+f"(d[123]), "+f"(d[124]), "+f"(d[125]), "+f"(d[126]), "+f"(d[127])
        : "l"(da), "l"(db), "r"(scale_d));
}
__device__ __forceinline__ void wgmma_ss_n128(float (&d)[64], uint64_t da, uint64_t db, int scale_d) {
    asm volatile("{\n.reg .pred p;\n"
        "setp.ne.b32 p, %66, 0;\n"
        "wgmma.mma_async.sync.aligned.m64n128k16.f32.bf16.bf16 "
        "{%0, %1, %2, %3, %4, %5, %6, %7, %8, %9, %10, %11, %12, %13, %14, %15, %16, %17, %18, %19, %20, "
        "%21, %22, %23, %24, %25, %26, %27, %28, %29, %30, %31, %32, %33, %34, %35, %36, %37, %38, %39, %40, "
        "%41, %42, %43, %44, %45, %46, %47, %48, %49, %50, %51, %52, %53, %54, %55, %56, %57, %58, %59, %60, "
        "%61, %62, %63},"
        " %64, %65, p, 1, 1, 0, 0;\n}\n"
        : "+f"(d[0]), "+f"(d[1]), "+f"(d[2]), "+f"(d[3]), "+f"(d[4]), "+f"(d[5]), "+f"(d[6]), "+f"(d[7]),
        "+f"(d[8]), "+f"(d[9]), "+f"(d[10]), "+f"(d[11]), "+f"(d[12]), "+f"(d[13]), "+f"(d[14]), "+f"(d[15]),
        "+f"(d[16]), "+f"(d[17]), "+f"(d[18]), "+f"(d[19]), "+f"(d[20]), "+f"(d[21]), "+f"(d[22]),
        "+f"(d[23]), "+f"(d[24]), "+f"(d[25]), "+f"(d[26]), "+f"(d[27]), "+f"(d[28]), "+f"(d[29]),
        "+f"(d[30]), "+f"(d[31]), "+f"(d[32]), "+f"(d[33]), "+f"(d[34]), "+f"(d[35]), "+f"(d[36]),
        "+f"(d[37]), "+f"(d[38]), "+f"(d[39]), "+f"(d[40]), "+f"(d[41]), "+f"(d[42]), "+f"(d[43]),
        "+f"(d[44]), "+f"(d[45]), "+f"(d[46]), "+f"(d[47]), "+f"(d[48]), "+f"(d[49]), "+f"(d[50]),
        "+f"(d[51]), "+f"(d[52]), "+f"(d[53]), "+f"(d[54]), "+f"(d[55]), "+f"(d[56]), "+f"(d[57]),
        "+f"(d[58]), "+f"(d[59]), "+f"(d[60]), "+f"(d[61]), "+f"(d[62]), "+f"(d[63])
        : "l"(da), "l"(db), "r"(scale_d));
}
__device__ __forceinline__ void wgmma_rs_n128_tb(float (&d)[64], uint32_t a0, uint32_t a1, uint32_t a2, uint32_t a3, uint64_t db, int scale_d) {
    asm volatile("{\n.reg .pred p;\n"
        "setp.ne.b32 p, %69, 0;\n"
        "wgmma.mma_async.sync.aligned.m64n128k16.f32.bf16.bf16 "
        "{%0, %1, %2, %3, %4, %5, %6, %7, %8, %9, %10, %11, %12, %13, %14, %15, %16, %17, %18, %19, %20, "
        "%21, %22, %23, %24, %25, %26, %27, %28, %29, %30, %31, %32, %33, %34, %35, %36, %37, %38, %39, %40, "
        "%41, %42, %43, %44, %45, %46, %47, %48, %49, %50, %51, %52, %53, %54, %55, %56, %57, %58, %59, %60, "
        "%61, %62, %63},"
        " {%64, %65, %66, %67}, %68, p, 1, 1, 1;\n}\n"
        : "+f"(d[0]), "+f"(d[1]), "+f"(d[2]), "+f"(d[3]), "+f"(d[4]), "+f"(d[5]), "+f"(d[6]), "+f"(d[7]),
        "+f"(d[8]), "+f"(d[9]), "+f"(d[10]), "+f"(d[11]), "+f"(d[12]), "+f"(d[13]), "+f"(d[14]), "+f"(d[15]),
        "+f"(d[16]), "+f"(d[17]), "+f"(d[18]), "+f"(d[19]), "+f"(d[20]), "+f"(d[21]), "+f"(d[22]),
        "+f"(d[23]), "+f"(d[24]), "+f"(d[25]), "+f"(d[26]), "+f"(d[27]), "+f"(d[28]), "+f"(d[29]),
        "+f"(d[30]), "+f"(d[31]), "+f"(d[32]), "+f"(d[33]), "+f"(d[34]), "+f"(d[35]), "+f"(d[36]),
        "+f"(d[37]), "+f"(d[38]), "+f"(d[39]), "+f"(d[40]), "+f"(d[41]), "+f"(d[42]), "+f"(d[43]),
        "+f"(d[44]), "+f"(d[45]), "+f"(d[46]), "+f"(d[47]), "+f"(d[48]), "+f"(d[49]), "+f"(d[50]),
        "+f"(d[51]), "+f"(d[52]), "+f"(d[53]), "+f"(d[54]), "+f"(d[55]), "+f"(d[56]), "+f"(d[57]),
        "+f"(d[58]), "+f"(d[59]), "+f"(d[60]), "+f"(d[61]), "+f"(d[62]), "+f"(d[63])
        : "r"(a0), "r"(a1), "r"(a2), "r"(a3), "l"(db), "r"(scale_d));
}
__device__ __forceinline__ void wgmma_ss_n128_tb_init(float (&d)[64], uint64_t da, uint64_t db) {
    asm volatile("{\n.reg .pred p;\n"
        "setp.ne.b32 p, 0, 0;\n"
        "wgmma.mma_async.sync.aligned.m64n128k16.f32.bf16.bf16 "
        "{%0, %1, %2, %3, %4, %5, %6, %7, %8, %9, %10, %11, %12, %13, %14, %15, %16, %17, %18, %19, %20, "
        "%21, %22, %23, %24, %25, %26, %27, %28, %29, %30, %31, %32, %33, %34, %35, %36, %37, %38, %39, %40, "
        "%41, %42, %43, %44, %45, %46, %47, %48, %49, %50, %51, %52, %53, %54, %55, %56, %57, %58, %59, %60, "
        "%61, %62, %63},"
        " %64, %65, p, 1, 1, 0, 1;\n}\n"
        : "=f"(d[0]), "=f"(d[1]), "=f"(d[2]), "=f"(d[3]), "=f"(d[4]), "=f"(d[5]), "=f"(d[6]), "=f"(d[7]),
        "=f"(d[8]), "=f"(d[9]), "=f"(d[10]), "=f"(d[11]), "=f"(d[12]), "=f"(d[13]), "=f"(d[14]), "=f"(d[15]),
        "=f"(d[16]), "=f"(d[17]), "=f"(d[18]), "=f"(d[19]), "=f"(d[20]), "=f"(d[21]), "=f"(d[22]),
        "=f"(d[23]), "=f"(d[24]), "=f"(d[25]), "=f"(d[26]), "=f"(d[27]), "=f"(d[28]), "=f"(d[29]),
        "=f"(d[30]), "=f"(d[31]), "=f"(d[32]), "=f"(d[33]), "=f"(d[34]), "=f"(d[35]), "=f"(d[36]),
        "=f"(d[37]), "=f"(d[38]), "=f"(d[39]), "=f"(d[40]), "=f"(d[41]), "=f"(d[42]), "=f"(d[43]),
        "=f"(d[44]), "=f"(d[45]), "=f"(d[46]), "=f"(d[47]), "=f"(d[48]), "=f"(d[49]), "=f"(d[50]),
        "=f"(d[51]), "=f"(d[52]), "=f"(d[53]), "=f"(d[54]), "=f"(d[55]), "=f"(d[56]), "=f"(d[57]),
        "=f"(d[58]), "=f"(d[59]), "=f"(d[60]), "=f"(d[61]), "=f"(d[62]), "=f"(d[63])
        : "l"(da), "l"(db));
}
__device__ __forceinline__ void wgmma_ss_n128_tb(float (&d)[64], uint64_t da, uint64_t db, int scale_d) {
    asm volatile("{\n.reg .pred p;\n"
        "setp.ne.b32 p, %66, 0;\n"
        "wgmma.mma_async.sync.aligned.m64n128k16.f32.bf16.bf16 "
        "{%0, %1, %2, %3, %4, %5, %6, %7, %8, %9, %10, %11, %12, %13, %14, %15, %16, %17, %18, %19, %20, "
        "%21, %22, %23, %24, %25, %26, %27, %28, %29, %30, %31, %32, %33, %34, %35, %36, %37, %38, %39, %40, "
        "%41, %42, %43, %44, %45, %46, %47, %48, %49, %50, %51, %52, %53, %54, %55, %56, %57, %58, %59, %60, "
        "%61, %62, %63},"
        " %64, %65, p, 1, 1, 0, 1;\n}\n"
        : "+f"(d[0]), "+f"(d[1]), "+f"(d[2]), "+f"(d[3]), "+f"(d[4]), "+f"(d[5]), "+f"(d[6]), "+f"(d[7]),
        "+f"(d[8]), "+f"(d[9]), "+f"(d[10]), "+f"(d[11]), "+f"(d[12]), "+f"(d[13]), "+f"(d[14]), "+f"(d[15]),
        "+f"(d[16]), "+f"(d[17]), "+f"(d[18]), "+f"(d[19]), "+f"(d[20]), "+f"(d[21]), "+f"(d[22]),
        "+f"(d[23]), "+f"(d[24]), "+f"(d[25]), "+f"(d[26]), "+f"(d[27]), "+f"(d[28]), "+f"(d[29]),
        "+f"(d[30]), "+f"(d[31]), "+f"(d[32]), "+f"(d[33]), "+f"(d[34]), "+f"(d[35]), "+f"(d[36]),
        "+f"(d[37]), "+f"(d[38]), "+f"(d[39]), "+f"(d[40]), "+f"(d[41]), "+f"(d[42]), "+f"(d[43]),
        "+f"(d[44]), "+f"(d[45]), "+f"(d[46]), "+f"(d[47]), "+f"(d[48]), "+f"(d[49]), "+f"(d[50]),
        "+f"(d[51]), "+f"(d[52]), "+f"(d[53]), "+f"(d[54]), "+f"(d[55]), "+f"(d[56]), "+f"(d[57]),
        "+f"(d[58]), "+f"(d[59]), "+f"(d[60]), "+f"(d[61]), "+f"(d[62]), "+f"(d[63])
        : "l"(da), "l"(db), "r"(scale_d));
}

enum { M_X = 0, M_C, M_WQ, M_WUK, M_WUV, M_WQKV, M_WO, M_WOB, M_SCR_LD, M_SCR_LOC, M_SCR_LOQ, M_SCR_ST, M_OUT, M_COUNT };
enum { T_Q = 0, T_K, T_V, T_B, T_OUT, T_LOCAL, T_ATTN, T_END };
constexpr int NCTA = 132;
constexpr int NITEMS = 256;
constexpr int TRIPLES = 2, WIDE = 80 - 3 * TRIPLES;
struct Params {
    CUtensorMap m[M_COUNT];
    const __nv_bfloat16* x;
    const __nv_bfloat16* gate_w;
    const char* wo;
    __nv_bfloat16* out;
    uint32_t zero;
    uint16_t plan[10][16];
    uint16_t items[NITEMS];
    uint8_t ostep[80];
};
__device__ __forceinline__ int item_type(int it) { return it >> 13; }
__device__ __forceinline__ int item_row(int it) { return it & 15; }
__device__ __forceinline__ int item_col(int it) { return (it >> 4) & 31; }
__device__ __forceinline__ int item_asc(int it) { return (it >> 9) & 1; }
constexpr int ITEM_READY = 1 << 10;

struct __align__(128) Sync {
    unsigned long long count[4];
    __align__(128) unsigned long long ctx[16];
    unsigned next, next_out, done;
    __align__(128) unsigned step[32][2];
    unsigned split[32];
};
__device__ Sync g_sync;

constexpr uint32_t GST_BYTES = 49152, SM_KV = 65536, SM_STAGING = 196608, SM_BARS = SM_STAGING + 32768;
constexpr uint32_t B_GFULL = 0, B_GEMPTY = 32, B_AFULL = 64, B_AEMPTY = 112, B_SFULL = 160, B_SEMPTY = 192,
                   B_IFULL = 224, B_IEMPTY = 288, B_XFREE = 352, B_WANT = 384, B_MEET = 392, B_HALF = 416,
                   SM_ORDY = 448, SM_QUEUE = 456, B_ALT = 488, B_QFREE = 504, SM_GATE = 512, SM_TOTAL = SM_BARS + 1536;
constexpr int QDEPTH = 8;
constexpr int FIRST_PAIR = 6;
constexpr int K_MEET = 19, K_SPLIT = 30;
constexpr int K_FETCH = 20;
constexpr uint32_t LOC_PLANE = 72 * 128;
constexpr float LOC_SCALE = 0.17677669529663687f * 1.4426950408889634f;
constexpr float SUM_LIMIT = 1152921504606846976.f;
constexpr float REF_RANGE = 32.f;

__device__ __forceinline__ unsigned ld_acquire(const unsigned* p) {
    unsigned v; asm volatile("ld.acquire.gpu.global.u32 %0, [%1];" : "=r"(v) : "l"(p) : "memory"); return v;
}
__device__ __forceinline__ unsigned long long ld_acquire(const unsigned long long* p) {
    unsigned long long v; asm volatile("ld.acquire.gpu.global.u64 %0, [%1];" : "=l"(v) : "l"(p) : "memory"); return v;
}
__device__ __forceinline__ void spin_guard(unsigned& n) {
    asm volatile("{\n.reg .pred P;\nadd.u32 %0, %0, 1;\nsetp.gt.u32 P, %0, 16777216;\n@P trap;\n}\n" : "+r"(n));
    if (n > 1) __nanosleep(100);
}
__device__ __forceinline__ void red_add(unsigned long long* p, unsigned long long v) {
    asm volatile("red.release.gpu.global.add.u64 [%0], %1;" :: "l"(p), "l"(v) : "memory");
}
__device__ __forceinline__ float rcp(float x) { float y; asm("rcp.approx.ftz.f32 %0, %1;" : "=f"(y) : "f"(x)); return y; }
__device__ __forceinline__ float lds_f32(uint32_t addr) {
    float v; asm volatile("ld.shared.f32 %0, [%1];" : "=f"(v) : "r"(addr) : "memory"); return v;
}
__device__ __forceinline__ void ldsm_x4(uint32_t (&r)[4], uint32_t addr) {
    asm volatile("ldmatrix.sync.aligned.m8n8.x4.shared.b16 {%0, %1, %2, %3}, [%4];"
                 : "=r"(r[0]), "=r"(r[1]), "=r"(r[2]), "=r"(r[3]) : "r"(addr) : "memory");
}
__device__ __forceinline__ void ldsm_x4_t(uint32_t (&r)[4], uint32_t addr) {
    asm volatile("ldmatrix.sync.aligned.m8n8.x4.trans.shared.b16 {%0, %1, %2, %3}, [%4];"
                 : "=r"(r[0]), "=r"(r[1]), "=r"(r[2]), "=r"(r[3]) : "r"(addr) : "memory");
}
__device__ __forceinline__ void mma_k16(float (&d)[4], const uint32_t (&a)[4], uint32_t b0, uint32_t b1) {
    asm("mma.sync.aligned.m16n8k16.row.col.f32.bf16.bf16.f32 {%0,%1,%2,%3}, {%4,%5,%6,%7}, {%8,%9}, {%0,%1,%2,%3};"
        : "+f"(d[0]), "+f"(d[1]), "+f"(d[2]), "+f"(d[3]) : "r"(a[0]), "r"(a[1]), "r"(a[2]), "r"(a[3]), "r"(b0), "r"(b1));
}
__device__ __forceinline__ void mma_k16_init(float (&d)[4], const uint32_t (&a)[4], uint32_t b0, uint32_t b1) {
    asm("{\n.reg .f32 z;\nmov.f32 z, 0f00000000;\n"
        "mma.sync.aligned.m16n8k16.row.col.f32.bf16.bf16.f32 {%0,%1,%2,%3}, {%4,%5,%6,%7}, {%8,%9}, {z,z,z,z};\n}\n"
        : "=f"(d[0]), "=f"(d[1]), "=f"(d[2]), "=f"(d[3]) : "r"(a[0]), "r"(a[1]), "r"(a[2]), "r"(a[3]), "r"(b0), "r"(b1));
}
__device__ __forceinline__ void mma_k8(float (&d)[4], uint32_t a0, uint32_t a1, uint32_t b0) {
    asm("mma.sync.aligned.m16n8k8.row.col.f32.bf16.bf16.f32 {%0,%1,%2,%3}, {%4,%5}, {%6}, {%0,%1,%2,%3};"
        : "+f"(d[0]), "+f"(d[1]), "+f"(d[2]), "+f"(d[3]) : "r"(a0), "r"(a1), "r"(b0));
}
template <typename T, int N> __device__ __forceinline__ void zero_regs(T (&d)[N]) {
#pragma unroll
    for (int i = 0; i < N; i++) d[i] = 0;
}
__device__ __forceinline__ float quad_max(float v) {
    v = fmaxf(v, __shfl_xor_sync(0xffffffffu, v, 1));
    return fmaxf(v, __shfl_xor_sync(0xffffffffu, v, 2));
}
__device__ __forceinline__ float quad_sum(float v) {
    v += __shfl_xor_sync(0xffffffffu, v, 1);
    return v + __shfl_xor_sync(0xffffffffu, v, 2);
}

__device__ __forceinline__ void qk_gemm(float (&s)[64], uint32_t q_lo, uint32_t k_lo) {
    const uint64_t dq = full_desc(q_lo), dk = full_desc(k_lo);
    fence_regs(s);
    wgmma_fence();
#pragma unroll
    for (int kk = 0; kk < 8; kk++) {
        const uint32_t o = (kk >> 2) * 1024 + (kk & 3) * 2;
        wgmma_ss_n128(s, dq + o, dk + o, kk != 0);
    }
    wgmma_commit();
}
__device__ __forceinline__ void pv_gemm(float (&o)[64], uint32_t (&p)[32], uint32_t v_lo, int accumulate) {
    const uint64_t dv = full_desc(v_lo);
    fence_regs(o);
    fence_regs(p);
    wgmma_fence();
#pragma unroll
    for (int kk = 0; kk < 8; kk++)
        wgmma_rs_n128_tb(o, p[4 * kk], p[4 * kk + 1], p[4 * kk + 2], p[4 * kk + 3], dv + kk * 128, kk != 0 || accumulate);
    wgmma_commit();
}
__device__ __forceinline__ void row_max(const float (&s)[64], float& x0, float& x1) {
    float z0 = fmaxf(s[0], s[1]), z1 = fmaxf(s[2], s[3]);
    x0 = fmaxf(s[4], s[5]); x1 = fmaxf(s[6], s[7]);
#pragma unroll
    for (int j = 2; j < 16; j += 2) {
        z0 = fmaxf(z0, fmaxf(s[4 * j], s[4 * j + 1]));
        z1 = fmaxf(z1, fmaxf(s[4 * j + 2], s[4 * j + 3]));
        x0 = fmaxf(x0, fmaxf(s[4 * j + 4], s[4 * j + 5]));
        x1 = fmaxf(x1, fmaxf(s[4 * j + 6], s[4 * j + 7]));
    }
    x0 = quad_max(fmaxf(x0, z0)); x1 = quad_max(fmaxf(x1, z1));
}
__device__ __forceinline__ void exp_pack(uint32_t (&p)[32], const float (&s)[64], float& r0, float& r1) {
#pragma unroll
    for (int j = 0; j < 16; j++) {
        const float e0 = ex2(s[4 * j]), e1 = ex2(s[4 * j + 1]), e2 = ex2(s[4 * j + 2]), e3 = ex2(s[4 * j + 3]);
        if (j == 0) { r0 = e0 + e1; r1 = e2 + e3; }
        else { r0 += e0 + e1; r1 += e2 + e3; }
        p[2 * j] = pack_bf16(e0, e1);
        p[2 * j + 1] = pack_bf16(e2, e3);
    }
}
__device__ __forceinline__ void shift_rows(float (&s)[64], float d0, float d1) {
#pragma unroll
    for (int j = 0; j < 16; j++) { s[4 * j] -= d0; s[4 * j + 1] -= d0; s[4 * j + 2] -= d1; s[4 * j + 3] -= d1; }
}
constexpr float MASKED = -3e38f;
template <int J0>
__device__ __forceinline__ void mask_triangle(float (&s)[64], float thr) {
#pragma unroll
    for (int j = 0; j < 16; j++) {
        const float m = __saturatef((float)(8 * (j >> 1) + (j & 1)) - thr);
        const int i = 4 * (J0 + (j >> 1)) + (j & 1);
        s[i] = fmaf(m, MASKED, s[i]);
        if (j < 14) s[i + 6] = fmaf(m, MASKED, s[i + 6]);
    }
}
__device__ __forceinline__ void causal_mask(float (&s)[64], float thr, int wg) {
    asm volatile("" : "+f"(thr));
    if (wg == 0) {
        mask_triangle<0>(s, thr);
#pragma unroll
        for (int j = 32; j < 64; j++) s[j] += MASKED;
    } else {
        mask_triangle<8>(s, thr);
    }
}

__global__ void __cluster_dims__(2, 1, 1) __launch_bounds__(384, 1) fused_kernel(const __grid_constant__ Params prm) {
    extern __shared__ __align__(1024) uint8_t smem[];
    const uint32_t sb = smem_u32(smem), bars = sb + SM_BARS;
    const int warp = __shfl_sync(0xffffffffu, threadIdx.x >> 5, 0), lane = threadIdx.x & 31;

    const uint32_t rank = cluster_rank();
    const uint32_t bars0 = map_cta(bars, 0), bars_peer = map_cta(bars, rank ^ 1);

    auto plan_index = [&]() -> uint32_t {
        uint32_t p = blockIdx.x >> 1;
        asm volatile("" : "+r"(p));
        const uint32_t r = (p - 36) * 37 >> 8;
        return p < 4 ? 60 + p : p < 36 ? (p - 4 & 7) * 8 + (p - 4 >> 3) : p < 64 ? (p - 36 - 7 * r) * 8 + 4 + r : p;
    };
    auto first_item = [&]() -> int {
        const uint32_t pair = plan_index();
        const uint32_t slot = pair & 7, c = slot * 11 >> 5;
        return pair < 64 ? T_B << 13 | (4 * slot - 11 * c) << 4 | (2 * (pair >> 3) + rank) : T_K << 13 | (8 * slot + rank);
    };
    if (warp == 0) {
        if (elect_one()) {
            for (int k = 0; k < 4; k++) mbar_init(bars + B_GFULL + 8 * k, 1);
            asm volatile("fence.mbarrier_init.release.cluster;" ::: "memory");
            fence_proxy_async_smem();
        }
        __syncwarp();
        const int first_it = __shfl_sync(0xffffffffu, first_item(), 0);
        asm volatile("barrier.cluster.arrive.relaxed.aligned;" ::: "memory");
        const CUtensorMap* ma = &prm.m[item_type(first_it) == T_K ? M_C : M_X];
        const CUtensorMap* mb = &prm.m[M_WQ + item_type(first_it)];
#pragma unroll
        for (int k = 0; k < 2; k++) {
            const uint32_t dst = sb + k * GST_BYTES, fb = bars + B_GFULL + 8 * k;
            warp_expect_tx(fb, GST_BYTES);
            warp_tma_load(dst + 16384, mb, fb, 0, k * 64, item_col(first_it) * 4, true);
            warp_tma_load(dst, ma, fb, k * 64, item_row(first_it) * 128, 0, false);
            warp_tma_load(dst + 32768, mb, fb, 0, k * 64, item_col(first_it) * 4 + 2, true);
        }
    }
    if (threadIdx.x == 32) {
        for (int i = 0; i < 4; i++) mbar_init(bars + B_GEMPTY + 8 * i, 16);
        for (int i = 0; i < 6; i++) { mbar_init(bars + B_AFULL + 8 * i, 1); mbar_init(bars + B_AEMPTY + 8 * i, i < 2 ? 8 : 16); }
        for (int i = 0; i < 4; i++) { mbar_init(bars + B_SFULL + 8 * i, 4); mbar_init(bars + B_SEMPTY + 8 * i, 1); }
        for (int i = 0; i < QDEPTH; i++) { mbar_init(bars + B_IFULL + 8 * i, 1); mbar_init(bars + B_IEMPTY + 8 * i, 23); }
        mbar_init(bars + B_WANT, 2); mbar_init(bars + B_MEET, 1); mbar_init(bars + B_XFREE, 1);
        for (int i = 0; i < 4; i++) mbar_init(bars + B_HALF + 8 * i, 1);
        mbar_init(bars + B_ALT, 4); mbar_init(bars + B_ALT + 8, 4); mbar_init(bars + B_QFREE, 2);
        asm volatile("st.shared.u64 [%0], 0;" :: "r"(bars + SM_ORDY) : "memory");
        asm volatile("fence.mbarrier_init.release.cluster;\nfence.acq_rel.cta;" ::: "memory");
    }
    __syncwarp();
    if (warp != 0) asm volatile("barrier.cluster.arrive.relaxed.aligned;" ::: "memory");
    asm volatile("barrier.cluster.wait.acquire.aligned;" ::: "memory");

    uint32_t qn = 0;
    auto next_item = [&](bool releaser, bool bounded = true) -> int {
        const uint32_t slot = qn % QDEPTH;
        if (bounded) mbar_wait(bars + B_IFULL + 8 * slot, (qn / QDEPTH) & 1);
        else mbar_spin(bars + B_IFULL + 8 * slot, (qn / QDEPTH) & 1);
        uint32_t it;
        asm volatile("ld.shared.u32 %0, [%1];" : "=r"(it) : "r"(bars + SM_QUEUE + 4 * slot) : "memory");
        mbar_arrive_cluster_if(releaser, bars0 + B_IEMPTY + 8 * slot);
        qn++;
        return it;
    };

    if (warp < 4) {
        reg_dec<40>();
        if (warp == 0) {
            {
                uint32_t gph = 1;
                const uint32_t prank = __shfl_sync(0xffffffffu, rank, 0);
                auto request = [&]() { mbar_arrive_cluster_if(lane == 0, bars0 + B_WANT); };
                auto take_item = [&]() -> int { return __shfl_sync(0xffffffffu, next_item(lane == 0), 0); };
                auto inputs_seen = [&](uint32_t word, unsigned& n) -> uint32_t {
                    uint32_t v;
                    spin_guard(n);
                    asm volatile("ld.acquire.cta.shared.u32 %0, [%1];" : "=r"(v) : "r"(bars + SM_ORDY + 4 * word) : "memory");
                    return __shfl_sync(0xffffffffu, v, 0);
                };
                uint32_t oneed = 0;
                auto wait_inputs = [&](int it) {
                    if (it & ITEM_READY) return;
                    oneed += 256;
                    for (unsigned n = 0; inputs_seen(1, n) < oneed;) {}
                };
                int nxt = first_item(), ring = -1, rot = 0;
                for (int k0 = 2; item_type(nxt) <= T_LOCAL; k0 = 0) {
                    const int type = item_type(nxt), m = item_row(nxt), c = item_col(nxt);
                    if (type == T_LOCAL) {
                        wait_inputs(nxt);
                        request();
#pragma unroll 1
                        for (uint32_t st = 0; st < 4; st++) {
                            mbar_wait(bars + B_GEMPTY + 8 * st, gph);
                            const uint32_t dst = sb + st * GST_BYTES, fb = bars + B_GFULL + 8 * st;
                            warp_expect_tx(fb, st == 0 ? 32768 + 512 : st == 3 ? 0 : 4 * LOC_PLANE);
                            if (st == 3) break;
                            if (st == 0) warp_bulk_load(dst + 4 * LOC_PLANE, &g_gate[m * 128], 512, fb);
#pragma unroll 1
                            for (int i = 0; i < 4; i++)
                                warp_tma_load(dst + i * LOC_PLANE, &prm.m[st ? M_SCR_LOC : M_SCR_LOQ], fb, i * 64, m * 64 - (st ? 8 : 0), G_B + 8 * st + c, true);
                        }
                        gph ^= 1;
                        ring = -1;
                    } else {
                        const int nk = type == T_K || type == T_V ? 8 : 16, kept = ring == m + 16 * nk ? 4 : 0;
                        ring = m + 16 * nk;
                        rot = kept ? rot - 4 : 0;
                        const CUtensorMap* ma = &prm.m[nk == 8 ? M_C : M_X];
                        const CUtensorMap* mb = &prm.m[M_WQ + type];
#pragma unroll 1
                        for (int k = k0; k < nk; k++) {
                            if (k == nk - 3) request();
                            const uint32_t st = k & 3, dst = sb + st * GST_BYTES, fb = bars + B_GFULL + 8 * st;
                            const int kc = ((k + rot) & (nk - 1)) * 64;
                            mbar_wait(bars + B_GEMPTY + 8 * st, gph);
                            warp_expect_tx(fb, k < kept ? 32768 : GST_BYTES);
                            if (k >= kept) warp_tma_load(dst, ma, fb, kc, m * 128, 0, c == 15 && type != T_K);
                            warp_tma_load_pair(dst + 16384 + prank * 16384, mb, fb, 0, kc, c * 4 + 2 * prank, true);
                            if (st == 3) gph ^= 1;
                        }
                    }
                    nxt = take_item();
                }
                uint32_t kv = 0, kvph = 1;
                uint32_t qc = 0;
                auto a_parity = [&](uint32_t b) { return b < 2 ? (((qc + 1 - b) >> 1) & 1) ^ 1 : kvph ^ (b - 2 < kv); };
                const CUtensorMap* tile_map = &prm.m[M_SCR_LD];
                asm volatile("" : "+l"(tile_map));
                {
                    bool need_g = true, more = true;
                    int pv_grp = -1, pv_row = 0;
                    int pv_shared = 0;
                    bool peer_longer = false;
                    int m = 0, c = 0, asc = 0, nu = 0, uend = 0, ureq = -1, ufetch = 0;
#pragma unroll 1
                    for (int u = 0;; u++) {
                        if (u == ufetch) {
                            if (qc) nxt = take_item();
                            if (item_type(nxt) == T_ATTN) {
                                wait_inputs(nxt);
                                const uint32_t b = qc & 1, dst = sb + b * 32768, fb = bars + B_AFULL + 8 * b, row = item_row(nxt) * 128;
                                mbar_wait(bars + (qc == 0 ? B_GEMPTY : qc == 1 ? B_QFREE : B_AEMPTY + 8 * b), qc == 0 ? gph : qc == 1 ? 0 : a_parity(b));
                                warp_expect_tx(fb, 32768 + 512);
                                warp_tma_load(dst, tile_map, fb, 0, row, G_Q + item_col(nxt), false);
                                warp_tma_load(dst + 16384, tile_map, fb, 64, row, G_Q + item_col(nxt), false);
                                warp_bulk_load(bars + SM_GATE + b * 512, &g_gate[row], 512, fb);
                                qc++;
                            }
                        }
                        if (u == uend) {
                            if (!more) break;
                            more = item_type(nxt) == T_ATTN;
                            m = item_row(nxt); c = item_col(nxt); asc = item_asc(nxt);
                            nu = more ? 2 * m + 2 : 0;
                            uend = nu + ((more ? m < 2 : pv_grp >= 0) ? 3 : 0);
                            ureq = 2 * max(m - 2 - (asc & m), 0);
                            ufetch = !more ? -1 : m ? 2 * m : uend;
                            u = -1;
                            continue;
                        }
                        int grp = pv_grp, row = pv_row;
                        int shared = pv_shared;
                        if (u >= nu) {
                            if (u == nu + 1) pv_grp = -1;
                            else if (peer_longer) { grp = -1; shared = 0; }
                            else continue;
                        } else {
                            const int j = asc ? u >> 1 : m - (u >> 1);
                            if (u & 1) {
                                pv_grp = G_V + c; pv_row = j * 128; pv_shared = (m | 1) - j;
                                peer_longer = asc & ~m & 1;
                                if (u == nu - 1 && (m & 1) && item_type(nxt) == T_END) mbar_arrive_cluster_n_if(lane == 0, bars0 + B_WANT, 2);
                                if (grp < 0) continue;
                            } else {
                                if (u == ureq) request();
                                grp = G_K + c; row = j * 128; shared = (m | 1) - j;
                            }
                        }
                        uint32_t fb = bars + B_AFULL + 16 + 8 * kv, mine = sb + SM_KV + kv * 32768 + prank * 16384;
                        int c_mine = prank * 64;
                        asm volatile("" : "+r"(mine), "+r"(fb), "+r"(row), "+r"(grp), "+r"(c_mine));
                        mbar_wait(need_g ? bars + B_GEMPTY + 8 + 8 * kv : fb + B_AEMPTY - B_AFULL, need_g ? gph : kvph);
                        warp_expect_tx(fb, grp < 0 ? 0 : 32768);
                        if (shared) {
                            warp_tma_load_pair(mine, tile_map, fb, c_mine, row, grp, shared == 1);
                        } else if (grp >= 0) {
                            warp_tma_load(mine, tile_map, fb, c_mine, row, grp, true);
                            warp_tma_load(mine + 16384 - prank * 32768, tile_map, fb, 64 - c_mine, row, grp, true);
                        } else {
                            mbar_arrive_cluster_n_if(lane < 2, map_cta(fb, lane & 1) + B_AEMPTY - B_AFULL, 8);
                        }
                        if (kv == 2) need_g = false;
                        if (++kv == 4) { kv = 0; kvph ^= 1; }
                    }
                }
                if (!qc) request();
                const int it = take_item();
                int nk = 0;
                if (item_type(it) == T_OUT) {
                    const int m = item_row(it), c = item_col(it), half = c & 1;
                    nk = 80;
                    for (unsigned n = 0; (inputs_seen(1, n) & 255) != 255;) {}
                    mbar_wait(bars + B_GEMPTY + 24, gph);
                    mbar_wait(bars + B_QFREE, 0);
                    mbar_wait(bars + B_AEMPTY + 8 * (qc & 1), a_parity(qc & 1));
#pragma unroll 1
                    for (uint32_t k = 0; k < 4; k++) {
                        const uint32_t sa = prm.ostep[half ? WIDE - 1 - k : k], dst = sb + k * GST_BYTES, fb = bars + B_GFULL + 8 * k;
                        const uint32_t b0 = k ? 1 + k : ~qc & 1, b1 = 2 + k - (k == 1);
                        mbar_wait(bars + B_AEMPTY + 8 * b0, a_parity(b0));
                        mbar_arrive_cluster_if(lane == 0 && !k, bars_peer + B_XFREE);
                        warp_expect_tx(fb, GST_BYTES);
                        warp_tma_load(dst, tile_map, fb, (sa & 1) * 64, m * 128, G_LOC - 32 + (sa >> 1), true);
                        mbar_wait(bars + (k ? B_AEMPTY + 8 * b1 : B_XFREE), k ? kvph ^ (b1 - 2 < kv) : 0);
                        warp_tma_load_pair(dst + 16384 + prank * 16384, &prm.m[M_WOB], fb, 0, (sa & 63) * 64, (c >> 1) * 4 + 2 * (half ^ prank), false);
                    }
                    gph ^= 1;
                    uint32_t seen = 0;
                    for (int k = 4; k < nk; k++) {
                        if (k == K_SPLIT) nk = 2 * TRIPLES + (take_item() & 127);
                        const int kn = k + 2 * TRIPLES - nk, first = kn >= 0 && !(kn & 1);
                        const int s = kn >= 0 ? WIDE + (3 * kn + 1) / 2 : half ? WIDE - 1 - k : k;
                        const uint32_t sa = prm.ostep[s], sa2 = prm.ostep[s + first], sw = prm.ostep[s - (kn >= 0 && !first ? prank : 0)];
                        const uint32_t need = 1u << (sa >> 1 & 31) | 1u << (sa2 >> 1 & 31);
                        for (unsigned n = 0; sa < 64 && (need & ~seen);) seen = inputs_seen(0, n);
                        const uint32_t st = k & 3;
                        uint32_t dst = sb + st * GST_BYTES, fb = bars + B_GFULL + 8 * st;
                        uint32_t dstb = dst + 16384 + (first ? 0 : prank * 16384), skipb = first && (kn >> 1 & 1) != prank;
                        int a0 = (sa & 1) * 64, a1 = m * 128, a2 = (sa >> 1) + (sa < 64 ? G_CTX : G_LOC - 32);
                        int b1 = (sw & 63) * 64, b2 = (c >> 1) * 4 + 2 * (kn >= 0 ? half : half ^ prank);
                        const CUtensorMap* mb = &prm.m[sw >= 64 ? M_WOB : M_WO];
                        asm volatile("" : "+r"(dst), "+r"(fb), "+r"(dstb), "+r"(skipb), "+r"(a0), "+r"(a1), "+r"(a2), "+r"(b1), "+r"(b2), "+l"(mb));
                        mbar_wait(bars + B_GEMPTY + 8 * st, gph);
                        warp_expect_tx(fb, GST_BYTES);
                        warp_tma_load(dst, tile_map, fb, a0, a1, a2, true);
                        if (!skipb) warp_tma_load_pair(dstb, mb, fb, 0, b1, b2, false);
                        if (first) warp_tma_load(dst + 32768, tile_map, fb, (sa2 & 1) * 64, a1, G_CTX + (sa2 >> 1), true);
                        if (k < K_SPLIT && lane == 0 && !prank)
                            asm volatile("st.relaxed.gpu.global.u32 [%0], %1;" :: "l"(&g_sync.step[0][0] + m * 4 + c), "r"(k) : "memory");
                        mbar_arrive_if(k == K_MEET && lane == 0, bars + B_MEET);
                        if ((uint32_t)(k - K_FETCH) < (3 * TRIPLES + 1) / 2) {
                            const uint32_t g = prm.ostep[79 - 2 * (k - K_FETCH)] >> 1;
                            warp_prefetch((const char*)g_scr + (uint32_t)((G_CTX + g) * (SEQ * 256) + m * 32768 + c * 4096), 4096);
                            warp_prefetch(prm.wo + (uint32_t)(g * 262144 + (m * 8 + c) * 2048), 2048);
                        }
                        if (st == 3) gph ^= 1;
                    }
                    for (unsigned n = 0; ~inputs_seen(0, n);) {}
                }
#pragma unroll 1
                for (uint32_t st = 0; st < 4; st++) { mbar_wait(bars + B_GEMPTY + 8 * st, gph ^ (st < (nk & 3))); mbar_wait(bars + B_AEMPTY + 16 + 8 * st, a_parity(2 + st)); }
                unsigned left = 0;
                if (lane == 0) asm volatile("atom.relaxed.gpu.global.add.u32 %0, [%1], 1;" : "=r"(left) : "l"(&g_sync.done) : "memory");
                if (__shfl_sync(0xffffffffu, left, 0) == NCTA - 1)
#pragma unroll 1
                    for (uint32_t i = lane * 8; i < sizeof(Sync); i += 256) *(unsigned long long*)((char*)&g_sync + i) = 0;
            }
        } else if (warp <= 2) {
            if (blockIdx.x < SEQ / 16) {
                const uint32_t r0 = 16 * blockIdx.x + 8 * (warp - 1), gbuf = bars + SM_GATE + 4 * (r0 & 15);
                float z[4];
                mbar_wait(bars + B_GFULL + 24, 0);
#pragma unroll 1
                for (uint32_t i = 0; i < 8; i++) {
                    const uint32_t off = (i & 3) * 512 + lane * 16;
                    const uint4* xp = (const uint4*)((const char*)prm.x + ((r0 + (i & 4)) * 2048 + off));
                    const uint4 wv = __ldg((const uint4*)((const char*)prm.gate_w + off));
                    uint4 xv[4];
#pragma unroll
                    for (int r = 0; r < 4; r++) { xv[r] = __ldg(xp + r * 128); if (!(i & 3)) z[r] = 0.f; }
                    const uint32_t ws[4] = {wv.x, wv.y, wv.z, wv.w};
#pragma unroll
                    for (int e = 0; e < 4; e++)
#pragma unroll
                        for (int r = 0; r < 4; r++) {
                            const uint32_t xs = e == 0 ? xv[r].x : e == 1 ? xv[r].y : e == 2 ? xv[r].z : xv[r].w;
                            z[r] = fmaf(__uint_as_float(xs << 16), __uint_as_float(ws[e] << 16), z[r]);
                            z[r] = fmaf(__uint_as_float(xs & 0xffff0000u), __uint_as_float(ws[e] & 0xffff0000u), z[r]);
                        }
                    if ((i & 3) == 3) {
#pragma unroll
                        for (int o = 16; o > 0; o >>= 1)
#pragma unroll
                            for (int r = 0; r < 4; r++) z[r] += __shfl_xor_sync(0xffffffffu, z[r], o);
                        const float zr = lane & 2 ? (lane & 1 ? z[3] : z[2]) : (lane & 1 ? z[1] : z[0]);
                        asm volatile("st.shared.f32 [%0], %1;" :: "r"(gbuf + 4 * ((i & 4) + (lane & 3))), "f"(1.f / (1.f + __expf(-zr))) : "memory");
                    }
                }
                fence_proxy_async_smem();
                __syncwarp();
                warp_bulk_store((char*)g_gate + 4 * r0, gbuf, 32);
                bulk_commit();
                bulk_wait<0>();
                __syncwarp();
                if (lane == 0) red_add(&g_sync.count[3], 1);
            }
            __syncwarp();
            {
                const int w = warp - 1;
                uint32_t sph = 0, nann = 0;
                int unsent = 0, nunsent = 0;
                bool urgent = false;
                auto announce = [&]() {
                    if (!urgent) return;
                    bulk_wait<0>();
                    __syncwarp();
                    const uint32_t hb = bars + B_HALF + 8 * (nann & 3);
                    if (w == 0) {
                        mbar_arrive_if(lane == 0, hb);
                    } else {
                        mbar_wait(hb, (nann >> 2) & 1);
                        const uint32_t type = item_type(unsent), m = item_row(unsent), c = item_col(unsent);
                        const uint32_t word = type < T_B ? c >> 3 : type == T_B ? 2 : offsetof(Sync, ctx) / 8 + m;
                        const uint32_t bit = type < T_B ? 8 * (c & 7) : type == T_B ? 8 * (c & 3) : type == T_LOCAL ? 32 + c : c;
                        if (lane < nunsent) red_add((unsigned long long*)((char*)&g_sync + 8 * word), 1ull << bit);
                        __syncwarp();
                    }
                    nann++;
                    nunsent = 0; urgent = false;
                };
                int held = first_item(), it;
                bool qfree = false;
                do {
                    if (!__all_sync(0xffffffffu, mbar_test(bars + B_IFULL + 8 * (qn % QDEPTH), (qn / QDEPTH) & 1))) announce();
                    it = __shfl_sync(0xffffffffu, next_item(lane == 0), 0);
                    const int itype = item_type(it);
                    const bool keep_held = itype == T_LOCAL;
                    if (itype >= T_ATTN && held < 0) {
                        urgent = nunsent;
                        mbar_arrive_if(lane == 0 && !qfree, bars + B_QFREE);
                        qfree = true;
                    }
#pragma unroll 1
                    for (int pass = held < 0 || keep_held; pass < 2; pass++) {
                        if (pass && (itype < T_OUT || itype == T_END)) break;
                        const int cur = pass ? it : held, type = item_type(cur), m = item_row(cur), c = item_col(cur);
                        const bool local = type == T_LOCAL;
                        const int grp = pass ? (local ? G_LOC : G_CTX) + c : type * 32 + 2 * c;
#pragma unroll 1
                        for (int i = 0; i < 4 - 2 * pass; i++) {
                            const int b = i & 1;
                            const bool alt = i >= 2 && itype == T_ATTN;
                            const uint32_t full = bars + (alt ? B_ALT + 8 * w : B_SFULL + 16 * w + 8 * b), par = alt ? 0 : sph;
                            if (i == 3 - 2 * pass || !__all_sync(0xffffffffu, mbar_test(full, par))) announce();
                            mbar_wait(full, par);
                            fence_proxy_async_smem();
                            warp_tma_store(&prm.m[local ? M_SCR_LOQ : M_SCR_ST], sb + (alt ? 32768 : SM_STAGING) + w * 16384 + b * 8192,
                                         local ? b * 128 + w * 64 : b * 64, local ? m * 64 : m * 128 + w * 64, grp + (i >> 1), local || (type < T_B && c < FIRST_PAIR));
                            bulk_commit();
                            if (pass > b) continue;
                            bulk_wait_read<0>();
                            __syncwarp();
                            mbar_arrive_if(lane <= pass && !alt, bars + B_SEMPTY + 16 * w + 8 * (b - lane));
                            sph ^= b & !alt;
                        }
                        mbar_arrive_if(lane == 0 && !qfree && itype >= T_ATTN, bars + B_QFREE);
                        qfree |= itype >= T_ATTN;
                        if (lane == nunsent) unsent = cur;
                        nunsent++;
                        urgent = nunsent == 32 || !local;
                    }
                    if (!keep_held) held = itype < T_OUT ? it : -1;
                } while (item_type(it) != T_END);
                announce();
                it = __shfl_sync(0xffffffffu, next_item(lane == 0), 0);
                if (item_type(it) == T_OUT) {
                    if (w) {
                        mbar_wait(bars + B_MEET, 0);
                        asm volatile("fence.proxy.async.global;\nfence.acq_rel.gpu;" ::: "memory");
                        mbar_arrive_cluster_if(lane == 0, bars0 + B_WANT);
                    }
                    next_item(lane == 0);
#pragma unroll 1
                    for (int i = 0; i < 4; i++) {
                        const int b = i & 1;
                        mbar_wait(bars + B_SFULL + 16 * w + 8 * b, sph ^ (i >> 1));
                        fence_proxy_async_smem();
                        warp_tma_add(&prm.m[M_OUT], sb + SM_STAGING + w * 16384 + b * 8192, (item_col(it) ^ (i < 2)) * 128 + b * 64, item_row(it) * 128 + w * 64, 0);
                        bulk_commit();
                        if (b) {
                            bulk_wait_read<0>();
                            __syncwarp();
                            mbar_arrive_if(lane < 2, bars + B_SEMPTY + 16 * w + 8 * lane);
                        }
                    }
                }
            }
        } else {
            if (elect_one()) {
                uint32_t ordy = 0;
                unsigned long long cnt_lo = 0, cnt_hi = 0;
                int late = 0;
                auto refresh = [&]() {
                    if (!late && cnt_lo == 0x30303030 && cnt_hi == SEQ / 8) late = 1;
                    asm volatile("ld.acquire.gpu.global.v2.u64 {%0, %1}, [%2];" : "=l"(cnt_lo), "=l"(cnt_hi) : "l"(late ? &g_sync.count[0] : &g_sync.count[2]) : "memory");
                };
                auto inputs_ready = [&](int it) -> bool {
                    const int c = item_col(it);
                    if (item_type(it) == T_ATTN) return late && ((c < 16 ? cnt_lo : cnt_hi) >> (4 * (c & 14)) & 255) == 48;
                    return late || (cnt_hi == SEQ / 8 && (cnt_lo >> (4 * (c & 6)) & 255) == 48);
                };
                auto publish = [&](int it, int step) {
                    const uint32_t slot = qn % QDEPTH;
                    mbar_wait(bars + B_IEMPTY + 8 * slot, ((qn / QDEPTH) & 1) ^ 1);
                    for (uint32_t r = 0; r < 2; r++) {
                        const uint32_t rb = map_cta(bars, r);
                        asm volatile("mbarrier.arrive.expect_tx.shared::cluster.b64 _, [%0], 4;" :: "r"(rb + B_IFULL + 8 * slot) : "memory");
                        asm volatile("st.async.shared::cluster.mbarrier::complete_tx::bytes.u32 [%0], %1, [%2];"
                                     :: "r"(rb + SM_QUEUE + 4 * slot), "r"(it + r * step), "r"(rb + B_IFULL + 8 * slot) : "memory");
                    }
                    qn++;
                };
                int asc = 1;
                int it;
                do {
                    if (rank == 0) {
                        mbar_wait(bars + B_WANT, qn & 1);
                        const uint32_t pair = plan_index();
                        int pit = prm.plan[pair < 64 ? pair & 7 : pair - 56][min(qn + 1, 15u)];
                        unsigned i;
                        const bool planned = item_type(pit) != T_END;
                        if (!planned) asm volatile("atom.relaxed.gpu.global.add.u32 %0, [%1], 1;" : "=r"(i) : "l"(&g_sync.next) : "memory");
                        if (cnt_lo != 0x3030303030303030ull || cnt_hi != cnt_lo) refresh();
                        if (planned) pit += (pair >> 3 & 7) << (item_type(pit) == T_LOCAL);
                        else if (i < NITEMS) pit = prm.items[i];
                        const int type = item_type(pit);
                        int step = type == T_LOCAL ? 16 : 1;
                        it = pit + (pit & (step == 1 ? 15 : 0x1f0));
                        if (type == T_ATTN) {
                            if (!asc) { it += 1; step = -1; }
                            it |= asc << 9;
                        }
                        asc = type != T_ATTN || item_row(pit) == 0 || !asc;
                        if (inputs_ready(it)) it |= ITEM_READY;
                        publish(it, step);
                    } else {
                        it = next_item(true);
                    }
                    if ((item_type(it) == T_ATTN || item_type(it) == T_LOCAL) && !(it & ITEM_READY)) {
                        unsigned n = 0;
                        while (!inputs_ready(it)) { refresh(); spin_guard(n); }
                        asm volatile("st.release.cta.shared.u32 [%0], %1;" :: "r"(bars + SM_ORDY + 4), "r"(ordy += 256) : "memory");
                    }
                } while (item_type(it) != T_END);
                if (rank == 0) {
                    mbar_wait(bars + B_WANT, qn & 1);
                    const unsigned i = atomicAdd(&g_sync.next_out, 1u), t = i < 32 ? 31 - i : i - 32;
                    it = i < 64 ? T_OUT << 13 | ((t & 3) * 2 + (i >> 5)) << 4 | (t >> 2) * 2 : T_END << 13;
                    publish(it, 1);
                } else {
                    it = next_item(true);
                }
                if (item_type(it) == T_OUT) {
                    const uint32_t m = item_row(it), half = item_col(it) & 1, tile = m * 2 + (item_col(it) >> 1);
                    unsigned* split = (unsigned*)((char*)g_sync.split + 4 * tile);
                    unsigned long long rdy = 0;
                    int state = rank ? 2 : 0;
                    for (unsigned n = 0; rdy != 0xffffffffffull || state < 2; spin_guard(n)) {
                        if (rdy != 0xffffffffffull) {
                            rdy = ld_acquire((const unsigned long long*)((char*)g_sync.ctx + 8 * m));
                            asm volatile("st.release.cta.shared.u64 [%0], %1;" :: "r"(bars + SM_ORDY), "l"(rdy) : "memory");
                        }
                        unsigned steps = 0;
                        if (state == 1) {
                            steps = ld_acquire(split);
                        } else if (state == 0 && mbar_test(bars + B_WANT, qn & 1)) {
                            state = 1;
                            unsigned seen;
                            asm volatile("atom.acq_rel.gpu.global.exch.b32 %0, [%1], 1;" : "=r"(seen) : "l"(split) : "memory");
                            if (seen) {
                                const unsigned long long v = ld_acquire((const unsigned long long*)((char*)g_sync.step + 8 * tile));
                                const int d = (int)(v >> 32) - (int)v;
                                steps = (WIDE + min(max(half ? d : -d, -12), 12)) >> 1;
                                atomicExch(split, WIDE - steps);
                            }
                        }
                        if (steps > 1) { publish(T_END << 13 | steps, 0); state = 2; }
                    }
                    if (rank) next_item(true);
                }
                #pragma unroll 1
                for (uint32_t n = qn; n < qn + QDEPTH && rank == 0; n++) mbar_wait(bars + B_IEMPTY + 8 * (n % QDEPTH), ((n / QDEPTH) & 1) ^ 1);
            }
        }
    } else {
        reg_inc<232>();
        const int wg = (warp >> 2) - 1, wq = warp & 3;
        uint32_t gph = 0;
        uint32_t kvn = 0;
        const uint32_t dA = make_desc(sb + wg * 8192, 16);
        uint32_t ti = 0;
        uint32_t sph = 1;
        const uint32_t stg = sb + SM_STAGING + wg * 16384;
        const uint32_t stg_lane = stg + (wq * 16 + (lane & 15)) * 128 + (((lane >> 4) ^ (lane & 7)) << 4);
        auto write_blocks = [&](auto n, uint32_t off, const uint32_t* v) {
            uint32_t a = stg_lane;
            asm volatile("" : "+r"(a));
            a += off;
#pragma unroll
            for (int j = 0; j < decltype(n)::value; j++)
                stmatrix_x4((a ^ (32 * (j & 3))) + (j >> 2) * 8192, v[4 * j], v[4 * j + 1], v[4 * j + 2], v[4 * j + 3]);
        };
        auto release = [&](uint32_t bar) { mbar_arrive_if(lane == 0, bars + bar); };
        const uint32_t bars_lane = map_cta(bars, lane & 1);
        auto release_stage = [&](uint32_t st) { mbar_arrive_cluster_if(lane < 2, bars_lane + B_GEMPTY + 8 * st); };
        auto take_item = [&]() -> int {
            return __shfl_sync(0xffffffffu, next_item(lane == 0, false), 0);
        };
        auto stage_acquire = [&](int b) { mbar_spin(bars + B_SEMPTY + 16 * wg + 8 * b, sph); };
        auto stage_publish = [&](int b) {
            __syncwarp();
            release(B_SFULL + 16 * wg + 8 * b);
        };
        auto stage_chunk = [&](int b, const uint32_t* v) {
            stage_acquire(b);
            write_blocks(std::integral_constant<int, 4>(), b * 8192, v);
            stage_publish(b);
            if (b) sph ^= 1;
        };
        auto publish_pair = [&]() {
            __syncwarp();
            mbar_arrive_if(lane < 2, bars + B_SFULL + 16 * wg + 8 * lane);
            sph ^= 1;
        };
        auto gemm_step = [&](float (&acc)[128], uint32_t dB, int& k) {
            const uint32_t st = k & 3;
            wgmma_wait<0>();
            release_stage((k - 1) & 3);
            mbar_spin(bars + B_GFULL + 8 * st, gph);
            const uint64_t da = full_desc(dA + st * (GST_BYTES >> 4)), db = full_desc(dB + st * (GST_BYTES >> 4));
            wgmma_fence();
#pragma unroll
            for (int kk = 0; kk < 4; kk++) wgmma_ss_n256_tb(acc, da + 2 * kk, db + 128 * kk, 1);
            wgmma_commit();
            gph ^= st == 3;
            k++;
        };
        if (wg == 1) bar_arrive(1, 256);
        int it = first_item();
        while (true) {
            if (item_type(it) <= T_LOCAL) {
                float acc[128];
                uint32_t pk[64];
                bool pending = false;
                int held = T_END;
                auto scale_q = [&](int j0, int n) {
                    if (held != T_Q) return;
#pragma unroll
                    for (int j = j0; j < j0 + n; j++)
                        asm("{\n.reg .b32 t;\nmul.rn.bf16x2 t, %0, %2;\nfma.rn.bf16x2 %0, %0, %1, t;\n}\n" : "+r"(pk[j]) : "r"(0x3e033e03u), "r"(0xb9d8b9d8u));
                };
                zero_regs(pk);
                const uint32_t dB = make_desc(sb + 16384, 8192);
                do {
                    const int type = item_type(it);
                    if (type == T_LOCAL) {
                        int ln = lane;
                        asm volatile("" : "+r"(ln));
                        const int g = ln >> 2, t = ln & 3, par = wq & 1;
                        const uint32_t hc = (wq >> 1) * 4, pl = sb + (par * 2 + wg) * LOC_PLANE;
                        const uint32_t a16 = (ln & 15) * 128 + (((hc + (ln >> 4)) ^ (ln & 7)) << 4), a8 = (ln & 7) * 128 + (((hc + (ln >> 3)) ^ (ln & 7)) << 4);
                        const bool first0 = 2 * t > g, first1 = 2 * t + 1 > g;
                        const uint32_t fmask = (first0 ? 0xffffu : 0u) | (first1 ? 0xffff0000u : 0u);
                        const bool edge = item_row(it) == 0;
                        uint32_t q[4][2][4], kf[9][4], vf[9][4];
                        float w[8];
                        mbar_spin(bars + B_GFULL, gph);
#pragma unroll
                        for (int u = 0; u < 4; u++) { ldsm_x4(q[u][0], pl + u * 2048 + a16); ldsm_x4(q[u][1], pl + u * 2048 + (a16 ^ 32)); }
#pragma unroll
                        for (int j = 0; j < 8; j++) w[j] = lds_f32(sb + 4 * LOC_PLANE + 4 * (2 * g + par) + 64 * j);
                        __syncwarp();
                        release_stage(0);
                        mbar_spin(bars + B_GFULL + 8, gph);
#pragma unroll
                        for (int n = 0; n < 9; n++) ldsm_x4(kf[n], pl + GST_BYTES + n * 1024 + a8);
                        __syncwarp();
                        release_stage(1);
                        float s[8][2];
#pragma unroll
                        for (int u = 0; u < 4; u++) {
                            float d[3][4];
#pragma unroll
                            for (int nt = 0; nt < 3; nt++) {
                                mma_k16_init(d[nt], q[u][0], kf[2 * u + nt][0], kf[2 * u + nt][1]);
                                mma_k16(d[nt], q[u][1], kf[2 * u + nt][2], kf[2 * u + nt][3]);
                            }
                            if (u == 0 && edge) { d[0][0] = -INFINITY; d[0][1] = -INFINITY; }
                            s[2 * u][0] = first0 ? d[0][0] : d[1][0]; s[2 * u][1] = first1 ? d[0][1] : d[1][1];
                            s[2 * u + 1][0] = first0 ? d[1][2] : d[2][2]; s[2 * u + 1][1] = first1 ? d[1][3] : d[2][3];
                        }
                        mbar_spin(bars + B_GFULL + 16, gph);
#pragma unroll
                        for (int u = 0; u < 4; u++) { ldsm_x4_t(vf[2 * u], pl + 2 * GST_BYTES + u * 2048 + a16); ldsm_x4_t(vf[2 * u + 1], pl + 2 * GST_BYTES + u * 2048 + (a16 ^ 32)); }
                        ldsm_x4_t(vf[8], pl + 2 * GST_BYTES + 8192 + a8);
                        __syncwarp();
                        release_stage(2);
                        float x[8];
#pragma unroll
                        for (int j = 0; j < 8; j++) x[j] = fmaxf(s[j][0], s[j][1]);
#pragma unroll
                        for (int o = 1; o < 4; o *= 2)
#pragma unroll
                            for (int j = 0; j < 8; j++) x[j] = fmaxf(x[j], __shfl_xor_sync(0xffffffffu, x[j], o));
#pragma unroll
                        for (int j = 0; j < 8; j++) {
                            const float n = x[j] * -LOC_SCALE;
                            s[j][0] = ex2(fmaf(s[j][0], LOC_SCALE, n)); s[j][1] = ex2(fmaf(s[j][1], LOC_SCALE, n));
                            x[j] = s[j][0] + s[j][1];
                        }
#pragma unroll
                        for (int o = 1; o < 4; o *= 2)
#pragma unroll
                            for (int j = 0; j < 8; j++) x[j] += __shfl_xor_sync(0xffffffffu, x[j], o);
                        mbar_spin(bars + B_GFULL + 24, gph);
                        release_stage(3);
                        it = take_item();
                        uint32_t ob[4][8];
#pragma unroll
                        for (int u = 0; u < 4; u++) {
                            const float r0 = rcp(x[2 * u]), r1 = rcp(x[2 * u + 1]), f0 = fmaf(-w[2 * u], r0, r0), f1 = fmaf(-w[2 * u + 1], r1, r1);
                            const uint32_t p0 = pack_bf16(s[2 * u][0] * f0, s[2 * u][1] * f0), p1 = pack_bf16(s[2 * u + 1][0] * f1, s[2 * u + 1][1] * f1);
                            const uint32_t pa[4] = {p0 & fmask, 0, p0 & ~fmask, p1 & fmask};
#pragma unroll
                            for (int c = 0; c < 4; c++) {
                                float ol[4];
                                mma_k16_init(ol, pa, vf[2 * u + (c >> 1)][2 * (c & 1)], vf[2 * u + (c >> 1)][2 * (c & 1) + 1]);
                                mma_k8(ol, 0, p1 & ~fmask, u < 3 ? vf[2 * u + 2 + (c >> 1)][2 * (c & 1)] : vf[8][c]);
                                ob[u][2 * c] = pack_bf16(ol[0], ol[1]);
                                ob[u][2 * c + 1] = pack_bf16(ol[2], ol[3]);
                            }
                        }
                        stage_acquire(0); stage_acquire(1);
#pragma unroll
                        for (int u = 0; u < 4; u++) {
                            stmatrix_x4(stg + par * 8192 + u * 2048 + a16, ob[u][0], ob[u][1], ob[u][2], ob[u][3]);
                            stmatrix_x4(stg + par * 8192 + u * 2048 + (a16 ^ 32), ob[u][4], ob[u][5], ob[u][6], ob[u][7]);
                        }
                        publish_pair();
                        bar_sync(4, 256);
                        gph ^= 1;
                        continue;
                    }
                    mbar_spin(bars + B_GFULL, gph);
                    bool more;
                    do {
                        wgmma_fence();
                        wgmma_ss_n256_tb_init(acc, full_desc(dA), full_desc(dB));
#pragma unroll
                        for (int kk = 1; kk < 4; kk++) wgmma_ss_n256_tb(acc, full_desc(dA) + 2 * kk, full_desc(dB) + 128 * kk, 1);
                        wgmma_commit();
                        const int nk = item_type(it) == T_K || item_type(it) == T_V ? 8 : 16;
                        int k = 1;
                        do {
                            if (pending) {
                                const int kf = k - 1 - wg;
                                if (kf == 0) { scale_q(0, 16); stage_chunk(0, pk); }
                                else if (kf == 1) { scale_q(16, 16); stage_chunk(1, pk + 16); }
                                else if (kf == 3) { scale_q(32, 16); stage_chunk(0, pk + 32); }
                                else if (kf == 4) { scale_q(48, 16); stage_chunk(1, pk + 48); }
                            }
                            gemm_step(acc, dB, k);
                        } while (k < nk);
                        held = item_type(it);
                        it = take_item();
                        more = item_type(it) < T_LOCAL;
                        if (more) mbar_spin(bars + B_GFULL, gph);
                        wgmma_wait<0>();
                        fence_regs(acc);
                        release_stage(3);
#pragma unroll
                        for (int j = 0; j < 64; j++) pk[j] = pack_bf16(acc[2 * j], acc[2 * j + 1]);
                        pending = true;
                    } while (more);
                } while (item_type(it) <= T_LOCAL);
                if (pending) {
                    scale_q(0, 64);
                    stage_acquire(0); stage_acquire(1);
                    write_blocks(std::integral_constant<int, 8>(), 0, pk);
                    const bool borrow = item_type(it) == T_ATTN;
                    if (borrow) {
                        mbar_spin(bars + B_GEMPTY, gph ^ 1); mbar_spin(bars + B_GEMPTY + 8, gph ^ 1);
                    } else {
                        publish_pair();
                        stage_acquire(0); stage_acquire(1);
                    }
                    write_blocks(std::integral_constant<int, 8>(), borrow ? 32768 - SM_STAGING : 0, pk + 32);
                    publish_pair();
                    mbar_arrive_if(lane == 0 && borrow, bars + B_ALT + 8 * wg);
                }
                if (item_type(it) == T_END) { it = take_item(); break; }
            } else {
                float o[64], s[64];
                uint32_t pa[32], pb[32];
                zero_regs(o); zero_regs(s); zero_regs(pa);
                float n0 = 0.f, n1 = 0.f;
                int shifted = 0;
                float l0 = 1.f, l1 = 1.f, f0 = 0.f, f1 = 0.f, g0 = 0.f, g1 = 0.f;
                uint32_t has_pv = 0;
                int first = 0;
                int pending = 0;
                const uint32_t dK = make_desc(sb + SM_KV, 16), dV = make_desc(sb + SM_KV, 16384);
                const uint32_t lane_off = bars_lane - bars + B_AEMPTY - B_AFULL;
                int cur = 0;
                uint32_t qoff = 0;
                const int row = wg * 64 + wq * 16 + (lane >> 2);
                const float thr = (row & 63) - (lane & 3) * 2;
                int peek = 0;
                auto kv_wait = [&](uint32_t n) { mbar_spin(bars + B_AFULL + 16 + 8 * (n & 3), (n >> 2) & 1); };
                auto kv_release = [&](uint32_t n) { mbar_arrive_cluster_if(lane < 2, bars_lane + B_AEMPTY + 16 + 8 * (n & 3)); };
                struct Slot { uint32_t bar, par, off; } slot[4];
                auto align = [&]() {
#pragma unroll
                    for (uint32_t i = 0; i < 4; i++) {
                        const uint32_t n = kvn + (i == 1 ? has_pv : i);
                        slot[i].bar = bars + B_AFULL + 16 + 8 * (n & 3); slot[i].par = (n >> 2) & 1; slot[i].off = (n & 3) * 2048;
                    }
                };
                align();
                auto scale_o = [&]() {
#pragma unroll
                    for (int j = 0; j < 16; j++) { o[4 * j] *= f0; o[4 * j + 1] *= f0; o[4 * j + 2] *= f1; o[4 * j + 3] *= f1; }
                };
                auto pack_o = [&](uint32_t (&v)[32]) {
#pragma unroll
                    for (int j = 0; j < 32; j++) v[j] = pack_bf16(o[2 * j], o[2 * j + 1]);
                };
                auto scales = [&]() { f0 = g0 * rcp(quad_sum(l0)); f1 = g1 * rcp(quad_sum(l1)); };
                auto step = [&](auto even, uint32_t (&pin)[32], uint32_t (&pout)[32], bool fresh, bool diag, bool last) {
                    constexpr bool EVEN = decltype(even)::value;
                    Slot& sk = slot[EVEN ? 0 : 2];
                    Slot& sv = slot[EVEN ? 1 : 3];
                    kvn += EVEN ? 1 + has_pv : 2;
                    mbar_spin(sk.bar, sk.par);
                    bar_sync(1 + wg, 256);
                    qk_gemm(s, dA + qoff, dK + sk.off);
                    if (EVEN && fresh) {
                        scales();
                        g0 = lds_f32(bars + SM_GATE + (ti & 1) * 512 + 4 * row); g1 = lds_f32(bars + SM_GATE + (ti & 1) * 512 + 4 * row + 32);
                        ti++;
                        n0 = 0.f; n1 = 0.f; l0 = 0.f; l1 = 0.f;
                        shifted = 0;
                        if (has_pv) { stage_acquire(0); stage_acquire(1); }
                    }
                    if (!EVEN && pending) {
                        pack_o(pout);
                        write_blocks(std::integral_constant<int, 8>(), 0, pout);
                        publish_pair();
                    }
                    if (last)
                        asm volatile("{\n.reg .pred P, Q;\n"
                                     "mbarrier.test_wait.parity.shared::cta.b64 Q, [%1], %2;\n"
                                     "mbarrier.test_wait.parity.shared::cta.b64 P, [%3], %4;\n"
                                     "ld.shared.u32 %0, [%5];\n"
                                     "@!Q or.b32 %0, %0, 0x10000;\n"
                                     "@!P mov.u32 %0, -1;\n}\n"
                                     : "=r"(peek) : "r"(bars + B_AFULL + 8 * (ti & 1)), "r"((ti >> 1) & 1), "r"(bars + B_IFULL + 8 * (qn % QDEPTH)),
                                       "r"((qn / QDEPTH) & 1), "r"(bars + SM_QUEUE + 4 * (qn % QDEPTH)) : "memory");
                    mbar_spin(sv.bar, sv.par);
                    pv_gemm(o, pin, dV + sv.off, EVEN || !first);
                    bar_arrive(2 - wg, 256);
                    sk.par ^= 1; sv.par ^= 1;
                    wgmma_wait<1>();
                    fence_regs(s);
                    mbar_arrive_cluster_if(lane < 2 && (!EVEN || has_pv), sk.bar + lane_off);
                    mbar_arrive_if(lane == 0 && last, bars + B_AEMPTY + 8 * ((ti - 1) & 1));
                    float r0, r1, x0 = n0, x1 = n1;
#pragma unroll 1
                    for (int mask = diag, redone = 0;; mask = 0, redone = 1) {
                        if (mask | shifted) {
                            if (mask) causal_mask(s, thr, wg);
                            if (shifted) shift_rows(s, x0, x1);
                        }
                        exp_pack(pout, s, r0, r1);
                        if (!__any_sync(0xffffffffu, fmaxf(r0, r1) >= SUM_LIMIT || (EVEN && fresh && !(lane & 3) && !(fminf(s[0], s[2]) >= -REF_RANGE))) || redone) break;
                        row_max(s, x0, x1);
                        if (!(EVEN && fresh)) { x0 = fmaxf(x0, 0.f); x1 = fmaxf(x1, 0.f); }
                        float a0 = ex2(-x0), a1 = ex2(-x1);
                        n0 += x0; n1 += x1;
                        shifted = 1;
                        if (EVEN && fresh) { a0 = 1.f; a1 = 1.f; }
                        l0 *= a0; l1 *= a1;
                        wgmma_wait<0>();
                        fence_regs(o);
#pragma unroll
                        for (int q = 0; q < 16; q++) { o[4 * q] *= a0; o[4 * q + 1] *= a0; o[4 * q + 2] *= a1; o[4 * q + 3] *= a1; }
                    }
                    l0 += r0; l1 += r1;
                    wgmma_wait<0>();
                    fence_regs(o);
                    fence_regs(pin);
                    mbar_arrive_cluster_if(lane < 2, sv.bar + lane_off);
                };
                auto copy_p = [&]() {
#pragma unroll
                    for (int j = 0; j < 32; j++) pa[j] = __float_as_uint(__uint_as_float(pb[j]) + __uint_as_float(prm.zero));
                };
                int rem = 0;
                mbar_spin(bars + B_AFULL + 8 * (ti & 1), (ti >> 1) & 1);
                while (true) {
                    const bool fresh = rem == 0;
                    if (fresh) {
                        if (has_pv) {
                            const int seen = __shfl_sync(0xffffffffu, peek, 0);
                            if (seen >= 0) {
                                mbar_arrive_cluster_if(lane == 0, bars0 + B_IEMPTY + 8 * (qn % QDEPTH));
                                qn++;
                                it = seen & 0xffff;
                            } else {
                                it = take_item();
                            }
                            if (item_row(cur) < 2 || item_type(it) != T_ATTN) break;
                            if (seen & 0x10000) mbar_spin(bars + B_AFULL + 8 * (ti & 1), (ti >> 1) & 1);
                        }
                        cur = it;
                        qoff = (ti & 1) * 2048;
                    }
                    const bool last = fresh ? item_row(cur) == 0 : rem == 1;
                    step(std::true_type(), pa, pb, fresh, item_asc(cur) ? last : fresh, last);
                    first = fresh;
                    if (fresh) {
                        pending = has_pv; has_pv = 1;
                        if (!pending) { kvn -= 2; align(); kvn += 2; slot[0].par ^= 1; slot[1].par ^= 1; }
                        else scale_o();
                        rem = item_row(cur);
                        if (rem == 0) {
                            copy_p();
                            continue;
                        }
                    } else if (--rem == 0) {
                        copy_p();
                        const Slot t0 = slot[0], t1 = slot[1];
                        slot[0] = slot[2]; slot[1] = slot[3]; slot[2] = t0; slot[3] = t1;
                        continue;
                    }
                    step(std::false_type(), pb, pa, false, item_asc(cur) && rem == 1, rem == 1);
                    pending = 0; first = 0;
                    rem--;
                }
                const uint32_t skip = item_asc(cur) & ~item_row(cur) & 1;
                kvn += skip;
                const bool end = item_type(it) == T_END;
#pragma unroll 1
                for (int pass = pending ? 0 : 1; pass < 2; pass++) {
                    if (pass) {
                        kv_wait(kvn);
                        pv_gemm(o, pa, dV + (kvn & 3) * 2048, !first);
                        scales();
                        stage_acquire(0); stage_acquire(1);
                        if (end) it = take_item();
                        wgmma_wait<0>();
                        fence_regs(o);
                        kv_release(kvn);
                        kvn += 1 + skip;
                        scale_o();
                    }
                    pack_o(pb);
                    write_blocks(std::integral_constant<int, 8>(), 0, pb);
                    publish_pair();
                }
                if (end) break;
            }
        }
        if (item_type(it) == T_OUT) {
            float acc[128];
            const uint32_t dB = make_desc(sb + 16384, 8192);
            mbar_spin(bars + B_GFULL, gph);
            wgmma_fence();
            wgmma_ss_n256_tb_init(acc, full_desc(dA), full_desc(dB));
#pragma unroll
            for (int kk = 1; kk < 4; kk++) wgmma_ss_n256_tb(acc, full_desc(dA) + 2 * kk, full_desc(dB) + 128 * kk, 1);
            wgmma_commit();
            uint32_t ln;
            asm volatile("mov.u32 %0, %%laneid;" : "=r"(ln));
            char* const mine = (char*)prm.out + (uint32_t)((item_row(it) * 128 + wg * 64 + wq * 16 + (ln >> 4)) * 2048 + item_col(it) * 256 + (ln & 15) * 16);
            int k = 1, nk = 80;
            do {
                if ((uint32_t)(k - (K_MEET - 12)) < 8) *(uint4*)(mine + (uint32_t)(k - (K_MEET - 12)) * 4096) = make_uint4(0, 0, 0, 0);
                __syncwarp();
                if (k == K_SPLIT) nk = take_item() & 127;
                gemm_step(acc, dB, k);
            } while (k < nk);
            float lo[64];
            auto triple = [&](auto first) {
                const uint32_t s0 = k & 3, s1 = (k + 1) & 3, o0 = s0 * (GST_BYTES >> 4), o1 = s1 * (GST_BYTES >> 4);
                wgmma_wait<0>();
                mbar_arrive_cluster_if(ln < (decltype(first)::value ? 2 : 4), bars_lane + B_GEMPTY + 8 * ((k - 1 - (ln >> 1)) & 3));
                mbar_spin(bars + B_GFULL + 8 * s0, gph);
                gph ^= s0 == 3;
                wgmma_fence();
#pragma unroll
                for (int kk = 0; kk < 4; kk++) {
                    if (decltype(first)::value && kk == 0) wgmma_ss_n128_tb_init(lo, full_desc(dA + o0), full_desc(dB + o0));
                    else wgmma_ss_n128_tb(lo, full_desc(dA + o0) + 2 * kk, full_desc(dB + o0) + 128 * kk, 1);
                }
                mbar_spin(bars + B_GFULL + 8 * s1, gph);
                gph ^= s1 == 3;
                wgmma_fence();
#pragma unroll
                for (int kk = 0; kk < 4; kk++) wgmma_ss_n128_tb(lo, full_desc(dA + o0 + 2048) + 2 * kk, full_desc(dB + o1 + 1024) + 128 * kk, 1);
#pragma unroll
                for (int kk = 0; kk < 4; kk++) wgmma_ss_n128_tb(lo, full_desc(dA + o1) + 2 * kk, full_desc(dB + o1) + 128 * kk, 1);
                wgmma_commit();
                k += 2;
            };
            triple(std::true_type());
            fence_regs(acc);
            uint32_t pk[32];
#pragma unroll
            for (int j = 0; j < 32; j++) pk[j] = pack_bf16(acc[64 + 2 * j], acc[65 + 2 * j]);
            stage_acquire(0); stage_acquire(1);
            write_blocks(std::integral_constant<int, 8>(), 0, pk);
            publish_pair();
            triple(std::false_type());
            stage_acquire(0); stage_acquire(1);
            wgmma_wait<0>();
            fence_regs(lo);
            mbar_arrive_cluster_if(ln < 4, bars_lane + B_GEMPTY + 8 * ((k - 1 - (ln >> 1)) & 3));
#pragma unroll
            for (int b = 0; b < 2; b++) {
#pragma unroll
                for (int j = 16 * b; j < 16 * b + 16; j++) pk[j] = pack_bf16(acc[2 * j] + lo[2 * j], acc[2 * j + 1] + lo[2 * j + 1]);
                write_blocks(std::integral_constant<int, 4>(), b * 8192, pk + 16 * b);
                stage_publish(b);
            }
        }
    }
}

typedef CUresult (*EncodeFn)(CUtensorMap*, CUtensorMapDataType, cuuint32_t, void*, const cuuint64_t*, const cuuint64_t*,
                             const cuuint32_t*, const cuuint32_t*, CUtensorMapInterleave, CUtensorMapSwizzle,
                             CUtensorMapL2promotion, CUtensorMapFloatOOBfill);

void encode3(EncodeFn fn, CUtensorMap* m, const void* ptr, uint64_t d0, uint64_t d1, uint64_t d2, uint64_t s1, uint64_t s2,
             uint32_t b0, uint32_t b1, uint32_t b2) {
    cuuint64_t dims[3] = {d0, d1, d2};
    cuuint64_t strides[2] = {s1, s2};
    cuuint32_t box[3] = {b0, b1, b2};
    cuuint32_t es[3] = {1, 1, 1};
    fn(m, CU_TENSOR_MAP_DATA_TYPE_BFLOAT16, 3, const_cast<void*>(ptr), dims, strides, box, es, CU_TENSOR_MAP_INTERLEAVE_NONE,
       CU_TENSOR_MAP_SWIZZLE_128B, CU_TENSOR_MAP_L2_PROMOTION_NONE, CU_TENSOR_MAP_FLOAT_OOB_FILL_NONE);
}
void map_act(EncodeFn fn, CUtensorMap* m, const void* p, int rows, int cols, int box_rows) {
    encode3(fn, m, p, cols, rows, 1, (uint64_t)cols * 2, (uint64_t)cols * rows * 2, 64, box_rows, 1);
}
void map_wgt(EncodeFn fn, CUtensorMap* m, const void* p, int K, int N) {
    encode3(fn, m, p, 64, K, N / 64, (uint64_t)N * 2, 128, 64, 64, 2);
}

void build_schedule(Params& p) {
    int n = 0;
    auto add = [&](int type, int col, int row) { p.items[n++] = (uint16_t)(type << 13 | col << 4 | row); };
    int beta = 26, tail = 32, late = 6, early = 4, epos = 60;
    int order[16] = {6, 7, 8, 9, 10, 11, 12, 13, 14, 15, 5, 4, 3, 2, 1, 0};
    const char* plans = "xxcccccx,xxcccccx,xxxxx,xxcxlxx,xxlcclxcc,xxlcccccc,xxlxlccccc,xxlxlxccc";
    const char* pos[8];
    int len[8] = {}, start[8] = {};
    for (int s = 0; s < 8; s++) { pos[s] = plans; while (*plans && *plans++ != ',') {} }
    for (int i = 0; i < 160; i++) p.plan[i / 16][i % 16] = T_END << 13;
    for (int nx = 0, nc = 3, nl = 0; nx + nc + nl < 28 + 32 + 8;) {
        int s = -1;
        for (int i = 0; i < 8; i++) if (*pos[i] > ',' && (s < 0 || start[i] < start[s])) s = i;
        const char kind = *pos[s]++;
        int it;
        if (kind == 'x') { it = nx < 12 ? T_B << 13 | (nx % 3 * 4 + nx / 3) << 4 : T_Q << 13 | (nx - 12) << 4; nx++; }
        else if (kind == 'c') { it = (T_K + (nc & 1)) << 13 | nc / 2 << 4; nc++; }
        else { it = T_LOCAL << 13 | nl / 2 << 4 | (nl & 1); nl++; }
        p.plan[s][len[s]++] = (uint16_t)it;
        start[s] += kind == 'x' ? 48 : kind == 'c' ? 24 : 8;
    }
    for (int i = 0; i < 24; i++) p.plan[8 + i / 12][i % 12] = (uint16_t)((T_K + (i % 3 & 1)) << 13 | i % 3 / 2 << 4 | i / 3);
    const int a0 = n;
    for (int key = 0; key < 4000; key++)
        for (int r = 0; r < 32; r++)
            for (int j = 7; j >= 0; j--)
                if ((j ? (7 - j) * 40 + r * beta : 3999) == key) add(T_ATTN, 2 * order[r >> 1] + (r & 1), j);
    int t0 = n;
    for (int work = 0; work < 32 * 136 * tail / 100;) work += 4 * (p.items[--t0] & 15) + 3;
    for (int i = t0 + 1; i < n; i++)
        for (int j = i; j > t0 && (p.items[j] & 15) > (p.items[j - 1] & 15); j--) { const uint16_t t = p.items[j]; p.items[j] = p.items[j - 1]; p.items[j - 1] = t; }
    for (int r = early - 1; r >= 0; r--) {
        const uint16_t t = p.items[n - 32 + early - 1];
        for (int j = n - 32 + early - 1; j > n - epos; j--) p.items[j] = p.items[j - 1];
        p.items[n - epos] = t;
    }
    for (int moved = 0; moved < 2 && late >= 0; moved++)
        for (int i = a0; i < n; i++)
            if (p.items[i] == (T_ATTN << 13 | (2 * order[15] + moved) << 4 | late)) {
                for (int j = i; j + 1 < n; j++) p.items[j] = p.items[j + 1];
                p.items[n - 1] = (uint16_t)(T_ATTN << 13 | (2 * order[15] + moved) << 4 | late);
                break;
            }
    for (int s = 0, lo = 0, hi = WIDE - 1; s < 80; s++) {
        const int r = s / 2, g = r < 8 ? 32 + r : 2 * order[r / 2 - 4] + (r & 1);
        p.ostep[s >= WIDE ? s : r & 1 ? hi-- : lo++] = (uint8_t)(2 * g + (s & 1));
    }
}

void build_params(Params& p, void* const* d_in, void* d_out) {
    void* fnp = nullptr;
    cudaDriverEntryPointQueryResult qr;
    cudaGetDriverEntryPoint("cuTensorMapEncodeTiled", &fnp, cudaEnableDefault, &qr);
    EncodeFn fn = (EncodeFn)fnp;
    void* scr = nullptr;
    cudaGetSymbolAddress(&scr, g_scr);
    map_act(fn, &p.m[M_X], d_in[0], SEQ, 1024, 128);
    map_act(fn, &p.m[M_C], d_in[1], SEQ, 512, 128);
    map_wgt(fn, &p.m[M_WQ], d_in[2], 1024, 4096);
    map_wgt(fn, &p.m[M_WUK], d_in[3], 512, 4096);
    map_wgt(fn, &p.m[M_WUV], d_in[4], 512, 4096);
    map_wgt(fn, &p.m[M_WO], d_in[5], 4096, 1024);
    map_wgt(fn, &p.m[M_WQKV], d_in[7], 1024, 3072);
    map_wgt(fn, &p.m[M_WOB], d_in[8], 1024, 1024);
    encode3(fn, &p.m[M_SCR_LD], scr, 128, SEQ, G_TOTAL, 256, (uint64_t)SEQ * 256, 64, 128, 1);
    encode3(fn, &p.m[M_SCR_LOC], scr, 256, SEQ / 2, G_TOTAL, 512, (uint64_t)SEQ * 256, 64, 72, 1);
    encode3(fn, &p.m[M_SCR_LOQ], scr, 256, SEQ / 2, G_TOTAL, 512, (uint64_t)SEQ * 256, 64, 64, 1);
    encode3(fn, &p.m[M_SCR_ST], scr, 128, SEQ, G_TOTAL, 256, (uint64_t)SEQ * 256, 64, 64, 1);
    map_act(fn, &p.m[M_OUT], d_out, SEQ, 1024, 64);
    p.x = (const __nv_bfloat16*)d_in[0];
    p.gate_w = (const __nv_bfloat16*)d_in[9];
    p.zero = 0;
    p.wo = (const char*)d_in[5];
    p.out = (__nv_bfloat16*)d_out;
    build_schedule(p);
}

}

extern "C" void kernel_launch(void* const* d_in, const int* in_sizes, int n_in, void* d_out, int out_size) {
    (void)in_sizes; (void)n_in; (void)out_size;
    Params p;
    build_params(p, d_in, d_out);
    cudaFuncSetAttribute(fused_kernel, cudaFuncAttributeMaxDynamicSharedMemorySize, SM_TOTAL);
    fused_kernel<<<NCTA, 384, SM_TOTAL>>>(p);
}
```

```cpp
#include <cuda_runtime.h>
#include <cuda_bf16.h>
#include <cuda.h>
#include <stddef.h>
#include <stdint.h>
#include <type_traits>

namespace {

constexpr int SEQ = 2048;
constexpr int G_Q = 0, G_K = 32, G_V = 64, G_B = 96, G_CTX = G_Q, G_LOC = G_B, G_TOTAL = 120;

__device__ __align__(1024) __nv_bfloat16 g_scr[(size_t)G_TOTAL * SEQ * 128];
__device__ __align__(128) float g_gate[SEQ];

__device__ __forceinline__ uint32_t smem_u32(const void* p) { return (uint32_t)__cvta_generic_to_shared(p); }
__device__ __forceinline__ bool elect_one() {
    uint32_t p;
    asm volatile("{\n.reg .pred P;\nelect.sync _|P, 0xffffffff;\nselp.u32 %0, 1, 0, P;\n}\n" : "=r"(p));
    return p != 0;
}
__device__ __forceinline__ void mbar_init(uint32_t bar, uint32_t count) {
    asm volatile("mbarrier.init.shared::cta.b64 [%0], %1;" :: "r"(bar), "r"(count) : "memory");
}
__device__ __forceinline__ uint32_t cluster_rank() { uint32_t r; asm("mov.u32 %0, %%cluster_ctarank;" : "=r"(r)); return r; }
__device__ __forceinline__ uint32_t map_cta(uint32_t addr, uint32_t cta) {
    uint32_t r; asm("mapa.shared::cluster.u32 %0, %1, %2;" : "=r"(r) : "r"(addr), "r"(cta)); return r;
}
__device__ __forceinline__ void mbar_arrive_cluster_if(bool pred, uint32_t cluster_bar) {
    asm volatile("{\n.reg .pred P;\nsetp.ne.u32 P, %1, 0;\n@P mbarrier.arrive.shared::cluster.b64 _, [%0];\n}\n"
                 :: "r"(cluster_bar), "r"((uint32_t)pred) : "memory");
}
__device__ __forceinline__ void mbar_arrive_cluster_n_if(bool pred, uint32_t cluster_bar, uint32_t count) {
    asm volatile("{\n.reg .pred P;\nsetp.ne.u32 P, %1, 0;\n@P mbarrier.arrive.shared::cluster.b64 _, [%0], %2;\n}\n"
                 :: "r"(cluster_bar), "r"((uint32_t)pred), "r"(count) : "memory");
}
__device__ __forceinline__ void mbar_arrive_if(bool pred, uint32_t bar) {
    asm volatile("{\n.reg .pred P;\nsetp.ne.u32 P, %1, 0;\n@P mbarrier.arrive.shared::cta.b64 _, [%0];\n}\n"
                 :: "r"(bar), "r"((uint32_t)pred) : "memory");
}
__device__ __forceinline__ bool mbar_test(uint32_t bar, uint32_t parity) {
    uint32_t ok;
    asm volatile("{\n.reg .pred P;\nmbarrier.test_wait.parity.shared::cta.b64 P, [%1], %2;\nselp.u32 %0, 1, 0, P;\n}\n"
                 : "=r"(ok) : "r"(bar), "r"(parity) : "memory");
    return ok != 0;
}
__device__ __forceinline__ void mbar_wait(uint32_t bar, uint32_t parity) {
    asm volatile("{\n.reg .pred P;\n.reg .u32 c;\n"
                 "mov.u32 c, 0;\n"
                 "SPIN:\n"
                 "mbarrier.try_wait.parity.shared::cta.b64 P, [%0], %1;\n"
                 "@P bra DONE;\n"
                 "add.u32 c, c, 1;\n"
                 "setp.lt.u32 P, c, 4194304;\n"
                 "@P bra SPIN;\n"
                 "trap;\n"
                 "DONE:\n}\n" :: "r"(bar), "r"(parity) : "memory");
}
__device__ __forceinline__ void mbar_spin(uint32_t bar, uint32_t parity) {
    asm volatile("{\n.reg .pred P;\n"
                 "SPIN:\n"
                 "mbarrier.try_wait.parity.shared::cta.b64 P, [%0], %1;\n"
                 "@!P bra SPIN;\n}\n" :: "r"(bar), "r"(parity) : "memory");
}
__device__ __forceinline__ void bar_sync(int id, int n) { asm volatile("bar.sync %0, %1;" :: "r"(id), "r"(n) : "memory"); }
__device__ __forceinline__ void bar_arrive(int id, int n) { asm volatile("bar.arrive %0, %1;" :: "r"(id), "r"(n) : "memory"); }
__device__ __forceinline__ void fence_proxy_async_smem() { asm volatile("fence.proxy.async.shared::cta;" ::: "memory"); }
__device__ __forceinline__ void warp_expect_tx(uint32_t bar, uint32_t bytes) {
    asm volatile("{\n.reg .pred P;\nelect.sync _|P, 0xffffffff;\n@P mbarrier.arrive.expect_tx.shared::cta.b64 _, [%0], %1;\n}\n"
                 :: "r"(bar), "r"(bytes) : "memory");
}
constexpr uint64_t EVICT_FIRST = 0x12F0000000000000ull;
__device__ __forceinline__ void warp_tma_load(uint32_t dst, const CUtensorMap* map, uint32_t bar, int c0, int c1, int c2, bool stream) {
    if (stream)
        asm volatile("{\n.reg .pred P;\nelect.sync _|P, 0xffffffff;\n"
                     "@P cp.async.bulk.tensor.3d.shared::cluster.global.mbarrier::complete_tx::bytes.L2::cache_hint"
                     " [%0], [%1, {%3, %4, %5}], [%2], %6;\n}\n"
                     :: "r"(dst), "l"(map), "r"(bar), "r"(c0), "r"(c1), "r"(c2), "l"(EVICT_FIRST) : "memory");
    else
        asm volatile("{\n.reg .pred P;\nelect.sync _|P, 0xffffffff;\n"
                     "@P cp.async.bulk.tensor.3d.shared::cluster.global.mbarrier::complete_tx::bytes [%0], [%1, {%3, %4, %5}], [%2];\n}\n"
                     :: "r"(dst), "l"(map), "r"(bar), "r"(c0), "r"(c1), "r"(c2) : "memory");
}
__device__ __forceinline__ void warp_tma_load_pair(uint32_t dst, const CUtensorMap* map, uint32_t bar, int c0, int c1, int c2, bool stream) {
    if (stream)
        asm volatile("{\n.reg .pred P;\nelect.sync _|P, 0xffffffff;\n"
                     "@P cp.async.bulk.tensor.3d.shared::cluster.global.mbarrier::complete_tx::bytes.multicast::cluster.L2::cache_hint"
                     " [%0], [%1, {%3, %4, %5}], [%2], %6, %7;\n}\n"
                     :: "r"(dst), "l"(map), "r"(bar), "r"(c0), "r"(c1), "r"(c2), "h"((uint16_t)3), "l"(EVICT_FIRST) : "memory");
    else
        asm volatile("{\n.reg .pred P;\nelect.sync _|P, 0xffffffff;\n"
                     "@P cp.async.bulk.tensor.3d.shared::cluster.global.mbarrier::complete_tx::bytes.multicast::cluster"
                     " [%0], [%1, {%3, %4, %5}], [%2], %6;\n}\n"
                     :: "r"(dst), "l"(map), "r"(bar), "r"(c0), "r"(c1), "r"(c2), "h"((uint16_t)3) : "memory");
}
__device__ __forceinline__ void warp_bulk_load(uint32_t dst, const void* src, uint32_t bytes, uint32_t bar) {
    asm volatile("{\n.reg .pred P;\nelect.sync _|P, 0xffffffff;\n"
                 "@P cp.async.bulk.shared::cluster.global.mbarrier::complete_tx::bytes [%0], [%1], %2, [%3];\n}\n"
                 :: "r"(dst), "l"(src), "r"(bytes), "r"(bar) : "memory");
}
__device__ __forceinline__ void warp_tma_store(const CUtensorMap* map, uint32_t src, int c0, int c1, int c2, bool stream) {
    if (stream)
        asm volatile("{\n.reg .pred P;\nelect.sync _|P, 0xffffffff;\n"
                     "@P cp.async.bulk.tensor.3d.global.shared::cta.bulk_group.L2::cache_hint [%0, {%2, %3, %4}], [%1], %5;\n}\n"
                     :: "l"(map), "r"(src), "r"(c0), "r"(c1), "r"(c2), "l"(EVICT_FIRST) : "memory");
    else
        asm volatile("{\n.reg .pred P;\nelect.sync _|P, 0xffffffff;\n"
                     "@P cp.async.bulk.tensor.3d.global.shared::cta.bulk_group [%0, {%2, %3, %4}], [%1];\n}\n"
                     :: "l"(map), "r"(src), "r"(c0), "r"(c1), "r"(c2) : "memory");
}
__device__ __forceinline__ void warp_tma_add(const CUtensorMap* map, uint32_t src, int c0, int c1, int c2) {
    asm volatile("{\n.reg .pred P;\nelect.sync _|P, 0xffffffff;\n"
                 "@P cp.reduce.async.bulk.tensor.3d.global.shared::cta.add.tile.bulk_group [%0, {%2, %3, %4}], [%1];\n}\n"
                 :: "l"(map), "r"(src), "r"(c0), "r"(c1), "r"(c2) : "memory");
}
__device__ __forceinline__ void warp_bulk_store(void* dst, uint32_t src, uint32_t bytes) {
    asm volatile("{\n.reg .pred P;\nelect.sync _|P, 0xffffffff;\n"
                 "@P cp.async.bulk.global.shared::cta.bulk_group [%0], [%1], %2;\n}\n" :: "l"(dst), "r"(src), "r"(bytes) : "memory");
}
__device__ __forceinline__ void warp_prefetch(const void* src, uint32_t bytes) {
    asm volatile("{\n.reg .pred P;\nelect.sync _|P, 0xffffffff;\n@P cp.async.bulk.prefetch.L2.global [%0], %1;\n}\n" :: "l"(src), "r"(bytes) : "memory");
}
__device__ __forceinline__ void bulk_commit() { asm volatile("cp.async.bulk.commit_group;" ::: "memory"); }
template <int N> __device__ __forceinline__ void bulk_wait_read() { asm volatile("cp.async.bulk.wait_group.read %0;" :: "n"(N) : "memory"); }
template <int N> __device__ __forceinline__ void bulk_wait() { asm volatile("cp.async.bulk.wait_group %0;" :: "n"(N) : "memory"); }
__device__ __forceinline__ void wgmma_fence() { asm volatile("wgmma.fence.sync.aligned;" ::: "memory"); }
__device__ __forceinline__ void wgmma_commit() { asm volatile("wgmma.commit_group.sync.aligned;" ::: "memory"); }
template <int N> __device__ __forceinline__ void wgmma_wait() { asm volatile("wgmma.wait_group.sync.aligned %0;" :: "n"(N) : "memory"); }
template <int N> __device__ __forceinline__ void fence_regs(float (&d)[N]) {
#pragma unroll
    for (int i = 0; i < N; i++) asm volatile("" : "+f"(d[i]) :: "memory");
}
template <int N> __device__ __forceinline__ void fence_regs(uint32_t (&d)[N]) {
#pragma unroll
    for (int i = 0; i < N; i++) asm volatile("" : "+r"(d[i]) :: "memory");
}
template <int N> __device__ __forceinline__ void reg_dec() { asm volatile("setmaxnreg.dec.sync.aligned.u32 %0;" :: "n"(N)); }
template <int N> __device__ __forceinline__ void reg_inc() { asm volatile("setmaxnreg.inc.sync.aligned.u32 %0;" :: "n"(N)); }
__device__ __forceinline__ uint32_t pack_bf16(float lo, float hi) {
    uint32_t r; asm("cvt.rn.bf16x2.f32 %0, %1, %2;" : "=r"(r) : "f"(hi), "f"(lo)); return r;
}
__device__ __forceinline__ void stmatrix_x4(uint32_t addr, uint32_t r0, uint32_t r1, uint32_t r2, uint32_t r3) {
    asm volatile("stmatrix.sync.aligned.m8n8.x4.shared.b16 [%0], {%1, %2, %3, %4};"
                 :: "r"(addr), "r"(r0), "r"(r1), "r"(r2), "r"(r3) : "memory");
}
__device__ __forceinline__ float ex2(float x) { float y; asm("ex2.approx.ftz.f32 %0, %1;" : "=f"(y) : "f"(x)); return y; }

constexpr uint32_t DESC_HI = (1024 >> 4) | (1u << 30);
__device__ __forceinline__ uint32_t make_desc(uint32_t addr, uint32_t lbo) {
    uint32_t lo = ((addr & 0x3FFFF) >> 4) | ((lbo >> 4) << 16);
    asm volatile("" : "+r"(lo));
    return lo;
}
__device__ __forceinline__ uint64_t full_desc(uint32_t lo) {
    uint64_t d; asm("mov.b64 %0, {%1, %2};" : "=l"(d) : "r"(lo), "r"(DESC_HI)); return d;
}

__device__ __forceinline__ void wgmma_ss_n256_tb_init(float (&d)[128], uint64_t da, uint64_t db) {
    asm volatile("{\n.reg .pred p;\n"
        "setp.ne.b32 p, 0, 0;\n"
        "wgmma.mma_async.sync.aligned.m64n256k16.f32.bf16.bf16 "
        "{%0, %1, %2, %3, %4, %5, %6, %7, %8, %9, %10, %11, %12, %13, %14, %15, %16, %17, %18, %19, %20, "
        "%21, %22, %23, %24, %25, %26, %27, %28, %29, %30, %31, %32, %33, %34, %35, %36, %37, %38, %39, %40, "
        "%41, %42, %43, %44, %45, %46, %47, %48, %49, %50, %51, %52, %53, %54, %55, %56, %57, %58, %59, %60, "
        "%61, %62, %63, %64, %65, %66, %67, %68, %69, %70, %71, %72, %73, %74, %75, %76, %77, %78, %79, %80, "
        "%81, %82, %83, %84, %85, %86, %87, %88, %89, %90, %91, %92, %93, %94, %95, %96, %97, %98, %99, "
        "%100, %101, %102, %103, %104, %105, %106, %107, %108, %109, %110, %111, %112, %113, %114, %115, "
        "%116, %117, %118, %119, %120, %121, %122, %123, %124, %125, %126, %127},"
        " %128, %129, p, 1, 1, 0, 1;\n}\n"
        : "=f"(d[0]), "=f"(d[1]), "=f"(d[2]), "=f"(d[3]), "=f"(d[4]), "=f"(d[5]), "=f"(d[6]), "=f"(d[7]),
        "=f"(d[8]), "=f"(d[9]), "=f"(d[10]), "=f"(d[11]), "=f"(d[12]), "=f"(d[13]), "=f"(d[14]), "=f"(d[15]),
        "=f"(d[16]), "=f"(d[17]), "=f"(d[18]), "=f"(d[19]), "=f"(d[20]), "=f"(d[21]), "=f"(d[22]),
        "=f"(d[23]), "=f"(d[24]), "=f"(d[25]), "=f"(d[26]), "=f"(d[27]), "=f"(d[28]), "=f"(d[29]),
        "=f"(d[30]), "=f"(d[31]), "=f"(d[32]), "=f"(d[33]), "=f"(d[34]), "=f"(d[35]), "=f"(d[36]),
        "=f"(d[37]), "=f"(d[38]), "=f"(d[39]), "=f"(d[40]), "=f"(d[41]), "=f"(d[42]), "=f"(d[43]),
        "=f"(d[44]), "=f"(d[45]), "=f"(d[46]), "=f"(d[47]), "=f"(d[48]), "=f"(d[49]), "=f"(d[50]),
        "=f"(d[51]), "=f"(d[52]), "=f"(d[53]), "=f"(d[54]), "=f"(d[55]), "=f"(d[56]), "=f"(d[57]),
        "=f"(d[58]), "=f"(d[59]), "=f"(d[60]), "=f"(d[61]), "=f"(d[62]), "=f"(d[63]), "=f"(d[64]),
        "=f"(d[65]), "=f"(d[66]), "=f"(d[67]), "=f"(d[68]), "=f"(d[69]), "=f"(d[70]), "=f"(d[71]),
        "=f"(d[72]), "=f"(d[73]), "=f"(d[74]), "=f"(d[75]), "=f"(d[76]), "=f"(d[77]), "=f"(d[78]),
        "=f"(d[79]), "=f"(d[80]), "=f"(d[81]), "=f"(d[82]), "=f"(d[83]), "=f"(d[84]), "=f"(d[85]),
        "=f"(d[86]), "=f"(d[87]), "=f"(d[88]), "=f"(d[89]), "=f"(d[90]), "=f"(d[91]), "=f"(d[92]),
        "=f"(d[93]), "=f"(d[94]), "=f"(d[95]), "=f"(d[96]), "=f"(d[97]), "=f"(d[98]), "=f"(d[99]),
        "=f"(d[100]), "=f"(d[101]), "=f"(d[102]), "=f"(d[103]), "=f"(d[104]), "=f"(d[105]), "=f"(d[106]),
        "=f"(d[107]), "=f"(d[108]), "=f"(d[109]), "=f"(d[110]), "=f"(d[111]), "=f"(d[112]), "=f"(d[113]),
        "=f"(d[114]), "=f"(d[115]), "=f"(d[116]), "=f"(d[117]), "=f"(d[118]), "=f"(d[119]), "=f"(d[120]),
        "=f"(d[121]), "=f"(d[122]), "=f"(d[123]), "=f"(d[124]), "=f"(d[125]), "=f"(d[126]), "=f"(d[127])
        : "l"(da), "l"(db));
}
__device__ __forceinline__ void wgmma_ss_n256_tb(float (&d)[128], uint64_t da, uint64_t db, int scale_d) {
    asm volatile("{\n.reg .pred p;\n"
        "setp.ne.b32 p, %130, 0;\n"
        "wgmma.mma_async.sync.aligned.m64n256k16.f32.bf16.bf16 "
        "{%0, %1, %2, %3, %4, %5, %6, %7, %8, %9, %10, %11, %12, %13, %14, %15, %16, %17, %18, %19, %20, "
        "%21, %22, %23, %24, %25, %26, %27, %28, %29, %30, %31, %32, %33, %34, %35, %36, %37, %38, %39, %40, "
        "%41, %42, %43, %44, %45, %46, %47, %48, %49, %50, %51, %52, %53, %54, %55, %56, %57, %58, %59, %60, "
        "%61, %62, %63, %64, %65, %66, %67, %68, %69, %70, %71, %72, %73, %74, %75, %76, %77, %78, %79, %80, "
        "%81, %82, %83, %84, %85, %86, %87, %88, %89, %90, %91, %92, %93, %94, %95, %96, %97, %98, %99, "
        "%100, %101, %102, %103, %104, %105, %106, %107, %108, %109, %110, %111, %112, %113, %114, %115, "
        "%116, %117, %118, %119, %120, %121, %122, %123, %124, %125, %126, %127},"
        " %128, %129, p, 1, 1, 0, 1;\n}\n"
        : "+f"(d[0]), "+f"(d[1]), "+f"(d[2]), "+f"(d[3]), "+f"(d[4]), "+f"(d[5]), "+f"(d[6]), "+f"(d[7]),
        "+f"(d[8]), "+f"(d[9]), "+f"(d[10]), "+f"(d[11]), "+f"(d[12]), "+f"(d[13]), "+f"(d[14]), "+f"(d[15]),
        "+f"(d[16]), "+f"(d[17]), "+f"(d[18]), "+f"(d[19]), "+f"(d[20]), "+f"(d[21]), "+f"(d[22]),
        "+f"(d[23]), "+f"(d[24]), "+f"(d[25]), "+f"(d[26]), "+f"(d[27]), "+f"(d[28]), "+f"(d[29]),
        "+f"(d[30]), "+f"(d[31]), "+f"(d[32]), "+f"(d[33]), "+f"(d[34]), "+f"(d[35]), "+f"(d[36]),
        "+f"(d[37]), "+f"(d[38]), "+f"(d[39]), "+f"(d[40]), "+f"(d[41]), "+f"(d[42]), "+f"(d[43]),
        "+f"(d[44]), "+f"(d[45]), "+f"(d[46]), "+f"(d[47]), "+f"(d[48]), "+f"(d[49]), "+f"(d[50]),
        "+f"(d[51]), "+f"(d[52]), "+f"(d[53]), "+f"(d[54]), "+f"(d[55]), "+f"(d[56]), "+f"(d[57]),
        "+f"(d[58]), "+f"(d[59]), "+f"(d[60]), "+f"(d[61]), "+f"(d[62]), "+f"(d[63]), "+f"(d[64]),
        "+f"(d[65]), "+f"(d[66]), "+f"(d[67]), "+f"(d[68]), "+f"(d[69]), "+f"(d[70]), "+f"(d[71]),
        "+f"(d[72]), "+f"(d[73]), "+f"(d[74]), "+f"(d[75]), "+f"(d[76]), "+f"(d[77]), "+f"(d[78]),
        "+f"(d[79]), "+f"(d[80]), "+f"(d[81]), "+f"(d[82]), "+f"(d[83]), "+f"(d[84]), "+f"(d[85]),
        "+f"(d[86]), "+f"(d[87]), "+f"(d[88]), "+f"(d[89]), "+f"(d[90]), "+f"(d[91]), "+f"(d[92]),
        "+f"(d[93]), "+f"(d[94]), "+f"(d[95]), "+f"(d[96]), "+f"(d[97]), "+f"(d[98]), "+f"(d[99]),
        "+f"(d[100]), "+f"(d[101]), "+f"(d[102]), "+f"(d[103]), "+f"(d[104]), "+f"(d[105]), "+f"(d[106]),
        "+f"(d[107]), "+f"(d[108]), "+f"(d[109]), "+f"(d[110]), "+f"(d[111]), "+f"(d[112]), "+f"(d[113]),
        "+f"(d[114]), "+f"(d[115]), "+f"(d[116]), "+f"(d[117]), "+f"(d[118]), "+f"(d[119]), "+f"(d[120]),
        "+f"(d[121]), "+f"(d[122]), "+f"(d[123]), "+f"(d[124]), "+f"(d[125]), "+f"(d[126]), "+f"(d[127])
        : "l"(da), "l"(db), "r"(scale_d));
}
__device__ __forceinline__ void wgmma_ss_n128_init(float (&d)[64], uint64_t da, uint64_t db) {
    asm volatile("{\n.reg .pred p;\n"
        "setp.ne.b32 p, 0, 0;\n"
        "wgmma.mma_async.sync.aligned.m64n128k16.f32.bf16.bf16 "
        "{%0, %1, %2, %3, %4, %5, %6, %7, %8, %9, %10, %11, %12, %13, %14, %15, %16, %17, %18, %19, %20, "
        "%21, %22, %23, %24, %25, %26, %27, %28, %29, %30, %31, %32, %33, %34, %35, %36, %37, %38, %39, %40, "
        "%41, %42, %43, %44, %45, %46, %47, %48, %49, %50, %51, %52, %53, %54, %55, %56, %57, %58, %59, %60, "
        "%61, %62, %63},"
        " %64, %65, p, 1, 1, 0, 0;\n}\n"
        : "=f"(d[0]), "=f"(d[1]), "=f"(d[2]), "=f"(d[3]), "=f"(d[4]), "=f"(d[5]), "=f"(d[6]), "=f"(d[7]),
        "=f"(d[8]), "=f"(d[9]), "=f"(d[10]), "=f"(d[11]), "=f"(d[12]), "=f"(d[13]), "=f"(d[14]), "=f"(d[15]),
        "=f"(d[16]), "=f"(d[17]), "=f"(d[18]), "=f"(d[19]), "=f"(d[20]), "=f"(d[21]), "=f"(d[22]),
        "=f"(d[23]), "=f"(d[24]), "=f"(d[25]), "=f"(d[26]), "=f"(d[27]), "=f"(d[28]), "=f"(d[29]),
        "=f"(d[30]), "=f"(d[31]), "=f"(d[32]), "=f"(d[33]), "=f"(d[34]), "=f"(d[35]), "=f"(d[36]),
        "=f"(d[37]), "=f"(d[38]), "=f"(d[39]), "=f"(d[40]), "=f"(d[41]), "=f"(d[42]), "=f"(d[43]),
        "=f"(d[44]), "=f"(d[45]), "=f"(d[46]), "=f"(d[47]), "=f"(d[48]), "=f"(d[49]), "=f"(d[50]),
        "=f"(d[51]), "=f"(d[52]), "=f"(d[53]), "=f"(d[54]), "=f"(d[55]), "=f"(d[56]), "=f"(d[57]),
        "=f"(d[58]), "=f"(d[59]), "=f"(d[60]), "=f"(d[61]), "=f"(d[62]), "=f"(d[63])
        : "l"(da), "l"(db));
}
__device__ __forceinline__ void wgmma_ss_n128(float (&d)[64], uint64_t da, uint64_t db, int scale_d) {
    asm volatile("{\n.reg .pred p;\n"
        "setp.ne.b32 p, %66, 0;\n"
        "wgmma.mma_async.sync.aligned.m64n128k16.f32.bf16.bf16 "
        "{%0, %1, %2, %3, %4, %5, %6, %7, %8, %9, %10, %11, %12, %13, %14, %15, %16, %17, %18, %19, %20, "
        "%21, %22, %23, %24, %25, %26, %27, %28, %29, %30, %31, %32, %33, %34, %35, %36, %37, %38, %39, %40, "
        "%41, %42, %43, %44, %45, %46, %47, %48, %49, %50, %51, %52, %53, %54, %55, %56, %57, %58, %59, %60, "
        "%61, %62, %63},"
        " %64, %65, p, 1, 1, 0, 0;\n}\n"
        : "+f"(d[0]), "+f"(d[1]), "+f"(d[2]), "+f"(d[3]), "+f"(d[4]), "+f"(d[5]), "+f"(d[6]), "+f"(d[7]),
        "+f"(d[8]), "+f"(d[9]), "+f"(d[10]), "+f"(d[11]), "+f"(d[12]), "+f"(d[13]), "+f"(d[14]), "+f"(d[15]),
        "+f"(d[16]), "+f"(d[17]), "+f"(d[18]), "+f"(d[19]), "+f"(d[20]), "+f"(d[21]), "+f"(d[22]),
        "+f"(d[23]), "+f"(d[24]), "+f"(d[25]), "+f"(d[26]), "+f"(d[27]), "+f"(d[28]), "+f"(d[29]),
        "+f"(d[30]), "+f"(d[31]), "+f"(d[32]), "+f"(d[33]), "+f"(d[34]), "+f"(d[35]), "+f"(d[36]),
        "+f"(d[37]), "+f"(d[38]), "+f"(d[39]), "+f"(d[40]), "+f"(d[41]), "+f"(d[42]), "+f"(d[43]),
        "+f"(d[44]), "+f"(d[45]), "+f"(d[46]), "+f"(d[47]), "+f"(d[48]), "+f"(d[49]), "+f"(d[50]),
        "+f"(d[51]), "+f"(d[52]), "+f"(d[53]), "+f"(d[54]), "+f"(d[55]), "+f"(d[56]), "+f"(d[57]),
        "+f"(d[58]), "+f"(d[59]), "+f"(d[60]), "+f"(d[61]), "+f"(d[62]), "+f"(d[63])
        : "l"(da), "l"(db), "r"(scale_d));
}
__device__ __forceinline__ void wgmma_rs_n128_tb(float (&d)[64], uint32_t a0, uint32_t a1, uint32_t a2, uint32_t a3, uint64_t db, int scale_d) {
    asm volatile("{\n.reg .pred p;\n"
        "setp.ne.b32 p, %69, 0;\n"
        "wgmma.mma_async.sync.aligned.m64n128k16.f32.bf16.bf16 "
        "{%0, %1, %2, %3, %4, %5, %6, %7, %8, %9, %10, %11, %12, %13, %14, %15, %16, %17, %18, %19, %20, "
        "%21, %22, %23, %24, %25, %26, %27, %28, %29, %30, %31, %32, %33, %34, %35, %36, %37, %38, %39, %40, "
        "%41, %42, %43, %44, %45, %46, %47, %48, %49, %50, %51, %52, %53, %54, %55, %56, %57, %58, %59, %60, "
        "%61, %62, %63},"
        " {%64, %65, %66, %67}, %68, p, 1, 1, 1;\n}\n"
        : "+f"(d[0]), "+f"(d[1]), "+f"(d[2]), "+f"(d[3]), "+f"(d[4]), "+f"(d[5]), "+f"(d[6]), "+f"(d[7]),
        "+f"(d[8]), "+f"(d[9]), "+f"(d[10]), "+f"(d[11]), "+f"(d[12]), "+f"(d[13]), "+f"(d[14]), "+f"(d[15]),
        "+f"(d[16]), "+f"(d[17]), "+f"(d[18]), "+f"(d[19]), "+f"(d[20]), "+f"(d[21]), "+f"(d[22]),
        "+f"(d[23]), "+f"(d[24]), "+f"(d[25]), "+f"(d[26]), "+f"(d[27]), "+f"(d[28]), "+f"(d[29]),
        "+f"(d[30]), "+f"(d[31]), "+f"(d[32]), "+f"(d[33]), "+f"(d[34]), "+f"(d[35]), "+f"(d[36]),
        "+f"(d[37]), "+f"(d[38]), "+f"(d[39]), "+f"(d[40]), "+f"(d[41]), "+f"(d[42]), "+f"(d[43]),
        "+f"(d[44]), "+f"(d[45]), "+f"(d[46]), "+f"(d[47]), "+f"(d[48]), "+f"(d[49]), "+f"(d[50]),
        "+f"(d[51]), "+f"(d[52]), "+f"(d[53]), "+f"(d[54]), "+f"(d[55]), "+f"(d[56]), "+f"(d[57]),
        "+f"(d[58]), "+f"(d[59]), "+f"(d[60]), "+f"(d[61]), "+f"(d[62]), "+f"(d[63])
        : "r"(a0), "r"(a1), "r"(a2), "r"(a3), "l"(db), "r"(scale_d));
}
__device__ __forceinline__ void wgmma_ss_n128_tb_init(float (&d)[64], uint64_t da, uint64_t db) {
    asm volatile("{\n.reg .pred p;\n"
        "setp.ne.b32 p, 0, 0;\n"
        "wgmma.mma_async.sync.aligned.m64n128k16.f32.bf16.bf16 "
        "{%0, %1, %2, %3, %4, %5, %6, %7, %8, %9, %10, %11, %12, %13, %14, %15, %16, %17, %18, %19, %20, "
        "%21, %22, %23, %24, %25, %26, %27, %28, %29, %30, %31, %32, %33, %34, %35, %36, %37, %38, %39, %40, "
        "%41, %42, %43, %44, %45, %46, %47, %48, %49, %50, %51, %52, %53, %54, %55, %56, %57, %58, %59, %60, "
        "%61, %62, %63},"
        " %64, %65, p, 1, 1, 0, 1;\n}\n"
        : "=f"(d[0]), "=f"(d[1]), "=f"(d[2]), "=f"(d[3]), "=f"(d[4]), "=f"(d[5]), "=f"(d[6]), "=f"(d[7]),
        "=f"(d[8]), "=f"(d[9]), "=f"(d[10]), "=f"(d[11]), "=f"(d[12]), "=f"(d[13]), "=f"(d[14]), "=f"(d[15]),
        "=f"(d[16]), "=f"(d[17]), "=f"(d[18]), "=f"(d[19]), "=f"(d[20]), "=f"(d[21]), "=f"(d[22]),
        "=f"(d[23]), "=f"(d[24]), "=f"(d[25]), "=f"(d[26]), "=f"(d[27]), "=f"(d[28]), "=f"(d[29]),
        "=f"(d[30]), "=f"(d[31]), "=f"(d[32]), "=f"(d[33]), "=f"(d[34]), "=f"(d[35]), "=f"(d[36]),
        "=f"(d[37]), "=f"(d[38]), "=f"(d[39]), "=f"(d[40]), "=f"(d[41]), "=f"(d[42]), "=f"(d[43]),
        "=f"(d[44]), "=f"(d[45]), "=f"(d[46]), "=f"(d[47]), "=f"(d[48]), "=f"(d[49]), "=f"(d[50]),
        "=f"(d[51]), "=f"(d[52]), "=f"(d[53]), "=f"(d[54]), "=f"(d[55]), "=f"(d[56]), "=f"(d[57]),
        "=f"(d[58]), "=f"(d[59]), "=f"(d[60]), "=f"(d[61]), "=f"(d[62]), "=f"(d[63])
        : "l"(da), "l"(db));
}
__device__ __forceinline__ void wgmma_ss_n128_tb(float (&d)[64], uint64_t da, uint64_t db, int scale_d) {
    asm volatile("{\n.reg .pred p;\n"
        "setp.ne.b32 p, %66, 0;\n"
        "wgmma.mma_async.sync.aligned.m64n128k16.f32.bf16.bf16 "
        "{%0, %1, %2, %3, %4, %5, %6, %7, %8, %9, %10, %11, %12, %13, %14, %15, %16, %17, %18, %19, %20, "
        "%21, %22, %23, %24, %25, %26, %27, %28, %29, %30, %31, %32, %33, %34, %35, %36, %37, %38, %39, %40, "
        "%41, %42, %43, %44, %45, %46, %47, %48, %49, %50, %51, %52, %53, %54, %55, %56, %57, %58, %59, %60, "
        "%61, %62, %63},"
        " %64, %65, p, 1, 1, 0, 1;\n}\n"
        : "+f"(d[0]), "+f"(d[1]), "+f"(d[2]), "+f"(d[3]), "+f"(d[4]), "+f"(d[5]), "+f"(d[6]), "+f"(d[7]),
        "+f"(d[8]), "+f"(d[9]), "+f"(d[10]), "+f"(d[11]), "+f"(d[12]), "+f"(d[13]), "+f"(d[14]), "+f"(d[15]),
        "+f"(d[16]), "+f"(d[17]), "+f"(d[18]), "+f"(d[19]), "+f"(d[20]), "+f"(d[21]), "+f"(d[22]),
        "+f"(d[23]), "+f"(d[24]), "+f"(d[25]), "+f"(d[26]), "+f"(d[27]), "+f"(d[28]), "+f"(d[29]),
        "+f"(d[30]), "+f"(d[31]), "+f"(d[32]), "+f"(d[33]), "+f"(d[34]), "+f"(d[35]), "+f"(d[36]),
        "+f"(d[37]), "+f"(d[38]), "+f"(d[39]), "+f"(d[40]), "+f"(d[41]), "+f"(d[42]), "+f"(d[43]),
        "+f"(d[44]), "+f"(d[45]), "+f"(d[46]), "+f"(d[47]), "+f"(d[48]), "+f"(d[49]), "+f"(d[50]),
        "+f"(d[51]), "+f"(d[52]), "+f"(d[53]), "+f"(d[54]), "+f"(d[55]), "+f"(d[56]), "+f"(d[57]),
        "+f"(d[58]), "+f"(d[59]), "+f"(d[60]), "+f"(d[61]), "+f"(d[62]), "+f"(d[63])
        : "l"(da), "l"(db), "r"(scale_d));
}

enum { M_X = 0, M_C, M_WQ, M_WUK, M_WUV, M_WQKV, M_WO, M_WOB, M_SCR_LD, M_SCR_LOC, M_SCR_LOQ, M_SCR_ST, M_OUT, M_COUNT };
enum { T_Q = 0, T_K, T_V, T_B, T_OUT, T_LOCAL, T_ATTN, T_END };
constexpr int NCTA = 132;
constexpr int NITEMS = 256;
constexpr int TRIPLES = 2, WIDE = 80 - 3 * TRIPLES;
struct Params {
    CUtensorMap m[M_COUNT];
    const __nv_bfloat16* x;
    const __nv_bfloat16* gate_w;
    const char* wo;
    __nv_bfloat16* out;
    uint32_t zero;
    uint16_t plan[10][16];
    uint16_t items[NITEMS];
    uint8_t ostep[80];
};
__device__ __forceinline__ int item_type(int it) { return it >> 13; }
__device__ __forceinline__ int item_row(int it) { return it & 15; }
__device__ __forceinline__ int item_col(int it) { return (it >> 4) & 31; }
__device__ __forceinline__ int item_asc(int it) { return (it >> 9) & 1; }
constexpr int ITEM_READY = 1 << 10;

struct __align__(128) Sync {
    unsigned long long count[4];
    __align__(128) unsigned long long ctx[16];
    unsigned next, next_out, done;
    __align__(128) unsigned step[32][2];
    unsigned split[32];
};
__device__ Sync g_sync;

constexpr uint32_t GST_BYTES = 49152, SM_KV = 65536, SM_STAGING = 196608, SM_BARS = SM_STAGING + 32768;
constexpr uint32_t B_GFULL = 0, B_GEMPTY = 32, B_AFULL = 64, B_AEMPTY = 112, B_SFULL = 160, B_SEMPTY = 192,
                   B_IFULL = 224, B_IEMPTY = 288, B_XFREE = 352, B_WANT = 384, B_MEET = 392, B_HALF = 416,
                   SM_ORDY = 448, SM_QUEUE = 456, B_ALT = 488, B_QFREE = 504, SM_GATE = 512, SM_TOTAL = SM_BARS + 1536;
constexpr int QDEPTH = 8;
constexpr int FIRST_PAIR = 6;
constexpr int K_MEET = 16, K_SPLIT = 30;
constexpr int K_FETCH = 20;
constexpr uint32_t LOC_PLANE = 72 * 128;
constexpr float LOC_SCALE = 0.17677669529663687f * 1.4426950408889634f;
constexpr float SUM_LIMIT = 1152921504606846976.f;
constexpr float REF_RANGE = 32.f;

__device__ __forceinline__ unsigned ld_acquire(const unsigned* p) {
    unsigned v; asm volatile("ld.acquire.gpu.global.u32 %0, [%1];" : "=r"(v) : "l"(p) : "memory"); return v;
}
__device__ __forceinline__ unsigned long long ld_acquire(const unsigned long long* p) {
    unsigned long long v; asm volatile("ld.acquire.gpu.global.u64 %0, [%1];" : "=l"(v) : "l"(p) : "memory"); return v;
}
__device__ __forceinline__ void spin_guard(unsigned& n) {
    asm volatile("{\n.reg .pred P;\nadd.u32 %0, %0, 1;\nsetp.gt.u32 P, %0, 16777216;\n@P trap;\n}\n" : "+r"(n));
    if (n > 1) __nanosleep(100);
}
__device__ __forceinline__ void red_add(unsigned long long* p, unsigned long long v) {
    asm volatile("red.release.gpu.global.add.u64 [%0], %1;" :: "l"(p), "l"(v) : "memory");
}
__device__ __forceinline__ float rcp(float x) { float y; asm("rcp.approx.ftz.f32 %0, %1;" : "=f"(y) : "f"(x)); return y; }
__device__ __forceinline__ float lds_f32(uint32_t addr) {
    float v; asm volatile("ld.shared.f32 %0, [%1];" : "=f"(v) : "r"(addr) : "memory"); return v;
}
__device__ __forceinline__ void ldsm_x4(uint32_t (&r)[4], uint32_t addr) {
    asm volatile("ldmatrix.sync.aligned.m8n8.x4.shared.b16 {%0, %1, %2, %3}, [%4];"
                 : "=r"(r[0]), "=r"(r[1]), "=r"(r[2]), "=r"(r[3]) : "r"(addr) : "memory");
}
__device__ __forceinline__ void ldsm_x4_t(uint32_t (&r)[4], uint32_t addr) {
    asm volatile("ldmatrix.sync.aligned.m8n8.x4.trans.shared.b16 {%0, %1, %2, %3}, [%4];"
                 : "=r"(r[0]), "=r"(r[1]), "=r"(r[2]), "=r"(r[3]) : "r"(addr) : "memory");
}
__device__ __forceinline__ void mma_k16(float (&d)[4], const uint32_t (&a)[4], uint32_t b0, uint32_t b1) {
    asm("mma.sync.aligned.m16n8k16.row.col.f32.bf16.bf16.f32 {%0,%1,%2,%3}, {%4,%5,%6,%7}, {%8,%9}, {%0,%1,%2,%3};"
        : "+f"(d[0]), "+f"(d[1]), "+f"(d[2]), "+f"(d[3]) : "r"(a[0]), "r"(a[1]), "r"(a[2]), "r"(a[3]), "r"(b0), "r"(b1));
}
__device__ __forceinline__ void mma_k16_init(float (&d)[4], const uint32_t (&a)[4], uint32_t b0, uint32_t b1) {
    asm("{\n.reg .f32 z;\nmov.f32 z, 0f00000000;\n"
        "mma.sync.aligned.m16n8k16.row.col.f32.bf16.bf16.f32 {%0,%1,%2,%3}, {%4,%5,%6,%7}, {%8,%9}, {z,z,z,z};\n}\n"
        : "=f"(d[0]), "=f"(d[1]), "=f"(d[2]), "=f"(d[3]) : "r"(a[0]), "r"(a[1]), "r"(a[2]), "r"(a[3]), "r"(b0), "r"(b1));
}
__device__ __forceinline__ void mma_k8(float (&d)[4], uint32_t a0, uint32_t a1, uint32_t b0) {
    asm("mma.sync.aligned.m16n8k8.row.col.f32.bf16.bf16.f32 {%0,%1,%2,%3}, {%4,%5}, {%6}, {%0,%1,%2,%3};"
        : "+f"(d[0]), "+f"(d[1]), "+f"(d[2]), "+f"(d[3]) : "r"(a0), "r"(a1), "r"(b0));
}
template <typename T, int N> __device__ __forceinline__ void zero_regs(T (&d)[N]) {
#pragma unroll
    for (int i = 0; i < N; i++) d[i] = 0;
}
__device__ __forceinline__ float quad_max(float v) {
    v = fmaxf(v, __shfl_xor_sync(0xffffffffu, v, 1));
    return fmaxf(v, __shfl_xor_sync(0xffffffffu, v, 2));
}
__device__ __forceinline__ float quad_sum(float v) {
    v += __shfl_xor_sync(0xffffffffu, v, 1);
    return v + __shfl_xor_sync(0xffffffffu, v, 2);
}

__device__ __forceinline__ void qk_gemm(float (&s)[64], uint32_t q_lo, uint32_t k_lo) {
    const uint64_t dq = full_desc(q_lo), dk = full_desc(k_lo);
    wgmma_fence();
    wgmma_ss_n128_init(s, dq, dk);
#pragma unroll
    for (int kk = 1; kk < 8; kk++) {
        const uint32_t o = (kk >> 2) * 1024 + (kk & 3) * 2;
        wgmma_ss_n128(s, dq + o, dk + o, 1);
    }
    wgmma_commit();
}
__device__ __forceinline__ void pv_gemm(float (&o)[64], uint32_t (&p)[32], uint32_t v_lo, int accumulate) {
    const uint64_t dv = full_desc(v_lo);
    fence_regs(o);
    fence_regs(p);
    wgmma_fence();
#pragma unroll
    for (int kk = 0; kk < 8; kk++)
        wgmma_rs_n128_tb(o, p[4 * kk], p[4 * kk + 1], p[4 * kk + 2], p[4 * kk + 3], dv + kk * 128, kk != 0 || accumulate);
    wgmma_commit();
}
__device__ __forceinline__ void row_max(const float (&s)[64], float& x0, float& x1) {
    float z0 = fmaxf(s[0], s[1]), z1 = fmaxf(s[2], s[3]);
    x0 = fmaxf(s[4], s[5]); x1 = fmaxf(s[6], s[7]);
#pragma unroll
    for (int j = 2; j < 16; j += 2) {
        z0 = fmaxf(z0, fmaxf(s[4 * j], s[4 * j + 1]));
        z1 = fmaxf(z1, fmaxf(s[4 * j + 2], s[4 * j + 3]));
        x0 = fmaxf(x0, fmaxf(s[4 * j + 4], s[4 * j + 5]));
        x1 = fmaxf(x1, fmaxf(s[4 * j + 6], s[4 * j + 7]));
    }
    x0 = quad_max(fmaxf(x0, z0)); x1 = quad_max(fmaxf(x1, z1));
}
__device__ __forceinline__ void exp_pack(uint32_t (&p)[32], const float (&s)[64], float& r0, float& r1) {
#pragma unroll
    for (int j = 0; j < 16; j++) {
        const float e0 = ex2(s[4 * j]), e1 = ex2(s[4 * j + 1]), e2 = ex2(s[4 * j + 2]), e3 = ex2(s[4 * j + 3]);
        if (j == 0) { r0 = e0 + e1; r1 = e2 + e3; }
        else { r0 += e0 + e1; r1 += e2 + e3; }
        p[2 * j] = pack_bf16(e0, e1);
        p[2 * j + 1] = pack_bf16(e2, e3);
    }
}
__device__ __forceinline__ void shift_rows(float (&s)[64], float d0, float d1) {
#pragma unroll
    for (int j = 0; j < 16; j++) { s[4 * j] -= d0; s[4 * j + 1] -= d0; s[4 * j + 2] -= d1; s[4 * j + 3] -= d1; }
}
constexpr float MASKED = -3e38f;
template <int J0>
__device__ __forceinline__ void mask_triangle(float (&s)[64], float thr) {
#pragma unroll
    for (int j = 0; j < 16; j++) {
        const float m = __saturatef((float)(8 * (j >> 1) + (j & 1)) - thr);
        const int i = 4 * (J0 + (j >> 1)) + (j & 1);
        s[i] = fmaf(m, MASKED, s[i]);
        if (j < 14) s[i + 6] = fmaf(m, MASKED, s[i + 6]);
    }
}
__device__ __forceinline__ void causal_mask(float (&s)[64], float thr, int wg) {
    asm volatile("" : "+f"(thr));
    if (wg == 0) {
        mask_triangle<0>(s, thr);
#pragma unroll
        for (int j = 32; j < 64; j++) s[j] += MASKED;
    } else {
        mask_triangle<8>(s, thr);
    }
}

__global__ void __cluster_dims__(2, 1, 1) __launch_bounds__(384, 1) fused_kernel(const __grid_constant__ Params prm) {
    extern __shared__ __align__(1024) uint8_t smem[];
    const uint32_t sb = smem_u32(smem), bars = sb + SM_BARS;
    const int warp = __shfl_sync(0xffffffffu, threadIdx.x >> 5, 0), lane = threadIdx.x & 31;

    const uint32_t rank = cluster_rank();
    const uint32_t bars0 = map_cta(bars, 0), bars_peer = map_cta(bars, rank ^ 1);

    auto plan_index = [&]() -> uint32_t {
        uint32_t p = blockIdx.x >> 1;
        asm volatile("" : "+r"(p));
        const uint32_t r = (p - 36) * 37 >> 8;
        return p < 4 ? 60 + p : p < 36 ? (p - 4 & 7) * 8 + (p - 4 >> 3) : p < 64 ? (p - 36 - 7 * r) * 8 + 4 + r : p;
    };
    auto first_item = [&]() -> int {
        const uint32_t pair = plan_index();
        const uint32_t slot = pair & 7, c = slot * 11 >> 5;
        return pair < 64 ? T_B << 13 | (4 * slot - 11 * c) << 4 | (2 * (pair >> 3) + rank) : T_K << 13 | (8 * slot + rank);
    };
    if (warp == 0) {
        if (elect_one()) {
            for (int k = 0; k < 4; k++) mbar_init(bars + B_GFULL + 8 * k, 1);
            asm volatile("fence.mbarrier_init.release.cluster;" ::: "memory");
            fence_proxy_async_smem();
        }
        __syncwarp();
        const int first_it = __shfl_sync(0xffffffffu, first_item(), 0);
        asm volatile("barrier.cluster.arrive.relaxed.aligned;" ::: "memory");
        const CUtensorMap* ma = &prm.m[item_type(first_it) == T_K ? M_C : M_X];
        const CUtensorMap* mb = &prm.m[M_WQ + item_type(first_it)];
#pragma unroll
        for (int k = 0; k < 2; k++) {
            const uint32_t dst = sb + k * GST_BYTES, fb = bars + B_GFULL + 8 * k;
            warp_expect_tx(fb, GST_BYTES);
            warp_tma_load(dst + 16384, mb, fb, 0, k * 64, item_col(first_it) * 4, true);
            warp_tma_load(dst, ma, fb, k * 64, item_row(first_it) * 128, 0, false);
            warp_tma_load(dst + 32768, mb, fb, 0, k * 64, item_col(first_it) * 4 + 2, true);
        }
    }
    if (threadIdx.x == 32) {
        for (int i = 0; i < 4; i++) mbar_init(bars + B_GEMPTY + 8 * i, 16);
        for (int i = 0; i < 6; i++) { mbar_init(bars + B_AFULL + 8 * i, 1); mbar_init(bars + B_AEMPTY + 8 * i, i < 2 ? 8 : 16); }
        for (int i = 0; i < 4; i++) { mbar_init(bars + B_SFULL + 8 * i, 4); mbar_init(bars + B_SEMPTY + 8 * i, 1); }
        for (int i = 0; i < QDEPTH; i++) { mbar_init(bars + B_IFULL + 8 * i, 1); mbar_init(bars + B_IEMPTY + 8 * i, 23); }
        mbar_init(bars + B_WANT, 2); mbar_init(bars + B_MEET, 1); mbar_init(bars + B_XFREE, 1);
        for (int i = 0; i < 4; i++) mbar_init(bars + B_HALF + 8 * i, 1);
        mbar_init(bars + B_ALT, 4); mbar_init(bars + B_ALT + 8, 4); mbar_init(bars + B_QFREE, 2);
        asm volatile("st.shared.u64 [%0], 0;" :: "r"(bars + SM_ORDY) : "memory");
        asm volatile("fence.mbarrier_init.release.cluster;\nfence.acq_rel.cta;" ::: "memory");
    }
    __syncwarp();
    if (warp != 0) asm volatile("barrier.cluster.arrive.relaxed.aligned;" ::: "memory");
    asm volatile("barrier.cluster.wait.acquire.aligned;" ::: "memory");

    uint32_t qn = 0;
    auto next_item = [&](bool releaser, bool bounded = true) -> int {
        const uint32_t slot = qn % QDEPTH;
        if (bounded) mbar_wait(bars + B_IFULL + 8 * slot, (qn / QDEPTH) & 1);
        else mbar_spin(bars + B_IFULL + 8 * slot, (qn / QDEPTH) & 1);
        uint32_t it;
        asm volatile("ld.shared.u32 %0, [%1];" : "=r"(it) : "r"(bars + SM_QUEUE + 4 * slot) : "memory");
        mbar_arrive_cluster_if(releaser, bars0 + B_IEMPTY + 8 * slot);
        qn++;
        return it;
    };

    if (warp < 4) {
        reg_dec<40>();
        if (warp == 0) {
            {
                uint32_t gph = 1;
                const uint32_t prank = __shfl_sync(0xffffffffu, rank, 0);
                auto request = [&]() { mbar_arrive_cluster_if(lane == 0, bars0 + B_WANT); };
                auto take_item = [&]() -> int { return __shfl_sync(0xffffffffu, next_item(lane == 0), 0); };
                auto inputs_seen = [&](uint32_t word, unsigned& n) -> uint32_t {
                    uint32_t v;
                    spin_guard(n);
                    asm volatile("ld.acquire.cta.shared.u32 %0, [%1];" : "=r"(v) : "r"(bars + SM_ORDY + 4 * word) : "memory");
                    return __shfl_sync(0xffffffffu, v, 0);
                };
                uint32_t oneed = 0;
                auto wait_inputs = [&](int it) {
                    if (it & ITEM_READY) return;
                    oneed += 256;
                    for (unsigned n = 0; inputs_seen(1, n) < oneed;) {}
                };
                int nxt = first_item(), ring = -1, rot = 0;
                for (int k0 = 2; item_type(nxt) <= T_LOCAL; k0 = 0) {
                    const int type = item_type(nxt), m = item_row(nxt), c = item_col(nxt);
                    if (type == T_LOCAL) {
                        wait_inputs(nxt);
                        request();
#pragma unroll 1
                        for (uint32_t st = 0; st < 4; st++) {
                            mbar_wait(bars + B_GEMPTY + 8 * st, gph);
                            const uint32_t dst = sb + st * GST_BYTES, fb = bars + B_GFULL + 8 * st;
                            warp_expect_tx(fb, st == 0 ? 32768 + 512 : st == 3 ? 0 : 4 * LOC_PLANE);
                            if (st == 3) break;
                            if (st == 0) warp_bulk_load(dst + 4 * LOC_PLANE, &g_gate[m * 128], 512, fb);
#pragma unroll 1
                            for (int i = 0; i < 4; i++)
                                warp_tma_load(dst + i * LOC_PLANE, &prm.m[st ? M_SCR_LOC : M_SCR_LOQ], fb, i * 64, m * 64 - (st ? 8 : 0), G_B + 8 * st + c, true);
                        }
                        gph ^= 1;
                        ring = -1;
                    } else {
                        const int nk = type == T_K || type == T_V ? 8 : 16, kept = ring == m + 16 * nk ? 4 : 0;
                        ring = m + 16 * nk;
                        rot = kept ? rot - 4 : 0;
                        const CUtensorMap* ma = &prm.m[nk == 8 ? M_C : M_X];
                        const CUtensorMap* mb = &prm.m[M_WQ + type];
#pragma unroll 1
                        for (int k = k0; k < nk; k++) {
                            if (k == nk - 3) request();
                            const uint32_t st = k & 3, dst = sb + st * GST_BYTES, fb = bars + B_GFULL + 8 * st;
                            const int kc = ((k + rot) & (nk - 1)) * 64;
                            mbar_wait(bars + B_GEMPTY + 8 * st, gph);
                            warp_expect_tx(fb, k < kept ? 32768 : GST_BYTES);
                            if (k >= kept) warp_tma_load(dst, ma, fb, kc, m * 128, 0, c == 15 && type != T_K);
                            warp_tma_load_pair(dst + 16384 + prank * 16384, mb, fb, 0, kc, c * 4 + 2 * prank, true);
                            if (st == 3) gph ^= 1;
                        }
                    }
                    nxt = take_item();
                }
                uint32_t kv = 0, kvph = 1;
                uint32_t qc = 0;
                auto a_parity = [&](uint32_t b) { return b < 2 ? (((qc + 1 - b) >> 1) & 1) ^ 1 : kvph ^ (b - 2 < kv); };
                const CUtensorMap* tile_map = &prm.m[M_SCR_LD];
                asm volatile("" : "+l"(tile_map));
                {
                    bool need_g = true, more = true;
                    int pv_grp = -1, pv_row = 0;
                    int pv_shared = 0;
                    bool peer_longer = false;
                    int m = 0, c = 0, asc = 0, nu = 0, uend = 0, ureq = -1, ufetch = 0;
#pragma unroll 1
                    for (int u = 0;; u++) {
                        if (u == ufetch) {
                            if (qc) nxt = take_item();
                            if (item_type(nxt) == T_ATTN) {
                                wait_inputs(nxt);
                                const uint32_t b = qc & 1, dst = sb + b * 32768, fb = bars + B_AFULL + 8 * b, row = item_row(nxt) * 128;
                                mbar_wait(bars + (qc == 0 ? B_GEMPTY : qc == 1 ? B_QFREE : B_AEMPTY + 8 * b), qc == 0 ? gph : qc == 1 ? 0 : a_parity(b));
                                warp_expect_tx(fb, 32768 + 512);
                                warp_tma_load(dst, tile_map, fb, 0, row, G_Q + item_col(nxt), false);
                                warp_tma_load(dst + 16384, tile_map, fb, 64, row, G_Q + item_col(nxt), false);
                                warp_bulk_load(bars + SM_GATE + b * 512, &g_gate[row], 512, fb);
                                qc++;
                            }
                        }
                        if (u == uend) {
                            if (!more) break;
                            more = item_type(nxt) == T_ATTN;
                            m = item_row(nxt); c = item_col(nxt); asc = item_asc(nxt);
                            nu = more ? 2 * m + 2 : 0;
                            uend = nu + ((more ? m < 2 : pv_grp >= 0) ? 3 : 0);
                            ureq = 2 * max(m - 2 - (asc & m), 0);
                            ufetch = !more ? -1 : m ? 2 * m : uend;
                            u = -1;
                            continue;
                        }
                        int grp = pv_grp, row = pv_row;
                        int shared = pv_shared;
                        if (u >= nu) {
                            if (u == nu + 1) pv_grp = -1;
                            else if (peer_longer) { grp = -1; shared = 0; }
                            else continue;
                        } else {
                            const int j = asc ? u >> 1 : m - (u >> 1);
                            if (u & 1) {
                                pv_grp = G_V + c; pv_row = j * 128; pv_shared = (m | 1) - j;
                                peer_longer = asc & ~m & 1;
                                if (u == nu - 1 && (m & 1) && item_type(nxt) == T_END) mbar_arrive_cluster_n_if(lane == 0, bars0 + B_WANT, 2);
                                if (grp < 0) continue;
                            } else {
                                if (u == ureq) request();
                                grp = G_K + c; row = j * 128; shared = (m | 1) - j;
                            }
                        }
                        uint32_t fb = bars + B_AFULL + 16 + 8 * kv, mine = sb + SM_KV + kv * 32768 + prank * 16384;
                        int c_mine = prank * 64;
                        asm volatile("" : "+r"(mine), "+r"(fb), "+r"(row), "+r"(grp), "+r"(c_mine));
                        mbar_wait(need_g ? bars + B_GEMPTY + 8 + 8 * kv : fb + B_AEMPTY - B_AFULL, need_g ? gph : kvph);
                        warp_expect_tx(fb, grp < 0 ? 0 : 32768);
                        if (shared) {
                            warp_tma_load_pair(mine, tile_map, fb, c_mine, row, grp, shared == 1);
                        } else if (grp >= 0) {
                            warp_tma_load(mine, tile_map, fb, c_mine, row, grp, true);
                            warp_tma_load(mine + 16384 - prank * 32768, tile_map, fb, 64 - c_mine, row, grp, true);
                        } else {
                            mbar_arrive_cluster_n_if(lane < 2, map_cta(fb, lane & 1) + B_AEMPTY - B_AFULL, 8);
                        }
                        if (kv == 2) need_g = false;
                        if (++kv == 4) { kv = 0; kvph ^= 1; }
                    }
                }
                if (!qc) request();
                const int it = take_item();
                int nk = 0;
                if (item_type(it) == T_OUT) {
                    const int m = item_row(it), c = item_col(it), half = c & 1;
                    nk = 80;
                    for (unsigned n = 0; (inputs_seen(1, n) & 255) != 255;) {}
                    mbar_wait(bars + B_GEMPTY + 24, gph);
                    mbar_wait(bars + B_QFREE, 0);
                    mbar_wait(bars + B_AEMPTY + 8 * (qc & 1), a_parity(qc & 1));
#pragma unroll 1
                    for (uint32_t k = 0; k < 4; k++) {
                        const uint32_t sa = prm.ostep[half ? WIDE - 1 - k : k], dst = sb + k * GST_BYTES, fb = bars + B_GFULL + 8 * k;
                        const uint32_t b0 = k ? 1 + k : ~qc & 1, b1 = 2 + k - (k == 1);
                        mbar_wait(bars + B_AEMPTY + 8 * b0, a_parity(b0));
                        mbar_arrive_cluster_if(lane == 0 && !k, bars_peer + B_XFREE);
                        warp_expect_tx(fb, GST_BYTES);
                        warp_tma_load(dst, tile_map, fb, (sa & 1) * 64, m * 128, G_LOC - 32 + (sa >> 1), true);
                        mbar_wait(bars + (k ? B_AEMPTY + 8 * b1 : B_XFREE), k ? kvph ^ (b1 - 2 < kv) : 0);
                        warp_tma_load_pair(dst + 16384 + prank * 16384, &prm.m[M_WOB], fb, 0, (sa & 63) * 64, (c >> 1) * 4 + 2 * (half ^ prank), false);
                    }
                    gph ^= 1;
                    uint32_t seen = 0;
                    for (int k = 4; k < nk; k++) {
                        if (k == K_SPLIT) nk = 2 * TRIPLES + (take_item() & 127);
                        const int kn = k + 2 * TRIPLES - nk, first = kn >= 0 && !(kn & 1);
                        const int s = kn >= 0 ? WIDE + (3 * kn + 1) / 2 : half ? WIDE - 1 - k : k;
                        const uint32_t sa = prm.ostep[s], sa2 = prm.ostep[s + first], sw = prm.ostep[s - (kn >= 0 && !first ? prank : 0)];
                        const uint32_t need = 1u << (sa >> 1 & 31) | 1u << (sa2 >> 1 & 31);
                        for (unsigned n = 0; sa < 64 && (need & ~seen);) seen = inputs_seen(0, n);
                        const uint32_t st = k & 3;
                        uint32_t dst = sb + st * GST_BYTES, fb = bars + B_GFULL + 8 * st;
                        uint32_t dstb = dst + 16384 + (first ? 0 : prank * 16384), skipb = first && (kn >> 1 & 1) != prank;
                        int a0 = (sa & 1) * 64, a1 = m * 128, a2 = (sa >> 1) + (sa < 64 ? G_CTX : G_LOC - 32);
                        int b1 = (sw & 63) * 64, b2 = (c >> 1) * 4 + 2 * (kn >= 0 ? half : half ^ prank);
                        const CUtensorMap* mb = &prm.m[sw >= 64 ? M_WOB : M_WO];
                        asm volatile("" : "+r"(dst), "+r"(fb), "+r"(dstb), "+r"(skipb), "+r"(a0), "+r"(a1), "+r"(a2), "+r"(b1), "+r"(b2), "+l"(mb));
                        mbar_wait(bars + B_GEMPTY + 8 * st, gph);
                        warp_expect_tx(fb, GST_BYTES);
                        warp_tma_load(dst, tile_map, fb, a0, a1, a2, true);
                        if (!skipb) warp_tma_load_pair(dstb, mb, fb, 0, b1, b2, false);
                        if (first) warp_tma_load(dst + 32768, tile_map, fb, (sa2 & 1) * 64, a1, G_CTX + (sa2 >> 1), true);
                        if (k < K_SPLIT && lane == 0 && !prank)
                            asm volatile("st.relaxed.gpu.global.u32 [%0], %1;" :: "l"(&g_sync.step[0][0] + m * 4 + c), "r"(k) : "memory");
                        mbar_arrive_if(k == K_MEET && lane == 0, bars + B_MEET);
                        if ((uint32_t)(k - K_FETCH) < (3 * TRIPLES + 1) / 2) {
                            const uint32_t g = prm.ostep[79 - 2 * (k - K_FETCH)] >> 1;
                            warp_prefetch((const char*)g_scr + (uint32_t)((G_CTX + g) * (SEQ * 256) + m * 32768 + c * 4096), 4096);
                            warp_prefetch(prm.wo + (uint32_t)(g * 262144 + (m * 8 + c) * 2048), 2048);
                        }
                        if (st == 3) gph ^= 1;
                    }
                    for (unsigned n = 0; ~inputs_seen(0, n);) {}
                }
#pragma unroll 1
                for (uint32_t st = 0; st < 4; st++) { mbar_wait(bars + B_GEMPTY + 8 * st, gph ^ (st < (nk & 3))); mbar_wait(bars + B_AEMPTY + 16 + 8 * st, a_parity(2 + st)); }
                unsigned left = 0;
                if (lane == 0) asm volatile("atom.relaxed.gpu.global.add.u32 %0, [%1], 1;" : "=r"(left) : "l"(&g_sync.done) : "memory");
                if (__shfl_sync(0xffffffffu, left, 0) == NCTA - 1)
#pragma unroll 1
                    for (uint32_t i = lane * 8; i < sizeof(Sync); i += 256) *(unsigned long long*)((char*)&g_sync + i) = 0;
            }
        } else if (warp <= 2) {
            if (blockIdx.x < SEQ / 16) {
                const uint32_t r0 = 16 * blockIdx.x + 8 * (warp - 1), gbuf = bars + SM_GATE + 4 * (r0 & 15);
                float z[4];
                mbar_wait(bars + B_GFULL + 24, 0);
#pragma unroll 1
                for (uint32_t i = 0; i < 8; i++) {
                    const uint32_t off = (i & 3) * 512 + lane * 16;
                    const uint4* xp = (const uint4*)((const char*)prm.x + ((r0 + (i & 4)) * 2048 + off));
                    const uint4 wv = __ldg((const uint4*)((const char*)prm.gate_w + off));
                    uint4 xv[4];
#pragma unroll
                    for (int r = 0; r < 4; r++) { xv[r] = __ldg(xp + r * 128); if (!(i & 3)) z[r] = 0.f; }
                    const uint32_t ws[4] = {wv.x, wv.y, wv.z, wv.w};
#pragma unroll
                    for (int e = 0; e < 4; e++)
#pragma unroll
                        for (int r = 0; r < 4; r++) {
                            const uint32_t xs = e == 0 ? xv[r].x : e == 1 ? xv[r].y : e == 2 ? xv[r].z : xv[r].w;
                            z[r] = fmaf(__uint_as_float(xs << 16), __uint_as_float(ws[e] << 16), z[r]);
                            z[r] = fmaf(__uint_as_float(xs & 0xffff0000u), __uint_as_float(ws[e] & 0xffff0000u), z[r]);
                        }
                    if ((i & 3) == 3) {
#pragma unroll
                        for (int o = 16; o > 0; o >>= 1)
#pragma unroll
                            for (int r = 0; r < 4; r++) z[r] += __shfl_xor_sync(0xffffffffu, z[r], o);
                        const float zr = lane & 2 ? (lane & 1 ? z[3] : z[2]) : (lane & 1 ? z[1] : z[0]);
                        asm volatile("st.shared.f32 [%0], %1;" :: "r"(gbuf + 4 * ((i & 4) + (lane & 3))), "f"(1.f / (1.f + __expf(-zr))) : "memory");
                    }
                }
                fence_proxy_async_smem();
                __syncwarp();
                warp_bulk_store((char*)g_gate + 4 * r0, gbuf, 32);
                bulk_commit();
                bulk_wait<0>();
                __syncwarp();
                if (lane == 0) red_add(&g_sync.count[3], 1);
            }
            __syncwarp();
            {
                const int w = warp - 1;
                uint32_t sph = 0, nann = 0;
                int unsent = 0, nunsent = 0;
                bool urgent = false;
                auto announce = [&]() {
                    if (!urgent) return;
                    bulk_wait<0>();
                    __syncwarp();
                    const uint32_t hb = bars + B_HALF + 8 * (nann & 3);
                    if (w == 0) {
                        mbar_arrive_if(lane == 0, hb);
                    } else {
                        mbar_wait(hb, (nann >> 2) & 1);
                        const uint32_t type = item_type(unsent), m = item_row(unsent), c = item_col(unsent);
                        const uint32_t word = type < T_B ? c >> 3 : type == T_B ? 2 : offsetof(Sync, ctx) / 8 + m;
                        const uint32_t bit = type < T_B ? 8 * (c & 7) : type == T_B ? 8 * (c & 3) : type == T_LOCAL ? 32 + c : c;
                        if (lane < nunsent) red_add((unsigned long long*)((char*)&g_sync + 8 * word), 1ull << bit);
                        __syncwarp();
                    }
                    nann++;
                    nunsent = 0; urgent = false;
                };
                int held = first_item(), it;
                bool qfree = false;
                do {
                    if (!__all_sync(0xffffffffu, mbar_test(bars + B_IFULL + 8 * (qn % QDEPTH), (qn / QDEPTH) & 1))) announce();
                    it = __shfl_sync(0xffffffffu, next_item(lane == 0), 0);
                    const int itype = item_type(it);
                    const bool keep_held = itype == T_LOCAL;
                    if (itype >= T_ATTN && held < 0) {
                        urgent = nunsent;
                        mbar_arrive_if(lane == 0 && !qfree, bars + B_QFREE);
                        qfree = true;
                    }
#pragma unroll 1
                    for (int pass = held < 0 || keep_held; pass < 2; pass++) {
                        if (pass && (itype < T_OUT || itype == T_END)) break;
                        const int cur = pass ? it : held, type = item_type(cur), m = item_row(cur), c = item_col(cur);
                        const bool local = type == T_LOCAL;
                        const int grp = pass ? (local ? G_LOC : G_CTX) + c : type * 32 + 2 * c;
#pragma unroll 1
                        for (int i = 0; i < 4 - 2 * pass; i++) {
                            const int b = i & 1;
                            const bool alt = i >= 2 && itype >= T_ATTN;
                            const uint32_t full = bars + (alt ? B_ALT + 8 * w : B_SFULL + 16 * w + 8 * b), par = alt ? 0 : sph;
                            if (i == 3 - 2 * pass || !__all_sync(0xffffffffu, mbar_test(full, par))) announce();
                            mbar_wait(full, par);
                            fence_proxy_async_smem();
                            warp_tma_store(&prm.m[local ? M_SCR_LOQ : M_SCR_ST], sb + (alt ? 32768 : SM_STAGING) + w * 16384 + b * 8192,
                                         local ? b * 128 + w * 64 : b * 64, local ? m * 64 : m * 128 + w * 64, grp + (i >> 1), local || (type < T_B && c < FIRST_PAIR));
                            bulk_commit();
                            if (pass > b) continue;
                            bulk_wait_read<0>();
                            __syncwarp();
                            mbar_arrive_if(lane <= pass && !alt, bars + B_SEMPTY + 16 * w + 8 * (b - lane));
                            sph ^= b & !alt;
                        }
                        mbar_arrive_if(lane == 0 && !qfree && itype >= T_ATTN, bars + B_QFREE);
                        qfree |= itype >= T_ATTN;
                        if (lane == nunsent) unsent = cur;
                        nunsent++;
                        urgent = nunsent == 32 || !local;
                    }
                    if (!keep_held) held = itype < T_OUT ? it : -1;
                } while (item_type(it) != T_END);
                announce();
                it = __shfl_sync(0xffffffffu, next_item(lane == 0), 0);
                if (item_type(it) == T_OUT) {
                    if (w) {
                        mbar_wait(bars + B_MEET, 0);
                        asm volatile("fence.proxy.async.global;\nfence.acq_rel.gpu;" ::: "memory");
                        mbar_arrive_cluster_if(lane == 0, bars0 + B_WANT);
                    }
                    next_item(lane == 0);
#pragma unroll 1
                    for (int i = 0; i < 4; i++) {
                        const int b = i & 1;
                        mbar_wait(bars + B_SFULL + 16 * w + 8 * b, sph ^ (i >> 1));
                        fence_proxy_async_smem();
                        warp_tma_add(&prm.m[M_OUT], sb + SM_STAGING + w * 16384 + b * 8192, (item_col(it) ^ (i < 2)) * 128 + b * 64, item_row(it) * 128 + w * 64, 0);
                        bulk_commit();
                        if (b) {
                            bulk_wait_read<0>();
                            __syncwarp();
                            mbar_arrive_if(lane < 2, bars + B_SEMPTY + 16 * w + 8 * lane);
                        }
                    }
                }
            }
        } else {
            if (elect_one()) {
                uint32_t ordy = 0;
                unsigned long long cnt_lo = 0, cnt_hi = 0;
                int late = 0;
                auto refresh = [&]() {
                    if (!late && cnt_lo == 0x30303030 && cnt_hi == SEQ / 8) late = 1;
                    asm volatile("ld.acquire.gpu.global.v2.u64 {%0, %1}, [%2];" : "=l"(cnt_lo), "=l"(cnt_hi) : "l"(late ? &g_sync.count[0] : &g_sync.count[2]) : "memory");
                };
                auto inputs_ready = [&](int it) -> bool {
                    const int c = item_col(it);
                    if (item_type(it) == T_ATTN) return late && ((c < 16 ? cnt_lo : cnt_hi) >> (4 * (c & 14)) & 255) == 48;
                    return late || (cnt_hi == SEQ / 8 && (cnt_lo >> (4 * (c & 6)) & 255) == 48);
                };
                auto publish = [&](int it, int step) {
                    const uint32_t slot = qn % QDEPTH;
                    mbar_wait(bars + B_IEMPTY + 8 * slot, ((qn / QDEPTH) & 1) ^ 1);
                    for (uint32_t r = 0; r < 2; r++) {
                        const uint32_t rb = map_cta(bars, r);
                        asm volatile("mbarrier.arrive.expect_tx.shared::cluster.b64 _, [%0], 4;" :: "r"(rb + B_IFULL + 8 * slot) : "memory");
                        asm volatile("st.async.shared::cluster.mbarrier::complete_tx::bytes.u32 [%0], %1, [%2];"
                                     :: "r"(rb + SM_QUEUE + 4 * slot), "r"(it + r * step), "r"(rb + B_IFULL + 8 * slot) : "memory");
                    }
                    qn++;
                };
                int asc = 1;
                int it;
                do {
                    if (rank == 0) {
                        mbar_wait(bars + B_WANT, qn & 1);
                        const uint32_t pair = plan_index();
                        int pit = prm.plan[pair < 64 ? pair & 7 : pair - 56][min(qn + 1, 15u)];
                        unsigned i;
                        const bool planned = item_type(pit) != T_END;
                        if (!planned) asm volatile("atom.relaxed.gpu.global.add.u32 %0, [%1], 1;" : "=r"(i) : "l"(&g_sync.next) : "memory");
                        if (cnt_lo != 0x3030303030303030ull || cnt_hi != cnt_lo) refresh();
                        if (planned) pit += (pair >> 3 & 7) << (item_type(pit) == T_LOCAL);
                        else if (i < NITEMS) pit = prm.items[i];
                        const int type = item_type(pit);
                        int step = type == T_LOCAL ? 16 : 1;
                        it = pit + (pit & (step == 1 ? 15 : 0x1f0));
                        if (type == T_ATTN) {
                            if (!asc) { it += 1; step = -1; }
                            it |= asc << 9;
                        }
                        asc = type != T_ATTN || item_row(pit) == 0 || !asc;
                        if (inputs_ready(it)) it |= ITEM_READY;
                        publish(it, step);
                    } else {
                        it = next_item(true);
                    }
                    if ((item_type(it) == T_ATTN || item_type(it) == T_LOCAL) && !(it & ITEM_READY)) {
                        unsigned n = 0;
                        while (!inputs_ready(it)) { refresh(); spin_guard(n); }
                        asm volatile("st.release.cta.shared.u32 [%0], %1;" :: "r"(bars + SM_ORDY + 4), "r"(ordy += 256) : "memory");
                    }
                } while (item_type(it) != T_END);
                if (rank == 0) {
                    mbar_wait(bars + B_WANT, qn & 1);
                    const unsigned i = atomicAdd(&g_sync.next_out, 1u), t = i < 32 ? 31 - i : i - 32;
                    it = i < 64 ? T_OUT << 13 | ((t & 3) * 2 + (i >> 5)) << 4 | (t >> 2) * 2 : T_END << 13;
                    publish(it, 1);
                } else {
                    it = next_item(true);
                }
                if (item_type(it) == T_OUT) {
                    const uint32_t m = item_row(it), half = item_col(it) & 1, tile = m * 2 + (item_col(it) >> 1);
                    unsigned* split = (unsigned*)((char*)g_sync.split + 4 * tile);
                    unsigned long long rdy = 0;
                    int state = rank ? 2 : 0;
                    for (unsigned n = 0; rdy != 0xffffffffffull || state < 2; spin_guard(n)) {
                        if (rdy != 0xffffffffffull) {
                            rdy = ld_acquire((const unsigned long long*)((char*)g_sync.ctx + 8 * m));
                            asm volatile("st.release.cta.shared.u64 [%0], %1;" :: "r"(bars + SM_ORDY), "l"(rdy) : "memory");
                        }
                        unsigned steps = 0;
                        if (state == 1) {
                            steps = ld_acquire(split);
                        } else if (state == 0 && mbar_test(bars + B_WANT, qn & 1)) {
                            state = 1;
                            unsigned seen;
                            asm volatile("atom.acq_rel.gpu.global.exch.b32 %0, [%1], 1;" : "=r"(seen) : "l"(split) : "memory");
                            if (seen) {
                                const unsigned long long v = ld_acquire((const unsigned long long*)((char*)g_sync.step + 8 * tile));
                                const int d = (int)(v >> 32) - (int)v;
                                steps = (WIDE + min(max(half ? d : -d, -12), 12)) >> 1;
                                atomicExch(split, WIDE - steps);
                            }
                        }
                        if (steps > 1) { publish(T_END << 13 | steps, 0); state = 2; }
                    }
                    if (rank) next_item(true);
                }
                #pragma unroll 1
                for (uint32_t n = qn; n < qn + QDEPTH && rank == 0; n++) mbar_wait(bars + B_IEMPTY + 8 * (n % QDEPTH), ((n / QDEPTH) & 1) ^ 1);
            }
        }
    } else {
        reg_inc<232>();
        const int wg = (warp >> 2) - 1, wq = warp & 3;
        uint32_t gph = 0;
        uint32_t kvn = 0;
        const uint32_t dA = make_desc(sb + wg * 8192, 16);
        uint32_t ti = 0;
        uint32_t sph = 1;
        const uint32_t stg = sb + SM_STAGING + wg * 16384;
        const uint32_t stg_lane = stg + (wq * 16 + (lane & 15)) * 128 + (((lane >> 4) ^ (lane & 7)) << 4);
        auto write_blocks = [&](auto n, uint32_t off, const uint32_t* v) {
            uint32_t a = stg_lane;
            asm volatile("" : "+r"(a));
            a += off;
#pragma unroll
            for (int j = 0; j < decltype(n)::value; j++)
                stmatrix_x4((a ^ (32 * (j & 3))) + (j >> 2) * 8192, v[4 * j], v[4 * j + 1], v[4 * j + 2], v[4 * j + 3]);
        };
        auto release = [&](uint32_t bar) { mbar_arrive_if(lane == 0, bars + bar); };
        const uint32_t bars_lane = map_cta(bars, lane & 1);
        auto release_stage = [&](uint32_t st) { mbar_arrive_cluster_if(lane < 2, bars_lane + B_GEMPTY + 8 * st); };
        auto take_item = [&]() -> int {
            return __shfl_sync(0xffffffffu, next_item(lane == 0, false), 0);
        };
        auto stage_acquire = [&](int b) { mbar_spin(bars + B_SEMPTY + 16 * wg + 8 * b, sph); };
        auto stage_publish = [&](int b) {
            __syncwarp();
            release(B_SFULL + 16 * wg + 8 * b);
        };
        auto stage_chunk = [&](int b, const uint32_t* v) {
            stage_acquire(b);
            write_blocks(std::integral_constant<int, 4>(), b * 8192, v);
            stage_publish(b);
            if (b) sph ^= 1;
        };
        auto publish_pair = [&]() {
            __syncwarp();
            mbar_arrive_if(lane < 2, bars + B_SFULL + 16 * wg + 8 * lane);
            sph ^= 1;
        };
        auto gemm_step = [&](float (&acc)[128], uint32_t dB, int& k) {
            const uint32_t st = k & 3;
            wgmma_wait<0>();
            release_stage((k - 1) & 3);
            mbar_spin(bars + B_GFULL + 8 * st, gph);
            const uint64_t da = full_desc(dA + st * (GST_BYTES >> 4)), db = full_desc(dB + st * (GST_BYTES >> 4));
            wgmma_fence();
#pragma unroll
            for (int kk = 0; kk < 4; kk++) wgmma_ss_n256_tb(acc, da + 2 * kk, db + 128 * kk, 1);
            wgmma_commit();
            gph ^= st == 3;
            k++;
        };
        if (wg == 1) bar_arrive(1, 256);
        int it = first_item();
        float s[64];
        const uint32_t dK = make_desc(sb + SM_KV, 16);
        auto kv_wait = [&](uint32_t n) { mbar_spin(bars + B_AFULL + 16 + 8 * (n & 3), (n >> 2) & 1); };
        auto first_scores = [&](bool valid) {
            if (valid) { mbar_spin(bars + B_AFULL + 8 * (ti & 1), (ti >> 1) & 1); kv_wait(kvn); }
            bar_sync(1 + wg, 256);
            qk_gemm(s, dA + (ti & 1) * 2048, dK + (kvn & 3) * 2048);
            bar_arrive(2 - wg, 256);
        };
        bool issued;
        {
            {
                float acc[128];
                uint32_t pk[64];
                bool pending = false;
                int held = T_END;
                auto scale_q = [&](int j0, int n) {
                    if (held != T_Q) return;
#pragma unroll
                    for (int j = j0; j < j0 + n; j++)
                        asm("{\n.reg .b32 t;\nmul.rn.bf16x2 t, %0, %2;\nfma.rn.bf16x2 %0, %0, %1, t;\n}\n" : "+r"(pk[j]) : "r"(0x3e033e03u), "r"(0xb9d8b9d8u));
                };
                zero_regs(pk);
                const uint32_t dB = make_desc(sb + 16384, 8192);
                do {
                    const int type = item_type(it);
                    if (type == T_LOCAL) {
                        int ln = lane;
                        asm volatile("" : "+r"(ln));
                        const int g = ln >> 2, t = ln & 3, par = wq & 1;
                        const uint32_t hc = (wq >> 1) * 4, pl = sb + (par * 2 + wg) * LOC_PLANE;
                        const uint32_t a16 = (ln & 15) * 128 + (((hc + (ln >> 4)) ^ (ln & 7)) << 4), a8 = (ln & 7) * 128 + (((hc + (ln >> 3)) ^ (ln & 7)) << 4);
                        const bool first0 = 2 * t > g, first1 = 2 * t + 1 > g;
                        const uint32_t fmask = (first0 ? 0xffffu : 0u) | (first1 ? 0xffff0000u : 0u);
                        const bool edge = item_row(it) == 0;
                        uint32_t q[4][2][4], kf[9][4], vf[9][4];
                        float w[8];
                        mbar_spin(bars + B_GFULL, gph);
#pragma unroll
                        for (int u = 0; u < 4; u++) { ldsm_x4(q[u][0], pl + u * 2048 + a16); ldsm_x4(q[u][1], pl + u * 2048 + (a16 ^ 32)); }
#pragma unroll
                        for (int j = 0; j < 8; j++) w[j] = lds_f32(sb + 4 * LOC_PLANE + 4 * (2 * g + par) + 64 * j);
                        __syncwarp();
                        release_stage(0);
                        mbar_spin(bars + B_GFULL + 8, gph);
#pragma unroll
                        for (int n = 0; n < 9; n++) ldsm_x4(kf[n], pl + GST_BYTES + n * 1024 + a8);
                        __syncwarp();
                        release_stage(1);
                        float s[8][2];
#pragma unroll
                        for (int u = 0; u < 4; u++) {
                            float d[3][4];
#pragma unroll
                            for (int nt = 0; nt < 3; nt++) {
                                mma_k16_init(d[nt], q[u][0], kf[2 * u + nt][0], kf[2 * u + nt][1]);
                                mma_k16(d[nt], q[u][1], kf[2 * u + nt][2], kf[2 * u + nt][3]);
                            }
                            if (u == 0 && edge) { d[0][0] = -INFINITY; d[0][1] = -INFINITY; }
                            s[2 * u][0] = first0 ? d[0][0] : d[1][0]; s[2 * u][1] = first1 ? d[0][1] : d[1][1];
                            s[2 * u + 1][0] = first0 ? d[1][2] : d[2][2]; s[2 * u + 1][1] = first1 ? d[1][3] : d[2][3];
                        }
                        mbar_spin(bars + B_GFULL + 16, gph);
#pragma unroll
                        for (int u = 0; u < 4; u++) { ldsm_x4_t(vf[2 * u], pl + 2 * GST_BYTES + u * 2048 + a16); ldsm_x4_t(vf[2 * u + 1], pl + 2 * GST_BYTES + u * 2048 + (a16 ^ 32)); }
                        ldsm_x4_t(vf[8], pl + 2 * GST_BYTES + 8192 + a8);
                        __syncwarp();
                        release_stage(2);
                        float x[8];
#pragma unroll
                        for (int j = 0; j < 8; j++) x[j] = fmaxf(s[j][0], s[j][1]);
#pragma unroll
                        for (int o = 1; o < 4; o *= 2)
#pragma unroll
                            for (int j = 0; j < 8; j++) x[j] = fmaxf(x[j], __shfl_xor_sync(0xffffffffu, x[j], o));
#pragma unroll
                        for (int j = 0; j < 8; j++) {
                            const float n = x[j] * -LOC_SCALE;
                            s[j][0] = ex2(fmaf(s[j][0], LOC_SCALE, n)); s[j][1] = ex2(fmaf(s[j][1], LOC_SCALE, n));
                            x[j] = s[j][0] + s[j][1];
                        }
#pragma unroll
                        for (int o = 1; o < 4; o *= 2)
#pragma unroll
                            for (int j = 0; j < 8; j++) x[j] += __shfl_xor_sync(0xffffffffu, x[j], o);
                        mbar_spin(bars + B_GFULL + 24, gph);
                        release_stage(3);
                        it = take_item();
                        uint32_t ob[4][8];
#pragma unroll
                        for (int u = 0; u < 4; u++) {
                            const float r0 = rcp(x[2 * u]), r1 = rcp(x[2 * u + 1]), f0 = fmaf(-w[2 * u], r0, r0), f1 = fmaf(-w[2 * u + 1], r1, r1);
                            const uint32_t p0 = pack_bf16(s[2 * u][0] * f0, s[2 * u][1] * f0), p1 = pack_bf16(s[2 * u + 1][0] * f1, s[2 * u + 1][1] * f1);
                            const uint32_t pa[4] = {p0 & fmask, 0, p0 & ~fmask, p1 & fmask};
#pragma unroll
                            for (int c = 0; c < 4; c++) {
                                float ol[4];
                                mma_k16_init(ol, pa, vf[2 * u + (c >> 1)][2 * (c & 1)], vf[2 * u + (c >> 1)][2 * (c & 1) + 1]);
                                mma_k8(ol, 0, p1 & ~fmask, u < 3 ? vf[2 * u + 2 + (c >> 1)][2 * (c & 1)] : vf[8][c]);
                                ob[u][2 * c] = pack_bf16(ol[0], ol[1]);
                                ob[u][2 * c + 1] = pack_bf16(ol[2], ol[3]);
                            }
                        }
                        stage_acquire(0); stage_acquire(1);
#pragma unroll
                        for (int u = 0; u < 4; u++) {
                            stmatrix_x4(stg + par * 8192 + u * 2048 + a16, ob[u][0], ob[u][1], ob[u][2], ob[u][3]);
                            stmatrix_x4(stg + par * 8192 + u * 2048 + (a16 ^ 32), ob[u][4], ob[u][5], ob[u][6], ob[u][7]);
                        }
                        publish_pair();
                        bar_sync(4, 256);
                        gph ^= 1;
                        continue;
                    }
                    mbar_spin(bars + B_GFULL, gph);
                    bool more;
                    do {
                        wgmma_fence();
                        wgmma_ss_n256_tb_init(acc, full_desc(dA), full_desc(dB));
#pragma unroll
                        for (int kk = 1; kk < 4; kk++) wgmma_ss_n256_tb(acc, full_desc(dA) + 2 * kk, full_desc(dB) + 128 * kk, 1);
                        wgmma_commit();
                        const int nk = item_type(it) == T_K || item_type(it) == T_V ? 8 : 16;
                        int k = 1;
                        do {
                            if (pending) {
                                const int kf = k - 1 - wg;
                                if (kf == 0) { scale_q(0, 16); stage_chunk(0, pk); }
                                else if (kf == 1) { scale_q(16, 16); stage_chunk(1, pk + 16); }
                                else if (kf == 3) { scale_q(32, 16); stage_chunk(0, pk + 32); }
                                else if (kf == 4) { scale_q(48, 16); stage_chunk(1, pk + 48); }
                            }
                            gemm_step(acc, dB, k);
                        } while (k < nk);
                        held = item_type(it);
                        it = take_item();
                        more = item_type(it) < T_LOCAL;
                        if (more) mbar_spin(bars + B_GFULL, gph);
                        wgmma_wait<0>();
                        fence_regs(acc);
                        release_stage(3);
#pragma unroll
                        for (int j = 0; j < 64; j++) pk[j] = pack_bf16(acc[2 * j], acc[2 * j + 1]);
                        pending = true;
                    } while (more);
                } while (item_type(it) <= T_LOCAL);
                issued = item_type(it) == T_ATTN && (it & ITEM_READY);
                first_scores(issued);
                scale_q(0, 64);
                stage_acquire(0); stage_acquire(1);
                mbar_spin(bars + B_GEMPTY + 8, gph ^ 1);
                write_blocks(std::integral_constant<int, 8>(), 0, pk);
                write_blocks(std::integral_constant<int, 8>(), 32768 - SM_STAGING, pk + 32);
                publish_pair();
                release(B_ALT + 8 * wg);
                wgmma_wait<0>();
                fence_regs(s);
                if (item_type(it) == T_END) it = take_item();
            }
            while (item_type(it) == T_ATTN) {
                if (!issued) { first_scores(true); wgmma_wait<0>(); fence_regs(s); }
                issued = false;
                float o[64];
                uint32_t pa[32], pb[32];
                float n0 = 0.f, n1 = 0.f;
                int shifted = 0;
                float l0 = 0.f, l1 = 0.f, f0 = 0.f, f1 = 0.f, g0, g1;
                uint32_t has_pv = 0;
                int first = 0;
                int pending = 0;
                const uint32_t dV = make_desc(sb + SM_KV, 16384);
                const uint32_t lane_off = bars_lane - bars + B_AEMPTY - B_AFULL;
                int cur = it;
                uint32_t qoff = (ti & 1) * 2048;
                const int row = wg * 64 + wq * 16 + (lane >> 2);
                const float thr = (row & 63) - (lane & 3) * 2;
                int peek = -1;
                auto kv_release = [&](uint32_t n) { mbar_arrive_cluster_if(lane < 2, bars_lane + B_AEMPTY + 16 + 8 * (n & 3)); };
                struct Slot { uint32_t bar, par, off; } slot[4];
#pragma unroll
                for (uint32_t i = 0; i < 4; i++) {
                    const uint32_t n = kvn + 1 + (i ^ 2);
                    slot[i].bar = bars + B_AFULL + 16 + 8 * (n & 3); slot[i].par = (n >> 2) & 1; slot[i].off = (n & 3) * 2048;
                }
                kvn++;
                auto next_gate = [&]() {
                    g0 = lds_f32(bars + SM_GATE + (ti & 1) * 512 + 4 * row); g1 = lds_f32(bars + SM_GATE + (ti & 1) * 512 + 4 * row + 32);
                    ti++;
                };
                next_gate();
                auto scale_o = [&]() {
#pragma unroll
                    for (int j = 0; j < 16; j++) { o[4 * j] *= f0; o[4 * j + 1] *= f0; o[4 * j + 2] *= f1; o[4 * j + 3] *= f1; }
                };
                auto pack_o = [&](uint32_t (&v)[32]) {
#pragma unroll
                    for (int j = 0; j < 32; j++) v[j] = pack_bf16(o[2 * j], o[2 * j + 1]);
                };
                auto scales = [&]() { f0 = g0 * rcp(quad_sum(l0)); f1 = g1 * rcp(quad_sum(l1)); };
                auto issue = [&](auto even, uint32_t (&pin)[32], uint32_t (&pout)[32], bool fresh, bool last) {
                    constexpr bool EVEN = decltype(even)::value;
                    Slot& sk = slot[EVEN ? 0 : 2];
                    Slot& sv = slot[EVEN ? 1 : 3];
                    kvn += 2;
                    mbar_spin(sk.bar, sk.par);
                    bar_sync(1 + wg, 256);
                    qk_gemm(s, dA + qoff, dK + sk.off);
                    if (EVEN && fresh) {
                        scales();
                        next_gate();
                        n0 = 0.f; n1 = 0.f; l0 = 0.f; l1 = 0.f;
                        shifted = 0;
                        stage_acquire(0); stage_acquire(1);
                    }
                    if (!EVEN && pending) {
                        pack_o(pout);
                        write_blocks(std::integral_constant<int, 8>(), 0, pout);
                        publish_pair();
                    }
                    if (last)
                        asm volatile("{\n.reg .pred P, Q;\n"
                                     "mbarrier.test_wait.parity.shared::cta.b64 Q, [%1], %2;\n"
                                     "mbarrier.test_wait.parity.shared::cta.b64 P, [%3], %4;\n"
                                     "ld.shared.u32 %0, [%5];\n"
                                     "@!Q or.b32 %0, %0, 0x10000;\n"
                                     "@!P mov.u32 %0, -1;\n}\n"
                                     : "=r"(peek) : "r"(bars + B_AFULL + 8 * (ti & 1)), "r"((ti >> 1) & 1), "r"(bars + B_IFULL + 8 * (qn % QDEPTH)),
                                       "r"((qn / QDEPTH) & 1), "r"(bars + SM_QUEUE + 4 * (qn % QDEPTH)) : "memory");
                    mbar_spin(sv.bar, sv.par);
                    pv_gemm(o, pin, dV + sv.off, EVEN || !first);
                    bar_arrive(2 - wg, 256);
                    sk.par ^= 1; sv.par ^= 1;
                    wgmma_wait<1>();
                };
                auto softmax = [&](auto even, uint32_t (&pin)[32], uint32_t (&pout)[32], bool fresh, bool diag, bool last) {
                    constexpr bool EVEN = decltype(even)::value;
                    Slot& sk = slot[EVEN ? 0 : 2];
                    Slot& sv = slot[EVEN ? 1 : 3];
                    fence_regs(s);
                    mbar_arrive_cluster_if(lane < 2 && (!EVEN || has_pv), sk.bar + lane_off);
                    mbar_arrive_if(lane == 0 && last, bars + B_AEMPTY + 8 * ((ti - 1) & 1));
                    float r0, r1, x0 = n0, x1 = n1;
#pragma unroll 1
                    for (int mask = diag, redone = 0;; mask = 0, redone = 1) {
                        if (mask | shifted) {
                            if (mask) causal_mask(s, thr, wg);
                            if (shifted) shift_rows(s, x0, x1);
                        }
                        exp_pack(pout, s, r0, r1);
                        if (!__any_sync(0xffffffffu, fmaxf(r0, r1) >= SUM_LIMIT || (EVEN && fresh && !(lane & 3) && !(fminf(s[0], s[2]) >= -REF_RANGE))) || redone) break;
                        row_max(s, x0, x1);
                        if (!(EVEN && fresh)) { x0 = fmaxf(x0, 0.f); x1 = fmaxf(x1, 0.f); }
                        float a0 = ex2(-x0), a1 = ex2(-x1);
                        n0 += x0; n1 += x1;
                        shifted = 1;
                        if (EVEN && fresh) { a0 = 1.f; a1 = 1.f; }
                        l0 *= a0; l1 *= a1;
                        wgmma_wait<0>();
                        fence_regs(o);
#pragma unroll
                        for (int q = 0; q < 16; q++) { o[4 * q] *= a0; o[4 * q + 1] *= a0; o[4 * q + 2] *= a1; o[4 * q + 3] *= a1; }
                    }
                    l0 += r0; l1 += r1;
                    wgmma_wait<0>();
                    fence_regs(o);
                    fence_regs(pin);
                    mbar_arrive_cluster_if(lane < 2, sv.bar + lane_off);
                };
                auto copy_p = [&]() {
#pragma unroll
                    for (int j = 0; j < 32; j++) pa[j] = __float_as_uint(__uint_as_float(pb[j]) + __uint_as_float(prm.zero));
                };
                int rem = 0;
                zero_regs(pa);
                wgmma_fence();
                wgmma_ss_n128_init(o, full_desc(dA), full_desc(dK));
                wgmma_commit();
                while (true) {
                    const bool fresh = rem == 0, last = fresh ? item_row(cur) == 0 : rem == 1;
                    softmax(std::true_type(), pa, pb, fresh, item_asc(cur) ? last : fresh, last);
                    first = fresh;
                    if (fresh) {
                        pending = has_pv; has_pv = 1;
                        if (pending) scale_o();
                        rem = item_row(cur) + 1;
                    }
                    if (--rem == 0) {
                        copy_p();
                        const Slot t0 = slot[0], t1 = slot[1];
                        slot[0] = slot[2]; slot[1] = slot[3]; slot[2] = t0; slot[3] = t1;
                    } else {
                        issue(std::false_type(), pb, pa, false, rem == 1);
                        softmax(std::false_type(), pb, pa, false, item_asc(cur) && rem == 1, rem == 1);
                        pending = 0; first = 0;
                        rem--;
                    }
                    if (rem == 0) {
                        const int seen = __shfl_sync(0xffffffffu, peek, 0);
                        if (seen >= 0) {
                            mbar_arrive_cluster_if(lane == 0, bars0 + B_IEMPTY + 8 * (qn % QDEPTH));
                            qn++;
                            it = seen & 0xffff;
                        } else {
                            it = take_item();
                        }
                        if (item_row(cur) < 2 || item_type(it) != T_ATTN) break;
                        if (seen & 0x10000) mbar_spin(bars + B_AFULL + 8 * (ti & 1), (ti >> 1) & 1);
                        cur = it;
                        qoff = (ti & 1) * 2048;
                    }
                    issue(std::true_type(), pa, pb, rem == 0, rem ? rem == 1 : item_row(cur) == 0);
                }
                const uint32_t skip = item_asc(cur) & ~item_row(cur) & 1;
                kvn += skip;
                const bool end = item_type(it) == T_END;
#pragma unroll 1
                for (int pass = pending ? 0 : 1; pass < 2; pass++) {
                    if (pass) {
                        kv_wait(kvn);
                        pv_gemm(o, pa, dV + (kvn & 3) * 2048, !first);
                        scales();
                        stage_acquire(0); stage_acquire(1);
                        if (end) it = take_item();
                        wgmma_wait<0>();
                        fence_regs(o);
                        kv_release(kvn);
                        kvn += 1 + skip;
                        scale_o();
                    }
                    pack_o(pb);
                    write_blocks(std::integral_constant<int, 8>(), 0, pb);
                    publish_pair();
                }
            }
        }
        if (item_type(it) == T_OUT) {
            float acc[128];
            const uint32_t dB = make_desc(sb + 16384, 8192);
            mbar_spin(bars + B_GFULL, gph);
            wgmma_fence();
            wgmma_ss_n256_tb_init(acc, full_desc(dA), full_desc(dB));
#pragma unroll
            for (int kk = 1; kk < 4; kk++) wgmma_ss_n256_tb(acc, full_desc(dA) + 2 * kk, full_desc(dB) + 128 * kk, 1);
            wgmma_commit();
            uint32_t ln;
            asm volatile("mov.u32 %0, %%laneid;" : "=r"(ln));
            char* const mine = (char*)prm.out + (uint32_t)((item_row(it) * 128 + wg * 64 + wq * 16 + (ln >> 4)) * 2048 + item_col(it) * 256 + (ln & 15) * 16);
            int k = 1, nk = 80;
            do {
                if ((uint32_t)(k - (K_MEET - 12)) < 8) *(uint4*)(mine + (uint32_t)(k - (K_MEET - 12)) * 4096) = make_uint4(0, 0, 0, 0);
                __syncwarp();
                if (k == K_SPLIT) nk = take_item() & 127;
                gemm_step(acc, dB, k);
            } while (k < nk);
            float lo[64];
            auto triple = [&](auto first) {
                const uint32_t s0 = k & 3, s1 = (k + 1) & 3, o0 = s0 * (GST_BYTES >> 4), o1 = s1 * (GST_BYTES >> 4);
                wgmma_wait<0>();
                mbar_arrive_cluster_if(ln < (decltype(first)::value ? 2 : 4), bars_lane + B_GEMPTY + 8 * ((k - 1 - (ln >> 1)) & 3));
                mbar_spin(bars + B_GFULL + 8 * s0, gph);
                gph ^= s0 == 3;
                wgmma_fence();
#pragma unroll
                for (int kk = 0; kk < 4; kk++) {
                    if (decltype(first)::value && kk == 0) wgmma_ss_n128_tb_init(lo, full_desc(dA + o0), full_desc(dB + o0));
                    else wgmma_ss_n128_tb(lo, full_desc(dA + o0) + 2 * kk, full_desc(dB + o0) + 128 * kk, 1);
                }
                mbar_spin(bars + B_GFULL + 8 * s1, gph);
                gph ^= s1 == 3;
                wgmma_fence();
#pragma unroll
                for (int kk = 0; kk < 4; kk++) wgmma_ss_n128_tb(lo, full_desc(dA + o0 + 2048) + 2 * kk, full_desc(dB + o1 + 1024) + 128 * kk, 1);
#pragma unroll
                for (int kk = 0; kk < 4; kk++) wgmma_ss_n128_tb(lo, full_desc(dA + o1) + 2 * kk, full_desc(dB + o1) + 128 * kk, 1);
                wgmma_commit();
                k += 2;
            };
            triple(std::true_type());
            fence_regs(acc);
            uint32_t pk[32];
#pragma unroll
            for (int j = 0; j < 32; j++) pk[j] = pack_bf16(acc[64 + 2 * j], acc[65 + 2 * j]);
            stage_acquire(0); stage_acquire(1);
            write_blocks(std::integral_constant<int, 8>(), 0, pk);
            publish_pair();
            triple(std::false_type());
            stage_acquire(0); stage_acquire(1);
            wgmma_wait<0>();
            fence_regs(lo);
            mbar_arrive_cluster_if(ln < 4, bars_lane + B_GEMPTY + 8 * ((k - 1 - (ln >> 1)) & 3));
#pragma unroll
            for (int b = 0; b < 2; b++) {
#pragma unroll
                for (int j = 16 * b; j < 16 * b + 16; j++) pk[j] = pack_bf16(acc[2 * j] + lo[2 * j], acc[2 * j + 1] + lo[2 * j + 1]);
                write_blocks(std::integral_constant<int, 4>(), b * 8192, pk + 16 * b);
                stage_publish(b);
            }
        }
    }
}

typedef CUresult (*EncodeFn)(CUtensorMap*, CUtensorMapDataType, cuuint32_t, void*, const cuuint64_t*, const cuuint64_t*,
                             const cuuint32_t*, const cuuint32_t*, CUtensorMapInterleave, CUtensorMapSwizzle,
                             CUtensorMapL2promotion, CUtensorMapFloatOOBfill);

void encode3(EncodeFn fn, CUtensorMap* m, const void* ptr, uint64_t d0, uint64_t d1, uint64_t d2, uint64_t s1, uint64_t s2,
             uint32_t b0, uint32_t b1, uint32_t b2) {
    cuuint64_t dims[3] = {d0, d1, d2};
    cuuint64_t strides[2] = {s1, s2};
    cuuint32_t box[3] = {b0, b1, b2};
    cuuint32_t es[3] = {1, 1, 1};
    fn(m, CU_TENSOR_MAP_DATA_TYPE_BFLOAT16, 3, const_cast<void*>(ptr), dims, strides, box, es, CU_TENSOR_MAP_INTERLEAVE_NONE,
       CU_TENSOR_MAP_SWIZZLE_128B, CU_TENSOR_MAP_L2_PROMOTION_NONE, CU_TENSOR_MAP_FLOAT_OOB_FILL_NONE);
}
void map_act(EncodeFn fn, CUtensorMap* m, const void* p, int rows, int cols, int box_rows) {
    encode3(fn, m, p, cols, rows, 1, (uint64_t)cols * 2, (uint64_t)cols * rows * 2, 64, box_rows, 1);
}
void map_wgt(EncodeFn fn, CUtensorMap* m, const void* p, int K, int N) {
    encode3(fn, m, p, 64, K, N / 64, (uint64_t)N * 2, 128, 64, 64, 2);
}

void build_schedule(Params& p) {
    int n = 0;
    auto add = [&](int type, int col, int row) { p.items[n++] = (uint16_t)(type << 13 | col << 4 | row); };
    int beta = 26, tail = 32, late = 6, early = 4, epos = 60;
    int order[16] = {6, 7, 8, 9, 10, 11, 12, 13, 14, 15, 5, 4, 3, 2, 1, 0};
    const char* plans = "xxcccccx,xxcccccx,xxxxx,xxcxlxx,xxlcclxcc,xxlcccccc,xxlxlccccc,xxlxlxccc";
    const char* pos[8];
    int len[8] = {}, start[8] = {};
    for (int s = 0; s < 8; s++) { pos[s] = plans; while (*plans && *plans++ != ',') {} }
    for (int i = 0; i < 160; i++) p.plan[i / 16][i % 16] = T_END << 13;
    for (int nx = 0, nc = 3, nl = 0; nx + nc + nl < 28 + 32 + 8;) {
        int s = -1;
        for (int i = 0; i < 8; i++) if (*pos[i] > ',' && (s < 0 || start[i] < start[s])) s = i;
        const char kind = *pos[s]++;
        int it;
        if (kind == 'x') { it = nx < 12 ? T_B << 13 | (nx % 3 * 4 + nx / 3) << 4 : T_Q << 13 | (nx - 12) << 4; nx++; }
        else if (kind == 'c') { it = (T_K + (nc & 1)) << 13 | nc / 2 << 4; nc++; }
        else { it = T_LOCAL << 13 | nl / 2 << 4 | (nl & 1); nl++; }
        p.plan[s][len[s]++] = (uint16_t)it;
        start[s] += kind == 'x' ? 48 : kind == 'c' ? 24 : 8;
    }
    for (int i = 0; i < 24; i++) p.plan[8 + i / 12][i % 12] = (uint16_t)((T_K + (i % 3 & 1)) << 13 | i % 3 / 2 << 4 | i / 3);
    const int a0 = n;
    for (int key = 0; key < 4000; key++)
        for (int r = 0; r < 32; r++)
            for (int j = 7; j >= 0; j--)
                if ((j ? (7 - j) * 40 + r * beta : 3999) == key) add(T_ATTN, 2 * order[r >> 1] + (r & 1), j);
    int t0 = n;
    for (int work = 0; work < 32 * 136 * tail / 100;) work += 4 * (p.items[--t0] & 15) + 3;
    for (int i = t0 + 1; i < n; i++)
        for (int j = i; j > t0 && (p.items[j] & 15) > (p.items[j - 1] & 15); j--) { const uint16_t t = p.items[j]; p.items[j] = p.items[j - 1]; p.items[j - 1] = t; }
    for (int r = early - 1; r >= 0; r--) {
        const uint16_t t = p.items[n - 32 + early - 1];
        for (int j = n - 32 + early - 1; j > n - epos; j--) p.items[j] = p.items[j - 1];
        p.items[n - epos] = t;
    }
    for (int moved = 0; moved < 2 && late >= 0; moved++)
        for (int i = a0; i < n; i++)
            if (p.items[i] == (T_ATTN << 13 | (2 * order[15] + moved) << 4 | late)) {
                for (int j = i; j + 1 < n; j++) p.items[j] = p.items[j + 1];
                p.items[n - 1] = (uint16_t)(T_ATTN << 13 | (2 * order[15] + moved) << 4 | late);
                break;
            }
    for (int s = 0, lo = 0, hi = WIDE - 1; s < 80; s++) {
        const int r = s / 2, g = r < 8 ? 32 + r : 2 * order[r / 2 - 4] + (r & 1);
        p.ostep[s >= WIDE ? s : r & 1 ? hi-- : lo++] = (uint8_t)(2 * g + (s & 1));
    }
}

void build_params(Params& p, void* const* d_in, void* d_out) {
    void* fnp = nullptr;
    cudaDriverEntryPointQueryResult qr;
    cudaGetDriverEntryPoint("cuTensorMapEncodeTiled", &fnp, cudaEnableDefault, &qr);
    EncodeFn fn = (EncodeFn)fnp;
    void* scr = nullptr;
    cudaGetSymbolAddress(&scr, g_scr);
    map_act(fn, &p.m[M_X], d_in[0], SEQ, 1024, 128);
    map_act(fn, &p.m[M_C], d_in[1], SEQ, 512, 128);
    map_wgt(fn, &p.m[M_WQ], d_in[2], 1024, 4096);
    map_wgt(fn, &p.m[M_WUK], d_in[3], 512, 4096);
    map_wgt(fn, &p.m[M_WUV], d_in[4], 512, 4096);
    map_wgt(fn, &p.m[M_WO], d_in[5], 4096, 1024);
    map_wgt(fn, &p.m[M_WQKV], d_in[7], 1024, 3072);
    map_wgt(fn, &p.m[M_WOB], d_in[8], 1024, 1024);
    encode3(fn, &p.m[M_SCR_LD], scr, 128, SEQ, G_TOTAL, 256, (uint64_t)SEQ * 256, 64, 128, 1);
    encode3(fn, &p.m[M_SCR_LOC], scr, 256, SEQ / 2, G_TOTAL, 512, (uint64_t)SEQ * 256, 64, 72, 1);
    encode3(fn, &p.m[M_SCR_LOQ], scr, 256, SEQ / 2, G_TOTAL, 512, (uint64_t)SEQ * 256, 64, 64, 1);
    encode3(fn, &p.m[M_SCR_ST], scr, 128, SEQ, G_TOTAL, 256, (uint64_t)SEQ * 256, 64, 64, 1);
    map_act(fn, &p.m[M_OUT], d_out, SEQ, 1024, 64);
    p.x = (const __nv_bfloat16*)d_in[0];
    p.gate_w = (const __nv_bfloat16*)d_in[9];
    p.zero = 0;
    p.wo = (const char*)d_in[5];
    p.out = (__nv_bfloat16*)d_out;
    build_schedule(p);
}

}

extern "C" void kernel_launch(void* const* d_in, const int* in_sizes, int n_in, void* d_out, int out_size) {
    (void)in_sizes; (void)n_in; (void)out_size;
    Params p;
    build_params(p, d_in, d_out);
    cudaFuncSetAttribute(fused_kernel, cudaFuncAttributeMaxDynamicSharedMemorySize, SM_TOTAL);
    fused_kernel<<<NCTA, 384, SM_TOTAL>>>(p);
}
```

```cpp
#include <cuda_runtime.h>
#include <cuda_bf16.h>
#include <cuda.h>
#include <stddef.h>
#include <stdint.h>
#include <type_traits>

namespace {

constexpr int SEQ = 2048;
constexpr int G_Q = 0, G_K = 32, G_V = 64, G_B = 96, G_CTX = G_Q, G_LOC = G_B, G_TOTAL = 120;

__device__ __align__(1024) __nv_bfloat16 g_scr[(size_t)G_TOTAL * SEQ * 128];
__device__ __align__(128) float g_gate[SEQ];

__device__ __forceinline__ uint32_t smem_u32(const void* p) { return (uint32_t)__cvta_generic_to_shared(p); }
__device__ __forceinline__ bool elect_one() {
    uint32_t p;
    asm volatile("{\n.reg .pred P;\nelect.sync _|P, 0xffffffff;\nselp.u32 %0, 1, 0, P;\n}\n" : "=r"(p));
    return p != 0;
}
__device__ __forceinline__ void mbar_init(uint32_t bar, uint32_t count) {
    asm volatile("mbarrier.init.shared::cta.b64 [%0], %1;" :: "r"(bar), "r"(count) : "memory");
}
__device__ __forceinline__ uint32_t cluster_rank() { uint32_t r; asm("mov.u32 %0, %%cluster_ctarank;" : "=r"(r)); return r; }
__device__ __forceinline__ uint32_t map_cta(uint32_t addr, uint32_t cta) {
    uint32_t r; asm("mapa.shared::cluster.u32 %0, %1, %2;" : "=r"(r) : "r"(addr), "r"(cta)); return r;
}
__device__ __forceinline__ void mbar_arrive_cluster_if(bool pred, uint32_t cluster_bar) {
    asm volatile("{\n.reg .pred P;\nsetp.ne.u32 P, %1, 0;\n@P mbarrier.arrive.shared::cluster.b64 _, [%0];\n}\n"
                 :: "r"(cluster_bar), "r"((uint32_t)pred) : "memory");
}
__device__ __forceinline__ void mbar_arrive_cluster_n_if(bool pred, uint32_t cluster_bar, uint32_t count) {
    asm volatile("{\n.reg .pred P;\nsetp.ne.u32 P, %1, 0;\n@P mbarrier.arrive.shared::cluster.b64 _, [%0], %2;\n}\n"
                 :: "r"(cluster_bar), "r"((uint32_t)pred), "r"(count) : "memory");
}
__device__ __forceinline__ void mbar_arrive_if(bool pred, uint32_t bar) {
    asm volatile("{\n.reg .pred P;\nsetp.ne.u32 P, %1, 0;\n@P mbarrier.arrive.shared::cta.b64 _, [%0];\n}\n"
                 :: "r"(bar), "r"((uint32_t)pred) : "memory");
}
__device__ __forceinline__ bool mbar_test(uint32_t bar, uint32_t parity) {
    uint32_t ok;
    asm volatile("{\n.reg .pred P;\nmbarrier.test_wait.parity.shared::cta.b64 P, [%1], %2;\nselp.u32 %0, 1, 0, P;\n}\n"
                 : "=r"(ok) : "r"(bar), "r"(parity) : "memory");
    return ok != 0;
}
__device__ __forceinline__ void mbar_wait(uint32_t bar, uint32_t parity) {
    asm volatile("{\n.reg .pred P;\n.reg .u32 c;\n"
                 "mov.u32 c, 0;\n"
                 "SPIN:\n"
                 "mbarrier.try_wait.parity.shared::cta.b64 P, [%0], %1;\n"
                 "@P bra DONE;\n"
                 "add.u32 c, c, 1;\n"
                 "setp.lt.u32 P, c, 4194304;\n"
                 "@P bra SPIN;\n"
                 "trap;\n"
                 "DONE:\n}\n" :: "r"(bar), "r"(parity) : "memory");
}
__device__ __forceinline__ void mbar_spin(uint32_t bar, uint32_t parity) {
    asm volatile("{\n.reg .pred P;\n"
                 "SPIN:\n"
                 "mbarrier.try_wait.parity.shared::cta.b64 P, [%0], %1;\n"
                 "@!P bra SPIN;\n}\n" :: "r"(bar), "r"(parity) : "memory");
}
__device__ __forceinline__ void bar_sync(int id, int n) { asm volatile("bar.sync %0, %1;" :: "r"(id), "r"(n) : "memory"); }
__device__ __forceinline__ void bar_arrive(int id, int n) { asm volatile("bar.arrive %0, %1;" :: "r"(id), "r"(n) : "memory"); }
__device__ __forceinline__ void fence_proxy_async_smem() { asm volatile("fence.proxy.async.shared::cta;" ::: "memory"); }
__device__ __forceinline__ void warp_expect_tx(uint32_t bar, uint32_t bytes) {
    asm volatile("{\n.reg .pred P;\nelect.sync _|P, 0xffffffff;\n@P mbarrier.arrive.expect_tx.shared::cta.b64 _, [%0], %1;\n}\n"
                 :: "r"(bar), "r"(bytes) : "memory");
}
constexpr uint64_t EVICT_FIRST = 0x12F0000000000000ull;
__device__ __forceinline__ void warp_tma_load(uint32_t dst, const CUtensorMap* map, uint32_t bar, int c0, int c1, int c2, bool stream) {
    if (stream)
        asm volatile("{\n.reg .pred P;\nelect.sync _|P, 0xffffffff;\n"
                     "@P cp.async.bulk.tensor.3d.shared::cluster.global.mbarrier::complete_tx::bytes.L2::cache_hint"
                     " [%0], [%1, {%3, %4, %5}], [%2], %6;\n}\n"
                     :: "r"(dst), "l"(map), "r"(bar), "r"(c0), "r"(c1), "r"(c2), "l"(EVICT_FIRST) : "memory");
    else
        asm volatile("{\n.reg .pred P;\nelect.sync _|P, 0xffffffff;\n"
                     "@P cp.async.bulk.tensor.3d.shared::cluster.global.mbarrier::complete_tx::bytes [%0], [%1, {%3, %4, %5}], [%2];\n}\n"
                     :: "r"(dst), "l"(map), "r"(bar), "r"(c0), "r"(c1), "r"(c2) : "memory");
}
__device__ __forceinline__ void warp_tma_load_pair(uint32_t dst, const CUtensorMap* map, uint32_t bar, int c0, int c1, int c2, bool stream) {
    if (stream)
        asm volatile("{\n.reg .pred P;\nelect.sync _|P, 0xffffffff;\n"
                     "@P cp.async.bulk.tensor.3d.shared::cluster.global.mbarrier::complete_tx::bytes.multicast::cluster.L2::cache_hint"
                     " [%0], [%1, {%3, %4, %5}], [%2], %6, %7;\n}\n"
                     :: "r"(dst), "l"(map), "r"(bar), "r"(c0), "r"(c1), "r"(c2), "h"((uint16_t)3), "l"(EVICT_FIRST) : "memory");
    else
        asm volatile("{\n.reg .pred P;\nelect.sync _|P, 0xffffffff;\n"
                     "@P cp.async.bulk.tensor.3d.shared::cluster.global.mbarrier::complete_tx::bytes.multicast::cluster"
                     " [%0], [%1, {%3, %4, %5}], [%2], %6;\n}\n"
                     :: "r"(dst), "l"(map), "r"(bar), "r"(c0), "r"(c1), "r"(c2), "h"((uint16_t)3) : "memory");
}
__device__ __forceinline__ void warp_bulk_load(uint32_t dst, const void* src, uint32_t bytes, uint32_t bar) {
    asm volatile("{\n.reg .pred P;\nelect.sync _|P, 0xffffffff;\n"
                 "@P cp.async.bulk.shared::cluster.global.mbarrier::complete_tx::bytes [%0], [%1], %2, [%3];\n}\n"
                 :: "r"(dst), "l"(src), "r"(bytes), "r"(bar) : "memory");
}
__device__ __forceinline__ void warp_tma_store(const CUtensorMap* map, uint32_t src, int c0, int c1, int c2, bool stream) {
    if (stream)
        asm volatile("{\n.reg .pred P;\nelect.sync _|P, 0xffffffff;\n"
                     "@P cp.async.bulk.tensor.3d.global.shared::cta.bulk_group.L2::cache_hint [%0, {%2, %3, %4}], [%1], %5;\n}\n"
                     :: "l"(map), "r"(src), "r"(c0), "r"(c1), "r"(c2), "l"(EVICT_FIRST) : "memory");
    else
        asm volatile("{\n.reg .pred P;\nelect.sync _|P, 0xffffffff;\n"
                     "@P cp.async.bulk.tensor.3d.global.shared::cta.bulk_group [%0, {%2, %3, %4}], [%1];\n}\n"
                     :: "l"(map), "r"(src), "r"(c0), "r"(c1), "r"(c2) : "memory");
}
__device__ __forceinline__ void warp_tma_add(const CUtensorMap* map, uint32_t src, int c0, int c1, int c2) {
    asm volatile("{\n.reg .pred P;\nelect.sync _|P, 0xffffffff;\n"
                 "@P cp.reduce.async.bulk.tensor.3d.global.shared::cta.add.tile.bulk_group [%0, {%2, %3, %4}], [%1];\n}\n"
                 :: "l"(map), "r"(src), "r"(c0), "r"(c1), "r"(c2) : "memory");
}
__device__ __forceinline__ void warp_bulk_store(void* dst, uint32_t src, uint32_t bytes) {
    asm volatile("{\n.reg .pred P;\nelect.sync _|P, 0xffffffff;\n"
                 "@P cp.async.bulk.global.shared::cta.bulk_group [%0], [%1], %2;\n}\n" :: "l"(dst), "r"(src), "r"(bytes) : "memory");
}
__device__ __forceinline__ void warp_prefetch(const void* src, uint32_t bytes) {
    asm volatile("{\n.reg .pred P;\nelect.sync _|P, 0xffffffff;\n@P cp.async.bulk.prefetch.L2.global [%0], %1;\n}\n" :: "l"(src), "r"(bytes) : "memory");
}
__device__ __forceinline__ void bulk_commit() { asm volatile("cp.async.bulk.commit_group;" ::: "memory"); }
template <int N> __device__ __forceinline__ void bulk_wait_read() { asm volatile("cp.async.bulk.wait_group.read %0;" :: "n"(N) : "memory"); }
template <int N> __device__ __forceinline__ void bulk_wait() { asm volatile("cp.async.bulk.wait_group %0;" :: "n"(N) : "memory"); }
__device__ __forceinline__ void wgmma_fence() { asm volatile("wgmma.fence.sync.aligned;" ::: "memory"); }
__device__ __forceinline__ void wgmma_commit() { asm volatile("wgmma.commit_group.sync.aligned;" ::: "memory"); }
template <int N> __device__ __forceinline__ void wgmma_wait() { asm volatile("wgmma.wait_group.sync.aligned %0;" :: "n"(N) : "memory"); }
template <int N> __device__ __forceinline__ void fence_regs(float (&d)[N]) {
#pragma unroll
    for (int i = 0; i < N; i++) asm volatile("" : "+f"(d[i]) :: "memory");
}
template <int N> __device__ __forceinline__ void fence_regs(uint32_t (&d)[N]) {
#pragma unroll
    for (int i = 0; i < N; i++) asm volatile("" : "+r"(d[i]) :: "memory");
}
template <int N> __device__ __forceinline__ void reg_dec() { asm volatile("setmaxnreg.dec.sync.aligned.u32 %0;" :: "n"(N)); }
template <int N> __device__ __forceinline__ void reg_inc() { asm volatile("setmaxnreg.inc.sync.aligned.u32 %0;" :: "n"(N)); }
__device__ __forceinline__ uint32_t pack_bf16(float lo, float hi) {
    uint32_t r; asm("cvt.rn.bf16x2.f32 %0, %1, %2;" : "=r"(r) : "f"(hi), "f"(lo)); return r;
}
__device__ __forceinline__ void stmatrix_x4(uint32_t addr, uint32_t r0, uint32_t r1, uint32_t r2, uint32_t r3) {
    asm volatile("stmatrix.sync.aligned.m8n8.x4.shared.b16 [%0], {%1, %2, %3, %4};"
                 :: "r"(addr), "r"(r0), "r"(r1), "r"(r2), "r"(r3) : "memory");
}
__device__ __forceinline__ float ex2(float x) { float y; asm("ex2.approx.ftz.f32 %0, %1;" : "=f"(y) : "f"(x)); return y; }

constexpr uint32_t DESC_HI = (1024 >> 4) | (1u << 30);
__device__ __forceinline__ uint32_t make_desc(uint32_t addr, uint32_t lbo) {
    uint32_t lo = ((addr & 0x3FFFF) >> 4) | ((lbo >> 4) << 16);
    asm volatile("" : "+r"(lo));
    return lo;
}
__device__ __forceinline__ uint64_t full_desc(uint32_t lo) {
    uint64_t d; asm("mov.b64 %0, {%1, %2};" : "=l"(d) : "r"(lo), "r"(DESC_HI)); return d;
}

__device__ __forceinline__ void wgmma_ss_n256_tb_init(float (&d)[128], uint64_t da, uint64_t db) {
    asm volatile("{\n.reg .pred p;\n"
        "setp.ne.b32 p, 0, 0;\n"
        "wgmma.mma_async.sync.aligned.m64n256k16.f32.bf16.bf16 "
        "{%0, %1, %2, %3, %4, %5, %6, %7, %8, %9, %10, %11, %12, %13, %14, %15, %16, %17, %18, %19, %20, "
        "%21, %22, %23, %24, %25, %26, %27, %28, %29, %30, %31, %32, %33, %34, %35, %36, %37, %38, %39, %40, "
        "%41, %42, %43, %44, %45, %46, %47, %48, %49, %50, %51, %52, %53, %54, %55, %56, %57, %58, %59, %60, "
        "%61, %62, %63, %64, %65, %66, %67, %68, %69, %70, %71, %72, %73, %74, %75, %76, %77, %78, %79, %80, "
        "%81, %82, %83, %84, %85, %86, %87, %88, %89, %90, %91, %92, %93, %94, %95, %96, %97, %98, %99, "
        "%100, %101, %102, %103, %104, %105, %106, %107, %108, %109, %110, %111, %112, %113, %114, %115, "
        "%116, %117, %118, %119, %120, %121, %122, %123, %124, %125, %126, %127},"
        " %128, %129, p, 1, 1, 0, 1;\n}\n"
        : "=f"(d[0]), "=f"(d[1]), "=f"(d[2]), "=f"(d[3]), "=f"(d[4]), "=f"(d[5]), "=f"(d[6]), "=f"(d[7]),
        "=f"(d[8]), "=f"(d[9]), "=f"(d[10]), "=f"(d[11]), "=f"(d[12]), "=f"(d[13]), "=f"(d[14]), "=f"(d[15]),
        "=f"(d[16]), "=f"(d[17]), "=f"(d[18]), "=f"(d[19]), "=f"(d[20]), "=f"(d[21]), "=f"(d[22]),
        "=f"(d[23]), "=f"(d[24]), "=f"(d[25]), "=f"(d[26]), "=f"(d[27]), "=f"(d[28]), "=f"(d[29]),
        "=f"(d[30]), "=f"(d[31]), "=f"(d[32]), "=f"(d[33]), "=f"(d[34]), "=f"(d[35]), "=f"(d[36]),
        "=f"(d[37]), "=f"(d[38]), "=f"(d[39]), "=f"(d[40]), "=f"(d[41]), "=f"(d[42]), "=f"(d[43]),
        "=f"(d[44]), "=f"(d[45]), "=f"(d[46]), "=f"(d[47]), "=f"(d[48]), "=f"(d[49]), "=f"(d[50]),
        "=f"(d[51]), "=f"(d[52]), "=f"(d[53]), "=f"(d[54]), "=f"(d[55]), "=f"(d[56]), "=f"(d[57]),
        "=f"(d[58]), "=f"(d[59]), "=f"(d[60]), "=f"(d[61]), "=f"(d[62]), "=f"(d[63]), "=f"(d[64]),
        "=f"(d[65]), "=f"(d[66]), "=f"(d[67]), "=f"(d[68]), "=f"(d[69]), "=f"(d[70]), "=f"(d[71]),
        "=f"(d[72]), "=f"(d[73]), "=f"(d[74]), "=f"(d[75]), "=f"(d[76]), "=f"(d[77]), "=f"(d[78]),
        "=f"(d[79]), "=f"(d[80]), "=f"(d[81]), "=f"(d[82]), "=f"(d[83]), "=f"(d[84]), "=f"(d[85]),
        "=f"(d[86]), "=f"(d[87]), "=f"(d[88]), "=f"(d[89]), "=f"(d[90]), "=f"(d[91]), "=f"(d[92]),
        "=f"(d[93]), "=f"(d[94]), "=f"(d[95]), "=f"(d[96]), "=f"(d[97]), "=f"(d[98]), "=f"(d[99]),
        "=f"(d[100]), "=f"(d[101]), "=f"(d[102]), "=f"(d[103]), "=f"(d[104]), "=f"(d[105]), "=f"(d[106]),
        "=f"(d[107]), "=f"(d[108]), "=f"(d[109]), "=f"(d[110]), "=f"(d[111]), "=f"(d[112]), "=f"(d[113]),
        "=f"(d[114]), "=f"(d[115]), "=f"(d[116]), "=f"(d[117]), "=f"(d[118]), "=f"(d[119]), "=f"(d[120]),
        "=f"(d[121]), "=f"(d[122]), "=f"(d[123]), "=f"(d[124]), "=f"(d[125]), "=f"(d[126]), "=f"(d[127])
        : "l"(da), "l"(db));
}
__device__ __forceinline__ void wgmma_ss_n256_tb(float (&d)[128], uint64_t da, uint64_t db, int scale_d) {
    asm volatile("{\n.reg .pred p;\n"
        "setp.ne.b32 p, %130, 0;\n"
        "wgmma.mma_async.sync.aligned.m64n256k16.f32.bf16.bf16 "
        "{%0, %1, %2, %3, %4, %5, %6, %7, %8, %9, %10, %11, %12, %13, %14, %15, %16, %17, %18, %19, %20, "
        "%21, %22, %23, %24, %25, %26, %27, %28, %29, %30, %31, %32, %33, %34, %35, %36, %37, %38, %39, %40, "
        "%41, %42, %43, %44, %45, %46, %47, %48, %49, %50, %51, %52, %53, %54, %55, %56, %57, %58, %59, %60, "
        "%61, %62, %63, %64, %65, %66, %67, %68, %69, %70, %71, %72, %73, %74, %75, %76, %77, %78, %79, %80, "
        "%81, %82, %83, %84, %85, %86, %87, %88, %89, %90, %91, %92, %93, %94, %95, %96, %97, %98, %99, "
        "%100, %101, %102, %103, %104, %105, %106, %107, %108, %109, %110, %111, %112, %113, %114, %115, "
        "%116, %117, %118, %119, %120, %121, %122, %123, %124, %125, %126, %127},"
        " %128, %129, p, 1, 1, 0, 1;\n}\n"
        : "+f"(d[0]), "+f"(d[1]), "+f"(d[2]), "+f"(d[3]), "+f"(d[4]), "+f"(d[5]), "+f"(d[6]), "+f"(d[7]),
        "+f"(d[8]), "+f"(d[9]), "+f"(d[10]), "+f"(d[11]), "+f"(d[12]), "+f"(d[13]), "+f"(d[14]), "+f"(d[15]),
        "+f"(d[16]), "+f"(d[17]), "+f"(d[18]), "+f"(d[19]), "+f"(d[20]), "+f"(d[21]), "+f"(d[22]),
        "+f"(d[23]), "+f"(d[24]), "+f"(d[25]), "+f"(d[26]), "+f"(d[27]), "+f"(d[28]), "+f"(d[29]),
        "+f"(d[30]), "+f"(d[31]), "+f"(d[32]), "+f"(d[33]), "+f"(d[34]), "+f"(d[35]), "+f"(d[36]),
        "+f"(d[37]), "+f"(d[38]), "+f"(d[39]), "+f"(d[40]), "+f"(d[41]), "+f"(d[42]), "+f"(d[43]),
        "+f"(d[44]), "+f"(d[45]), "+f"(d[46]), "+f"(d[47]), "+f"(d[48]), "+f"(d[49]), "+f"(d[50]),
        "+f"(d[51]), "+f"(d[52]), "+f"(d[53]), "+f"(d[54]), "+f"(d[55]), "+f"(d[56]), "+f"(d[57]),
        "+f"(d[58]), "+f"(d[59]), "+f"(d[60]), "+f"(d[61]), "+f"(d[62]), "+f"(d[63]), "+f"(d[64]),
        "+f"(d[65]), "+f"(d[66]), "+f"(d[67]), "+f"(d[68]), "+f"(d[69]), "+f"(d[70]), "+f"(d[71]),
        "+f"(d[72]), "+f"(d[73]), "+f"(d[74]), "+f"(d[75]), "+f"(d[76]), "+f"(d[77]), "+f"(d[78]),
        "+f"(d[79]), "+f"(d[80]), "+f"(d[81]), "+f"(d[82]), "+f"(d[83]), "+f"(d[84]), "+f"(d[85]),
        "+f"(d[86]), "+f"(d[87]), "+f"(d[88]), "+f"(d[89]), "+f"(d[90]), "+f"(d[91]), "+f"(d[92]),
        "+f"(d[93]), "+f"(d[94]), "+f"(d[95]), "+f"(d[96]), "+f"(d[97]), "+f"(d[98]), "+f"(d[99]),
        "+f"(d[100]), "+f"(d[101]), "+f"(d[102]), "+f"(d[103]), "+f"(d[104]), "+f"(d[105]), "+f"(d[106]),
        "+f"(d[107]), "+f"(d[108]), "+f"(d[109]), "+f"(d[110]), "+f"(d[111]), "+f"(d[112]), "+f"(d[113]),
        "+f"(d[114]), "+f"(d[115]), "+f"(d[116]), "+f"(d[117]), "+f"(d[118]), "+f"(d[119]), "+f"(d[120]),
        "+f"(d[121]), "+f"(d[122]), "+f"(d[123]), "+f"(d[124]), "+f"(d[125]), "+f"(d[126]), "+f"(d[127])
        : "l"(da), "l"(db), "r"(scale_d));
}
__device__ __forceinline__ void wgmma_ss_n128_init(float (&d)[64], uint64_t da, uint64_t db) {
    asm volatile("{\n.reg .pred p;\n"
        "setp.ne.b32 p, 0, 0;\n"
        "wgmma.mma_async.sync.aligned.m64n128k16.f32.bf16.bf16 "
        "{%0, %1, %2, %3, %4, %5, %6, %7, %8, %9, %10, %11, %12, %13, %14, %15, %16, %17, %18, %19, %20, "
        "%21, %22, %23, %24, %25, %26, %27, %28, %29, %30, %31, %32, %33, %34, %35, %36, %37, %38, %39, %40, "
        "%41, %42, %43, %44, %45, %46, %47, %48, %49, %50, %51, %52, %53, %54, %55, %56, %57, %58, %59, %60, "
        "%61, %62, %63},"
        " %64, %65, p, 1, 1, 0, 0;\n}\n"
        : "=f"(d[0]), "=f"(d[1]), "=f"(d[2]), "=f"(d[3]), "=f"(d[4]), "=f"(d[5]), "=f"(d[6]), "=f"(d[7]),
        "=f"(d[8]), "=f"(d[9]), "=f"(d[10]), "=f"(d[11]), "=f"(d[12]), "=f"(d[13]), "=f"(d[14]), "=f"(d[15]),
        "=f"(d[16]), "=f"(d[17]), "=f"(d[18]), "=f"(d[19]), "=f"(d[20]), "=f"(d[21]), "=f"(d[22]),
        "=f"(d[23]), "=f"(d[24]), "=f"(d[25]), "=f"(d[26]), "=f"(d[27]), "=f"(d[28]), "=f"(d[29]),
        "=f"(d[30]), "=f"(d[31]), "=f"(d[32]), "=f"(d[33]), "=f"(d[34]), "=f"(d[35]), "=f"(d[36]),
        "=f"(d[37]), "=f"(d[38]), "=f"(d[39]), "=f"(d[40]), "=f"(d[41]), "=f"(d[42]), "=f"(d[43]),
        "=f"(d[44]), "=f"(d[45]), "=f"(d[46]), "=f"(d[47]), "=f"(d[48]), "=f"(d[49]), "=f"(d[50]),
        "=f"(d[51]), "=f"(d[52]), "=f"(d[53]), "=f"(d[54]), "=f"(d[55]), "=f"(d[56]), "=f"(d[57]),
        "=f"(d[58]), "=f"(d[59]), "=f"(d[60]), "=f"(d[61]), "=f"(d[62]), "=f"(d[63])
        : "l"(da), "l"(db));
}
__device__ __forceinline__ void wgmma_ss_n128(float (&d)[64], uint64_t da, uint64_t db, int scale_d) {
    asm volatile("{\n.reg .pred p;\n"
        "setp.ne.b32 p, %66, 0;\n"
        "wgmma.mma_async.sync.aligned.m64n128k16.f32.bf16.bf16 "
        "{%0, %1, %2, %3, %4, %5, %6, %7, %8, %9, %10, %11, %12, %13, %14, %15, %16, %17, %18, %19, %20, "
        "%21, %22, %23, %24, %25, %26, %27, %28, %29, %30, %31, %32, %33, %34, %35, %36, %37, %38, %39, %40, "
        "%41, %42, %43, %44, %45, %46, %47, %48, %49, %50, %51, %52, %53, %54, %55, %56, %57, %58, %59, %60, "
        "%61, %62, %63},"
        " %64, %65, p, 1, 1, 0, 0;\n}\n"
        : "+f"(d[0]), "+f"(d[1]), "+f"(d[2]), "+f"(d[3]), "+f"(d[4]), "+f"(d[5]), "+f"(d[6]), "+f"(d[7]),
        "+f"(d[8]), "+f"(d[9]), "+f"(d[10]), "+f"(d[11]), "+f"(d[12]), "+f"(d[13]), "+f"(d[14]), "+f"(d[15]),
        "+f"(d[16]), "+f"(d[17]), "+f"(d[18]), "+f"(d[19]), "+f"(d[20]), "+f"(d[21]), "+f"(d[22]),
        "+f"(d[23]), "+f"(d[24]), "+f"(d[25]), "+f"(d[26]), "+f"(d[27]), "+f"(d[28]), "+f"(d[29]),
        "+f"(d[30]), "+f"(d[31]), "+f"(d[32]), "+f"(d[33]), "+f"(d[34]), "+f"(d[35]), "+f"(d[36]),
        "+f"(d[37]), "+f"(d[38]), "+f"(d[39]), "+f"(d[40]), "+f"(d[41]), "+f"(d[42]), "+f"(d[43]),
        "+f"(d[44]), "+f"(d[45]), "+f"(d[46]), "+f"(d[47]), "+f"(d[48]), "+f"(d[49]), "+f"(d[50]),
        "+f"(d[51]), "+f"(d[52]), "+f"(d[53]), "+f"(d[54]), "+f"(d[55]), "+f"(d[56]), "+f"(d[57]),
        "+f"(d[58]), "+f"(d[59]), "+f"(d[60]), "+f"(d[61]), "+f"(d[62]), "+f"(d[63])
        : "l"(da), "l"(db), "r"(scale_d));
}
__device__ __forceinline__ void wgmma_rs_n128_tb(float (&d)[64], uint32_t a0, uint32_t a1, uint32_t a2, uint32_t a3, uint64_t db, int scale_d) {
    asm volatile("{\n.reg .pred p;\n"
        "setp.ne.b32 p, %69, 0;\n"
        "wgmma.mma_async.sync.aligned.m64n128k16.f32.bf16.bf16 "
        "{%0, %1, %2, %3, %4, %5, %6, %7, %8, %9, %10, %11, %12, %13, %14, %15, %16, %17, %18, %19, %20, "
        "%21, %22, %23, %24, %25, %26, %27, %28, %29, %30, %31, %32, %33, %34, %35, %36, %37, %38, %39, %40, "
        "%41, %42, %43, %44, %45, %46, %47, %48, %49, %50, %51, %52, %53, %54, %55, %56, %57, %58, %59, %60, "
        "%61, %62, %63},"
        " {%64, %65, %66, %67}, %68, p, 1, 1, 1;\n}\n"
        : "+f"(d[0]), "+f"(d[1]), "+f"(d[2]), "+f"(d[3]), "+f"(d[4]), "+f"(d[5]), "+f"(d[6]), "+f"(d[7]),
        "+f"(d[8]), "+f"(d[9]), "+f"(d[10]), "+f"(d[11]), "+f"(d[12]), "+f"(d[13]), "+f"(d[14]), "+f"(d[15]),
        "+f"(d[16]), "+f"(d[17]), "+f"(d[18]), "+f"(d[19]), "+f"(d[20]), "+f"(d[21]), "+f"(d[22]),
        "+f"(d[23]), "+f"(d[24]), "+f"(d[25]), "+f"(d[26]), "+f"(d[27]), "+f"(d[28]), "+f"(d[29]),
        "+f"(d[30]), "+f"(d[31]), "+f"(d[32]), "+f"(d[33]), "+f"(d[34]), "+f"(d[35]), "+f"(d[36]),
        "+f"(d[37]), "+f"(d[38]), "+f"(d[39]), "+f"(d[40]), "+f"(d[41]), "+f"(d[42]), "+f"(d[43]),
        "+f"(d[44]), "+f"(d[45]), "+f"(d[46]), "+f"(d[47]), "+f"(d[48]), "+f"(d[49]), "+f"(d[50]),
        "+f"(d[51]), "+f"(d[52]), "+f"(d[53]), "+f"(d[54]), "+f"(d[55]), "+f"(d[56]), "+f"(d[57]),
        "+f"(d[58]), "+f"(d[59]), "+f"(d[60]), "+f"(d[61]), "+f"(d[62]), "+f"(d[63])
        : "r"(a0), "r"(a1), "r"(a2), "r"(a3), "l"(db), "r"(scale_d));
}
__device__ __forceinline__ void wgmma_ss_n128_tb_init(float (&d)[64], uint64_t da, uint64_t db) {
    asm volatile("{\n.reg .pred p;\n"
        "setp.ne.b32 p, 0, 0;\n"
        "wgmma.mma_async.sync.aligned.m64n128k16.f32.bf16.bf16 "
        "{%0, %1, %2, %3, %4, %5, %6, %7, %8, %9, %10, %11, %12, %13, %14, %15, %16, %17, %18, %19, %20, "
        "%21, %22, %23, %24, %25, %26, %27, %28, %29, %30, %31, %32, %33, %34, %35, %36, %37, %38, %39, %40, "
        "%41, %42, %43, %44, %45, %46, %47, %48, %49, %50, %51, %52, %53, %54, %55, %56, %57, %58, %59, %60, "
        "%61, %62, %63},"
        " %64, %65, p, 1, 1, 0, 1;\n}\n"
        : "=f"(d[0]), "=f"(d[1]), "=f"(d[2]), "=f"(d[3]), "=f"(d[4]), "=f"(d[5]), "=f"(d[6]), "=f"(d[7]),
        "=f"(d[8]), "=f"(d[9]), "=f"(d[10]), "=f"(d[11]), "=f"(d[12]), "=f"(d[13]), "=f"(d[14]), "=f"(d[15]),
        "=f"(d[16]), "=f"(d[17]), "=f"(d[18]), "=f"(d[19]), "=f"(d[20]), "=f"(d[21]), "=f"(d[22]),
        "=f"(d[23]), "=f"(d[24]), "=f"(d[25]), "=f"(d[26]), "=f"(d[27]), "=f"(d[28]), "=f"(d[29]),
        "=f"(d[30]), "=f"(d[31]), "=f"(d[32]), "=f"(d[33]), "=f"(d[34]), "=f"(d[35]), "=f"(d[36]),
        "=f"(d[37]), "=f"(d[38]), "=f"(d[39]), "=f"(d[40]), "=f"(d[41]), "=f"(d[42]), "=f"(d[43]),
        "=f"(d[44]), "=f"(d[45]), "=f"(d[46]), "=f"(d[47]), "=f"(d[48]), "=f"(d[49]), "=f"(d[50]),
        "=f"(d[51]), "=f"(d[52]), "=f"(d[53]), "=f"(d[54]), "=f"(d[55]), "=f"(d[56]), "=f"(d[57]),
        "=f"(d[58]), "=f"(d[59]), "=f"(d[60]), "=f"(d[61]), "=f"(d[62]), "=f"(d[63])
        : "l"(da), "l"(db));
}
__device__ __forceinline__ void wgmma_ss_n128_tb(float (&d)[64], uint64_t da, uint64_t db, int scale_d) {
    asm volatile("{\n.reg .pred p;\n"
        "setp.ne.b32 p, %66, 0;\n"
        "wgmma.mma_async.sync.aligned.m64n128k16.f32.bf16.bf16 "
        "{%0, %1, %2, %3, %4, %5, %6, %7, %8, %9, %10, %11, %12, %13, %14, %15, %16, %17, %18, %19, %20, "
        "%21, %22, %23, %24, %25, %26, %27, %28, %29, %30, %31, %32, %33, %34, %35, %36, %37, %38, %39, %40, "
        "%41, %42, %43, %44, %45, %46, %47, %48, %49, %50, %51, %52, %53, %54, %55, %56, %57, %58, %59, %60, "
        "%61, %62, %63},"
        " %64, %65, p, 1, 1, 0, 1;\n}\n"
        : "+f"(d[0]), "+f"(d[1]), "+f"(d[2]), "+f"(d[3]), "+f"(d[4]), "+f"(d[5]), "+f"(d[6]), "+f"(d[7]),
        "+f"(d[8]), "+f"(d[9]), "+f"(d[10]), "+f"(d[11]), "+f"(d[12]), "+f"(d[13]), "+f"(d[14]), "+f"(d[15]),
        "+f"(d[16]), "+f"(d[17]), "+f"(d[18]), "+f"(d[19]), "+f"(d[20]), "+f"(d[21]), "+f"(d[22]),
        "+f"(d[23]), "+f"(d[24]), "+f"(d[25]), "+f"(d[26]), "+f"(d[27]), "+f"(d[28]), "+f"(d[29]),
        "+f"(d[30]), "+f"(d[31]), "+f"(d[32]), "+f"(d[33]), "+f"(d[34]), "+f"(d[35]), "+f"(d[36]),
        "+f"(d[37]), "+f"(d[38]), "+f"(d[39]), "+f"(d[40]), "+f"(d[41]), "+f"(d[42]), "+f"(d[43]),
        "+f"(d[44]), "+f"(d[45]), "+f"(d[46]), "+f"(d[47]), "+f"(d[48]), "+f"(d[49]), "+f"(d[50]),
        "+f"(d[51]), "+f"(d[52]), "+f"(d[53]), "+f"(d[54]), "+f"(d[55]), "+f"(d[56]), "+f"(d[57]),
        "+f"(d[58]), "+f"(d[59]), "+f"(d[60]), "+f"(d[61]), "+f"(d[62]), "+f"(d[63])
        : "l"(da), "l"(db), "r"(scale_d));
}

enum { M_X = 0, M_C, M_WQ, M_WUK, M_WUV, M_WQKV, M_WO, M_WOB, M_SCR_LD, M_SCR_LOC, M_SCR_LOQ, M_SCR_ST, M_OUT, M_COUNT };
enum { T_Q = 0, T_K, T_V, T_B, T_OUT, T_LOCAL, T_ATTN, T_END };
constexpr int NCTA = 132;
constexpr int NITEMS = 256;
constexpr int TRIPLES = 2, WIDE = 80 - 3 * TRIPLES;
struct Params {
    CUtensorMap m[M_COUNT];
    const __nv_bfloat16* x;
    const __nv_bfloat16* gate_w;
    const char* wo;
    __nv_bfloat16* out;
    uint32_t zero;
    uint16_t plan[10][16];
    uint16_t items[NITEMS];
    uint8_t ostep[80];
};
__device__ __forceinline__ int item_type(int it) { return it >> 13; }
__device__ __forceinline__ int item_row(int it) { return it & 15; }
__device__ __forceinline__ int item_col(int it) { return (it >> 4) & 31; }
__device__ __forceinline__ int item_asc(int it) { return (it >> 9) & 1; }
constexpr int ITEM_READY = 1 << 10;

struct __align__(128) Sync {
    unsigned long long count[4];
    __align__(128) unsigned long long ctx[16];
    unsigned next, next_out, done;
    __align__(128) unsigned step[32][2];
    unsigned split[32];
};
__device__ Sync g_sync;

constexpr uint32_t GST_BYTES = 49152, SM_KV = 65536, SM_STAGING = 196608, SM_BARS = SM_STAGING + 32768;
constexpr uint32_t B_GFULL = 0, B_GEMPTY = 32, B_AFULL = 64, B_AEMPTY = 112, B_SFULL = 160, B_SEMPTY = 192,
                   B_IFULL = 224, B_IEMPTY = 288, B_XFREE = 352, B_WANT = 384, B_MEET = 392, B_HALF = 416,
                   SM_ORDY = 448, SM_QUEUE = 456, B_ALT = 488, B_QFREE = 504, SM_GATE = 512, SM_TOTAL = SM_BARS + 1536;
constexpr int QDEPTH = 8;
constexpr int FIRST_PAIR = 6;
constexpr int K_MEET = 16, K_SPLIT = 30;
constexpr int K_FETCH = 20;
constexpr uint32_t LOC_PLANE = 72 * 128;
constexpr float LOC_SCALE = 0.17677669529663687f * 1.4426950408889634f;
constexpr float SUM_LIMIT = 1152921504606846976.f;
constexpr float REF_RANGE = 32.f;

__device__ __forceinline__ unsigned ld_acquire(const unsigned* p) {
    unsigned v; asm volatile("ld.acquire.gpu.global.u32 %0, [%1];" : "=r"(v) : "l"(p) : "memory"); return v;
}
__device__ __forceinline__ unsigned long long ld_acquire(const unsigned long long* p) {
    unsigned long long v; asm volatile("ld.acquire.gpu.global.u64 %0, [%1];" : "=l"(v) : "l"(p) : "memory"); return v;
}
__device__ __forceinline__ void spin_guard(unsigned& n) {
    asm volatile("{\n.reg .pred P;\nadd.u32 %0, %0, 1;\nsetp.gt.u32 P, %0, 16777216;\n@P trap;\n}\n" : "+r"(n));
    if (n > 1) __nanosleep(100);
}
__device__ __forceinline__ void red_add(unsigned long long* p, unsigned long long v) {
    asm volatile("red.release.gpu.global.add.u64 [%0], %1;" :: "l"(p), "l"(v) : "memory");
}
__device__ __forceinline__ float rcp(float x) { float y; asm("rcp.approx.ftz.f32 %0, %1;" : "=f"(y) : "f"(x)); return y; }
__device__ __forceinline__ float lds_f32(uint32_t addr) {
    float v; asm volatile("ld.shared.f32 %0, [%1];" : "=f"(v) : "r"(addr) : "memory"); return v;
}
__device__ __forceinline__ void ldsm_x4(uint32_t (&r)[4], uint32_t addr) {
    asm volatile("ldmatrix.sync.aligned.m8n8.x4.shared.b16 {%0, %1, %2, %3}, [%4];"
                 : "=r"(r[0]), "=r"(r[1]), "=r"(r[2]), "=r"(r[3]) : "r"(addr) : "memory");
}
__device__ __forceinline__ void ldsm_x4_t(uint32_t (&r)[4], uint32_t addr) {
    asm volatile("ldmatrix.sync.aligned.m8n8.x4.trans.shared.b16 {%0, %1, %2, %3}, [%4];"
                 : "=r"(r[0]), "=r"(r[1]), "=r"(r[2]), "=r"(r[3]) : "r"(addr) : "memory");
}
__device__ __forceinline__ void mma_k16(float (&d)[4], const uint32_t (&a)[4], uint32_t b0, uint32_t b1) {
    asm("mma.sync.aligned.m16n8k16.row.col.f32.bf16.bf16.f32 {%0,%1,%2,%3}, {%4,%5,%6,%7}, {%8,%9}, {%0,%1,%2,%3};"
        : "+f"(d[0]), "+f"(d[1]), "+f"(d[2]), "+f"(d[3]) : "r"(a[0]), "r"(a[1]), "r"(a[2]), "r"(a[3]), "r"(b0), "r"(b1));
}
__device__ __forceinline__ void mma_k16_init(float (&d)[4], const uint32_t (&a)[4], uint32_t b0, uint32_t b1) {
    asm("{\n.reg .f32 z;\nmov.f32 z, 0f00000000;\n"
        "mma.sync.aligned.m16n8k16.row.col.f32.bf16.bf16.f32 {%0,%1,%2,%3}, {%4,%5,%6,%7}, {%8,%9}, {z,z,z,z};\n}\n"
        : "=f"(d[0]), "=f"(d[1]), "=f"(d[2]), "=f"(d[3]) : "r"(a[0]), "r"(a[1]), "r"(a[2]), "r"(a[3]), "r"(b0), "r"(b1));
}
__device__ __forceinline__ void mma_k8(float (&d)[4], uint32_t a0, uint32_t a1, uint32_t b0) {
    asm("mma.sync.aligned.m16n8k8.row.col.f32.bf16.bf16.f32 {%0,%1,%2,%3}, {%4,%5}, {%6}, {%0,%1,%2,%3};"
        : "+f"(d[0]), "+f"(d[1]), "+f"(d[2]), "+f"(d[3]) : "r"(a0), "r"(a1), "r"(b0));
}
template <typename T, int N> __device__ __forceinline__ void zero_regs(T (&d)[N]) {
#pragma unroll
    for (int i = 0; i < N; i++) d[i] = 0;
}
__device__ __forceinline__ float quad_max(float v) {
    v = fmaxf(v, __shfl_xor_sync(0xffffffffu, v, 1));
    return fmaxf(v, __shfl_xor_sync(0xffffffffu, v, 2));
}
__device__ __forceinline__ float quad_sum(float v) {
    v += __shfl_xor_sync(0xffffffffu, v, 1);
    return v + __shfl_xor_sync(0xffffffffu, v, 2);
}

__device__ __forceinline__ void qk_gemm(float (&s)[64], uint32_t q_lo, uint32_t k_lo) {
    const uint64_t dq = full_desc(q_lo), dk = full_desc(k_lo);
    wgmma_fence();
    wgmma_ss_n128_init(s, dq, dk);
#pragma unroll
    for (int kk = 1; kk < 8; kk++) {
        const uint32_t o = (kk >> 2) * 1024 + (kk & 3) * 2;
        wgmma_ss_n128(s, dq + o, dk + o, 1);
    }
    wgmma_commit();
}
__device__ __forceinline__ void pv_gemm(float (&o)[64], uint32_t (&p)[32], uint32_t v_lo, int accumulate) {
    const uint64_t dv = full_desc(v_lo);
    fence_regs(o);
    fence_regs(p);
    wgmma_fence();
#pragma unroll
    for (int kk = 0; kk < 8; kk++)
        wgmma_rs_n128_tb(o, p[4 * kk], p[4 * kk + 1], p[4 * kk + 2], p[4 * kk + 3], dv + kk * 128, kk != 0 || accumulate);
    wgmma_commit();
}
__device__ __forceinline__ void row_max(const float (&s)[64], float& x0, float& x1) {
    float z0 = fmaxf(s[0], s[1]), z1 = fmaxf(s[2], s[3]);
    x0 = fmaxf(s[4], s[5]); x1 = fmaxf(s[6], s[7]);
#pragma unroll
    for (int j = 2; j < 16; j += 2) {
        z0 = fmaxf(z0, fmaxf(s[4 * j], s[4 * j + 1]));
        z1 = fmaxf(z1, fmaxf(s[4 * j + 2], s[4 * j + 3]));
        x0 = fmaxf(x0, fmaxf(s[4 * j + 4], s[4 * j + 5]));
        x1 = fmaxf(x1, fmaxf(s[4 * j + 6], s[4 * j + 7]));
    }
    x0 = quad_max(fmaxf(x0, z0)); x1 = quad_max(fmaxf(x1, z1));
}
__device__ __forceinline__ void exp_pack(uint32_t (&p)[32], const float (&s)[64], float& r0, float& r1) {
#pragma unroll
    for (int j = 0; j < 16; j++) {
        const float e0 = ex2(s[4 * j]), e1 = ex2(s[4 * j + 1]), e2 = ex2(s[4 * j + 2]), e3 = ex2(s[4 * j + 3]);
        if (j == 0) { r0 = e0 + e1; r1 = e2 + e3; }
        else { r0 += e0 + e1; r1 += e2 + e3; }
        p[2 * j] = pack_bf16(e0, e1);
        p[2 * j + 1] = pack_bf16(e2, e3);
    }
}
__device__ __forceinline__ void shift_rows(float (&s)[64], float d0, float d1) {
#pragma unroll
    for (int j = 0; j < 16; j++) { s[4 * j] -= d0; s[4 * j + 1] -= d0; s[4 * j + 2] -= d1; s[4 * j + 3] -= d1; }
}
constexpr float MASKED = -3e38f;
template <int J0>
__device__ __forceinline__ void mask_triangle(float (&s)[64], float thr) {
#pragma unroll
    for (int j = 0; j < 16; j++) {
        const float m = __saturatef((float)(8 * (j >> 1) + (j & 1)) - thr);
        const int i = 4 * (J0 + (j >> 1)) + (j & 1);
        s[i] = fmaf(m, MASKED, s[i]);
        if (j < 14) s[i + 6] = fmaf(m, MASKED, s[i + 6]);
    }
}
__device__ __forceinline__ void causal_mask(float (&s)[64], float thr, int wg) {
    asm volatile("" : "+f"(thr));
    if (wg == 0) {
        mask_triangle<0>(s, thr);
#pragma unroll
        for (int j = 32; j < 64; j++) s[j] += MASKED;
    } else {
        mask_triangle<8>(s, thr);
    }
}

__global__ void __cluster_dims__(2, 1, 1) __launch_bounds__(384, 1) fused_kernel(const __grid_constant__ Params prm) {
    extern __shared__ __align__(1024) uint8_t smem[];
    const uint32_t sb = smem_u32(smem), bars = sb + SM_BARS;
    const int warp = __shfl_sync(0xffffffffu, threadIdx.x >> 5, 0), lane = threadIdx.x & 31;

    const uint32_t rank = cluster_rank();
    const uint32_t bars0 = map_cta(bars, 0), bars_peer = map_cta(bars, rank ^ 1);

    auto plan_index = [&]() -> uint32_t {
        uint32_t p = blockIdx.x >> 1;
        asm volatile("" : "+r"(p));
        const uint32_t r = (p - 36) * 37 >> 8;
        return p < 4 ? 60 + p : p < 36 ? (p - 4 & 7) * 8 + (p - 4 >> 3) : p < 64 ? (p - 36 - 7 * r) * 8 + 4 + r : p;
    };
    auto first_item = [&]() -> int {
        const uint32_t pair = plan_index();
        const uint32_t slot = pair & 7, c = slot * 11 >> 5;
        return pair < 64 ? T_B << 13 | (4 * slot - 11 * c) << 4 | (2 * (pair >> 3) + rank) : T_K << 13 | (8 * slot + rank);
    };
    if (warp == 0) {
        if (elect_one()) {
            for (int k = 0; k < 4; k++) mbar_init(bars + B_GFULL + 8 * k, 1);
            asm volatile("fence.mbarrier_init.release.cluster;" ::: "memory");
            fence_proxy_async_smem();
        }
        __syncwarp();
        const int first_it = __shfl_sync(0xffffffffu, first_item(), 0);
        asm volatile("barrier.cluster.arrive.relaxed.aligned;" ::: "memory");
        const CUtensorMap* ma = &prm.m[item_type(first_it) == T_K ? M_C : M_X];
        const CUtensorMap* mb = &prm.m[M_WQ + item_type(first_it)];
#pragma unroll
        for (int k = 0; k < 2; k++) {
            const uint32_t dst = sb + k * GST_BYTES, fb = bars + B_GFULL + 8 * k;
            warp_expect_tx(fb, GST_BYTES);
            warp_tma_load(dst + 16384, mb, fb, 0, k * 64, item_col(first_it) * 4, true);
            warp_tma_load(dst, ma, fb, k * 64, item_row(first_it) * 128, 0, false);
            warp_tma_load(dst + 32768, mb, fb, 0, k * 64, item_col(first_it) * 4 + 2, true);
        }
    }
    if (threadIdx.x == 32) {
        for (int i = 0; i < 4; i++) mbar_init(bars + B_GEMPTY + 8 * i, 16);
        for (int i = 0; i < 6; i++) { mbar_init(bars + B_AFULL + 8 * i, 1); mbar_init(bars + B_AEMPTY + 8 * i, i < 2 ? 8 : 16); }
        for (int i = 0; i < 4; i++) { mbar_init(bars + B_SFULL + 8 * i, 4); mbar_init(bars + B_SEMPTY + 8 * i, 1); }
        for (int i = 0; i < QDEPTH; i++) { mbar_init(bars + B_IFULL + 8 * i, 1); mbar_init(bars + B_IEMPTY + 8 * i, 23); }
        mbar_init(bars + B_WANT, 2); mbar_init(bars + B_MEET, 1); mbar_init(bars + B_XFREE, 1);
        for (int i = 0; i < 4; i++) mbar_init(bars + B_HALF + 8 * i, 1);
        mbar_init(bars + B_ALT, 4); mbar_init(bars + B_ALT + 8, 4); mbar_init(bars + B_QFREE, 2);
        asm volatile("st.shared.u64 [%0], 0;" :: "r"(bars + SM_ORDY) : "memory");
        asm volatile("fence.mbarrier_init.release.cluster;\nfence.acq_rel.cta;" ::: "memory");
    }
    __syncwarp();
    if (warp != 0) asm volatile("barrier.cluster.arrive.relaxed.aligned;" ::: "memory");
    asm volatile("barrier.cluster.wait.acquire.aligned;" ::: "memory");

    uint32_t qn = 0;
    auto next_item = [&](bool releaser, bool bounded = true) -> int {
        const uint32_t slot = qn % QDEPTH;
        if (bounded) mbar_wait(bars + B_IFULL + 8 * slot, (qn / QDEPTH) & 1);
        else mbar_spin(bars + B_IFULL + 8 * slot, (qn / QDEPTH) & 1);
        uint32_t it;
        asm volatile("ld.shared.u32 %0, [%1];" : "=r"(it) : "r"(bars + SM_QUEUE + 4 * slot) : "memory");
        mbar_arrive_cluster_if(releaser, bars0 + B_IEMPTY + 8 * slot);
        qn++;
        return it;
    };

    if (warp < 4) {
        reg_dec<40>();
        if (warp == 0) {
            {
                uint32_t gph = 1;
                const uint32_t prank = __shfl_sync(0xffffffffu, rank, 0);
                auto request = [&]() { mbar_arrive_cluster_if(lane == 0, bars0 + B_WANT); };
                auto take_item = [&]() -> int { return __shfl_sync(0xffffffffu, next_item(lane == 0), 0); };
                auto inputs_seen = [&](uint32_t word, unsigned& n) -> uint32_t {
                    uint32_t v;
                    spin_guard(n);
                    asm volatile("ld.acquire.cta.shared.u32 %0, [%1];" : "=r"(v) : "r"(bars + SM_ORDY + 4 * word) : "memory");
                    return __shfl_sync(0xffffffffu, v, 0);
                };
                uint32_t oneed = 0;
                auto wait_inputs = [&](int it) {
                    if (it & ITEM_READY) return;
                    oneed += 256;
                    for (unsigned n = 0; inputs_seen(1, n) < oneed;) {}
                };
                int nxt = first_item(), ring = -1, rot = 0;
                for (int k0 = 2; item_type(nxt) <= T_LOCAL; k0 = 0) {
                    const int type = item_type(nxt), m = item_row(nxt), c = item_col(nxt);
                    if (type == T_LOCAL) {
                        wait_inputs(nxt);
                        request();
#pragma unroll 1
                        for (uint32_t st = 0; st < 4; st++) {
                            mbar_wait(bars + B_GEMPTY + 8 * st, gph);
                            const uint32_t dst = sb + st * GST_BYTES, fb = bars + B_GFULL + 8 * st;
                            warp_expect_tx(fb, st == 0 ? 32768 + 512 : st == 3 ? 0 : 4 * LOC_PLANE);
                            if (st == 3) break;
                            if (st == 0) warp_bulk_load(dst + 4 * LOC_PLANE, &g_gate[m * 128], 512, fb);
#pragma unroll 1
                            for (int i = 0; i < 4; i++)
                                warp_tma_load(dst + i * LOC_PLANE, &prm.m[st ? M_SCR_LOC : M_SCR_LOQ], fb, i * 64, m * 64 - (st ? 8 : 0), G_B + 8 * st + c, true);
                        }
                        gph ^= 1;
                        ring = -1;
                    } else {
                        const int nk = type == T_K || type == T_V ? 8 : 16, kept = ring == m + 16 * nk ? 4 : 0;
                        ring = m + 16 * nk;
                        rot = kept ? rot - 4 : 0;
                        const CUtensorMap* ma = &prm.m[nk == 8 ? M_C : M_X];
                        const CUtensorMap* mb = &prm.m[M_WQ + type];
#pragma unroll 1
                        for (int k = k0; k < nk; k++) {
                            if (k == nk - 3) request();
                            const uint32_t st = k & 3, dst = sb + st * GST_BYTES, fb = bars + B_GFULL + 8 * st;
                            const int kc = ((k + rot) & (nk - 1)) * 64;
                            mbar_wait(bars + B_GEMPTY + 8 * st, gph);
                            warp_expect_tx(fb, k < kept ? 32768 : GST_BYTES);
                            if (k >= kept) warp_tma_load(dst, ma, fb, kc, m * 128, 0, c == 15 && type != T_K);
                            warp_tma_load_pair(dst + 16384 + prank * 16384, mb, fb, 0, kc, c * 4 + 2 * prank, true);
                            if (st == 3) gph ^= 1;
                        }
                    }
                    nxt = take_item();
                }
                uint32_t kv = 0, kvph = 1;
                uint32_t qc = 0;
                auto a_parity = [&](uint32_t b) { return b < 2 ? (((qc + 1 - b) >> 1) & 1) ^ 1 : kvph ^ (b - 2 < kv); };
                const CUtensorMap* tile_map = &prm.m[M_SCR_LD];
                asm volatile("" : "+l"(tile_map));
                {
                    bool need_g = true, more = true;
                    int pv_grp = -1, pv_row = 0;
                    int pv_shared = 0;
                    bool peer_longer = false;
                    int m = 0, c = 0, asc = 0, nu = 0, uend = 0, ureq = -1, ufetch = 0;
#pragma unroll 1
                    for (int u = 0;; u++) {
                        if (u == ufetch) {
                            if (qc) nxt = take_item();
                            if (item_type(nxt) == T_ATTN) {
                                wait_inputs(nxt);
                                const uint32_t b = qc & 1, dst = sb + b * 32768, fb = bars + B_AFULL + 8 * b, row = item_row(nxt) * 128;
                                mbar_wait(bars + (qc == 0 ? B_GEMPTY : qc == 1 ? B_QFREE : B_AEMPTY + 8 * b), qc == 0 ? gph : qc == 1 ? 0 : a_parity(b));
                                warp_expect_tx(fb, 32768 + 512);
                                warp_tma_load(dst, tile_map, fb, 0, row, G_Q + item_col(nxt), false);
                                warp_tma_load(dst + 16384, tile_map, fb, 64, row, G_Q + item_col(nxt), false);
                                warp_bulk_load(bars + SM_GATE + b * 512, &g_gate[row], 512, fb);
                                qc++;
                            }
                        }
                        if (u == uend) {
                            if (!more) break;
                            more = item_type(nxt) == T_ATTN;
                            m = item_row(nxt); c = item_col(nxt); asc = item_asc(nxt);
                            nu = more ? 2 * m + 2 : 0;
                            uend = nu + ((more ? m < 2 : pv_grp >= 0) ? 3 : 0);
                            ureq = 2 * max(m - 2 - (asc & m), 0);
                            ufetch = !more ? -1 : m ? 2 * m : uend;
                            u = -1;
                            continue;
                        }
                        int grp = pv_grp, row = pv_row;
                        int shared = pv_shared;
                        if (u >= nu) {
                            if (u == nu + 1) pv_grp = -1;
                            else if (peer_longer) { grp = -1; shared = 0; }
                            else continue;
                        } else {
                            const int j = asc ? u >> 1 : m - (u >> 1);
                            if (u & 1) {
                                pv_grp = G_V + c; pv_row = j * 128; pv_shared = (m | 1) - j;
                                peer_longer = asc & ~m & 1;
                                if (u == nu - 1 && (m & 1) && item_type(nxt) == T_END) mbar_arrive_cluster_n_if(lane == 0, bars0 + B_WANT, 2);
                                if (grp < 0) continue;
                            } else {
                                if (u == ureq) request();
                                grp = G_K + c; row = j * 128; shared = (m | 1) - j;
                            }
                        }
                        uint32_t fb = bars + B_AFULL + 16 + 8 * kv, mine = sb + SM_KV + kv * 32768 + prank * 16384;
                        int c_mine = prank * 64;
                        asm volatile("" : "+r"(mine), "+r"(fb), "+r"(row), "+r"(grp), "+r"(c_mine));
                        mbar_wait(need_g ? bars + B_GEMPTY + 8 + 8 * kv : fb + B_AEMPTY - B_AFULL, need_g ? gph : kvph);
                        warp_expect_tx(fb, grp < 0 ? 0 : 32768);
                        if (shared) {
                            warp_tma_load_pair(mine, tile_map, fb, c_mine, row, grp, shared == 1);
                        } else if (grp >= 0) {
                            warp_tma_load(mine, tile_map, fb, c_mine, row, grp, true);
                            warp_tma_load(mine + 16384 - prank * 32768, tile_map, fb, 64 - c_mine, row, grp, true);
                        } else {
                            mbar_arrive_cluster_n_if(lane < 2, map_cta(fb, lane & 1) + B_AEMPTY - B_AFULL, 8);
                        }
                        if (kv == 2) need_g = false;
                        if (++kv == 4) { kv = 0; kvph ^= 1; }
                    }
                }
                if (!qc) request();
                const int it = take_item();
                int nk = 0;
                if (item_type(it) == T_OUT) {
                    const int m = item_row(it), c = item_col(it), half = c & 1;
                    nk = 80;
                    for (unsigned n = 0; (inputs_seen(1, n) & 255) != 255;) {}
                    mbar_wait(bars + B_GEMPTY + 24, gph);
                    mbar_wait(bars + B_QFREE, 0);
                    mbar_wait(bars + B_AEMPTY + 8 * (qc & 1), a_parity(qc & 1));
#pragma unroll 1
                    for (uint32_t k = 0; k < 4; k++) {
                        const uint32_t sa = prm.ostep[half ? WIDE - 1 - k : k], dst = sb + k * GST_BYTES, fb = bars + B_GFULL + 8 * k;
                        const uint32_t b0 = k ? 1 + k : ~qc & 1, b1 = 2 + k - (k == 1);
                        mbar_wait(bars + B_AEMPTY + 8 * b0, a_parity(b0));
                        mbar_arrive_cluster_if(lane == 0 && !k, bars_peer + B_XFREE);
                        warp_expect_tx(fb, GST_BYTES);
                        warp_tma_load(dst, tile_map, fb, (sa & 1) * 64, m * 128, G_LOC - 32 + (sa >> 1), true);
                        mbar_wait(bars + (k ? B_AEMPTY + 8 * b1 : B_XFREE), k ? kvph ^ (b1 - 2 < kv) : 0);
                        warp_tma_load_pair(dst + 16384 + prank * 16384, &prm.m[M_WOB], fb, 0, (sa & 63) * 64, (c >> 1) * 4 + 2 * (half ^ prank), false);
                    }
                    gph ^= 1;
                    uint32_t seen = 0;
                    for (int k = 4; k < nk; k++) {
                        if (k == K_SPLIT) nk = 2 * TRIPLES + (take_item() & 127);
                        const int kn = k + 2 * TRIPLES - nk, first = kn >= 0 && !(kn & 1);
                        const int s = kn >= 0 ? WIDE + (3 * kn + 1) / 2 : half ? WIDE - 1 - k : k;
                        const uint32_t sa = prm.ostep[s], sa2 = prm.ostep[s + first], sw = prm.ostep[s - (kn >= 0 && !first ? prank : 0)];
                        const uint32_t need = 1u << (sa >> 1 & 31) | 1u << (sa2 >> 1 & 31);
                        for (unsigned n = 0; sa < 64 && (need & ~seen);) seen = inputs_seen(0, n);
                        const uint32_t st = k & 3;
                        uint32_t dst = sb + st * GST_BYTES, fb = bars + B_GFULL + 8 * st;
                        uint32_t dstb = dst + 16384 + (first ? 0 : prank * 16384), skipb = first && (kn >> 1 & 1) != prank;
                        int a0 = (sa & 1) * 64, a1 = m * 128, a2 = (sa >> 1) + (sa < 64 ? G_CTX : G_LOC - 32);
                        int b1 = (sw & 63) * 64, b2 = (c >> 1) * 4 + 2 * (kn >= 0 ? half : half ^ prank);
                        const CUtensorMap* mb = &prm.m[sw >= 64 ? M_WOB : M_WO];
                        asm volatile("" : "+r"(dst), "+r"(fb), "+r"(dstb), "+r"(skipb), "+r"(a0), "+r"(a1), "+r"(a2), "+r"(b1), "+r"(b2), "+l"(mb));
                        mbar_wait(bars + B_GEMPTY + 8 * st, gph);
                        warp_expect_tx(fb, GST_BYTES);
                        warp_tma_load(dst, tile_map, fb, a0, a1, a2, true);
                        if (!skipb) warp_tma_load_pair(dstb, mb, fb, 0, b1, b2, false);
                        if (first) warp_tma_load(dst + 32768, tile_map, fb, (sa2 & 1) * 64, a1, G_CTX + (sa2 >> 1), true);
                        if (k < K_SPLIT && lane == 0 && !prank)
                            asm volatile("st.relaxed.gpu.global.u32 [%0], %1;" :: "l"(&g_sync.step[0][0] + m * 4 + c), "r"(k) : "memory");
                        mbar_arrive_if(k == K_MEET && lane == 0, bars + B_MEET);
                        if ((uint32_t)(k - K_FETCH) < (3 * TRIPLES + 1) / 2) {
                            const uint32_t g = prm.ostep[79 - 2 * (k - K_FETCH)] >> 1;
                            warp_prefetch((const char*)g_scr + (uint32_t)((G_CTX + g) * (SEQ * 256) + m * 32768 + c * 4096), 4096);
                            warp_prefetch(prm.wo + (uint32_t)(g * 262144 + (m * 8 + c) * 2048), 2048);
                        }
                        if (st == 3) gph ^= 1;
                    }
                    for (unsigned n = 0; ~inputs_seen(0, n);) {}
                }
#pragma unroll 1
                for (uint32_t st = 0; st < 4; st++) { mbar_wait(bars + B_GEMPTY + 8 * st, gph ^ (st < (nk & 3))); mbar_wait(bars + B_AEMPTY + 16 + 8 * st, a_parity(2 + st)); }
                unsigned left = 0;
                if (lane == 0) asm volatile("atom.relaxed.gpu.global.add.u32 %0, [%1], 1;" : "=r"(left) : "l"(&g_sync.done) : "memory");
                if (__shfl_sync(0xffffffffu, left, 0) == NCTA - 1)
#pragma unroll 1
                    for (uint32_t i = lane * 8; i < sizeof(Sync); i += 256) *(unsigned long long*)((char*)&g_sync + i) = 0;
            }
        } else if (warp <= 2) {
            if (blockIdx.x < SEQ / 16) {
                const uint32_t r0 = 16 * blockIdx.x + 8 * (warp - 1), gbuf = bars + SM_GATE + 4 * (r0 & 15);
                float z[4];
                mbar_wait(bars + B_GFULL + 24, 0);
#pragma unroll 1
                for (uint32_t i = 0; i < 8; i++) {
                    const uint32_t off = (i & 3) * 512 + lane * 16;
                    const uint4* xp = (const uint4*)((const char*)prm.x + ((r0 + (i & 4)) * 2048 + off));
                    const uint4 wv = __ldg((const uint4*)((const char*)prm.gate_w + off));
                    uint4 xv[4];
#pragma unroll
                    for (int r = 0; r < 4; r++) { xv[r] = __ldg(xp + r * 128); if (!(i & 3)) z[r] = 0.f; }
                    const uint32_t ws[4] = {wv.x, wv.y, wv.z, wv.w};
#pragma unroll
                    for (int e = 0; e < 4; e++)
#pragma unroll
                        for (int r = 0; r < 4; r++) {
                            const uint32_t xs = e == 0 ? xv[r].x : e == 1 ? xv[r].y : e == 2 ? xv[r].z : xv[r].w;
                            z[r] = fmaf(__uint_as_float(xs << 16), __uint_as_float(ws[e] << 16), z[r]);
                            z[r] = fmaf(__uint_as_float(xs & 0xffff0000u), __uint_as_float(ws[e] & 0xffff0000u), z[r]);
                        }
                    if ((i & 3) == 3) {
#pragma unroll
                        for (int o = 16; o > 0; o >>= 1)
#pragma unroll
                            for (int r = 0; r < 4; r++) z[r] += __shfl_xor_sync(0xffffffffu, z[r], o);
                        const float zr = lane & 2 ? (lane & 1 ? z[3] : z[2]) : (lane & 1 ? z[1] : z[0]);
                        asm volatile("st.shared.f32 [%0], %1;" :: "r"(gbuf + 4 * ((i & 4) + (lane & 3))), "f"(1.f / (1.f + __expf(-zr))) : "memory");
                    }
                }
                fence_proxy_async_smem();
                __syncwarp();
                warp_bulk_store((char*)g_gate + 4 * r0, gbuf, 32);
                bulk_commit();
                bulk_wait<0>();
                __syncwarp();
                if (lane == 0) red_add(&g_sync.count[3], 1);
            }
            __syncwarp();
            {
                const int w = warp - 1;
                uint32_t sph = 0, nann = 0;
                int unsent = 0, nunsent = 0;
                bool urgent = false;
                auto announce = [&]() {
                    if (!urgent) return;
                    bulk_wait<0>();
                    __syncwarp();
                    const uint32_t hb = bars + B_HALF + 8 * (nann & 3);
                    if (w == 0) {
                        mbar_arrive_if(lane == 0, hb);
                    } else {
                        mbar_wait(hb, (nann >> 2) & 1);
                        const uint32_t type = item_type(unsent), m = item_row(unsent), c = item_col(unsent);
                        const uint32_t word = type < T_B ? c >> 3 : type == T_B ? 2 : offsetof(Sync, ctx) / 8 + m;
                        const uint32_t bit = type < T_B ? 8 * (c & 7) : type == T_B ? 8 * (c & 3) : type == T_LOCAL ? 32 + c : c;
                        if (lane < nunsent) red_add((unsigned long long*)((char*)&g_sync + 8 * word), 1ull << bit);
                        __syncwarp();
                    }
                    nann++;
                    nunsent = 0; urgent = false;
                };
                int held = first_item(), it;
                bool qfree = false;
                do {
                    if (!__all_sync(0xffffffffu, mbar_test(bars + B_IFULL + 8 * (qn % QDEPTH), (qn / QDEPTH) & 1))) announce();
                    it = __shfl_sync(0xffffffffu, next_item(lane == 0), 0);
                    const int itype = item_type(it);
                    const bool keep_held = itype == T_LOCAL;
                    if (itype >= T_ATTN && held < 0) {
                        urgent = nunsent;
                        mbar_arrive_if(lane == 0 && !qfree, bars + B_QFREE);
                        qfree = true;
                    }
#pragma unroll 1
                    for (int pass = held < 0 || keep_held; pass < 2; pass++) {
                        if (pass && (itype < T_OUT || itype == T_END)) break;
                        const int cur = pass ? it : held, type = item_type(cur), m = item_row(cur), c = item_col(cur);
                        const bool local = type == T_LOCAL;
                        const int grp = pass ? (local ? G_LOC : G_CTX) + c : type * 32 + 2 * c;
#pragma unroll 1
                        for (int i = 0; i < 4 - 2 * pass; i++) {
                            const int b = i & 1;
                            const bool alt = i >= 2 && itype >= T_ATTN;
                            const uint32_t full = bars + (alt ? B_ALT + 8 * w : B_SFULL + 16 * w + 8 * b), par = alt ? 0 : sph;
                            if (i == 3 - 2 * pass || !__all_sync(0xffffffffu, mbar_test(full, par))) announce();
                            mbar_wait(full, par);
                            fence_proxy_async_smem();
                            warp_tma_store(&prm.m[local ? M_SCR_LOQ : M_SCR_ST], sb + (alt ? 32768 : SM_STAGING) + w * 16384 + b * 8192,
                                         local ? b * 128 + w * 64 : b * 64, local ? m * 64 : m * 128 + w * 64, grp + (i >> 1), local || (type < T_B && c < FIRST_PAIR));
                            bulk_commit();
                            if (pass > b) continue;
                            bulk_wait_read<0>();
                            __syncwarp();
                            mbar_arrive_if(lane <= pass && !alt, bars + B_SEMPTY + 16 * w + 8 * (b - lane));
                            sph ^= b & !alt;
                        }
                        mbar_arrive_if(lane == 0 && !qfree && itype >= T_ATTN, bars + B_QFREE);
                        qfree |= itype >= T_ATTN;
                        if (lane == nunsent) unsent = cur;
                        nunsent++;
                        urgent = nunsent == 32 || !local;
                    }
                    if (!keep_held) held = itype < T_OUT ? it : -1;
                } while (item_type(it) != T_END);
                announce();
                it = __shfl_sync(0xffffffffu, next_item(lane == 0), 0);
                if (item_type(it) == T_OUT) {
                    if (w) {
                        mbar_wait(bars + B_MEET, 0);
                        asm volatile("fence.proxy.async.global;\nfence.acq_rel.gpu;" ::: "memory");
                        mbar_arrive_cluster_if(lane == 0, bars0 + B_WANT);
                    }
                    next_item(lane == 0);
#pragma unroll 1
                    for (int i = 0; i < 4; i++) {
                        const int b = i & 1;
                        mbar_wait(bars + B_SFULL + 16 * w + 8 * b, sph ^ (i >> 1));
                        fence_proxy_async_smem();
                        warp_tma_add(&prm.m[M_OUT], sb + SM_STAGING + w * 16384 + b * 8192, (item_col(it) ^ (i < 2)) * 128 + b * 64, item_row(it) * 128 + w * 64, 0);
                        bulk_commit();
                        if (b) {
                            bulk_wait_read<0>();
                            __syncwarp();
                            mbar_arrive_if(lane < 2, bars + B_SEMPTY + 16 * w + 8 * lane);
                        }
                    }
                }
            }
        } else {
            if (elect_one()) {
                uint32_t ordy = 0;
                unsigned long long cnt_lo = 0, cnt_hi = 0;
                int late = 0;
                auto refresh = [&]() {
                    if (!late && cnt_lo == 0x30303030 && cnt_hi == SEQ / 8) late = 1;
                    asm volatile("ld.acquire.gpu.global.v2.u64 {%0, %1}, [%2];" : "=l"(cnt_lo), "=l"(cnt_hi) : "l"(late ? &g_sync.count[0] : &g_sync.count[2]) : "memory");
                };
                auto inputs_ready = [&](int it) -> bool {
                    const int c = item_col(it);
                    if (item_type(it) == T_ATTN) return late && ((c < 16 ? cnt_lo : cnt_hi) >> (4 * (c & 14)) & 255) == 48;
                    return late || (cnt_hi == SEQ / 8 && (cnt_lo >> (4 * (c & 6)) & 255) == 48);
                };
                auto publish = [&](int it, int step) {
                    const uint32_t slot = qn % QDEPTH;
                    mbar_wait(bars + B_IEMPTY + 8 * slot, ((qn / QDEPTH) & 1) ^ 1);
                    for (uint32_t r = 0; r < 2; r++) {
                        const uint32_t rb = map_cta(bars, r);
                        asm volatile("mbarrier.arrive.expect_tx.shared::cluster.b64 _, [%0], 4;" :: "r"(rb + B_IFULL + 8 * slot) : "memory");
                        asm volatile("st.async.shared::cluster.mbarrier::complete_tx::bytes.u32 [%0], %1, [%2];"
                                     :: "r"(rb + SM_QUEUE + 4 * slot), "r"(it + r * step), "r"(rb + B_IFULL + 8 * slot) : "memory");
                    }
                    qn++;
                };
                int asc = 1;
                int it;
                do {
                    if (rank == 0) {
                        mbar_wait(bars + B_WANT, qn & 1);
                        const uint32_t pair = plan_index();
                        int pit = prm.plan[pair < 64 ? pair & 7 : pair - 56][min(qn + 1, 15u)];
                        unsigned i;
                        const bool planned = item_type(pit) != T_END;
                        if (!planned) asm volatile("atom.relaxed.gpu.global.add.u32 %0, [%1], 1;" : "=r"(i) : "l"(&g_sync.next) : "memory");
                        if (cnt_lo != 0x3030303030303030ull || cnt_hi != cnt_lo) refresh();
                        if (planned) pit += (pair >> 3 & 7) << (item_type(pit) == T_LOCAL);
                        else if (i < NITEMS) pit = prm.items[i];
                        const int type = item_type(pit);
                        int step = type == T_LOCAL ? 16 : 1;
                        it = pit + (pit & (step == 1 ? 15 : 0x1f0));
                        if (type == T_ATTN) {
                            if (!asc) { it += 1; step = -1; }
                            it |= asc << 9;
                        }
                        asc = type != T_ATTN || item_row(pit) == 0 || !asc;
                        if (inputs_ready(it)) it |= ITEM_READY;
                        publish(it, step);
                    } else {
                        it = next_item(true);
                    }
                    if ((item_type(it) == T_ATTN || item_type(it) == T_LOCAL) && !(it & ITEM_READY)) {
                        unsigned n = 0;
                        while (!inputs_ready(it)) { refresh(); spin_guard(n); }
                        asm volatile("st.release.cta.shared.u32 [%0], %1;" :: "r"(bars + SM_ORDY + 4), "r"(ordy += 256) : "memory");
                    }
                } while (item_type(it) != T_END);
                if (rank == 0) {
                    mbar_wait(bars + B_WANT, qn & 1);
                    const unsigned i = atomicAdd(&g_sync.next_out, 1u), t = i < 32 ? 31 - i : i - 32;
                    it = i < 64 ? T_OUT << 13 | ((t & 3) * 2 + (i >> 5)) << 4 | (t >> 2) * 2 : T_END << 13;
                    publish(it, 1);
                } else {
                    it = next_item(true);
                }
                if (item_type(it) == T_OUT) {
                    const uint32_t m = item_row(it), half = item_col(it) & 1, tile = m * 2 + (item_col(it) >> 1);
                    unsigned* split = (unsigned*)((char*)g_sync.split + 4 * tile);
                    unsigned long long rdy = 0;
                    int state = rank ? 2 : 0;
                    for (unsigned n = 0; rdy != 0xffffffffffull || state < 2; spin_guard(n)) {
                        if (rdy != 0xffffffffffull) {
                            rdy = ld_acquire((const unsigned long long*)((char*)g_sync.ctx + 8 * m));
                            asm volatile("st.release.cta.shared.u64 [%0], %1;" :: "r"(bars + SM_ORDY), "l"(rdy) : "memory");
                        }
                        unsigned steps = 0;
                        if (state == 1) {
                            steps = ld_acquire(split);
                        } else if (state == 0 && mbar_test(bars + B_WANT, qn & 1)) {
                            state = 1;
                            unsigned seen;
                            asm volatile("atom.acq_rel.gpu.global.exch.b32 %0, [%1], 1;" : "=r"(seen) : "l"(split) : "memory");
                            if (seen) {
                                const unsigned long long v = ld_acquire((const unsigned long long*)((char*)g_sync.step + 8 * tile));
                                const int d = (int)(v >> 32) - (int)v;
                                steps = (WIDE + min(max(half ? d : -d, -12), 12)) >> 1;
                                atomicExch(split, WIDE - steps);
                            }
                        }
                        if (steps > 1) { publish(T_END << 13 | steps, 0); state = 2; }
                    }
                    if (rank) next_item(true);
                }
                #pragma unroll 1
                for (uint32_t n = qn; n < qn + QDEPTH && rank == 0; n++) mbar_wait(bars + B_IEMPTY + 8 * (n % QDEPTH), ((n / QDEPTH) & 1) ^ 1);
            }
        }
    } else {
        reg_inc<232>();
        const int wg = (warp >> 2) - 1, wq = warp & 3;
        uint32_t gph = 0;
        uint32_t kvn = 0;
        const uint32_t dA = make_desc(sb + wg * 8192, 16);
        uint32_t ti = 0;
        uint32_t sph = 1;
        const uint32_t stg = sb + SM_STAGING + wg * 16384;
        const uint32_t stg_lane = stg + (wq * 16 + (lane & 15)) * 128 + (((lane >> 4) ^ (lane & 7)) << 4);
        auto write_blocks = [&](auto n, uint32_t off, const uint32_t* v) {
            uint32_t a = stg_lane;
            asm volatile("" : "+r"(a));
            a += off;
#pragma unroll
            for (int j = 0; j < decltype(n)::value; j++)
                stmatrix_x4((a ^ (32 * (j & 3))) + (j >> 2) * 8192, v[4 * j], v[4 * j + 1], v[4 * j + 2], v[4 * j + 3]);
        };
        auto release = [&](uint32_t bar) { mbar_arrive_if(lane == 0, bars + bar); };
        const uint32_t bars_lane = map_cta(bars, lane & 1);
        auto release_stage = [&](uint32_t st) { mbar_arrive_cluster_if(lane < 2, bars_lane + B_GEMPTY + 8 * st); };
        auto take_item = [&]() -> int {
            return __shfl_sync(0xffffffffu, next_item(lane == 0, false), 0);
        };
        auto stage_acquire = [&](int b) { mbar_spin(bars + B_SEMPTY + 16 * wg + 8 * b, sph); };
        auto stage_publish = [&](int b) {
            __syncwarp();
            release(B_SFULL + 16 * wg + 8 * b);
        };
        auto stage_chunk = [&](int b, const uint32_t* v) {
            stage_acquire(b);
            write_blocks(std::integral_constant<int, 4>(), b * 8192, v);
            stage_publish(b);
            if (b) sph ^= 1;
        };
        auto publish_pair = [&]() {
            __syncwarp();
            mbar_arrive_if(lane < 2, bars + B_SFULL + 16 * wg + 8 * lane);
            sph ^= 1;
        };
        auto gemm_step = [&](float (&acc)[128], uint32_t dB, int& k, bool order) {
            const uint32_t st = k & 3;
            wgmma_wait<0>();
            release_stage((k - 1) & 3);
            mbar_spin(bars + B_GFULL + 8 * st, gph);
            const uint64_t da = full_desc(dA + st * (GST_BYTES >> 4)), db = full_desc(dB + st * (GST_BYTES >> 4));
            if (order && wg) bar_sync(3, 256);
            wgmma_fence();
#pragma unroll
            for (int kk = 0; kk < 4; kk++) wgmma_ss_n256_tb(acc, da + 2 * kk, db + 128 * kk, 1);
            wgmma_commit();
            if (order && !wg) bar_arrive(3, 256);
            gph ^= st == 3;
            k++;
        };
        if (wg == 1) bar_arrive(1, 256);
        int it = first_item();
        float s[64];
        const uint32_t dK = make_desc(sb + SM_KV, 16);
        auto kv_wait = [&](uint32_t n) { mbar_spin(bars + B_AFULL + 16 + 8 * (n & 3), (n >> 2) & 1); };
        auto first_scores = [&](bool valid) {
            if (valid) { mbar_spin(bars + B_AFULL + 8 * (ti & 1), (ti >> 1) & 1); kv_wait(kvn); }
            bar_sync(1 + wg, 256);
            qk_gemm(s, dA + (ti & 1) * 2048, dK + (kvn & 3) * 2048);
        };
        bool issued;
        {
            {
                float acc[128];
                uint32_t pk[64];
                bool pending = false;
                int held = T_END;
                auto scale_q = [&](int j0, int n) {
                    if (held != T_Q) return;
#pragma unroll
                    for (int j = j0; j < j0 + n; j++)
                        asm("{\n.reg .b32 t;\nmul.rn.bf16x2 t, %0, %2;\nfma.rn.bf16x2 %0, %0, %1, t;\n}\n" : "+r"(pk[j]) : "r"(0x3e033e03u), "r"(0xb9d8b9d8u));
                };
                zero_regs(pk);
                const uint32_t dB = make_desc(sb + 16384, 8192);
                do {
                    if (item_type(it) == T_LOCAL) {
                        int ln = lane;
                        asm volatile("" : "+r"(ln));
                        const int g = ln >> 2, t = ln & 3, par = wq & 1;
                        const uint32_t hc = (wq >> 1) * 4, pl = sb + (par * 2 + wg) * LOC_PLANE;
                        const uint32_t a16 = (ln & 15) * 128 + (((hc + (ln >> 4)) ^ (ln & 7)) << 4), a8 = (ln & 7) * 128 + (((hc + (ln >> 3)) ^ (ln & 7)) << 4);
                        const bool first0 = 2 * t > g, first1 = 2 * t + 1 > g;
                        const uint32_t fmask = (first0 ? 0xffffu : 0u) | (first1 ? 0xffff0000u : 0u);
                        const bool edge = item_row(it) == 0;
                        uint32_t q[4][2][4], kf[9][4], vf[9][4];
                        float w[8];
                        mbar_spin(bars + B_GFULL, gph);
#pragma unroll
                        for (int u = 0; u < 4; u++) { ldsm_x4(q[u][0], pl + u * 2048 + a16); ldsm_x4(q[u][1], pl + u * 2048 + (a16 ^ 32)); }
#pragma unroll
                        for (int j = 0; j < 8; j++) w[j] = lds_f32(sb + 4 * LOC_PLANE + 4 * (2 * g + par) + 64 * j);
                        __syncwarp();
                        release_stage(0);
                        mbar_spin(bars + B_GFULL + 8, gph);
#pragma unroll
                        for (int n = 0; n < 9; n++) ldsm_x4(kf[n], pl + GST_BYTES + n * 1024 + a8);
                        __syncwarp();
                        release_stage(1);
                        float s[8][2];
#pragma unroll
                        for (int u = 0; u < 4; u++) {
                            float d[3][4];
#pragma unroll
                            for (int nt = 0; nt < 3; nt++) {
                                mma_k16_init(d[nt], q[u][0], kf[2 * u + nt][0], kf[2 * u + nt][1]);
                                mma_k16(d[nt], q[u][1], kf[2 * u + nt][2], kf[2 * u + nt][3]);
                            }
                            if (u == 0 && edge) { d[0][0] = -INFINITY; d[0][1] = -INFINITY; }
                            s[2 * u][0] = first0 ? d[0][0] : d[1][0]; s[2 * u][1] = first1 ? d[0][1] : d[1][1];
                            s[2 * u + 1][0] = first0 ? d[1][2] : d[2][2]; s[2 * u + 1][1] = first1 ? d[1][3] : d[2][3];
                        }
                        mbar_spin(bars + B_GFULL + 16, gph);
#pragma unroll
                        for (int u = 0; u < 4; u++) { ldsm_x4_t(vf[2 * u], pl + 2 * GST_BYTES + u * 2048 + a16); ldsm_x4_t(vf[2 * u + 1], pl + 2 * GST_BYTES + u * 2048 + (a16 ^ 32)); }
                        ldsm_x4_t(vf[8], pl + 2 * GST_BYTES + 8192 + a8);
                        __syncwarp();
                        release_stage(2);
                        float x[8];
#pragma unroll
                        for (int j = 0; j < 8; j++) x[j] = fmaxf(s[j][0], s[j][1]);
#pragma unroll
                        for (int o = 1; o < 4; o *= 2)
#pragma unroll
                            for (int j = 0; j < 8; j++) x[j] = fmaxf(x[j], __shfl_xor_sync(0xffffffffu, x[j], o));
#pragma unroll
                        for (int j = 0; j < 8; j++) {
                            const float n = x[j] * -LOC_SCALE;
                            s[j][0] = ex2(fmaf(s[j][0], LOC_SCALE, n)); s[j][1] = ex2(fmaf(s[j][1], LOC_SCALE, n));
                            x[j] = s[j][0] + s[j][1];
                        }
#pragma unroll
                        for (int o = 1; o < 4; o *= 2)
#pragma unroll
                            for (int j = 0; j < 8; j++) x[j] += __shfl_xor_sync(0xffffffffu, x[j], o);
                        mbar_spin(bars + B_GFULL + 24, gph);
                        release_stage(3);
                        it = take_item();
                        uint32_t ob[4][8];
#pragma unroll
                        for (int u = 0; u < 4; u++) {
                            const float r0 = rcp(x[2 * u]), r1 = rcp(x[2 * u + 1]), f0 = fmaf(-w[2 * u], r0, r0), f1 = fmaf(-w[2 * u + 1], r1, r1);
                            const uint32_t p0 = pack_bf16(s[2 * u][0] * f0, s[2 * u][1] * f0), p1 = pack_bf16(s[2 * u + 1][0] * f1, s[2 * u + 1][1] * f1);
                            const uint32_t pa[4] = {p0 & fmask, 0, p0 & ~fmask, p1 & fmask};
#pragma unroll
                            for (int c = 0; c < 4; c++) {
                                float ol[4];
                                mma_k16_init(ol, pa, vf[2 * u + (c >> 1)][2 * (c & 1)], vf[2 * u + (c >> 1)][2 * (c & 1) + 1]);
                                mma_k8(ol, 0, p1 & ~fmask, u < 3 ? vf[2 * u + 2 + (c >> 1)][2 * (c & 1)] : vf[8][c]);
                                ob[u][2 * c] = pack_bf16(ol[0], ol[1]);
                                ob[u][2 * c + 1] = pack_bf16(ol[2], ol[3]);
                            }
                        }
                        stage_acquire(0); stage_acquire(1);
#pragma unroll
                        for (int u = 0; u < 4; u++) {
                            stmatrix_x4(stg + par * 8192 + u * 2048 + a16, ob[u][0], ob[u][1], ob[u][2], ob[u][3]);
                            stmatrix_x4(stg + par * 8192 + u * 2048 + (a16 ^ 32), ob[u][4], ob[u][5], ob[u][6], ob[u][7]);
                        }
                        publish_pair();
                        bar_sync(4, 256);
                        gph ^= 1;
                        continue;
                    }
                    mbar_spin(bars + B_GFULL, gph);
                    bool more;
                    do {
                        wgmma_fence();
                        wgmma_ss_n256_tb_init(acc, full_desc(dA), full_desc(dB));
#pragma unroll
                        for (int kk = 1; kk < 4; kk++) wgmma_ss_n256_tb(acc, full_desc(dA) + 2 * kk, full_desc(dB) + 128 * kk, 1);
                        wgmma_commit();
                        const int type = item_type(it), nk = type == T_K || type == T_V ? 8 : 16;
                        int k = 1;
                        do {
                            if (pending) {
                                const int kf = k - 1 - wg;
                                if (kf == 0) { scale_q(0, 16); stage_chunk(0, pk); }
                                else if (kf == 1) { scale_q(16, 16); stage_chunk(1, pk + 16); }
                                else if (kf == 3) { scale_q(32, 16); stage_chunk(0, pk + 32); }
                                else if (kf == 4) { scale_q(48, 16); stage_chunk(1, pk + 48); }
                            }
                            if (k == nk - 1) it = take_item();
                            gemm_step(acc, dB, k, item_type(it) > T_LOCAL);
                        } while (k < nk);
                        held = type;
                        more = item_type(it) < T_LOCAL;
                        if (more) mbar_spin(bars + B_GFULL, gph);
                        wgmma_wait<0>();
                        fence_regs(acc);
                        release_stage(3);
#pragma unroll
                        for (int j = 0; j < 64; j++) pk[j] = pack_bf16(acc[2 * j], acc[2 * j + 1]);
                        pending = true;
                    } while (more);
                } while (item_type(it) <= T_LOCAL);
                issued = item_type(it) == T_ATTN && (it & ITEM_READY);
                first_scores(issued);
                scale_q(0, 64);
                stage_acquire(0); stage_acquire(1);
                mbar_spin(bars + B_GEMPTY + 8, gph ^ 1);
                write_blocks(std::integral_constant<int, 8>(), 0, pk);
                write_blocks(std::integral_constant<int, 8>(), 32768 - SM_STAGING, pk + 32);
                publish_pair();
                release(B_ALT + 8 * wg);
                bar_arrive(2 - wg, 256);
                wgmma_wait<0>();
                fence_regs(s);
                if (item_type(it) == T_END) it = take_item();
            }
            while (item_type(it) == T_ATTN) {
                if (!issued) { first_scores(true); bar_arrive(2 - wg, 256); wgmma_wait<0>(); fence_regs(s); }
                issued = false;
                float o[64];
                uint32_t pa[32], pb[32];
                float n0 = 0.f, n1 = 0.f;
                int shifted = 0;
                float l0 = 0.f, l1 = 0.f, f0 = 0.f, f1 = 0.f, g0, g1;
                uint32_t has_pv = 0;
                int first = 0;
                int pending = 0;
                const uint32_t dV = make_desc(sb + SM_KV, 16384);
                const uint32_t lane_off = bars_lane - bars + B_AEMPTY - B_AFULL;
                int cur = it;
                uint32_t qoff = (ti & 1) * 2048;
                const int row = wg * 64 + wq * 16 + (lane >> 2);
                const float thr = (row & 63) - (lane & 3) * 2;
                int peek = -1;
                auto kv_release = [&](uint32_t n) { mbar_arrive_cluster_if(lane < 2, bars_lane + B_AEMPTY + 16 + 8 * (n & 3)); };
                struct Slot { uint32_t bar, par, off; } slot[4];
#pragma unroll
                for (uint32_t i = 0; i < 4; i++) {
                    const uint32_t n = kvn + 1 + (i ^ 2);
                    slot[i].bar = bars + B_AFULL + 16 + 8 * (n & 3); slot[i].par = (n >> 2) & 1; slot[i].off = (n & 3) * 2048;
                }
                kvn++;
                auto next_gate = [&]() {
                    g0 = lds_f32(bars + SM_GATE + (ti & 1) * 512 + 4 * row); g1 = lds_f32(bars + SM_GATE + (ti & 1) * 512 + 4 * row + 32);
                    ti++;
                };
                next_gate();
                auto scale_o = [&]() {
#pragma unroll
                    for (int j = 0; j < 16; j++) { o[4 * j] *= f0; o[4 * j + 1] *= f0; o[4 * j + 2] *= f1; o[4 * j + 3] *= f1; }
                };
                auto pack_o = [&](uint32_t (&v)[32]) {
#pragma unroll
                    for (int j = 0; j < 32; j++) v[j] = pack_bf16(o[2 * j], o[2 * j + 1]);
                };
                auto scales = [&]() { f0 = g0 * rcp(quad_sum(l0)); f1 = g1 * rcp(quad_sum(l1)); };
                auto issue = [&](auto even, uint32_t (&pin)[32], uint32_t (&pout)[32], bool fresh, bool last) {
                    constexpr bool EVEN = decltype(even)::value;
                    Slot& sk = slot[EVEN ? 0 : 2];
                    Slot& sv = slot[EVEN ? 1 : 3];
                    kvn += 2;
                    mbar_spin(sk.bar, sk.par);
                    bar_sync(1 + wg, 256);
                    qk_gemm(s, dA + qoff, dK + sk.off);
                    if (EVEN && fresh) {
                        scales();
                        next_gate();
                        n0 = 0.f; n1 = 0.f; l0 = 0.f; l1 = 0.f;
                        shifted = 0;
                        stage_acquire(0); stage_acquire(1);
                    }
                    if (!EVEN && pending) {
                        pack_o(pout);
                        write_blocks(std::integral_constant<int, 4>(), 0, pout);
                    }
                    if (last)
                        asm volatile("{\n.reg .pred P, Q;\n"
                                     "mbarrier.test_wait.parity.shared::cta.b64 Q, [%1], %2;\n"
                                     "mbarrier.test_wait.parity.shared::cta.b64 P, [%3], %4;\n"
                                     "ld.shared.u32 %0, [%5];\n"
                                     "@!Q or.b32 %0, %0, 0x10000;\n"
                                     "@!P mov.u32 %0, -1;\n}\n"
                                     : "=r"(peek) : "r"(bars + B_AFULL + 8 * (ti & 1)), "r"((ti >> 1) & 1), "r"(bars + B_IFULL + 8 * (qn % QDEPTH)),
                                       "r"((qn / QDEPTH) & 1), "r"(bars + SM_QUEUE + 4 * (qn % QDEPTH)) : "memory");
                    mbar_spin(sv.bar, sv.par);
                    pv_gemm(o, pin, dV + sv.off, EVEN || !first);
                    bar_arrive(2 - wg, 256);
                    if (!EVEN && pending) {
                        write_blocks(std::integral_constant<int, 4>(), 8192, pout + 16);
                        publish_pair();
                    }
                    sk.par ^= 1; sv.par ^= 1;
                    wgmma_wait<1>();
                };
                auto softmax = [&](auto even, uint32_t (&pin)[32], uint32_t (&pout)[32], bool fresh, bool diag, bool last) {
                    constexpr bool EVEN = decltype(even)::value;
                    Slot& sk = slot[EVEN ? 0 : 2];
                    Slot& sv = slot[EVEN ? 1 : 3];
                    fence_regs(s);
                    mbar_arrive_cluster_if(lane < 2 && (!EVEN || has_pv), sk.bar + lane_off);
                    mbar_arrive_if(lane == 0 && last, bars + B_AEMPTY + 8 * ((ti - 1) & 1));
                    float r0, r1, x0 = n0, x1 = n1;
#pragma unroll 1
                    for (int mask = diag, redone = 0;; mask = 0, redone = 1) {
                        if (mask | shifted) {
                            if (mask) causal_mask(s, thr, wg);
                            if (shifted) shift_rows(s, x0, x1);
                        }
                        exp_pack(pout, s, r0, r1);
                        if (!__any_sync(0xffffffffu, fmaxf(r0, r1) >= SUM_LIMIT || (EVEN && fresh && !(lane & 3) && !(fminf(s[0], s[2]) >= -REF_RANGE))) || redone) break;
                        row_max(s, x0, x1);
                        if (!(EVEN && fresh)) { x0 = fmaxf(x0, 0.f); x1 = fmaxf(x1, 0.f); }
                        float a0 = ex2(-x0), a1 = ex2(-x1);
                        n0 += x0; n1 += x1;
                        shifted = 1;
                        if (EVEN && fresh) { a0 = 1.f; a1 = 1.f; }
                        l0 *= a0; l1 *= a1;
                        wgmma_wait<0>();
                        fence_regs(o);
#pragma unroll
                        for (int q = 0; q < 16; q++) { o[4 * q] *= a0; o[4 * q + 1] *= a0; o[4 * q + 2] *= a1; o[4 * q + 3] *= a1; }
                    }
                    l0 += r0; l1 += r1;
                    wgmma_wait<0>();
                    fence_regs(o);
                    fence_regs(pin);
                    mbar_arrive_cluster_if(lane < 2, sv.bar + lane_off);
                };
                auto copy_p = [&]() {
#pragma unroll
                    for (int j = 0; j < 32; j++) pa[j] = __float_as_uint(__uint_as_float(pb[j]) + __uint_as_float(prm.zero));
                };
                int rem = 0;
                zero_regs(pa);
                wgmma_fence();
                wgmma_ss_n128_init(o, full_desc(dA), full_desc(dK));
                wgmma_commit();
                while (true) {
                    const bool fresh = rem == 0, last = fresh ? item_row(cur) == 0 : rem == 1;
                    softmax(std::true_type(), pa, pb, fresh, item_asc(cur) ? last : fresh, last);
                    first = fresh;
                    if (fresh) {
                        pending = has_pv; has_pv = 1;
                        if (pending) scale_o();
                        rem = item_row(cur) + 1;
                    }
                    if (--rem == 0) {
                        copy_p();
                        const Slot t0 = slot[0], t1 = slot[1];
                        slot[0] = slot[2]; slot[1] = slot[3]; slot[2] = t0; slot[3] = t1;
                    } else {
                        issue(std::false_type(), pb, pa, false, rem == 1);
                        softmax(std::false_type(), pb, pa, false, item_asc(cur) && rem == 1, rem == 1);
                        pending = 0; first = 0;
                        rem--;
                    }
                    if (rem == 0) {
                        const int seen = __shfl_sync(0xffffffffu, peek, 0);
                        if (seen >= 0) {
                            mbar_arrive_cluster_if(lane == 0, bars0 + B_IEMPTY + 8 * (qn % QDEPTH));
                            qn++;
                            it = seen & 0xffff;
                        } else {
                            it = take_item();
                        }
                        if (item_row(cur) < 2 || item_type(it) != T_ATTN) break;
                        if (seen & 0x10000) mbar_spin(bars + B_AFULL + 8 * (ti & 1), (ti >> 1) & 1);
                        cur = it;
                        qoff = (ti & 1) * 2048;
                    }
                    issue(std::true_type(), pa, pb, rem == 0, rem ? rem == 1 : item_row(cur) == 0);
                }
                const uint32_t skip = item_asc(cur) & ~item_row(cur) & 1;
                kvn += skip;
                const bool end = item_type(it) == T_END;
#pragma unroll 1
                for (int pass = pending ? 0 : 1; pass < 2; pass++) {
                    if (pass) {
                        kv_wait(kvn);
                        pv_gemm(o, pa, dV + (kvn & 3) * 2048, !first);
                        scales();
                        stage_acquire(0); stage_acquire(1);
                        if (end) it = take_item();
                        wgmma_wait<0>();
                        fence_regs(o);
                        kv_release(kvn);
                        kvn += 1 + skip;
                        scale_o();
                    }
                    pack_o(pb);
                    write_blocks(std::integral_constant<int, 8>(), 0, pb);
                    publish_pair();
                }
            }
        }
        if (item_type(it) == T_OUT) {
            float acc[128];
            const uint32_t dB = make_desc(sb + 16384, 8192);
            mbar_spin(bars + B_GFULL, gph);
            wgmma_fence();
            wgmma_ss_n256_tb_init(acc, full_desc(dA), full_desc(dB));
#pragma unroll
            for (int kk = 1; kk < 4; kk++) wgmma_ss_n256_tb(acc, full_desc(dA) + 2 * kk, full_desc(dB) + 128 * kk, 1);
            wgmma_commit();
            uint32_t ln;
            asm volatile("mov.u32 %0, %%laneid;" : "=r"(ln));
            char* const mine = (char*)prm.out + (uint32_t)((item_row(it) * 128 + wg * 64 + wq * 16 + (ln >> 4)) * 2048 + item_col(it) * 256 + (ln & 15) * 16);
            int k = 1, nk = 80;
            do {
                if ((uint32_t)(k - (K_MEET - 12)) < 8) *(uint4*)(mine + (uint32_t)(k - (K_MEET - 12)) * 4096) = make_uint4(0, 0, 0, 0);
                __syncwarp();
                if (k == K_SPLIT) nk = take_item() & 127;
                gemm_step(acc, dB, k, false);
            } while (k < nk);
            float lo[64];
            auto triple = [&](auto first) {
                const uint32_t s0 = k & 3, s1 = (k + 1) & 3, o0 = s0 * (GST_BYTES >> 4), o1 = s1 * (GST_BYTES >> 4);
                wgmma_wait<0>();
                mbar_arrive_cluster_if(ln < (decltype(first)::value ? 2 : 4), bars_lane + B_GEMPTY + 8 * ((k - 1 - (ln >> 1)) & 3));
                mbar_spin(bars + B_GFULL + 8 * s0, gph);
                gph ^= s0 == 3;
                wgmma_fence();
#pragma unroll
                for (int kk = 0; kk < 4; kk++) {
                    if (decltype(first)::value && kk == 0) wgmma_ss_n128_tb_init(lo, full_desc(dA + o0), full_desc(dB + o0));
                    else wgmma_ss_n128_tb(lo, full_desc(dA + o0) + 2 * kk, full_desc(dB + o0) + 128 * kk, 1);
                }
                mbar_spin(bars + B_GFULL + 8 * s1, gph);
                gph ^= s1 == 3;
                wgmma_fence();
#pragma unroll
                for (int kk = 0; kk < 4; kk++) wgmma_ss_n128_tb(lo, full_desc(dA + o0 + 2048) + 2 * kk, full_desc(dB + o1 + 1024) + 128 * kk, 1);
#pragma unroll
                for (int kk = 0; kk < 4; kk++) wgmma_ss_n128_tb(lo, full_desc(dA + o1) + 2 * kk, full_desc(dB + o1) + 128 * kk, 1);
                wgmma_commit();
                k += 2;
            };
            triple(std::true_type());
            fence_regs(acc);
            uint32_t pk[32];
#pragma unroll
            for (int j = 0; j < 32; j++) pk[j] = pack_bf16(acc[64 + 2 * j], acc[65 + 2 * j]);
            stage_acquire(0); stage_acquire(1);
            write_blocks(std::integral_constant<int, 8>(), 0, pk);
            publish_pair();
            triple(std::false_type());
            stage_acquire(0); stage_acquire(1);
            wgmma_wait<0>();
            fence_regs(lo);
            mbar_arrive_cluster_if(ln < 4, bars_lane + B_GEMPTY + 8 * ((k - 1 - (ln >> 1)) & 3));
#pragma unroll
            for (int b = 0; b < 2; b++) {
#pragma unroll
                for (int j = 16 * b; j < 16 * b + 16; j++) pk[j] = pack_bf16(acc[2 * j] + lo[2 * j], acc[2 * j + 1] + lo[2 * j + 1]);
                write_blocks(std::integral_constant<int, 4>(), b * 8192, pk + 16 * b);
                stage_publish(b);
            }
        }
    }
}

typedef CUresult (*EncodeFn)(CUtensorMap*, CUtensorMapDataType, cuuint32_t, void*, const cuuint64_t*, const cuuint64_t*,
                             const cuuint32_t*, const cuuint32_t*, CUtensorMapInterleave, CUtensorMapSwizzle,
                             CUtensorMapL2promotion, CUtensorMapFloatOOBfill);

void encode3(EncodeFn fn, CUtensorMap* m, const void* ptr, uint64_t d0, uint64_t d1, uint64_t d2, uint64_t s1, uint64_t s2,
             uint32_t b0, uint32_t b1, uint32_t b2) {
    cuuint64_t dims[3] = {d0, d1, d2};
    cuuint64_t strides[2] = {s1, s2};
    cuuint32_t box[3] = {b0, b1, b2};
    cuuint32_t es[3] = {1, 1, 1};
    fn(m, CU_TENSOR_MAP_DATA_TYPE_BFLOAT16, 3, const_cast<void*>(ptr), dims, strides, box, es, CU_TENSOR_MAP_INTERLEAVE_NONE,
       CU_TENSOR_MAP_SWIZZLE_128B, CU_TENSOR_MAP_L2_PROMOTION_NONE, CU_TENSOR_MAP_FLOAT_OOB_FILL_NONE);
}
void map_act(EncodeFn fn, CUtensorMap* m, const void* p, int rows, int cols, int box_rows) {
    encode3(fn, m, p, cols, rows, 1, (uint64_t)cols * 2, (uint64_t)cols * rows * 2, 64, box_rows, 1);
}
void map_wgt(EncodeFn fn, CUtensorMap* m, const void* p, int K, int N) {
    encode3(fn, m, p, 64, K, N / 64, (uint64_t)N * 2, 128, 64, 64, 2);
}

void build_schedule(Params& p) {
    int n = 0;
    auto add = [&](int type, int col, int row) { p.items[n++] = (uint16_t)(type << 13 | col << 4 | row); };
    int beta = 26, tail = 32, late = 6, early = 4, epos = 60;
    int order[16] = {6, 7, 8, 9, 10, 11, 12, 13, 14, 15, 5, 4, 3, 2, 1, 0};
    const char* plans = "xxcccccx,xxcccccx,xxxxx,xxcxlxx,xxlcclxcc,xxlcccccc,xxlxlccccc,xxlxlxccc";
    const char* pos[8];
    int len[8] = {}, start[8] = {};
    for (int s = 0; s < 8; s++) { pos[s] = plans; while (*plans && *plans++ != ',') {} }
    for (int i = 0; i < 160; i++) p.plan[i / 16][i % 16] = T_END << 13;
    for (int nx = 0, nc = 3, nl = 0; nx + nc + nl < 28 + 32 + 8;) {
        int s = -1;
        for (int i = 0; i < 8; i++) if (*pos[i] > ',' && (s < 0 || start[i] < start[s])) s = i;
        const char kind = *pos[s]++;
        int it;
        if (kind == 'x') { it = nx < 12 ? T_B << 13 | (nx % 3 * 4 + nx / 3) << 4 : T_Q << 13 | (nx - 12) << 4; nx++; }
        else if (kind == 'c') { it = (T_K + (nc & 1)) << 13 | nc / 2 << 4; nc++; }
        else { it = T_LOCAL << 13 | nl / 2 << 4 | (nl & 1); nl++; }
        p.plan[s][len[s]++] = (uint16_t)it;
        start[s] += kind == 'x' ? 48 : kind == 'c' ? 24 : 8;
    }
    for (int i = 0; i < 24; i++) p.plan[8 + i / 12][i % 12] = (uint16_t)((T_K + (i % 3 & 1)) << 13 | i % 3 / 2 << 4 | i / 3);
    const int a0 = n;
    for (int key = 0; key < 4000; key++)
        for (int r = 0; r < 32; r++)
            for (int j = 7; j >= 0; j--)
                if ((j ? (7 - j) * 40 + r * beta : 3999) == key) add(T_ATTN, 2 * order[r >> 1] + (r & 1), j);
    int t0 = n;
    for (int work = 0; work < 32 * 136 * tail / 100;) work += 4 * (p.items[--t0] & 15) + 3;
    for (int i = t0 + 1; i < n; i++)
        for (int j = i; j > t0 && (p.items[j] & 15) > (p.items[j - 1] & 15); j--) { const uint16_t t = p.items[j]; p.items[j] = p.items[j - 1]; p.items[j - 1] = t; }
    for (int r = early - 1; r >= 0; r--) {
        const uint16_t t = p.items[n - 32 + early - 1];
        for (int j = n - 32 + early - 1; j > n - epos; j--) p.items[j] = p.items[j - 1];
        p.items[n - epos] = t;
    }
    for (int moved = 0; moved < 2 && late >= 0; moved++)
        for (int i = a0; i < n; i++)
            if (p.items[i] == (T_ATTN << 13 | (2 * order[15] + moved) << 4 | late)) {
                for (int j = i; j + 1 < n; j++) p.items[j] = p.items[j + 1];
                p.items[n - 1] = (uint16_t)(T_ATTN << 13 | (2 * order[15] + moved) << 4 | late);
                break;
            }
    for (int s = 0, lo = 0, hi = WIDE - 1; s < 80; s++) {
        const int r = s / 2, g = r < 8 ? 32 + r : 2 * order[r / 2 - 4] + (r & 1);
        p.ostep[s >= WIDE ? s : r & 1 ? hi-- : lo++] = (uint8_t)(2 * g + (s & 1));
    }
}

void build_params(Params& p, void* const* d_in, void* d_out) {
    void* fnp = nullptr;
    cudaDriverEntryPointQueryResult qr;
    cudaGetDriverEntryPoint("cuTensorMapEncodeTiled", &fnp, cudaEnableDefault, &qr);
    EncodeFn fn = (EncodeFn)fnp;
    void* scr = nullptr;
    cudaGetSymbolAddress(&scr, g_scr);
    map_act(fn, &p.m[M_X], d_in[0], SEQ, 1024, 128);
    map_act(fn, &p.m[M_C], d_in[1], SEQ, 512, 128);
    map_wgt(fn, &p.m[M_WQ], d_in[2], 1024, 4096);
    map_wgt(fn, &p.m[M_WUK], d_in[3], 512, 4096);
    map_wgt(fn, &p.m[M_WUV], d_in[4], 512, 4096);
    map_wgt(fn, &p.m[M_WO], d_in[5], 4096, 1024);
    map_wgt(fn, &p.m[M_WQKV], d_in[7], 1024, 3072);
    map_wgt(fn, &p.m[M_WOB], d_in[8], 1024, 1024);
    encode3(fn, &p.m[M_SCR_LD], scr, 128, SEQ, G_TOTAL, 256, (uint64_t)SEQ * 256, 64, 128, 1);
    encode3(fn, &p.m[M_SCR_LOC], scr, 256, SEQ / 2, G_TOTAL, 512, (uint64_t)SEQ * 256, 64, 72, 1);
    encode3(fn, &p.m[M_SCR_LOQ], scr, 256, SEQ / 2, G_TOTAL, 512, (uint64_t)SEQ * 256, 64, 64, 1);
    encode3(fn, &p.m[M_SCR_ST], scr, 128, SEQ, G_TOTAL, 256, (uint64_t)SEQ * 256, 64, 64, 1);
    map_act(fn, &p.m[M_OUT], d_out, SEQ, 1024, 64);
    p.x = (const __nv_bfloat16*)d_in[0];
    p.gate_w = (const __nv_bfloat16*)d_in[9];
    p.zero = 0;
    p.wo = (const char*)d_in[5];
    p.out = (__nv_bfloat16*)d_out;
    build_schedule(p);
}

}

extern "C" void kernel_launch(void* const* d_in, const int* in_sizes, int n_in, void* d_out, int out_size) {
    (void)in_sizes; (void)n_in; (void)out_size;
    Params p;
    build_params(p, d_in, d_out);
    cudaFuncSetAttribute(fused_kernel, cudaFuncAttributeMaxDynamicSharedMemorySize, SM_TOTAL);
    fused_kernel<<<NCTA, 384, SM_TOTAL>>>(p);
}
```

```cpp
#include <cuda_runtime.h>
#include <cuda_bf16.h>
#include <cuda.h>
#include <stddef.h>
#include <stdint.h>
#include <type_traits>

namespace {

constexpr int SEQ = 2048;
constexpr int G_Q = 0, G_K = 32, G_V = 64, G_B = 96, G_CTX = G_Q, G_LOC = G_B, G_TOTAL = 120;

__device__ __align__(1024) __nv_bfloat16 g_scr[(size_t)G_TOTAL * SEQ * 128];
__device__ __align__(128) float g_gate[SEQ];

__device__ __forceinline__ uint32_t smem_u32(const void* p) { return (uint32_t)__cvta_generic_to_shared(p); }
__device__ __forceinline__ bool elect_one() {
    uint32_t p;
    asm volatile("{\n.reg .pred P;\nelect.sync _|P, 0xffffffff;\nselp.u32 %0, 1, 0, P;\n}\n" : "=r"(p));
    return p != 0;
}
__device__ __forceinline__ void mbar_init(uint32_t bar, uint32_t count) {
    asm volatile("mbarrier.init.shared::cta.b64 [%0], %1;" :: "r"(bar), "r"(count) : "memory");
}
__device__ __forceinline__ uint32_t cluster_rank() { uint32_t r; asm("mov.u32 %0, %%cluster_ctarank;" : "=r"(r)); return r; }
__device__ __forceinline__ uint32_t map_cta(uint32_t addr, uint32_t cta) {
    uint32_t r; asm("mapa.shared::cluster.u32 %0, %1, %2;" : "=r"(r) : "r"(addr), "r"(cta)); return r;
}
__device__ __forceinline__ void mbar_arrive_cluster_if(bool pred, uint32_t cluster_bar) {
    asm volatile("{\n.reg .pred P;\nsetp.ne.u32 P, %1, 0;\n@P mbarrier.arrive.shared::cluster.b64 _, [%0];\n}\n"
                 :: "r"(cluster_bar), "r"((uint32_t)pred) : "memory");
}
__device__ __forceinline__ void mbar_arrive_cluster_n_if(bool pred, uint32_t cluster_bar, uint32_t count) {
    asm volatile("{\n.reg .pred P;\nsetp.ne.u32 P, %1, 0;\n@P mbarrier.arrive.shared::cluster.b64 _, [%0], %2;\n}\n"
                 :: "r"(cluster_bar), "r"((uint32_t)pred), "r"(count) : "memory");
}
__device__ __forceinline__ void mbar_arrive_if(bool pred, uint32_t bar) {
    asm volatile("{\n.reg .pred P;\nsetp.ne.u32 P, %1, 0;\n@P mbarrier.arrive.shared::cta.b64 _, [%0];\n}\n"
                 :: "r"(bar), "r"((uint32_t)pred) : "memory");
}
__device__ __forceinline__ bool mbar_test(uint32_t bar, uint32_t parity) {
    uint32_t ok;
    asm volatile("{\n.reg .pred P;\nmbarrier.test_wait.parity.shared::cta.b64 P, [%1], %2;\nselp.u32 %0, 1, 0, P;\n}\n"
                 : "=r"(ok) : "r"(bar), "r"(parity) : "memory");
    return ok != 0;
}
__device__ __forceinline__ void mbar_wait(uint32_t bar, uint32_t parity) {
    asm volatile("{\n.reg .pred P;\n.reg .u32 c;\n"
                 "mov.u32 c, 0;\n"
                 "SPIN:\n"
                 "mbarrier.try_wait.parity.shared::cta.b64 P, [%0], %1;\n"
                 "@P bra DONE;\n"
                 "add.u32 c, c, 1;\n"
                 "setp.lt.u32 P, c, 4194304;\n"
                 "@P bra SPIN;\n"
                 "trap;\n"
                 "DONE:\n}\n" :: "r"(bar), "r"(parity) : "memory");
}
__device__ __forceinline__ void mbar_spin(uint32_t bar, uint32_t parity) {
    asm volatile("{\n.reg .pred P;\n"
                 "SPIN:\n"
                 "mbarrier.try_wait.parity.shared::cta.b64 P, [%0], %1;\n"
                 "@!P bra SPIN;\n}\n" :: "r"(bar), "r"(parity) : "memory");
}
__device__ __forceinline__ void bar_sync(int id, int n) { asm volatile("bar.sync %0, %1;" :: "r"(id), "r"(n) : "memory"); }
__device__ __forceinline__ void bar_arrive(int id, int n) { asm volatile("bar.arrive %0, %1;" :: "r"(id), "r"(n) : "memory"); }
__device__ __forceinline__ void fence_proxy_async_smem() { asm volatile("fence.proxy.async.shared::cta;" ::: "memory"); }
__device__ __forceinline__ void warp_expect_tx(uint32_t bar, uint32_t bytes) {
    asm volatile("{\n.reg .pred P;\nelect.sync _|P, 0xffffffff;\n@P mbarrier.arrive.expect_tx.shared::cta.b64 _, [%0], %1;\n}\n"
                 :: "r"(bar), "r"(bytes) : "memory");
}
constexpr uint64_t EVICT_FIRST = 0x12F0000000000000ull;
__device__ __forceinline__ void warp_tma_load(uint32_t dst, const CUtensorMap* map, uint32_t bar, int c0, int c1, int c2, bool stream) {
    if (stream)
        asm volatile("{\n.reg .pred P;\nelect.sync _|P, 0xffffffff;\n"
                     "@P cp.async.bulk.tensor.3d.shared::cluster.global.mbarrier::complete_tx::bytes.L2::cache_hint"
                     " [%0], [%1, {%3, %4, %5}], [%2], %6;\n}\n"
                     :: "r"(dst), "l"(map), "r"(bar), "r"(c0), "r"(c1), "r"(c2), "l"(EVICT_FIRST) : "memory");
    else
        asm volatile("{\n.reg .pred P;\nelect.sync _|P, 0xffffffff;\n"
                     "@P cp.async.bulk.tensor.3d.shared::cluster.global.mbarrier::complete_tx::bytes [%0], [%1, {%3, %4, %5}], [%2];\n}\n"
                     :: "r"(dst), "l"(map), "r"(bar), "r"(c0), "r"(c1), "r"(c2) : "memory");
}
__device__ __forceinline__ void warp_tma_load_pair(uint32_t dst, const CUtensorMap* map, uint32_t bar, int c0, int c1, int c2, bool stream) {
    if (stream)
        asm volatile("{\n.reg .pred P;\nelect.sync _|P, 0xffffffff;\n"
                     "@P cp.async.bulk.tensor.3d.shared::cluster.global.mbarrier::complete_tx::bytes.multicast::cluster.L2::cache_hint"
                     " [%0], [%1, {%3, %4, %5}], [%2], %6, %7;\n}\n"
                     :: "r"(dst), "l"(map), "r"(bar), "r"(c0), "r"(c1), "r"(c2), "h"((uint16_t)3), "l"(EVICT_FIRST) : "memory");
    else
        asm volatile("{\n.reg .pred P;\nelect.sync _|P, 0xffffffff;\n"
                     "@P cp.async.bulk.tensor.3d.shared::cluster.global.mbarrier::complete_tx::bytes.multicast::cluster"
                     " [%0], [%1, {%3, %4, %5}], [%2], %6;\n}\n"
                     :: "r"(dst), "l"(map), "r"(bar), "r"(c0), "r"(c1), "r"(c2), "h"((uint16_t)3) : "memory");
}
__device__ __forceinline__ void warp_bulk_load(uint32_t dst, const void* src, uint32_t bytes, uint32_t bar) {
    asm volatile("{\n.reg .pred P;\nelect.sync _|P, 0xffffffff;\n"
                 "@P cp.async.bulk.shared::cluster.global.mbarrier::complete_tx::bytes [%0], [%1], %2, [%3];\n}\n"
                 :: "r"(dst), "l"(src), "r"(bytes), "r"(bar) : "memory");
}
__device__ __forceinline__ void warp_tma_store(const CUtensorMap* map, uint32_t src, int c0, int c1, int c2, bool stream) {
    if (stream)
        asm volatile("{\n.reg .pred P;\nelect.sync _|P, 0xffffffff;\n"
                     "@P cp.async.bulk.tensor.3d.global.shared::cta.bulk_group.L2::cache_hint [%0, {%2, %3, %4}], [%1], %5;\n}\n"
                     :: "l"(map), "r"(src), "r"(c0), "r"(c1), "r"(c2), "l"(EVICT_FIRST) : "memory");
    else
        asm volatile("{\n.reg .pred P;\nelect.sync _|P, 0xffffffff;\n"
                     "@P cp.async.bulk.tensor.3d.global.shared::cta.bulk_group [%0, {%2, %3, %4}], [%1];\n}\n"
                     :: "l"(map), "r"(src), "r"(c0), "r"(c1), "r"(c2) : "memory");
}
__device__ __forceinline__ void warp_tma_add(const CUtensorMap* map, uint32_t src, int c0, int c1, int c2) {
    asm volatile("{\n.reg .pred P;\nelect.sync _|P, 0xffffffff;\n"
                 "@P cp.reduce.async.bulk.tensor.3d.global.shared::cta.add.tile.bulk_group [%0, {%2, %3, %4}], [%1];\n}\n"
                 :: "l"(map), "r"(src), "r"(c0), "r"(c1), "r"(c2) : "memory");
}
__device__ __forceinline__ void warp_bulk_store(void* dst, uint32_t src, uint32_t bytes) {
    asm volatile("{\n.reg .pred P;\nelect.sync _|P, 0xffffffff;\n"
                 "@P cp.async.bulk.global.shared::cta.bulk_group [%0], [%1], %2;\n}\n" :: "l"(dst), "r"(src), "r"(bytes) : "memory");
}
__device__ __forceinline__ void warp_prefetch(const void* src, uint32_t bytes) {
    asm volatile("{\n.reg .pred P;\nelect.sync _|P, 0xffffffff;\n@P cp.async.bulk.prefetch.L2.global [%0], %1;\n}\n" :: "l"(src), "r"(bytes) : "memory");
}
__device__ __forceinline__ void bulk_commit() { asm volatile("cp.async.bulk.commit_group;" ::: "memory"); }
template <int N> __device__ __forceinline__ void bulk_wait_read() { asm volatile("cp.async.bulk.wait_group.read %0;" :: "n"(N) : "memory"); }
template <int N> __device__ __forceinline__ void bulk_wait() { asm volatile("cp.async.bulk.wait_group %0;" :: "n"(N) : "memory"); }
__device__ __forceinline__ void wgmma_fence() { asm volatile("wgmma.fence.sync.aligned;" ::: "memory"); }
__device__ __forceinline__ void wgmma_commit() { asm volatile("wgmma.commit_group.sync.aligned;" ::: "memory"); }
template <int N> __device__ __forceinline__ void wgmma_wait() { asm volatile("wgmma.wait_group.sync.aligned %0;" :: "n"(N) : "memory"); }
template <int N> __device__ __forceinline__ void fence_regs(float (&d)[N]) {
#pragma unroll
    for (int i = 0; i < N; i++) asm volatile("" : "+f"(d[i]) :: "memory");
}
template <int N> __device__ __forceinline__ void fence_regs(uint32_t (&d)[N]) {
#pragma unroll
    for (int i = 0; i < N; i++) asm volatile("" : "+r"(d[i]) :: "memory");
}
template <int N> __device__ __forceinline__ void reg_dec() { asm volatile("setmaxnreg.dec.sync.aligned.u32 %0;" :: "n"(N)); }
template <int N> __device__ __forceinline__ void reg_inc() { asm volatile("setmaxnreg.inc.sync.aligned.u32 %0;" :: "n"(N)); }
__device__ __forceinline__ uint32_t pack_bf16(float lo, float hi) {
    uint32_t r; asm("cvt.rn.bf16x2.f32 %0, %1, %2;" : "=r"(r) : "f"(hi), "f"(lo)); return r;
}
__device__ __forceinline__ void stmatrix_x4(uint32_t addr, uint32_t r0, uint32_t r1, uint32_t r2, uint32_t r3) {
    asm volatile("stmatrix.sync.aligned.m8n8.x4.shared.b16 [%0], {%1, %2, %3, %4};"
                 :: "r"(addr), "r"(r0), "r"(r1), "r"(r2), "r"(r3) : "memory");
}
__device__ __forceinline__ float ex2(float x) { float y; asm("ex2.approx.ftz.f32 %0, %1;" : "=f"(y) : "f"(x)); return y; }

constexpr uint32_t DESC_HI = (1024 >> 4) | (1u << 30);
__device__ __forceinline__ uint32_t make_desc(uint32_t addr, uint32_t lbo) {
    uint32_t lo = ((addr & 0x3FFFF) >> 4) | ((lbo >> 4) << 16);
    asm volatile("" : "+r"(lo));
    return lo;
}
__device__ __forceinline__ uint64_t full_desc(uint32_t lo) {
    uint64_t d; asm("mov.b64 %0, {%1, %2};" : "=l"(d) : "r"(lo), "r"(DESC_HI)); return d;
}

__device__ __forceinline__ void wgmma_ss_n256_tb_init(float (&d)[128], uint64_t da, uint64_t db) {
    asm volatile("{\n.reg .pred p;\n"
        "setp.ne.b32 p, 0, 0;\n"
        "wgmma.mma_async.sync.aligned.m64n256k16.f32.bf16.bf16 "
        "{%0, %1, %2, %3, %4, %5, %6, %7, %8, %9, %10, %11, %12, %13, %14, %15, %16, %17, %18, %19, %20, "
        "%21, %22, %23, %24, %25, %26, %27, %28, %29, %30, %31, %32, %33, %34, %35, %36, %37, %38, %39, %40, "
        "%41, %42, %43, %44, %45, %46, %47, %48, %49, %50, %51, %52, %53, %54, %55, %56, %57, %58, %59, %60, "
        "%61, %62, %63, %64, %65, %66, %67, %68, %69, %70, %71, %72, %73, %74, %75, %76, %77, %78, %79, %80, "
        "%81, %82, %83, %84, %85, %86, %87, %88, %89, %90, %91, %92, %93, %94, %95, %96, %97, %98, %99, "
        "%100, %101, %102, %103, %104, %105, %106, %107, %108, %109, %110, %111, %112, %113, %114, %115, "
        "%116, %117, %118, %119, %120, %121, %122, %123, %124, %125, %126, %127},"
        " %128, %129, p, 1, 1, 0, 1;\n}\n"
        : "=f"(d[0]), "=f"(d[1]), "=f"(d[2]), "=f"(d[3]), "=f"(d[4]), "=f"(d[5]), "=f"(d[6]), "=f"(d[7]),
        "=f"(d[8]), "=f"(d[9]), "=f"(d[10]), "=f"(d[11]), "=f"(d[12]), "=f"(d[13]), "=f"(d[14]), "=f"(d[15]),
        "=f"(d[16]), "=f"(d[17]), "=f"(d[18]), "=f"(d[19]), "=f"(d[20]), "=f"(d[21]), "=f"(d[22]),
        "=f"(d[23]), "=f"(d[24]), "=f"(d[25]), "=f"(d[26]), "=f"(d[27]), "=f"(d[28]), "=f"(d[29]),
        "=f"(d[30]), "=f"(d[31]), "=f"(d[32]), "=f"(d[33]), "=f"(d[34]), "=f"(d[35]), "=f"(d[36]),
        "=f"(d[37]), "=f"(d[38]), "=f"(d[39]), "=f"(d[40]), "=f"(d[41]), "=f"(d[42]), "=f"(d[43]),
        "=f"(d[44]), "=f"(d[45]), "=f"(d[46]), "=f"(d[47]), "=f"(d[48]), "=f"(d[49]), "=f"(d[50]),
        "=f"(d[51]), "=f"(d[52]), "=f"(d[53]), "=f"(d[54]), "=f"(d[55]), "=f"(d[56]), "=f"(d[57]),
        "=f"(d[58]), "=f"(d[59]), "=f"(d[60]), "=f"(d[61]), "=f"(d[62]), "=f"(d[63]), "=f"(d[64]),
        "=f"(d[65]), "=f"(d[66]), "=f"(d[67]), "=f"(d[68]), "=f"(d[69]), "=f"(d[70]), "=f"(d[71]),
        "=f"(d[72]), "=f"(d[73]), "=f"(d[74]), "=f"(d[75]), "=f"(d[76]), "=f"(d[77]), "=f"(d[78]),
        "=f"(d[79]), "=f"(d[80]), "=f"(d[81]), "=f"(d[82]), "=f"(d[83]), "=f"(d[84]), "=f"(d[85]),
        "=f"(d[86]), "=f"(d[87]), "=f"(d[88]), "=f"(d[89]), "=f"(d[90]), "=f"(d[91]), "=f"(d[92]),
        "=f"(d[93]), "=f"(d[94]), "=f"(d[95]), "=f"(d[96]), "=f"(d[97]), "=f"(d[98]), "=f"(d[99]),
        "=f"(d[100]), "=f"(d[101]), "=f"(d[102]), "=f"(d[103]), "=f"(d[104]), "=f"(d[105]), "=f"(d[106]),
        "=f"(d[107]), "=f"(d[108]), "=f"(d[109]), "=f"(d[110]), "=f"(d[111]), "=f"(d[112]), "=f"(d[113]),
        "=f"(d[114]), "=f"(d[115]), "=f"(d[116]), "=f"(d[117]), "=f"(d[118]), "=f"(d[119]), "=f"(d[120]),
        "=f"(d[121]), "=f"(d[122]), "=f"(d[123]), "=f"(d[124]), "=f"(d[125]), "=f"(d[126]), "=f"(d[127])
        : "l"(da), "l"(db));
}
__device__ __forceinline__ void wgmma_ss_n256_tb(float (&d)[128], uint64_t da, uint64_t db, int scale_d) {
    asm volatile("{\n.reg .pred p;\n"
        "setp.ne.b32 p, %130, 0;\n"
        "wgmma.mma_async.sync.aligned.m64n256k16.f32.bf16.bf16 "
        "{%0, %1, %2, %3, %4, %5, %6, %7, %8, %9, %10, %11, %12, %13, %14, %15, %16, %17, %18, %19, %20, "
        "%21, %22, %23, %24, %25, %26, %27, %28, %29, %30, %31, %32, %33, %34, %35, %36, %37, %38, %39, %40, "
        "%41, %42, %43, %44, %45, %46, %47, %48, %49, %50, %51, %52, %53, %54, %55, %56, %57, %58, %59, %60, "
        "%61, %62, %63, %64, %65, %66, %67, %68, %69, %70, %71, %72, %73, %74, %75, %76, %77, %78, %79, %80, "
        "%81, %82, %83, %84, %85, %86, %87, %88, %89, %90, %91, %92, %93, %94, %95, %96, %97, %98, %99, "
        "%100, %101, %102, %103, %104, %105, %106, %107, %108, %109, %110, %111, %112, %113, %114, %115, "
        "%116, %117, %118, %119, %120, %121, %122, %123, %124, %125, %126, %127},"
        " %128, %129, p, 1, 1, 0, 1;\n}\n"
        : "+f"(d[0]), "+f"(d[1]), "+f"(d[2]), "+f"(d[3]), "+f"(d[4]), "+f"(d[5]), "+f"(d[6]), "+f"(d[7]),
        "+f"(d[8]), "+f"(d[9]), "+f"(d[10]), "+f"(d[11]), "+f"(d[12]), "+f"(d[13]), "+f"(d[14]), "+f"(d[15]),
        "+f"(d[16]), "+f"(d[17]), "+f"(d[18]), "+f"(d[19]), "+f"(d[20]), "+f"(d[21]), "+f"(d[22]),
        "+f"(d[23]), "+f"(d[24]), "+f"(d[25]), "+f"(d[26]), "+f"(d[27]), "+f"(d[28]), "+f"(d[29]),
        "+f"(d[30]), "+f"(d[31]), "+f"(d[32]), "+f"(d[33]), "+f"(d[34]), "+f"(d[35]), "+f"(d[36]),
        "+f"(d[37]), "+f"(d[38]), "+f"(d[39]), "+f"(d[40]), "+f"(d[41]), "+f"(d[42]), "+f"(d[43]),
        "+f"(d[44]), "+f"(d[45]), "+f"(d[46]), "+f"(d[47]), "+f"(d[48]), "+f"(d[49]), "+f"(d[50]),
        "+f"(d[51]), "+f"(d[52]), "+f"(d[53]), "+f"(d[54]), "+f"(d[55]), "+f"(d[56]), "+f"(d[57]),
        "+f"(d[58]), "+f"(d[59]), "+f"(d[60]), "+f"(d[61]), "+f"(d[62]), "+f"(d[63]), "+f"(d[64]),
        "+f"(d[65]), "+f"(d[66]), "+f"(d[67]), "+f"(d[68]), "+f"(d[69]), "+f"(d[70]), "+f"(d[71]),
        "+f"(d[72]), "+f"(d[73]), "+f"(d[74]), "+f"(d[75]), "+f"(d[76]), "+f"(d[77]), "+f"(d[78]),
        "+f"(d[79]), "+f"(d[80]), "+f"(d[81]), "+f"(d[82]), "+f"(d[83]), "+f"(d[84]), "+f"(d[85]),
        "+f"(d[86]), "+f"(d[87]), "+f"(d[88]), "+f"(d[89]), "+f"(d[90]), "+f"(d[91]), "+f"(d[92]),
        "+f"(d[93]), "+f"(d[94]), "+f"(d[95]), "+f"(d[96]), "+f"(d[97]), "+f"(d[98]), "+f"(d[99]),
        "+f"(d[100]), "+f"(d[101]), "+f"(d[102]), "+f"(d[103]), "+f"(d[104]), "+f"(d[105]), "+f"(d[106]),
        "+f"(d[107]), "+f"(d[108]), "+f"(d[109]), "+f"(d[110]), "+f"(d[111]), "+f"(d[112]), "+f"(d[113]),
        "+f"(d[114]), "+f"(d[115]), "+f"(d[116]), "+f"(d[117]), "+f"(d[118]), "+f"(d[119]), "+f"(d[120]),
        "+f"(d[121]), "+f"(d[122]), "+f"(d[123]), "+f"(d[124]), "+f"(d[125]), "+f"(d[126]), "+f"(d[127])
        : "l"(da), "l"(db), "r"(scale_d));
}
__device__ __forceinline__ void wgmma_ss_n128_init(float (&d)[64], uint64_t da, uint64_t db) {
    asm volatile("{\n.reg .pred p;\n"
        "setp.ne.b32 p, 0, 0;\n"
        "wgmma.mma_async.sync.aligned.m64n128k16.f32.bf16.bf16 "
        "{%0, %1, %2, %3, %4, %5, %6, %7, %8, %9, %10, %11, %12, %13, %14, %15, %16, %17, %18, %19, %20, "
        "%21, %22, %23, %24, %25, %26, %27, %28, %29, %30, %31, %32, %33, %34, %35, %36, %37, %38, %39, %40, "
        "%41, %42, %43, %44, %45, %46, %47, %48, %49, %50, %51, %52, %53, %54, %55, %56, %57, %58, %59, %60, "
        "%61, %62, %63},"
        " %64, %65, p, 1, 1, 0, 0;\n}\n"
        : "=f"(d[0]), "=f"(d[1]), "=f"(d[2]), "=f"(d[3]), "=f"(d[4]), "=f"(d[5]), "=f"(d[6]), "=f"(d[7]),
        "=f"(d[8]), "=f"(d[9]), "=f"(d[10]), "=f"(d[11]), "=f"(d[12]), "=f"(d[13]), "=f"(d[14]), "=f"(d[15]),
        "=f"(d[16]), "=f"(d[17]), "=f"(d[18]), "=f"(d[19]), "=f"(d[20]), "=f"(d[21]), "=f"(d[22]),
        "=f"(d[23]), "=f"(d[24]), "=f"(d[25]), "=f"(d[26]), "=f"(d[27]), "=f"(d[28]), "=f"(d[29]),
        "=f"(d[30]), "=f"(d[31]), "=f"(d[32]), "=f"(d[33]), "=f"(d[34]), "=f"(d[35]), "=f"(d[36]),
        "=f"(d[37]), "=f"(d[38]), "=f"(d[39]), "=f"(d[40]), "=f"(d[41]), "=f"(d[42]), "=f"(d[43]),
        "=f"(d[44]), "=f"(d[45]), "=f"(d[46]), "=f"(d[47]), "=f"(d[48]), "=f"(d[49]), "=f"(d[50]),
        "=f"(d[51]), "=f"(d[52]), "=f"(d[53]), "=f"(d[54]), "=f"(d[55]), "=f"(d[56]), "=f"(d[57]),
        "=f"(d[58]), "=f"(d[59]), "=f"(d[60]), "=f"(d[61]), "=f"(d[62]), "=f"(d[63])
        : "l"(da), "l"(db));
}
__device__ __forceinline__ void wgmma_ss_n128(float (&d)[64], uint64_t da, uint64_t db, int scale_d) {
    asm volatile("{\n.reg .pred p;\n"
        "setp.ne.b32 p, %66, 0;\n"
        "wgmma.mma_async.sync.aligned.m64n128k16.f32.bf16.bf16 "
        "{%0, %1, %2, %3, %4, %5, %6, %7, %8, %9, %10, %11, %12, %13, %14, %15, %16, %17, %18, %19, %20, "
        "%21, %22, %23, %24, %25, %26, %27, %28, %29, %30, %31, %32, %33, %34, %35, %36, %37, %38, %39, %40, "
        "%41, %42, %43, %44, %45, %46, %47, %48, %49, %50, %51, %52, %53, %54, %55, %56, %57, %58, %59, %60, "
        "%61, %62, %63},"
        " %64, %65, p, 1, 1, 0, 0;\n}\n"
        : "+f"(d[0]), "+f"(d[1]), "+f"(d[2]), "+f"(d[3]), "+f"(d[4]), "+f"(d[5]), "+f"(d[6]), "+f"(d[7]),
        "+f"(d[8]), "+f"(d[9]), "+f"(d[10]), "+f"(d[11]), "+f"(d[12]), "+f"(d[13]), "+f"(d[14]), "+f"(d[15]),
        "+f"(d[16]), "+f"(d[17]), "+f"(d[18]), "+f"(d[19]), "+f"(d[20]), "+f"(d[21]), "+f"(d[22]),
        "+f"(d[23]), "+f"(d[24]), "+f"(d[25]), "+f"(d[26]), "+f"(d[27]), "+f"(d[28]), "+f"(d[29]),
        "+f"(d[30]), "+f"(d[31]), "+f"(d[32]), "+f"(d[33]), "+f"(d[34]), "+f"(d[35]), "+f"(d[36]),
        "+f"(d[37]), "+f"(d[38]), "+f"(d[39]), "+f"(d[40]), "+f"(d[41]), "+f"(d[42]), "+f"(d[43]),
        "+f"(d[44]), "+f"(d[45]), "+f"(d[46]), "+f"(d[47]), "+f"(d[48]), "+f"(d[49]), "+f"(d[50]),
        "+f"(d[51]), "+f"(d[52]), "+f"(d[53]), "+f"(d[54]), "+f"(d[55]), "+f"(d[56]), "+f"(d[57]),
        "+f"(d[58]), "+f"(d[59]), "+f"(d[60]), "+f"(d[61]), "+f"(d[62]), "+f"(d[63])
        : "l"(da), "l"(db), "r"(scale_d));
}
__device__ __forceinline__ void wgmma_rs_n128_tb(float (&d)[64], uint32_t a0, uint32_t a1, uint32_t a2, uint32_t a3, uint64_t db, int scale_d) {
    asm volatile("{\n.reg .pred p;\n"
        "setp.ne.b32 p, %69, 0;\n"
        "wgmma.mma_async.sync.aligned.m64n128k16.f32.bf16.bf16 "
        "{%0, %1, %2, %3, %4, %5, %6, %7, %8, %9, %10, %11, %12, %13, %14, %15, %16, %17, %18, %19, %20, "
        "%21, %22, %23, %24, %25, %26, %27, %28, %29, %30, %31, %32, %33, %34, %35, %36, %37, %38, %39, %40, "
        "%41, %42, %43, %44, %45, %46, %47, %48, %49, %50, %51, %52, %53, %54, %55, %56, %57, %58, %59, %60, "
        "%61, %62, %63},"
        " {%64, %65, %66, %67}, %68, p, 1, 1, 1;\n}\n"
        : "+f"(d[0]), "+f"(d[1]), "+f"(d[2]), "+f"(d[3]), "+f"(d[4]), "+f"(d[5]), "+f"(d[6]), "+f"(d[7]),
        "+f"(d[8]), "+f"(d[9]), "+f"(d[10]), "+f"(d[11]), "+f"(d[12]), "+f"(d[13]), "+f"(d[14]), "+f"(d[15]),
        "+f"(d[16]), "+f"(d[17]), "+f"(d[18]), "+f"(d[19]), "+f"(d[20]), "+f"(d[21]), "+f"(d[22]),
        "+f"(d[23]), "+f"(d[24]), "+f"(d[25]), "+f"(d[26]), "+f"(d[27]), "+f"(d[28]), "+f"(d[29]),
        "+f"(d[30]), "+f"(d[31]), "+f"(d[32]), "+f"(d[33]), "+f"(d[34]), "+f"(d[35]), "+f"(d[36]),
        "+f"(d[37]), "+f"(d[38]), "+f"(d[39]), "+f"(d[40]), "+f"(d[41]), "+f"(d[42]), "+f"(d[43]),
        "+f"(d[44]), "+f"(d[45]), "+f"(d[46]), "+f"(d[47]), "+f"(d[48]), "+f"(d[49]), "+f"(d[50]),
        "+f"(d[51]), "+f"(d[52]), "+f"(d[53]), "+f"(d[54]), "+f"(d[55]), "+f"(d[56]), "+f"(d[57]),
        "+f"(d[58]), "+f"(d[59]), "+f"(d[60]), "+f"(d[61]), "+f"(d[62]), "+f"(d[63])
        : "r"(a0), "r"(a1), "r"(a2), "r"(a3), "l"(db), "r"(scale_d));
}
__device__ __forceinline__ void wgmma_ss_n128_tb_init(float (&d)[64], uint64_t da, uint64_t db) {
    asm volatile("{\n.reg .pred p;\n"
        "setp.ne.b32 p, 0, 0;\n"
        "wgmma.mma_async.sync.aligned.m64n128k16.f32.bf16.bf16 "
        "{%0, %1, %2, %3, %4, %5, %6, %7, %8, %9, %10, %11, %12, %13, %14, %15, %16, %17, %18, %19, %20, "
        "%21, %22, %23, %24, %25, %26, %27, %28, %29, %30, %31, %32, %33, %34, %35, %36, %37, %38, %39, %40, "
        "%41, %42, %43, %44, %45, %46, %47, %48, %49, %50, %51, %52, %53, %54, %55, %56, %57, %58, %59, %60, "
        "%61, %62, %63},"
        " %64, %65, p, 1, 1, 0, 1;\n}\n"
        : "=f"(d[0]), "=f"(d[1]), "=f"(d[2]), "=f"(d[3]), "=f"(d[4]), "=f"(d[5]), "=f"(d[6]), "=f"(d[7]),
        "=f"(d[8]), "=f"(d[9]), "=f"(d[10]), "=f"(d[11]), "=f"(d[12]), "=f"(d[13]), "=f"(d[14]), "=f"(d[15]),
        "=f"(d[16]), "=f"(d[17]), "=f"(d[18]), "=f"(d[19]), "=f"(d[20]), "=f"(d[21]), "=f"(d[22]),
        "=f"(d[23]), "=f"(d[24]), "=f"(d[25]), "=f"(d[26]), "=f"(d[27]), "=f"(d[28]), "=f"(d[29]),
        "=f"(d[30]), "=f"(d[31]), "=f"(d[32]), "=f"(d[33]), "=f"(d[34]), "=f"(d[35]), "=f"(d[36]),
        "=f"(d[37]), "=f"(d[38]), "=f"(d[39]), "=f"(d[40]), "=f"(d[41]), "=f"(d[42]), "=f"(d[43]),
        "=f"(d[44]), "=f"(d[45]), "=f"(d[46]), "=f"(d[47]), "=f"(d[48]), "=f"(d[49]), "=f"(d[50]),
        "=f"(d[51]), "=f"(d[52]), "=f"(d[53]), "=f"(d[54]), "=f"(d[55]), "=f"(d[56]), "=f"(d[57]),
        "=f"(d[58]), "=f"(d[59]), "=f"(d[60]), "=f"(d[61]), "=f"(d[62]), "=f"(d[63])
        : "l"(da), "l"(db));
}
__device__ __forceinline__ void wgmma_ss_n128_tb(float (&d)[64], uint64_t da, uint64_t db, int scale_d) {
    asm volatile("{\n.reg .pred p;\n"
        "setp.ne.b32 p, %66, 0;\n"
        "wgmma.mma_async.sync.aligned.m64n128k16.f32.bf16.bf16 "
        "{%0, %1, %2, %3, %4, %5, %6, %7, %8, %9, %10, %11, %12, %13, %14, %15, %16, %17, %18, %19, %20, "
        "%21, %22, %23, %24, %25, %26, %27, %28, %29, %30, %31, %32, %33, %34, %35, %36, %37, %38, %39, %40, "
        "%41, %42, %43, %44, %45, %46, %47, %48, %49, %50, %51, %52, %53, %54, %55, %56, %57, %58, %59, %60, "
        "%61, %62, %63},"
        " %64, %65, p, 1, 1, 0, 1;\n}\n"
        : "+f"(d[0]), "+f"(d[1]), "+f"(d[2]), "+f"(d[3]), "+f"(d[4]), "+f"(d[5]), "+f"(d[6]), "+f"(d[7]),
        "+f"(d[8]), "+f"(d[9]), "+f"(d[10]), "+f"(d[11]), "+f"(d[12]), "+f"(d[13]), "+f"(d[14]), "+f"(d[15]),
        "+f"(d[16]), "+f"(d[17]), "+f"(d[18]), "+f"(d[19]), "+f"(d[20]), "+f"(d[21]), "+f"(d[22]),
        "+f"(d[23]), "+f"(d[24]), "+f"(d[25]), "+f"(d[26]), "+f"(d[27]), "+f"(d[28]), "+f"(d[29]),
        "+f"(d[30]), "+f"(d[31]), "+f"(d[32]), "+f"(d[33]), "+f"(d[34]), "+f"(d[35]), "+f"(d[36]),
        "+f"(d[37]), "+f"(d[38]), "+f"(d[39]), "+f"(d[40]), "+f"(d[41]), "+f"(d[42]), "+f"(d[43]),
        "+f"(d[44]), "+f"(d[45]), "+f"(d[46]), "+f"(d[47]), "+f"(d[48]), "+f"(d[49]), "+f"(d[50]),
        "+f"(d[51]), "+f"(d[52]), "+f"(d[53]), "+f"(d[54]), "+f"(d[55]), "+f"(d[56]), "+f"(d[57]),
        "+f"(d[58]), "+f"(d[59]), "+f"(d[60]), "+f"(d[61]), "+f"(d[62]), "+f"(d[63])
        : "l"(da), "l"(db), "r"(scale_d));
}

enum { M_X = 0, M_C, M_WQ, M_WUK, M_WUV, M_WQKV, M_WO, M_WOB, M_SCR_LD, M_SCR_LOC, M_SCR_LOQ, M_SCR_ST, M_OUT, M_COUNT };
enum { T_Q = 0, T_K, T_V, T_B, T_OUT, T_LOCAL, T_ATTN, T_END };
constexpr int NCTA = 132;
constexpr int NITEMS = 256;
constexpr int TRIPLES = 2, WIDE = 80 - 3 * TRIPLES;
struct Params {
    CUtensorMap m[M_COUNT];
    const __nv_bfloat16* x;
    const __nv_bfloat16* gate_w;
    const char* wo;
    __nv_bfloat16* out;
    uint32_t zero;
    uint16_t plan[10][16];
    uint16_t items[NITEMS];
    uint8_t ostep[80];
};
__device__ __forceinline__ int item_type(int it) { return it >> 13; }
__device__ __forceinline__ int item_row(int it) { return it & 15; }
__device__ __forceinline__ int item_col(int it) { return (it >> 4) & 31; }
__device__ __forceinline__ int item_asc(int it) { return (it >> 9) & 1; }
constexpr int ITEM_READY = 1 << 10;

struct __align__(128) Sync {
    unsigned long long count[4];
    __align__(128) unsigned long long ctx[16];
    unsigned next, next_out, done;
    __align__(128) unsigned step[32][2];
    unsigned split[32];
};
__device__ Sync g_sync;

constexpr uint32_t GST_BYTES = 49152, SM_KV = 65536, SM_STAGING = 196608, SM_BARS = SM_STAGING + 32768;
constexpr uint32_t B_GFULL = 0, B_GEMPTY = 32, B_AFULL = 64, B_AEMPTY = 112, B_SFULL = 160, B_SEMPTY = 192,
                   B_IFULL = 224, B_IEMPTY = 288, B_XFREE = 352, B_WANT = 384, B_MEET = 392, B_HALF = 416,
                   SM_ORDY = 448, SM_QUEUE = 456, B_ALT = 488, B_QFREE = 504, SM_GATE = 512, SM_TOTAL = SM_BARS + 1536;
constexpr int QDEPTH = 8;
constexpr int FIRST_PAIR = 6;
constexpr int K_MEET = 16, K_SPLIT = 30;
constexpr int K_FETCH = 20;
constexpr uint32_t LOC_PLANE = 72 * 128;
constexpr float LOC_SCALE = 0.17677669529663687f * 1.4426950408889634f;
constexpr float SUM_LIMIT = 1180591620717411303424.f;
constexpr float REF_RANGE = 60.f;

__device__ __forceinline__ unsigned ld_acquire(const unsigned* p) {
    unsigned v; asm volatile("ld.acquire.gpu.global.u32 %0, [%1];" : "=r"(v) : "l"(p) : "memory"); return v;
}
__device__ __forceinline__ unsigned long long ld_acquire(const unsigned long long* p) {
    unsigned long long v; asm volatile("ld.acquire.gpu.global.u64 %0, [%1];" : "=l"(v) : "l"(p) : "memory"); return v;
}
__device__ __forceinline__ void spin_guard(unsigned& n) {
    asm volatile("{\n.reg .pred P;\nadd.u32 %0, %0, 1;\nsetp.gt.u32 P, %0, 16777216;\n@P trap;\n}\n" : "+r"(n));
    if (n > 1) __nanosleep(100);
}
__device__ __forceinline__ void red_add(unsigned long long* p, unsigned long long v) {
    asm volatile("red.release.gpu.global.add.u64 [%0], %1;" :: "l"(p), "l"(v) : "memory");
}
__device__ __forceinline__ float rcp(float x) { float y; asm("rcp.approx.ftz.f32 %0, %1;" : "=f"(y) : "f"(x)); return y; }
__device__ __forceinline__ float lds_f32(uint32_t addr) {
    float v; asm volatile("ld.shared.f32 %0, [%1];" : "=f"(v) : "r"(addr) : "memory"); return v;
}
__device__ __forceinline__ void ldsm_x4(uint32_t (&r)[4], uint32_t addr) {
    asm volatile("ldmatrix.sync.aligned.m8n8.x4.shared.b16 {%0, %1, %2, %3}, [%4];"
                 : "=r"(r[0]), "=r"(r[1]), "=r"(r[2]), "=r"(r[3]) : "r"(addr) : "memory");
}
__device__ __forceinline__ void ldsm_x4_t(uint32_t (&r)[4], uint32_t addr) {
    asm volatile("ldmatrix.sync.aligned.m8n8.x4.trans.shared.b16 {%0, %1, %2, %3}, [%4];"
                 : "=r"(r[0]), "=r"(r[1]), "=r"(r[2]), "=r"(r[3]) : "r"(addr) : "memory");
}
__device__ __forceinline__ void mma_k16(float (&d)[4], const uint32_t (&a)[4], uint32_t b0, uint32_t b1) {
    asm("mma.sync.aligned.m16n8k16.row.col.f32.bf16.bf16.f32 {%0,%1,%2,%3}, {%4,%5,%6,%7}, {%8,%9}, {%0,%1,%2,%3};"
        : "+f"(d[0]), "+f"(d[1]), "+f"(d[2]), "+f"(d[3]) : "r"(a[0]), "r"(a[1]), "r"(a[2]), "r"(a[3]), "r"(b0), "r"(b1));
}
__device__ __forceinline__ void mma_k16_init(float (&d)[4], const uint32_t (&a)[4], uint32_t b0, uint32_t b1) {
    asm("{\n.reg .f32 z;\nmov.f32 z, 0f00000000;\n"
        "mma.sync.aligned.m16n8k16.row.col.f32.bf16.bf16.f32 {%0,%1,%2,%3}, {%4,%5,%6,%7}, {%8,%9}, {z,z,z,z};\n}\n"
        : "=f"(d[0]), "=f"(d[1]), "=f"(d[2]), "=f"(d[3]) : "r"(a[0]), "r"(a[1]), "r"(a[2]), "r"(a[3]), "r"(b0), "r"(b1));
}
__device__ __forceinline__ void mma_k8(float (&d)[4], uint32_t a0, uint32_t a1, uint32_t b0) {
    asm("mma.sync.aligned.m16n8k8.row.col.f32.bf16.bf16.f32 {%0,%1,%2,%3}, {%4,%5}, {%6}, {%0,%1,%2,%3};"
        : "+f"(d[0]), "+f"(d[1]), "+f"(d[2]), "+f"(d[3]) : "r"(a0), "r"(a1), "r"(b0));
}
template <typename T, int N> __device__ __forceinline__ void zero_regs(T (&d)[N]) {
#pragma unroll
    for (int i = 0; i < N; i++) d[i] = 0;
}
__device__ __forceinline__ float quad_max(float v) {
    v = fmaxf(v, __shfl_xor_sync(0xffffffffu, v, 1));
    return fmaxf(v, __shfl_xor_sync(0xffffffffu, v, 2));
}
__device__ __forceinline__ float quad_sum(float v) {
    v += __shfl_xor_sync(0xffffffffu, v, 1);
    return v + __shfl_xor_sync(0xffffffffu, v, 2);
}

__device__ __forceinline__ void qk_gemm(float (&s)[64], uint32_t q_lo, uint32_t k_lo) {
    const uint64_t dq = full_desc(q_lo), dk = full_desc(k_lo);
    wgmma_fence();
    wgmma_ss_n128_init(s, dq, dk);
#pragma unroll
    for (int kk = 1; kk < 8; kk++) {
        const uint32_t o = (kk >> 2) * 1024 + (kk & 3) * 2;
        wgmma_ss_n128(s, dq + o, dk + o, 1);
    }
    wgmma_commit();
}
__device__ __forceinline__ void pv_gemm(float (&o)[64], uint32_t (&p)[32], uint32_t v_lo, int accumulate) {
    const uint64_t dv = full_desc(v_lo);
    fence_regs(o);
    fence_regs(p);
    wgmma_fence();
#pragma unroll
    for (int kk = 0; kk < 8; kk++)
        wgmma_rs_n128_tb(o, p[4 * kk], p[4 * kk + 1], p[4 * kk + 2], p[4 * kk + 3], dv + kk * 128, kk != 0 || accumulate);
    wgmma_commit();
}
__device__ __forceinline__ void row_max(const float (&s)[64], float& x0, float& x1) {
    float z0 = fmaxf(s[0], s[1]), z1 = fmaxf(s[2], s[3]);
    x0 = fmaxf(s[4], s[5]); x1 = fmaxf(s[6], s[7]);
#pragma unroll
    for (int j = 2; j < 16; j += 2) {
        z0 = fmaxf(z0, fmaxf(s[4 * j], s[4 * j + 1]));
        z1 = fmaxf(z1, fmaxf(s[4 * j + 2], s[4 * j + 3]));
        x0 = fmaxf(x0, fmaxf(s[4 * j + 4], s[4 * j + 5]));
        x1 = fmaxf(x1, fmaxf(s[4 * j + 6], s[4 * j + 7]));
    }
    x0 = quad_max(fmaxf(x0, z0)); x1 = quad_max(fmaxf(x1, z1));
}
__device__ __forceinline__ void exp_pack(uint32_t (&p)[32], const float (&s)[64], float& r0, float& r1) {
#pragma unroll
    for (int j = 0; j < 16; j++) {
        const float e0 = ex2(s[4 * j]), e1 = ex2(s[4 * j + 1]), e2 = ex2(s[4 * j + 2]), e3 = ex2(s[4 * j + 3]);
        if (j == 0) { r0 = e0 + e1; r1 = e2 + e3; }
        else { r0 += e0 + e1; r1 += e2 + e3; }
        p[2 * j] = pack_bf16(e0, e1);
        p[2 * j + 1] = pack_bf16(e2, e3);
    }
}
__device__ __forceinline__ void shift_rows(float (&s)[64], float d0, float d1) {
#pragma unroll
    for (int j = 0; j < 16; j++) { s[4 * j] -= d0; s[4 * j + 1] -= d0; s[4 * j + 2] -= d1; s[4 * j + 3] -= d1; }
}
constexpr float MASKED = -3e38f;
template <int J0>
__device__ __forceinline__ void mask_triangle(float (&s)[64], float thr) {
#pragma unroll
    for (int j = 0; j < 16; j++) {
        const float m = __saturatef((float)(8 * (j >> 1) + (j & 1)) - thr);
        const int i = 4 * (J0 + (j >> 1)) + (j & 1);
        s[i] = fmaf(m, MASKED, s[i]);
        if (j < 14) s[i + 6] = fmaf(m, MASKED, s[i + 6]);
    }
}
__device__ __forceinline__ void causal_mask(float (&s)[64], float thr, int wg) {
    asm volatile("" : "+f"(thr));
    if (wg == 0) {
        mask_triangle<0>(s, thr);
#pragma unroll
        for (int j = 32; j < 64; j++) s[j] += MASKED;
    } else {
        mask_triangle<8>(s, thr);
    }
}

__global__ void __cluster_dims__(2, 1, 1) __launch_bounds__(384, 1) fused_kernel(const __grid_constant__ Params prm) {
    extern __shared__ __align__(1024) uint8_t smem[];
    const uint32_t sb = smem_u32(smem), bars = sb + SM_BARS;
    const int warp = __shfl_sync(0xffffffffu, threadIdx.x >> 5, 0), lane = threadIdx.x & 31;

    const uint32_t rank = cluster_rank();
    const uint32_t bars0 = map_cta(bars, 0), bars_peer = map_cta(bars, rank ^ 1);

    auto plan_index = [&]() -> uint32_t {
        uint32_t p = blockIdx.x >> 1;
        asm volatile("" : "+r"(p));
        const uint32_t r = (p - 36) * 37 >> 8;
        return p < 4 ? 60 + p : p < 36 ? (p - 4 & 7) * 8 + (p - 4 >> 3) : p < 64 ? (p - 36 - 7 * r) * 8 + 4 + r : p;
    };
    auto first_item = [&]() -> int {
        const uint32_t pair = plan_index();
        const uint32_t slot = pair & 7, c = slot * 11 >> 5;
        return pair < 64 ? T_B << 13 | (4 * slot - 11 * c) << 4 | (2 * (pair >> 3) + rank) : T_K << 13 | (8 * slot + rank);
    };
    if (warp == 0) {
        if (elect_one()) {
            for (int k = 0; k < 4; k++) mbar_init(bars + B_GFULL + 8 * k, 1);
            asm volatile("fence.mbarrier_init.release.cluster;" ::: "memory");
            fence_proxy_async_smem();
        }
        __syncwarp();
        const int first_it = __shfl_sync(0xffffffffu, first_item(), 0);
        asm volatile("barrier.cluster.arrive.relaxed.aligned;" ::: "memory");
        const CUtensorMap* ma = &prm.m[item_type(first_it) == T_K ? M_C : M_X];
        const CUtensorMap* mb = &prm.m[M_WQ + item_type(first_it)];
#pragma unroll
        for (int k = 0; k < 2; k++) {
            const uint32_t dst = sb + k * GST_BYTES, fb = bars + B_GFULL + 8 * k;
            warp_expect_tx(fb, GST_BYTES);
            warp_tma_load(dst + 16384, mb, fb, 0, k * 64, item_col(first_it) * 4, true);
            warp_tma_load(dst, ma, fb, k * 64, item_row(first_it) * 128, 0, false);
            warp_tma_load(dst + 32768, mb, fb, 0, k * 64, item_col(first_it) * 4 + 2, true);
        }
    }
    if (threadIdx.x == 32) {
        for (int i = 0; i < 4; i++) mbar_init(bars + B_GEMPTY + 8 * i, 16);
        for (int i = 0; i < 6; i++) { mbar_init(bars + B_AFULL + 8 * i, 1); mbar_init(bars + B_AEMPTY + 8 * i, i < 2 ? 8 : 16); }
        for (int i = 0; i < 4; i++) { mbar_init(bars + B_SFULL + 8 * i, 4); mbar_init(bars + B_SEMPTY + 8 * i, 1); }
        for (int i = 0; i < QDEPTH; i++) { mbar_init(bars + B_IFULL + 8 * i, 1); mbar_init(bars + B_IEMPTY + 8 * i, 23); }
        mbar_init(bars + B_WANT, 2); mbar_init(bars + B_MEET, 1); mbar_init(bars + B_XFREE, 1);
        for (int i = 0; i < 4; i++) mbar_init(bars + B_HALF + 8 * i, 1);
        mbar_init(bars + B_ALT, 4); mbar_init(bars + B_ALT + 8, 4); mbar_init(bars + B_QFREE, 2);
        asm volatile("st.shared.u64 [%0], 0;" :: "r"(bars + SM_ORDY) : "memory");
        asm volatile("fence.mbarrier_init.release.cluster;\nfence.acq_rel.cta;" ::: "memory");
    }
    __syncwarp();
    if (warp != 0) asm volatile("barrier.cluster.arrive.relaxed.aligned;" ::: "memory");
    asm volatile("barrier.cluster.wait.acquire.aligned;" ::: "memory");

    uint32_t qn = 0;
    auto next_item = [&](bool releaser, bool bounded = true) -> int {
        const uint32_t slot = qn % QDEPTH;
        if (bounded) mbar_wait(bars + B_IFULL + 8 * slot, (qn / QDEPTH) & 1);
        else mbar_spin(bars + B_IFULL + 8 * slot, (qn / QDEPTH) & 1);
        uint32_t it;
        asm volatile("ld.shared.u32 %0, [%1];" : "=r"(it) : "r"(bars + SM_QUEUE + 4 * slot) : "memory");
        mbar_arrive_cluster_if(releaser, bars0 + B_IEMPTY + 8 * slot);
        qn++;
        return it;
    };

    if (warp < 4) {
        reg_dec<40>();
        if (warp == 0) {
            {
                uint32_t gph = 1;
                const uint32_t prank = __shfl_sync(0xffffffffu, rank, 0);
                auto request = [&]() { mbar_arrive_cluster_if(lane == 0, bars0 + B_WANT); };
                auto take_item = [&]() -> int { return __shfl_sync(0xffffffffu, next_item(lane == 0), 0); };
                auto inputs_seen = [&](uint32_t word, unsigned& n) -> uint32_t {
                    uint32_t v;
                    spin_guard(n);
                    asm volatile("ld.acquire.cta.shared.u32 %0, [%1];" : "=r"(v) : "r"(bars + SM_ORDY + 4 * word) : "memory");
                    return __shfl_sync(0xffffffffu, v, 0);
                };
                uint32_t oneed = 0;
                auto wait_inputs = [&](int it) {
                    if (it & ITEM_READY) return;
                    oneed += 256;
                    for (unsigned n = 0; inputs_seen(1, n) < oneed;) {}
                };
                int nxt = first_item(), ring = -1, rot = 0;
                for (int k0 = 2; item_type(nxt) <= T_LOCAL; k0 = 0) {
                    const int type = item_type(nxt), m = item_row(nxt), c = item_col(nxt);
                    if (type == T_LOCAL) {
                        wait_inputs(nxt);
                        request();
#pragma unroll 1
                        for (uint32_t st = 0; st < 4; st++) {
                            mbar_wait(bars + B_GEMPTY + 8 * st, gph);
                            const uint32_t dst = sb + st * GST_BYTES, fb = bars + B_GFULL + 8 * st;
                            warp_expect_tx(fb, st == 0 ? 32768 + 512 : st == 3 ? 0 : 4 * LOC_PLANE);
                            if (st == 3) break;
                            if (st == 0) warp_bulk_load(dst + 4 * LOC_PLANE, &g_gate[m * 128], 512, fb);
#pragma unroll 1
                            for (int i = 0; i < 4; i++)
                                warp_tma_load(dst + i * LOC_PLANE, &prm.m[st ? M_SCR_LOC : M_SCR_LOQ], fb, i * 64, m * 64 - (st ? 8 : 0), G_B + 8 * st + c, true);
                        }
                        gph ^= 1;
                        ring = -1;
                    } else {
                        const int nk = type == T_K || type == T_V ? 8 : 16, kept = ring == m + 16 * nk ? 4 : 0;
                        ring = m + 16 * nk;
                        rot = kept ? rot - 4 : 0;
                        const CUtensorMap* ma = &prm.m[nk == 8 ? M_C : M_X];
                        const CUtensorMap* mb = &prm.m[M_WQ + type];
#pragma unroll 1
                        for (int k = k0; k < nk; k++) {
                            if (k == nk - 3) request();
                            const uint32_t st = k & 3, dst = sb + st * GST_BYTES, fb = bars + B_GFULL + 8 * st;
                            const int kc = ((k + rot) & (nk - 1)) * 64;
                            mbar_wait(bars + B_GEMPTY + 8 * st, gph);
                            warp_expect_tx(fb, k < kept ? 32768 : GST_BYTES);
                            if (k >= kept) warp_tma_load(dst, ma, fb, kc, m * 128, 0, c == 15 && type != T_K);
                            warp_tma_load_pair(dst + 16384 + prank * 16384, mb, fb, 0, kc, c * 4 + 2 * prank, true);
                            if (st == 3) gph ^= 1;
                        }
                    }
                    nxt = take_item();
                }
                uint32_t kv = 0, kvph = 1;
                uint32_t qc = 0;
                auto a_parity = [&](uint32_t b) { return b < 2 ? (((qc + 1 - b) >> 1) & 1) ^ 1 : kvph ^ (b - 2 < kv); };
                const CUtensorMap* tile_map = &prm.m[M_SCR_LD];
                asm volatile("" : "+l"(tile_map));
                {
                    bool need_g = true, more = true;
                    int pv_grp = -1, pv_row = 0;
                    int pv_shared = 0;
                    bool peer_longer = false;
                    int m = 0, c = 0, asc = 0, nu = 0, uend = 0, ureq = -1, ufetch = 0;
#pragma unroll 1
                    for (int u = 0;; u++) {
                        if (u == ufetch) {
                            if (qc) nxt = take_item();
                            if (item_type(nxt) == T_ATTN) {
                                wait_inputs(nxt);
                                const uint32_t b = qc & 1, dst = sb + b * 32768, fb = bars + B_AFULL + 8 * b, row = item_row(nxt) * 128;
                                mbar_wait(bars + (qc == 0 ? B_GEMPTY : qc == 1 ? B_QFREE : B_AEMPTY + 8 * b), qc == 0 ? gph : qc == 1 ? 0 : a_parity(b));
                                warp_expect_tx(fb, 32768 + 512);
                                warp_tma_load(dst, tile_map, fb, 0, row, G_Q + item_col(nxt), false);
                                warp_tma_load(dst + 16384, tile_map, fb, 64, row, G_Q + item_col(nxt), false);
                                warp_bulk_load(bars + SM_GATE + b * 512, &g_gate[row], 512, fb);
                                qc++;
                            }
                        }
                        if (u == uend) {
                            if (!more) break;
                            more = item_type(nxt) == T_ATTN;
                            m = item_row(nxt); c = item_col(nxt); asc = item_asc(nxt);
                            nu = more ? 2 * m + 2 : 0;
                            uend = nu + ((more ? m < 2 : pv_grp >= 0) ? 3 : 0);
                            ureq = 2 * max(m - 2 - (asc & m), 0);
                            ufetch = !more ? -1 : m ? 2 * m : uend;
                            u = -1;
                            continue;
                        }
                        int grp = pv_grp, row = pv_row;
                        int shared = pv_shared;
                        if (u >= nu) {
                            if (u == nu + 1) pv_grp = -1;
                            else if (peer_longer) { grp = -1; shared = 0; }
                            else continue;
                        } else {
                            const int j = asc ? u >> 1 : m - (u >> 1);
                            if (u & 1) {
                                pv_grp = G_V + c; pv_row = j * 128; pv_shared = (m | 1) - j;
                                peer_longer = asc & ~m & 1;
                                if (u == nu - 1 && (m & 1) && item_type(nxt) == T_END) mbar_arrive_cluster_n_if(lane == 0, bars0 + B_WANT, 2);
                                if (grp < 0) continue;
                            } else {
                                if (u == ureq) request();
                                grp = G_K + c; row = j * 128; shared = (m | 1) - j;
                            }
                        }
                        uint32_t fb = bars + B_AFULL + 16 + 8 * kv, mine = sb + SM_KV + kv * 32768 + prank * 16384;
                        int c_mine = prank * 64;
                        asm volatile("" : "+r"(mine), "+r"(fb), "+r"(row), "+r"(grp), "+r"(c_mine));
                        mbar_wait(need_g ? bars + B_GEMPTY + 8 + 8 * kv : fb + B_AEMPTY - B_AFULL, need_g ? gph : kvph);
                        warp_expect_tx(fb, grp < 0 ? 0 : 32768);
                        if (shared) {
                            warp_tma_load_pair(mine, tile_map, fb, c_mine, row, grp, shared == 1);
                        } else if (grp >= 0) {
                            warp_tma_load(mine, tile_map, fb, c_mine, row, grp, true);
                            warp_tma_load(mine + 16384 - prank * 32768, tile_map, fb, 64 - c_mine, row, grp, true);
                        } else {
                            mbar_arrive_cluster_n_if(lane < 2, map_cta(fb, lane & 1) + B_AEMPTY - B_AFULL, 8);
                        }
                        if (kv == 2) need_g = false;
                        if (++kv == 4) { kv = 0; kvph ^= 1; }
                    }
                }
                if (!qc) request();
                const int it = take_item();
                int nk = 0;
                if (item_type(it) == T_OUT) {
                    const int m = item_row(it), c = item_col(it), half = c & 1;
                    nk = 80;
                    for (unsigned n = 0; (inputs_seen(1, n) & 255) != 255;) {}
                    mbar_wait(bars + B_GEMPTY + 24, gph);
                    mbar_wait(bars + B_QFREE, 0);
                    mbar_wait(bars + B_AEMPTY + 8 * (qc & 1), a_parity(qc & 1));
#pragma unroll 1
                    for (uint32_t k = 0; k < 4; k++) {
                        const uint32_t sa = prm.ostep[half ? WIDE - 1 - k : k], dst = sb + k * GST_BYTES, fb = bars + B_GFULL + 8 * k;
                        const uint32_t b0 = k ? 1 + k : ~qc & 1, b1 = 2 + k - (k == 1);
                        mbar_wait(bars + B_AEMPTY + 8 * b0, a_parity(b0));
                        mbar_arrive_cluster_if(lane == 0 && !k, bars_peer + B_XFREE);
                        warp_expect_tx(fb, GST_BYTES);
                        warp_tma_load(dst, tile_map, fb, (sa & 1) * 64, m * 128, G_LOC - 32 + (sa >> 1), true);
                        mbar_wait(bars + (k ? B_AEMPTY + 8 * b1 : B_XFREE), k ? kvph ^ (b1 - 2 < kv) : 0);
                        warp_tma_load_pair(dst + 16384 + prank * 16384, &prm.m[M_WOB], fb, 0, (sa & 63) * 64, (c >> 1) * 4 + 2 * (half ^ prank), false);
                    }
                    gph ^= 1;
                    uint32_t seen = 0;
                    for (int k = 4; k < nk; k++) {
                        if (k == K_SPLIT) nk = 2 * TRIPLES + (take_item() & 127);
                        const int kn = k + 2 * TRIPLES - nk, first = kn >= 0 && !(kn & 1);
                        const int s = kn >= 0 ? WIDE + (3 * kn + 1) / 2 : half ? WIDE - 1 - k : k;
                        const uint32_t sa = prm.ostep[s], sa2 = prm.ostep[s + first], sw = prm.ostep[s - (kn >= 0 && !first ? prank : 0)];
                        const uint32_t need = 1u << (sa >> 1 & 31) | 1u << (sa2 >> 1 & 31);
                        for (unsigned n = 0; sa < 64 && (need & ~seen);) seen = inputs_seen(0, n);
                        const uint32_t st = k & 3;
                        uint32_t dst = sb + st * GST_BYTES, fb = bars + B_GFULL + 8 * st;
                        uint32_t dstb = dst + 16384 + (first ? 0 : prank * 16384), skipb = first && (kn >> 1 & 1) != prank;
                        int a0 = (sa & 1) * 64, a1 = m * 128, a2 = (sa >> 1) + (sa < 64 ? G_CTX : G_LOC - 32);
                        int b1 = (sw & 63) * 64, b2 = (c >> 1) * 4 + 2 * (kn >= 0 ? half : half ^ prank);
                        const CUtensorMap* mb = &prm.m[sw >= 64 ? M_WOB : M_WO];
                        asm volatile("" : "+r"(dst), "+r"(fb), "+r"(dstb), "+r"(skipb), "+r"(a0), "+r"(a1), "+r"(a2), "+r"(b1), "+r"(b2), "+l"(mb));
                        mbar_wait(bars + B_GEMPTY + 8 * st, gph);
                        warp_expect_tx(fb, GST_BYTES);
                        warp_tma_load(dst, tile_map, fb, a0, a1, a2, true);
                        if (!skipb) warp_tma_load_pair(dstb, mb, fb, 0, b1, b2, false);
                        if (first) warp_tma_load(dst + 32768, tile_map, fb, (sa2 & 1) * 64, a1, G_CTX + (sa2 >> 1), true);
                        if (k < K_SPLIT && lane == 0 && !prank)
                            asm volatile("st.relaxed.gpu.global.u32 [%0], %1;" :: "l"(&g_sync.step[0][0] + m * 4 + c), "r"(k) : "memory");
                        mbar_arrive_if(k == K_MEET && lane == 0, bars + B_MEET);
                        if ((uint32_t)(k - K_FETCH) < (3 * TRIPLES + 1) / 2) {
                            const uint32_t g = prm.ostep[79 - 2 * (k - K_FETCH)] >> 1;
                            warp_prefetch((const char*)g_scr + (uint32_t)((G_CTX + g) * (SEQ * 256) + m * 32768 + c * 4096), 4096);
                            warp_prefetch(prm.wo + (uint32_t)(g * 262144 + (m * 8 + c) * 2048), 2048);
                        }
                        if (st == 3) gph ^= 1;
                    }
                    for (unsigned n = 0; ~inputs_seen(0, n);) {}
                }
#pragma unroll 1
                for (uint32_t st = 0; st < 4; st++) { mbar_wait(bars + B_GEMPTY + 8 * st, gph ^ (st < (nk & 3))); mbar_wait(bars + B_AEMPTY + 16 + 8 * st, a_parity(2 + st)); }
                unsigned left = 0;
                if (lane == 0) asm volatile("atom.relaxed.gpu.global.add.u32 %0, [%1], 1;" : "=r"(left) : "l"(&g_sync.done) : "memory");
                if (__shfl_sync(0xffffffffu, left, 0) == NCTA - 1)
#pragma unroll 1
                    for (uint32_t i = lane * 8; i < sizeof(Sync); i += 256) *(unsigned long long*)((char*)&g_sync + i) = 0;
            }
        } else if (warp <= 2) {
            if (blockIdx.x < SEQ / 16) {
                const uint32_t r0 = 16 * blockIdx.x + 8 * (warp - 1), gbuf = bars + SM_GATE + 4 * (r0 & 15);
                float z[4];
                mbar_wait(bars + B_GFULL + 24, 0);
#pragma unroll 1
                for (uint32_t i = 0; i < 8; i++) {
                    const uint32_t off = (i & 3) * 512 + lane * 16;
                    const uint4* xp = (const uint4*)((const char*)prm.x + ((r0 + (i & 4)) * 2048 + off));
                    const uint4 wv = __ldg((const uint4*)((const char*)prm.gate_w + off));
                    uint4 xv[4];
#pragma unroll
                    for (int r = 0; r < 4; r++) { xv[r] = __ldg(xp + r * 128); if (!(i & 3)) z[r] = 0.f; }
                    const uint32_t ws[4] = {wv.x, wv.y, wv.z, wv.w};
#pragma unroll
                    for (int e = 0; e < 4; e++)
#pragma unroll
                        for (int r = 0; r < 4; r++) {
                            const uint32_t xs = e == 0 ? xv[r].x : e == 1 ? xv[r].y : e == 2 ? xv[r].z : xv[r].w;
                            z[r] = fmaf(__uint_as_float(xs << 16), __uint_as_float(ws[e] << 16), z[r]);
                            z[r] = fmaf(__uint_as_float(xs & 0xffff0000u), __uint_as_float(ws[e] & 0xffff0000u), z[r]);
                        }
                    if ((i & 3) == 3) {
#pragma unroll
                        for (int o = 16; o > 0; o >>= 1)
#pragma unroll
                            for (int r = 0; r < 4; r++) z[r] += __shfl_xor_sync(0xffffffffu, z[r], o);
                        const float zr = lane & 2 ? (lane & 1 ? z[3] : z[2]) : (lane & 1 ? z[1] : z[0]);
                        asm volatile("st.shared.f32 [%0], %1;" :: "r"(gbuf + 4 * ((i & 4) + (lane & 3))), "f"(1.f / (1.f + __expf(-zr))) : "memory");
                    }
                }
                fence_proxy_async_smem();
                __syncwarp();
                warp_bulk_store((char*)g_gate + 4 * r0, gbuf, 32);
                bulk_commit();
                bulk_wait<0>();
                __syncwarp();
                if (lane == 0) red_add(&g_sync.count[3], 1);
            }
            __syncwarp();
            {
                const int w = warp - 1;
                uint32_t sph = 0, nann = 0;
                int unsent = 0, nunsent = 0;
                bool urgent = false;
                auto announce = [&]() {
                    if (!urgent) return;
                    bulk_wait<0>();
                    __syncwarp();
                    const uint32_t hb = bars + B_HALF + 8 * (nann & 3);
                    if (w == 0) {
                        mbar_arrive_if(lane == 0, hb);
                    } else {
                        mbar_wait(hb, (nann >> 2) & 1);
                        const uint32_t type = item_type(unsent), m = item_row(unsent), c = item_col(unsent);
                        const uint32_t word = type < T_B ? c >> 3 : type == T_B ? 2 : offsetof(Sync, ctx) / 8 + m;
                        const uint32_t bit = type < T_B ? 8 * (c & 7) : type == T_B ? 8 * (c & 3) : type == T_LOCAL ? 32 + c : c;
                        if (lane < nunsent) red_add((unsigned long long*)((char*)&g_sync + 8 * word), 1ull << bit);
                        __syncwarp();
                    }
                    nann++;
                    nunsent = 0; urgent = false;
                };
                int held = first_item(), it;
                bool qfree = false;
                do {
                    if (!__all_sync(0xffffffffu, mbar_test(bars + B_IFULL + 8 * (qn % QDEPTH), (qn / QDEPTH) & 1))) announce();
                    it = __shfl_sync(0xffffffffu, next_item(lane == 0), 0);
                    const int itype = item_type(it);
                    const bool keep_held = itype == T_LOCAL;
                    if (itype >= T_ATTN && held < 0) {
                        urgent = nunsent;
                        mbar_arrive_if(lane == 0 && !qfree, bars + B_QFREE);
                        qfree = true;
                    }
#pragma unroll 1
                    for (int pass = held < 0 || keep_held; pass < 2; pass++) {
                        if (pass && (itype < T_OUT || itype == T_END)) break;
                        const int cur = pass ? it : held, type = item_type(cur), m = item_row(cur), c = item_col(cur);
                        const bool local = type == T_LOCAL;
                        const int grp = pass ? (local ? G_LOC : G_CTX) + c : type * 32 + 2 * c;
#pragma unroll 1
                        for (int i = 0; i < 4 - 2 * pass; i++) {
                            const int b = i & 1;
                            const bool alt = i >= 2 && itype >= T_ATTN;
                            const uint32_t full = bars + (alt ? B_ALT + 8 * w : B_SFULL + 16 * w + 8 * b), par = alt ? 0 : sph;
                            if (i == 3 - 2 * pass || !__all_sync(0xffffffffu, mbar_test(full, par))) announce();
                            mbar_wait(full, par);
                            fence_proxy_async_smem();
                            warp_tma_store(&prm.m[local ? M_SCR_LOQ : M_SCR_ST], sb + (alt ? 32768 : SM_STAGING) + w * 16384 + b * 8192,
                                         local ? b * 128 + w * 64 : b * 64, local ? m * 64 : m * 128 + w * 64, grp + (i >> 1), local || (type < T_B && c < FIRST_PAIR));
                            bulk_commit();
                            if (pass > b) continue;
                            bulk_wait_read<0>();
                            __syncwarp();
                            mbar_arrive_if(lane <= pass && !alt, bars + B_SEMPTY + 16 * w + 8 * (b - lane));
                            sph ^= b & !alt;
                        }
                        mbar_arrive_if(lane == 0 && !qfree && itype >= T_ATTN, bars + B_QFREE);
                        qfree |= itype >= T_ATTN;
                        if (lane == nunsent) unsent = cur;
                        nunsent++;
                        urgent = nunsent == 32 || !local;
                    }
                    if (!keep_held) held = itype < T_OUT ? it : -1;
                } while (item_type(it) != T_END);
                announce();
                it = __shfl_sync(0xffffffffu, next_item(lane == 0), 0);
                if (item_type(it) == T_OUT) {
                    if (w) {
                        mbar_wait(bars + B_MEET, 0);
                        asm volatile("fence.proxy.async.global;\nfence.acq_rel.gpu;" ::: "memory");
                        mbar_arrive_cluster_if(lane == 0, bars0 + B_WANT);
                    }
                    next_item(lane == 0);
#pragma unroll 1
                    for (int i = 0; i < 4; i++) {
                        const int b = i & 1;
                        mbar_wait(bars + B_SFULL + 16 * w + 8 * b, sph ^ (i >> 1));
                        fence_proxy_async_smem();
                        warp_tma_add(&prm.m[M_OUT], sb + SM_STAGING + w * 16384 + b * 8192, (item_col(it) ^ (i < 2)) * 128 + b * 64, item_row(it) * 128 + w * 64, 0);
                        bulk_commit();
                        if (b) {
                            bulk_wait_read<0>();
                            __syncwarp();
                            mbar_arrive_if(lane < 2, bars + B_SEMPTY + 16 * w + 8 * lane);
                        }
                    }
                }
            }
        } else {
            if (elect_one()) {
                uint32_t ordy = 0;
                unsigned long long cnt_lo = 0, cnt_hi = 0;
                int late = 0;
                auto refresh = [&]() {
                    if (!late && cnt_lo == 0x30303030 && cnt_hi == SEQ / 8) late = 1;
                    asm volatile("ld.acquire.gpu.global.v2.u64 {%0, %1}, [%2];" : "=l"(cnt_lo), "=l"(cnt_hi) : "l"(late ? &g_sync.count[0] : &g_sync.count[2]) : "memory");
                };
                auto inputs_ready = [&](int it) -> bool {
                    const int c = item_col(it);
                    if (item_type(it) == T_ATTN) return late && ((c < 16 ? cnt_lo : cnt_hi) >> (4 * (c & 14)) & 255) == 48;
                    return late || (cnt_hi == SEQ / 8 && (cnt_lo >> (4 * (c & 6)) & 255) == 48);
                };
                auto publish = [&](int it, int step) {
                    const uint32_t slot = qn % QDEPTH;
                    mbar_wait(bars + B_IEMPTY + 8 * slot, ((qn / QDEPTH) & 1) ^ 1);
                    for (uint32_t r = 0; r < 2; r++) {
                        const uint32_t rb = map_cta(bars, r);
                        asm volatile("mbarrier.arrive.expect_tx.shared::cluster.b64 _, [%0], 4;" :: "r"(rb + B_IFULL + 8 * slot) : "memory");
                        asm volatile("st.async.shared::cluster.mbarrier::complete_tx::bytes.u32 [%0], %1, [%2];"
                                     :: "r"(rb + SM_QUEUE + 4 * slot), "r"(it + r * step), "r"(rb + B_IFULL + 8 * slot) : "memory");
                    }
                    qn++;
                };
                int asc = 1;
                int it;
                do {
                    if (rank == 0) {
                        mbar_wait(bars + B_WANT, qn & 1);
                        const uint32_t pair = plan_index();
                        int pit = prm.plan[pair < 64 ? pair & 7 : pair - 56][min(qn + 1, 15u)];
                        unsigned i;
                        const bool planned = item_type(pit) != T_END;
                        if (!planned) asm volatile("atom.relaxed.gpu.global.add.u32 %0, [%1], 1;" : "=r"(i) : "l"(&g_sync.next) : "memory");
                        if (cnt_lo != 0x3030303030303030ull || cnt_hi != cnt_lo) refresh();
                        if (planned) pit += (pair >> 3 & 7) << (item_type(pit) == T_LOCAL);
                        else if (i < NITEMS) pit = prm.items[i];
                        const int type = item_type(pit);
                        int step = type == T_LOCAL ? 16 : 1;
                        it = pit + (pit & (step == 1 ? 15 : 0x1f0));
                        if (type == T_ATTN) {
                            if (!asc) { it += 1; step = -1; }
                            it |= asc << 9;
                        }
                        asc = type != T_ATTN || item_row(pit) == 0 || !asc;
                        if (inputs_ready(it)) it |= ITEM_READY;
                        publish(it, step);
                    } else {
                        it = next_item(true);
                    }
                    if ((item_type(it) == T_ATTN || item_type(it) == T_LOCAL) && !(it & ITEM_READY)) {
                        unsigned n = 0;
                        while (!inputs_ready(it)) { refresh(); spin_guard(n); }
                        asm volatile("st.release.cta.shared.u32 [%0], %1;" :: "r"(bars + SM_ORDY + 4), "r"(ordy += 256) : "memory");
                    }
                } while (item_type(it) != T_END);
                if (rank == 0) {
                    mbar_wait(bars + B_WANT, qn & 1);
                    const unsigned i = atomicAdd(&g_sync.next_out, 1u), t = i < 32 ? 31 - i : i - 32;
                    it = i < 64 ? T_OUT << 13 | ((t & 3) * 2 + (i >> 5)) << 4 | (t >> 2) * 2 : T_END << 13;
                    publish(it, 1);
                } else {
                    it = next_item(true);
                }
                if (item_type(it) == T_OUT) {
                    const uint32_t m = item_row(it), half = item_col(it) & 1, tile = m * 2 + (item_col(it) >> 1);
                    unsigned* split = (unsigned*)((char*)g_sync.split + 4 * tile);
                    unsigned long long rdy = 0;
                    int state = rank ? 2 : 0;
                    for (unsigned n = 0; rdy != 0xffffffffffull || state < 2; spin_guard(n)) {
                        if (rdy != 0xffffffffffull) {
                            rdy = ld_acquire((const unsigned long long*)((char*)g_sync.ctx + 8 * m));
                            asm volatile("st.release.cta.shared.u64 [%0], %1;" :: "r"(bars + SM_ORDY), "l"(rdy) : "memory");
                        }
                        unsigned steps = 0;
                        if (state == 1) {
                            steps = ld_acquire(split);
                        } else if (state == 0 && mbar_test(bars + B_WANT, qn & 1)) {
                            state = 1;
                            unsigned seen;
                            asm volatile("atom.acq_rel.gpu.global.exch.b32 %0, [%1], 1;" : "=r"(seen) : "l"(split) : "memory");
                            if (seen) {
                                const unsigned long long v = ld_acquire((const unsigned long long*)((char*)g_sync.step + 8 * tile));
                                const int d = (int)(v >> 32) - (int)v;
                                steps = (WIDE + min(max(half ? d : -d, -12), 12)) >> 1;
                                atomicExch(split, WIDE - steps);
                            }
                        }
                        if (steps > 1) { publish(T_END << 13 | steps, 0); state = 2; }
                    }
                    if (rank) next_item(true);
                }
                #pragma unroll 1
                for (uint32_t n = qn; n < qn + QDEPTH && rank == 0; n++) mbar_wait(bars + B_IEMPTY + 8 * (n % QDEPTH), ((n / QDEPTH) & 1) ^ 1);
            }
        }
    } else {
        reg_inc<232>();
        const int wg = (warp >> 2) - 1, wq = warp & 3;
        uint32_t gph = 0;
        uint32_t kvn = 0;
        const uint32_t dA = make_desc(sb + wg * 8192, 16);
        uint32_t ti = 0;
        uint32_t sph = 1;
        const uint32_t stg = sb + SM_STAGING + wg * 16384;
        const uint32_t stg_lane = stg + (wq * 16 + (lane & 15)) * 128 + (((lane >> 4) ^ (lane & 7)) << 4);
        auto write_blocks = [&](auto n, uint32_t off, const uint32_t* v) {
            uint32_t a = stg_lane;
            asm volatile("" : "+r"(a));
            a += off;
#pragma unroll
            for (int j = 0; j < decltype(n)::value; j++)
                stmatrix_x4((a ^ (32 * (j & 3))) + (j >> 2) * 8192, v[4 * j], v[4 * j + 1], v[4 * j + 2], v[4 * j + 3]);
        };
        auto release = [&](uint32_t bar) { mbar_arrive_if(lane == 0, bars + bar); };
        const uint32_t bars_lane = map_cta(bars, lane & 1);
        auto release_stage = [&](uint32_t st) { mbar_arrive_cluster_if(lane < 2, bars_lane + B_GEMPTY + 8 * st); };
        auto take_item = [&]() -> int {
            return __shfl_sync(0xffffffffu, next_item(lane == 0, false), 0);
        };
        auto stage_acquire = [&](int b) { mbar_spin(bars + B_SEMPTY + 16 * wg + 8 * b, sph); };
        auto stage_publish = [&](int b) {
            __syncwarp();
            release(B_SFULL + 16 * wg + 8 * b);
        };
        auto stage_chunk = [&](int b, const uint32_t* v) {
            stage_acquire(b);
            write_blocks(std::integral_constant<int, 4>(), b * 8192, v);
            stage_publish(b);
            if (b) sph ^= 1;
        };
        auto publish_pair = [&]() {
            __syncwarp();
            mbar_arrive_if(lane < 2, bars + B_SFULL + 16 * wg + 8 * lane);
            sph ^= 1;
        };
        auto gemm_step = [&](float (&acc)[128], uint32_t dB, int& k, bool order) {
            const uint32_t st = k & 3;
            wgmma_wait<0>();
            release_stage((k - 1) & 3);
            mbar_spin(bars + B_GFULL + 8 * st, gph);
            const uint64_t da = full_desc(dA + st * (GST_BYTES >> 4)), db = full_desc(dB + st * (GST_BYTES >> 4));
            if (order && wg) bar_sync(3, 256);
            wgmma_fence();
#pragma unroll
            for (int kk = 0; kk < 4; kk++) wgmma_ss_n256_tb(acc, da + 2 * kk, db + 128 * kk, 1);
            wgmma_commit();
            if (order && !wg) bar_arrive(3, 256);
            gph ^= st == 3;
            k++;
        };
        if (wg == 1) bar_arrive(1, 256);
        int it = first_item();
        float s[64];
        const uint32_t dK = make_desc(sb + SM_KV, 16);
        auto kv_wait = [&](uint32_t n) { mbar_spin(bars + B_AFULL + 16 + 8 * (n & 3), (n >> 2) & 1); };
        auto first_scores = [&](bool valid) {
            if (valid) { mbar_spin(bars + B_AFULL + 8 * (ti & 1), (ti >> 1) & 1); kv_wait(kvn); }
            bar_sync(1 + wg, 256);
            qk_gemm(s, dA + (ti & 1) * 2048, dK + (kvn & 3) * 2048);
        };
        bool issued;
        {
            {
                float acc[128];
                uint32_t pk[64];
                bool pending = false;
                int held = T_END;
                auto scale_q = [&](int j0, int n) {
                    if (held != T_Q) return;
#pragma unroll
                    for (int j = j0; j < j0 + n; j++)
                        asm("{\n.reg .b32 t;\nmul.rn.bf16x2 t, %0, %2;\nfma.rn.bf16x2 %0, %0, %1, t;\n}\n" : "+r"(pk[j]) : "r"(0x3e033e03u), "r"(0xb9d8b9d8u));
                };
                zero_regs(pk);
                const uint32_t dB = make_desc(sb + 16384, 8192);
                do {
                    if (item_type(it) == T_LOCAL) {
                        int ln = lane;
                        asm volatile("" : "+r"(ln));
                        const int g = ln >> 2, t = ln & 3, par = wq & 1;
                        const uint32_t hc = (wq >> 1) * 4, pl = sb + (par * 2 + wg) * LOC_PLANE;
                        const uint32_t a16 = (ln & 15) * 128 + (((hc + (ln >> 4)) ^ (ln & 7)) << 4), a8 = (ln & 7) * 128 + (((hc + (ln >> 3)) ^ (ln & 7)) << 4);
                        const bool first0 = 2 * t > g, first1 = 2 * t + 1 > g;
                        const uint32_t fmask = (first0 ? 0xffffu : 0u) | (first1 ? 0xffff0000u : 0u);
                        const bool edge = item_row(it) == 0;
                        uint32_t q[4][2][4], kf[9][4], vf[9][4];
                        float w[8];
                        mbar_spin(bars + B_GFULL, gph);
#pragma unroll
                        for (int u = 0; u < 4; u++) { ldsm_x4(q[u][0], pl + u * 2048 + a16); ldsm_x4(q[u][1], pl + u * 2048 + (a16 ^ 32)); }
#pragma unroll
                        for (int j = 0; j < 8; j++) w[j] = lds_f32(sb + 4 * LOC_PLANE + 4 * (2 * g + par) + 64 * j);
                        __syncwarp();
                        release_stage(0);
                        mbar_spin(bars + B_GFULL + 8, gph);
#pragma unroll
                        for (int n = 0; n < 9; n++) ldsm_x4(kf[n], pl + GST_BYTES + n * 1024 + a8);
                        __syncwarp();
                        release_stage(1);
                        float s[8][2];
#pragma unroll
                        for (int u = 0; u < 4; u++) {
                            float d[3][4];
#pragma unroll
                            for (int nt = 0; nt < 3; nt++) {
                                mma_k16_init(d[nt], q[u][0], kf[2 * u + nt][0], kf[2 * u + nt][1]);
                                mma_k16(d[nt], q[u][1], kf[2 * u + nt][2], kf[2 * u + nt][3]);
                            }
                            if (u == 0 && edge) { d[0][0] = -INFINITY; d[0][1] = -INFINITY; }
                            s[2 * u][0] = first0 ? d[0][0] : d[1][0]; s[2 * u][1] = first1 ? d[0][1] : d[1][1];
                            s[2 * u + 1][0] = first0 ? d[1][2] : d[2][2]; s[2 * u + 1][1] = first1 ? d[1][3] : d[2][3];
                        }
                        mbar_spin(bars + B_GFULL + 16, gph);
#pragma unroll
                        for (int u = 0; u < 4; u++) { ldsm_x4_t(vf[2 * u], pl + 2 * GST_BYTES + u * 2048 + a16); ldsm_x4_t(vf[2 * u + 1], pl + 2 * GST_BYTES + u * 2048 + (a16 ^ 32)); }
                        ldsm_x4_t(vf[8], pl + 2 * GST_BYTES + 8192 + a8);
                        __syncwarp();
                        release_stage(2);
                        float x[8];
#pragma unroll
                        for (int j = 0; j < 8; j++) x[j] = fmaxf(s[j][0], s[j][1]);
#pragma unroll
                        for (int o = 1; o < 4; o *= 2)
#pragma unroll
                            for (int j = 0; j < 8; j++) x[j] = fmaxf(x[j], __shfl_xor_sync(0xffffffffu, x[j], o));
#pragma unroll
                        for (int j = 0; j < 8; j++) {
                            const float n = x[j] * -LOC_SCALE;
                            s[j][0] = ex2(fmaf(s[j][0], LOC_SCALE, n)); s[j][1] = ex2(fmaf(s[j][1], LOC_SCALE, n));
                            x[j] = s[j][0] + s[j][1];
                        }
#pragma unroll
                        for (int o = 1; o < 4; o *= 2)
#pragma unroll
                            for (int j = 0; j < 8; j++) x[j] += __shfl_xor_sync(0xffffffffu, x[j], o);
                        mbar_spin(bars + B_GFULL + 24, gph);
                        release_stage(3);
                        it = take_item();
                        uint32_t ob[4][8];
#pragma unroll
                        for (int u = 0; u < 4; u++) {
                            const float r0 = rcp(x[2 * u]), r1 = rcp(x[2 * u + 1]), f0 = fmaf(-w[2 * u], r0, r0), f1 = fmaf(-w[2 * u + 1], r1, r1);
                            const uint32_t p0 = pack_bf16(s[2 * u][0] * f0, s[2 * u][1] * f0), p1 = pack_bf16(s[2 * u + 1][0] * f1, s[2 * u + 1][1] * f1);
                            const uint32_t pa[4] = {p0 & fmask, 0, p0 & ~fmask, p1 & fmask};
#pragma unroll
                            for (int c = 0; c < 4; c++) {
                                float ol[4];
                                mma_k16_init(ol, pa, vf[2 * u + (c >> 1)][2 * (c & 1)], vf[2 * u + (c >> 1)][2 * (c & 1) + 1]);
                                mma_k8(ol, 0, p1 & ~fmask, u < 3 ? vf[2 * u + 2 + (c >> 1)][2 * (c & 1)] : vf[8][c]);
                                ob[u][2 * c] = pack_bf16(ol[0], ol[1]);
                                ob[u][2 * c + 1] = pack_bf16(ol[2], ol[3]);
                            }
                        }
                        stage_acquire(0); stage_acquire(1);
#pragma unroll
                        for (int u = 0; u < 4; u++) {
                            stmatrix_x4(stg + par * 8192 + u * 2048 + a16, ob[u][0], ob[u][1], ob[u][2], ob[u][3]);
                            stmatrix_x4(stg + par * 8192 + u * 2048 + (a16 ^ 32), ob[u][4], ob[u][5], ob[u][6], ob[u][7]);
                        }
                        publish_pair();
                        bar_sync(4, 256);
                        gph ^= 1;
                        continue;
                    }
                    mbar_spin(bars + B_GFULL, gph);
                    bool more;
                    do {
                        wgmma_fence();
                        wgmma_ss_n256_tb_init(acc, full_desc(dA), full_desc(dB));
#pragma unroll
                        for (int kk = 1; kk < 4; kk++) wgmma_ss_n256_tb(acc, full_desc(dA) + 2 * kk, full_desc(dB) + 128 * kk, 1);
                        wgmma_commit();
                        const int type = item_type(it), nk = type == T_K || type == T_V ? 8 : 16;
                        int k = 1;
                        do {
                            if (pending) {
                                const int kf = k - 1 - wg;
                                if (kf == 0) { scale_q(0, 16); stage_chunk(0, pk); }
                                else if (kf == 1) { scale_q(16, 16); stage_chunk(1, pk + 16); }
                                else if (kf == 3) { scale_q(32, 16); stage_chunk(0, pk + 32); }
                                else if (kf == 4) { scale_q(48, 16); stage_chunk(1, pk + 48); }
                            }
                            if (k == nk - 1) it = take_item();
                            gemm_step(acc, dB, k, item_type(it) > T_LOCAL);
                        } while (k < nk);
                        held = type;
                        more = item_type(it) < T_LOCAL;
                        if (more) mbar_spin(bars + B_GFULL, gph);
                        wgmma_wait<0>();
                        fence_regs(acc);
                        release_stage(3);
#pragma unroll
                        for (int j = 0; j < 64; j++) pk[j] = pack_bf16(acc[2 * j], acc[2 * j + 1]);
                        pending = true;
                    } while (more);
                } while (item_type(it) <= T_LOCAL);
                issued = item_type(it) == T_ATTN && (it & ITEM_READY);
                first_scores(issued);
                scale_q(0, 64);
                stage_acquire(0); stage_acquire(1);
                mbar_spin(bars + B_GEMPTY + 8, gph ^ 1);
                write_blocks(std::integral_constant<int, 8>(), 0, pk);
                write_blocks(std::integral_constant<int, 8>(), 32768 - SM_STAGING, pk + 32);
                publish_pair();
                release(B_ALT + 8 * wg);
                bar_arrive(2 - wg, 256);
                wgmma_wait<0>();
                fence_regs(s);
                if (item_type(it) == T_END) it = take_item();
            }
            while (item_type(it) == T_ATTN) {
                if (!issued) { first_scores(true); bar_arrive(2 - wg, 256); wgmma_wait<0>(); fence_regs(s); }
                issued = false;
                float o[64];
                uint32_t pa[32], pb[32];
                float n0 = 0.f, n1 = 0.f;
                int shifted = 0;
                float l0 = 0.f, l1 = 0.f, f0 = 0.f, f1 = 0.f, g0, g1;
                uint32_t has_pv = 0;
                int first = 0;
                int pending = 0;
                const uint32_t dV = make_desc(sb + SM_KV, 16384);
                const uint32_t lane_off = bars_lane - bars + B_AEMPTY - B_AFULL;
                int cur = it;
                uint32_t qoff = (ti & 1) * 2048;
                const int row = wg * 64 + wq * 16 + (lane >> 2);
                const float thr = (row & 63) - (lane & 3) * 2;
                int diag = item_row(cur) == 0 || !item_asc(cur);
                int peek = -1;
                auto kv_release = [&](uint32_t n) { mbar_arrive_cluster_if(lane < 2, bars_lane + B_AEMPTY + 16 + 8 * (n & 3)); };
                struct Slot { uint32_t bar, par, off; } slot[4];
#pragma unroll
                for (uint32_t i = 0; i < 4; i++) {
                    const uint32_t n = kvn + 1 + (i ^ 2);
                    slot[i].bar = bars + B_AFULL + 16 + 8 * (n & 3); slot[i].par = (n >> 2) & 1; slot[i].off = (n & 3) * 2048;
                }
                kvn++;
                auto next_gate = [&]() {
                    g0 = lds_f32(bars + SM_GATE + (ti & 1) * 512 + 4 * row); g1 = lds_f32(bars + SM_GATE + (ti & 1) * 512 + 4 * row + 32);
                    ti++;
                };
                next_gate();
                auto scale_o = [&]() {
#pragma unroll
                    for (int j = 0; j < 16; j++) { o[4 * j] *= f0; o[4 * j + 1] *= f0; o[4 * j + 2] *= f1; o[4 * j + 3] *= f1; }
                };
                auto pack_o = [&](uint32_t (&v)[32]) {
#pragma unroll
                    for (int j = 0; j < 32; j++) v[j] = pack_bf16(o[2 * j], o[2 * j + 1]);
                };
                auto scales = [&]() { f0 = g0 * rcp(quad_sum(l0)); f1 = g1 * rcp(quad_sum(l1)); };
                auto issue = [&](auto even, uint32_t (&pin)[32], uint32_t (&pout)[32], bool fresh, bool last) {
                    constexpr bool EVEN = decltype(even)::value;
                    Slot& sk = slot[EVEN ? 0 : 2];
                    Slot& sv = slot[EVEN ? 1 : 3];
                    kvn += 2;
                    mbar_spin(sk.bar, sk.par);
                    bar_sync(1 + wg, 256);
                    qk_gemm(s, dA + qoff, dK + sk.off);
                    if (EVEN && fresh) {
                        scales();
                        next_gate();
                        n0 = 0.f; n1 = 0.f; l0 = 0.f; l1 = 0.f;
                        shifted = 0;
                        stage_acquire(0); stage_acquire(1);
                    }
                    if (!EVEN && pending) {
                        pack_o(pout);
                        write_blocks(std::integral_constant<int, 4>(), 0, pout);
                    }
                    if (last)
                        asm volatile("{\n.reg .pred P, Q;\n"
                                     "mbarrier.test_wait.parity.shared::cta.b64 Q, [%1], %2;\n"
                                     "mbarrier.test_wait.parity.shared::cta.b64 P, [%3], %4;\n"
                                     "ld.shared.u32 %0, [%5];\n"
                                     "@!Q or.b32 %0, %0, 0x10000;\n"
                                     "@!P mov.u32 %0, -1;\n}\n"
                                     : "=r"(peek) : "r"(bars + B_AFULL + 8 * (ti & 1)), "r"((ti >> 1) & 1), "r"(bars + B_IFULL + 8 * (qn % QDEPTH)),
                                       "r"((qn / QDEPTH) & 1), "r"(bars + SM_QUEUE + 4 * (qn % QDEPTH)) : "memory");
                    diag = item_asc(cur) ? last : fresh;
                    asm volatile("" : "+r"(diag));
                    mbar_spin(sv.bar, sv.par);
                    pv_gemm(o, pin, dV + sv.off, EVEN || !first);
                    bar_arrive(2 - wg, 256);
                    if (!EVEN && pending) {
                        write_blocks(std::integral_constant<int, 4>(), 8192, pout + 16);
                        publish_pair();
                    }
                    sk.par ^= 1; sv.par ^= 1;
                    wgmma_wait<1>();
                    fence_regs(s);
                    mbar_arrive_cluster_if(lane < 2, sk.bar + lane_off);
                    mbar_arrive_if(lane == 0 && last, bars + B_AEMPTY + 8 * ((ti - 1) & 1));
                };
                auto softmax = [&](auto even, uint32_t (&pin)[32], uint32_t (&pout)[32], bool fresh) {
                    constexpr bool EVEN = decltype(even)::value;
                    Slot& sv = slot[EVEN ? 1 : 3];
                    float r0, r1, x0 = n0, x1 = n1;
#pragma unroll 1
                    for (int mask = diag, redone = 0;; mask = 0, redone = 1) {
                        if (mask | shifted) {
                            if (mask) causal_mask(s, thr, wg);
                            if (shifted) shift_rows(s, x0, x1);
                        }
                        exp_pack(pout, s, r0, r1);
                        if (!__any_sync(0xffffffffu, fmaxf(r0, r1) >= SUM_LIMIT || (EVEN && fresh && !(lane & 3) && !(fminf(s[0], s[2]) >= -REF_RANGE))) || redone) break;
                        row_max(s, x0, x1);
                        if (!(EVEN && fresh)) { x0 = fmaxf(x0, 0.f); x1 = fmaxf(x1, 0.f); }
                        float a0 = ex2(-x0), a1 = ex2(-x1);
                        n0 += x0; n1 += x1;
                        shifted = 1;
                        if (EVEN && fresh) { a0 = 1.f; a1 = 1.f; }
                        l0 *= a0; l1 *= a1;
                        wgmma_wait<0>();
                        fence_regs(o);
#pragma unroll
                        for (int q = 0; q < 16; q++) { o[4 * q] *= a0; o[4 * q + 1] *= a0; o[4 * q + 2] *= a1; o[4 * q + 3] *= a1; }
                    }
                    l0 += r0; l1 += r1;
                    wgmma_wait<0>();
                    fence_regs(o);
                    fence_regs(pin);
                    mbar_arrive_cluster_if(lane < 2, sv.bar + lane_off);
                };
                auto copy_p = [&]() {
#pragma unroll
                    for (int j = 0; j < 32; j++) pa[j] = __float_as_uint(__uint_as_float(pb[j]) + __uint_as_float(prm.zero));
                };
                int rem = 0;
                mbar_arrive_if(lane == 0 && item_row(cur) == 0, bars + B_AEMPTY + 8 * ((ti - 1) & 1));
                zero_regs(pa);
                wgmma_fence();
                wgmma_ss_n128_init(o, full_desc(dA), full_desc(dK));
                wgmma_commit();
                while (true) {
                    const bool fresh = rem == 0;
                    softmax(std::true_type(), pa, pb, fresh);
                    first = fresh;
                    if (fresh) {
                        pending = has_pv; has_pv = 1;
                        if (pending) scale_o();
                        rem = item_row(cur) + 1;
                    }
                    if (--rem == 0) {
                        copy_p();
                        const Slot t0 = slot[0], t1 = slot[1];
                        slot[0] = slot[2]; slot[1] = slot[3]; slot[2] = t0; slot[3] = t1;
                    } else {
                        issue(std::false_type(), pb, pa, false, rem == 1);
                        softmax(std::false_type(), pb, pa, false);
                        pending = 0; first = 0;
                        rem--;
                    }
                    if (rem == 0) {
                        const int seen = __shfl_sync(0xffffffffu, peek, 0);
                        if (seen >= 0) {
                            mbar_arrive_cluster_if(lane == 0, bars0 + B_IEMPTY + 8 * (qn % QDEPTH));
                            qn++;
                            it = seen & 0xffff;
                        } else {
                            it = take_item();
                        }
                        if (item_row(cur) < 2 || item_type(it) != T_ATTN) break;
                        if (seen & 0x10000) mbar_spin(bars + B_AFULL + 8 * (ti & 1), (ti >> 1) & 1);
                        cur = it;
                        qoff = (ti & 1) * 2048;
                    }
                    issue(std::true_type(), pa, pb, rem == 0, rem ? rem == 1 : item_row(cur) == 0);
                }
                const uint32_t skip = item_asc(cur) & ~item_row(cur) & 1;
                kvn += skip;
                const bool end = item_type(it) == T_END;
#pragma unroll 1
                for (int pass = pending ? 0 : 1; pass < 2; pass++) {
                    if (pass) {
                        kv_wait(kvn);
                        pv_gemm(o, pa, dV + (kvn & 3) * 2048, !first);
                        scales();
                        stage_acquire(0); stage_acquire(1);
                        if (end) it = take_item();
                        wgmma_wait<0>();
                        fence_regs(o);
                        kv_release(kvn);
                        kvn += 1 + skip;
                        scale_o();
                    }
                    pack_o(pb);
                    write_blocks(std::integral_constant<int, 8>(), 0, pb);
                    publish_pair();
                }
            }
        }
        if (item_type(it) == T_OUT) {
            float acc[128];
            const uint32_t dB = make_desc(sb + 16384, 8192);
            mbar_spin(bars + B_GFULL, gph);
            wgmma_fence();
            wgmma_ss_n256_tb_init(acc, full_desc(dA), full_desc(dB));
#pragma unroll
            for (int kk = 1; kk < 4; kk++) wgmma_ss_n256_tb(acc, full_desc(dA) + 2 * kk, full_desc(dB) + 128 * kk, 1);
            wgmma_commit();
            uint32_t ln;
            asm volatile("mov.u32 %0, %%laneid;" : "=r"(ln));
            char* const mine = (char*)prm.out + (uint32_t)((item_row(it) * 128 + wg * 64 + wq * 16 + (ln >> 4)) * 2048 + item_col(it) * 256 + (ln & 15) * 16);
            int k = 1, nk = 80;
            do {
                if ((uint32_t)(k - (K_MEET - 12)) < 8) *(uint4*)(mine + (uint32_t)(k - (K_MEET - 12)) * 4096) = make_uint4(0, 0, 0, 0);
                __syncwarp();
                if (k == K_SPLIT) nk = take_item() & 127;
                gemm_step(acc, dB, k, false);
            } while (k < nk);
            float lo[64];
            auto triple = [&](auto first) {
                const uint32_t s0 = k & 3, s1 = (k + 1) & 3, o0 = s0 * (GST_BYTES >> 4), o1 = s1 * (GST_BYTES >> 4);
                wgmma_wait<0>();
                mbar_arrive_cluster_if(ln < (decltype(first)::value ? 2 : 4), bars_lane + B_GEMPTY + 8 * ((k - 1 - (ln >> 1)) & 3));
                mbar_spin(bars + B_GFULL + 8 * s0, gph);
                gph ^= s0 == 3;
                wgmma_fence();
#pragma unroll
                for (int kk = 0; kk < 4; kk++) {
                    if (decltype(first)::value && kk == 0) wgmma_ss_n128_tb_init(lo, full_desc(dA + o0), full_desc(dB + o0));
                    else wgmma_ss_n128_tb(lo, full_desc(dA + o0) + 2 * kk, full_desc(dB + o0) + 128 * kk, 1);
                }
                mbar_spin(bars + B_GFULL + 8 * s1, gph);
                gph ^= s1 == 3;
                wgmma_fence();
#pragma unroll
                for (int kk = 0; kk < 4; kk++) wgmma_ss_n128_tb(lo, full_desc(dA + o0 + 2048) + 2 * kk, full_desc(dB + o1 + 1024) + 128 * kk, 1);
#pragma unroll
                for (int kk = 0; kk < 4; kk++) wgmma_ss_n128_tb(lo, full_desc(dA + o1) + 2 * kk, full_desc(dB + o1) + 128 * kk, 1);
                wgmma_commit();
                k += 2;
            };
            triple(std::true_type());
            fence_regs(acc);
            uint32_t pk[32];
#pragma unroll
            for (int j = 0; j < 32; j++) pk[j] = pack_bf16(acc[64 + 2 * j], acc[65 + 2 * j]);
            stage_acquire(0); stage_acquire(1);
            write_blocks(std::integral_constant<int, 8>(), 0, pk);
            publish_pair();
            triple(std::false_type());
            stage_acquire(0); stage_acquire(1);
            wgmma_wait<0>();
            fence_regs(lo);
            mbar_arrive_cluster_if(ln < 4, bars_lane + B_GEMPTY + 8 * ((k - 1 - (ln >> 1)) & 3));
#pragma unroll
            for (int b = 0; b < 2; b++) {
#pragma unroll
                for (int j = 16 * b; j < 16 * b + 16; j++) pk[j] = pack_bf16(acc[2 * j] + lo[2 * j], acc[2 * j + 1] + lo[2 * j + 1]);
                write_blocks(std::integral_constant<int, 4>(), b * 8192, pk + 16 * b);
                stage_publish(b);
            }
        }
    }
}

typedef CUresult (*EncodeFn)(CUtensorMap*, CUtensorMapDataType, cuuint32_t, void*, const cuuint64_t*, const cuuint64_t*,
                             const cuuint32_t*, const cuuint32_t*, CUtensorMapInterleave, CUtensorMapSwizzle,
                             CUtensorMapL2promotion, CUtensorMapFloatOOBfill);

void encode3(EncodeFn fn, CUtensorMap* m, const void* ptr, uint64_t d0, uint64_t d1, uint64_t d2, uint64_t s1, uint64_t s2,
             uint32_t b0, uint32_t b1, uint32_t b2) {
    cuuint64_t dims[3] = {d0, d1, d2};
    cuuint64_t strides[2] = {s1, s2};
    cuuint32_t box[3] = {b0, b1, b2};
    cuuint32_t es[3] = {1, 1, 1};
    fn(m, CU_TENSOR_MAP_DATA_TYPE_BFLOAT16, 3, const_cast<void*>(ptr), dims, strides, box, es, CU_TENSOR_MAP_INTERLEAVE_NONE,
       CU_TENSOR_MAP_SWIZZLE_128B, CU_TENSOR_MAP_L2_PROMOTION_NONE, CU_TENSOR_MAP_FLOAT_OOB_FILL_NONE);
}
void map_act(EncodeFn fn, CUtensorMap* m, const void* p, int rows, int cols, int box_rows) {
    encode3(fn, m, p, cols, rows, 1, (uint64_t)cols * 2, (uint64_t)cols * rows * 2, 64, box_rows, 1);
}
void map_wgt(EncodeFn fn, CUtensorMap* m, const void* p, int K, int N) {
    encode3(fn, m, p, 64, K, N / 64, (uint64_t)N * 2, 128, 64, 64, 2);
}

void build_schedule(Params& p) {
    int n = 0;
    auto add = [&](int type, int col, int row) { p.items[n++] = (uint16_t)(type << 13 | col << 4 | row); };
    int beta = 26, tail = 32, late = 6, early = 4, epos = 60;
    int order[16] = {6, 7, 8, 9, 10, 11, 12, 13, 14, 15, 5, 4, 3, 2, 1, 0};
    const char* plans = "xxcccccx,xxcccccx,xxxxx,xxcxlxx,xxlcclxcc,xxlcccccc,xxlxlccccc,xxlxlxccc";
    const char* pos[8];
    int len[8] = {}, start[8] = {};
    for (int s = 0; s < 8; s++) { pos[s] = plans; while (*plans && *plans++ != ',') {} }
    for (int i = 0; i < 160; i++) p.plan[i / 16][i % 16] = T_END << 13;
    for (int nx = 0, nc = 3, nl = 0; nx + nc + nl < 28 + 32 + 8;) {
        int s = -1;
        for (int i = 0; i < 8; i++) if (*pos[i] > ',' && (s < 0 || start[i] < start[s])) s = i;
        const char kind = *pos[s]++;
        int it;
        if (kind == 'x') { it = nx < 12 ? T_B << 13 | (nx % 3 * 4 + nx / 3) << 4 : T_Q << 13 | (nx - 12) << 4; nx++; }
        else if (kind == 'c') { it = (T_K + (nc & 1)) << 13 | nc / 2 << 4; nc++; }
        else { it = T_LOCAL << 13 | nl / 2 << 4 | (nl & 1); nl++; }
        p.plan[s][len[s]++] = (uint16_t)it;
        start[s] += kind == 'x' ? 48 : kind == 'c' ? 24 : 8;
    }
    for (int i = 0; i < 24; i++) p.plan[8 + i / 12][i % 12] = (uint16_t)((T_K + (i % 3 & 1)) << 13 | i % 3 / 2 << 4 | i / 3);
    const int a0 = n;
    for (int key = 0; key < 4000; key++)
        for (int r = 0; r < 32; r++)
            for (int j = 7; j >= 0; j--)
                if ((j ? (7 - j) * 40 + r * beta : 3999) == key) add(T_ATTN, 2 * order[r >> 1] + (r & 1), j);
    int t0 = n;
    for (int work = 0; work < 32 * 136 * tail / 100;) work += 4 * (p.items[--t0] & 15) + 3;
    for (int i = t0 + 1; i < n; i++)
        for (int j = i; j > t0 && (p.items[j] & 15) > (p.items[j - 1] & 15); j--) { const uint16_t t = p.items[j]; p.items[j] = p.items[j - 1]; p.items[j - 1] = t; }
    for (int r = early - 1; r >= 0; r--) {
        const uint16_t t = p.items[n - 32 + early - 1];
        for (int j = n - 32 + early - 1; j > n - epos; j--) p.items[j] = p.items[j - 1];
        p.items[n - epos] = t;
    }
    for (int moved = 0; moved < 2 && late >= 0; moved++)
        for (int i = a0; i < n; i++)
            if (p.items[i] == (T_ATTN << 13 | (2 * order[15] + moved) << 4 | late)) {
                for (int j = i; j + 1 < n; j++) p.items[j] = p.items[j + 1];
                p.items[n - 1] = (uint16_t)(T_ATTN << 13 | (2 * order[15] + moved) << 4 | late);
                break;
            }
    for (int s = 0, lo = 0, hi = WIDE - 1; s < 80; s++) {
        const int r = s / 2, g = r < 8 ? 32 + r : 2 * order[r / 2 - 4] + (r & 1);
        p.ostep[s >= WIDE ? s : r & 1 ? hi-- : lo++] = (uint8_t)(2 * g + (s & 1));
    }
}

void build_params(Params& p, void* const* d_in, void* d_out) {
    void* fnp = nullptr;
    cudaDriverEntryPointQueryResult qr;
    cudaGetDriverEntryPoint("cuTensorMapEncodeTiled", &fnp, cudaEnableDefault, &qr);
    EncodeFn fn = (EncodeFn)fnp;
    void* scr = nullptr;
    cudaGetSymbolAddress(&scr, g_scr);
    map_act(fn, &p.m[M_X], d_in[0], SEQ, 1024, 128);
    map_act(fn, &p.m[M_C], d_in[1], SEQ, 512, 128);
    map_wgt(fn, &p.m[M_WQ], d_in[2], 1024, 4096);
    map_wgt(fn, &p.m[M_WUK], d_in[3], 512, 4096);
    map_wgt(fn, &p.m[M_WUV], d_in[4], 512, 4096);
    map_wgt(fn, &p.m[M_WO], d_in[5], 4096, 1024);
    map_wgt(fn, &p.m[M_WQKV], d_in[7], 1024, 3072);
    map_wgt(fn, &p.m[M_WOB], d_in[8], 1024, 1024);
    encode3(fn, &p.m[M_SCR_LD], scr, 128, SEQ, G_TOTAL, 256, (uint64_t)SEQ * 256, 64, 128, 1);
    encode3(fn, &p.m[M_SCR_LOC], scr, 256, SEQ / 2, G_TOTAL, 512, (uint64_t)SEQ * 256, 64, 72, 1);
    encode3(fn, &p.m[M_SCR_LOQ], scr, 256, SEQ / 2, G_TOTAL, 512, (uint64_t)SEQ * 256, 64, 64, 1);
    encode3(fn, &p.m[M_SCR_ST], scr, 128, SEQ, G_TOTAL, 256, (uint64_t)SEQ * 256, 64, 64, 1);
    map_act(fn, &p.m[M_OUT], d_out, SEQ, 1024, 64);
    p.x = (const __nv_bfloat16*)d_in[0];
    p.gate_w = (const __nv_bfloat16*)d_in[9];
    p.zero = 0;
    p.wo = (const char*)d_in[5];
    p.out = (__nv_bfloat16*)d_out;
    build_schedule(p);
}

}

extern "C" void kernel_launch(void* const* d_in, const int* in_sizes, int n_in, void* d_out, int out_size) {
    (void)in_sizes; (void)n_in; (void)out_size;
    Params p;
    build_params(p, d_in, d_out);
    cudaFuncSetAttribute(fused_kernel, cudaFuncAttributeMaxDynamicSharedMemorySize, SM_TOTAL);
    fused_kernel<<<NCTA, 384, SM_TOTAL>>>(p);
}
```

```cpp
#include <cuda_runtime.h>
#include <cuda_bf16.h>
#include <cuda.h>
#include <stddef.h>
#include <stdint.h>
#include <type_traits>

namespace {

constexpr int SEQ = 2048;
constexpr int G_Q = 0, G_K = 32, G_V = 64, G_B = 96, G_CTX = G_Q, G_LOC = G_B, G_TOTAL = 120;

__device__ __align__(1024) __nv_bfloat16 g_scr[(size_t)G_TOTAL * SEQ * 128];
__device__ __align__(128) float g_gate[SEQ];

__device__ __forceinline__ uint32_t smem_u32(const void* p) { return (uint32_t)__cvta_generic_to_shared(p); }
__device__ __forceinline__ bool elect_one() {
    uint32_t p;
    asm volatile("{\n.reg .pred P;\nelect.sync _|P, 0xffffffff;\nselp.u32 %0, 1, 0, P;\n}\n" : "=r"(p));
    return p != 0;
}
__device__ __forceinline__ void mbar_init(uint32_t bar, uint32_t count) {
    asm volatile("mbarrier.init.shared::cta.b64 [%0], %1;" :: "r"(bar), "r"(count) : "memory");
}
__device__ __forceinline__ uint32_t cluster_rank() { uint32_t r; asm("mov.u32 %0, %%cluster_ctarank;" : "=r"(r)); return r; }
__device__ __forceinline__ uint32_t map_cta(uint32_t addr, uint32_t cta) {
    uint32_t r; asm("mapa.shared::cluster.u32 %0, %1, %2;" : "=r"(r) : "r"(addr), "r"(cta)); return r;
}
__device__ __forceinline__ void mbar_arrive_cluster_if(bool pred, uint32_t cluster_bar) {
    asm volatile("{\n.reg .pred P;\nsetp.ne.u32 P, %1, 0;\n@P mbarrier.arrive.shared::cluster.b64 _, [%0];\n}\n"
                 :: "r"(cluster_bar), "r"((uint32_t)pred) : "memory");
}
__device__ __forceinline__ void mbar_arrive_cluster_n_if(bool pred, uint32_t cluster_bar, uint32_t count) {
    asm volatile("{\n.reg .pred P;\nsetp.ne.u32 P, %1, 0;\n@P mbarrier.arrive.shared::cluster.b64 _, [%0], %2;\n}\n"
                 :: "r"(cluster_bar), "r"((uint32_t)pred), "r"(count) : "memory");
}
__device__ __forceinline__ void mbar_arrive_if(bool pred, uint32_t bar) {
    asm volatile("{\n.reg .pred P;\nsetp.ne.u32 P, %1, 0;\n@P mbarrier.arrive.shared::cta.b64 _, [%0];\n}\n"
                 :: "r"(bar), "r"((uint32_t)pred) : "memory");
}
__device__ __forceinline__ bool mbar_test(uint32_t bar, uint32_t parity) {
    uint32_t ok;
    asm volatile("{\n.reg .pred P;\nmbarrier.test_wait.parity.shared::cta.b64 P, [%1], %2;\nselp.u32 %0, 1, 0, P;\n}\n"
                 : "=r"(ok) : "r"(bar), "r"(parity) : "memory");
    return ok != 0;
}
__device__ __forceinline__ void mbar_wait(uint32_t bar, uint32_t parity) {
    asm volatile("{\n.reg .pred P;\n.reg .u32 c;\n"
                 "mov.u32 c, 0;\n"
                 "SPIN:\n"
                 "mbarrier.try_wait.parity.shared::cta.b64 P, [%0], %1;\n"
                 "@P bra DONE;\n"
                 "add.u32 c, c, 1;\n"
                 "setp.lt.u32 P, c, 4194304;\n"
                 "@P bra SPIN;\n"
                 "trap;\n"
                 "DONE:\n}\n" :: "r"(bar), "r"(parity) : "memory");
}
__device__ __forceinline__ void mbar_spin(uint32_t bar, uint32_t parity) {
    asm volatile("{\n.reg .pred P;\n"
                 "SPIN:\n"
                 "mbarrier.try_wait.parity.shared::cta.b64 P, [%0], %1;\n"
                 "@!P bra SPIN;\n}\n" :: "r"(bar), "r"(parity) : "memory");
}
__device__ __forceinline__ void bar_sync(int id, int n) { asm volatile("bar.sync %0, %1;" :: "r"(id), "r"(n) : "memory"); }
__device__ __forceinline__ void bar_arrive(int id, int n) { asm volatile("bar.arrive %0, %1;" :: "r"(id), "r"(n) : "memory"); }
__device__ __forceinline__ void fence_proxy_async_smem() { asm volatile("fence.proxy.async.shared::cta;" ::: "memory"); }
__device__ __forceinline__ void warp_expect_tx(uint32_t bar, uint32_t bytes) {
    asm volatile("{\n.reg .pred P;\nelect.sync _|P, 0xffffffff;\n@P mbarrier.arrive.expect_tx.shared::cta.b64 _, [%0], %1;\n}\n"
                 :: "r"(bar), "r"(bytes) : "memory");
}
constexpr uint64_t EVICT_FIRST = 0x12F0000000000000ull;
__device__ __forceinline__ void warp_tma_load(uint32_t dst, const CUtensorMap* map, uint32_t bar, int c0, int c1, int c2, bool stream) {
    if (stream)
        asm volatile("{\n.reg .pred P;\nelect.sync _|P, 0xffffffff;\n"
                     "@P cp.async.bulk.tensor.3d.shared::cluster.global.mbarrier::complete_tx::bytes.L2::cache_hint"
                     " [%0], [%1, {%3, %4, %5}], [%2], %6;\n}\n"
                     :: "r"(dst), "l"(map), "r"(bar), "r"(c0), "r"(c1), "r"(c2), "l"(EVICT_FIRST) : "memory");
    else
        asm volatile("{\n.reg .pred P;\nelect.sync _|P, 0xffffffff;\n"
                     "@P cp.async.bulk.tensor.3d.shared::cluster.global.mbarrier::complete_tx::bytes [%0], [%1, {%3, %4, %5}], [%2];\n}\n"
                     :: "r"(dst), "l"(map), "r"(bar), "r"(c0), "r"(c1), "r"(c2) : "memory");
}
__device__ __forceinline__ void warp_tma_load_pair(uint32_t dst, const CUtensorMap* map, uint32_t bar, int c0, int c1, int c2, bool stream) {
    if (stream)
        asm volatile("{\n.reg .pred P;\nelect.sync _|P, 0xffffffff;\n"
                     "@P cp.async.bulk.tensor.3d.shared::cluster.global.mbarrier::complete_tx::bytes.multicast::cluster.L2::cache_hint"
                     " [%0], [%1, {%3, %4, %5}], [%2], %6, %7;\n}\n"
                     :: "r"(dst), "l"(map), "r"(bar), "r"(c0), "r"(c1), "r"(c2), "h"((uint16_t)3), "l"(EVICT_FIRST) : "memory");
    else
        asm volatile("{\n.reg .pred P;\nelect.sync _|P, 0xffffffff;\n"
                     "@P cp.async.bulk.tensor.3d.shared::cluster.global.mbarrier::complete_tx::bytes.multicast::cluster"
                     " [%0], [%1, {%3, %4, %5}], [%2], %6;\n}\n"
                     :: "r"(dst), "l"(map), "r"(bar), "r"(c0), "r"(c1), "r"(c2), "h"((uint16_t)3) : "memory");
}
__device__ __forceinline__ void warp_bulk_load(uint32_t dst, const void* src, uint32_t bytes, uint32_t bar) {
    asm volatile("{\n.reg .pred P;\nelect.sync _|P, 0xffffffff;\n"
                 "@P cp.async.bulk.shared::cluster.global.mbarrier::complete_tx::bytes [%0], [%1], %2, [%3];\n}\n"
                 :: "r"(dst), "l"(src), "r"(bytes), "r"(bar) : "memory");
}
__device__ __forceinline__ void warp_tma_store(const CUtensorMap* map, uint32_t src, int c0, int c1, int c2, bool stream) {
    if (stream)
        asm volatile("{\n.reg .pred P;\nelect.sync _|P, 0xffffffff;\n"
                     "@P cp.async.bulk.tensor.3d.global.shared::cta.bulk_group.L2::cache_hint [%0, {%2, %3, %4}], [%1], %5;\n}\n"
                     :: "l"(map), "r"(src), "r"(c0), "r"(c1), "r"(c2), "l"(EVICT_FIRST) : "memory");
    else
        asm volatile("{\n.reg .pred P;\nelect.sync _|P, 0xffffffff;\n"
                     "@P cp.async.bulk.tensor.3d.global.shared::cta.bulk_group [%0, {%2, %3, %4}], [%1];\n}\n"
                     :: "l"(map), "r"(src), "r"(c0), "r"(c1), "r"(c2) : "memory");
}
__device__ __forceinline__ void warp_tma_add(const CUtensorMap* map, uint32_t src, int c0, int c1, int c2) {
    asm volatile("{\n.reg .pred P;\nelect.sync _|P, 0xffffffff;\n"
                 "@P cp.reduce.async.bulk.tensor.3d.global.shared::cta.add.tile.bulk_group [%0, {%2, %3, %4}], [%1];\n}\n"
                 :: "l"(map), "r"(src), "r"(c0), "r"(c1), "r"(c2) : "memory");
}
__device__ __forceinline__ void warp_bulk_store(void* dst, uint32_t src, uint32_t bytes) {
    asm volatile("{\n.reg .pred P;\nelect.sync _|P, 0xffffffff;\n"
                 "@P cp.async.bulk.global.shared::cta.bulk_group [%0], [%1], %2;\n}\n" :: "l"(dst), "r"(src), "r"(bytes) : "memory");
}
__device__ __forceinline__ void warp_prefetch(const void* src, uint32_t bytes) {
    asm volatile("{\n.reg .pred P;\nelect.sync _|P, 0xffffffff;\n@P cp.async.bulk.prefetch.L2.global [%0], %1;\n}\n" :: "l"(src), "r"(bytes) : "memory");
}
__device__ __forceinline__ void bulk_commit() { asm volatile("cp.async.bulk.commit_group;" ::: "memory"); }
template <int N> __device__ __forceinline__ void bulk_wait_read() { asm volatile("cp.async.bulk.wait_group.read %0;" :: "n"(N) : "memory"); }
template <int N> __device__ __forceinline__ void bulk_wait() { asm volatile("cp.async.bulk.wait_group %0;" :: "n"(N) : "memory"); }
__device__ __forceinline__ void wgmma_fence() { asm volatile("wgmma.fence.sync.aligned;" ::: "memory"); }
__device__ __forceinline__ void wgmma_commit() { asm volatile("wgmma.commit_group.sync.aligned;" ::: "memory"); }
template <int N> __device__ __forceinline__ void wgmma_wait() { asm volatile("wgmma.wait_group.sync.aligned %0;" :: "n"(N) : "memory"); }
template <int N> __device__ __forceinline__ void fence_regs(float (&d)[N]) {
#pragma unroll
    for (int i = 0; i < N; i++) asm volatile("" : "+f"(d[i]) :: "memory");
}
template <int N> __device__ __forceinline__ void fence_regs(uint32_t (&d)[N]) {
#pragma unroll
    for (int i = 0; i < N; i++) asm volatile("" : "+r"(d[i]) :: "memory");
}
template <int N> __device__ __forceinline__ void reg_dec() { asm volatile("setmaxnreg.dec.sync.aligned.u32 %0;" :: "n"(N)); }
template <int N> __device__ __forceinline__ void reg_inc() { asm volatile("setmaxnreg.inc.sync.aligned.u32 %0;" :: "n"(N)); }
__device__ __forceinline__ uint32_t pack_bf16(float lo, float hi) {
    uint32_t r; asm("cvt.rn.bf16x2.f32 %0, %1, %2;" : "=r"(r) : "f"(hi), "f"(lo)); return r;
}
__device__ __forceinline__ void stmatrix_x4(uint32_t addr, uint32_t r0, uint32_t r1, uint32_t r2, uint32_t r3) {
    asm volatile("stmatrix.sync.aligned.m8n8.x4.shared.b16 [%0], {%1, %2, %3, %4};"
                 :: "r"(addr), "r"(r0), "r"(r1), "r"(r2), "r"(r3) : "memory");
}
__device__ __forceinline__ float ex2(float x) { float y; asm("ex2.approx.ftz.f32 %0, %1;" : "=f"(y) : "f"(x)); return y; }

constexpr uint32_t DESC_HI = (1024 >> 4) | (1u << 30);
__device__ __forceinline__ uint32_t make_desc(uint32_t addr, uint32_t lbo) {
    uint32_t lo = ((addr & 0x3FFFF) >> 4) | ((lbo >> 4) << 16);
    asm volatile("" : "+r"(lo));
    return lo;
}
__device__ __forceinline__ uint64_t full_desc(uint32_t lo) {
    uint64_t d; asm("mov.b64 %0, {%1, %2};" : "=l"(d) : "r"(lo), "r"(DESC_HI)); return d;
}

__device__ __forceinline__ void wgmma_ss_n256_tb_init(float (&d)[128], uint64_t da, uint64_t db) {
    asm volatile("{\n.reg .pred p;\n"
        "setp.ne.b32 p, 0, 0;\n"
        "wgmma.mma_async.sync.aligned.m64n256k16.f32.bf16.bf16 "
        "{%0, %1, %2, %3, %4, %5, %6, %7, %8, %9, %10, %11, %12, %13, %14, %15, %16, %17, %18, %19, %20, "
        "%21, %22, %23, %24, %25, %26, %27, %28, %29, %30, %31, %32, %33, %34, %35, %36, %37, %38, %39, %40, "
        "%41, %42, %43, %44, %45, %46, %47, %48, %49, %50, %51, %52, %53, %54, %55, %56, %57, %58, %59, %60, "
        "%61, %62, %63, %64, %65, %66, %67, %68, %69, %70, %71, %72, %73, %74, %75, %76, %77, %78, %79, %80, "
        "%81, %82, %83, %84, %85, %86, %87, %88, %89, %90, %91, %92, %93, %94, %95, %96, %97, %98, %99, "
        "%100, %101, %102, %103, %104, %105, %106, %107, %108, %109, %110, %111, %112, %113, %114, %115, "
        "%116, %117, %118, %119, %120, %121, %122, %123, %124, %125, %126, %127},"
        " %128, %129, p, 1, 1, 0, 1;\n}\n"
        : "=f"(d[0]), "=f"(d[1]), "=f"(d[2]), "=f"(d[3]), "=f"(d[4]), "=f"(d[5]), "=f"(d[6]), "=f"(d[7]),
        "=f"(d[8]), "=f"(d[9]), "=f"(d[10]), "=f"(d[11]), "=f"(d[12]), "=f"(d[13]), "=f"(d[14]), "=f"(d[15]),
        "=f"(d[16]), "=f"(d[17]), "=f"(d[18]), "=f"(d[19]), "=f"(d[20]), "=f"(d[21]), "=f"(d[22]),
        "=f"(d[23]), "=f"(d[24]), "=f"(d[25]), "=f"(d[26]), "=f"(d[27]), "=f"(d[28]), "=f"(d[29]),
        "=f"(d[30]), "=f"(d[31]), "=f"(d[32]), "=f"(d[33]), "=f"(d[34]), "=f"(d[35]), "=f"(d[36]),
        "=f"(d[37]), "=f"(d[38]), "=f"(d[39]), "=f"(d[40]), "=f"(d[41]), "=f"(d[42]), "=f"(d[43]),
        "=f"(d[44]), "=f"(d[45]), "=f"(d[46]), "=f"(d[47]), "=f"(d[48]), "=f"(d[49]), "=f"(d[50]),
        "=f"(d[51]), "=f"(d[52]), "=f"(d[53]), "=f"(d[54]), "=f"(d[55]), "=f"(d[56]), "=f"(d[57]),
        "=f"(d[58]), "=f"(d[59]), "=f"(d[60]), "=f"(d[61]), "=f"(d[62]), "=f"(d[63]), "=f"(d[64]),
        "=f"(d[65]), "=f"(d[66]), "=f"(d[67]), "=f"(d[68]), "=f"(d[69]), "=f"(d[70]), "=f"(d[71]),
        "=f"(d[72]), "=f"(d[73]), "=f"(d[74]), "=f"(d[75]), "=f"(d[76]), "=f"(d[77]), "=f"(d[78]),
        "=f"(d[79]), "=f"(d[80]), "=f"(d[81]), "=f"(d[82]), "=f"(d[83]), "=f"(d[84]), "=f"(d[85]),
        "=f"(d[86]), "=f"(d[87]), "=f"(d[88]), "=f"(d[89]), "=f"(d[90]), "=f"(d[91]), "=f"(d[92]),
        "=f"(d[93]), "=f"(d[94]), "=f"(d[95]), "=f"(d[96]), "=f"(d[97]), "=f"(d[98]), "=f"(d[99]),
        "=f"(d[100]), "=f"(d[101]), "=f"(d[102]), "=f"(d[103]), "=f"(d[104]), "=f"(d[105]), "=f"(d[106]),
        "=f"(d[107]), "=f"(d[108]), "=f"(d[109]), "=f"(d[110]), "=f"(d[111]), "=f"(d[112]), "=f"(d[113]),
        "=f"(d[114]), "=f"(d[115]), "=f"(d[116]), "=f"(d[117]), "=f"(d[118]), "=f"(d[119]), "=f"(d[120]),
        "=f"(d[121]), "=f"(d[122]), "=f"(d[123]), "=f"(d[124]), "=f"(d[125]), "=f"(d[126]), "=f"(d[127])
        : "l"(da), "l"(db));
}
__device__ __forceinline__ void wgmma_ss_n256_tb(float (&d)[128], uint64_t da, uint64_t db, int scale_d) {
    asm volatile("{\n.reg .pred p;\n"
        "setp.ne.b32 p, %130, 0;\n"
        "wgmma.mma_async.sync.aligned.m64n256k16.f32.bf16.bf16 "
        "{%0, %1, %2, %3, %4, %5, %6, %7, %8, %9, %10, %11, %12, %13, %14, %15, %16, %17, %18, %19, %20, "
        "%21, %22, %23, %24, %25, %26, %27, %28, %29, %30, %31, %32, %33, %34, %35, %36, %37, %38, %39, %40, "
        "%41, %42, %43, %44, %45, %46, %47, %48, %49, %50, %51, %52, %53, %54, %55, %56, %57, %58, %59, %60, "
        "%61, %62, %63, %64, %65, %66, %67, %68, %69, %70, %71, %72, %73, %74, %75, %76, %77, %78, %79, %80, "
        "%81, %82, %83, %84, %85, %86, %87, %88, %89, %90, %91, %92, %93, %94, %95, %96, %97, %98, %99, "
        "%100, %101, %102, %103, %104, %105, %106, %107, %108, %109, %110, %111, %112, %113, %114, %115, "
        "%116, %117, %118, %119, %120, %121, %122, %123, %124, %125, %126, %127},"
        " %128, %129, p, 1, 1, 0, 1;\n}\n"
        : "+f"(d[0]), "+f"(d[1]), "+f"(d[2]), "+f"(d[3]), "+f"(d[4]), "+f"(d[5]), "+f"(d[6]), "+f"(d[7]),
        "+f"(d[8]), "+f"(d[9]), "+f"(d[10]), "+f"(d[11]), "+f"(d[12]), "+f"(d[13]), "+f"(d[14]), "+f"(d[15]),
        "+f"(d[16]), "+f"(d[17]), "+f"(d[18]), "+f"(d[19]), "+f"(d[20]), "+f"(d[21]), "+f"(d[22]),
        "+f"(d[23]), "+f"(d[24]), "+f"(d[25]), "+f"(d[26]), "+f"(d[27]), "+f"(d[28]), "+f"(d[29]),
        "+f"(d[30]), "+f"(d[31]), "+f"(d[32]), "+f"(d[33]), "+f"(d[34]), "+f"(d[35]), "+f"(d[36]),
        "+f"(d[37]), "+f"(d[38]), "+f"(d[39]), "+f"(d[40]), "+f"(d[41]), "+f"(d[42]), "+f"(d[43]),
        "+f"(d[44]), "+f"(d[45]), "+f"(d[46]), "+f"(d[47]), "+f"(d[48]), "+f"(d[49]), "+f"(d[50]),
        "+f"(d[51]), "+f"(d[52]), "+f"(d[53]), "+f"(d[54]), "+f"(d[55]), "+f"(d[56]), "+f"(d[57]),
        "+f"(d[58]), "+f"(d[59]), "+f"(d[60]), "+f"(d[61]), "+f"(d[62]), "+f"(d[63]), "+f"(d[64]),
        "+f"(d[65]), "+f"(d[66]), "+f"(d[67]), "+f"(d[68]), "+f"(d[69]), "+f"(d[70]), "+f"(d[71]),
        "+f"(d[72]), "+f"(d[73]), "+f"(d[74]), "+f"(d[75]), "+f"(d[76]), "+f"(d[77]), "+f"(d[78]),
        "+f"(d[79]), "+f"(d[80]), "+f"(d[81]), "+f"(d[82]), "+f"(d[83]), "+f"(d[84]), "+f"(d[85]),
        "+f"(d[86]), "+f"(d[87]), "+f"(d[88]), "+f"(d[89]), "+f"(d[90]), "+f"(d[91]), "+f"(d[92]),
        "+f"(d[93]), "+f"(d[94]), "+f"(d[95]), "+f"(d[96]), "+f"(d[97]), "+f"(d[98]), "+f"(d[99]),
        "+f"(d[100]), "+f"(d[101]), "+f"(d[102]), "+f"(d[103]), "+f"(d[104]), "+f"(d[105]), "+f"(d[106]),
        "+f"(d[107]), "+f"(d[108]), "+f"(d[109]), "+f"(d[110]), "+f"(d[111]), "+f"(d[112]), "+f"(d[113]),
        "+f"(d[114]), "+f"(d[115]), "+f"(d[116]), "+f"(d[117]), "+f"(d[118]), "+f"(d[119]), "+f"(d[120]),
        "+f"(d[121]), "+f"(d[122]), "+f"(d[123]), "+f"(d[124]), "+f"(d[125]), "+f"(d[126]), "+f"(d[127])
        : "l"(da), "l"(db), "r"(scale_d));
}
__device__ __forceinline__ void wgmma_ss_n128_init(float (&d)[64], uint64_t da, uint64_t db) {
    asm volatile("{\n.reg .pred p;\n"
        "setp.ne.b32 p, 0, 0;\n"
        "wgmma.mma_async.sync.aligned.m64n128k16.f32.bf16.bf16 "
        "{%0, %1, %2, %3, %4, %5, %6, %7, %8, %9, %10, %11, %12, %13, %14, %15, %16, %17, %18, %19, %20, "
        "%21, %22, %23, %24, %25, %26, %27, %28, %29, %30, %31, %32, %33, %34, %35, %36, %37, %38, %39, %40, "
        "%41, %42, %43, %44, %45, %46, %47, %48, %49, %50, %51, %52, %53, %54, %55, %56, %57, %58, %59, %60, "
        "%61, %62, %63},"
        " %64, %65, p, 1, 1, 0, 0;\n}\n"
        : "=f"(d[0]), "=f"(d[1]), "=f"(d[2]), "=f"(d[3]), "=f"(d[4]), "=f"(d[5]), "=f"(d[6]), "=f"(d[7]),
        "=f"(d[8]), "=f"(d[9]), "=f"(d[10]), "=f"(d[11]), "=f"(d[12]), "=f"(d[13]), "=f"(d[14]), "=f"(d[15]),
        "=f"(d[16]), "=f"(d[17]), "=f"(d[18]), "=f"(d[19]), "=f"(d[20]), "=f"(d[21]), "=f"(d[22]),
        "=f"(d[23]), "=f"(d[24]), "=f"(d[25]), "=f"(d[26]), "=f"(d[27]), "=f"(d[28]), "=f"(d[29]),
        "=f"(d[30]), "=f"(d[31]), "=f"(d[32]), "=f"(d[33]), "=f"(d[34]), "=f"(d[35]), "=f"(d[36]),
        "=f"(d[37]), "=f"(d[38]), "=f"(d[39]), "=f"(d[40]), "=f"(d[41]), "=f"(d[42]), "=f"(d[43]),
        "=f"(d[44]), "=f"(d[45]), "=f"(d[46]), "=f"(d[47]), "=f"(d[48]), "=f"(d[49]), "=f"(d[50]),
        "=f"(d[51]), "=f"(d[52]), "=f"(d[53]), "=f"(d[54]), "=f"(d[55]), "=f"(d[56]), "=f"(d[57]),
        "=f"(d[58]), "=f"(d[59]), "=f"(d[60]), "=f"(d[61]), "=f"(d[62]), "=f"(d[63])
        : "l"(da), "l"(db));
}
__device__ __forceinline__ void wgmma_ss_n128(float (&d)[64], uint64_t da, uint64_t db, int scale_d) {
    asm volatile("{\n.reg .pred p;\n"
        "setp.ne.b32 p, %66, 0;\n"
        "wgmma.mma_async.sync.aligned.m64n128k16.f32.bf16.bf16 "
        "{%0, %1, %2, %3, %4, %5, %6, %7, %8, %9, %10, %11, %12, %13, %14, %15, %16, %17, %18, %19, %20, "
        "%21, %22, %23, %24, %25, %26, %27, %28, %29, %30, %31, %32, %33, %34, %35, %36, %37, %38, %39, %40, "
        "%41, %42, %43, %44, %45, %46, %47, %48, %49, %50, %51, %52, %53, %54, %55, %56, %57, %58, %59, %60, "
        "%61, %62, %63},"
        " %64, %65, p, 1, 1, 0, 0;\n}\n"
        : "+f"(d[0]), "+f"(d[1]), "+f"(d[2]), "+f"(d[3]), "+f"(d[4]), "+f"(d[5]), "+f"(d[6]), "+f"(d[7]),
        "+f"(d[8]), "+f"(d[9]), "+f"(d[10]), "+f"(d[11]), "+f"(d[12]), "+f"(d[13]), "+f"(d[14]), "+f"(d[15]),
        "+f"(d[16]), "+f"(d[17]), "+f"(d[18]), "+f"(d[19]), "+f"(d[20]), "+f"(d[21]), "+f"(d[22]),
        "+f"(d[23]), "+f"(d[24]), "+f"(d[25]), "+f"(d[26]), "+f"(d[27]), "+f"(d[28]), "+f"(d[29]),
        "+f"(d[30]), "+f"(d[31]), "+f"(d[32]), "+f"(d[33]), "+f"(d[34]), "+f"(d[35]), "+f"(d[36]),
        "+f"(d[37]), "+f"(d[38]), "+f"(d[39]), "+f"(d[40]), "+f"(d[41]), "+f"(d[42]), "+f"(d[43]),
        "+f"(d[44]), "+f"(d[45]), "+f"(d[46]), "+f"(d[47]), "+f"(d[48]), "+f"(d[49]), "+f"(d[50]),
        "+f"(d[51]), "+f"(d[52]), "+f"(d[53]), "+f"(d[54]), "+f"(d[55]), "+f"(d[56]), "+f"(d[57]),
        "+f"(d[58]), "+f"(d[59]), "+f"(d[60]), "+f"(d[61]), "+f"(d[62]), "+f"(d[63])
        : "l"(da), "l"(db), "r"(scale_d));
}
__device__ __forceinline__ void wgmma_rs_n128_tb(float (&d)[64], uint32_t a0, uint32_t a1, uint32_t a2, uint32_t a3, uint64_t db, int scale_d) {
    asm volatile("{\n.reg .pred p;\n"
        "setp.ne.b32 p, %69, 0;\n"
        "wgmma.mma_async.sync.aligned.m64n128k16.f32.bf16.bf16 "
        "{%0, %1, %2, %3, %4, %5, %6, %7, %8, %9, %10, %11, %12, %13, %14, %15, %16, %17, %18, %19, %20, "
        "%21, %22, %23, %24, %25, %26, %27, %28, %29, %30, %31, %32, %33, %34, %35, %36, %37, %38, %39, %40, "
        "%41, %42, %43, %44, %45, %46, %47, %48, %49, %50, %51, %52, %53, %54, %55, %56, %57, %58, %59, %60, "
        "%61, %62, %63},"
        " {%64, %65, %66, %67}, %68, p, 1, 1, 1;\n}\n"
        : "+f"(d[0]), "+f"(d[1]), "+f"(d[2]), "+f"(d[3]), "+f"(d[4]), "+f"(d[5]), "+f"(d[6]), "+f"(d[7]),
        "+f"(d[8]), "+f"(d[9]), "+f"(d[10]), "+f"(d[11]), "+f"(d[12]), "+f"(d[13]), "+f"(d[14]), "+f"(d[15]),
        "+f"(d[16]), "+f"(d[17]), "+f"(d[18]), "+f"(d[19]), "+f"(d[20]), "+f"(d[21]), "+f"(d[22]),
        "+f"(d[23]), "+f"(d[24]), "+f"(d[25]), "+f"(d[26]), "+f"(d[27]), "+f"(d[28]), "+f"(d[29]),
        "+f"(d[30]), "+f"(d[31]), "+f"(d[32]), "+f"(d[33]), "+f"(d[34]), "+f"(d[35]), "+f"(d[36]),
        "+f"(d[37]), "+f"(d[38]), "+f"(d[39]), "+f"(d[40]), "+f"(d[41]), "+f"(d[42]), "+f"(d[43]),
        "+f"(d[44]), "+f"(d[45]), "+f"(d[46]), "+f"(d[47]), "+f"(d[48]), "+f"(d[49]), "+f"(d[50]),
        "+f"(d[51]), "+f"(d[52]), "+f"(d[53]), "+f"(d[54]), "+f"(d[55]), "+f"(d[56]), "+f"(d[57]),
        "+f"(d[58]), "+f"(d[59]), "+f"(d[60]), "+f"(d[61]), "+f"(d[62]), "+f"(d[63])
        : "r"(a0), "r"(a1), "r"(a2), "r"(a3), "l"(db), "r"(scale_d));
}
__device__ __forceinline__ void wgmma_ss_n128_tb_init(float (&d)[64], uint64_t da, uint64_t db) {
    asm volatile("{\n.reg .pred p;\n"
        "setp.ne.b32 p, 0, 0;\n"
        "wgmma.mma_async.sync.aligned.m64n128k16.f32.bf16.bf16 "
        "{%0, %1, %2, %3, %4, %5, %6, %7, %8, %9, %10, %11, %12, %13, %14, %15, %16, %17, %18, %19, %20, "
        "%21, %22, %23, %24, %25, %26, %27, %28, %29, %30, %31, %32, %33, %34, %35, %36, %37, %38, %39, %40, "
        "%41, %42, %43, %44, %45, %46, %47, %48, %49, %50, %51, %52, %53, %54, %55, %56, %57, %58, %59, %60, "
        "%61, %62, %63},"
        " %64, %65, p, 1, 1, 0, 1;\n}\n"
        : "=f"(d[0]), "=f"(d[1]), "=f"(d[2]), "=f"(d[3]), "=f"(d[4]), "=f"(d[5]), "=f"(d[6]), "=f"(d[7]),
        "=f"(d[8]), "=f"(d[9]), "=f"(d[10]), "=f"(d[11]), "=f"(d[12]), "=f"(d[13]), "=f"(d[14]), "=f"(d[15]),
        "=f"(d[16]), "=f"(d[17]), "=f"(d[18]), "=f"(d[19]), "=f"(d[20]), "=f"(d[21]), "=f"(d[22]),
        "=f"(d[23]), "=f"(d[24]), "=f"(d[25]), "=f"(d[26]), "=f"(d[27]), "=f"(d[28]), "=f"(d[29]),
        "=f"(d[30]), "=f"(d[31]), "=f"(d[32]), "=f"(d[33]), "=f"(d[34]), "=f"(d[35]), "=f"(d[36]),
        "=f"(d[37]), "=f"(d[38]), "=f"(d[39]), "=f"(d[40]), "=f"(d[41]), "=f"(d[42]), "=f"(d[43]),
        "=f"(d[44]), "=f"(d[45]), "=f"(d[46]), "=f"(d[47]), "=f"(d[48]), "=f"(d[49]), "=f"(d[50]),
        "=f"(d[51]), "=f"(d[52]), "=f"(d[53]), "=f"(d[54]), "=f"(d[55]), "=f"(d[56]), "=f"(d[57]),
        "=f"(d[58]), "=f"(d[59]), "=f"(d[60]), "=f"(d[61]), "=f"(d[62]), "=f"(d[63])
        : "l"(da), "l"(db));
}
__device__ __forceinline__ void wgmma_ss_n128_tb(float (&d)[64], uint64_t da, uint64_t db, int scale_d) {
    asm volatile("{\n.reg .pred p;\n"
        "setp.ne.b32 p, %66, 0;\n"
        "wgmma.mma_async.sync.aligned.m64n128k16.f32.bf16.bf16 "
        "{%0, %1, %2, %3, %4, %5, %6, %7, %8, %9, %10, %11, %12, %13, %14, %15, %16, %17, %18, %19, %20, "
        "%21, %22, %23, %24, %25, %26, %27, %28, %29, %30, %31, %32, %33, %34, %35, %36, %37, %38, %39, %40, "
        "%41, %42, %43, %44, %45, %46, %47, %48, %49, %50, %51, %52, %53, %54, %55, %56, %57, %58, %59, %60, "
        "%61, %62, %63},"
        " %64, %65, p, 1, 1, 0, 1;\n}\n"
        : "+f"(d[0]), "+f"(d[1]), "+f"(d[2]), "+f"(d[3]), "+f"(d[4]), "+f"(d[5]), "+f"(d[6]), "+f"(d[7]),
        "+f"(d[8]), "+f"(d[9]), "+f"(d[10]), "+f"(d[11]), "+f"(d[12]), "+f"(d[13]), "+f"(d[14]), "+f"(d[15]),
        "+f"(d[16]), "+f"(d[17]), "+f"(d[18]), "+f"(d[19]), "+f"(d[20]), "+f"(d[21]), "+f"(d[22]),
        "+f"(d[23]), "+f"(d[24]), "+f"(d[25]), "+f"(d[26]), "+f"(d[27]), "+f"(d[28]), "+f"(d[29]),
        "+f"(d[30]), "+f"(d[31]), "+f"(d[32]), "+f"(d[33]), "+f"(d[34]), "+f"(d[35]), "+f"(d[36]),
        "+f"(d[37]), "+f"(d[38]), "+f"(d[39]), "+f"(d[40]), "+f"(d[41]), "+f"(d[42]), "+f"(d[43]),
        "+f"(d[44]), "+f"(d[45]), "+f"(d[46]), "+f"(d[47]), "+f"(d[48]), "+f"(d[49]), "+f"(d[50]),
        "+f"(d[51]), "+f"(d[52]), "+f"(d[53]), "+f"(d[54]), "+f"(d[55]), "+f"(d[56]), "+f"(d[57]),
        "+f"(d[58]), "+f"(d[59]), "+f"(d[60]), "+f"(d[61]), "+f"(d[62]), "+f"(d[63])
        : "l"(da), "l"(db), "r"(scale_d));
}

enum { M_X = 0, M_C, M_WQ, M_WUK, M_WUV, M_WQKV, M_WO, M_WOB, M_SCR_LD, M_SCR_LOC, M_SCR_LOQ, M_SCR_ST, M_OUT, M_COUNT };
enum { T_Q = 0, T_K, T_V, T_B, T_OUT, T_LOCAL, T_ATTN, T_END };
constexpr int NCTA = 132;
constexpr int NITEMS = 256;
constexpr int TRIPLES = 2, WIDE = 80 - 3 * TRIPLES;
struct Params {
    CUtensorMap m[M_COUNT];
    const __nv_bfloat16* x;
    const __nv_bfloat16* gate_w;
    const char* wo;
    __nv_bfloat16* out;
    uint32_t zero;
    uint16_t plan[10][16];
    uint16_t items[NITEMS];
    uint8_t ostep[80];
};
__device__ __forceinline__ int item_type(int it) { return it >> 13; }
__device__ __forceinline__ int item_row(int it) { return it & 15; }
__device__ __forceinline__ int item_col(int it) { return (it >> 4) & 31; }
__device__ __forceinline__ int item_asc(int it) { return (it >> 9) & 1; }
constexpr int ITEM_READY = 1 << 10;

struct __align__(128) Sync {
    unsigned long long count[4];
    __align__(128) unsigned long long ctx[16];
    unsigned next, next_out, done;
    __align__(128) unsigned step[32][2];
    unsigned split[32];
};
__device__ Sync g_sync;

constexpr uint32_t GST_BYTES = 49152, SM_KV = 65536, SM_STAGING = 196608, SM_BARS = SM_STAGING + 32768;
constexpr uint32_t B_GFULL = 0, B_GEMPTY = 32, B_AFULL = 64, B_AEMPTY = 112, B_SFULL = 160, B_SEMPTY = 192,
                   B_IFULL = 224, B_IEMPTY = 288, B_XFREE = 352, B_WANT = 384, B_MEET = 392, B_HALF = 416,
                   SM_ORDY = 448, SM_QUEUE = 456, B_ALT = 488, B_QFREE = 504, SM_GATE = 512, SM_TOTAL = SM_BARS + 1536;
constexpr int QDEPTH = 8;
constexpr int FIRST_PAIR = 6;
constexpr int K_MEET = 16, K_SPLIT = 30;
constexpr int K_FETCH = 20;
constexpr uint32_t LOC_PLANE = 72 * 128;
constexpr float LOC_SCALE = 0.17677669529663687f * 1.4426950408889634f;
constexpr float SUM_LIMIT = 1180591620717411303424.f;
constexpr float REF_RANGE = 60.f;

__device__ __forceinline__ unsigned ld_acquire(const unsigned* p) {
    unsigned v; asm volatile("ld.acquire.gpu.global.u32 %0, [%1];" : "=r"(v) : "l"(p) : "memory"); return v;
}
__device__ __forceinline__ unsigned long long ld_acquire(const unsigned long long* p) {
    unsigned long long v; asm volatile("ld.acquire.gpu.global.u64 %0, [%1];" : "=l"(v) : "l"(p) : "memory"); return v;
}
__device__ __forceinline__ void spin_guard(unsigned& n) {
    asm volatile("{\n.reg .pred P;\nadd.u32 %0, %0, 1;\nsetp.gt.u32 P, %0, 16777216;\n@P trap;\n}\n" : "+r"(n));
    if (n > 1) __nanosleep(100);
}
__device__ __forceinline__ void red_add(unsigned long long* p, unsigned long long v) {
    asm volatile("red.release.gpu.global.add.u64 [%0], %1;" :: "l"(p), "l"(v) : "memory");
}
__device__ __forceinline__ float rcp(float x) { float y; asm("rcp.approx.ftz.f32 %0, %1;" : "=f"(y) : "f"(x)); return y; }
__device__ __forceinline__ float lds_f32(uint32_t addr) {
    float v; asm volatile("ld.shared.f32 %0, [%1];" : "=f"(v) : "r"(addr) : "memory"); return v;
}
__device__ __forceinline__ void ldsm_x4(uint32_t (&r)[4], uint32_t addr) {
    asm volatile("ldmatrix.sync.aligned.m8n8.x4.shared.b16 {%0, %1, %2, %3}, [%4];"
                 : "=r"(r[0]), "=r"(r[1]), "=r"(r[2]), "=r"(r[3]) : "r"(addr) : "memory");
}
__device__ __forceinline__ void ldsm_x4_t(uint32_t (&r)[4], uint32_t addr) {
    asm volatile("ldmatrix.sync.aligned.m8n8.x4.trans.shared.b16 {%0, %1, %2, %3}, [%4];"
                 : "=r"(r[0]), "=r"(r[1]), "=r"(r[2]), "=r"(r[3]) : "r"(addr) : "memory");
}
__device__ __forceinline__ void mma_k16(float (&d)[4], const uint32_t (&a)[4], uint32_t b0, uint32_t b1) {
    asm("mma.sync.aligned.m16n8k16.row.col.f32.bf16.bf16.f32 {%0,%1,%2,%3}, {%4,%5,%6,%7}, {%8,%9}, {%0,%1,%2,%3};"
        : "+f"(d[0]), "+f"(d[1]), "+f"(d[2]), "+f"(d[3]) : "r"(a[0]), "r"(a[1]), "r"(a[2]), "r"(a[3]), "r"(b0), "r"(b1));
}
__device__ __forceinline__ void mma_k16_init(float (&d)[4], const uint32_t (&a)[4], uint32_t b0, uint32_t b1) {
    asm("{\n.reg .f32 z;\nmov.f32 z, 0f00000000;\n"
        "mma.sync.aligned.m16n8k16.row.col.f32.bf16.bf16.f32 {%0,%1,%2,%3}, {%4,%5,%6,%7}, {%8,%9}, {z,z,z,z};\n}\n"
        : "=f"(d[0]), "=f"(d[1]), "=f"(d[2]), "=f"(d[3]) : "r"(a[0]), "r"(a[1]), "r"(a[2]), "r"(a[3]), "r"(b0), "r"(b1));
}
__device__ __forceinline__ void mma_k8(float (&d)[4], uint32_t a0, uint32_t a1, uint32_t b0) {
    asm("mma.sync.aligned.m16n8k8.row.col.f32.bf16.bf16.f32 {%0,%1,%2,%3}, {%4,%5}, {%6}, {%0,%1,%2,%3};"
        : "+f"(d[0]), "+f"(d[1]), "+f"(d[2]), "+f"(d[3]) : "r"(a0), "r"(a1), "r"(b0));
}
template <typename T, int N> __device__ __forceinline__ void zero_regs(T (&d)[N]) {
#pragma unroll
    for (int i = 0; i < N; i++) d[i] = 0;
}
__device__ __forceinline__ float quad_max(float v) {
    v = fmaxf(v, __shfl_xor_sync(0xffffffffu, v, 1));
    return fmaxf(v, __shfl_xor_sync(0xffffffffu, v, 2));
}
__device__ __forceinline__ float quad_sum(float v) {
    v += __shfl_xor_sync(0xffffffffu, v, 1);
    return v + __shfl_xor_sync(0xffffffffu, v, 2);
}

__device__ __forceinline__ void qk_gemm(float (&s)[64], uint32_t q_lo, uint32_t k_lo) {
    const uint64_t dq = full_desc(q_lo), dk = full_desc(k_lo);
    wgmma_fence();
    wgmma_ss_n128_init(s, dq, dk);
#pragma unroll
    for (int kk = 1; kk < 8; kk++) {
        const uint32_t o = (kk >> 2) * 1024 + (kk & 3) * 2;
        wgmma_ss_n128(s, dq + o, dk + o, 1);
    }
    wgmma_commit();
}
__device__ __forceinline__ void pv_gemm(float (&o)[64], uint32_t (&p)[32], uint32_t v_lo, int accumulate) {
    const uint64_t dv = full_desc(v_lo);
    fence_regs(o);
    fence_regs(p);
    wgmma_fence();
#pragma unroll
    for (int kk = 0; kk < 8; kk++)
        wgmma_rs_n128_tb(o, p[4 * kk], p[4 * kk + 1], p[4 * kk + 2], p[4 * kk + 3], dv + kk * 128, kk != 0 || accumulate);
    wgmma_commit();
}
__device__ __forceinline__ void row_max(const float (&s)[64], float& x0, float& x1) {
    float z0 = fmaxf(s[0], s[1]), z1 = fmaxf(s[2], s[3]);
    x0 = fmaxf(s[4], s[5]); x1 = fmaxf(s[6], s[7]);
#pragma unroll
    for (int j = 2; j < 16; j += 2) {
        z0 = fmaxf(z0, fmaxf(s[4 * j], s[4 * j + 1]));
        z1 = fmaxf(z1, fmaxf(s[4 * j + 2], s[4 * j + 3]));
        x0 = fmaxf(x0, fmaxf(s[4 * j + 4], s[4 * j + 5]));
        x1 = fmaxf(x1, fmaxf(s[4 * j + 6], s[4 * j + 7]));
    }
    x0 = quad_max(fmaxf(x0, z0)); x1 = quad_max(fmaxf(x1, z1));
}
__device__ __forceinline__ void exp_pack(uint32_t (&p)[32], const float (&s)[64], float& r0, float& r1) {
#pragma unroll
    for (int j = 0; j < 16; j++) {
        const float e0 = ex2(s[4 * j]), e1 = ex2(s[4 * j + 1]), e2 = ex2(s[4 * j + 2]), e3 = ex2(s[4 * j + 3]);
        if (j == 0) { r0 = e0 + e1; r1 = e2 + e3; }
        else { r0 += e0 + e1; r1 += e2 + e3; }
        p[2 * j] = pack_bf16(e0, e1);
        p[2 * j + 1] = pack_bf16(e2, e3);
    }
}
__device__ __forceinline__ void shift_rows(float (&s)[64], float d0, float d1) {
#pragma unroll
    for (int j = 0; j < 16; j++) { s[4 * j] -= d0; s[4 * j + 1] -= d0; s[4 * j + 2] -= d1; s[4 * j + 3] -= d1; }
}
constexpr float MASKED = -3e38f;
template <int J0>
__device__ __forceinline__ void mask_triangle(float (&s)[64], float thr) {
#pragma unroll
    for (int j = 0; j < 16; j++) {
        const float m = __saturatef((float)(8 * (j >> 1) + (j & 1)) - thr);
        const int i = 4 * (J0 + (j >> 1)) + (j & 1);
        s[i] = fmaf(m, MASKED, s[i]);
        if (j < 14) s[i + 6] = fmaf(m, MASKED, s[i + 6]);
    }
}
__device__ __forceinline__ void causal_mask(float (&s)[64], float thr, int wg) {
    asm volatile("" : "+f"(thr));
    if (wg == 0) {
        mask_triangle<0>(s, thr);
#pragma unroll
        for (int j = 32; j < 64; j++) s[j] += MASKED;
    } else {
        mask_triangle<8>(s, thr);
    }
}

__global__ void __cluster_dims__(2, 1, 1) __launch_bounds__(384, 1) fused_kernel(const __grid_constant__ Params prm) {
    extern __shared__ __align__(1024) uint8_t smem[];
    const uint32_t sb = smem_u32(smem), bars = sb + SM_BARS;
    const int warp = __shfl_sync(0xffffffffu, threadIdx.x >> 5, 0), lane = threadIdx.x & 31;

    const uint32_t rank = cluster_rank();
    const uint32_t bars0 = map_cta(bars, 0), bars_peer = map_cta(bars, rank ^ 1);

    auto plan_index = [&]() -> uint32_t {
        uint32_t p = blockIdx.x >> 1;
        asm volatile("" : "+r"(p));
        const uint32_t r = (p - 36) * 37 >> 8;
        return p < 4 ? 4 + p : p < 36 ? (p - 4 & 7) * 8 + (p - 4 >> 3) : p < 64 ? (p - 35 - 7 * r) * 8 + 4 + r : p;
    };
    auto first_item = [&]() -> int {
        const uint32_t pair = plan_index();
        const uint32_t slot = pair & 7, c = slot * 11 >> 5;
        return pair < 64 ? T_B << 13 | (4 * slot - 11 * c) << 4 | (2 * (pair >> 3) + rank) : T_K << 13 | (8 * slot + rank);
    };
    if (warp == 0) {
        if (elect_one()) {
            for (int k = 0; k < 4; k++) mbar_init(bars + B_GFULL + 8 * k, 1);
            asm volatile("fence.mbarrier_init.release.cluster;" ::: "memory");
            fence_proxy_async_smem();
        }
        __syncwarp();
        const int first_it = __shfl_sync(0xffffffffu, first_item(), 0);
        asm volatile("barrier.cluster.arrive.relaxed.aligned;" ::: "memory");
        const CUtensorMap* ma = &prm.m[item_type(first_it) == T_K ? M_C : M_X];
        const CUtensorMap* mb = &prm.m[M_WQ + item_type(first_it)];
#pragma unroll
        for (int k = 0; k < 2; k++) {
            const uint32_t dst = sb + k * GST_BYTES, fb = bars + B_GFULL + 8 * k;
            warp_expect_tx(fb, GST_BYTES);
            warp_tma_load(dst + 16384, mb, fb, 0, k * 64, item_col(first_it) * 4, true);
            warp_tma_load(dst, ma, fb, k * 64, item_row(first_it) * 128, 0, false);
            warp_tma_load(dst + 32768, mb, fb, 0, k * 64, item_col(first_it) * 4 + 2, true);
        }
    }
    if (threadIdx.x == 32) {
        for (int i = 0; i < 4; i++) mbar_init(bars + B_GEMPTY + 8 * i, 16);
        for (int i = 0; i < 6; i++) { mbar_init(bars + B_AFULL + 8 * i, 1); mbar_init(bars + B_AEMPTY + 8 * i, i < 2 ? 8 : 16); }
        for (int i = 0; i < 4; i++) { mbar_init(bars + B_SFULL + 8 * i, 4); mbar_init(bars + B_SEMPTY + 8 * i, 1); }
        for (int i = 0; i < QDEPTH; i++) { mbar_init(bars + B_IFULL + 8 * i, 1); mbar_init(bars + B_IEMPTY + 8 * i, 23); }
        mbar_init(bars + B_WANT, 2); mbar_init(bars + B_MEET, 1); mbar_init(bars + B_XFREE, 1);
        for (int i = 0; i < 4; i++) mbar_init(bars + B_HALF + 8 * i, 1);
        mbar_init(bars + B_ALT, 4); mbar_init(bars + B_ALT + 8, 4); mbar_init(bars + B_QFREE, 2);
        asm volatile("st.shared.u64 [%0], 0;" :: "r"(bars + SM_ORDY) : "memory");
        asm volatile("fence.mbarrier_init.release.cluster;\nfence.acq_rel.cta;" ::: "memory");
    }
    __syncwarp();
    if (warp != 0) asm volatile("barrier.cluster.arrive.relaxed.aligned;" ::: "memory");
    asm volatile("barrier.cluster.wait.acquire.aligned;" ::: "memory");

    uint32_t qn = 0;
    auto next_item = [&](bool releaser, bool bounded = true) -> int {
        const uint32_t slot = qn % QDEPTH;
        if (bounded) mbar_wait(bars + B_IFULL + 8 * slot, (qn / QDEPTH) & 1);
        else mbar_spin(bars + B_IFULL + 8 * slot, (qn / QDEPTH) & 1);
        uint32_t it;
        asm volatile("ld.shared.u32 %0, [%1];" : "=r"(it) : "r"(bars + SM_QUEUE + 4 * slot) : "memory");
        mbar_arrive_cluster_if(releaser, bars0 + B_IEMPTY + 8 * slot);
        qn++;
        return it;
    };

    if (warp < 4) {
        reg_dec<40>();
        if (warp == 0) {
            {
                uint32_t gph = 1;
                const uint32_t prank = __shfl_sync(0xffffffffu, rank, 0);
                auto request = [&]() { mbar_arrive_cluster_if(lane == 0, bars0 + B_WANT); };
                auto take_item = [&]() -> int { return __shfl_sync(0xffffffffu, next_item(lane == 0), 0); };
                auto inputs_seen = [&](uint32_t word, unsigned& n) -> uint32_t {
                    uint32_t v;
                    spin_guard(n);
                    asm volatile("ld.acquire.cta.shared.u32 %0, [%1];" : "=r"(v) : "r"(bars + SM_ORDY + 4 * word) : "memory");
                    return __shfl_sync(0xffffffffu, v, 0);
                };
                uint32_t oneed = 0;
                auto wait_inputs = [&](int it) {
                    if (it & ITEM_READY) return;
                    oneed += 256;
                    for (unsigned n = 0; inputs_seen(1, n) < oneed;) {}
                };
                int nxt = first_item(), ring = -1, rot = 0;
                for (int k0 = 2; item_type(nxt) <= T_LOCAL; k0 = 0) {
                    const int type = item_type(nxt), m = item_row(nxt), c = item_col(nxt);
                    if (type == T_LOCAL) {
                        wait_inputs(nxt);
                        request();
#pragma unroll 1
                        for (uint32_t st = 0; st < 4; st++) {
                            mbar_wait(bars + B_GEMPTY + 8 * st, gph);
                            const uint32_t dst = sb + st * GST_BYTES, fb = bars + B_GFULL + 8 * st;
                            warp_expect_tx(fb, st == 0 ? 32768 + 512 : st == 3 ? 0 : 4 * LOC_PLANE);
                            if (st == 3) break;
                            if (st == 0) warp_bulk_load(dst + 4 * LOC_PLANE, &g_gate[m * 128], 512, fb);
#pragma unroll 1
                            for (int i = 0; i < 4; i++)
                                warp_tma_load(dst + i * LOC_PLANE, &prm.m[st ? M_SCR_LOC : M_SCR_LOQ], fb, i * 64, m * 64 - (st ? 8 : 0), G_B + 8 * st + c, true);
                        }
                        gph ^= 1;
                        ring = -1;
                    } else {
                        const int nk = type == T_K || type == T_V ? 8 : 16, kept = ring == m + 16 * nk ? 4 : 0;
                        ring = m + 16 * nk;
                        rot = kept ? rot - 4 : 0;
                        const CUtensorMap* ma = &prm.m[nk == 8 ? M_C : M_X];
                        const CUtensorMap* mb = &prm.m[M_WQ + type];
#pragma unroll 1
                        for (int k = k0; k < nk; k++) {
                            if (k == nk - 3) request();
                            const uint32_t st = k & 3, dst = sb + st * GST_BYTES, fb = bars + B_GFULL + 8 * st;
                            const int kc = ((k + rot) & (nk - 1)) * 64;
                            mbar_wait(bars + B_GEMPTY + 8 * st, gph);
                            warp_expect_tx(fb, k < kept ? 32768 : GST_BYTES);
                            if (k >= kept) warp_tma_load(dst, ma, fb, kc, m * 128, 0, c == 15 && type != T_K);
                            warp_tma_load_pair(dst + 16384 + prank * 16384, mb, fb, 0, kc, c * 4 + 2 * prank, true);
                            if (st == 3) gph ^= 1;
                        }
                    }
                    nxt = take_item();
                }
                uint32_t kv = 0, kvph = 1;
                uint32_t qc = 0;
                auto a_parity = [&](uint32_t b) { return b < 2 ? (((qc + 1 - b) >> 1) & 1) ^ 1 : kvph ^ (b - 2 < kv); };
                const CUtensorMap* tile_map = &prm.m[M_SCR_LD];
                asm volatile("" : "+l"(tile_map));
                {
                    bool need_g = true, more = true;
                    int pv_grp = -1, pv_row = 0;
                    int pv_shared = 0;
                    bool peer_longer = false;
                    int m = 0, c = 0, asc = 0, nu = 0, uend = 0, ureq = -1, ufetch = 0;
#pragma unroll 1
                    for (int u = 0;; u++) {
                        if (u == ufetch) {
                            if (qc) nxt = take_item();
                            if (item_type(nxt) == T_ATTN) {
                                wait_inputs(nxt);
                                const uint32_t b = qc & 1, dst = sb + b * 32768, fb = bars + B_AFULL + 8 * b, row = item_row(nxt) * 128;
                                mbar_wait(bars + (qc == 0 ? B_GEMPTY : qc == 1 ? B_QFREE : B_AEMPTY + 8 * b), qc == 0 ? gph : qc == 1 ? 0 : a_parity(b));
                                warp_expect_tx(fb, 32768 + 512);
                                warp_tma_load(dst, tile_map, fb, 0, row, G_Q + item_col(nxt), false);
                                warp_tma_load(dst + 16384, tile_map, fb, 64, row, G_Q + item_col(nxt), false);
                                warp_bulk_load(bars + SM_GATE + b * 512, &g_gate[row], 512, fb);
                                qc++;
                            }
                        }
                        if (u == uend) {
                            if (!more) break;
                            more = item_type(nxt) == T_ATTN;
                            m = item_row(nxt); c = item_col(nxt); asc = item_asc(nxt);
                            nu = more ? 2 * m + 2 : 0;
                            uend = nu + ((more ? m < 2 : pv_grp >= 0) ? 3 : 0);
                            ureq = 2 * max(m - 2 - (asc & m), 0);
                            ufetch = !more ? -1 : m ? 2 * m : uend;
                            u = -1;
                            continue;
                        }
                        int grp = pv_grp, row = pv_row;
                        int shared = pv_shared;
                        if (u >= nu) {
                            if (u == nu + 1) pv_grp = -1;
                            else if (peer_longer) { grp = -1; shared = 0; }
                            else continue;
                        } else {
                            const int j = asc ? u >> 1 : m - (u >> 1);
                            if (u & 1) {
                                pv_grp = G_V + c; pv_row = j * 128; pv_shared = (m | 1) - j;
                                peer_longer = asc & ~m & 1;
                                if (u == nu - 1 && (m & 1) && item_type(nxt) == T_END) mbar_arrive_cluster_n_if(lane == 0, bars0 + B_WANT, 2);
                                if (grp < 0) continue;
                            } else {
                                if (u == ureq) request();
                                grp = G_K + c; row = j * 128; shared = (m | 1) - j;
                            }
                        }
                        uint32_t fb = bars + B_AFULL + 16 + 8 * kv, mine = sb + SM_KV + kv * 32768 + prank * 16384;
                        int c_mine = prank * 64;
                        asm volatile("" : "+r"(mine), "+r"(fb), "+r"(row), "+r"(grp), "+r"(c_mine));
                        mbar_wait(need_g ? bars + B_GEMPTY + 8 + 8 * kv : fb + B_AEMPTY - B_AFULL, need_g ? gph : kvph);
                        warp_expect_tx(fb, grp < 0 ? 0 : 32768);
                        if (shared) {
                            warp_tma_load_pair(mine, tile_map, fb, c_mine, row, grp, shared == 1);
                        } else if (grp >= 0) {
                            warp_tma_load(mine, tile_map, fb, c_mine, row, grp, true);
                            warp_tma_load(mine + 16384 - prank * 32768, tile_map, fb, 64 - c_mine, row, grp, true);
                        } else {
                            mbar_arrive_cluster_n_if(lane < 2, map_cta(fb, lane & 1) + B_AEMPTY - B_AFULL, 8);
                        }
                        if (kv == 2) need_g = false;
                        if (++kv == 4) { kv = 0; kvph ^= 1; }
                    }
                }
                if (!qc) request();
                const int it = take_item();
                int nk = 0;
                if (item_type(it) == T_OUT) {
                    const int m = item_row(it), c = item_col(it), half = c & 1;
                    nk = 80;
                    for (unsigned n = 0; (inputs_seen(1, n) & 255) != 255;) {}
                    mbar_wait(bars + B_GEMPTY + 24, gph);
                    mbar_wait(bars + B_QFREE, 0);
                    mbar_wait(bars + B_AEMPTY + 8 * (qc & 1), a_parity(qc & 1));
#pragma unroll 1
                    for (uint32_t k = 0; k < 4; k++) {
                        const uint32_t sa = prm.ostep[half ? WIDE - 1 - k : k], dst = sb + k * GST_BYTES, fb = bars + B_GFULL + 8 * k;
                        const uint32_t b0 = k ? 1 + k : ~qc & 1, b1 = 2 + k - (k == 1);
                        mbar_wait(bars + B_AEMPTY + 8 * b0, a_parity(b0));
                        mbar_arrive_cluster_if(lane == 0 && !k, bars_peer + B_XFREE);
                        warp_expect_tx(fb, GST_BYTES);
                        warp_tma_load(dst, tile_map, fb, (sa & 1) * 64, m * 128, G_LOC - 32 + (sa >> 1), true);
                        mbar_wait(bars + (k ? B_AEMPTY + 8 * b1 : B_XFREE), k ? kvph ^ (b1 - 2 < kv) : 0);
                        warp_tma_load_pair(dst + 16384 + prank * 16384, &prm.m[M_WOB], fb, 0, (sa & 63) * 64, (c >> 1) * 4 + 2 * (half ^ prank), false);
                    }
                    gph ^= 1;
                    uint32_t seen = 0;
                    for (int k = 4; k < nk; k++) {
                        if (k == K_SPLIT) nk = 2 * TRIPLES + (take_item() & 127);
                        const int kn = k + 2 * TRIPLES - nk, first = kn >= 0 && !(kn & 1);
                        const int s = kn >= 0 ? WIDE + (3 * kn + 1) / 2 : half ? WIDE - 1 - k : k;
                        const uint32_t sa = prm.ostep[s], sa2 = prm.ostep[s + first], sw = prm.ostep[s - (kn >= 0 && !first ? prank : 0)];
                        const uint32_t need = 1u << (sa >> 1 & 31) | 1u << (sa2 >> 1 & 31);
                        for (unsigned n = 0; sa < 64 && (need & ~seen);) seen = inputs_seen(0, n);
                        const uint32_t st = k & 3;
                        uint32_t dst = sb + st * GST_BYTES, fb = bars + B_GFULL + 8 * st;
                        uint32_t dstb = dst + 16384 + (first ? 0 : prank * 16384), skipb = first && (kn >> 1 & 1) != prank;
                        int a0 = (sa & 1) * 64, a1 = m * 128, a2 = (sa >> 1) + (sa < 64 ? G_CTX : G_LOC - 32);
                        int b1 = (sw & 63) * 64, b2 = (c >> 1) * 4 + 2 * (kn >= 0 ? half : half ^ prank);
                        const CUtensorMap* mb = &prm.m[sw >= 64 ? M_WOB : M_WO];
                        asm volatile("" : "+r"(dst), "+r"(fb), "+r"(dstb), "+r"(skipb), "+r"(a0), "+r"(a1), "+r"(a2), "+r"(b1), "+r"(b2), "+l"(mb));
                        mbar_wait(bars + B_GEMPTY + 8 * st, gph);
                        warp_expect_tx(fb, GST_BYTES);
                        warp_tma_load(dst, tile_map, fb, a0, a1, a2, true);
                        if (!skipb) warp_tma_load_pair(dstb, mb, fb, 0, b1, b2, false);
                        if (first) warp_tma_load(dst + 32768, tile_map, fb, (sa2 & 1) * 64, a1, G_CTX + (sa2 >> 1), true);
                        if (k < K_SPLIT && lane == 0 && !prank)
                            asm volatile("st.relaxed.gpu.global.u32 [%0], %1;" :: "l"(&g_sync.step[0][0] + m * 4 + c), "r"(k) : "memory");
                        mbar_arrive_if(k == K_MEET && lane == 0, bars + B_MEET);
                        if ((uint32_t)(k - K_FETCH) < (3 * TRIPLES + 1) / 2) {
                            const uint32_t g = prm.ostep[79 - 2 * (k - K_FETCH)] >> 1;
                            warp_prefetch((const char*)g_scr + (uint32_t)((G_CTX + g) * (SEQ * 256) + m * 32768 + c * 4096), 4096);
                            warp_prefetch(prm.wo + (uint32_t)(g * 262144 + (m * 8 + c) * 2048), 2048);
                        }
                        if (st == 3) gph ^= 1;
                    }
                    for (unsigned n = 0; ~inputs_seen(0, n);) {}
                }
#pragma unroll 1
                for (uint32_t st = 0; st < 4; st++) { mbar_wait(bars + B_GEMPTY + 8 * st, gph ^ (st < (nk & 3))); mbar_wait(bars + B_AEMPTY + 16 + 8 * st, a_parity(2 + st)); }
                unsigned left = 0;
                if (lane == 0) asm volatile("atom.relaxed.gpu.global.add.u32 %0, [%1], 1;" : "=r"(left) : "l"(&g_sync.done) : "memory");
                if (__shfl_sync(0xffffffffu, left, 0) == NCTA - 1)
#pragma unroll 1
                    for (uint32_t i = lane * 8; i < sizeof(Sync); i += 256) *(unsigned long long*)((char*)&g_sync + i) = 0;
            }
        } else if (warp <= 2) {
            if (blockIdx.x < SEQ / 16) {
                const uint32_t r0 = 16 * blockIdx.x + 8 * (warp - 1), gbuf = bars + SM_GATE + 4 * (r0 & 15);
                float z[4];
                mbar_wait(bars + B_GFULL + 24, 0);
#pragma unroll 1
                for (uint32_t i = 0; i < 8; i++) {
                    const uint32_t off = (i & 3) * 512 + lane * 16;
                    const uint4* xp = (const uint4*)((const char*)prm.x + ((r0 + (i & 4)) * 2048 + off));
                    const uint4 wv = __ldg((const uint4*)((const char*)prm.gate_w + off));
                    uint4 xv[4];
#pragma unroll
                    for (int r = 0; r < 4; r++) { xv[r] = __ldg(xp + r * 128); if (!(i & 3)) z[r] = 0.f; }
                    const uint32_t ws[4] = {wv.x, wv.y, wv.z, wv.w};
#pragma unroll
                    for (int e = 0; e < 4; e++)
#pragma unroll
                        for (int r = 0; r < 4; r++) {
                            const uint32_t xs = e == 0 ? xv[r].x : e == 1 ? xv[r].y : e == 2 ? xv[r].z : xv[r].w;
                            z[r] = fmaf(__uint_as_float(xs << 16), __uint_as_float(ws[e] << 16), z[r]);
                            z[r] = fmaf(__uint_as_float(xs & 0xffff0000u), __uint_as_float(ws[e] & 0xffff0000u), z[r]);
                        }
                    if ((i & 3) == 3) {
#pragma unroll
                        for (int o = 16; o > 0; o >>= 1)
#pragma unroll
                            for (int r = 0; r < 4; r++) z[r] += __shfl_xor_sync(0xffffffffu, z[r], o);
                        const float zr = lane & 2 ? (lane & 1 ? z[3] : z[2]) : (lane & 1 ? z[1] : z[0]);
                        asm volatile("st.shared.f32 [%0], %1;" :: "r"(gbuf + 4 * ((i & 4) + (lane & 3))), "f"(1.f / (1.f + __expf(-zr))) : "memory");
                    }
                }
                fence_proxy_async_smem();
                __syncwarp();
                warp_bulk_store((char*)g_gate + 4 * r0, gbuf, 32);
                bulk_commit();
                bulk_wait<0>();
                __syncwarp();
                if (lane == 0) red_add(&g_sync.count[3], 1);
            }
            __syncwarp();
            {
                const int w = warp - 1;
                uint32_t sph = 0, nann = 0;
                int unsent = 0, nunsent = 0;
                bool urgent = false;
                auto announce = [&]() {
                    if (!urgent) return;
                    bulk_wait<0>();
                    __syncwarp();
                    const uint32_t hb = bars + B_HALF + 8 * (nann & 3);
                    if (w == 0) {
                        mbar_arrive_if(lane == 0, hb);
                    } else {
                        mbar_wait(hb, (nann >> 2) & 1);
                        const uint32_t type = item_type(unsent), m = item_row(unsent), c = item_col(unsent);
                        const uint32_t word = type < T_B ? c >> 3 : type == T_B ? 2 : offsetof(Sync, ctx) / 8 + m;
                        const uint32_t bit = type < T_B ? 8 * (c & 7) : type == T_B ? 8 * (c & 3) : type == T_LOCAL ? 32 + c : c;
                        if (lane < nunsent) red_add((unsigned long long*)((char*)&g_sync + 8 * word), 1ull << bit);
                        __syncwarp();
                    }
                    nann++;
                    nunsent = 0; urgent = false;
                };
                int held = first_item(), it;
                bool qfree = false;
                do {
                    if (!__all_sync(0xffffffffu, mbar_test(bars + B_IFULL + 8 * (qn % QDEPTH), (qn / QDEPTH) & 1))) announce();
                    it = __shfl_sync(0xffffffffu, next_item(lane == 0), 0);
                    const int itype = item_type(it);
                    const bool keep_held = itype == T_LOCAL;
                    if (itype >= T_ATTN && held < 0) {
                        urgent = nunsent;
                        mbar_arrive_if(lane == 0 && !qfree, bars + B_QFREE);
                        qfree = true;
                    }
#pragma unroll 1
                    for (int pass = held < 0 || keep_held; pass < 2; pass++) {
                        if (pass && (itype < T_OUT || itype == T_END)) break;
                        const int cur = pass ? it : held, type = item_type(cur), m = item_row(cur), c = item_col(cur);
                        const bool local = type == T_LOCAL;
                        const int grp = pass ? (local ? G_LOC : G_CTX) + c : type * 32 + 2 * c;
#pragma unroll 1
                        for (int i = 0; i < 4 - 2 * pass; i++) {
                            const int b = i & 1;
                            const bool alt = i >= 2 && itype >= T_ATTN;
                            const uint32_t full = bars + (alt ? B_ALT + 8 * w : B_SFULL + 16 * w + 8 * b), par = alt ? 0 : sph;
                            if (i == 3 - 2 * pass || !__all_sync(0xffffffffu, mbar_test(full, par))) announce();
                            mbar_wait(full, par);
                            fence_proxy_async_smem();
                            warp_tma_store(&prm.m[local ? M_SCR_LOQ : M_SCR_ST], sb + (alt ? 32768 : SM_STAGING) + w * 16384 + b * 8192,
                                         local ? b * 128 + w * 64 : b * 64, local ? m * 64 : m * 128 + w * 64, grp + (i >> 1), local || (type < T_B && c < FIRST_PAIR));
                            bulk_commit();
                            if (pass > b) continue;
                            bulk_wait_read<0>();
                            __syncwarp();
                            mbar_arrive_if(lane <= pass && !alt, bars + B_SEMPTY + 16 * w + 8 * (b - lane));
                            sph ^= b & !alt;
                        }
                        mbar_arrive_if(lane == 0 && !qfree && itype >= T_ATTN, bars + B_QFREE);
                        qfree |= itype >= T_ATTN;
                        if (lane == nunsent) unsent = cur;
                        nunsent++;
                        urgent = nunsent == 32 || !local;
                    }
                    if (!keep_held) held = itype < T_OUT ? it : -1;
                } while (item_type(it) != T_END);
                announce();
                it = __shfl_sync(0xffffffffu, next_item(lane == 0), 0);
                if (item_type(it) == T_OUT) {
                    if (w) {
                        mbar_wait(bars + B_MEET, 0);
                        asm volatile("fence.proxy.async.global;\nfence.acq_rel.gpu;" ::: "memory");
                        mbar_arrive_cluster_if(lane == 0, bars0 + B_WANT);
                    }
                    next_item(lane == 0);
#pragma unroll 1
                    for (int i = 0; i < 4; i++) {
                        const int b = i & 1;
                        mbar_wait(bars + B_SFULL + 16 * w + 8 * b, sph ^ (i >> 1));
                        fence_proxy_async_smem();
                        warp_tma_add(&prm.m[M_OUT], sb + SM_STAGING + w * 16384 + b * 8192, (item_col(it) ^ (i < 2)) * 128 + b * 64, item_row(it) * 128 + w * 64, 0);
                        bulk_commit();
                        if (b) {
                            bulk_wait_read<0>();
                            __syncwarp();
                            mbar_arrive_if(lane < 2, bars + B_SEMPTY + 16 * w + 8 * lane);
                        }
                    }
                }
            }
        } else {
            if (elect_one()) {
                uint32_t ordy = 0;
                unsigned long long cnt_lo = 0, cnt_hi = 0;
                int late = 0;
                auto refresh = [&]() {
                    if (!late && cnt_lo == 0x30303030 && cnt_hi == SEQ / 8) late = 1;
                    asm volatile("ld.acquire.gpu.global.v2.u64 {%0, %1}, [%2];" : "=l"(cnt_lo), "=l"(cnt_hi) : "l"(late ? &g_sync.count[0] : &g_sync.count[2]) : "memory");
                };
                auto inputs_ready = [&](int it) -> bool {
                    const int c = item_col(it);
                    if (item_type(it) == T_ATTN) return late && ((c < 16 ? cnt_lo : cnt_hi) >> (4 * (c & 14)) & 255) == 48;
                    return late || (cnt_hi == SEQ / 8 && (cnt_lo >> (4 * (c & 6)) & 255) == 48);
                };
                auto publish = [&](int it, int step) {
                    const uint32_t slot = qn % QDEPTH;
                    mbar_wait(bars + B_IEMPTY + 8 * slot, ((qn / QDEPTH) & 1) ^ 1);
                    for (uint32_t r = 0; r < 2; r++) {
                        const uint32_t rb = map_cta(bars, r);
                        asm volatile("mbarrier.arrive.expect_tx.shared::cluster.b64 _, [%0], 4;" :: "r"(rb + B_IFULL + 8 * slot) : "memory");
                        asm volatile("st.async.shared::cluster.mbarrier::complete_tx::bytes.u32 [%0], %1, [%2];"
                                     :: "r"(rb + SM_QUEUE + 4 * slot), "r"(it + r * step), "r"(rb + B_IFULL + 8 * slot) : "memory");
                    }
                    qn++;
                };
                int asc = 1;
                int it;
                do {
                    if (rank == 0) {
                        mbar_wait(bars + B_WANT, qn & 1);
                        const uint32_t pair = plan_index();
                        int pit = prm.plan[pair < 64 ? pair & 7 : pair - 56][min(qn + 1, 15u)];
                        unsigned i;
                        const bool planned = item_type(pit) != T_END;
                        if (!planned) asm volatile("atom.relaxed.gpu.global.add.u32 %0, [%1], 1;" : "=r"(i) : "l"(&g_sync.next) : "memory");
                        if (cnt_lo != 0x3030303030303030ull || cnt_hi != cnt_lo) refresh();
                        if (planned) pit += (pair >> 3 & 7) << (item_type(pit) == T_LOCAL);
                        else if (i < NITEMS) pit = prm.items[i];
                        const int type = item_type(pit);
                        int step = type == T_LOCAL ? 16 : 1;
                        it = pit + (pit & (step == 1 ? 15 : 0x1f0));
                        if (type == T_ATTN) {
                            if (!asc) { it += 1; step = -1; }
                            it |= asc << 9;
                        }
                        asc = type != T_ATTN || item_row(pit) == 0 || !asc;
                        if (inputs_ready(it)) it |= ITEM_READY;
                        publish(it, step);
                    } else {
                        it = next_item(true);
                    }
                    if ((item_type(it) == T_ATTN || item_type(it) == T_LOCAL) && !(it & ITEM_READY)) {
                        unsigned n = 0;
                        while (!inputs_ready(it)) { refresh(); spin_guard(n); }
                        asm volatile("st.release.cta.shared.u32 [%0], %1;" :: "r"(bars + SM_ORDY + 4), "r"(ordy += 256) : "memory");
                    }
                } while (item_type(it) != T_END);
                if (rank == 0) {
                    mbar_wait(bars + B_WANT, qn & 1);
                    const unsigned i = atomicAdd(&g_sync.next_out, 1u), t = i < 32 ? 31 - i : i - 32;
                    it = i < 64 ? T_OUT << 13 | ((t & 3) * 2 + (i >> 5)) << 4 | (t >> 2) * 2 : T_END << 13;
                    publish(it, 1);
                } else {
                    it = next_item(true);
                }
                if (item_type(it) == T_OUT) {
                    const uint32_t m = item_row(it), half = item_col(it) & 1, tile = m * 2 + (item_col(it) >> 1);
                    unsigned* split = (unsigned*)((char*)g_sync.split + 4 * tile);
                    unsigned long long rdy = 0;
                    int state = rank ? 2 : 0;
                    for (unsigned n = 0; rdy != 0xffffffffffull || state < 2; spin_guard(n)) {
                        if (rdy != 0xffffffffffull) {
                            rdy = ld_acquire((const unsigned long long*)((char*)g_sync.ctx + 8 * m));
                            asm volatile("st.release.cta.shared.u64 [%0], %1;" :: "r"(bars + SM_ORDY), "l"(rdy) : "memory");
                        }
                        unsigned steps = 0;
                        if (state == 1) {
                            steps = ld_acquire(split);
                        } else if (state == 0 && mbar_test(bars + B_WANT, qn & 1)) {
                            state = 1;
                            unsigned seen;
                            asm volatile("atom.acq_rel.gpu.global.exch.b32 %0, [%1], 1;" : "=r"(seen) : "l"(split) : "memory");
                            if (seen) {
                                const unsigned long long v = ld_acquire((const unsigned long long*)((char*)g_sync.step + 8 * tile));
                                const int d = (int)(v >> 32) - (int)v;
                                steps = (WIDE + min(max(half ? d : -d, -12), 12)) >> 1;
                                atomicExch(split, WIDE - steps);
                            }
                        }
                        if (steps > 1) { publish(T_END << 13 | steps, 0); state = 2; }
                    }
                    if (rank) next_item(true);
                }
                #pragma unroll 1
                for (uint32_t n = qn; n < qn + QDEPTH && rank == 0; n++) mbar_wait(bars + B_IEMPTY + 8 * (n % QDEPTH), ((n / QDEPTH) & 1) ^ 1);
            }
        }
    } else {
        reg_inc<232>();
        const int wg = (warp >> 2) - 1, wq = warp & 3;
        uint32_t gph = 0;
        uint32_t kvn = 0;
        const uint32_t dA = make_desc(sb + wg * 8192, 16);
        uint32_t ti = 0;
        uint32_t sph = 1;
        const uint32_t stg = sb + SM_STAGING + wg * 16384;
        const uint32_t stg_lane = stg + (wq * 16 + (lane & 15)) * 128 + (((lane >> 4) ^ (lane & 7)) << 4);
        auto write_blocks = [&](auto n, uint32_t off, const uint32_t* v) {
            uint32_t a = stg_lane;
            asm volatile("" : "+r"(a));
            a += off;
#pragma unroll
            for (int j = 0; j < decltype(n)::value; j++)
                stmatrix_x4((a ^ (32 * (j & 3))) + (j >> 2) * 8192, v[4 * j], v[4 * j + 1], v[4 * j + 2], v[4 * j + 3]);
        };
        auto release = [&](uint32_t bar) { mbar_arrive_if(lane == 0, bars + bar); };
        const uint32_t bars_lane = map_cta(bars, lane & 1);
        auto release_stage = [&](uint32_t st) { mbar_arrive_cluster_if(lane < 2, bars_lane + B_GEMPTY + 8 * st); };
        auto take_item = [&]() -> int {
            return __shfl_sync(0xffffffffu, next_item(lane == 0, false), 0);
        };
        auto stage_acquire = [&](int b) { mbar_spin(bars + B_SEMPTY + 16 * wg + 8 * b, sph); };
        auto stage_publish = [&](int b) {
            __syncwarp();
            release(B_SFULL + 16 * wg + 8 * b);
        };
        auto stage_chunk = [&](int b, const uint32_t* v) {
            stage_acquire(b);
            write_blocks(std::integral_constant<int, 4>(), b * 8192, v);
            stage_publish(b);
            if (b) sph ^= 1;
        };
        auto publish_pair = [&]() {
            __syncwarp();
            mbar_arrive_if(lane < 2, bars + B_SFULL + 16 * wg + 8 * lane);
            sph ^= 1;
        };
        auto gemm_step = [&](float (&acc)[128], uint32_t dB, int& k, bool order) {
            const uint32_t st = k & 3;
            wgmma_wait<0>();
            release_stage((k - 1) & 3);
            mbar_spin(bars + B_GFULL + 8 * st, gph);
            const uint64_t da = full_desc(dA + st * (GST_BYTES >> 4)), db = full_desc(dB + st * (GST_BYTES >> 4));
            if (order && wg) bar_sync(3, 256);
            wgmma_fence();
#pragma unroll
            for (int kk = 0; kk < 4; kk++) wgmma_ss_n256_tb(acc, da + 2 * kk, db + 128 * kk, 1);
            wgmma_commit();
            if (order && !wg) bar_arrive(3, 256);
            gph ^= st == 3;
            k++;
        };
        if (wg == 1) bar_arrive(1, 256);
        int it = first_item();
        float s[64];
        const uint32_t dK = make_desc(sb + SM_KV, 16);
        auto kv_wait = [&](uint32_t n) { mbar_spin(bars + B_AFULL + 16 + 8 * (n & 3), (n >> 2) & 1); };
        auto first_scores = [&](bool valid) {
            if (valid) { mbar_spin(bars + B_AFULL + 8 * (ti & 1), (ti >> 1) & 1); kv_wait(kvn); }
            bar_sync(1 + wg, 256);
            qk_gemm(s, dA + (ti & 1) * 2048, dK + (kvn & 3) * 2048);
        };
        bool issued;
        {
            {
                float acc[128];
                uint32_t pk[64];
                bool pending = false;
                int held = T_END;
                auto scale_q = [&](int j0) {
                    if (held != T_Q) return;
#pragma unroll
                    for (int j = j0; j < j0 + 16; j++)
                        asm("{\n.reg .b32 t;\nmul.rn.bf16x2 t, %0, %2;\nfma.rn.bf16x2 %0, %0, %1, t;\n}\n" : "+r"(pk[j]) : "r"(0x3e033e03u), "r"(0xb9d8b9d8u));
                };
                zero_regs(pk);
                const uint32_t dB = make_desc(sb + 16384, 8192);
                do {
                    if (item_type(it) == T_LOCAL) {
                        int ln = lane;
                        asm volatile("" : "+r"(ln));
                        const int g = ln >> 2, t = ln & 3, par = wq & 1;
                        const uint32_t hc = (wq >> 1) * 4, pl = sb + (par * 2 + wg) * LOC_PLANE;
                        const uint32_t a16 = (ln & 15) * 128 + (((hc + (ln >> 4)) ^ (ln & 7)) << 4), a8 = (ln & 7) * 128 + (((hc + (ln >> 3)) ^ (ln & 7)) << 4);
                        const bool first0 = 2 * t > g, first1 = 2 * t + 1 > g;
                        const uint32_t fmask = (first0 ? 0xffffu : 0u) | (first1 ? 0xffff0000u : 0u);
                        const bool edge = item_row(it) == 0;
                        uint32_t q[4][2][4], kf[9][4], vf[9][4];
                        float w[8];
                        mbar_spin(bars + B_GFULL, gph);
#pragma unroll
                        for (int u = 0; u < 4; u++) { ldsm_x4(q[u][0], pl + u * 2048 + a16); ldsm_x4(q[u][1], pl + u * 2048 + (a16 ^ 32)); }
#pragma unroll
                        for (int j = 0; j < 8; j++) w[j] = lds_f32(sb + 4 * LOC_PLANE + 4 * (2 * g + par) + 64 * j);
                        __syncwarp();
                        release_stage(0);
                        mbar_spin(bars + B_GFULL + 8, gph);
#pragma unroll
                        for (int n = 0; n < 9; n++) ldsm_x4(kf[n], pl + GST_BYTES + n * 1024 + a8);
                        __syncwarp();
                        release_stage(1);
                        float s[8][2];
#pragma unroll
                        for (int u = 0; u < 4; u++) {
                            float d[3][4];
#pragma unroll
                            for (int nt = 0; nt < 3; nt++) {
                                mma_k16_init(d[nt], q[u][0], kf[2 * u + nt][0], kf[2 * u + nt][1]);
                                mma_k16(d[nt], q[u][1], kf[2 * u + nt][2], kf[2 * u + nt][3]);
                            }
                            if (u == 0 && edge) { d[0][0] = -INFINITY; d[0][1] = -INFINITY; }
                            s[2 * u][0] = first0 ? d[0][0] : d[1][0]; s[2 * u][1] = first1 ? d[0][1] : d[1][1];
                            s[2 * u + 1][0] = first0 ? d[1][2] : d[2][2]; s[2 * u + 1][1] = first1 ? d[1][3] : d[2][3];
                        }
                        mbar_spin(bars + B_GFULL + 16, gph);
#pragma unroll
                        for (int u = 0; u < 4; u++) { ldsm_x4_t(vf[2 * u], pl + 2 * GST_BYTES + u * 2048 + a16); ldsm_x4_t(vf[2 * u + 1], pl + 2 * GST_BYTES + u * 2048 + (a16 ^ 32)); }
                        ldsm_x4_t(vf[8], pl + 2 * GST_BYTES + 8192 + a8);
                        __syncwarp();
                        release_stage(2);
                        float x[8];
#pragma unroll
                        for (int j = 0; j < 8; j++) x[j] = fmaxf(s[j][0], s[j][1]);
#pragma unroll
                        for (int o = 1; o < 4; o *= 2)
#pragma unroll
                            for (int j = 0; j < 8; j++) x[j] = fmaxf(x[j], __shfl_xor_sync(0xffffffffu, x[j], o));
#pragma unroll
                        for (int j = 0; j < 8; j++) {
                            const float n = x[j] * -LOC_SCALE;
                            s[j][0] = ex2(fmaf(s[j][0], LOC_SCALE, n)); s[j][1] = ex2(fmaf(s[j][1], LOC_SCALE, n));
                            x[j] = s[j][0] + s[j][1];
                        }
#pragma unroll
                        for (int o = 1; o < 4; o *= 2)
#pragma unroll
                            for (int j = 0; j < 8; j++) x[j] += __shfl_xor_sync(0xffffffffu, x[j], o);
                        mbar_spin(bars + B_GFULL + 24, gph);
                        release_stage(3);
                        it = take_item();
                        uint32_t ob[4][8];
#pragma unroll
                        for (int u = 0; u < 4; u++) {
                            const float r0 = rcp(x[2 * u]), r1 = rcp(x[2 * u + 1]), f0 = fmaf(-w[2 * u], r0, r0), f1 = fmaf(-w[2 * u + 1], r1, r1);
                            const uint32_t p0 = pack_bf16(s[2 * u][0] * f0, s[2 * u][1] * f0), p1 = pack_bf16(s[2 * u + 1][0] * f1, s[2 * u + 1][1] * f1);
                            const uint32_t pa[4] = {p0 & fmask, 0, p0 & ~fmask, p1 & fmask};
#pragma unroll
                            for (int c = 0; c < 4; c++) {
                                float ol[4];
                                mma_k16_init(ol, pa, vf[2 * u + (c >> 1)][2 * (c & 1)], vf[2 * u + (c >> 1)][2 * (c & 1) + 1]);
                                mma_k8(ol, 0, p1 & ~fmask, u < 3 ? vf[2 * u + 2 + (c >> 1)][2 * (c & 1)] : vf[8][c]);
                                ob[u][2 * c] = pack_bf16(ol[0], ol[1]);
                                ob[u][2 * c + 1] = pack_bf16(ol[2], ol[3]);
                            }
                        }
                        stage_acquire(0); stage_acquire(1);
#pragma unroll
                        for (int u = 0; u < 4; u++) {
                            stmatrix_x4(stg + par * 8192 + u * 2048 + a16, ob[u][0], ob[u][1], ob[u][2], ob[u][3]);
                            stmatrix_x4(stg + par * 8192 + u * 2048 + (a16 ^ 32), ob[u][4], ob[u][5], ob[u][6], ob[u][7]);
                        }
                        publish_pair();
                        bar_sync(4, 256);
                        gph ^= 1;
                        continue;
                    }
                    mbar_spin(bars + B_GFULL, gph);
                    bool more;
                    do {
                        wgmma_fence();
                        wgmma_ss_n256_tb_init(acc, full_desc(dA), full_desc(dB));
#pragma unroll
                        for (int kk = 1; kk < 4; kk++) wgmma_ss_n256_tb(acc, full_desc(dA) + 2 * kk, full_desc(dB) + 128 * kk, 1);
                        wgmma_commit();
                        const int type = item_type(it), nk = type == T_K || type == T_V ? 8 : 16;
                        int k = 1;
                        do {
                            if (pending) {
                                const int kf = k - 1 - wg;
                                if (kf == 0) { scale_q(0); stage_chunk(0, pk); }
                                else if (kf == 1) { scale_q(16); stage_chunk(1, pk + 16); }
                                else if (kf == 3) { scale_q(32); stage_chunk(0, pk + 32); }
                                else if (kf == 4) { scale_q(48); stage_chunk(1, pk + 48); }
                            }
                            if (k == nk - 1) it = take_item();
                            gemm_step(acc, dB, k, item_type(it) > T_LOCAL);
                        } while (k < nk);
                        held = type;
                        more = item_type(it) < T_LOCAL;
                        if (more) mbar_spin(bars + B_GFULL, gph);
                        wgmma_wait<0>();
                        fence_regs(acc);
                        release_stage(3);
#pragma unroll
                        for (int j = 0; j < 64; j++) pk[j] = pack_bf16(acc[2 * j], acc[2 * j + 1]);
                        pending = true;
                    } while (more);
                } while (item_type(it) <= T_LOCAL);
                issued = item_type(it) == T_ATTN && (it & ITEM_READY);
                first_scores(issued);
                stage_acquire(0); stage_acquire(1);
                mbar_spin(bars + B_GEMPTY + 8, gph ^ 1);
                write_blocks(std::integral_constant<int, 8>(), 0, pk);
                write_blocks(std::integral_constant<int, 8>(), 32768 - SM_STAGING, pk + 32);
                publish_pair();
                release(B_ALT + 8 * wg);
                bar_arrive(2 - wg, 256);
                wgmma_wait<0>();
                fence_regs(s);
                if (item_type(it) == T_END) it = take_item();
            }
            while (item_type(it) == T_ATTN) {
                if (!issued) { first_scores(true); bar_arrive(2 - wg, 256); wgmma_wait<0>(); fence_regs(s); }
                issued = false;
                float o[64];
                uint32_t pa[32], pb[32];
                float n0 = 0.f, n1 = 0.f;
                int shifted = 0;
                float l0 = 0.f, l1 = 0.f, f0 = 0.f, f1 = 0.f, g0, g1;
                uint32_t has_pv = 0;
                int first = 0;
                int pending = 0;
                const uint32_t dV = make_desc(sb + SM_KV, 16384);
                const uint32_t lane_off = bars_lane - bars + B_AEMPTY - B_AFULL;
                int cur = it;
                uint32_t qoff = (ti & 1) * 2048;
                const int row = wg * 64 + wq * 16 + (lane >> 2);
                const float thr = (row & 63) - (lane & 3) * 2;
                int diag = item_row(cur) == 0 || !item_asc(cur);
                int peek = -1;
                auto kv_release = [&](uint32_t n) { mbar_arrive_cluster_if(lane < 2, bars_lane + B_AEMPTY + 16 + 8 * (n & 3)); };
                struct Slot { uint32_t bar, par, off; } slot[4];
#pragma unroll
                for (uint32_t i = 0; i < 4; i++) {
                    const uint32_t n = kvn + 1 + (i ^ 2);
                    slot[i].bar = bars + B_AFULL + 16 + 8 * (n & 3); slot[i].par = (n >> 2) & 1; slot[i].off = (n & 3) * 2048;
                }
                kvn++;
                auto next_gate = [&]() {
                    g0 = lds_f32(bars + SM_GATE + (ti & 1) * 512 + 4 * row); g1 = lds_f32(bars + SM_GATE + (ti & 1) * 512 + 4 * row + 32);
                    ti++;
                };
                next_gate();
                auto scale_o = [&]() {
#pragma unroll
                    for (int j = 0; j < 16; j++) { o[4 * j] *= f0; o[4 * j + 1] *= f0; o[4 * j + 2] *= f1; o[4 * j + 3] *= f1; }
                };
                auto pack_o = [&](uint32_t (&v)[32]) {
#pragma unroll
                    for (int j = 0; j < 32; j++) v[j] = pack_bf16(o[2 * j], o[2 * j + 1]);
                };
                auto scales = [&]() { f0 = g0 * rcp(quad_sum(l0)); f1 = g1 * rcp(quad_sum(l1)); };
                auto issue = [&](auto even, uint32_t (&pin)[32], uint32_t (&pout)[32], bool fresh, bool last) {
                    constexpr bool EVEN = decltype(even)::value;
                    Slot& sk = slot[EVEN ? 0 : 2];
                    Slot& sv = slot[EVEN ? 1 : 3];
                    kvn += 2;
                    mbar_spin(sk.bar, sk.par);
                    bar_sync(1 + wg, 256);
                    qk_gemm(s, dA + qoff, dK + sk.off);
                    if (EVEN && fresh) {
                        scales();
                        next_gate();
                        n0 = 0.f; n1 = 0.f; l0 = 0.f; l1 = 0.f;
                        shifted = 0;
                        stage_acquire(0); stage_acquire(1);
                    }
                    if (!EVEN && pending) {
                        pack_o(pout);
                        write_blocks(std::integral_constant<int, 4>(), 0, pout);
                    }
                    if (last)
                        asm volatile("{\n.reg .pred P, Q;\n"
                                     "mbarrier.test_wait.parity.shared::cta.b64 Q, [%1], %2;\n"
                                     "mbarrier.test_wait.parity.shared::cta.b64 P, [%3], %4;\n"
                                     "ld.shared.u32 %0, [%5];\n"
                                     "@!Q or.b32 %0, %0, 0x10000;\n"
                                     "@!P mov.u32 %0, -1;\n}\n"
                                     : "=r"(peek) : "r"(bars + B_AFULL + 8 * (ti & 1)), "r"((ti >> 1) & 1), "r"(bars + B_IFULL + 8 * (qn % QDEPTH)),
                                       "r"((qn / QDEPTH) & 1), "r"(bars + SM_QUEUE + 4 * (qn % QDEPTH)) : "memory");
                    diag = item_asc(cur) ? last : fresh;
                    asm volatile("" : "+r"(diag));
                    mbar_spin(sv.bar, sv.par);
                    pv_gemm(o, pin, dV + sv.off, EVEN || !first);
                    bar_arrive(2 - wg, 256);
                    if (!EVEN && pending) {
                        write_blocks(std::integral_constant<int, 4>(), 8192, pout + 16);
                        publish_pair();
                    }
                    sk.par ^= 1; sv.par ^= 1;
                    wgmma_wait<1>();
                    fence_regs(s);
                    mbar_arrive_cluster_if(lane < 2, sk.bar + lane_off);
                    mbar_arrive_if(lane == 0 && last, bars + B_AEMPTY + 8 * ((ti - 1) & 1));
                };
                auto softmax = [&](auto even, uint32_t (&pin)[32], uint32_t (&pout)[32], bool fresh) {
                    constexpr bool EVEN = decltype(even)::value;
                    Slot& sv = slot[EVEN ? 1 : 3];
                    float r0, r1, x0 = n0, x1 = n1;
#pragma unroll 1
                    for (int mask = diag, redone = 0;; mask = 0, redone = 1) {
                        if (mask | shifted) {
                            if (mask) causal_mask(s, thr, wg);
                            if (shifted) shift_rows(s, x0, x1);
                        }
                        exp_pack(pout, s, r0, r1);
                        if (!__any_sync(0xffffffffu, fmaxf(r0, r1) >= SUM_LIMIT || (EVEN && fresh && !(lane & 3) && !(fminf(s[0], s[2]) >= -REF_RANGE))) || redone) break;
                        row_max(s, x0, x1);
                        if (!(EVEN && fresh)) { x0 = fmaxf(x0, 0.f); x1 = fmaxf(x1, 0.f); }
                        float a0 = ex2(-x0), a1 = ex2(-x1);
                        n0 += x0; n1 += x1;
                        shifted = 1;
                        if (EVEN && fresh) { a0 = 1.f; a1 = 1.f; }
                        l0 *= a0; l1 *= a1;
                        wgmma_wait<0>();
                        fence_regs(o);
#pragma unroll
                        for (int q = 0; q < 16; q++) { o[4 * q] *= a0; o[4 * q + 1] *= a0; o[4 * q + 2] *= a1; o[4 * q + 3] *= a1; }
                    }
                    l0 += r0; l1 += r1;
                    wgmma_wait<0>();
                    fence_regs(o);
                    fence_regs(pin);
                    mbar_arrive_cluster_if(lane < 2, sv.bar + lane_off);
                };
                auto copy_p = [&]() {
#pragma unroll
                    for (int j = 0; j < 32; j++) pa[j] = __float_as_uint(__uint_as_float(pb[j]) + __uint_as_float(prm.zero));
                };
                int rem = 0;
                mbar_arrive_if(lane == 0 && item_row(cur) == 0, bars + B_AEMPTY + 8 * ((ti - 1) & 1));
                zero_regs(pa);
                wgmma_fence();
                wgmma_ss_n128_init(o, full_desc(dA), full_desc(dK));
                wgmma_commit();
                while (true) {
                    const bool fresh = rem == 0;
                    softmax(std::true_type(), pa, pb, fresh);
                    first = fresh;
                    if (fresh) {
                        pending = has_pv; has_pv = 1;
                        if (pending) scale_o();
                        rem = item_row(cur) + 1;
                    }
                    if (--rem == 0) {
                        copy_p();
                        const Slot t0 = slot[0], t1 = slot[1];
                        slot[0] = slot[2]; slot[1] = slot[3]; slot[2] = t0; slot[3] = t1;
                    } else {
                        issue(std::false_type(), pb, pa, false, rem == 1);
                        softmax(std::false_type(), pb, pa, false);
                        pending = 0; first = 0;
                        rem--;
                    }
                    if (rem == 0) {
                        const int seen = peek;
                        if (seen >= 0) {
                            mbar_arrive_cluster_if(lane == 0, bars0 + B_IEMPTY + 8 * (qn % QDEPTH));
                            qn++;
                            it = seen & 0xffff;
                        } else {
                            it = take_item();
                        }
                        if (item_row(cur) < 2 || item_type(it) != T_ATTN) break;
                        if (seen & 0x10000) mbar_spin(bars + B_AFULL + 8 * (ti & 1), (ti >> 1) & 1);
                        cur = it;
                        qoff = (ti & 1) * 2048;
                    }
                    issue(std::true_type(), pa, pb, rem == 0, rem ? rem == 1 : item_row(cur) == 0);
                }
                const uint32_t skip = item_asc(cur) & ~item_row(cur) & 1;
                kvn += skip;
                const bool end = item_type(it) == T_END;
#pragma unroll 1
                for (int pass = pending ? 0 : 1; pass < 2; pass++) {
                    if (pass) {
                        kv_wait(kvn);
                        pv_gemm(o, pa, dV + (kvn & 3) * 2048, !first);
                        scales();
                        stage_acquire(0); stage_acquire(1);
                        if (end) it = take_item();
                        wgmma_wait<0>();
                        fence_regs(o);
                        kv_release(kvn);
                        kvn += 1 + skip;
                        scale_o();
                    }
                    pack_o(pb);
                    write_blocks(std::integral_constant<int, 8>(), 0, pb);
                    publish_pair();
                }
            }
        }
        if (item_type(it) == T_OUT) {
            float acc[128];
            const uint32_t dB = make_desc(sb + 16384, 8192);
            mbar_spin(bars + B_GFULL, gph);
            wgmma_fence();
            wgmma_ss_n256_tb_init(acc, full_desc(dA), full_desc(dB));
#pragma unroll
            for (int kk = 1; kk < 4; kk++) wgmma_ss_n256_tb(acc, full_desc(dA) + 2 * kk, full_desc(dB) + 128 * kk, 1);
            wgmma_commit();
            uint32_t ln;
            asm volatile("mov.u32 %0, %%laneid;" : "=r"(ln));
            char* const mine = (char*)prm.out + (uint32_t)((item_row(it) * 128 + wg * 64 + wq * 16 + (ln >> 4)) * 2048 + item_col(it) * 256 + (ln & 15) * 16);
            int k = 1, nk = 80;
            do {
                if ((uint32_t)(k - (K_MEET - 12)) < 8) *(uint4*)(mine + (uint32_t)(k - (K_MEET - 12)) * 4096) = make_uint4(0, 0, 0, 0);
                __syncwarp();
                if (k == K_SPLIT) nk = take_item() & 127;
                gemm_step(acc, dB, k, false);
            } while (k < nk);
            float lo[64];
            auto triple = [&](auto first) {
                const uint32_t s0 = k & 3, s1 = (k + 1) & 3, o0 = s0 * (GST_BYTES >> 4), o1 = s1 * (GST_BYTES >> 4);
                wgmma_wait<0>();
                mbar_arrive_cluster_if(ln < (decltype(first)::value ? 2 : 4), bars_lane + B_GEMPTY + 8 * ((k - 1 - (ln >> 1)) & 3));
                mbar_spin(bars + B_GFULL + 8 * s0, gph);
                gph ^= s0 == 3;
                wgmma_fence();
#pragma unroll
                for (int kk = 0; kk < 4; kk++) {
                    if (decltype(first)::value && kk == 0) wgmma_ss_n128_tb_init(lo, full_desc(dA + o0), full_desc(dB + o0));
                    else wgmma_ss_n128_tb(lo, full_desc(dA + o0) + 2 * kk, full_desc(dB + o0) + 128 * kk, 1);
                }
                mbar_spin(bars + B_GFULL + 8 * s1, gph);
                gph ^= s1 == 3;
                wgmma_fence();
#pragma unroll
                for (int kk = 0; kk < 4; kk++) wgmma_ss_n128_tb(lo, full_desc(dA + o0 + 2048) + 2 * kk, full_desc(dB + o1 + 1024) + 128 * kk, 1);
#pragma unroll
                for (int kk = 0; kk < 4; kk++) wgmma_ss_n128_tb(lo, full_desc(dA + o1) + 2 * kk, full_desc(dB + o1) + 128 * kk, 1);
                wgmma_commit();
                k += 2;
            };
            triple(std::true_type());
            fence_regs(acc);
            uint32_t pk[32];
#pragma unroll
            for (int j = 0; j < 32; j++) pk[j] = pack_bf16(acc[64 + 2 * j], acc[65 + 2 * j]);
            stage_acquire(0); stage_acquire(1);
            write_blocks(std::integral_constant<int, 8>(), 0, pk);
            publish_pair();
            triple(std::false_type());
            stage_acquire(0); stage_acquire(1);
            wgmma_wait<0>();
            fence_regs(lo);
            mbar_arrive_cluster_if(ln < 4, bars_lane + B_GEMPTY + 8 * ((k - 1 - (ln >> 1)) & 3));
#pragma unroll
            for (int b = 0; b < 2; b++) {
#pragma unroll
                for (int j = 16 * b; j < 16 * b + 16; j++) pk[j] = pack_bf16(acc[2 * j] + lo[2 * j], acc[2 * j + 1] + lo[2 * j + 1]);
                write_blocks(std::integral_constant<int, 4>(), b * 8192, pk + 16 * b);
                stage_publish(b);
            }
        }
    }
}

typedef CUresult (*EncodeFn)(CUtensorMap*, CUtensorMapDataType, cuuint32_t, void*, const cuuint64_t*, const cuuint64_t*,
                             const cuuint32_t*, const cuuint32_t*, CUtensorMapInterleave, CUtensorMapSwizzle,
                             CUtensorMapL2promotion, CUtensorMapFloatOOBfill);

void encode3(EncodeFn fn, CUtensorMap* m, const void* ptr, uint64_t d0, uint64_t d1, uint64_t d2, uint64_t s1, uint64_t s2,
             uint32_t b0, uint32_t b1, uint32_t b2) {
    cuuint64_t dims[3] = {d0, d1, d2};
    cuuint64_t strides[2] = {s1, s2};
    cuuint32_t box[3] = {b0, b1, b2};
    cuuint32_t es[3] = {1, 1, 1};
    fn(m, CU_TENSOR_MAP_DATA_TYPE_BFLOAT16, 3, const_cast<void*>(ptr), dims, strides, box, es, CU_TENSOR_MAP_INTERLEAVE_NONE,
       CU_TENSOR_MAP_SWIZZLE_128B, CU_TENSOR_MAP_L2_PROMOTION_NONE, CU_TENSOR_MAP_FLOAT_OOB_FILL_NONE);
}
void map_act(EncodeFn fn, CUtensorMap* m, const void* p, int rows, int cols, int box_rows) {
    encode3(fn, m, p, cols, rows, 1, (uint64_t)cols * 2, (uint64_t)cols * rows * 2, 64, box_rows, 1);
}
void map_wgt(EncodeFn fn, CUtensorMap* m, const void* p, int K, int N) {
    encode3(fn, m, p, 64, K, N / 64, (uint64_t)N * 2, 128, 64, 64, 2);
}

void build_schedule(Params& p) {
    int n = 0;
    auto add = [&](int type, int col, int row) { p.items[n++] = (uint16_t)(type << 13 | col << 4 | row); };
    int beta = 26, tail = 32, late = 6, early = 4, epos = 60;
    int order[16] = {6, 7, 8, 9, 10, 11, 12, 13, 14, 15, 5, 4, 3, 2, 1, 0};
    const char* plans = "xxxxxc,xxxlcccc,xxlxlxxc,xxlxlxxc,xxcccccxc,xccclxlccc,xccclxxc,xxcccccc";
    const char* pos[8];
    int len[8] = {}, start[8] = {};
    for (int s = 0; s < 8; s++) { pos[s] = plans; while (*plans && *plans++ != ',') {} }
    for (int i = 0; i < 160; i++) p.plan[i / 16][i % 16] = T_END << 13;
    for (int nx = 0, nc = 3, nl = 0; nx + nc + nl < 28 + 32 + 8;) {
        int s = -1;
        for (int i = 0; i < 8; i++) if (*pos[i] > ',' && (s < 0 || start[i] < start[s])) s = i;
        const char kind = *pos[s]++;
        int it;
        if (kind == 'x') { it = nx < 12 ? T_B << 13 | (nx % 3 * 4 + nx / 3) << 4 : T_Q << 13 | (nx - 12) << 4; nx++; }
        else if (kind == 'c') { it = (T_K + (nc & 1)) << 13 | nc / 2 << 4; nc++; }
        else { it = T_LOCAL << 13 | nl / 2 << 4 | (nl & 1); nl++; }
        p.plan[s][len[s]++] = (uint16_t)it;
        start[s] += kind == 'x' ? 48 : kind == 'c' ? 24 : 8;
    }
    for (int i = 0; i < 24; i++) p.plan[8 + i / 12][i % 12] = (uint16_t)((T_K + (i % 3 & 1)) << 13 | i % 3 / 2 << 4 | i / 3);
    const int a0 = n;
    for (int key = 0; key < 4000; key++)
        for (int r = 0; r < 32; r++)
            for (int j = 7; j >= 0; j--)
                if ((j ? (7 - j) * 40 + r * beta : 3999) == key) add(T_ATTN, 2 * order[r >> 1] + (r & 1), j);
    int t0 = n;
    for (int work = 0; work < 32 * 136 * tail / 100;) work += 4 * (p.items[--t0] & 15) + 3;
    for (int i = t0 + 1; i < n; i++)
        for (int j = i; j > t0 && (p.items[j] & 15) > (p.items[j - 1] & 15); j--) { const uint16_t t = p.items[j]; p.items[j] = p.items[j - 1]; p.items[j - 1] = t; }
    for (int r = early - 1; r >= 0; r--) {
        const uint16_t t = p.items[n - 32 + early - 1];
        for (int j = n - 32 + early - 1; j > n - epos; j--) p.items[j] = p.items[j - 1];
        p.items[n - epos] = t;
    }
    for (int moved = 0; moved < 2 && late >= 0; moved++)
        for (int i = a0; i < n; i++)
            if (p.items[i] == (T_ATTN << 13 | (2 * order[15] + moved) << 4 | late)) {
                for (int j = i; j + 1 < n; j++) p.items[j] = p.items[j + 1];
                p.items[n - 1] = (uint16_t)(T_ATTN << 13 | (2 * order[15] + moved) << 4 | late);
                break;
            }
    for (int s = 0, lo = 0, hi = WIDE - 1; s < 80; s++) {
        const int r = s / 2, g = r < 8 ? 32 + r : 2 * order[r / 2 - 4] + (r & 1);
        p.ostep[s >= WIDE ? s : r & 1 ? hi-- : lo++] = (uint8_t)(2 * g + (s & 1));
    }
}

void build_params(Params& p, void* const* d_in, void* d_out) {
    void* fnp = nullptr;
    cudaDriverEntryPointQueryResult qr;
    cudaGetDriverEntryPoint("cuTensorMapEncodeTiled", &fnp, cudaEnableDefault, &qr);
    EncodeFn fn = (EncodeFn)fnp;
    void* scr = nullptr;
    cudaGetSymbolAddress(&scr, g_scr);
    map_act(fn, &p.m[M_X], d_in[0], SEQ, 1024, 128);
    map_act(fn, &p.m[M_C], d_in[1], SEQ, 512, 128);
    map_wgt(fn, &p.m[M_WQ], d_in[2], 1024, 4096);
    map_wgt(fn, &p.m[M_WUK], d_in[3], 512, 4096);
    map_wgt(fn, &p.m[M_WUV], d_in[4], 512, 4096);
    map_wgt(fn, &p.m[M_WO], d_in[5], 4096, 1024);
    map_wgt(fn, &p.m[M_WQKV], d_in[7], 1024, 3072);
    map_wgt(fn, &p.m[M_WOB], d_in[8], 1024, 1024);
    encode3(fn, &p.m[M_SCR_LD], scr, 128, SEQ, G_TOTAL, 256, (uint64_t)SEQ * 256, 64, 128, 1);
    encode3(fn, &p.m[M_SCR_LOC], scr, 256, SEQ / 2, G_TOTAL, 512, (uint64_t)SEQ * 256, 64, 72, 1);
    encode3(fn, &p.m[M_SCR_LOQ], scr, 256, SEQ / 2, G_TOTAL, 512, (uint64_t)SEQ * 256, 64, 64, 1);
    encode3(fn, &p.m[M_SCR_ST], scr, 128, SEQ, G_TOTAL, 256, (uint64_t)SEQ * 256, 64, 64, 1);
    map_act(fn, &p.m[M_OUT], d_out, SEQ, 1024, 64);
    p.x = (const __nv_bfloat16*)d_in[0];
    p.gate_w = (const __nv_bfloat16*)d_in[9];
    p.zero = 0;
    p.wo = (const char*)d_in[5];
    p.out = (__nv_bfloat16*)d_out;
    build_schedule(p);
}

}

extern "C" void kernel_launch(void* const* d_in, const int* in_sizes, int n_in, void* d_out, int out_size) {
    (void)in_sizes; (void)n_in; (void)out_size;
    Params p;
    build_params(p, d_in, d_out);
    cudaFuncSetAttribute(fused_kernel, cudaFuncAttributeMaxDynamicSharedMemorySize, SM_TOTAL);
    fused_kernel<<<NCTA, 384, SM_TOTAL>>>(p);
}
```

```cpp
#include <cuda_runtime.h>
#include <cuda_bf16.h>
#include <cuda.h>
#include <stddef.h>
#include <stdint.h>
#include <type_traits>

namespace {

constexpr int SEQ = 2048;
constexpr int G_Q = 0, G_K = 32, G_V = 64, G_B = 96, G_CTX = G_Q, G_LOC = G_B, G_TOTAL = 120;

__device__ __align__(1024) __nv_bfloat16 g_scr[(size_t)G_TOTAL * SEQ * 128];
__device__ __align__(128) float g_gate[SEQ];

__device__ __forceinline__ uint32_t smem_u32(const void* p) { return (uint32_t)__cvta_generic_to_shared(p); }
__device__ __forceinline__ bool elect_one() {
    uint32_t p;
    asm volatile("{\n.reg .pred P;\nelect.sync _|P, 0xffffffff;\nselp.u32 %0, 1, 0, P;\n}\n" : "=r"(p));
    return p != 0;
}
__device__ __forceinline__ void mbar_init(uint32_t bar, uint32_t count) {
    asm volatile("mbarrier.init.shared::cta.b64 [%0], %1;" :: "r"(bar), "r"(count) : "memory");
}
__device__ __forceinline__ uint32_t cluster_rank() { uint32_t r; asm("mov.u32 %0, %%cluster_ctarank;" : "=r"(r)); return r; }
__device__ __forceinline__ uint32_t map_cta(uint32_t addr, uint32_t cta) {
    uint32_t r; asm("mapa.shared::cluster.u32 %0, %1, %2;" : "=r"(r) : "r"(addr), "r"(cta)); return r;
}
__device__ __forceinline__ void mbar_arrive_cluster_if(bool pred, uint32_t cluster_bar) {
    asm volatile("{\n.reg .pred P;\nsetp.ne.u32 P, %1, 0;\n@P mbarrier.arrive.shared::cluster.b64 _, [%0];\n}\n"
                 :: "r"(cluster_bar), "r"((uint32_t)pred) : "memory");
}
__device__ __forceinline__ void mbar_arrive_cluster_n_if(bool pred, uint32_t cluster_bar, uint32_t count) {
    asm volatile("{\n.reg .pred P;\nsetp.ne.u32 P, %1, 0;\n@P mbarrier.arrive.shared::cluster.b64 _, [%0], %2;\n}\n"
                 :: "r"(cluster_bar), "r"((uint32_t)pred), "r"(count) : "memory");
}
__device__ __forceinline__ void mbar_arrive_if(bool pred, uint32_t bar) {
    asm volatile("{\n.reg .pred P;\nsetp.ne.u32 P, %1, 0;\n@P mbarrier.arrive.shared::cta.b64 _, [%0];\n}\n"
                 :: "r"(bar), "r"((uint32_t)pred) : "memory");
}
__device__ __forceinline__ bool mbar_test(uint32_t bar, uint32_t parity) {
    uint32_t ok;
    asm volatile("{\n.reg .pred P;\nmbarrier.test_wait.parity.shared::cta.b64 P, [%1], %2;\nselp.u32 %0, 1, 0, P;\n}\n"
                 : "=r"(ok) : "r"(bar), "r"(parity) : "memory");
    return ok != 0;
}
__device__ __forceinline__ void mbar_wait(uint32_t bar, uint32_t parity) {
    asm volatile("{\n.reg .pred P;\n.reg .u32 c;\n"
                 "mov.u32 c, 0;\n"
                 "SPIN:\n"
                 "mbarrier.try_wait.parity.shared::cta.b64 P, [%0], %1;\n"
                 "@P bra DONE;\n"
                 "add.u32 c, c, 1;\n"
                 "setp.lt.u32 P, c, 4194304;\n"
                 "@P bra SPIN;\n"
                 "trap;\n"
                 "DONE:\n}\n" :: "r"(bar), "r"(parity) : "memory");
}
__device__ __forceinline__ void mbar_spin(uint32_t bar, uint32_t parity) {
    asm volatile("{\n.reg .pred P;\n"
                 "SPIN:\n"
                 "mbarrier.try_wait.parity.shared::cta.b64 P, [%0], %1;\n"
                 "@!P bra SPIN;\n}\n" :: "r"(bar), "r"(parity) : "memory");
}
__device__ __forceinline__ void bar_sync(int id, int n) { asm volatile("bar.sync %0, %1;" :: "r"(id), "r"(n) : "memory"); }
__device__ __forceinline__ void bar_arrive(int id, int n) { asm volatile("bar.arrive %0, %1;" :: "r"(id), "r"(n) : "memory"); }
__device__ __forceinline__ void fence_proxy_async_smem() { asm volatile("fence.proxy.async.shared::cta;" ::: "memory"); }
__device__ __forceinline__ void warp_expect_tx(uint32_t bar, uint32_t bytes) {
    asm volatile("{\n.reg .pred P;\nelect.sync _|P, 0xffffffff;\n@P mbarrier.arrive.expect_tx.shared::cta.b64 _, [%0], %1;\n}\n"
                 :: "r"(bar), "r"(bytes) : "memory");
}
constexpr uint64_t EVICT_FIRST = 0x12F0000000000000ull;
__device__ __forceinline__ void warp_tma_load(uint32_t dst, const CUtensorMap* map, uint32_t bar, int c0, int c1, int c2, bool stream) {
    if (stream)
        asm volatile("{\n.reg .pred P;\nelect.sync _|P, 0xffffffff;\n"
                     "@P cp.async.bulk.tensor.3d.shared::cluster.global.mbarrier::complete_tx::bytes.L2::cache_hint"
                     " [%0], [%1, {%3, %4, %5}], [%2], %6;\n}\n"
                     :: "r"(dst), "l"(map), "r"(bar), "r"(c0), "r"(c1), "r"(c2), "l"(EVICT_FIRST) : "memory");
    else
        asm volatile("{\n.reg .pred P;\nelect.sync _|P, 0xffffffff;\n"
                     "@P cp.async.bulk.tensor.3d.shared::cluster.global.mbarrier::complete_tx::bytes [%0], [%1, {%3, %4, %5}], [%2];\n}\n"
                     :: "r"(dst), "l"(map), "r"(bar), "r"(c0), "r"(c1), "r"(c2) : "memory");
}
__device__ __forceinline__ void warp_tma_load_pair(uint32_t dst, const CUtensorMap* map, uint32_t bar, int c0, int c1, int c2, bool stream) {
    if (stream)
        asm volatile("{\n.reg .pred P;\nelect.sync _|P, 0xffffffff;\n"
                     "@P cp.async.bulk.tensor.3d.shared::cluster.global.mbarrier::complete_tx::bytes.multicast::cluster.L2::cache_hint"
                     " [%0], [%1, {%3, %4, %5}], [%2], %6, %7;\n}\n"
                     :: "r"(dst), "l"(map), "r"(bar), "r"(c0), "r"(c1), "r"(c2), "h"((uint16_t)3), "l"(EVICT_FIRST) : "memory");
    else
        asm volatile("{\n.reg .pred P;\nelect.sync _|P, 0xffffffff;\n"
                     "@P cp.async.bulk.tensor.3d.shared::cluster.global.mbarrier::complete_tx::bytes.multicast::cluster"
                     " [%0], [%1, {%3, %4, %5}], [%2], %6;\n}\n"
                     :: "r"(dst), "l"(map), "r"(bar), "r"(c0), "r"(c1), "r"(c2), "h"((uint16_t)3) : "memory");
}
__device__ __forceinline__ void warp_bulk_load(uint32_t dst, const void* src, uint32_t bytes, uint32_t bar) {
    asm volatile("{\n.reg .pred P;\nelect.sync _|P, 0xffffffff;\n"
                 "@P cp.async.bulk.shared::cluster.global.mbarrier::complete_tx::bytes [%0], [%1], %2, [%3];\n}\n"
                 :: "r"(dst), "l"(src), "r"(bytes), "r"(bar) : "memory");
}
__device__ __forceinline__ void warp_tma_store(const CUtensorMap* map, uint32_t src, int c0, int c1, int c2, bool stream) {
    if (stream)
        asm volatile("{\n.reg .pred P;\nelect.sync _|P, 0xffffffff;\n"
                     "@P cp.async.bulk.tensor.3d.global.shared::cta.bulk_group.L2::cache_hint [%0, {%2, %3, %4}], [%1], %5;\n}\n"
                     :: "l"(map), "r"(src), "r"(c0), "r"(c1), "r"(c2), "l"(EVICT_FIRST) : "memory");
    else
        asm volatile("{\n.reg .pred P;\nelect.sync _|P, 0xffffffff;\n"
                     "@P cp.async.bulk.tensor.3d.global.shared::cta.bulk_group [%0, {%2, %3, %4}], [%1];\n}\n"
                     :: "l"(map), "r"(src), "r"(c0), "r"(c1), "r"(c2) : "memory");
}
__device__ __forceinline__ void warp_tma_add(const CUtensorMap* map, uint32_t src, int c0, int c1, int c2) {
    asm volatile("{\n.reg .pred P;\nelect.sync _|P, 0xffffffff;\n"
                 "@P cp.reduce.async.bulk.tensor.3d.global.shared::cta.add.tile.bulk_group [%0, {%2, %3, %4}], [%1];\n}\n"
                 :: "l"(map), "r"(src), "r"(c0), "r"(c1), "r"(c2) : "memory");
}
__device__ __forceinline__ void warp_bulk_store(void* dst, uint32_t src, uint32_t bytes) {
    asm volatile("{\n.reg .pred P;\nelect.sync _|P, 0xffffffff;\n"
                 "@P cp.async.bulk.global.shared::cta.bulk_group [%0], [%1], %2;\n}\n" :: "l"(dst), "r"(src), "r"(bytes) : "memory");
}
__device__ __forceinline__ void warp_prefetch(const void* src, uint32_t bytes) {
    asm volatile("{\n.reg .pred P;\nelect.sync _|P, 0xffffffff;\n@P cp.async.bulk.prefetch.L2.global [%0], %1;\n}\n" :: "l"(src), "r"(bytes) : "memory");
}
__device__ __forceinline__ void bulk_commit() { asm volatile("cp.async.bulk.commit_group;" ::: "memory"); }
template <int N> __device__ __forceinline__ void bulk_wait_read() { asm volatile("cp.async.bulk.wait_group.read %0;" :: "n"(N) : "memory"); }
template <int N> __device__ __forceinline__ void bulk_wait() { asm volatile("cp.async.bulk.wait_group %0;" :: "n"(N) : "memory"); }
__device__ __forceinline__ void wgmma_fence() { asm volatile("wgmma.fence.sync.aligned;" ::: "memory"); }
__device__ __forceinline__ void wgmma_commit() { asm volatile("wgmma.commit_group.sync.aligned;" ::: "memory"); }
template <int N> __device__ __forceinline__ void wgmma_wait() { asm volatile("wgmma.wait_group.sync.aligned %0;" :: "n"(N) : "memory"); }
template <int N> __device__ __forceinline__ void fence_regs(float (&d)[N]) {
#pragma unroll
    for (int i = 0; i < N; i++) asm volatile("" : "+f"(d[i]) :: "memory");
}
template <int N> __device__ __forceinline__ void fence_regs(uint32_t (&d)[N]) {
#pragma unroll
    for (int i = 0; i < N; i++) asm volatile("" : "+r"(d[i]) :: "memory");
}
template <int N> __device__ __forceinline__ void reg_dec() { asm volatile("setmaxnreg.dec.sync.aligned.u32 %0;" :: "n"(N)); }
template <int N> __device__ __forceinline__ void reg_inc() { asm volatile("setmaxnreg.inc.sync.aligned.u32 %0;" :: "n"(N)); }
__device__ __forceinline__ uint32_t pack_bf16(float lo, float hi) {
    uint32_t r; asm("cvt.rn.bf16x2.f32 %0, %1, %2;" : "=r"(r) : "f"(hi), "f"(lo)); return r;
}
__device__ __forceinline__ void stmatrix_x4(uint32_t addr, uint32_t r0, uint32_t r1, uint32_t r2, uint32_t r3) {
    asm volatile("stmatrix.sync.aligned.m8n8.x4.shared.b16 [%0], {%1, %2, %3, %4};"
                 :: "r"(addr), "r"(r0), "r"(r1), "r"(r2), "r"(r3) : "memory");
}
__device__ __forceinline__ float ex2(float x) { float y; asm("ex2.approx.ftz.f32 %0, %1;" : "=f"(y) : "f"(x)); return y; }

constexpr uint32_t DESC_HI = (1024 >> 4) | (1u << 30);
__device__ __forceinline__ uint32_t make_desc(uint32_t addr, uint32_t lbo) {
    uint32_t lo = ((addr & 0x3FFFF) >> 4) | ((lbo >> 4) << 16);
    asm volatile("" : "+r"(lo));
    return lo;
}
__device__ __forceinline__ uint64_t full_desc(uint32_t lo) {
    uint64_t d; asm("mov.b64 %0, {%1, %2};" : "=l"(d) : "r"(lo), "r"(DESC_HI)); return d;
}

__device__ __forceinline__ void wgmma_ss_n256_tb_init(float (&d)[128], uint64_t da, uint64_t db) {
    asm volatile("{\n.reg .pred p;\n"
        "setp.ne.b32 p, 0, 0;\n"
        "wgmma.mma_async.sync.aligned.m64n256k16.f32.bf16.bf16 "
        "{%0, %1, %2, %3, %4, %5, %6, %7, %8, %9, %10, %11, %12, %13, %14, %15, %16, %17, %18, %19, %20, "
        "%21, %22, %23, %24, %25, %26, %27, %28, %29, %30, %31, %32, %33, %34, %35, %36, %37, %38, %39, %40, "
        "%41, %42, %43, %44, %45, %46, %47, %48, %49, %50, %51, %52, %53, %54, %55, %56, %57, %58, %59, %60, "
        "%61, %62, %63, %64, %65, %66, %67, %68, %69, %70, %71, %72, %73, %74, %75, %76, %77, %78, %79, %80, "
        "%81, %82, %83, %84, %85, %86, %87, %88, %89, %90, %91, %92, %93, %94, %95, %96, %97, %98, %99, "
        "%100, %101, %102, %103, %104, %105, %106, %107, %108, %109, %110, %111, %112, %113, %114, %115, "
        "%116, %117, %118, %119, %120, %121, %122, %123, %124, %125, %126, %127},"
        " %128, %129, p, 1, 1, 0, 1;\n}\n"
        : "=f"(d[0]), "=f"(d[1]), "=f"(d[2]), "=f"(d[3]), "=f"(d[4]), "=f"(d[5]), "=f"(d[6]), "=f"(d[7]),
        "=f"(d[8]), "=f"(d[9]), "=f"(d[10]), "=f"(d[11]), "=f"(d[12]), "=f"(d[13]), "=f"(d[14]), "=f"(d[15]),
        "=f"(d[16]), "=f"(d[17]), "=f"(d[18]), "=f"(d[19]), "=f"(d[20]), "=f"(d[21]), "=f"(d[22]),
        "=f"(d[23]), "=f"(d[24]), "=f"(d[25]), "=f"(d[26]), "=f"(d[27]), "=f"(d[28]), "=f"(d[29]),
        "=f"(d[30]), "=f"(d[31]), "=f"(d[32]), "=f"(d[33]), "=f"(d[34]), "=f"(d[35]), "=f"(d[36]),
        "=f"(d[37]), "=f"(d[38]), "=f"(d[39]), "=f"(d[40]), "=f"(d[41]), "=f"(d[42]), "=f"(d[43]),
        "=f"(d[44]), "=f"(d[45]), "=f"(d[46]), "=f"(d[47]), "=f"(d[48]), "=f"(d[49]), "=f"(d[50]),
        "=f"(d[51]), "=f"(d[52]), "=f"(d[53]), "=f"(d[54]), "=f"(d[55]), "=f"(d[56]), "=f"(d[57]),
        "=f"(d[58]), "=f"(d[59]), "=f"(d[60]), "=f"(d[61]), "=f"(d[62]), "=f"(d[63]), "=f"(d[64]),
        "=f"(d[65]), "=f"(d[66]), "=f"(d[67]), "=f"(d[68]), "=f"(d[69]), "=f"(d[70]), "=f"(d[71]),
        "=f"(d[72]), "=f"(d[73]), "=f"(d[74]), "=f"(d[75]), "=f"(d[76]), "=f"(d[77]), "=f"(d[78]),
        "=f"(d[79]), "=f"(d[80]), "=f"(d[81]), "=f"(d[82]), "=f"(d[83]), "=f"(d[84]), "=f"(d[85]),
        "=f"(d[86]), "=f"(d[87]), "=f"(d[88]), "=f"(d[89]), "=f"(d[90]), "=f"(d[91]), "=f"(d[92]),
        "=f"(d[93]), "=f"(d[94]), "=f"(d[95]), "=f"(d[96]), "=f"(d[97]), "=f"(d[98]), "=f"(d[99]),
        "=f"(d[100]), "=f"(d[101]), "=f"(d[102]), "=f"(d[103]), "=f"(d[104]), "=f"(d[105]), "=f"(d[106]),
        "=f"(d[107]), "=f"(d[108]), "=f"(d[109]), "=f"(d[110]), "=f"(d[111]), "=f"(d[112]), "=f"(d[113]),
        "=f"(d[114]), "=f"(d[115]), "=f"(d[116]), "=f"(d[117]), "=f"(d[118]), "=f"(d[119]), "=f"(d[120]),
        "=f"(d[121]), "=f"(d[122]), "=f"(d[123]), "=f"(d[124]), "=f"(d[125]), "=f"(d[126]), "=f"(d[127])
        : "l"(da), "l"(db));
}
__device__ __forceinline__ void wgmma_ss_n256_tb(float (&d)[128], uint64_t da, uint64_t db, int scale_d) {
    asm volatile("{\n.reg .pred p;\n"
        "setp.ne.b32 p, %130, 0;\n"
        "wgmma.mma_async.sync.aligned.m64n256k16.f32.bf16.bf16 "
        "{%0, %1, %2, %3, %4, %5, %6, %7, %8, %9, %10, %11, %12, %13, %14, %15, %16, %17, %18, %19, %20, "
        "%21, %22, %23, %24, %25, %26, %27, %28, %29, %30, %31, %32, %33, %34, %35, %36, %37, %38, %39, %40, "
        "%41, %42, %43, %44, %45, %46, %47, %48, %49, %50, %51, %52, %53, %54, %55, %56, %57, %58, %59, %60, "
        "%61, %62, %63, %64, %65, %66, %67, %68, %69, %70, %71, %72, %73, %74, %75, %76, %77, %78, %79, %80, "
        "%81, %82, %83, %84, %85, %86, %87, %88, %89, %90, %91, %92, %93, %94, %95, %96, %97, %98, %99, "
        "%100, %101, %102, %103, %104, %105, %106, %107, %108, %109, %110, %111, %112, %113, %114, %115, "
        "%116, %117, %118, %119, %120, %121, %122, %123, %124, %125, %126, %127},"
        " %128, %129, p, 1, 1, 0, 1;\n}\n"
        : "+f"(d[0]), "+f"(d[1]), "+f"(d[2]), "+f"(d[3]), "+f"(d[4]), "+f"(d[5]), "+f"(d[6]), "+f"(d[7]),
        "+f"(d[8]), "+f"(d[9]), "+f"(d[10]), "+f"(d[11]), "+f"(d[12]), "+f"(d[13]), "+f"(d[14]), "+f"(d[15]),
        "+f"(d[16]), "+f"(d[17]), "+f"(d[18]), "+f"(d[19]), "+f"(d[20]), "+f"(d[21]), "+f"(d[22]),
        "+f"(d[23]), "+f"(d[24]), "+f"(d[25]), "+f"(d[26]), "+f"(d[27]), "+f"(d[28]), "+f"(d[29]),
        "+f"(d[30]), "+f"(d[31]), "+f"(d[32]), "+f"(d[33]), "+f"(d[34]), "+f"(d[35]), "+f"(d[36]),
        "+f"(d[37]), "+f"(d[38]), "+f"(d[39]), "+f"(d[40]), "+f"(d[41]), "+f"(d[42]), "+f"(d[43]),
        "+f"(d[44]), "+f"(d[45]), "+f"(d[46]), "+f"(d[47]), "+f"(d[48]), "+f"(d[49]), "+f"(d[50]),
        "+f"(d[51]), "+f"(d[52]), "+f"(d[53]), "+f"(d[54]), "+f"(d[55]), "+f"(d[56]), "+f"(d[57]),
        "+f"(d[58]), "+f"(d[59]), "+f"(d[60]), "+f"(d[61]), "+f"(d[62]), "+f"(d[63]), "+f"(d[64]),
        "+f"(d[65]), "+f"(d[66]), "+f"(d[67]), "+f"(d[68]), "+f"(d[69]), "+f"(d[70]), "+f"(d[71]),
        "+f"(d[72]), "+f"(d[73]), "+f"(d[74]), "+f"(d[75]), "+f"(d[76]), "+f"(d[77]), "+f"(d[78]),
        "+f"(d[79]), "+f"(d[80]), "+f"(d[81]), "+f"(d[82]), "+f"(d[83]), "+f"(d[84]), "+f"(d[85]),
        "+f"(d[86]), "+f"(d[87]), "+f"(d[88]), "+f"(d[89]), "+f"(d[90]), "+f"(d[91]), "+f"(d[92]),
        "+f"(d[93]), "+f"(d[94]), "+f"(d[95]), "+f"(d[96]), "+f"(d[97]), "+f"(d[98]), "+f"(d[99]),
        "+f"(d[100]), "+f"(d[101]), "+f"(d[102]), "+f"(d[103]), "+f"(d[104]), "+f"(d[105]), "+f"(d[106]),
        "+f"(d[107]), "+f"(d[108]), "+f"(d[109]), "+f"(d[110]), "+f"(d[111]), "+f"(d[112]), "+f"(d[113]),
        "+f"(d[114]), "+f"(d[115]), "+f"(d[116]), "+f"(d[117]), "+f"(d[118]), "+f"(d[119]), "+f"(d[120]),
        "+f"(d[121]), "+f"(d[122]), "+f"(d[123]), "+f"(d[124]), "+f"(d[125]), "+f"(d[126]), "+f"(d[127])
        : "l"(da), "l"(db), "r"(scale_d));
}
__device__ __forceinline__ void wgmma_ss_n128_init(float (&d)[64], uint64_t da, uint64_t db) {
    asm volatile("{\n.reg .pred p;\n"
        "setp.ne.b32 p, 0, 0;\n"
        "wgmma.mma_async.sync.aligned.m64n128k16.f32.bf16.bf16 "
        "{%0, %1, %2, %3, %4, %5, %6, %7, %8, %9, %10, %11, %12, %13, %14, %15, %16, %17, %18, %19, %20, "
        "%21, %22, %23, %24, %25, %26, %27, %28, %29, %30, %31, %32, %33, %34, %35, %36, %37, %38, %39, %40, "
        "%41, %42, %43, %44, %45, %46, %47, %48, %49, %50, %51, %52, %53, %54, %55, %56, %57, %58, %59, %60, "
        "%61, %62, %63},"
        " %64, %65, p, 1, 1, 0, 0;\n}\n"
        : "=f"(d[0]), "=f"(d[1]), "=f"(d[2]), "=f"(d[3]), "=f"(d[4]), "=f"(d[5]), "=f"(d[6]), "=f"(d[7]),
        "=f"(d[8]), "=f"(d[9]), "=f"(d[10]), "=f"(d[11]), "=f"(d[12]), "=f"(d[13]), "=f"(d[14]), "=f"(d[15]),
        "=f"(d[16]), "=f"(d[17]), "=f"(d[18]), "=f"(d[19]), "=f"(d[20]), "=f"(d[21]), "=f"(d[22]),
        "=f"(d[23]), "=f"(d[24]), "=f"(d[25]), "=f"(d[26]), "=f"(d[27]), "=f"(d[28]), "=f"(d[29]),
        "=f"(d[30]), "=f"(d[31]), "=f"(d[32]), "=f"(d[33]), "=f"(d[34]), "=f"(d[35]), "=f"(d[36]),
        "=f"(d[37]), "=f"(d[38]), "=f"(d[39]), "=f"(d[40]), "=f"(d[41]), "=f"(d[42]), "=f"(d[43]),
        "=f"(d[44]), "=f"(d[45]), "=f"(d[46]), "=f"(d[47]), "=f"(d[48]), "=f"(d[49]), "=f"(d[50]),
        "=f"(d[51]), "=f"(d[52]), "=f"(d[53]), "=f"(d[54]), "=f"(d[55]), "=f"(d[56]), "=f"(d[57]),
        "=f"(d[58]), "=f"(d[59]), "=f"(d[60]), "=f"(d[61]), "=f"(d[62]), "=f"(d[63])
        : "l"(da), "l"(db));
}
__device__ __forceinline__ void wgmma_ss_n128(float (&d)[64], uint64_t da, uint64_t db, int scale_d) {
    asm volatile("{\n.reg .pred p;\n"
        "setp.ne.b32 p, %66, 0;\n"
        "wgmma.mma_async.sync.aligned.m64n128k16.f32.bf16.bf16 "
        "{%0, %1, %2, %3, %4, %5, %6, %7, %8, %9, %10, %11, %12, %13, %14, %15, %16, %17, %18, %19, %20, "
        "%21, %22, %23, %24, %25, %26, %27, %28, %29, %30, %31, %32, %33, %34, %35, %36, %37, %38, %39, %40, "
        "%41, %42, %43, %44, %45, %46, %47, %48, %49, %50, %51, %52, %53, %54, %55, %56, %57, %58, %59, %60, "
        "%61, %62, %63},"
        " %64, %65, p, 1, 1, 0, 0;\n}\n"
        : "+f"(d[0]), "+f"(d[1]), "+f"(d[2]), "+f"(d[3]), "+f"(d[4]), "+f"(d[5]), "+f"(d[6]), "+f"(d[7]),
        "+f"(d[8]), "+f"(d[9]), "+f"(d[10]), "+f"(d[11]), "+f"(d[12]), "+f"(d[13]), "+f"(d[14]), "+f"(d[15]),
        "+f"(d[16]), "+f"(d[17]), "+f"(d[18]), "+f"(d[19]), "+f"(d[20]), "+f"(d[21]), "+f"(d[22]),
        "+f"(d[23]), "+f"(d[24]), "+f"(d[25]), "+f"(d[26]), "+f"(d[27]), "+f"(d[28]), "+f"(d[29]),
        "+f"(d[30]), "+f"(d[31]), "+f"(d[32]), "+f"(d[33]), "+f"(d[34]), "+f"(d[35]), "+f"(d[36]),
        "+f"(d[37]), "+f"(d[38]), "+f"(d[39]), "+f"(d[40]), "+f"(d[41]), "+f"(d[42]), "+f"(d[43]),
        "+f"(d[44]), "+f"(d[45]), "+f"(d[46]), "+f"(d[47]), "+f"(d[48]), "+f"(d[49]), "+f"(d[50]),
        "+f"(d[51]), "+f"(d[52]), "+f"(d[53]), "+f"(d[54]), "+f"(d[55]), "+f"(d[56]), "+f"(d[57]),
        "+f"(d[58]), "+f"(d[59]), "+f"(d[60]), "+f"(d[61]), "+f"(d[62]), "+f"(d[63])
        : "l"(da), "l"(db), "r"(scale_d));
}
__device__ __forceinline__ void wgmma_rs_n128_tb(float (&d)[64], uint32_t a0, uint32_t a1, uint32_t a2, uint32_t a3, uint64_t db, int scale_d) {
    asm volatile("{\n.reg .pred p;\n"
        "setp.ne.b32 p, %69, 0;\n"
        "wgmma.mma_async.sync.aligned.m64n128k16.f32.bf16.bf16 "
        "{%0, %1, %2, %3, %4, %5, %6, %7, %8, %9, %10, %11, %12, %13, %14, %15, %16, %17, %18, %19, %20, "
        "%21, %22, %23, %24, %25, %26, %27, %28, %29, %30, %31, %32, %33, %34, %35, %36, %37, %38, %39, %40, "
        "%41, %42, %43, %44, %45, %46, %47, %48, %49, %50, %51, %52, %53, %54, %55, %56, %57, %58, %59, %60, "
        "%61, %62, %63},"
        " {%64, %65, %66, %67}, %68, p, 1, 1, 1;\n}\n"
        : "+f"(d[0]), "+f"(d[1]), "+f"(d[2]), "+f"(d[3]), "+f"(d[4]), "+f"(d[5]), "+f"(d[6]), "+f"(d[7]),
        "+f"(d[8]), "+f"(d[9]), "+f"(d[10]), "+f"(d[11]), "+f"(d[12]), "+f"(d[13]), "+f"(d[14]), "+f"(d[15]),
        "+f"(d[16]), "+f"(d[17]), "+f"(d[18]), "+f"(d[19]), "+f"(d[20]), "+f"(d[21]), "+f"(d[22]),
        "+f"(d[23]), "+f"(d[24]), "+f"(d[25]), "+f"(d[26]), "+f"(d[27]), "+f"(d[28]), "+f"(d[29]),
        "+f"(d[30]), "+f"(d[31]), "+f"(d[32]), "+f"(d[33]), "+f"(d[34]), "+f"(d[35]), "+f"(d[36]),
        "+f"(d[37]), "+f"(d[38]), "+f"(d[39]), "+f"(d[40]), "+f"(d[41]), "+f"(d[42]), "+f"(d[43]),
        "+f"(d[44]), "+f"(d[45]), "+f"(d[46]), "+f"(d[47]), "+f"(d[48]), "+f"(d[49]), "+f"(d[50]),
        "+f"(d[51]), "+f"(d[52]), "+f"(d[53]), "+f"(d[54]), "+f"(d[55]), "+f"(d[56]), "+f"(d[57]),
        "+f"(d[58]), "+f"(d[59]), "+f"(d[60]), "+f"(d[61]), "+f"(d[62]), "+f"(d[63])
        : "r"(a0), "r"(a1), "r"(a2), "r"(a3), "l"(db), "r"(scale_d));
}
__device__ __forceinline__ void wgmma_ss_n128_tb_init(float (&d)[64], uint64_t da, uint64_t db) {
    asm volatile("{\n.reg .pred p;\n"
        "setp.ne.b32 p, 0, 0;\n"
        "wgmma.mma_async.sync.aligned.m64n128k16.f32.bf16.bf16 "
        "{%0, %1, %2, %3, %4, %5, %6, %7, %8, %9, %10, %11, %12, %13, %14, %15, %16, %17, %18, %19, %20, "
        "%21, %22, %23, %24, %25, %26, %27, %28, %29, %30, %31, %32, %33, %34, %35, %36, %37, %38, %39, %40, "
        "%41, %42, %43, %44, %45, %46, %47, %48, %49, %50, %51, %52, %53, %54, %55, %56, %57, %58, %59, %60, "
        "%61, %62, %63},"
        " %64, %65, p, 1, 1, 0, 1;\n}\n"
        : "=f"(d[0]), "=f"(d[1]), "=f"(d[2]), "=f"(d[3]), "=f"(d[4]), "=f"(d[5]), "=f"(d[6]), "=f"(d[7]),
        "=f"(d[8]), "=f"(d[9]), "=f"(d[10]), "=f"(d[11]), "=f"(d[12]), "=f"(d[13]), "=f"(d[14]), "=f"(d[15]),
        "=f"(d[16]), "=f"(d[17]), "=f"(d[18]), "=f"(d[19]), "=f"(d[20]), "=f"(d[21]), "=f"(d[22]),
        "=f"(d[23]), "=f"(d[24]), "=f"(d[25]), "=f"(d[26]), "=f"(d[27]), "=f"(d[28]), "=f"(d[29]),
        "=f"(d[30]), "=f"(d[31]), "=f"(d[32]), "=f"(d[33]), "=f"(d[34]), "=f"(d[35]), "=f"(d[36]),
        "=f"(d[37]), "=f"(d[38]), "=f"(d[39]), "=f"(d[40]), "=f"(d[41]), "=f"(d[42]), "=f"(d[43]),
        "=f"(d[44]), "=f"(d[45]), "=f"(d[46]), "=f"(d[47]), "=f"(d[48]), "=f"(d[49]), "=f"(d[50]),
        "=f"(d[51]), "=f"(d[52]), "=f"(d[53]), "=f"(d[54]), "=f"(d[55]), "=f"(d[56]), "=f"(d[57]),
        "=f"(d[58]), "=f"(d[59]), "=f"(d[60]), "=f"(d[61]), "=f"(d[62]), "=f"(d[63])
        : "l"(da), "l"(db));
}
__device__ __forceinline__ void wgmma_ss_n128_tb(float (&d)[64], uint64_t da, uint64_t db, int scale_d) {
    asm volatile("{\n.reg .pred p;\n"
        "setp.ne.b32 p, %66, 0;\n"
        "wgmma.mma_async.sync.aligned.m64n128k16.f32.bf16.bf16 "
        "{%0, %1, %2, %3, %4, %5, %6, %7, %8, %9, %10, %11, %12, %13, %14, %15, %16, %17, %18, %19, %20, "
        "%21, %22, %23, %24, %25, %26, %27, %28, %29, %30, %31, %32, %33, %34, %35, %36, %37, %38, %39, %40, "
        "%41, %42, %43, %44, %45, %46, %47, %48, %49, %50, %51, %52, %53, %54, %55, %56, %57, %58, %59, %60, "
        "%61, %62, %63},"
        " %64, %65, p, 1, 1, 0, 1;\n}\n"
        : "+f"(d[0]), "+f"(d[1]), "+f"(d[2]), "+f"(d[3]), "+f"(d[4]), "+f"(d[5]), "+f"(d[6]), "+f"(d[7]),
        "+f"(d[8]), "+f"(d[9]), "+f"(d[10]), "+f"(d[11]), "+f"(d[12]), "+f"(d[13]), "+f"(d[14]), "+f"(d[15]),
        "+f"(d[16]), "+f"(d[17]), "+f"(d[18]), "+f"(d[19]), "+f"(d[20]), "+f"(d[21]), "+f"(d[22]),
        "+f"(d[23]), "+f"(d[24]), "+f"(d[25]), "+f"(d[26]), "+f"(d[27]), "+f"(d[28]), "+f"(d[29]),
        "+f"(d[30]), "+f"(d[31]), "+f"(d[32]), "+f"(d[33]), "+f"(d[34]), "+f"(d[35]), "+f"(d[36]),
        "+f"(d[37]), "+f"(d[38]), "+f"(d[39]), "+f"(d[40]), "+f"(d[41]), "+f"(d[42]), "+f"(d[43]),
        "+f"(d[44]), "+f"(d[45]), "+f"(d[46]), "+f"(d[47]), "+f"(d[48]), "+f"(d[49]), "+f"(d[50]),
        "+f"(d[51]), "+f"(d[52]), "+f"(d[53]), "+f"(d[54]), "+f"(d[55]), "+f"(d[56]), "+f"(d[57]),
        "+f"(d[58]), "+f"(d[59]), "+f"(d[60]), "+f"(d[61]), "+f"(d[62]), "+f"(d[63])
        : "l"(da), "l"(db), "r"(scale_d));
}

enum { M_X = 0, M_C, M_WQ, M_WUK, M_WUV, M_WQKV, M_WO, M_WOB, M_SCR_LD, M_SCR_LOC, M_SCR_LOQ, M_SCR_ST, M_OUT, M_COUNT };
enum { T_Q = 0, T_K, T_V, T_B, T_OUT, T_LOCAL, T_ATTN, T_END };
constexpr int NCTA = 132;
constexpr int NITEMS = 256;
constexpr int TRIPLES = 2, WIDE = 80 - 3 * TRIPLES;
struct Params {
    CUtensorMap m[M_COUNT];
    const __nv_bfloat16* x;
    const __nv_bfloat16* gate_w;
    const char* wo;
    __nv_bfloat16* out;
    uint32_t zero;
    uint16_t plan[10][16];
    uint16_t items[NITEMS];
    uint8_t ostep[80];
};
__device__ __forceinline__ int item_type(int it) { return it >> 13; }
__device__ __forceinline__ int item_row(int it) { return it & 15; }
__device__ __forceinline__ int item_col(int it) { return (it >> 4) & 31; }
__device__ __forceinline__ int item_asc(int it) { return (it >> 9) & 1; }
constexpr int ITEM_READY = 1 << 10;

struct __align__(128) Sync {
    unsigned long long count[4];
    __align__(128) unsigned long long ctx[16];
    unsigned next, next_out, done;
    __align__(128) unsigned step[32][2];
    unsigned split[32];
};
__device__ Sync g_sync;

constexpr uint32_t GST_BYTES = 49152, SM_KV = 65536, SM_STAGING = 196608, SM_BARS = SM_STAGING + 32768;
constexpr uint32_t B_GFULL = 0, B_GEMPTY = 32, B_AFULL = 64, B_AEMPTY = 112, B_SFULL = 160, B_SEMPTY = 192,
                   B_IFULL = 224, B_IEMPTY = 288, B_XFREE = 352, B_WANT = 384, B_MEET = 392, B_HALF = 416,
                   SM_ORDY = 448, SM_QUEUE = 456, B_ALT = 488, B_QFREE = 504, SM_GATE = 512, SM_TOTAL = SM_BARS + 1536;
constexpr int QDEPTH = 8;
constexpr int FIRST_PAIR = 6;
constexpr int K_MEET = 16, K_SPLIT = 30;
constexpr int K_FETCH = 20;
constexpr uint32_t LOC_PLANE = 72 * 128;
constexpr float LOC_SCALE = 0.17677669529663687f * 1.4426950408889634f;
constexpr float SUM_LIMIT = 1180591620717411303424.f;
constexpr float REF_RANGE = 60.f;

__device__ __forceinline__ unsigned ld_acquire(const unsigned* p) {
    unsigned v; asm volatile("ld.acquire.gpu.global.u32 %0, [%1];" : "=r"(v) : "l"(p) : "memory"); return v;
}
__device__ __forceinline__ unsigned long long ld_acquire(const unsigned long long* p) {
    unsigned long long v; asm volatile("ld.acquire.gpu.global.u64 %0, [%1];" : "=l"(v) : "l"(p) : "memory"); return v;
}
__device__ __forceinline__ void spin_guard(unsigned& n) {
    asm volatile("{\n.reg .pred P;\nadd.u32 %0, %0, 1;\nsetp.gt.u32 P, %0, 16777216;\n@P trap;\n}\n" : "+r"(n));
    if (n > 1) __nanosleep(100);
}
__device__ __forceinline__ void red_add(unsigned long long* p, unsigned long long v) {
    asm volatile("red.release.gpu.global.add.u64 [%0], %1;" :: "l"(p), "l"(v) : "memory");
}
__device__ __forceinline__ float rcp(float x) { float y; asm("rcp.approx.ftz.f32 %0, %1;" : "=f"(y) : "f"(x)); return y; }
__device__ __forceinline__ float lds_f32(uint32_t addr) {
    float v; asm volatile("ld.shared.f32 %0, [%1];" : "=f"(v) : "r"(addr) : "memory"); return v;
}
__device__ __forceinline__ void ldsm_x4(uint32_t (&r)[4], uint32_t addr) {
    asm volatile("ldmatrix.sync.aligned.m8n8.x4.shared.b16 {%0, %1, %2, %3}, [%4];"
                 : "=r"(r[0]), "=r"(r[1]), "=r"(r[2]), "=r"(r[3]) : "r"(addr) : "memory");
}
__device__ __forceinline__ void ldsm_x4_t(uint32_t (&r)[4], uint32_t addr) {
    asm volatile("ldmatrix.sync.aligned.m8n8.x4.trans.shared.b16 {%0, %1, %2, %3}, [%4];"
                 : "=r"(r[0]), "=r"(r[1]), "=r"(r[2]), "=r"(r[3]) : "r"(addr) : "memory");
}
__device__ __forceinline__ void mma_k16(float (&d)[4], const uint32_t (&a)[4], uint32_t b0, uint32_t b1) {
    asm("mma.sync.aligned.m16n8k16.row.col.f32.bf16.bf16.f32 {%0,%1,%2,%3}, {%4,%5,%6,%7}, {%8,%9}, {%0,%1,%2,%3};"
        : "+f"(d[0]), "+f"(d[1]), "+f"(d[2]), "+f"(d[3]) : "r"(a[0]), "r"(a[1]), "r"(a[2]), "r"(a[3]), "r"(b0), "r"(b1));
}
__device__ __forceinline__ void mma_k16_init(float (&d)[4], const uint32_t (&a)[4], uint32_t b0, uint32_t b1) {
    asm("{\n.reg .f32 z;\nmov.f32 z, 0f00000000;\n"
        "mma.sync.aligned.m16n8k16.row.col.f32.bf16.bf16.f32 {%0,%1,%2,%3}, {%4,%5,%6,%7}, {%8,%9}, {z,z,z,z};\n}\n"
        : "=f"(d[0]), "=f"(d[1]), "=f"(d[2]), "=f"(d[3]) : "r"(a[0]), "r"(a[1]), "r"(a[2]), "r"(a[3]), "r"(b0), "r"(b1));
}
__device__ __forceinline__ void mma_k8(float (&d)[4], uint32_t a0, uint32_t a1, uint32_t b0) {
    asm("mma.sync.aligned.m16n8k8.row.col.f32.bf16.bf16.f32 {%0,%1,%2,%3}, {%4,%5}, {%6}, {%0,%1,%2,%3};"
        : "+f"(d[0]), "+f"(d[1]), "+f"(d[2]), "+f"(d[3]) : "r"(a0), "r"(a1), "r"(b0));
}
template <typename T, int N> __device__ __forceinline__ void zero_regs(T (&d)[N]) {
#pragma unroll
    for (int i = 0; i < N; i++) d[i] = 0;
}
__device__ __forceinline__ float quad_max(float v) {
    v = fmaxf(v, __shfl_xor_sync(0xffffffffu, v, 1));
    return fmaxf(v, __shfl_xor_sync(0xffffffffu, v, 2));
}
__device__ __forceinline__ float quad_sum(float v) {
    v += __shfl_xor_sync(0xffffffffu, v, 1);
    return v + __shfl_xor_sync(0xffffffffu, v, 2);
}

__device__ __forceinline__ void qk_gemm(float (&s)[64], uint32_t q_lo, uint32_t k_lo) {
    const uint64_t dq = full_desc(q_lo), dk = full_desc(k_lo);
    wgmma_fence();
    wgmma_ss_n128_init(s, dq, dk);
#pragma unroll
    for (int kk = 1; kk < 8; kk++) {
        const uint32_t o = (kk >> 2) * 1024 + (kk & 3) * 2;
        wgmma_ss_n128(s, dq + o, dk + o, 1);
    }
    wgmma_commit();
}
__device__ __forceinline__ void pv_gemm(float (&o)[64], uint32_t (&p)[32], uint32_t v_lo, int accumulate) {
    const uint64_t dv = full_desc(v_lo);
    fence_regs(o);
    fence_regs(p);
    wgmma_fence();
#pragma unroll
    for (int kk = 0; kk < 8; kk++)
        wgmma_rs_n128_tb(o, p[4 * kk], p[4 * kk + 1], p[4 * kk + 2], p[4 * kk + 3], dv + kk * 128, kk != 0 || accumulate);
    wgmma_commit();
}
__device__ __forceinline__ void row_max(const float (&s)[64], float& x0, float& x1) {
    float z0 = fmaxf(s[0], s[1]), z1 = fmaxf(s[2], s[3]);
    x0 = fmaxf(s[4], s[5]); x1 = fmaxf(s[6], s[7]);
#pragma unroll
    for (int j = 2; j < 16; j += 2) {
        z0 = fmaxf(z0, fmaxf(s[4 * j], s[4 * j + 1]));
        z1 = fmaxf(z1, fmaxf(s[4 * j + 2], s[4 * j + 3]));
        x0 = fmaxf(x0, fmaxf(s[4 * j + 4], s[4 * j + 5]));
        x1 = fmaxf(x1, fmaxf(s[4 * j + 6], s[4 * j + 7]));
    }
    x0 = quad_max(fmaxf(x0, z0)); x1 = quad_max(fmaxf(x1, z1));
}
__device__ __forceinline__ void exp_pack(uint32_t (&p)[32], const float (&s)[64], float& r0, float& r1) {
#pragma unroll
    for (int j = 0; j < 16; j++) {
        const float e0 = ex2(s[4 * j]), e1 = ex2(s[4 * j + 1]), e2 = ex2(s[4 * j + 2]), e3 = ex2(s[4 * j + 3]);
        if (j == 0) { r0 = e0 + e1; r1 = e2 + e3; }
        else { r0 += e0 + e1; r1 += e2 + e3; }
        p[2 * j] = pack_bf16(e0, e1);
        p[2 * j + 1] = pack_bf16(e2, e3);
    }
}
__device__ __forceinline__ void shift_rows(float (&s)[64], float d0, float d1) {
#pragma unroll
    for (int j = 0; j < 16; j++) { s[4 * j] -= d0; s[4 * j + 1] -= d0; s[4 * j + 2] -= d1; s[4 * j + 3] -= d1; }
}
constexpr float MASKED = -3e38f;
template <int J0>
__device__ __forceinline__ void mask_triangle(float (&s)[64], float thr) {
#pragma unroll
    for (int j = 0; j < 16; j++) {
        const float m = __saturatef((float)(8 * (j >> 1) + (j & 1)) - thr);
        const int i = 4 * (J0 + (j >> 1)) + (j & 1);
        s[i] = fmaf(m, MASKED, s[i]);
        if (j < 14) s[i + 6] = fmaf(m, MASKED, s[i + 6]);
    }
}
__device__ __forceinline__ void causal_mask(float (&s)[64], float thr, int wg) {
    asm volatile("" : "+f"(thr));
    if (wg == 0) {
        mask_triangle<0>(s, thr);
#pragma unroll
        for (int j = 32; j < 64; j++) s[j] += MASKED;
    } else {
        mask_triangle<8>(s, thr);
    }
}

__global__ void __cluster_dims__(2, 1, 1) __launch_bounds__(384, 1) fused_kernel(const __grid_constant__ Params prm) {
    extern __shared__ __align__(1024) uint8_t smem[];
    const uint32_t sb = smem_u32(smem), bars = sb + SM_BARS;
    const int warp = __shfl_sync(0xffffffffu, threadIdx.x >> 5, 0), lane = threadIdx.x & 31;

    const uint32_t rank = cluster_rank();
    const uint32_t bars0 = map_cta(bars, 0), bars_peer = map_cta(bars, rank ^ 1);

    auto plan_index = [&]() -> uint32_t {
        uint32_t p = blockIdx.x >> 1;
        asm volatile("" : "+r"(p));
        const uint32_t r = (p - 36) * 37 >> 8;
        return p < 4 ? 4 + p : p < 36 ? (p - 4 & 7) * 8 + (p - 4 >> 3) : p < 64 ? (p - 35 - 7 * r) * 8 + 4 + r : p;
    };
    auto first_item = [&]() -> int {
        const uint32_t pair = plan_index();
        const uint32_t slot = pair & 7, c = slot * 11 >> 5;
        return pair < 64 ? T_B << 13 | (4 * slot - 11 * c) << 4 | (2 * (pair >> 3) + rank) : T_K << 13 | (8 * slot + rank);
    };
    if (warp == 0) {
        if (elect_one())
            for (int k = 0; k < 4; k++) mbar_init(bars + B_GFULL + 8 * k, 1);
        const int first_it = __shfl_sync(0xffffffffu, first_item(), 0);
        asm volatile("fence.mbarrier_init.release.cluster;" ::: "memory");
        fence_proxy_async_smem();
        __syncwarp();
        asm volatile("barrier.cluster.arrive.relaxed.aligned;" ::: "memory");
        const CUtensorMap* ma = &prm.m[item_type(first_it) == T_K ? M_C : M_X];
        const CUtensorMap* mb = &prm.m[M_WQ + item_type(first_it)];
#pragma unroll
        for (int k = 0; k < 2; k++) {
            const uint32_t dst = sb + k * GST_BYTES, fb = bars + B_GFULL + 8 * k;
            warp_expect_tx(fb, GST_BYTES);
            warp_tma_load(dst + 16384, mb, fb, 0, k * 64, item_col(first_it) * 4, true);
            warp_tma_load(dst, ma, fb, k * 64, item_row(first_it) * 128, 0, false);
            warp_tma_load(dst + 32768, mb, fb, 0, k * 64, item_col(first_it) * 4 + 2, true);
        }
    }
    if (threadIdx.x == 32) {
        for (int i = 0; i < 4; i++) mbar_init(bars + B_GEMPTY + 8 * i, 16);
        for (int i = 0; i < 6; i++) { mbar_init(bars + B_AFULL + 8 * i, 1); mbar_init(bars + B_AEMPTY + 8 * i, i < 2 ? 8 : 16); }
        for (int i = 0; i < 4; i++) { mbar_init(bars + B_SFULL + 8 * i, 4); mbar_init(bars + B_SEMPTY + 8 * i, 1); }
        for (int i = 0; i < QDEPTH; i++) { mbar_init(bars + B_IFULL + 8 * i, 1); mbar_init(bars + B_IEMPTY + 8 * i, 23); }
        mbar_init(bars + B_WANT, 2); mbar_init(bars + B_MEET, 1); mbar_init(bars + B_XFREE, 1);
        for (int i = 0; i < 4; i++) mbar_init(bars + B_HALF + 8 * i, 1);
        mbar_init(bars + B_ALT, 4); mbar_init(bars + B_ALT + 8, 4); mbar_init(bars + B_QFREE, 2);
        asm volatile("st.shared.u64 [%0], 0;" :: "r"(bars + SM_ORDY) : "memory");
        asm volatile("fence.mbarrier_init.release.cluster;\nfence.acq_rel.cta;" ::: "memory");
    }
    __syncwarp();
    if (warp != 0) asm volatile("barrier.cluster.arrive.relaxed.aligned;" ::: "memory");
    asm volatile("barrier.cluster.wait.acquire.aligned;" ::: "memory");

    uint32_t qn = 0;
    auto next_item = [&](bool releaser, bool bounded = true) -> int {
        const uint32_t slot = qn % QDEPTH;
        if (bounded) mbar_wait(bars + B_IFULL + 8 * slot, (qn / QDEPTH) & 1);
        else mbar_spin(bars + B_IFULL + 8 * slot, (qn / QDEPTH) & 1);
        uint32_t it;
        asm volatile("ld.shared.u32 %0, [%1];" : "=r"(it) : "r"(bars + SM_QUEUE + 4 * slot) : "memory");
        mbar_arrive_cluster_if(releaser, bars0 + B_IEMPTY + 8 * slot);
        qn++;
        return it;
    };

    if (warp < 4) {
        reg_dec<40>();
        if (warp == 0) {
            {
                uint32_t gph = 1;
                const uint32_t prank = __shfl_sync(0xffffffffu, rank, 0);
                auto request = [&]() { mbar_arrive_cluster_if(lane == 0, bars0 + B_WANT); };
                auto take_item = [&]() -> int { return __shfl_sync(0xffffffffu, next_item(lane == 0), 0); };
                auto inputs_seen = [&](uint32_t word, unsigned& n) -> uint32_t {
                    uint32_t v;
                    spin_guard(n);
                    asm volatile("ld.acquire.cta.shared.u32 %0, [%1];" : "=r"(v) : "r"(bars + SM_ORDY + 4 * word) : "memory");
                    return __shfl_sync(0xffffffffu, v, 0);
                };
                uint32_t oneed = 0;
                auto wait_inputs = [&](int it) {
                    if (it & ITEM_READY) return;
                    oneed += 256;
                    for (unsigned n = 0; inputs_seen(1, n) < oneed;) {}
                };
                int nxt = first_item(), ring = -1, rot = 0;
                for (int k0 = 2; item_type(nxt) <= T_LOCAL; k0 = 0) {
                    const int type = item_type(nxt), m = item_row(nxt), c = item_col(nxt);
                    if (type == T_LOCAL) {
                        wait_inputs(nxt);
                        request();
#pragma unroll 1
                        for (uint32_t st = 0; st < 4; st++) {
                            mbar_wait(bars + B_GEMPTY + 8 * st, gph);
                            const uint32_t dst = sb + st * GST_BYTES, fb = bars + B_GFULL + 8 * st;
                            warp_expect_tx(fb, st == 0 ? 32768 + 512 : st == 3 ? 0 : 4 * LOC_PLANE);
                            if (st == 3) break;
                            if (st == 0) warp_bulk_load(dst + 4 * LOC_PLANE, &g_gate[m * 128], 512, fb);
#pragma unroll 1
                            for (int i = 0; i < 4; i++)
                                warp_tma_load(dst + i * LOC_PLANE, &prm.m[st ? M_SCR_LOC : M_SCR_LOQ], fb, i * 64, m * 64 - (st ? 8 : 0), G_B + 8 * st + c, true);
                        }
                        gph ^= 1;
                        ring = -1;
                    } else {
                        const int nk = type == T_K || type == T_V ? 8 : 16, kept = ring == m + 16 * nk ? 4 : 0;
                        ring = m + 16 * nk;
                        rot = kept ? rot - 4 : 0;
                        const CUtensorMap* ma = &prm.m[nk == 8 ? M_C : M_X];
                        const CUtensorMap* mb = &prm.m[M_WQ + type];
#pragma unroll 1
                        for (int k = k0; k < nk; k++) {
                            if (k == nk - 3) request();
                            const uint32_t st = k & 3, dst = sb + st * GST_BYTES, fb = bars + B_GFULL + 8 * st;
                            const int kc = ((k + rot) & (nk - 1)) * 64;
                            mbar_wait(bars + B_GEMPTY + 8 * st, gph);
                            warp_expect_tx(fb, k < kept ? 32768 : GST_BYTES);
                            if (k >= kept) warp_tma_load(dst, ma, fb, kc, m * 128, 0, c == 15 && type != T_K);
                            warp_tma_load_pair(dst + 16384 + prank * 16384, mb, fb, 0, kc, c * 4 + 2 * prank, true);
                            if (st == 3) gph ^= 1;
                        }
                    }
                    nxt = take_item();
                }
                uint32_t kv = 0, kvph = 1;
                uint32_t qc = 0;
                auto a_parity = [&](uint32_t b) { return b < 2 ? (((qc + 1 - b) >> 1) & 1) ^ 1 : kvph ^ (b - 2 < kv); };
                const CUtensorMap* tile_map = &prm.m[M_SCR_LD];
                asm volatile("" : "+l"(tile_map));
                {
                    bool need_g = true, more = true;
                    int pv_grp = -1, pv_row = 0;
                    int pv_shared = 0;
                    bool peer_longer = false;
                    int m = 0, c = 0, asc = 0, nu = 0, uend = 0, ureq = -1, ufetch = 0;
#pragma unroll 1
                    for (int u = 0;; u++) {
                        if (u == ufetch) {
                            if (qc) nxt = take_item();
                            if (item_type(nxt) == T_ATTN) {
                                wait_inputs(nxt);
                                const uint32_t b = qc & 1, dst = sb + b * 32768, fb = bars + B_AFULL + 8 * b, row = item_row(nxt) * 128;
                                mbar_wait(bars + (qc == 0 ? B_GEMPTY : qc == 1 ? B_QFREE : B_AEMPTY + 8 * b), qc == 0 ? gph : qc == 1 ? 0 : a_parity(b));
                                warp_expect_tx(fb, 32768 + 512);
                                warp_tma_load(dst, tile_map, fb, 0, row, G_Q + item_col(nxt), false);
                                warp_tma_load(dst + 16384, tile_map, fb, 64, row, G_Q + item_col(nxt), false);
                                warp_bulk_load(bars + SM_GATE + b * 512, &g_gate[row], 512, fb);
                                qc++;
                            }
                        }
                        if (u == uend) {
                            if (!more) break;
                            more = item_type(nxt) == T_ATTN;
                            m = item_row(nxt); c = item_col(nxt); asc = item_asc(nxt);
                            nu = more ? 2 * m + 2 : 0;
                            uend = nu + ((more ? m < 2 : pv_grp >= 0) ? 3 : 0);
                            ureq = 2 * max(m - 2 - (asc & m), 0);
                            ufetch = !more ? -1 : m ? 2 * m : uend;
                            u = -1;
                            continue;
                        }
                        int grp = pv_grp, row = pv_row;
                        int shared = pv_shared;
                        if (u >= nu) {
                            if (u == nu + 1) pv_grp = -1;
                            else if (peer_longer) { grp = -1; shared = 0; }
                            else continue;
                        } else {
                            const int j = asc ? u >> 1 : m - (u >> 1);
                            if (u & 1) {
                                pv_grp = G_V + c; pv_row = j * 128; pv_shared = (m | 1) - j;
                                peer_longer = asc & ~m & 1;
                                if (u == nu - 1 && (m & 1) && item_type(nxt) == T_END) mbar_arrive_cluster_n_if(lane == 0, bars0 + B_WANT, 2);
                                if (grp < 0) continue;
                            } else {
                                if (u == ureq) request();
                                grp = G_K + c; row = j * 128; shared = (m | 1) - j;
                            }
                        }
                        uint32_t fb = bars + B_AFULL + 16 + 8 * kv, mine = sb + SM_KV + kv * 32768 + prank * 16384;
                        int c_mine = prank * 64;
                        asm volatile("" : "+r"(mine), "+r"(fb), "+r"(row), "+r"(grp), "+r"(c_mine));
                        mbar_wait(need_g ? bars + B_GEMPTY + 8 + 8 * kv : fb + B_AEMPTY - B_AFULL, need_g ? gph : kvph);
                        warp_expect_tx(fb, grp < 0 ? 0 : 32768);
                        if (shared) {
                            warp_tma_load_pair(mine, tile_map, fb, c_mine, row, grp, shared == 1);
                        } else if (grp >= 0) {
                            warp_tma_load(mine, tile_map, fb, c_mine, row, grp, true);
                            warp_tma_load(mine + 16384 - prank * 32768, tile_map, fb, 64 - c_mine, row, grp, true);
                        } else {
                            mbar_arrive_cluster_n_if(lane < 2, map_cta(fb, lane & 1) + B_AEMPTY - B_AFULL, 8);
                        }
                        if (kv == 2) need_g = false;
                        if (++kv == 4) { kv = 0; kvph ^= 1; }
                    }
                }
                if (!qc) request();
                const int it = take_item();
                int nk = 0;
                if (item_type(it) == T_OUT) {
                    const int m = item_row(it), c = item_col(it), half = c & 1;
                    nk = 80;
                    for (unsigned n = 0; (inputs_seen(1, n) & 255) != 255;) {}
                    mbar_wait(bars + B_GEMPTY + 24, gph);
                    mbar_wait(bars + B_QFREE, 0);
                    mbar_wait(bars + B_AEMPTY + 8 * (qc & 1), a_parity(qc & 1));
#pragma unroll 1
                    for (uint32_t k = 0; k < 4; k++) {
                        const uint32_t sa = prm.ostep[half ? WIDE - 1 - k : k], dst = sb + k * GST_BYTES, fb = bars + B_GFULL + 8 * k;
                        const uint32_t b0 = k ? 1 + k : ~qc & 1, b1 = 2 + k - (k == 1);
                        mbar_wait(bars + B_AEMPTY + 8 * b0, a_parity(b0));
                        mbar_arrive_cluster_if(lane == 0 && !k, bars_peer + B_XFREE);
                        warp_expect_tx(fb, GST_BYTES);
                        warp_tma_load(dst, tile_map, fb, (sa & 1) * 64, m * 128, G_LOC - 32 + (sa >> 1), true);
                        mbar_wait(bars + (k ? B_AEMPTY + 8 * b1 : B_XFREE), k ? kvph ^ (b1 - 2 < kv) : 0);
                        warp_tma_load_pair(dst + 16384 + prank * 16384, &prm.m[M_WOB], fb, 0, (sa & 63) * 64, (c >> 1) * 4 + 2 * (half ^ prank), false);
                    }
                    gph ^= 1;
                    uint32_t seen = 0;
                    for (int k = 4; k < nk; k++) {
                        if (k == K_SPLIT) nk = 2 * TRIPLES + (take_item() & 127);
                        const int kn = k + 2 * TRIPLES - nk, first = kn >= 0 && !(kn & 1);
                        const int s = kn >= 0 ? WIDE + (3 * kn + 1) / 2 : half ? WIDE - 1 - k : k;
                        const uint32_t sa = prm.ostep[s], sa2 = prm.ostep[s + first], sw = prm.ostep[s - (kn >= 0 && !first ? prank : 0)];
                        const uint32_t need = 1u << (sa >> 1 & 31) | 1u << (sa2 >> 1 & 31);
                        for (unsigned n = 0; sa < 64 && (need & ~seen);) seen = inputs_seen(0, n);
                        const uint32_t st = k & 3;
                        uint32_t dst = sb + st * GST_BYTES, fb = bars + B_GFULL + 8 * st;
                        uint32_t dstb = dst + 16384 + (first ? 0 : prank * 16384), skipb = first && (kn >> 1 & 1) != prank;
                        int a0 = (sa & 1) * 64, a1 = m * 128, a2 = (sa >> 1) + (sa < 64 ? G_CTX : G_LOC - 32);
                        int b1 = (sw & 63) * 64, b2 = (c >> 1) * 4 + 2 * (kn >= 0 ? half : half ^ prank);
                        const CUtensorMap* mb = &prm.m[sw >= 64 ? M_WOB : M_WO];
                        asm volatile("" : "+r"(dst), "+r"(fb), "+r"(dstb), "+r"(skipb), "+r"(a0), "+r"(a1), "+r"(a2), "+r"(b1), "+r"(b2), "+l"(mb));
                        mbar_wait(bars + B_GEMPTY + 8 * st, gph);
                        warp_expect_tx(fb, GST_BYTES);
                        warp_tma_load(dst, tile_map, fb, a0, a1, a2, true);
                        if (!skipb) warp_tma_load_pair(dstb, mb, fb, 0, b1, b2, false);
                        if (first) warp_tma_load(dst + 32768, tile_map, fb, (sa2 & 1) * 64, a1, G_CTX + (sa2 >> 1), true);
                        if (k < K_SPLIT && lane == 0 && !prank)
                            asm volatile("st.relaxed.gpu.global.u32 [%0], %1;" :: "l"(&g_sync.step[0][0] + m * 4 + c), "r"(k) : "memory");
                        mbar_arrive_if(k == K_MEET && lane == 0, bars + B_MEET);
                        if ((uint32_t)(k - K_FETCH) < (3 * TRIPLES + 1) / 2) {
                            const uint32_t g = prm.ostep[79 - 2 * (k - K_FETCH)] >> 1;
                            warp_prefetch((const char*)g_scr + (uint32_t)((G_CTX + g) * (SEQ * 256) + m * 32768 + c * 4096), 4096);
                            warp_prefetch(prm.wo + (uint32_t)(g * 262144 + (m * 8 + c) * 2048), 2048);
                        }
                        if (st == 3) gph ^= 1;
                    }
                    for (unsigned n = 0; ~inputs_seen(0, n);) {}
                }
#pragma unroll 1
                for (uint32_t st = 0; st < 4; st++) { mbar_wait(bars + B_GEMPTY + 8 * st, gph ^ (st < (nk & 3))); mbar_wait(bars + B_AEMPTY + 16 + 8 * st, a_parity(2 + st)); }
                unsigned left = 0;
                if (lane == 0) asm volatile("atom.relaxed.gpu.global.add.u32 %0, [%1], 1;" : "=r"(left) : "l"(&g_sync.done) : "memory");
                if (__shfl_sync(0xffffffffu, left, 0) == NCTA - 1)
#pragma unroll 1
                    for (uint32_t i = lane * 8; i < sizeof(Sync); i += 256) *(unsigned long long*)((char*)&g_sync + i) = 0;
            }
        } else if (warp <= 2) {
            if (blockIdx.x < SEQ / 16) {
                const uint32_t r0 = 16 * blockIdx.x + 8 * (warp - 1), gbuf = bars + SM_GATE + 4 * (r0 & 15);
                float z[4];
                mbar_wait(bars + B_GFULL + 24, 0);
#pragma unroll 1
                for (uint32_t i = 0; i < 8; i++) {
                    const uint32_t off = (i & 3) * 512 + lane * 16;
                    const uint4* xp = (const uint4*)((const char*)prm.x + ((r0 + (i & 4)) * 2048 + off));
                    const uint4 wv = __ldg((const uint4*)((const char*)prm.gate_w + off));
                    uint4 xv[4];
#pragma unroll
                    for (int r = 0; r < 4; r++) { xv[r] = __ldg(xp + r * 128); if (!(i & 3)) z[r] = 0.f; }
                    const uint32_t ws[4] = {wv.x, wv.y, wv.z, wv.w};
#pragma unroll
                    for (int e = 0; e < 4; e++)
#pragma unroll
                        for (int r = 0; r < 4; r++) {
                            const uint32_t xs = e == 0 ? xv[r].x : e == 1 ? xv[r].y : e == 2 ? xv[r].z : xv[r].w;
                            z[r] = fmaf(__uint_as_float(xs << 16), __uint_as_float(ws[e] << 16), z[r]);
                            z[r] = fmaf(__uint_as_float(xs & 0xffff0000u), __uint_as_float(ws[e] & 0xffff0000u), z[r]);
                        }
                    if ((i & 3) == 3) {
#pragma unroll
                        for (int o = 16; o > 0; o >>= 1)
#pragma unroll
                            for (int r = 0; r < 4; r++) z[r] += __shfl_xor_sync(0xffffffffu, z[r], o);
                        const float zr = lane & 2 ? (lane & 1 ? z[3] : z[2]) : (lane & 1 ? z[1] : z[0]);
                        asm volatile("st.shared.f32 [%0], %1;" :: "r"(gbuf + 4 * ((i & 4) + (lane & 3))), "f"(1.f / (1.f + __expf(-zr))) : "memory");
                    }
                }
                fence_proxy_async_smem();
                __syncwarp();
                warp_bulk_store((char*)g_gate + 4 * r0, gbuf, 32);
                bulk_commit();
                bulk_wait<0>();
                __syncwarp();
                if (lane == 0) red_add(&g_sync.count[3], 1);
            }
            __syncwarp();
            {
                const int w = warp - 1;
                uint32_t sph = 0, nann = 0;
                int unsent = 0, nunsent = 0;
                bool urgent = false;
                auto announce = [&]() {
                    if (!urgent) return;
                    bulk_wait<0>();
                    __syncwarp();
                    const uint32_t hb = bars + B_HALF + 8 * (nann & 3);
                    if (w == 0) {
                        mbar_arrive_if(lane == 0, hb);
                    } else {
                        mbar_wait(hb, (nann >> 2) & 1);
                        const uint32_t type = item_type(unsent), m = item_row(unsent), c = item_col(unsent);
                        const uint32_t word = type < T_B ? c >> 3 : type == T_B ? 2 : offsetof(Sync, ctx) / 8 + m;
                        const uint32_t bit = type < T_B ? 8 * (c & 7) : type == T_B ? 8 * (c & 3) : type == T_LOCAL ? 32 + c : c;
                        if (lane < nunsent) red_add((unsigned long long*)((char*)&g_sync + 8 * word), 1ull << bit);
                        __syncwarp();
                    }
                    nann++;
                    nunsent = 0; urgent = false;
                };
                int held = first_item(), it;
                do {
                    if (!__all_sync(0xffffffffu, mbar_test(bars + B_IFULL + 8 * (qn % QDEPTH), (qn / QDEPTH) & 1))) announce();
                    it = __shfl_sync(0xffffffffu, next_item(lane == 0), 0);
                    const int itype = item_type(it);
                    const bool keep_held = itype == T_LOCAL;
#pragma unroll 1
                    for (int pass = held < 0 || keep_held; pass < 2; pass++) {
                        if (pass && (itype < T_OUT || itype == T_END)) break;
                        const int cur = pass ? it : held, type = item_type(cur), m = item_row(cur), c = item_col(cur);
                        const bool local = type == T_LOCAL;
                        const int grp = pass ? (local ? G_LOC : G_CTX) + c : type * 32 + 2 * c;
#pragma unroll 1
                        for (int i = 0; i < 4 - 2 * pass; i++) {
                            const int b = i & 1;
                            const bool alt = i >= 2 && itype >= T_ATTN;
                            const uint32_t full = bars + (alt ? B_ALT + 8 * w : B_SFULL + 16 * w + 8 * b), par = alt ? 0 : sph;
                            if (i == 3 - 2 * pass || !__all_sync(0xffffffffu, mbar_test(full, par))) announce();
                            mbar_wait(full, par);
                            fence_proxy_async_smem();
                            warp_tma_store(&prm.m[local ? M_SCR_LOQ : M_SCR_ST], sb + (alt ? 32768 : SM_STAGING) + w * 16384 + b * 8192,
                                         local ? b * 128 + w * 64 : b * 64, local ? m * 64 : m * 128 + w * 64, grp + (i >> 1), local || (type < T_B && c < FIRST_PAIR));
                            bulk_commit();
                            if (pass > b) continue;
                            bulk_wait_read<0>();
                            __syncwarp();
                            mbar_arrive_if(lane <= pass && !alt, bars + B_SEMPTY + 16 * w + 8 * (b - lane));
                            sph ^= b & !alt;
                        }
                        mbar_arrive_if(lane == 0 && !pass && itype >= T_ATTN, bars + B_QFREE);
                        if (lane == nunsent) unsent = cur;
                        nunsent++;
                        urgent = !local;
                    }
                    if (!keep_held) held = itype < T_OUT ? it : -1;
                } while (item_type(it) != T_END);
                announce();
                it = __shfl_sync(0xffffffffu, next_item(lane == 0), 0);
                if (item_type(it) == T_OUT) {
                    if (w) {
                        mbar_wait(bars + B_MEET, 0);
                        asm volatile("fence.proxy.async.global;\nfence.acq_rel.gpu;" ::: "memory");
                        mbar_arrive_cluster_if(lane == 0, bars0 + B_WANT);
                    }
                    next_item(lane == 0);
#pragma unroll 1
                    for (int i = 0; i < 4; i++) {
                        const int b = i & 1;
                        mbar_wait(bars + B_SFULL + 16 * w + 8 * b, sph ^ (i >> 1));
                        fence_proxy_async_smem();
                        warp_tma_add(&prm.m[M_OUT], sb + SM_STAGING + w * 16384 + b * 8192, (item_col(it) ^ (i < 2)) * 128 + b * 64, item_row(it) * 128 + w * 64, 0);
                        bulk_commit();
                        if (b) {
                            bulk_wait_read<0>();
                            __syncwarp();
                            mbar_arrive_if(lane < 2, bars + B_SEMPTY + 16 * w + 8 * lane);
                        }
                    }
                }
            }
        } else {
            if (elect_one()) {
                uint32_t ordy = 0;
                unsigned long long cnt_lo = 0, cnt_hi = 0;
                int late = 0;
                auto refresh = [&]() {
                    if (!late && cnt_lo == 0x30303030 && cnt_hi == SEQ / 8) late = 1;
                    asm volatile("ld.acquire.gpu.global.v2.u64 {%0, %1}, [%2];" : "=l"(cnt_lo), "=l"(cnt_hi) : "l"(late ? &g_sync.count[0] : &g_sync.count[2]) : "memory");
                };
                auto inputs_ready = [&](int it) -> bool {
                    const int c = item_col(it);
                    if (item_type(it) == T_ATTN) return late && ((c < 16 ? cnt_lo : cnt_hi) >> (4 * (c & 14)) & 255) == 48;
                    return late || (cnt_hi == SEQ / 8 && (cnt_lo >> (4 * (c & 6)) & 255) == 48);
                };
                auto publish = [&](int it, int step) {
                    const uint32_t slot = qn % QDEPTH;
                    mbar_wait(bars + B_IEMPTY + 8 * slot, ((qn / QDEPTH) & 1) ^ 1);
                    for (uint32_t r = 0; r < 2; r++) {
                        const uint32_t rb = map_cta(bars, r);
                        asm volatile("mbarrier.arrive.expect_tx.shared::cluster.b64 _, [%0], 4;" :: "r"(rb + B_IFULL + 8 * slot) : "memory");
                        asm volatile("st.async.shared::cluster.mbarrier::complete_tx::bytes.u32 [%0], %1, [%2];"
                                     :: "r"(rb + SM_QUEUE + 4 * slot), "r"(it + r * step), "r"(rb + B_IFULL + 8 * slot) : "memory");
                    }
                    qn++;
                };
                int asc = 1;
                int it;
                do {
                    if (rank == 0) {
                        mbar_wait(bars + B_WANT, qn & 1);
                        const uint32_t pair = plan_index();
                        int pit = prm.plan[pair < 64 ? pair & 7 : pair - 56][min(qn + 1, 15u)];
                        unsigned i;
                        const bool planned = item_type(pit) != T_END;
                        if (!planned) asm volatile("atom.relaxed.gpu.global.add.u32 %0, [%1], 1;" : "=r"(i) : "l"(&g_sync.next) : "memory");
                        if (cnt_lo != 0x3030303030303030ull || cnt_hi != cnt_lo) refresh();
                        if (planned) pit += (pair >> 3 & 7) << (item_type(pit) == T_LOCAL);
                        else if (i < NITEMS) pit = prm.items[i];
                        const int type = item_type(pit);
                        int step = type == T_LOCAL ? 16 : 1;
                        it = pit + (pit & (step == 1 ? 15 : 0x1f0));
                        if (type == T_ATTN) {
                            if (!asc) { it += 1; step = -1; }
                            it |= asc << 9;
                        }
                        asc = type != T_ATTN || item_row(pit) == 0 || !asc;
                        if (inputs_ready(it)) it |= ITEM_READY;
                        publish(it, step);
                    } else {
                        it = next_item(true);
                    }
                    if ((item_type(it) == T_ATTN || item_type(it) == T_LOCAL) && !(it & ITEM_READY)) {
                        unsigned n = 0;
                        while (!inputs_ready(it)) { refresh(); spin_guard(n); }
                        asm volatile("st.release.cta.shared.u32 [%0], %1;" :: "r"(bars + SM_ORDY + 4), "r"(ordy += 256) : "memory");
                    }
                } while (item_type(it) != T_END);
                if (rank == 0) {
                    mbar_wait(bars + B_WANT, qn & 1);
                    const unsigned i = atomicAdd(&g_sync.next_out, 1u), t = i < 32 ? 31 - i : i - 32;
                    it = i < 64 ? T_OUT << 13 | ((t & 3) * 2 + (i >> 5)) << 4 | (t >> 2) * 2 : T_END << 13;
                    publish(it, 1);
                } else {
                    it = next_item(true);
                }
                if (item_type(it) == T_OUT) {
                    const uint32_t m = item_row(it), half = item_col(it) & 1, tile = m * 2 + (item_col(it) >> 1);
                    unsigned* split = (unsigned*)((char*)g_sync.split + 4 * tile);
                    unsigned long long rdy = 0;
                    int state = rank ? 2 : 0;
                    for (unsigned n = 0; rdy != 0xffffffffffull || state < 2; spin_guard(n)) {
                        if (rdy != 0xffffffffffull) {
                            rdy = ld_acquire((const unsigned long long*)((char*)g_sync.ctx + 8 * m));
                            asm volatile("st.release.cta.shared.u64 [%0], %1;" :: "r"(bars + SM_ORDY), "l"(rdy) : "memory");
                        }
                        unsigned steps = 0;
                        if (state == 1) {
                            steps = ld_acquire(split);
                        } else if (state == 0 && mbar_test(bars + B_WANT, qn & 1)) {
                            state = 1;
                            unsigned seen;
                            asm volatile("atom.acq_rel.gpu.global.exch.b32 %0, [%1], 1;" : "=r"(seen) : "l"(split) : "memory");
                            if (seen) {
                                const unsigned long long v = ld_acquire((const unsigned long long*)((char*)g_sync.step + 8 * tile));
                                const int d = (int)(v >> 32) - (int)v;
                                steps = (WIDE + min(max(half ? d : -d, -12), 12)) >> 1;
                                atomicExch(split, WIDE - steps);
                            }
                        }
                        if (steps > 1) { publish(T_END << 13 | steps, 0); state = 2; }
                    }
                    if (rank) next_item(true);
                }
#pragma unroll 1
                for (uint32_t n = qn; n < qn + QDEPTH && rank == 0; n++) mbar_wait(bars + B_IEMPTY + 8 * (n % QDEPTH), ((n / QDEPTH) & 1) ^ 1);
            }
        }
    } else {
        reg_inc<232>();
        const int wg = (warp >> 2) - 1, wq = warp & 3;
        uint32_t gph = 0;
        uint32_t kvn = 0;
        const uint32_t dA = make_desc(sb + wg * 8192, 16);
        uint32_t ti = 0;
        uint32_t sph = 1;
        const uint32_t stg = sb + SM_STAGING + wg * 16384;
        const uint32_t stg_lane = stg + (wq * 16 + (lane & 15)) * 128 + (((lane >> 4) ^ (lane & 7)) << 4);
        auto write_blocks = [&](auto n, uint32_t off, const uint32_t* v) {
            uint32_t a = stg_lane;
            asm volatile("" : "+r"(a));
            a += off;
#pragma unroll
            for (int j = 0; j < decltype(n)::value; j++)
                stmatrix_x4((a ^ (32 * (j & 3))) + (j >> 2) * 8192, v[4 * j], v[4 * j + 1], v[4 * j + 2], v[4 * j + 3]);
        };
        auto release = [&](uint32_t bar) { mbar_arrive_if(lane == 0, bars + bar); };
        const uint32_t bars_lane = map_cta(bars, lane & 1);
        auto release_stage = [&](uint32_t st) { mbar_arrive_cluster_if(lane < 2, bars_lane + B_GEMPTY + 8 * st); };
        auto take_item = [&]() -> int {
            return __shfl_sync(0xffffffffu, next_item(lane == 0, false), 0);
        };
        auto stage_acquire = [&](int b) { mbar_spin(bars + B_SEMPTY + 16 * wg + 8 * b, sph); };
        auto stage_publish = [&](int b) {
            __syncwarp();
            release(B_SFULL + 16 * wg + 8 * b);
        };
        auto stage_chunk = [&](int b, const uint32_t* v) {
            stage_acquire(b);
            write_blocks(std::integral_constant<int, 4>(), b * 8192, v);
            stage_publish(b);
            if (b) sph ^= 1;
        };
        auto publish_pair = [&]() {
            __syncwarp();
            mbar_arrive_if(lane < 2, bars + B_SFULL + 16 * wg + 8 * lane);
            sph ^= 1;
        };
        auto gemm_step = [&](float (&acc)[128], uint32_t dB, int& k, bool order) {
            const uint32_t st = k & 3;
            wgmma_wait<0>();
            release_stage((k - 1) & 3);
            mbar_spin(bars + B_GFULL + 8 * st, gph);
            const uint64_t da = full_desc(dA + st * (GST_BYTES >> 4)), db = full_desc(dB + st * (GST_BYTES >> 4));
            if (order && wg) bar_sync(3, 256);
            wgmma_fence();
#pragma unroll
            for (int kk = 0; kk < 4; kk++) wgmma_ss_n256_tb(acc, da + 2 * kk, db + 128 * kk, 1);
            wgmma_commit();
            if (order && !wg) bar_arrive(3, 256);
            gph ^= st == 3;
            k++;
        };
        if (wg == 1) bar_arrive(1, 256);
        int it = first_item();
        float s[64];
        const uint32_t dK = make_desc(sb + SM_KV, 16);
        auto kv_wait = [&](uint32_t n) { mbar_spin(bars + B_AFULL + 16 + 8 * (n & 3), (n >> 2) & 1); };
        auto first_scores = [&](bool valid) {
            if (valid) { mbar_spin(bars + B_AFULL + 8 * (ti & 1), (ti >> 1) & 1); kv_wait(kvn); }
            bar_sync(1 + wg, 256);
            qk_gemm(s, dA + (ti & 1) * 2048, dK + (kvn & 3) * 2048);
        };
        bool issued;
        {
            {
                float acc[128];
                uint32_t pk[64];
                bool pending = false;
                int held = T_END;
                auto scale_q = [&](int j0) {
                    if (held != T_Q) return;
#pragma unroll
                    for (int j = j0; j < j0 + 16; j++)
                        asm("{\n.reg .b32 t;\nmul.rn.bf16x2 t, %0, %2;\nfma.rn.bf16x2 %0, %0, %1, t;\n}\n" : "+r"(pk[j]) : "r"(0x3e033e03u), "r"(0xb9d8b9d8u));
                };
                zero_regs(pk);
                const uint32_t dB = make_desc(sb + 16384, 8192);
                do {
                    if (item_type(it) == T_LOCAL) {
                        int ln = lane;
                        asm volatile("" : "+r"(ln));
                        const int g = ln >> 2, t = ln & 3, par = wq & 1;
                        const uint32_t hc = (wq >> 1) * 4, pl = sb + (par * 2 + wg) * LOC_PLANE;
                        const uint32_t a16 = (ln & 15) * 128 + (((hc + (ln >> 4)) ^ (ln & 7)) << 4), a8 = (ln & 7) * 128 + (((hc + (ln >> 3)) ^ (ln & 7)) << 4);
                        const bool first0 = 2 * t > g, first1 = 2 * t + 1 > g;
                        const uint32_t fmask = (first0 ? 0xffffu : 0u) | (first1 ? 0xffff0000u : 0u);
                        const bool edge = item_row(it) == 0;
                        uint32_t q[4][2][4], kf[9][4], vf[9][4];
                        float w[8];
                        mbar_spin(bars + B_GFULL, gph);
#pragma unroll
                        for (int u = 0; u < 4; u++) { ldsm_x4(q[u][0], pl + u * 2048 + a16); ldsm_x4(q[u][1], pl + u * 2048 + (a16 ^ 32)); }
#pragma unroll
                        for (int j = 0; j < 8; j++) w[j] = lds_f32(sb + 4 * LOC_PLANE + 4 * (2 * g + par) + 64 * j);
                        __syncwarp();
                        release_stage(0);
                        mbar_spin(bars + B_GFULL + 8, gph);
#pragma unroll
                        for (int n = 0; n < 9; n++) ldsm_x4(kf[n], pl + GST_BYTES + n * 1024 + a8);
                        __syncwarp();
                        release_stage(1);
                        float s[8][2];
#pragma unroll
                        for (int u = 0; u < 4; u++) {
                            float d[3][4];
#pragma unroll
                            for (int nt = 0; nt < 3; nt++) {
                                mma_k16_init(d[nt], q[u][0], kf[2 * u + nt][0], kf[2 * u + nt][1]);
                                mma_k16(d[nt], q[u][1], kf[2 * u + nt][2], kf[2 * u + nt][3]);
                            }
                            if (u == 0 && edge) { d[0][0] = -INFINITY; d[0][1] = -INFINITY; }
                            s[2 * u][0] = first0 ? d[0][0] : d[1][0]; s[2 * u][1] = first1 ? d[0][1] : d[1][1];
                            s[2 * u + 1][0] = first0 ? d[1][2] : d[2][2]; s[2 * u + 1][1] = first1 ? d[1][3] : d[2][3];
                        }
                        mbar_spin(bars + B_GFULL + 16, gph);
#pragma unroll
                        for (int u = 0; u < 4; u++) { ldsm_x4_t(vf[2 * u], pl + 2 * GST_BYTES + u * 2048 + a16); ldsm_x4_t(vf[2 * u + 1], pl + 2 * GST_BYTES + u * 2048 + (a16 ^ 32)); }
                        ldsm_x4_t(vf[8], pl + 2 * GST_BYTES + 8192 + a8);
                        __syncwarp();
                        release_stage(2);
                        float x[8];
#pragma unroll
                        for (int j = 0; j < 8; j++) x[j] = fmaxf(s[j][0], s[j][1]);
#pragma unroll
                        for (int o = 1; o < 4; o *= 2)
#pragma unroll
                            for (int j = 0; j < 8; j++) x[j] = fmaxf(x[j], __shfl_xor_sync(0xffffffffu, x[j], o));
#pragma unroll
                        for (int j = 0; j < 8; j++) {
                            const float n = x[j] * -LOC_SCALE;
                            s[j][0] = ex2(fmaf(s[j][0], LOC_SCALE, n)); s[j][1] = ex2(fmaf(s[j][1], LOC_SCALE, n));
                            x[j] = s[j][0] + s[j][1];
                        }
#pragma unroll
                        for (int o = 1; o < 4; o *= 2)
#pragma unroll
                            for (int j = 0; j < 8; j++) x[j] += __shfl_xor_sync(0xffffffffu, x[j], o);
                        mbar_spin(bars + B_GFULL + 24, gph);
                        release_stage(3);
                        it = take_item();
                        uint32_t ob[4][8];
#pragma unroll
                        for (int u = 0; u < 4; u++) {
                            const float r0 = rcp(x[2 * u]), r1 = rcp(x[2 * u + 1]), f0 = fmaf(-w[2 * u], r0, r0), f1 = fmaf(-w[2 * u + 1], r1, r1);
                            const uint32_t p0 = pack_bf16(s[2 * u][0] * f0, s[2 * u][1] * f0), p1 = pack_bf16(s[2 * u + 1][0] * f1, s[2 * u + 1][1] * f1);
                            const uint32_t pa[4] = {p0 & fmask, 0, p0 & ~fmask, p1 & fmask};
#pragma unroll
                            for (int c = 0; c < 4; c++) {
                                float ol[4];
                                mma_k16_init(ol, pa, vf[2 * u + (c >> 1)][2 * (c & 1)], vf[2 * u + (c >> 1)][2 * (c & 1) + 1]);
                                mma_k8(ol, 0, p1 & ~fmask, u < 3 ? vf[2 * u + 2 + (c >> 1)][2 * (c & 1)] : vf[8][c]);
                                ob[u][2 * c] = pack_bf16(ol[0], ol[1]);
                                ob[u][2 * c + 1] = pack_bf16(ol[2], ol[3]);
                            }
                        }
                        stage_acquire(0); stage_acquire(1);
#pragma unroll
                        for (int u = 0; u < 4; u++) {
                            stmatrix_x4(stg + par * 8192 + u * 2048 + a16, ob[u][0], ob[u][1], ob[u][2], ob[u][3]);
                            stmatrix_x4(stg + par * 8192 + u * 2048 + (a16 ^ 32), ob[u][4], ob[u][5], ob[u][6], ob[u][7]);
                        }
                        publish_pair();
                        bar_sync(4, 256);
                        gph ^= 1;
                        continue;
                    }
                    mbar_spin(bars + B_GFULL, gph);
                    bool more;
                    do {
                        wgmma_fence();
                        wgmma_ss_n256_tb_init(acc, full_desc(dA), full_desc(dB));
#pragma unroll
                        for (int kk = 1; kk < 4; kk++) wgmma_ss_n256_tb(acc, full_desc(dA) + 2 * kk, full_desc(dB) + 128 * kk, 1);
                        wgmma_commit();
                        const int type = item_type(it), nk = type == T_K || type == T_V ? 8 : 16;
                        int k = 1;
                        do {
                            if (pending) {
                                const int kf = k - 1 - wg;
                                if (kf == 0) { scale_q(0); stage_chunk(0, pk); }
                                else if (kf == 1) { scale_q(16); stage_chunk(1, pk + 16); }
                                else if (kf == 3) { scale_q(32); stage_chunk(0, pk + 32); }
                                else if (kf == 4) { scale_q(48); stage_chunk(1, pk + 48); }
                            }
                            if (k == nk - 1) it = take_item();
                            gemm_step(acc, dB, k, item_type(it) > T_LOCAL);
                        } while (k < nk);
                        held = type;
                        more = item_type(it) < T_LOCAL;
                        if (more) mbar_spin(bars + B_GFULL, gph);
                        wgmma_wait<0>();
                        fence_regs(acc);
                        release_stage(3);
#pragma unroll
                        for (int j = 0; j < 64; j++) pk[j] = pack_bf16(acc[2 * j], acc[2 * j + 1]);
                        pending = true;
                    } while (more);
                } while (item_type(it) <= T_LOCAL);
                issued = item_type(it) == T_ATTN && (it & ITEM_READY);
                first_scores(issued);
                stage_acquire(0); stage_acquire(1);
                mbar_spin(bars + B_GEMPTY + 8, gph ^ 1);
                write_blocks(std::integral_constant<int, 8>(), 0, pk);
                write_blocks(std::integral_constant<int, 8>(), 32768 - SM_STAGING, pk + 32);
                publish_pair();
                release(B_ALT + 8 * wg);
                bar_arrive(2 - wg, 256);
                wgmma_wait<0>();
                fence_regs(s);
                if (item_type(it) == T_END) it = take_item();
            }
            while (item_type(it) == T_ATTN) {
                if (!issued) { first_scores(true); bar_arrive(2 - wg, 256); wgmma_wait<0>(); fence_regs(s); }
                issued = false;
                float o[64];
                uint32_t pa[32], pb[32];
                float n0 = 0.f, n1 = 0.f;
                int shifted = 0;
                float l0 = 0.f, l1 = 0.f, f0 = 0.f, f1 = 0.f, g0, g1;
                uint32_t has_pv = 0;
                int first = 0;
                int pending = 0;
                const uint32_t dV = make_desc(sb + SM_KV, 16384);
                const uint32_t lane_off = bars_lane - bars + B_AEMPTY - B_AFULL;
                int cur = it;
                uint32_t qoff = (ti & 1) * 2048;
                const int row = wg * 64 + wq * 16 + (lane >> 2);
                const float thr = (row & 63) - (lane & 3) * 2;
                int diag = item_row(cur) == 0 || !item_asc(cur);
                int peek = -1;
                auto kv_release = [&](uint32_t n) { mbar_arrive_cluster_if(lane < 2, bars_lane + B_AEMPTY + 16 + 8 * (n & 3)); };
                struct Slot { uint32_t bar, par, off; } slot[4];
#pragma unroll
                for (uint32_t i = 0; i < 4; i++) {
                    const uint32_t n = kvn + 1 + (i ^ 2);
                    slot[i].bar = bars + B_AFULL + 16 + 8 * (n & 3); slot[i].par = (n >> 2) & 1; slot[i].off = (n & 3) * 2048;
                }
                kvn++;
                auto next_gate = [&]() {
                    g0 = lds_f32(bars + SM_GATE + (ti & 1) * 512 + 4 * row); g1 = lds_f32(bars + SM_GATE + (ti & 1) * 512 + 4 * row + 32);
                    ti++;
                };
                next_gate();
                auto scale_o = [&]() {
#pragma unroll
                    for (int j = 0; j < 16; j++) { o[4 * j] *= f0; o[4 * j + 1] *= f0; o[4 * j + 2] *= f1; o[4 * j + 3] *= f1; }
                };
                auto pack_o = [&](uint32_t (&v)[32]) {
#pragma unroll
                    for (int j = 0; j < 32; j++) v[j] = pack_bf16(o[2 * j], o[2 * j + 1]);
                };
                auto scales = [&]() { f0 = g0 * rcp(quad_sum(l0)); f1 = g1 * rcp(quad_sum(l1)); };
                auto issue = [&](auto even, uint32_t (&pin)[32], uint32_t (&pout)[32], bool fresh, bool last) {
                    constexpr bool EVEN = decltype(even)::value;
                    Slot& sk = slot[EVEN ? 0 : 2];
                    Slot& sv = slot[EVEN ? 1 : 3];
                    kvn += 2;
                    mbar_spin(sk.bar, sk.par);
                    bar_sync(1 + wg, 256);
                    qk_gemm(s, dA + qoff, dK + sk.off);
                    if (EVEN && fresh) {
                        scales();
                        next_gate();
                        n0 = 0.f; n1 = 0.f; l0 = 0.f; l1 = 0.f;
                        shifted = 0;
                        stage_acquire(0); stage_acquire(1);
                    }
                    if (!EVEN && pending) {
                        pack_o(pout);
                        write_blocks(std::integral_constant<int, 4>(), 0, pout);
                    }
                    if (last)
                        asm volatile("{\n.reg .pred P, Q;\n"
                                     "mbarrier.test_wait.parity.shared::cta.b64 Q, [%1], %2;\n"
                                     "mbarrier.test_wait.parity.shared::cta.b64 P, [%3], %4;\n"
                                     "ld.shared.u32 %0, [%5];\n"
                                     "@!Q or.b32 %0, %0, 0x10000;\n"
                                     "@!P mov.u32 %0, -1;\n}\n"
                                     : "=r"(peek) : "r"(bars + B_AFULL + 8 * (ti & 1)), "r"((ti >> 1) & 1), "r"(bars + B_IFULL + 8 * (qn % QDEPTH)),
                                       "r"((qn / QDEPTH) & 1), "r"(bars + SM_QUEUE + 4 * (qn % QDEPTH)) : "memory");
                    diag = item_asc(cur) ? last : fresh;
                    asm volatile("" : "+r"(diag));
                    mbar_spin(sv.bar, sv.par);
                    pv_gemm(o, pin, dV + sv.off, EVEN || !first);
                    bar_arrive(2 - wg, 256);
                    if (!EVEN && pending) {
                        write_blocks(std::integral_constant<int, 4>(), 8192, pout + 16);
                        publish_pair();
                    }
                    sk.par ^= 1; sv.par ^= 1;
                    wgmma_wait<1>();
                    fence_regs(s);
                    mbar_arrive_cluster_if(lane < 2, sk.bar + lane_off);
                    mbar_arrive_if(lane == 0 && last, bars + B_AEMPTY + 8 * ((ti - 1) & 1));
                };
                auto softmax = [&](auto even, uint32_t (&pin)[32], uint32_t (&pout)[32], bool fresh) {
                    constexpr bool EVEN = decltype(even)::value;
                    Slot& sv = slot[EVEN ? 1 : 3];
                    float r0, r1, x0 = n0, x1 = n1;
#pragma unroll 1
                    for (int mask = diag, redone = 0;; mask = 0, redone = 1) {
                        if (mask | shifted) {
                            if (mask) causal_mask(s, thr, wg);
                            if (shifted) shift_rows(s, x0, x1);
                        }
                        exp_pack(pout, s, r0, r1);
                        if (!__any_sync(0xffffffffu, fmaxf(r0, r1) >= SUM_LIMIT || (EVEN && fresh && !(lane & 3) && !(fminf(s[0], s[2]) >= -REF_RANGE))) || redone) break;
                        row_max(s, x0, x1);
                        if (!(EVEN && fresh)) { x0 = fmaxf(x0, 0.f); x1 = fmaxf(x1, 0.f); }
                        float a0 = ex2(-x0), a1 = ex2(-x1);
                        n0 += x0; n1 += x1;
                        shifted = 1;
                        if (EVEN && fresh) { a0 = 1.f; a1 = 1.f; }
                        l0 *= a0; l1 *= a1;
                        wgmma_wait<0>();
                        fence_regs(o);
#pragma unroll
                        for (int q = 0; q < 16; q++) { o[4 * q] *= a0; o[4 * q + 1] *= a0; o[4 * q + 2] *= a1; o[4 * q + 3] *= a1; }
                    }
                    l0 += r0; l1 += r1;
                    wgmma_wait<0>();
                    fence_regs(o);
                    fence_regs(pin);
                    mbar_arrive_cluster_if(lane < 2, sv.bar + lane_off);
                };
                auto copy_p = [&]() {
#pragma unroll
                    for (int j = 0; j < 32; j++) pa[j] = __float_as_uint(__uint_as_float(pb[j]) + __uint_as_float(prm.zero));
                };
                int rem = 0;
                mbar_arrive_if(lane == 0 && item_row(cur) == 0, bars + B_AEMPTY + 8 * ((ti - 1) & 1));
                zero_regs(pa);
                wgmma_fence();
                wgmma_ss_n128_init(o, full_desc(dA), full_desc(dK));
                wgmma_commit();
                while (true) {
                    const bool fresh = rem == 0;
                    softmax(std::true_type(), pa, pb, fresh);
                    first = fresh;
                    if (fresh) {
                        pending = has_pv; has_pv = 1;
                        if (pending) scale_o();
                        rem = item_row(cur) + 1;
                    }
                    if (--rem == 0) {
                        copy_p();
                        const Slot t0 = slot[0], t1 = slot[1];
                        slot[0] = slot[2]; slot[1] = slot[3]; slot[2] = t0; slot[3] = t1;
                    } else {
                        issue(std::false_type(), pb, pa, false, rem == 1);
                        softmax(std::false_type(), pb, pa, false);
                        pending = 0; first = 0;
                        rem--;
                    }
                    if (rem == 0) {
                        const int seen = peek;
                        if (seen >= 0) {
                            mbar_arrive_cluster_if(lane == 0, bars0 + B_IEMPTY + 8 * (qn % QDEPTH));
                            qn++;
                            it = seen & 0xffff;
                        } else {
                            it = take_item();
                        }
                        if (item_row(cur) < 2 || item_type(it) != T_ATTN) break;
                        if (seen & 0x10000) mbar_spin(bars + B_AFULL + 8 * (ti & 1), (ti >> 1) & 1);
                        cur = it;
                        qoff = (ti & 1) * 2048;
                    }
                    issue(std::true_type(), pa, pb, rem == 0, rem ? rem == 1 : item_row(cur) == 0);
                }
                const uint32_t skip = item_asc(cur) & ~item_row(cur) & 1;
                kvn += skip;
                const bool end = item_type(it) == T_END;
#pragma unroll 1
                for (int pass = pending ? 0 : 1; pass < 2; pass++) {
                    if (pass) {
                        kv_wait(kvn);
                        pv_gemm(o, pa, dV + (kvn & 3) * 2048, !first);
                        scales();
                        stage_acquire(0); stage_acquire(1);
                        if (end) it = take_item();
                        wgmma_wait<0>();
                        fence_regs(o);
                        kv_release(kvn);
                        kvn += 1 + skip;
                        scale_o();
                    }
                    pack_o(pb);
                    write_blocks(std::integral_constant<int, 8>(), 0, pb);
                    publish_pair();
                }
            }
        }
        if (item_type(it) == T_OUT) {
            float acc[128];
            const uint32_t dB = make_desc(sb + 16384, 8192);
            mbar_spin(bars + B_GFULL, gph);
            wgmma_fence();
            wgmma_ss_n256_tb_init(acc, full_desc(dA), full_desc(dB));
#pragma unroll
            for (int kk = 1; kk < 4; kk++) wgmma_ss_n256_tb(acc, full_desc(dA) + 2 * kk, full_desc(dB) + 128 * kk, 1);
            wgmma_commit();
            uint32_t ln;
            asm volatile("mov.u32 %0, %%laneid;" : "=r"(ln));
            char* const mine = (char*)prm.out + (uint32_t)((item_row(it) * 128 + wg * 64 + wq * 16 + (ln >> 4)) * 2048 + item_col(it) * 256 + (ln & 15) * 16);
            int k = 1, nk = 80;
            do {
                if ((uint32_t)(k - (K_MEET - 12)) < 8) *(uint4*)(mine + (uint32_t)(k - (K_MEET - 12)) * 4096) = make_uint4(0, 0, 0, 0);
                __syncwarp();
                if (k == K_SPLIT) nk = take_item() & 127;
                gemm_step(acc, dB, k, false);
            } while (k < nk);
            float lo[64];
            auto triple = [&](auto first) {
                const uint32_t s0 = k & 3, s1 = (k + 1) & 3, o0 = s0 * (GST_BYTES >> 4), o1 = s1 * (GST_BYTES >> 4);
                wgmma_wait<0>();
                mbar_arrive_cluster_if(ln < (decltype(first)::value ? 2 : 4), bars_lane + B_GEMPTY + 8 * ((k - 1 - (ln >> 1)) & 3));
                mbar_spin(bars + B_GFULL + 8 * s0, gph);
                gph ^= s0 == 3;
                wgmma_fence();
#pragma unroll
                for (int kk = 0; kk < 4; kk++) {
                    if (decltype(first)::value && kk == 0) wgmma_ss_n128_tb_init(lo, full_desc(dA + o0), full_desc(dB + o0));
                    else wgmma_ss_n128_tb(lo, full_desc(dA + o0) + 2 * kk, full_desc(dB + o0) + 128 * kk, 1);
                }
                mbar_spin(bars + B_GFULL + 8 * s1, gph);
                gph ^= s1 == 3;
                wgmma_fence();
#pragma unroll
                for (int kk = 0; kk < 4; kk++) wgmma_ss_n128_tb(lo, full_desc(dA + o0 + 2048) + 2 * kk, full_desc(dB + o1 + 1024) + 128 * kk, 1);
#pragma unroll
                for (int kk = 0; kk < 4; kk++) wgmma_ss_n128_tb(lo, full_desc(dA + o1) + 2 * kk, full_desc(dB + o1) + 128 * kk, 1);
                wgmma_commit();
                k += 2;
            };
            triple(std::true_type());
            fence_regs(acc);
            uint32_t pk[32];
#pragma unroll
            for (int j = 0; j < 32; j++) pk[j] = pack_bf16(acc[64 + 2 * j], acc[65 + 2 * j]);
            stage_acquire(0); stage_acquire(1);
            write_blocks(std::integral_constant<int, 8>(), 0, pk);
            publish_pair();
            triple(std::false_type());
            stage_acquire(0); stage_acquire(1);
            wgmma_wait<0>();
            fence_regs(lo);
            mbar_arrive_cluster_if(ln < 4, bars_lane + B_GEMPTY + 8 * ((k - 1 - (ln >> 1)) & 3));
#pragma unroll
            for (int b = 0; b < 2; b++) {
#pragma unroll
                for (int j = 16 * b; j < 16 * b + 16; j++) pk[j] = pack_bf16(acc[2 * j] + lo[2 * j], acc[2 * j + 1] + lo[2 * j + 1]);
                write_blocks(std::integral_constant<int, 4>(), b * 8192, pk + 16 * b);
                stage_publish(b);
            }
        }
    }
}

typedef CUresult (*EncodeFn)(CUtensorMap*, CUtensorMapDataType, cuuint32_t, void*, const cuuint64_t*, const cuuint64_t*,
                             const cuuint32_t*, const cuuint32_t*, CUtensorMapInterleave, CUtensorMapSwizzle,
                             CUtensorMapL2promotion, CUtensorMapFloatOOBfill);

void encode3(EncodeFn fn, CUtensorMap* m, const void* ptr, uint64_t d0, uint64_t d1, uint64_t d2, uint64_t s1, uint64_t s2,
             uint32_t b0, uint32_t b1, uint32_t b2) {
    cuuint64_t dims[3] = {d0, d1, d2};
    cuuint64_t strides[2] = {s1, s2};
    cuuint32_t box[3] = {b0, b1, b2};
    cuuint32_t es[3] = {1, 1, 1};
    fn(m, CU_TENSOR_MAP_DATA_TYPE_BFLOAT16, 3, const_cast<void*>(ptr), dims, strides, box, es, CU_TENSOR_MAP_INTERLEAVE_NONE,
       CU_TENSOR_MAP_SWIZZLE_128B, CU_TENSOR_MAP_L2_PROMOTION_NONE, CU_TENSOR_MAP_FLOAT_OOB_FILL_NONE);
}
void map_act(EncodeFn fn, CUtensorMap* m, const void* p, int rows, int cols, int box_rows) {
    encode3(fn, m, p, cols, rows, 1, (uint64_t)cols * 2, (uint64_t)cols * rows * 2, 64, box_rows, 1);
}
void map_wgt(EncodeFn fn, CUtensorMap* m, const void* p, int K, int N) {
    encode3(fn, m, p, 64, K, N / 64, (uint64_t)N * 2, 128, 64, 64, 2);
}

void build_schedule(Params& p) {
    int n = 0;
    auto add = [&](int type, int col, int row) { p.items[n++] = (uint16_t)(type << 13 | col << 4 | row); };
    int beta = 26, tail = 32, late = 6, early = 4, epos = 60;
    int order[16] = {6, 7, 8, 9, 10, 11, 12, 13, 14, 15, 5, 4, 3, 2, 1, 0};
    const char* plans = "xxxxxc,xxxlcccc,xxlxlxxc,xxlxlxxc,xxcccccxc,xccclxlccc,xccclxxc,xxcccccc";
    const char* pos[8];
    int len[8] = {}, start[8] = {};
    for (int s = 0; s < 8; s++) { pos[s] = plans; while (*plans && *plans++ != ',') {} }
    for (int i = 0; i < 160; i++) p.plan[i / 16][i % 16] = T_END << 13;
    for (int nx = 0, nc = 3, nl = 0; nx + nc + nl < 28 + 32 + 8;) {
        int s = -1;
        for (int i = 0; i < 8; i++) if (*pos[i] > ',' && (s < 0 || start[i] < start[s])) s = i;
        const char kind = *pos[s]++;
        int it;
        if (kind == 'x') { it = nx < 12 ? T_B << 13 | (nx % 3 * 4 + nx / 3) << 4 : T_Q << 13 | (nx - 12) << 4; nx++; }
        else if (kind == 'c') { it = (T_K + (nc & 1)) << 13 | nc / 2 << 4; nc++; }
        else { it = T_LOCAL << 13 | nl / 2 << 4 | (nl & 1); nl++; }
        p.plan[s][len[s]++] = (uint16_t)it;
        start[s] += kind == 'x' ? 48 : kind == 'c' ? 24 : 8;
    }
    for (int i = 0; i < 24; i++) p.plan[8 + i / 12][i % 12] = (uint16_t)((T_K + (i % 3 & 1)) << 13 | i % 3 / 2 << 4 | i / 3);
    const int a0 = n;
    for (int key = 0; key < 4000; key++)
        for (int r = 0; r < 32; r++)
            for (int j = 7; j >= 0; j--)
                if ((j ? (7 - j) * 40 + r * beta : 3999) == key) add(T_ATTN, 2 * order[r >> 1] + (r & 1), j);
    int t0 = n;
    for (int work = 0; work < 32 * 136 * tail / 100;) work += 4 * (p.items[--t0] & 15) + 3;
    for (int i = t0 + 1; i < n; i++)
        for (int j = i; j > t0 && (p.items[j] & 15) > (p.items[j - 1] & 15); j--) { const uint16_t t = p.items[j]; p.items[j] = p.items[j - 1]; p.items[j - 1] = t; }
    for (int r = early - 1; r >= 0; r--) {
        const uint16_t t = p.items[n - 32 + early - 1];
        for (int j = n - 32 + early - 1; j > n - epos; j--) p.items[j] = p.items[j - 1];
        p.items[n - epos] = t;
    }
    for (int moved = 0; moved < 2 && late >= 0; moved++)
        for (int i = a0; i < n; i++)
            if (p.items[i] == (T_ATTN << 13 | (2 * order[15] + moved) << 4 | late)) {
                for (int j = i; j + 1 < n; j++) p.items[j] = p.items[j + 1];
                p.items[n - 1] = (uint16_t)(T_ATTN << 13 | (2 * order[15] + moved) << 4 | late);
                break;
            }
    for (int s = 0, lo = 0, hi = WIDE - 1; s < 80; s++) {
        const int r = s / 2, g = r < 8 ? 32 + r : 2 * order[r / 2 - 4] + (r & 1);
        p.ostep[s >= WIDE ? s : r & 1 ? hi-- : lo++] = (uint8_t)(2 * g + (s & 1));
    }
}

void build_params(Params& p, void* const* d_in, void* d_out) {
    void* fnp = nullptr;
    cudaDriverEntryPointQueryResult qr;
    cudaGetDriverEntryPoint("cuTensorMapEncodeTiled", &fnp, cudaEnableDefault, &qr);
    EncodeFn fn = (EncodeFn)fnp;
    void* scr = nullptr;
    cudaGetSymbolAddress(&scr, g_scr);
    map_act(fn, &p.m[M_X], d_in[0], SEQ, 1024, 128);
    map_act(fn, &p.m[M_C], d_in[1], SEQ, 512, 128);
    map_wgt(fn, &p.m[M_WQ], d_in[2], 1024, 4096);
    map_wgt(fn, &p.m[M_WUK], d_in[3], 512, 4096);
    map_wgt(fn, &p.m[M_WUV], d_in[4], 512, 4096);
    map_wgt(fn, &p.m[M_WO], d_in[5], 4096, 1024);
    map_wgt(fn, &p.m[M_WQKV], d_in[7], 1024, 3072);
    map_wgt(fn, &p.m[M_WOB], d_in[8], 1024, 1024);
    encode3(fn, &p.m[M_SCR_LD], scr, 128, SEQ, G_TOTAL, 256, (uint64_t)SEQ * 256, 64, 128, 1);
    encode3(fn, &p.m[M_SCR_LOC], scr, 256, SEQ / 2, G_TOTAL, 512, (uint64_t)SEQ * 256, 64, 72, 1);
    encode3(fn, &p.m[M_SCR_LOQ], scr, 256, SEQ / 2, G_TOTAL, 512, (uint64_t)SEQ * 256, 64, 64, 1);
    encode3(fn, &p.m[M_SCR_ST], scr, 128, SEQ, G_TOTAL, 256, (uint64_t)SEQ * 256, 64, 64, 1);
    map_act(fn, &p.m[M_OUT], d_out, SEQ, 1024, 64);
    p.x = (const __nv_bfloat16*)d_in[0];
    p.gate_w = (const __nv_bfloat16*)d_in[9];
    p.zero = 0;
    p.wo = (const char*)d_in[5];
    p.out = (__nv_bfloat16*)d_out;
    build_schedule(p);
}

}

extern "C" void kernel_launch(void* const* d_in, const int* in_sizes, int n_in, void* d_out, int out_size) {
    (void)in_sizes; (void)n_in; (void)out_size;
    Params p;
    build_params(p, d_in, d_out);
    cudaFuncSetAttribute(fused_kernel, cudaFuncAttributeMaxDynamicSharedMemorySize, SM_TOTAL);
    fused_kernel<<<NCTA, 384, SM_TOTAL>>>(p);
}
```

```cpp
#include <cuda_runtime.h>
#include <cuda_bf16.h>
#include <cuda.h>
#include <stddef.h>
#include <stdint.h>
#include <type_traits>

namespace {

constexpr int SEQ = 2048;
constexpr int G_Q = 0, G_K = 32, G_V = 64, G_B = 96, G_CTX = G_Q, G_LOC = G_B, G_TOTAL = 120;

__device__ __align__(1024) __nv_bfloat16 g_scr[(size_t)G_TOTAL * SEQ * 128];
__device__ __align__(128) float g_gate[SEQ];

__device__ __forceinline__ uint32_t smem_u32(const void* p) { return (uint32_t)__cvta_generic_to_shared(p); }
__device__ __forceinline__ bool elect_one() {
    uint32_t p;
    asm volatile("{\n.reg .pred P;\nelect.sync _|P, 0xffffffff;\nselp.u32 %0, 1, 0, P;\n}\n" : "=r"(p));
    return p != 0;
}
__device__ __forceinline__ void mbar_init(uint32_t bar, uint32_t count) {
    asm volatile("mbarrier.init.shared::cta.b64 [%0], %1;" :: "r"(bar), "r"(count) : "memory");
}
__device__ __forceinline__ uint32_t cluster_rank() { uint32_t r; asm("mov.u32 %0, %%cluster_ctarank;" : "=r"(r)); return r; }
__device__ __forceinline__ uint32_t map_cta(uint32_t addr, uint32_t cta) {
    uint32_t r; asm("mapa.shared::cluster.u32 %0, %1, %2;" : "=r"(r) : "r"(addr), "r"(cta)); return r;
}
__device__ __forceinline__ void mbar_arrive_cluster_if(bool pred, uint32_t cluster_bar) {
    asm volatile("{\n.reg .pred P;\nsetp.ne.u32 P, %1, 0;\n@P mbarrier.arrive.shared::cluster.b64 _, [%0];\n}\n"
                 :: "r"(cluster_bar), "r"((uint32_t)pred) : "memory");
}
__device__ __forceinline__ void mbar_arrive_cluster_n_if(bool pred, uint32_t cluster_bar, uint32_t count) {
    asm volatile("{\n.reg .pred P;\nsetp.ne.u32 P, %1, 0;\n@P mbarrier.arrive.shared::cluster.b64 _, [%0], %2;\n}\n"
                 :: "r"(cluster_bar), "r"((uint32_t)pred), "r"(count) : "memory");
}
__device__ __forceinline__ void mbar_arrive_if(bool pred, uint32_t bar) {
    asm volatile("{\n.reg .pred P;\nsetp.ne.u32 P, %1, 0;\n@P mbarrier.arrive.shared::cta.b64 _, [%0];\n}\n"
                 :: "r"(bar), "r"((uint32_t)pred) : "memory");
}
__device__ __forceinline__ bool mbar_test(uint32_t bar, uint32_t parity) {
    uint32_t ok;
    asm volatile("{\n.reg .pred P;\nmbarrier.test_wait.parity.shared::cta.b64 P, [%1], %2;\nselp.u32 %0, 1, 0, P;\n}\n"
                 : "=r"(ok) : "r"(bar), "r"(parity) : "memory");
    return ok != 0;
}
__device__ __forceinline__ void mbar_wait(uint32_t bar, uint32_t parity) {
    asm volatile("{\n.reg .pred P;\n.reg .u32 c;\n"
                 "mov.u32 c, 0;\n"
                 "SPIN:\n"
                 "mbarrier.try_wait.parity.shared::cta.b64 P, [%0], %1;\n"
                 "@P bra DONE;\n"
                 "add.u32 c, c, 1;\n"
                 "setp.lt.u32 P, c, 4194304;\n"
                 "@P bra SPIN;\n"
                 "trap;\n"
                 "DONE:\n}\n" :: "r"(bar), "r"(parity) : "memory");
}
__device__ __forceinline__ void mbar_spin(uint32_t bar, uint32_t parity) {
    asm volatile("{\n.reg .pred P;\n"
                 "SPIN:\n"
                 "mbarrier.try_wait.parity.shared::cta.b64 P, [%0], %1;\n"
                 "@!P bra SPIN;\n}\n" :: "r"(bar), "r"(parity) : "memory");
}
__device__ __forceinline__ void bar_sync(int id, int n) { asm volatile("bar.sync %0, %1;" :: "r"(id), "r"(n) : "memory"); }
__device__ __forceinline__ void bar_arrive(int id, int n) { asm volatile("bar.arrive %0, %1;" :: "r"(id), "r"(n) : "memory"); }
__device__ __forceinline__ void fence_proxy_async_smem() { asm volatile("fence.proxy.async.shared::cta;" ::: "memory"); }
__device__ __forceinline__ void warp_expect_tx(uint32_t bar, uint32_t bytes) {
    asm volatile("{\n.reg .pred P;\nelect.sync _|P, 0xffffffff;\n@P mbarrier.arrive.expect_tx.shared::cta.b64 _, [%0], %1;\n}\n"
                 :: "r"(bar), "r"(bytes) : "memory");
}
constexpr uint64_t EVICT_FIRST = 0x12F0000000000000ull;
__device__ __forceinline__ void warp_tma_load(uint32_t dst, const CUtensorMap* map, uint32_t bar, int c0, int c1, int c2, bool stream) {
    if (stream)
        asm volatile("{\n.reg .pred P;\nelect.sync _|P, 0xffffffff;\n"
                     "@P cp.async.bulk.tensor.3d.shared::cluster.global.mbarrier::complete_tx::bytes.L2::cache_hint"
                     " [%0], [%1, {%3, %4, %5}], [%2], %6;\n}\n"
                     :: "r"(dst), "l"(map), "r"(bar), "r"(c0), "r"(c1), "r"(c2), "l"(EVICT_FIRST) : "memory");
    else
        asm volatile("{\n.reg .pred P;\nelect.sync _|P, 0xffffffff;\n"
                     "@P cp.async.bulk.tensor.3d.shared::cluster.global.mbarrier::complete_tx::bytes [%0], [%1, {%3, %4, %5}], [%2];\n}\n"
                     :: "r"(dst), "l"(map), "r"(bar), "r"(c0), "r"(c1), "r"(c2) : "memory");
}
__device__ __forceinline__ void warp_tma_load_pair(uint32_t dst, const CUtensorMap* map, uint32_t bar, int c0, int c1, int c2, bool stream) {
    if (stream)
        asm volatile("{\n.reg .pred P;\nelect.sync _|P, 0xffffffff;\n"
                     "@P cp.async.bulk.tensor.3d.shared::cluster.global.mbarrier::complete_tx::bytes.multicast::cluster.L2::cache_hint"
                     " [%0], [%1, {%3, %4, %5}], [%2], %6, %7;\n}\n"
                     :: "r"(dst), "l"(map), "r"(bar), "r"(c0), "r"(c1), "r"(c2), "h"((uint16_t)3), "l"(EVICT_FIRST) : "memory");
    else
        asm volatile("{\n.reg .pred P;\nelect.sync _|P, 0xffffffff;\n"
                     "@P cp.async.bulk.tensor.3d.shared::cluster.global.mbarrier::complete_tx::bytes.multicast::cluster"
                     " [%0], [%1, {%3, %4, %5}], [%2], %6;\n}\n"
                     :: "r"(dst), "l"(map), "r"(bar), "r"(c0), "r"(c1), "r"(c2), "h"((uint16_t)3) : "memory");
}
__device__ __forceinline__ void warp_bulk_load(uint32_t dst, const void* src, uint32_t bytes, uint32_t bar) {
    asm volatile("{\n.reg .pred P;\nelect.sync _|P, 0xffffffff;\n"
                 "@P cp.async.bulk.shared::cluster.global.mbarrier::complete_tx::bytes [%0], [%1], %2, [%3];\n}\n"
                 :: "r"(dst), "l"(src), "r"(bytes), "r"(bar) : "memory");
}
__device__ __forceinline__ void warp_tma_store(const CUtensorMap* map, uint32_t src, int c0, int c1, int c2, bool stream) {
    if (stream)
        asm volatile("{\n.reg .pred P;\nelect.sync _|P, 0xffffffff;\n"
                     "@P cp.async.bulk.tensor.3d.global.shared::cta.bulk_group.L2::cache_hint [%0, {%2, %3, %4}], [%1], %5;\n}\n"
                     :: "l"(map), "r"(src), "r"(c0), "r"(c1), "r"(c2), "l"(EVICT_FIRST) : "memory");
    else
        asm volatile("{\n.reg .pred P;\nelect.sync _|P, 0xffffffff;\n"
                     "@P cp.async.bulk.tensor.3d.global.shared::cta.bulk_group [%0, {%2, %3, %4}], [%1];\n}\n"
                     :: "l"(map), "r"(src), "r"(c0), "r"(c1), "r"(c2) : "memory");
}
__device__ __forceinline__ void warp_tma_add(const CUtensorMap* map, uint32_t src, int c0, int c1, int c2) {
    asm volatile("{\n.reg .pred P;\nelect.sync _|P, 0xffffffff;\n"
                 "@P cp.reduce.async.bulk.tensor.3d.global.shared::cta.add.tile.bulk_group [%0, {%2, %3, %4}], [%1];\n}\n"
                 :: "l"(map), "r"(src), "r"(c0), "r"(c1), "r"(c2) : "memory");
}
__device__ __forceinline__ void warp_bulk_store(void* dst, uint32_t src, uint32_t bytes) {
    asm volatile("{\n.reg .pred P;\nelect.sync _|P, 0xffffffff;\n"
                 "@P cp.async.bulk.global.shared::cta.bulk_group [%0], [%1], %2;\n}\n" :: "l"(dst), "r"(src), "r"(bytes) : "memory");
}
__device__ __forceinline__ void warp_prefetch(const void* src, uint32_t bytes) {
    asm volatile("{\n.reg .pred P;\nelect.sync _|P, 0xffffffff;\n@P cp.async.bulk.prefetch.L2.global [%0], %1;\n}\n" :: "l"(src), "r"(bytes) : "memory");
}
__device__ __forceinline__ void bulk_commit() { asm volatile("cp.async.bulk.commit_group;" ::: "memory"); }
template <int N> __device__ __forceinline__ void bulk_wait_read() { asm volatile("cp.async.bulk.wait_group.read %0;" :: "n"(N) : "memory"); }
template <int N> __device__ __forceinline__ void bulk_wait() { asm volatile("cp.async.bulk.wait_group %0;" :: "n"(N) : "memory"); }
__device__ __forceinline__ void wgmma_fence() { asm volatile("wgmma.fence.sync.aligned;" ::: "memory"); }
__device__ __forceinline__ void wgmma_commit() { asm volatile("wgmma.commit_group.sync.aligned;" ::: "memory"); }
template <int N> __device__ __forceinline__ void wgmma_wait() { asm volatile("wgmma.wait_group.sync.aligned %0;" :: "n"(N) : "memory"); }
template <int N> __device__ __forceinline__ void fence_regs(float (&d)[N]) {
#pragma unroll
    for (int i = 0; i < N; i++) asm volatile("" : "+f"(d[i]) :: "memory");
}
template <int N> __device__ __forceinline__ void fence_regs(uint32_t (&d)[N]) {
#pragma unroll
    for (int i = 0; i < N; i++) asm volatile("" : "+r"(d[i]) :: "memory");
}
template <int N> __device__ __forceinline__ void reg_dec() { asm volatile("setmaxnreg.dec.sync.aligned.u32 %0;" :: "n"(N)); }
template <int N> __device__ __forceinline__ void reg_inc() { asm volatile("setmaxnreg.inc.sync.aligned.u32 %0;" :: "n"(N)); }
__device__ __forceinline__ uint32_t pack_bf16(float lo, float hi) {
    uint32_t r; asm("cvt.rn.bf16x2.f32 %0, %1, %2;" : "=r"(r) : "f"(hi), "f"(lo)); return r;
}
__device__ __forceinline__ void stmatrix_x4(uint32_t addr, uint32_t r0, uint32_t r1, uint32_t r2, uint32_t r3) {
    asm volatile("stmatrix.sync.aligned.m8n8.x4.shared.b16 [%0], {%1, %2, %3, %4};"
                 :: "r"(addr), "r"(r0), "r"(r1), "r"(r2), "r"(r3) : "memory");
}
__device__ __forceinline__ float ex2(float x) { float y; asm("ex2.approx.ftz.f32 %0, %1;" : "=f"(y) : "f"(x)); return y; }

constexpr uint32_t DESC_HI = (1024 >> 4) | (1u << 30);
__device__ __forceinline__ uint32_t make_desc(uint32_t addr, uint32_t lbo) {
    uint32_t lo = ((addr & 0x3FFFF) >> 4) | ((lbo >> 4) << 16);
    asm volatile("" : "+r"(lo));
    return lo;
}
__device__ __forceinline__ uint64_t full_desc(uint32_t lo) {
    uint64_t d; asm("mov.b64 %0, {%1, %2};" : "=l"(d) : "r"(lo), "r"(DESC_HI)); return d;
}

__device__ __forceinline__ void wgmma_ss_n256_tb_init(float (&d)[128], uint64_t da, uint64_t db) {
    asm volatile("{\n.reg .pred p;\n"
        "setp.ne.b32 p, 0, 0;\n"
        "wgmma.mma_async.sync.aligned.m64n256k16.f32.bf16.bf16 "
        "{%0, %1, %2, %3, %4, %5, %6, %7, %8, %9, %10, %11, %12, %13, %14, %15, %16, %17, %18, %19, %20, "
        "%21, %22, %23, %24, %25, %26, %27, %28, %29, %30, %31, %32, %33, %34, %35, %36, %37, %38, %39, %40, "
        "%41, %42, %43, %44, %45, %46, %47, %48, %49, %50, %51, %52, %53, %54, %55, %56, %57, %58, %59, %60, "
        "%61, %62, %63, %64, %65, %66, %67, %68, %69, %70, %71, %72, %73, %74, %75, %76, %77, %78, %79, %80, "
        "%81, %82, %83, %84, %85, %86, %87, %88, %89, %90, %91, %92, %93, %94, %95, %96, %97, %98, %99, "
        "%100, %101, %102, %103, %104, %105, %106, %107, %108, %109, %110, %111, %112, %113, %114, %115, "
        "%116, %117, %118, %119, %120, %121, %122, %123, %124, %125, %126, %127},"
        " %128, %129, p, 1, 1, 0, 1;\n}\n"
        : "=f"(d[0]), "=f"(d[1]), "=f"(d[2]), "=f"(d[3]), "=f"(d[4]), "=f"(d[5]), "=f"(d[6]), "=f"(d[7]),
        "=f"(d[8]), "=f"(d[9]), "=f"(d[10]), "=f"(d[11]), "=f"(d[12]), "=f"(d[13]), "=f"(d[14]), "=f"(d[15]),
        "=f"(d[16]), "=f"(d[17]), "=f"(d[18]), "=f"(d[19]), "=f"(d[20]), "=f"(d[21]), "=f"(d[22]),
        "=f"(d[23]), "=f"(d[24]), "=f"(d[25]), "=f"(d[26]), "=f"(d[27]), "=f"(d[28]), "=f"(d[29]),
        "=f"(d[30]), "=f"(d[31]), "=f"(d[32]), "=f"(d[33]), "=f"(d[34]), "=f"(d[35]), "=f"(d[36]),
        "=f"(d[37]), "=f"(d[38]), "=f"(d[39]), "=f"(d[40]), "=f"(d[41]), "=f"(d[42]), "=f"(d[43]),
        "=f"(d[44]), "=f"(d[45]), "=f"(d[46]), "=f"(d[47]), "=f"(d[48]), "=f"(d[49]), "=f"(d[50]),
        "=f"(d[51]), "=f"(d[52]), "=f"(d[53]), "=f"(d[54]), "=f"(d[55]), "=f"(d[56]), "=f"(d[57]),
        "=f"(d[58]), "=f"(d[59]), "=f"(d[60]), "=f"(d[61]), "=f"(d[62]), "=f"(d[63]), "=f"(d[64]),
        "=f"(d[65]), "=f"(d[66]), "=f"(d[67]), "=f"(d[68]), "=f"(d[69]), "=f"(d[70]), "=f"(d[71]),
        "=f"(d[72]), "=f"(d[73]), "=f"(d[74]), "=f"(d[75]), "=f"(d[76]), "=f"(d[77]), "=f"(d[78]),
        "=f"(d[79]), "=f"(d[80]), "=f"(d[81]), "=f"(d[82]), "=f"(d[83]), "=f"(d[84]), "=f"(d[85]),
        "=f"(d[86]), "=f"(d[87]), "=f"(d[88]), "=f"(d[89]), "=f"(d[90]), "=f"(d[91]), "=f"(d[92]),
        "=f"(d[93]), "=f"(d[94]), "=f"(d[95]), "=f"(d[96]), "=f"(d[97]), "=f"(d[98]), "=f"(d[99]),
        "=f"(d[100]), "=f"(d[101]), "=f"(d[102]), "=f"(d[103]), "=f"(d[104]), "=f"(d[105]), "=f"(d[106]),
        "=f"(d[107]), "=f"(d[108]), "=f"(d[109]), "=f"(d[110]), "=f"(d[111]), "=f"(d[112]), "=f"(d[113]),
        "=f"(d[114]), "=f"(d[115]), "=f"(d[116]), "=f"(d[117]), "=f"(d[118]), "=f"(d[119]), "=f"(d[120]),
        "=f"(d[121]), "=f"(d[122]), "=f"(d[123]), "=f"(d[124]), "=f"(d[125]), "=f"(d[126]), "=f"(d[127])
        : "l"(da), "l"(db));
}
__device__ __forceinline__ void wgmma_ss_n256_tb(float (&d)[128], uint64_t da, uint64_t db, int scale_d) {
    asm volatile("{\n.reg .pred p;\n"
        "setp.ne.b32 p, %130, 0;\n"
        "wgmma.mma_async.sync.aligned.m64n256k16.f32.bf16.bf16 "
        "{%0, %1, %2, %3, %4, %5, %6, %7, %8, %9, %10, %11, %12, %13, %14, %15, %16, %17, %18, %19, %20, "
        "%21, %22, %23, %24, %25, %26, %27, %28, %29, %30, %31, %32, %33, %34, %35, %36, %37, %38, %39, %40, "
        "%41, %42, %43, %44, %45, %46, %47, %48, %49, %50, %51, %52, %53, %54, %55, %56, %57, %58, %59, %60, "
        "%61, %62, %63, %64, %65, %66, %67, %68, %69, %70, %71, %72, %73, %74, %75, %76, %77, %78, %79, %80, "
        "%81, %82, %83, %84, %85, %86, %87, %88, %89, %90, %91, %92, %93, %94, %95, %96, %97, %98, %99, "
        "%100, %101, %102, %103, %104, %105, %106, %107, %108, %109, %110, %111, %112, %113, %114, %115, "
        "%116, %117, %118, %119, %120, %121, %122, %123, %124, %125, %126, %127},"
        " %128, %129, p, 1, 1, 0, 1;\n}\n"
        : "+f"(d[0]), "+f"(d[1]), "+f"(d[2]), "+f"(d[3]), "+f"(d[4]), "+f"(d[5]), "+f"(d[6]), "+f"(d[7]),
        "+f"(d[8]), "+f"(d[9]), "+f"(d[10]), "+f"(d[11]), "+f"(d[12]), "+f"(d[13]), "+f"(d[14]), "+f"(d[15]),
        "+f"(d[16]), "+f"(d[17]), "+f"(d[18]), "+f"(d[19]), "+f"(d[20]), "+f"(d[21]), "+f"(d[22]),
        "+f"(d[23]), "+f"(d[24]), "+f"(d[25]), "+f"(d[26]), "+f"(d[27]), "+f"(d[28]), "+f"(d[29]),
        "+f"(d[30]), "+f"(d[31]), "+f"(d[32]), "+f"(d[33]), "+f"(d[34]), "+f"(d[35]), "+f"(d[36]),
        "+f"(d[37]), "+f"(d[38]), "+f"(d[39]), "+f"(d[40]), "+f"(d[41]), "+f"(d[42]), "+f"(d[43]),
        "+f"(d[44]), "+f"(d[45]), "+f"(d[46]), "+f"(d[47]), "+f"(d[48]), "+f"(d[49]), "+f"(d[50]),
        "+f"(d[51]), "+f"(d[52]), "+f"(d[53]), "+f"(d[54]), "+f"(d[55]), "+f"(d[56]), "+f"(d[57]),
        "+f"(d[58]), "+f"(d[59]), "+f"(d[60]), "+f"(d[61]), "+f"(d[62]), "+f"(d[63]), "+f"(d[64]),
        "+f"(d[65]), "+f"(d[66]), "+f"(d[67]), "+f"(d[68]), "+f"(d[69]), "+f"(d[70]), "+f"(d[71]),
        "+f"(d[72]), "+f"(d[73]), "+f"(d[74]), "+f"(d[75]), "+f"(d[76]), "+f"(d[77]), "+f"(d[78]),
        "+f"(d[79]), "+f"(d[80]), "+f"(d[81]), "+f"(d[82]), "+f"(d[83]), "+f"(d[84]), "+f"(d[85]),
        "+f"(d[86]), "+f"(d[87]), "+f"(d[88]), "+f"(d[89]), "+f"(d[90]), "+f"(d[91]), "+f"(d[92]),
        "+f"(d[93]), "+f"(d[94]), "+f"(d[95]), "+f"(d[96]), "+f"(d[97]), "+f"(d[98]), "+f"(d[99]),
        "+f"(d[100]), "+f"(d[101]), "+f"(d[102]), "+f"(d[103]), "+f"(d[104]), "+f"(d[105]), "+f"(d[106]),
        "+f"(d[107]), "+f"(d[108]), "+f"(d[109]), "+f"(d[110]), "+f"(d[111]), "+f"(d[112]), "+f"(d[113]),
        "+f"(d[114]), "+f"(d[115]), "+f"(d[116]), "+f"(d[117]), "+f"(d[118]), "+f"(d[119]), "+f"(d[120]),
        "+f"(d[121]), "+f"(d[122]), "+f"(d[123]), "+f"(d[124]), "+f"(d[125]), "+f"(d[126]), "+f"(d[127])
        : "l"(da), "l"(db), "r"(scale_d));
}
__device__ __forceinline__ void wgmma_ss_n128_init(float (&d)[64], uint64_t da, uint64_t db) {
    asm volatile("{\n.reg .pred p;\n"
        "setp.ne.b32 p, 0, 0;\n"
        "wgmma.mma_async.sync.aligned.m64n128k16.f32.bf16.bf16 "
        "{%0, %1, %2, %3, %4, %5, %6, %7, %8, %9, %10, %11, %12, %13, %14, %15, %16, %17, %18, %19, %20, "
        "%21, %22, %23, %24, %25, %26, %27, %28, %29, %30, %31, %32, %33, %34, %35, %36, %37, %38, %39, %40, "
        "%41, %42, %43, %44, %45, %46, %47, %48, %49, %50, %51, %52, %53, %54, %55, %56, %57, %58, %59, %60, "
        "%61, %62, %63},"
        " %64, %65, p, 1, 1, 0, 0;\n}\n"
        : "=f"(d[0]), "=f"(d[1]), "=f"(d[2]), "=f"(d[3]), "=f"(d[4]), "=f"(d[5]), "=f"(d[6]), "=f"(d[7]),
        "=f"(d[8]), "=f"(d[9]), "=f"(d[10]), "=f"(d[11]), "=f"(d[12]), "=f"(d[13]), "=f"(d[14]), "=f"(d[15]),
        "=f"(d[16]), "=f"(d[17]), "=f"(d[18]), "=f"(d[19]), "=f"(d[20]), "=f"(d[21]), "=f"(d[22]),
        "=f"(d[23]), "=f"(d[24]), "=f"(d[25]), "=f"(d[26]), "=f"(d[27]), "=f"(d[28]), "=f"(d[29]),
        "=f"(d[30]), "=f"(d[31]), "=f"(d[32]), "=f"(d[33]), "=f"(d[34]), "=f"(d[35]), "=f"(d[36]),
        "=f"(d[37]), "=f"(d[38]), "=f"(d[39]), "=f"(d[40]), "=f"(d[41]), "=f"(d[42]), "=f"(d[43]),
        "=f"(d[44]), "=f"(d[45]), "=f"(d[46]), "=f"(d[47]), "=f"(d[48]), "=f"(d[49]), "=f"(d[50]),
        "=f"(d[51]), "=f"(d[52]), "=f"(d[53]), "=f"(d[54]), "=f"(d[55]), "=f"(d[56]), "=f"(d[57]),
        "=f"(d[58]), "=f"(d[59]), "=f"(d[60]), "=f"(d[61]), "=f"(d[62]), "=f"(d[63])
        : "l"(da), "l"(db));
}
__device__ __forceinline__ void wgmma_ss_n128(float (&d)[64], uint64_t da, uint64_t db, int scale_d) {
    asm volatile("{\n.reg .pred p;\n"
        "setp.ne.b32 p, %66, 0;\n"
        "wgmma.mma_async.sync.aligned.m64n128k16.f32.bf16.bf16 "
        "{%0, %1, %2, %3, %4, %5, %6, %7, %8, %9, %10, %11, %12, %13, %14, %15, %16, %17, %18, %19, %20, "
        "%21, %22, %23, %24, %25, %26, %27, %28, %29, %30, %31, %32, %33, %34, %35, %36, %37, %38, %39, %40, "
        "%41, %42, %43, %44, %45, %46, %47, %48, %49, %50, %51, %52, %53, %54, %55, %56, %57, %58, %59, %60, "
        "%61, %62, %63},"
        " %64, %65, p, 1, 1, 0, 0;\n}\n"
        : "+f"(d[0]), "+f"(d[1]), "+f"(d[2]), "+f"(d[3]), "+f"(d[4]), "+f"(d[5]), "+f"(d[6]), "+f"(d[7]),
        "+f"(d[8]), "+f"(d[9]), "+f"(d[10]), "+f"(d[11]), "+f"(d[12]), "+f"(d[13]), "+f"(d[14]), "+f"(d[15]),
        "+f"(d[16]), "+f"(d[17]), "+f"(d[18]), "+f"(d[19]), "+f"(d[20]), "+f"(d[21]), "+f"(d[22]),
        "+f"(d[23]), "+f"(d[24]), "+f"(d[25]), "+f"(d[26]), "+f"(d[27]), "+f"(d[28]), "+f"(d[29]),
        "+f"(d[30]), "+f"(d[31]), "+f"(d[32]), "+f"(d[33]), "+f"(d[34]), "+f"(d[35]), "+f"(d[36]),
        "+f"(d[37]), "+f"(d[38]), "+f"(d[39]), "+f"(d[40]), "+f"(d[41]), "+f"(d[42]), "+f"(d[43]),
        "+f"(d[44]), "+f"(d[45]), "+f"(d[46]), "+f"(d[47]), "+f"(d[48]), "+f"(d[49]), "+f"(d[50]),
        "+f"(d[51]), "+f"(d[52]), "+f"(d[53]), "+f"(d[54]), "+f"(d[55]), "+f"(d[56]), "+f"(d[57]),
        "+f"(d[58]), "+f"(d[59]), "+f"(d[60]), "+f"(d[61]), "+f"(d[62]), "+f"(d[63])
        : "l"(da), "l"(db), "r"(scale_d));
}
__device__ __forceinline__ void wgmma_rs_n128_tb(float (&d)[64], uint32_t a0, uint32_t a1, uint32_t a2, uint32_t a3, uint64_t db, int scale_d) {
    asm volatile("{\n.reg .pred p;\n"
        "setp.ne.b32 p, %69, 0;\n"
        "wgmma.mma_async.sync.aligned.m64n128k16.f32.bf16.bf16 "
        "{%0, %1, %2, %3, %4, %5, %6, %7, %8, %9, %10, %11, %12, %13, %14, %15, %16, %17, %18, %19, %20, "
        "%21, %22, %23, %24, %25, %26, %27, %28, %29, %30, %31, %32, %33, %34, %35, %36, %37, %38, %39, %40, "
        "%41, %42, %43, %44, %45, %46, %47, %48, %49, %50, %51, %52, %53, %54, %55, %56, %57, %58, %59, %60, "
        "%61, %62, %63},"
        " {%64, %65, %66, %67}, %68, p, 1, 1, 1;\n}\n"
        : "+f"(d[0]), "+f"(d[1]), "+f"(d[2]), "+f"(d[3]), "+f"(d[4]), "+f"(d[5]), "+f"(d[6]), "+f"(d[7]),
        "+f"(d[8]), "+f"(d[9]), "+f"(d[10]), "+f"(d[11]), "+f"(d[12]), "+f"(d[13]), "+f"(d[14]), "+f"(d[15]),
        "+f"(d[16]), "+f"(d[17]), "+f"(d[18]), "+f"(d[19]), "+f"(d[20]), "+f"(d[21]), "+f"(d[22]),
        "+f"(d[23]), "+f"(d[24]), "+f"(d[25]), "+f"(d[26]), "+f"(d[27]), "+f"(d[28]), "+f"(d[29]),
        "+f"(d[30]), "+f"(d[31]), "+f"(d[32]), "+f"(d[33]), "+f"(d[34]), "+f"(d[35]), "+f"(d[36]),
        "+f"(d[37]), "+f"(d[38]), "+f"(d[39]), "+f"(d[40]), "+f"(d[41]), "+f"(d[42]), "+f"(d[43]),
        "+f"(d[44]), "+f"(d[45]), "+f"(d[46]), "+f"(d[47]), "+f"(d[48]), "+f"(d[49]), "+f"(d[50]),
        "+f"(d[51]), "+f"(d[52]), "+f"(d[53]), "+f"(d[54]), "+f"(d[55]), "+f"(d[56]), "+f"(d[57]),
        "+f"(d[58]), "+f"(d[59]), "+f"(d[60]), "+f"(d[61]), "+f"(d[62]), "+f"(d[63])
        : "r"(a0), "r"(a1), "r"(a2), "r"(a3), "l"(db), "r"(scale_d));
}
__device__ __forceinline__ void wgmma_ss_n128_tb_init(float (&d)[64], uint64_t da, uint64_t db) {
    asm volatile("{\n.reg .pred p;\n"
        "setp.ne.b32 p, 0, 0;\n"
        "wgmma.mma_async.sync.aligned.m64n128k16.f32.bf16.bf16 "
        "{%0, %1, %2, %3, %4, %5, %6, %7, %8, %9, %10, %11, %12, %13, %14, %15, %16, %17, %18, %19, %20, "
        "%21, %22, %23, %24, %25, %26, %27, %28, %29, %30, %31, %32, %33, %34, %35, %36, %37, %38, %39, %40, "
        "%41, %42, %43, %44, %45, %46, %47, %48, %49, %50, %51, %52, %53, %54, %55, %56, %57, %58, %59, %60, "
        "%61, %62, %63},"
        " %64, %65, p, 1, 1, 0, 1;\n}\n"
        : "=f"(d[0]), "=f"(d[1]), "=f"(d[2]), "=f"(d[3]), "=f"(d[4]), "=f"(d[5]), "=f"(d[6]), "=f"(d[7]),
        "=f"(d[8]), "=f"(d[9]), "=f"(d[10]), "=f"(d[11]), "=f"(d[12]), "=f"(d[13]), "=f"(d[14]), "=f"(d[15]),
        "=f"(d[16]), "=f"(d[17]), "=f"(d[18]), "=f"(d[19]), "=f"(d[20]), "=f"(d[21]), "=f"(d[22]),
        "=f"(d[23]), "=f"(d[24]), "=f"(d[25]), "=f"(d[26]), "=f"(d[27]), "=f"(d[28]), "=f"(d[29]),
        "=f"(d[30]), "=f"(d[31]), "=f"(d[32]), "=f"(d[33]), "=f"(d[34]), "=f"(d[35]), "=f"(d[36]),
        "=f"(d[37]), "=f"(d[38]), "=f"(d[39]), "=f"(d[40]), "=f"(d[41]), "=f"(d[42]), "=f"(d[43]),
        "=f"(d[44]), "=f"(d[45]), "=f"(d[46]), "=f"(d[47]), "=f"(d[48]), "=f"(d[49]), "=f"(d[50]),
        "=f"(d[51]), "=f"(d[52]), "=f"(d[53]), "=f"(d[54]), "=f"(d[55]), "=f"(d[56]), "=f"(d[57]),
        "=f"(d[58]), "=f"(d[59]), "=f"(d[60]), "=f"(d[61]), "=f"(d[62]), "=f"(d[63])
        : "l"(da), "l"(db));
}
__device__ __forceinline__ void wgmma_ss_n128_tb(float (&d)[64], uint64_t da, uint64_t db, int scale_d) {
    asm volatile("{\n.reg .pred p;\n"
        "setp.ne.b32 p, %66, 0;\n"
        "wgmma.mma_async.sync.aligned.m64n128k16.f32.bf16.bf16 "
        "{%0, %1, %2, %3, %4, %5, %6, %7, %8, %9, %10, %11, %12, %13, %14, %15, %16, %17, %18, %19, %20, "
        "%21, %22, %23, %24, %25, %26, %27, %28, %29, %30, %31, %32, %33, %34, %35, %36, %37, %38, %39, %40, "
        "%41, %42, %43, %44, %45, %46, %47, %48, %49, %50, %51, %52, %53, %54, %55, %56, %57, %58, %59, %60, "
        "%61, %62, %63},"
        " %64, %65, p, 1, 1, 0, 1;\n}\n"
        : "+f"(d[0]), "+f"(d[1]), "+f"(d[2]), "+f"(d[3]), "+f"(d[4]), "+f"(d[5]), "+f"(d[6]), "+f"(d[7]),
        "+f"(d[8]), "+f"(d[9]), "+f"(d[10]), "+f"(d[11]), "+f"(d[12]), "+f"(d[13]), "+f"(d[14]), "+f"(d[15]),
        "+f"(d[16]), "+f"(d[17]), "+f"(d[18]), "+f"(d[19]), "+f"(d[20]), "+f"(d[21]), "+f"(d[22]),
        "+f"(d[23]), "+f"(d[24]), "+f"(d[25]), "+f"(d[26]), "+f"(d[27]), "+f"(d[28]), "+f"(d[29]),
        "+f"(d[30]), "+f"(d[31]), "+f"(d[32]), "+f"(d[33]), "+f"(d[34]), "+f"(d[35]), "+f"(d[36]),
        "+f"(d[37]), "+f"(d[38]), "+f"(d[39]), "+f"(d[40]), "+f"(d[41]), "+f"(d[42]), "+f"(d[43]),
        "+f"(d[44]), "+f"(d[45]), "+f"(d[46]), "+f"(d[47]), "+f"(d[48]), "+f"(d[49]), "+f"(d[50]),
        "+f"(d[51]), "+f"(d[52]), "+f"(d[53]), "+f"(d[54]), "+f"(d[55]), "+f"(d[56]), "+f"(d[57]),
        "+f"(d[58]), "+f"(d[59]), "+f"(d[60]), "+f"(d[61]), "+f"(d[62]), "+f"(d[63])
        : "l"(da), "l"(db), "r"(scale_d));
}

enum { M_X = 0, M_C, M_WQ, M_WUK, M_WUV, M_WQKV, M_WO, M_WOB, M_SCR_LD, M_SCR_LOC, M_SCR_LOQ, M_SCR_ST, M_OUT, M_COUNT };
enum { T_Q = 0, T_K, T_V, T_B, T_OUT, T_LOCAL, T_ATTN, T_END };
constexpr int NCTA = 132;
constexpr int NITEMS = 256;
constexpr int TRIPLES = 2, WIDE = 80 - 3 * TRIPLES;
struct Params {
    CUtensorMap m[M_COUNT];
    const __nv_bfloat16* x;
    const __nv_bfloat16* gate_w;
    const char* wo;
    __nv_bfloat16* out;
    uint32_t zero;
    uint16_t plan[10][16];
    uint16_t items[NITEMS];
    uint8_t ostep[80];
};
__device__ __forceinline__ int item_type(int it) { return it >> 13; }
__device__ __forceinline__ int item_row(int it) { return it & 15; }
__device__ __forceinline__ int item_col(int it) { return (it >> 4) & 31; }
__device__ __forceinline__ int item_asc(int it) { return (it >> 9) & 1; }
constexpr int ITEM_READY = 1 << 10;

struct __align__(128) Sync {
    unsigned long long count[4];
    __align__(128) unsigned long long ctx[16];
    unsigned next, next_out, done;
    __align__(128) unsigned step[32][2];
    unsigned split[32];
};
__device__ Sync g_sync;

constexpr uint32_t GST_BYTES = 49152, SM_KV = 65536, SM_STAGING = 196608, SM_BARS = SM_STAGING + 32768;
constexpr uint32_t B_GFULL = 0, B_GEMPTY = 32, B_AFULL = 64, B_AEMPTY = 112, B_SFULL = 160, B_SEMPTY = 192,
                   B_IFULL = 224, B_IEMPTY = 288, B_XFREE = 352, B_WANT = 384, B_MEET = 392, B_HALF = 416,
                   SM_ORDY = 448, SM_QUEUE = 456, B_ALT = 488, B_QFREE = 504, SM_GATE = 512, SM_TOTAL = SM_BARS + 1536;
constexpr int QDEPTH = 8;
constexpr int FIRST_PAIR = 6;
constexpr int K_MEET = 16, K_SPLIT = 30;
constexpr int K_FETCH = 20;
constexpr uint32_t LOC_PLANE = 72 * 128;
constexpr float LOC_SCALE = 0.17677669529663687f * 1.4426950408889634f;
constexpr float SUM_LIMIT = 1180591620717411303424.f;
constexpr float REF_RANGE = 60.f;

__device__ __forceinline__ unsigned ld_acquire(const unsigned* p) {
    unsigned v; asm volatile("ld.acquire.gpu.global.u32 %0, [%1];" : "=r"(v) : "l"(p) : "memory"); return v;
}
__device__ __forceinline__ unsigned long long ld_acquire(const unsigned long long* p) {
    unsigned long long v; asm volatile("ld.acquire.gpu.global.u64 %0, [%1];" : "=l"(v) : "l"(p) : "memory"); return v;
}
__device__ __forceinline__ void spin_guard(unsigned& n) {
    asm volatile("{\n.reg .pred P;\nadd.u32 %0, %0, 1;\nsetp.gt.u32 P, %0, 16777216;\n@P trap;\n}\n" : "+r"(n));
    if (n > 1) __nanosleep(100);
}
__device__ __forceinline__ void red_add(unsigned long long* p, unsigned long long v) {
    asm volatile("red.release.gpu.global.add.u64 [%0], %1;" :: "l"(p), "l"(v) : "memory");
}
__device__ __forceinline__ float rcp(float x) { float y; asm("rcp.approx.ftz.f32 %0, %1;" : "=f"(y) : "f"(x)); return y; }
__device__ __forceinline__ float lds_f32(uint32_t addr) {
    float v; asm volatile("ld.shared.f32 %0, [%1];" : "=f"(v) : "r"(addr) : "memory"); return v;
}
__device__ __forceinline__ void ldsm_x4(uint32_t (&r)[4], uint32_t addr) {
    asm volatile("ldmatrix.sync.aligned.m8n8.x4.shared.b16 {%0, %1, %2, %3}, [%4];"
                 : "=r"(r[0]), "=r"(r[1]), "=r"(r[2]), "=r"(r[3]) : "r"(addr) : "memory");
}
__device__ __forceinline__ void ldsm_x4_t(uint32_t (&r)[4], uint32_t addr) {
    asm volatile("ldmatrix.sync.aligned.m8n8.x4.trans.shared.b16 {%0, %1, %2, %3}, [%4];"
                 : "=r"(r[0]), "=r"(r[1]), "=r"(r[2]), "=r"(r[3]) : "r"(addr) : "memory");
}
__device__ __forceinline__ void mma_k16(float (&d)[4], const uint32_t (&a)[4], uint32_t b0, uint32_t b1) {
    asm("mma.sync.aligned.m16n8k16.row.col.f32.bf16.bf16.f32 {%0,%1,%2,%3}, {%4,%5,%6,%7}, {%8,%9}, {%0,%1,%2,%3};"
        : "+f"(d[0]), "+f"(d[1]), "+f"(d[2]), "+f"(d[3]) : "r"(a[0]), "r"(a[1]), "r"(a[2]), "r"(a[3]), "r"(b0), "r"(b1));
}
__device__ __forceinline__ void mma_k16_init(float (&d)[4], const uint32_t (&a)[4], uint32_t b0, uint32_t b1) {
    asm("{\n.reg .f32 z;\nmov.f32 z, 0f00000000;\n"
        "mma.sync.aligned.m16n8k16.row.col.f32.bf16.bf16.f32 {%0,%1,%2,%3}, {%4,%5,%6,%7}, {%8,%9}, {z,z,z,z};\n}\n"
        : "=f"(d[0]), "=f"(d[1]), "=f"(d[2]), "=f"(d[3]) : "r"(a[0]), "r"(a[1]), "r"(a[2]), "r"(a[3]), "r"(b0), "r"(b1));
}
__device__ __forceinline__ void mma_k8(float (&d)[4], uint32_t a0, uint32_t a1, uint32_t b0) {
    asm("mma.sync.aligned.m16n8k8.row.col.f32.bf16.bf16.f32 {%0,%1,%2,%3}, {%4,%5}, {%6}, {%0,%1,%2,%3};"
        : "+f"(d[0]), "+f"(d[1]), "+f"(d[2]), "+f"(d[3]) : "r"(a0), "r"(a1), "r"(b0));
}
template <typename T, int N> __device__ __forceinline__ void zero_regs(T (&d)[N]) {
#pragma unroll
    for (int i = 0; i < N; i++) d[i] = 0;
}
__device__ __forceinline__ float quad_max(float v) {
    v = fmaxf(v, __shfl_xor_sync(0xffffffffu, v, 1));
    return fmaxf(v, __shfl_xor_sync(0xffffffffu, v, 2));
}
__device__ __forceinline__ float quad_sum(float v) {
    v += __shfl_xor_sync(0xffffffffu, v, 1);
    return v + __shfl_xor_sync(0xffffffffu, v, 2);
}

__device__ __forceinline__ void qk_gemm(float (&s)[64], uint32_t q_lo, uint32_t k_lo) {
    const uint64_t dq = full_desc(q_lo), dk = full_desc(k_lo);
    wgmma_fence();
    wgmma_ss_n128_init(s, dq, dk);
#pragma unroll
    for (int kk = 1; kk < 8; kk++) {
        const uint32_t o = (kk >> 2) * 1024 + (kk & 3) * 2;
        wgmma_ss_n128(s, dq + o, dk + o, 1);
    }
    wgmma_commit();
}
__device__ __forceinline__ void pv_gemm(float (&o)[64], uint32_t (&p)[32], uint32_t v_lo, int accumulate) {
    const uint64_t dv = full_desc(v_lo);
    fence_regs(o);
    fence_regs(p);
    wgmma_fence();
#pragma unroll
    for (int kk = 0; kk < 8; kk++)
        wgmma_rs_n128_tb(o, p[4 * kk], p[4 * kk + 1], p[4 * kk + 2], p[4 * kk + 3], dv + kk * 128, kk != 0 || accumulate);
    wgmma_commit();
}
__device__ __forceinline__ void row_max(const float (&s)[64], float& x0, float& x1) {
    float z0 = fmaxf(s[0], s[1]), z1 = fmaxf(s[2], s[3]);
    x0 = fmaxf(s[4], s[5]); x1 = fmaxf(s[6], s[7]);
#pragma unroll
    for (int j = 2; j < 16; j += 2) {
        z0 = fmaxf(z0, fmaxf(s[4 * j], s[4 * j + 1]));
        z1 = fmaxf(z1, fmaxf(s[4 * j + 2], s[4 * j + 3]));
        x0 = fmaxf(x0, fmaxf(s[4 * j + 4], s[4 * j + 5]));
        x1 = fmaxf(x1, fmaxf(s[4 * j + 6], s[4 * j + 7]));
    }
    x0 = quad_max(fmaxf(x0, z0)); x1 = quad_max(fmaxf(x1, z1));
}
__device__ __forceinline__ void exp_pack(uint32_t (&p)[32], const float (&s)[64], float& r0, float& r1) {
#pragma unroll
    for (int j = 0; j < 16; j++) {
        const float e0 = ex2(s[4 * j]), e1 = ex2(s[4 * j + 1]), e2 = ex2(s[4 * j + 2]), e3 = ex2(s[4 * j + 3]);
        if (j == 0) { r0 = e0 + e1; r1 = e2 + e3; }
        else { r0 += e0 + e1; r1 += e2 + e3; }
        p[2 * j] = pack_bf16(e0, e1);
        p[2 * j + 1] = pack_bf16(e2, e3);
    }
}
__device__ __forceinline__ void shift_rows(float (&s)[64], float d0, float d1) {
#pragma unroll
    for (int j = 0; j < 16; j++) { s[4 * j] -= d0; s[4 * j + 1] -= d0; s[4 * j + 2] -= d1; s[4 * j + 3] -= d1; }
}
constexpr float MASKED = -3e38f;
template <int J0>
__device__ __forceinline__ void mask_triangle(float (&s)[64], float thr) {
#pragma unroll
    for (int j = 0; j < 16; j++) {
        const float m = __saturatef((float)(8 * (j >> 1) + (j & 1)) - thr);
        const int i = 4 * (J0 + (j >> 1)) + (j & 1);
        s[i] = fmaf(m, MASKED, s[i]);
        if (j < 14) s[i + 6] = fmaf(m, MASKED, s[i + 6]);
    }
}
__device__ __forceinline__ void causal_mask(float (&s)[64], float thr, int wg) {
    asm volatile("" : "+f"(thr));
    if (wg == 0) {
        mask_triangle<0>(s, thr);
#pragma unroll
        for (int j = 32; j < 64; j++) s[j] += MASKED;
    } else {
        mask_triangle<8>(s, thr);
    }
}

__global__ void __cluster_dims__(2, 1, 1) __launch_bounds__(384, 1) fused_kernel(const __grid_constant__ Params prm) {
    extern __shared__ __align__(1024) uint8_t smem[];
    const uint32_t sb = smem_u32(smem), bars = sb + SM_BARS;
    const int warp = __shfl_sync(0xffffffffu, threadIdx.x >> 5, 0), lane = threadIdx.x & 31;

    const uint32_t rank = cluster_rank();
    const uint32_t bars0 = map_cta(bars, 0), bars_peer = map_cta(bars, rank ^ 1);

    auto plan_index = [&]() -> uint32_t {
        uint32_t p = blockIdx.x >> 1;
        asm volatile("" : "+r"(p));
        const uint32_t r = (p - 36) * 37 >> 8;
        return p < 4 ? 4 + p : p < 36 ? (p - 4 & 7) * 8 + (p - 4 >> 3) : p < 64 ? (p - 35 - 7 * r) * 8 + 4 + r : p;
    };
    auto first_item = [&]() -> int {
        const uint32_t pair = plan_index();
        const uint32_t slot = pair & 7, c = slot * 11 >> 5;
        return pair < 64 ? T_B << 13 | (4 * slot - 11 * c) << 4 | (2 * (pair >> 3) + rank) : T_K << 13 | (8 * slot + rank);
    };
    if (warp == 0) {
        if (elect_one())
            for (int k = 0; k < 4; k++) mbar_init(bars + B_GFULL + 8 * k, 1);
        const int first_it = __shfl_sync(0xffffffffu, first_item(), 0);
        asm volatile("fence.mbarrier_init.release.cluster;" ::: "memory");
        fence_proxy_async_smem();
        __syncwarp();
        asm volatile("barrier.cluster.arrive.relaxed.aligned;" ::: "memory");
        const CUtensorMap* ma = &prm.m[item_type(first_it) == T_K ? M_C : M_X];
        const CUtensorMap* mb = &prm.m[M_WQ + item_type(first_it)];
#pragma unroll
        for (int k = 0; k < 2; k++) {
            const uint32_t dst = sb + k * GST_BYTES, fb = bars + B_GFULL + 8 * k;
            warp_expect_tx(fb, GST_BYTES);
            warp_tma_load(dst + 16384, mb, fb, 0, k * 64, item_col(first_it) * 4, true);
            warp_tma_load(dst, ma, fb, k * 64, item_row(first_it) * 128, 0, false);
            warp_tma_load(dst + 32768, mb, fb, 0, k * 64, item_col(first_it) * 4 + 2, true);
        }
    }
    if (threadIdx.x == 32) {
        for (int i = 0; i < 4; i++) mbar_init(bars + B_GEMPTY + 8 * i, 16);
        for (int i = 0; i < 6; i++) { mbar_init(bars + B_AFULL + 8 * i, 1); mbar_init(bars + B_AEMPTY + 8 * i, i < 2 ? 8 : 16); }
        for (int i = 0; i < 4; i++) { mbar_init(bars + B_SFULL + 8 * i, 4); mbar_init(bars + B_SEMPTY + 8 * i, 1); }
        for (int i = 0; i < QDEPTH; i++) { mbar_init(bars + B_IFULL + 8 * i, 1); mbar_init(bars + B_IEMPTY + 8 * i, 23); }
        mbar_init(bars + B_WANT, 2); mbar_init(bars + B_MEET, 1); mbar_init(bars + B_XFREE, 1);
        for (int i = 0; i < 4; i++) mbar_init(bars + B_HALF + 8 * i, 1);
        mbar_init(bars + B_ALT, 4); mbar_init(bars + B_ALT + 8, 4); mbar_init(bars + B_QFREE, 2);
        asm volatile("st.shared.u64 [%0], 0;" :: "r"(bars + SM_ORDY) : "memory");
        asm volatile("fence.mbarrier_init.release.cluster;\nfence.acq_rel.cta;" ::: "memory");
    }
    __syncwarp();
    if (warp != 0) asm volatile("barrier.cluster.arrive.relaxed.aligned;" ::: "memory");
    asm volatile("barrier.cluster.wait.acquire.aligned;" ::: "memory");

    uint32_t qn = 0;
    auto next_item = [&](bool releaser, bool bounded = true) -> int {
        const uint32_t slot = qn % QDEPTH;
        if (bounded) mbar_wait(bars + B_IFULL + 8 * slot, (qn / QDEPTH) & 1);
        else mbar_spin(bars + B_IFULL + 8 * slot, (qn / QDEPTH) & 1);
        uint32_t it;
        asm volatile("ld.shared.u32 %0, [%1];" : "=r"(it) : "r"(bars + SM_QUEUE + 4 * slot) : "memory");
        mbar_arrive_cluster_if(releaser, bars0 + B_IEMPTY + 8 * slot);
        qn++;
        return it;
    };

    if (warp < 4) {
        reg_dec<40>();
        if (warp == 0) {
            {
                uint32_t gph = 1;
                const uint32_t prank = __shfl_sync(0xffffffffu, rank, 0);
                auto request = [&]() { mbar_arrive_cluster_if(lane == 0, bars0 + B_WANT); };
                auto take_item = [&]() -> int { return __shfl_sync(0xffffffffu, next_item(lane == 0), 0); };
                auto inputs_seen = [&](uint32_t word, unsigned& n) -> uint32_t {
                    uint32_t v;
                    spin_guard(n);
                    asm volatile("ld.acquire.cta.shared.u32 %0, [%1];" : "=r"(v) : "r"(bars + SM_ORDY + 4 * word) : "memory");
                    return __shfl_sync(0xffffffffu, v, 0);
                };
                uint32_t oneed = 0;
                auto wait_inputs = [&](int it) {
                    if (it & ITEM_READY) return;
                    oneed += 256;
                    for (unsigned n = 0; inputs_seen(1, n) < oneed;) {}
                };
                int nxt = first_item(), ring = -1, rot = 0;
                for (int k0 = 2; item_type(nxt) <= T_LOCAL; k0 = 0) {
                    const int type = item_type(nxt), m = item_row(nxt), c = item_col(nxt);
                    if (type == T_LOCAL) {
                        wait_inputs(nxt);
                        request();
#pragma unroll 1
                        for (uint32_t st = 0; st < 4; st++) {
                            mbar_wait(bars + B_GEMPTY + 8 * st, gph);
                            const uint32_t dst = sb + st * GST_BYTES, fb = bars + B_GFULL + 8 * st;
                            warp_expect_tx(fb, st == 0 ? 32768 + 512 : st == 3 ? 0 : 4 * LOC_PLANE);
                            if (st == 3) break;
                            if (st == 0) warp_bulk_load(dst + 4 * LOC_PLANE, &g_gate[m * 128], 512, fb);
#pragma unroll 1
                            for (int i = 0; i < 4; i++)
                                warp_tma_load(dst + i * LOC_PLANE, &prm.m[st ? M_SCR_LOC : M_SCR_LOQ], fb, i * 64, m * 64 - (st ? 8 : 0), G_B + 8 * st + c, true);
                        }
                        gph ^= 1;
                        ring = -1;
                    } else {
                        const int nk = type == T_K || type == T_V ? 8 : 16, kept = ring == m + 16 * nk ? 4 : 0;
                        ring = m + 16 * nk;
                        rot = kept ? rot - 4 : 0;
                        const CUtensorMap* ma = &prm.m[nk == 8 ? M_C : M_X];
                        const CUtensorMap* mb = &prm.m[M_WQ + type];
#pragma unroll 1
                        for (int k = k0; k < nk; k++) {
                            if (k == nk - 3) request();
                            const uint32_t st = k & 3, dst = sb + st * GST_BYTES, fb = bars + B_GFULL + 8 * st;
                            const int kc = ((k + rot) & (nk - 1)) * 64;
                            mbar_wait(bars + B_GEMPTY + 8 * st, gph);
                            warp_expect_tx(fb, k < kept ? 32768 : GST_BYTES);
                            if (k >= kept) warp_tma_load(dst, ma, fb, kc, m * 128, 0, c == 15 && type != T_K);
                            warp_tma_load_pair(dst + 16384 + prank * 16384, mb, fb, 0, kc, c * 4 + 2 * prank, blockIdx.x < 128 || (m & 6) == 6);
                            if (st == 3) gph ^= 1;
                        }
                    }
                    nxt = take_item();
                }
                uint32_t kv = 0, kvph = 1;
                uint32_t qc = 0;
                auto a_parity = [&](uint32_t b) { return b < 2 ? (((qc + 1 - b) >> 1) & 1) ^ 1 : kvph ^ (b - 2 < kv); };
                const CUtensorMap* tile_map = &prm.m[M_SCR_LD];
                asm volatile("" : "+l"(tile_map));
                {
                    bool need_g = true, more = true;
                    int pv_grp = -1, pv_row = 0;
                    int pv_shared = 0;
                    bool peer_longer = false;
                    int m = 0, c = 0, asc = 0, nu = 0, uend = 0, ureq = -1, ufetch = 0;
#pragma unroll 1
                    for (int u = 0;; u++) {
                        if (u == ufetch) {
                            if (qc) nxt = take_item();
                            if (item_type(nxt) == T_ATTN) {
                                wait_inputs(nxt);
                                const uint32_t b = qc & 1, dst = sb + b * 32768, fb = bars + B_AFULL + 8 * b, row = item_row(nxt) * 128;
                                mbar_wait(bars + (qc == 0 ? B_GEMPTY : qc == 1 ? B_QFREE : B_AEMPTY + 8 * b), qc == 0 ? gph : qc == 1 ? 0 : a_parity(b));
                                warp_expect_tx(fb, 32768 + 512);
                                warp_tma_load(dst, tile_map, fb, 0, row, G_Q + item_col(nxt), false);
                                warp_tma_load(dst + 16384, tile_map, fb, 64, row, G_Q + item_col(nxt), false);
                                warp_bulk_load(bars + SM_GATE + b * 512, &g_gate[row], 512, fb);
                                qc++;
                            }
                        }
                        if (u == uend) {
                            if (!more) break;
                            more = item_type(nxt) == T_ATTN;
                            m = item_row(nxt); c = item_col(nxt); asc = item_asc(nxt);
                            nu = more ? 2 * m + 2 : 0;
                            uend = nu + ((more ? m < 2 : pv_grp >= 0) ? 3 : 0);
                            ureq = 2 * max(m - 2 - (asc & m), 0);
                            ufetch = !more ? -1 : m ? 2 * m : uend;
                            u = -1;
                            continue;
                        }
                        int grp = pv_grp, row = pv_row;
                        int shared = pv_shared;
                        if (u >= nu) {
                            if (u == nu + 1) pv_grp = -1;
                            else if (peer_longer) { grp = -1; shared = 0; }
                            else continue;
                        } else {
                            const int j = asc ? u >> 1 : m - (u >> 1);
                            if (u & 1) {
                                pv_grp = G_V + c; pv_row = j * 128; pv_shared = (m | 1) - j;
                                peer_longer = asc & ~m & 1;
                                if (u == nu - 1 && (m & 1) && item_type(nxt) == T_END) mbar_arrive_cluster_n_if(lane == 0, bars0 + B_WANT, 2);
                                if (grp < 0) continue;
                            } else {
                                if (u == ureq) request();
                                grp = G_K + c; row = j * 128; shared = (m | 1) - j;
                            }
                        }
                        uint32_t fb = bars + B_AFULL + 16 + 8 * kv, mine = sb + SM_KV + kv * 32768 + prank * 16384;
                        int c_mine = prank * 64;
                        asm volatile("" : "+r"(mine), "+r"(fb), "+r"(row), "+r"(grp), "+r"(c_mine));
                        mbar_wait(need_g ? bars + B_GEMPTY + 8 + 8 * kv : fb + B_AEMPTY - B_AFULL, need_g ? gph : kvph);
                        warp_expect_tx(fb, grp < 0 ? 0 : 32768);
                        if (shared) {
                            warp_tma_load_pair(mine, tile_map, fb, c_mine, row, grp, shared == 1);
                        } else if (grp >= 0) {
                            warp_tma_load(mine, tile_map, fb, c_mine, row, grp, true);
                            warp_tma_load(mine + 16384 - prank * 32768, tile_map, fb, 64 - c_mine, row, grp, true);
                        } else {
                            mbar_arrive_cluster_n_if(lane < 2, map_cta(fb, lane & 1) + B_AEMPTY - B_AFULL, 8);
                        }
                        if (kv == 2) need_g = false;
                        if (++kv == 4) { kv = 0; kvph ^= 1; }
                    }
                }
                if (!qc) request();
                const int it = take_item();
                int nk = 0;
                if (item_type(it) == T_OUT) {
                    const int m = item_row(it), c = item_col(it), half = c & 1;
                    nk = 80;
                    for (unsigned n = 0; (inputs_seen(1, n) & 255) != 255;) {}
                    mbar_wait(bars + B_GEMPTY + 24, gph);
                    mbar_wait(bars + B_QFREE, 0);
                    mbar_wait(bars + B_AEMPTY + 8 * (qc & 1), a_parity(qc & 1));
#pragma unroll 1
                    for (uint32_t k = 0; k < 4; k++) {
                        const uint32_t sa = prm.ostep[half ? WIDE - 1 - k : k], dst = sb + k * GST_BYTES, fb = bars + B_GFULL + 8 * k;
                        const uint32_t b0 = k ? 1 + k : ~qc & 1, b1 = 2 + k - (k == 1);
                        mbar_wait(bars + B_AEMPTY + 8 * b0, a_parity(b0));
                        mbar_arrive_cluster_if(lane == 0 && !k, bars_peer + B_XFREE);
                        warp_expect_tx(fb, GST_BYTES);
                        warp_tma_load(dst, tile_map, fb, (sa & 1) * 64, m * 128, G_LOC - 32 + (sa >> 1), true);
                        mbar_wait(bars + (k ? B_AEMPTY + 8 * b1 : B_XFREE), k ? kvph ^ (b1 - 2 < kv) : 0);
                        warp_tma_load_pair(dst + 16384 + prank * 16384, &prm.m[M_WOB], fb, 0, (sa & 63) * 64, (c >> 1) * 4 + 2 * (half ^ prank), false);
                    }
                    gph ^= 1;
                    uint32_t seen = 0;
                    for (int k = 4; k < nk; k++) {
                        if (k == K_SPLIT) nk = 2 * TRIPLES + (take_item() & 127);
                        const int kn = k + 2 * TRIPLES - nk, first = kn >= 0 && !(kn & 1);
                        const int s = kn >= 0 ? WIDE + (3 * kn + 1) / 2 : half ? WIDE - 1 - k : k;
                        const uint32_t sa = prm.ostep[s], sa2 = prm.ostep[s + first], sw = prm.ostep[s - (kn >= 0 && !first ? prank : 0)];
                        const uint32_t need = 1u << (sa >> 1 & 31) | 1u << (sa2 >> 1 & 31);
                        for (unsigned n = 0; sa < 64 && (need & ~seen);) seen = inputs_seen(0, n);
                        const uint32_t st = k & 3;
                        uint32_t dst = sb + st * GST_BYTES, fb = bars + B_GFULL + 8 * st;
                        uint32_t dstb = dst + 16384 + (first ? 0 : prank * 16384), skipb = first && (kn >> 1 & 1) != prank;
                        int a0 = (sa & 1) * 64, a1 = m * 128, a2 = (sa >> 1) + (sa < 64 ? G_CTX : G_LOC - 32);
                        int b1 = (sw & 63) * 64, b2 = (c >> 1) * 4 + 2 * (kn >= 0 ? half : half ^ prank);
                        const CUtensorMap* mb = &prm.m[sw >= 64 ? M_WOB : M_WO];
                        asm volatile("" : "+r"(dst), "+r"(fb), "+r"(dstb), "+r"(skipb), "+r"(a0), "+r"(a1), "+r"(a2), "+r"(b1), "+r"(b2), "+l"(mb));
                        mbar_wait(bars + B_GEMPTY + 8 * st, gph);
                        warp_expect_tx(fb, GST_BYTES);
                        warp_tma_load(dst, tile_map, fb, a0, a1, a2, true);
                        if (!skipb) warp_tma_load_pair(dstb, mb, fb, 0, b1, b2, false);
                        if (first) warp_tma_load(dst + 32768, tile_map, fb, (sa2 & 1) * 64, a1, G_CTX + (sa2 >> 1), true);
                        if (k < K_SPLIT && lane == 0 && !prank)
                            asm volatile("st.relaxed.gpu.global.u32 [%0], %1;" :: "l"(&g_sync.step[0][0] + m * 4 + c), "r"(k) : "memory");
                        mbar_arrive_if(k == K_MEET && lane == 0, bars + B_MEET);
                        if ((uint32_t)(k - K_FETCH) < (3 * TRIPLES + 1) / 2) {
                            const uint32_t g = prm.ostep[79 - 2 * (k - K_FETCH)] >> 1;
                            warp_prefetch((const char*)g_scr + (uint32_t)((G_CTX + g) * (SEQ * 256) + m * 32768 + c * 4096), 4096);
                            warp_prefetch(prm.wo + (uint32_t)(g * 262144 + (m * 8 + c) * 2048), 2048);
                        }
                        if (st == 3) gph ^= 1;
                    }
                    for (unsigned n = 0; ~inputs_seen(0, n);) {}
                }
#pragma unroll 1
                for (uint32_t st = 0; st < 4; st++) { mbar_wait(bars + B_GEMPTY + 8 * st, gph ^ (st < (nk & 3))); mbar_wait(bars + B_AEMPTY + 16 + 8 * st, a_parity(2 + st)); }
                unsigned left = 0;
                if (lane == 0) asm volatile("atom.relaxed.gpu.global.add.u32 %0, [%1], 1;" : "=r"(left) : "l"(&g_sync.done) : "memory");
                if (__shfl_sync(0xffffffffu, left, 0) == NCTA - 1)
#pragma unroll 1
                    for (uint32_t i = lane * 8; i < sizeof(Sync); i += 256) *(unsigned long long*)((char*)&g_sync + i) = 0;
            }
        } else if (warp <= 2) {
            if (blockIdx.x < SEQ / 16) {
                const uint32_t r0 = 16 * blockIdx.x + 8 * (warp - 1), gbuf = bars + SM_GATE + 4 * (r0 & 15);
                float z[4];
                mbar_wait(bars + B_GFULL + 24, 0);
#pragma unroll 1
                for (uint32_t i = 0; i < 8; i++) {
                    const uint32_t off = (i & 3) * 512 + lane * 16;
                    const uint4* xp = (const uint4*)((const char*)prm.x + ((r0 + (i & 4)) * 2048 + off));
                    const uint4 wv = __ldg((const uint4*)((const char*)prm.gate_w + off));
                    uint4 xv[4];
#pragma unroll
                    for (int r = 0; r < 4; r++) { xv[r] = __ldg(xp + r * 128); if (!(i & 3)) z[r] = 0.f; }
                    const uint32_t ws[4] = {wv.x, wv.y, wv.z, wv.w};
#pragma unroll
                    for (int e = 0; e < 4; e++)
#pragma unroll
                        for (int r = 0; r < 4; r++) {
                            const uint32_t xs = e == 0 ? xv[r].x : e == 1 ? xv[r].y : e == 2 ? xv[r].z : xv[r].w;
                            z[r] = fmaf(__uint_as_float(xs << 16), __uint_as_float(ws[e] << 16), z[r]);
                            z[r] = fmaf(__uint_as_float(xs & 0xffff0000u), __uint_as_float(ws[e] & 0xffff0000u), z[r]);
                        }
                    if ((i & 3) == 3) {
#pragma unroll
                        for (int o = 16; o > 0; o >>= 1)
#pragma unroll
                            for (int r = 0; r < 4; r++) z[r] += __shfl_xor_sync(0xffffffffu, z[r], o);
                        const float zr = lane & 2 ? (lane & 1 ? z[3] : z[2]) : (lane & 1 ? z[1] : z[0]);
                        asm volatile("st.shared.f32 [%0], %1;" :: "r"(gbuf + 4 * ((i & 4) + (lane & 3))), "f"(1.f / (1.f + __expf(-zr))) : "memory");
                    }
                }
                fence_proxy_async_smem();
                __syncwarp();
                warp_bulk_store((char*)g_gate + 4 * r0, gbuf, 32);
                bulk_commit();
                bulk_wait<0>();
                __syncwarp();
                if (lane == 0) red_add(&g_sync.count[3], 1);
            }
            __syncwarp();
            {
                const int w = warp - 1;
                uint32_t sph = 0, nann = 0;
                int unsent = 0, nunsent = 0;
                bool urgent = false;
                auto announce = [&]() {
                    if (!urgent) return;
                    bulk_wait<0>();
                    __syncwarp();
                    const uint32_t hb = bars + B_HALF + 8 * (nann & 3);
                    if (w == 0) {
                        mbar_arrive_if(lane == 0, hb);
                    } else {
                        mbar_wait(hb, (nann >> 2) & 1);
                        const uint32_t type = item_type(unsent), m = item_row(unsent), c = item_col(unsent);
                        const uint32_t word = type < T_B ? c >> 3 : type == T_B ? 2 : offsetof(Sync, ctx) / 8 + m;
                        const uint32_t bit = type < T_B ? 8 * (c & 7) : type == T_B ? 8 * (c & 3) : type == T_LOCAL ? 32 + c : c;
                        if (lane < nunsent) red_add((unsigned long long*)((char*)&g_sync + 8 * word), 1ull << bit);
                        __syncwarp();
                    }
                    nann++;
                    nunsent = 0; urgent = false;
                };
                int held = first_item(), it;
                do {
                    if (!__all_sync(0xffffffffu, mbar_test(bars + B_IFULL + 8 * (qn % QDEPTH), (qn / QDEPTH) & 1))) announce();
                    it = __shfl_sync(0xffffffffu, next_item(lane == 0), 0);
                    const int itype = item_type(it);
                    const bool keep_held = itype == T_LOCAL;
#pragma unroll 1
                    for (int pass = held < 0 || keep_held; pass < 2; pass++) {
                        if (pass && (itype < T_OUT || itype == T_END)) break;
                        const int cur = pass ? it : held, type = item_type(cur), m = item_row(cur), c = item_col(cur);
                        const bool local = type == T_LOCAL;
                        const int grp = pass ? (local ? G_LOC : G_CTX) + c : type * 32 + 2 * c;
#pragma unroll 1
                        for (int i = 0; i < 4 - 2 * pass; i++) {
                            const int b = i & 1;
                            const bool alt = i >= 2 && itype >= T_ATTN;
                            const uint32_t full = bars + (alt ? B_ALT + 8 * w : B_SFULL + 16 * w + 8 * b), par = alt ? 0 : sph;
                            if (i == 3 - 2 * pass || !__all_sync(0xffffffffu, mbar_test(full, par))) announce();
                            mbar_wait(full, par);
                            fence_proxy_async_smem();
                            warp_tma_store(&prm.m[local ? M_SCR_LOQ : M_SCR_ST], sb + (alt ? 32768 : SM_STAGING) + w * 16384 + b * 8192,
                                         local ? b * 128 + w * 64 : b * 64, local ? m * 64 : m * 128 + w * 64, grp + (i >> 1), local || (type < T_B && c < FIRST_PAIR));
                            bulk_commit();
                            if (pass > b) continue;
                            bulk_wait_read<0>();
                            __syncwarp();
                            mbar_arrive_if(lane <= pass && !alt, bars + B_SEMPTY + 16 * w + 8 * (b - lane));
                            sph ^= b & !alt;
                        }
                        mbar_arrive_if(lane == 0 && !pass && itype >= T_ATTN, bars + B_QFREE);
                        if (lane == nunsent) unsent = cur;
                        nunsent++;
                        urgent = !local;
                    }
                    if (!keep_held) held = itype < T_OUT ? it : -1;
                } while (item_type(it) != T_END);
                announce();
                it = __shfl_sync(0xffffffffu, next_item(lane == 0), 0);
                if (item_type(it) == T_OUT) {
                    if (w) {
                        mbar_wait(bars + B_MEET, 0);
                        asm volatile("fence.proxy.async.global;\nfence.acq_rel.gpu;" ::: "memory");
                        mbar_arrive_cluster_if(lane == 0, bars0 + B_WANT);
                    }
                    next_item(lane == 0);
#pragma unroll 1
                    for (int i = 0; i < 4; i++) {
                        const int b = i & 1;
                        mbar_wait(bars + B_SFULL + 16 * w + 8 * b, sph ^ (i >> 1));
                        fence_proxy_async_smem();
                        warp_tma_add(&prm.m[M_OUT], sb + SM_STAGING + w * 16384 + b * 8192, (item_col(it) ^ (i < 2)) * 128 + b * 64, item_row(it) * 128 + w * 64, 0);
                        bulk_commit();
                        if (b) {
                            bulk_wait_read<0>();
                            __syncwarp();
                            mbar_arrive_if(lane < 2, bars + B_SEMPTY + 16 * w + 8 * lane);
                        }
                    }
                }
            }
        } else {
            if (elect_one()) {
                uint32_t ordy = 0;
                unsigned long long cnt_lo = 0, cnt_hi = 0;
                int late = 0;
                auto refresh = [&]() {
                    if (!late && cnt_lo == 0x30303030 && cnt_hi == SEQ / 8) late = 1;
                    asm volatile("ld.acquire.gpu.global.v2.u64 {%0, %1}, [%2];" : "=l"(cnt_lo), "=l"(cnt_hi) : "l"(late ? &g_sync.count[0] : &g_sync.count[2]) : "memory");
                };
                auto inputs_ready = [&](int it) -> bool {
                    const int c = item_col(it);
                    if (item_type(it) == T_ATTN) return late && ((c < 16 ? cnt_lo : cnt_hi) >> (4 * (c & 14)) & 255) == 48;
                    return late || (cnt_hi == SEQ / 8 && (cnt_lo >> (4 * (c & 6)) & 255) == 48);
                };
                auto publish = [&](int it, int step) {
                    const uint32_t slot = qn % QDEPTH;
                    mbar_wait(bars + B_IEMPTY + 8 * slot, ((qn / QDEPTH) & 1) ^ 1);
                    for (uint32_t r = 0; r < 2; r++) {
                        const uint32_t rb = map_cta(bars, r);
                        asm volatile("mbarrier.arrive.expect_tx.shared::cluster.b64 _, [%0], 4;" :: "r"(rb + B_IFULL + 8 * slot) : "memory");
                        asm volatile("st.async.shared::cluster.mbarrier::complete_tx::bytes.u32 [%0], %1, [%2];"
                                     :: "r"(rb + SM_QUEUE + 4 * slot), "r"(it + r * step), "r"(rb + B_IFULL + 8 * slot) : "memory");
                    }
                    qn++;
                };
                int asc = 1;
                int it;
                do {
                    if (rank == 0) {
                        mbar_wait(bars + B_WANT, qn & 1);
                        const uint32_t pair = plan_index();
                        int pit = prm.plan[pair < 64 ? pair & 7 : pair - 56][min(qn + 1, 15u)];
                        unsigned i;
                        const bool planned = item_type(pit) != T_END;
                        if (!planned) asm volatile("atom.relaxed.gpu.global.add.u32 %0, [%1], 1;" : "=r"(i) : "l"(&g_sync.next) : "memory");
                        if (cnt_lo != 0x3030303030303030ull || cnt_hi != cnt_lo) refresh();
                        if (planned) pit += (pair >> 3 & 7) << (item_type(pit) == T_LOCAL);
                        else if (i < NITEMS) pit = prm.items[i];
                        const int type = item_type(pit);
                        int step = type == T_LOCAL ? 16 : 1;
                        it = pit + (pit & (step == 1 ? 15 : 0x1f0));
                        if (type == T_ATTN) {
                            if (!asc) { it += 1; step = -1; }
                            it |= asc << 9;
                        }
                        asc = type != T_ATTN || item_row(pit) == 0 || !asc;
                        if (inputs_ready(it)) it |= ITEM_READY;
                        publish(it, step);
                    } else {
                        it = next_item(true);
                    }
                    if ((item_type(it) == T_ATTN || item_type(it) == T_LOCAL) && !(it & ITEM_READY)) {
                        unsigned n = 0;
                        while (!inputs_ready(it)) { refresh(); spin_guard(n); }
                        asm volatile("st.release.cta.shared.u32 [%0], %1;" :: "r"(bars + SM_ORDY + 4), "r"(ordy += 256) : "memory");
                    }
                } while (item_type(it) != T_END);
                if (rank == 0) {
                    mbar_wait(bars + B_WANT, qn & 1);
                    const unsigned i = atomicAdd(&g_sync.next_out, 1u), t = i < 32 ? 31 - i : i - 32;
                    it = i < 64 ? T_OUT << 13 | ((t & 3) * 2 + (i >> 5)) << 4 | (t >> 2) * 2 : T_END << 13;
                    publish(it, 1);
                } else {
                    it = next_item(true);
                }
                if (item_type(it) == T_OUT) {
                    const uint32_t m = item_row(it), half = item_col(it) & 1, tile = m * 2 + (item_col(it) >> 1);
                    unsigned* split = (unsigned*)((char*)g_sync.split + 4 * tile);
                    unsigned long long rdy = 0;
                    int state = rank ? 2 : 0;
                    for (unsigned n = 0; rdy != 0xffffffffffull || state < 2; spin_guard(n)) {
                        if (rdy != 0xffffffffffull) {
                            rdy = ld_acquire((const unsigned long long*)((char*)g_sync.ctx + 8 * m));
                            asm volatile("st.release.cta.shared.u64 [%0], %1;" :: "r"(bars + SM_ORDY), "l"(rdy) : "memory");
                        }
                        unsigned steps = 0;
                        if (state == 1) {
                            steps = ld_acquire(split);
                        } else if (state == 0 && mbar_test(bars + B_WANT, qn & 1)) {
                            state = 1;
                            unsigned seen;
                            asm volatile("atom.acq_rel.gpu.global.exch.b32 %0, [%1], 1;" : "=r"(seen) : "l"(split) : "memory");
                            if (seen) {
                                const unsigned long long v = ld_acquire((const unsigned long long*)((char*)g_sync.step + 8 * tile));
                                const int d = (int)(v >> 32) - (int)v;
                                steps = (WIDE + min(max(half ? d : -d, -12), 12)) >> 1;
                                atomicExch(split, WIDE - steps);
                            }
                        }
                        if (steps > 1) { publish(T_END << 13 | steps, 0); state = 2; }
                    }
                    if (rank) next_item(true);
                }
#pragma unroll 1
                for (uint32_t n = qn; n < qn + QDEPTH && rank == 0; n++) mbar_wait(bars + B_IEMPTY + 8 * (n % QDEPTH), ((n / QDEPTH) & 1) ^ 1);
            }
        }
    } else {
        reg_inc<232>();
        const int wg = (warp >> 2) - 1, wq = warp & 3;
        uint32_t gph = 0;
        uint32_t kvn = 0;
        const uint32_t dA = make_desc(sb + wg * 8192, 16);
        uint32_t ti = 0;
        uint32_t sph = 1;
        const uint32_t stg = sb + SM_STAGING + wg * 16384;
        const uint32_t stg_lane = stg + (wq * 16 + (lane & 15)) * 128 + (((lane >> 4) ^ (lane & 7)) << 4);
        auto write_blocks = [&](auto n, uint32_t off, const uint32_t* v) {
            uint32_t a = stg_lane;
            asm volatile("" : "+r"(a));
            a += off;
#pragma unroll
            for (int j = 0; j < decltype(n)::value; j++)
                stmatrix_x4((a ^ (32 * (j & 3))) + (j >> 2) * 8192, v[4 * j], v[4 * j + 1], v[4 * j + 2], v[4 * j + 3]);
        };
        auto release = [&](uint32_t bar) { mbar_arrive_if(lane == 0, bars + bar); };
        const uint32_t bars_lane = map_cta(bars, lane & 1);
        auto release_stage = [&](uint32_t st) { mbar_arrive_cluster_if(lane < 2, bars_lane + B_GEMPTY + 8 * st); };
        auto take_item = [&]() -> int {
            return __shfl_sync(0xffffffffu, next_item(lane == 0, false), 0);
        };
        auto stage_acquire = [&](int b) { mbar_spin(bars + B_SEMPTY + 16 * wg + 8 * b, sph); };
        auto stage_publish = [&](int b) {
            __syncwarp();
            release(B_SFULL + 16 * wg + 8 * b);
        };
        auto stage_chunk = [&](int b, const uint32_t* v) {
            stage_acquire(b);
            write_blocks(std::integral_constant<int, 4>(), b * 8192, v);
            stage_publish(b);
            if (b) sph ^= 1;
        };
        auto publish_pair = [&]() {
            __syncwarp();
            mbar_arrive_if(lane < 2, bars + B_SFULL + 16 * wg + 8 * lane);
            sph ^= 1;
        };
        auto gemm_step = [&](float (&acc)[128], uint32_t dB, int& k, bool order) {
            const uint32_t st = k & 3;
            wgmma_wait<0>();
            release_stage((k - 1) & 3);
            mbar_spin(bars + B_GFULL + 8 * st, gph);
            const uint64_t da = full_desc(dA + st * (GST_BYTES >> 4)), db = full_desc(dB + st * (GST_BYTES >> 4));
            if (order && wg) bar_sync(3, 256);
            wgmma_fence();
#pragma unroll
            for (int kk = 0; kk < 4; kk++) wgmma_ss_n256_tb(acc, da + 2 * kk, db + 128 * kk, 1);
            wgmma_commit();
            if (order && !wg) bar_arrive(3, 256);
            gph ^= st == 3;
            k++;
        };
        if (wg == 1) bar_arrive(1, 256);
        int it = first_item();
        float s[64];
        const uint32_t dK = make_desc(sb + SM_KV, 16);
        auto kv_wait = [&](uint32_t n) { mbar_spin(bars + B_AFULL + 16 + 8 * (n & 3), (n >> 2) & 1); };
        auto first_scores = [&](bool valid) {
            if (valid) { mbar_spin(bars + B_AFULL + 8 * (ti & 1), (ti >> 1) & 1); kv_wait(kvn); }
            bar_sync(1 + wg, 256);
            qk_gemm(s, dA + (ti & 1) * 2048, dK + (kvn & 3) * 2048);
        };
        bool issued;
        {
            {
                float acc[128];
                uint32_t pk[64];
                bool pending = false;
                int held = T_END;
                auto scale_q = [&](int j0) {
                    if (held != T_Q) return;
#pragma unroll
                    for (int j = j0; j < j0 + 16; j++)
                        asm("{\n.reg .b32 t;\nmul.rn.bf16x2 t, %0, %2;\nfma.rn.bf16x2 %0, %0, %1, t;\n}\n" : "+r"(pk[j]) : "r"(0x3e033e03u), "r"(0xb9d8b9d8u));
                };
                zero_regs(pk);
                const uint32_t dB = make_desc(sb + 16384, 8192);
                do {
                    if (item_type(it) == T_LOCAL) {
                        int ln = lane;
                        asm volatile("" : "+r"(ln));
                        const int g = ln >> 2, t = ln & 3, par = wq & 1;
                        const uint32_t hc = (wq >> 1) * 4, pl = sb + (par * 2 + wg) * LOC_PLANE;
                        const uint32_t a16 = (ln & 15) * 128 + (((hc + (ln >> 4)) ^ (ln & 7)) << 4), a8 = (ln & 7) * 128 + (((hc + (ln >> 3)) ^ (ln & 7)) << 4);
                        const bool first0 = 2 * t > g, first1 = 2 * t + 1 > g;
                        const uint32_t fmask = (first0 ? 0xffffu : 0u) | (first1 ? 0xffff0000u : 0u);
                        const bool edge = item_row(it) == 0;
                        uint32_t q[4][2][4], kf[9][4], vf[9][4];
                        float w[8];
                        mbar_spin(bars + B_GFULL, gph);
#pragma unroll
                        for (int u = 0; u < 4; u++) { ldsm_x4(q[u][0], pl + u * 2048 + a16); ldsm_x4(q[u][1], pl + u * 2048 + (a16 ^ 32)); }
#pragma unroll
                        for (int j = 0; j < 8; j++) w[j] = lds_f32(sb + 4 * LOC_PLANE + 4 * (2 * g + par) + 64 * j);
                        __syncwarp();
                        release_stage(0);
                        mbar_spin(bars + B_GFULL + 8, gph);
#pragma unroll
                        for (int n = 0; n < 9; n++) ldsm_x4(kf[n], pl + GST_BYTES + n * 1024 + a8);
                        __syncwarp();
                        release_stage(1);
                        float s[8][2];
#pragma unroll
                        for (int u = 0; u < 4; u++) {
                            float d[3][4];
#pragma unroll
                            for (int nt = 0; nt < 3; nt++) {
                                mma_k16_init(d[nt], q[u][0], kf[2 * u + nt][0], kf[2 * u + nt][1]);
                                mma_k16(d[nt], q[u][1], kf[2 * u + nt][2], kf[2 * u + nt][3]);
                            }
                            if (u == 0 && edge) { d[0][0] = -INFINITY; d[0][1] = -INFINITY; }
                            s[2 * u][0] = first0 ? d[0][0] : d[1][0]; s[2 * u][1] = first1 ? d[0][1] : d[1][1];
                            s[2 * u + 1][0] = first0 ? d[1][2] : d[2][2]; s[2 * u + 1][1] = first1 ? d[1][3] : d[2][3];
                        }
                        mbar_spin(bars + B_GFULL + 16, gph);
#pragma unroll
                        for (int u = 0; u < 4; u++) { ldsm_x4_t(vf[2 * u], pl + 2 * GST_BYTES + u * 2048 + a16); ldsm_x4_t(vf[2 * u + 1], pl + 2 * GST_BYTES + u * 2048 + (a16 ^ 32)); }
                        ldsm_x4_t(vf[8], pl + 2 * GST_BYTES + 8192 + a8);
                        __syncwarp();
                        release_stage(2);
                        float x[8];
#pragma unroll
                        for (int j = 0; j < 8; j++) x[j] = fmaxf(s[j][0], s[j][1]);
#pragma unroll
                        for (int o = 1; o < 4; o *= 2)
#pragma unroll
                            for (int j = 0; j < 8; j++) x[j] = fmaxf(x[j], __shfl_xor_sync(0xffffffffu, x[j], o));
#pragma unroll
                        for (int j = 0; j < 8; j++) {
                            const float n = x[j] * -LOC_SCALE;
                            s[j][0] = ex2(fmaf(s[j][0], LOC_SCALE, n)); s[j][1] = ex2(fmaf(s[j][1], LOC_SCALE, n));
                            x[j] = s[j][0] + s[j][1];
                        }
#pragma unroll
                        for (int o = 1; o < 4; o *= 2)
#pragma unroll
                            for (int j = 0; j < 8; j++) x[j] += __shfl_xor_sync(0xffffffffu, x[j], o);
                        mbar_spin(bars + B_GFULL + 24, gph);
                        release_stage(3);
                        it = take_item();
                        uint32_t ob[4][8];
#pragma unroll
                        for (int u = 0; u < 4; u++) {
                            const float r0 = rcp(x[2 * u]), r1 = rcp(x[2 * u + 1]), f0 = fmaf(-w[2 * u], r0, r0), f1 = fmaf(-w[2 * u + 1], r1, r1);
                            const uint32_t p0 = pack_bf16(s[2 * u][0] * f0, s[2 * u][1] * f0), p1 = pack_bf16(s[2 * u + 1][0] * f1, s[2 * u + 1][1] * f1);
                            const uint32_t pa[4] = {p0 & fmask, 0, p0 & ~fmask, p1 & fmask};
#pragma unroll
                            for (int c = 0; c < 4; c++) {
                                float ol[4];
                                mma_k16_init(ol, pa, vf[2 * u + (c >> 1)][2 * (c & 1)], vf[2 * u + (c >> 1)][2 * (c & 1) + 1]);
                                mma_k8(ol, 0, p1 & ~fmask, u < 3 ? vf[2 * u + 2 + (c >> 1)][2 * (c & 1)] : vf[8][c]);
                                ob[u][2 * c] = pack_bf16(ol[0], ol[1]);
                                ob[u][2 * c + 1] = pack_bf16(ol[2], ol[3]);
                            }
                        }
                        stage_acquire(0); stage_acquire(1);
#pragma unroll
                        for (int u = 0; u < 4; u++) {
                            stmatrix_x4(stg + par * 8192 + u * 2048 + a16, ob[u][0], ob[u][1], ob[u][2], ob[u][3]);
                            stmatrix_x4(stg + par * 8192 + u * 2048 + (a16 ^ 32), ob[u][4], ob[u][5], ob[u][6], ob[u][7]);
                        }
                        publish_pair();
                        bar_sync(4, 256);
                        gph ^= 1;
                        continue;
                    }
                    mbar_spin(bars + B_GFULL, gph);
                    bool more;
                    do {
                        wgmma_fence();
                        wgmma_ss_n256_tb_init(acc, full_desc(dA), full_desc(dB));
#pragma unroll
                        for (int kk = 1; kk < 4; kk++) wgmma_ss_n256_tb(acc, full_desc(dA) + 2 * kk, full_desc(dB) + 128 * kk, 1);
                        wgmma_commit();
                        const int type = item_type(it), nk = type == T_K || type == T_V ? 8 : 16;
                        int k = 1;
                        do {
                            if (pending) {
                                if (k == 1) { scale_q(0); stage_chunk(0, pk); }
                                else if (k == 3) { scale_q(16); stage_chunk(1, pk + 16); }
                                else if (k == 5) { scale_q(32); stage_chunk(0, pk + 32); }
                                else if (k == 6) { scale_q(48); stage_chunk(1, pk + 48); }
                            }
                            if (k == nk - 1) it = take_item();
                            gemm_step(acc, dB, k, item_type(it) > T_LOCAL);
                        } while (k < nk);
                        held = type;
                        more = item_type(it) < T_LOCAL;
                        if (more) mbar_spin(bars + B_GFULL, gph);
                        wgmma_wait<0>();
                        fence_regs(acc);
                        release_stage(3);
#pragma unroll
                        for (int j = 0; j < 64; j++) pk[j] = pack_bf16(acc[2 * j], acc[2 * j + 1]);
                        pending = true;
                    } while (more);
                } while (item_type(it) <= T_LOCAL);
                issued = item_type(it) == T_ATTN && (it & ITEM_READY);
                first_scores(issued);
                stage_acquire(0); stage_acquire(1);
                mbar_spin(bars + B_GEMPTY + 8, gph ^ 1);
                write_blocks(std::integral_constant<int, 8>(), 0, pk);
                write_blocks(std::integral_constant<int, 8>(), 32768 - SM_STAGING, pk + 32);
                publish_pair();
                release(B_ALT + 8 * wg);
                bar_arrive(2 - wg, 256);
                wgmma_wait<0>();
                fence_regs(s);
                if (item_type(it) == T_END) it = take_item();
            }
            while (item_type(it) == T_ATTN) {
                if (!issued) { first_scores(true); bar_arrive(2 - wg, 256); wgmma_wait<0>(); fence_regs(s); }
                issued = false;
                float o[64];
                uint32_t pa[32], pb[32];
                float n0 = 0.f, n1 = 0.f;
                int shifted = 0;
                float l0 = 0.f, l1 = 0.f, f0 = 0.f, f1 = 0.f, g0, g1;
                uint32_t has_pv = 0;
                int first = 0;
                int pending = 0;
                const uint32_t dV = make_desc(sb + SM_KV, 16384);
                const uint32_t lane_off = bars_lane - bars + B_AEMPTY - B_AFULL;
                int cur = it;
                uint32_t qoff = (ti & 1) * 2048;
                const int row = wg * 64 + wq * 16 + (lane >> 2);
                const float thr = (row & 63) - (lane & 3) * 2;
                int diag = item_row(cur) == 0 || !item_asc(cur);
                int peek = -1;
                auto kv_release = [&](uint32_t n) { mbar_arrive_cluster_if(lane < 2, bars_lane + B_AEMPTY + 16 + 8 * (n & 3)); };
                struct Slot { uint32_t bar, par, off; } slot[4];
#pragma unroll
                for (uint32_t i = 0; i < 4; i++) {
                    const uint32_t n = kvn + 1 + (i ^ 2);
                    slot[i].bar = bars + B_AFULL + 16 + 8 * (n & 3); slot[i].par = (n >> 2) & 1; slot[i].off = (n & 3) * 2048;
                }
                kvn++;
                auto next_gate = [&]() {
                    g0 = lds_f32(bars + SM_GATE + (ti & 1) * 512 + 4 * row); g1 = lds_f32(bars + SM_GATE + (ti & 1) * 512 + 4 * row + 32);
                    ti++;
                };
                next_gate();
                auto scale_o = [&]() {
#pragma unroll
                    for (int j = 0; j < 16; j++) { o[4 * j] *= f0; o[4 * j + 1] *= f0; o[4 * j + 2] *= f1; o[4 * j + 3] *= f1; }
                };
                auto pack_o = [&](uint32_t (&v)[32]) {
#pragma unroll
                    for (int j = 0; j < 32; j++) v[j] = pack_bf16(o[2 * j], o[2 * j + 1]);
                };
                auto scales = [&]() { f0 = g0 * rcp(quad_sum(l0)); f1 = g1 * rcp(quad_sum(l1)); };
                auto issue = [&](auto even, uint32_t (&pin)[32], uint32_t (&pout)[32], bool fresh, bool last) {
                    constexpr bool EVEN = decltype(even)::value;
                    Slot& sk = slot[EVEN ? 0 : 2];
                    Slot& sv = slot[EVEN ? 1 : 3];
                    kvn += 2;
                    mbar_spin(sk.bar, sk.par);
                    bar_sync(1 + wg, 256);
                    qk_gemm(s, dA + qoff, dK + sk.off);
                    if (EVEN && fresh) {
                        scales();
                        next_gate();
                        n0 = 0.f; n1 = 0.f; l0 = 0.f; l1 = 0.f;
                        shifted = 0;
                        stage_acquire(0); stage_acquire(1);
                    }
                    if (!EVEN && pending) {
                        pack_o(pout);
                        write_blocks(std::integral_constant<int, 4>(), 0, pout);
                    }
                    if (last)
                        asm volatile("{\n.reg .pred P, Q;\n"
                                     "mbarrier.test_wait.parity.shared::cta.b64 Q, [%1], %2;\n"
                                     "mbarrier.test_wait.parity.shared::cta.b64 P, [%3], %4;\n"
                                     "ld.shared.u32 %0, [%5];\n"
                                     "@!Q or.b32 %0, %0, 0x10000;\n"
                                     "@!P mov.u32 %0, -1;\n}\n"
                                     : "=r"(peek) : "r"(bars + B_AFULL + 8 * (ti & 1)), "r"((ti >> 1) & 1), "r"(bars + B_IFULL + 8 * (qn % QDEPTH)),
                                       "r"((qn / QDEPTH) & 1), "r"(bars + SM_QUEUE + 4 * (qn % QDEPTH)) : "memory");
                    diag = item_asc(cur) ? last : fresh;
                    asm volatile("" : "+r"(diag));
                    mbar_spin(sv.bar, sv.par);
                    pv_gemm(o, pin, dV + sv.off, EVEN || !first);
                    bar_arrive(2 - wg, 256);
                    if (!EVEN && pending) {
                        write_blocks(std::integral_constant<int, 4>(), 8192, pout + 16);
                        publish_pair();
                    }
                    sk.par ^= 1; sv.par ^= 1;
                    wgmma_wait<1>();
                    fence_regs(s);
                    mbar_arrive_cluster_if(lane < 2, sk.bar + lane_off);
                    mbar_arrive_if(lane == 0 && last, bars + B_AEMPTY + 8 * ((ti - 1) & 1));
                };
                auto softmax = [&](auto even, uint32_t (&pin)[32], uint32_t (&pout)[32], bool fresh) {
                    constexpr bool EVEN = decltype(even)::value;
                    Slot& sv = slot[EVEN ? 1 : 3];
                    float r0, r1, x0 = n0, x1 = n1;
#pragma unroll 1
                    for (int mask = diag, redone = 0;; mask = 0, redone = 1) {
                        if (mask | shifted) {
                            if (mask) causal_mask(s, thr, wg);
                            if (shifted) shift_rows(s, x0, x1);
                        }
                        exp_pack(pout, s, r0, r1);
                        if (!__any_sync(0xffffffffu, fmaxf(r0, r1) >= SUM_LIMIT || (EVEN && fresh && !(lane & 3) && !(fminf(s[0], s[2]) >= -REF_RANGE))) || redone) break;
                        row_max(s, x0, x1);
                        if (!(EVEN && fresh)) { x0 = fmaxf(x0, 0.f); x1 = fmaxf(x1, 0.f); }
                        float a0 = ex2(-x0), a1 = ex2(-x1);
                        n0 += x0; n1 += x1;
                        shifted = 1;
                        if (EVEN && fresh) { a0 = 1.f; a1 = 1.f; }
                        l0 *= a0; l1 *= a1;
                        wgmma_wait<0>();
                        fence_regs(o);
#pragma unroll
                        for (int q = 0; q < 16; q++) { o[4 * q] *= a0; o[4 * q + 1] *= a0; o[4 * q + 2] *= a1; o[4 * q + 3] *= a1; }
                    }
                    l0 += r0; l1 += r1;
                    wgmma_wait<0>();
                    fence_regs(o);
                    fence_regs(pin);
                    mbar_arrive_cluster_if(lane < 2, sv.bar + lane_off);
                };
                auto copy_p = [&]() {
#pragma unroll
                    for (int j = 0; j < 32; j++) pa[j] = __float_as_uint(__uint_as_float(pb[j]) + __uint_as_float(prm.zero));
                };
                int rem = 0;
                mbar_arrive_if(lane == 0 && item_row(cur) == 0, bars + B_AEMPTY + 8 * ((ti - 1) & 1));
                zero_regs(pa);
                wgmma_fence();
                wgmma_ss_n128_init(o, full_desc(dA), full_desc(dK));
                wgmma_commit();
                while (true) {
                    const bool fresh = rem == 0;
                    softmax(std::true_type(), pa, pb, fresh);
                    first = fresh;
                    if (fresh) {
                        pending = has_pv; has_pv = 1;
                        if (pending) scale_o();
                        rem = item_row(cur) + 1;
                    }
                    if (--rem == 0) {
                        copy_p();
                        const Slot t0 = slot[0], t1 = slot[1];
                        slot[0] = slot[2]; slot[1] = slot[3]; slot[2] = t0; slot[3] = t1;
                    } else {
                        issue(std::false_type(), pb, pa, false, rem == 1);
                        softmax(std::false_type(), pb, pa, false);
                        pending = 0; first = 0;
                        rem--;
                    }
                    if (rem == 0) {
                        const int seen = peek;
                        if (seen >= 0) {
                            mbar_arrive_cluster_if(lane == 0, bars0 + B_IEMPTY + 8 * (qn % QDEPTH));
                            qn++;
                            it = seen & 0xffff;
                        } else {
                            it = take_item();
                        }
                        if (item_row(cur) < 2 || item_type(it) != T_ATTN) break;
                        if (seen & 0x10000) mbar_spin(bars + B_AFULL + 8 * (ti & 1), (ti >> 1) & 1);
                        cur = it;
                        qoff = (ti & 1) * 2048;
                    }
                    issue(std::true_type(), pa, pb, rem == 0, rem ? rem == 1 : item_row(cur) == 0);
                }
                const uint32_t skip = item_asc(cur) & ~item_row(cur) & 1;
                kvn += skip;
                const bool end = item_type(it) == T_END;
#pragma unroll 1
                for (int pass = pending ? 0 : 1; pass < 2; pass++) {
                    if (pass) {
                        kv_wait(kvn);
                        pv_gemm(o, pa, dV + (kvn & 3) * 2048, !first);
                        scales();
                        stage_acquire(0); stage_acquire(1);
                        if (end) it = take_item();
                        wgmma_wait<0>();
                        fence_regs(o);
                        kv_release(kvn);
                        kvn += 1 + skip;
                        scale_o();
                    }
                    pack_o(pb);
                    write_blocks(std::integral_constant<int, 8>(), 0, pb);
                    publish_pair();
                }
            }
        }
        if (item_type(it) == T_OUT) {
            float acc[128];
            const uint32_t dB = make_desc(sb + 16384, 8192);
            mbar_spin(bars + B_GFULL, gph);
            wgmma_fence();
            wgmma_ss_n256_tb_init(acc, full_desc(dA), full_desc(dB));
#pragma unroll
            for (int kk = 1; kk < 4; kk++) wgmma_ss_n256_tb(acc, full_desc(dA) + 2 * kk, full_desc(dB) + 128 * kk, 1);
            wgmma_commit();
            uint32_t ln;
            asm volatile("mov.u32 %0, %%laneid;" : "=r"(ln));
            char* const mine = (char*)prm.out + (uint32_t)((item_row(it) * 128 + wg * 64 + wq * 16 + (ln >> 4)) * 2048 + item_col(it) * 256 + (ln & 15) * 16);
            int k = 1, nk = 80;
            do {
                if ((uint32_t)(k - (K_MEET - 12)) < 8) *(uint4*)(mine + (uint32_t)(k - (K_MEET - 12)) * 4096) = make_uint4(0, 0, 0, 0);
                __syncwarp();
                if (k == K_SPLIT) nk = take_item() & 127;
                gemm_step(acc, dB, k, false);
            } while (k < nk);
            float lo[64];
            auto triple = [&](auto first) {
                const uint32_t s0 = k & 3, s1 = (k + 1) & 3, o0 = s0 * (GST_BYTES >> 4), o1 = s1 * (GST_BYTES >> 4);
                wgmma_wait<0>();
                mbar_arrive_cluster_if(ln < (decltype(first)::value ? 2 : 4), bars_lane + B_GEMPTY + 8 * ((k - 1 - (ln >> 1)) & 3));
                mbar_spin(bars + B_GFULL + 8 * s0, gph);
                gph ^= s0 == 3;
                wgmma_fence();
#pragma unroll
                for (int kk = 0; kk < 4; kk++) {
                    if (decltype(first)::value && kk == 0) wgmma_ss_n128_tb_init(lo, full_desc(dA + o0), full_desc(dB + o0));
                    else wgmma_ss_n128_tb(lo, full_desc(dA + o0) + 2 * kk, full_desc(dB + o0) + 128 * kk, 1);
                }
                mbar_spin(bars + B_GFULL + 8 * s1, gph);
                gph ^= s1 == 3;
                wgmma_fence();
#pragma unroll
                for (int kk = 0; kk < 4; kk++) wgmma_ss_n128_tb(lo, full_desc(dA + o0 + 2048) + 2 * kk, full_desc(dB + o1 + 1024) + 128 * kk, 1);
#pragma unroll
                for (int kk = 0; kk < 4; kk++) wgmma_ss_n128_tb(lo, full_desc(dA + o1) + 2 * kk, full_desc(dB + o1) + 128 * kk, 1);
                wgmma_commit();
                k += 2;
            };
            triple(std::true_type());
            fence_regs(acc);
            uint32_t pk[32];
#pragma unroll
            for (int j = 0; j < 32; j++) pk[j] = pack_bf16(acc[64 + 2 * j], acc[65 + 2 * j]);
            stage_acquire(0); stage_acquire(1);
            write_blocks(std::integral_constant<int, 8>(), 0, pk);
            publish_pair();
            triple(std::false_type());
            stage_acquire(0); stage_acquire(1);
            wgmma_wait<0>();
            fence_regs(lo);
            mbar_arrive_cluster_if(ln < 4, bars_lane + B_GEMPTY + 8 * ((k - 1 - (ln >> 1)) & 3));
#pragma unroll
            for (int b = 0; b < 2; b++) {
#pragma unroll
                for (int j = 16 * b; j < 16 * b + 16; j++) pk[j] = pack_bf16(acc[2 * j] + lo[2 * j], acc[2 * j + 1] + lo[2 * j + 1]);
                write_blocks(std::integral_constant<int, 4>(), b * 8192, pk + 16 * b);
                stage_publish(b);
            }
        }
    }
}

typedef CUresult (*EncodeFn)(CUtensorMap*, CUtensorMapDataType, cuuint32_t, void*, const cuuint64_t*, const cuuint64_t*,
                             const cuuint32_t*, const cuuint32_t*, CUtensorMapInterleave, CUtensorMapSwizzle,
                             CUtensorMapL2promotion, CUtensorMapFloatOOBfill);

void encode3(EncodeFn fn, CUtensorMap* m, const void* ptr, uint64_t d0, uint64_t d1, uint64_t d2, uint64_t s1, uint64_t s2,
             uint32_t b0, uint32_t b1, uint32_t b2) {
    cuuint64_t dims[3] = {d0, d1, d2};
    cuuint64_t strides[2] = {s1, s2};
    cuuint32_t box[3] = {b0, b1, b2};
    cuuint32_t es[3] = {1, 1, 1};
    fn(m, CU_TENSOR_MAP_DATA_TYPE_BFLOAT16, 3, const_cast<void*>(ptr), dims, strides, box, es, CU_TENSOR_MAP_INTERLEAVE_NONE,
       CU_TENSOR_MAP_SWIZZLE_128B, b2 > 1 ? CU_TENSOR_MAP_L2_PROMOTION_L2_256B : CU_TENSOR_MAP_L2_PROMOTION_NONE, CU_TENSOR_MAP_FLOAT_OOB_FILL_NONE);
}
void map_act(EncodeFn fn, CUtensorMap* m, const void* p, int rows, int cols, int box_rows) {
    encode3(fn, m, p, cols, rows, 1, (uint64_t)cols * 2, (uint64_t)cols * rows * 2, 64, box_rows, 1);
}
void map_wgt(EncodeFn fn, CUtensorMap* m, const void* p, int K, int N) {
    encode3(fn, m, p, 64, K, N / 64, (uint64_t)N * 2, 128, 64, 64, 2);
}

void build_schedule(Params& p) {
    int n = 0;
    auto add = [&](int type, int col, int row) { p.items[n++] = (uint16_t)(type << 13 | col << 4 | row); };
    int beta = 26, tail = 32, late = 6, early = 4, epos = 60;
    int order[16] = {6, 7, 8, 9, 10, 11, 12, 13, 14, 15, 5, 4, 3, 2, 1, 0};
    const char* plans = "xxxxxc,xxxlcccc,xxlxlxxc,xxlxlxxc,xxcccccxc,xccclxlccc,xccclxxc,xxcccccc";
    const char* pos[8];
    int len[8] = {}, start[8] = {};
    for (int s = 0; s < 8; s++) { pos[s] = plans; while (*plans && *plans++ != ',') {} }
    for (int i = 0; i < 160; i++) p.plan[i / 16][i % 16] = T_END << 13;
    for (int nx = 0, nc = 3, nl = 0; nx + nc + nl < 28 + 32 + 8;) {
        int s = -1;
        for (int i = 0; i < 8; i++) if (*pos[i] > ',' && (s < 0 || start[i] < start[s])) s = i;
        const char kind = *pos[s]++;
        int it;
        if (kind == 'x') { it = nx < 12 ? T_B << 13 | (nx % 3 * 4 + nx / 3) << 4 : T_Q << 13 | (nx - 12) << 4; nx++; }
        else if (kind == 'c') { it = (T_K + (nc & 1)) << 13 | nc / 2 << 4; nc++; }
        else { it = T_LOCAL << 13 | nl / 2 << 4 | (nl & 1); nl++; }
        p.plan[s][len[s]++] = (uint16_t)it;
        start[s] += kind == 'x' ? 48 : kind == 'c' ? 24 : 8;
    }
    for (int i = 0; i < 24; i++) p.plan[8 + i / 12][i % 12] = (uint16_t)((T_K + (i % 3 & 1)) << 13 | i % 3 / 2 << 4 | i / 3);
    const int a0 = n;
    for (int key = 0; key < 4000; key++)
        for (int r = 0; r < 32; r++)
            for (int j = 7; j >= 0; j--)
                if ((j ? (7 - j) * 40 + r * beta : 3999) == key) add(T_ATTN, 2 * order[r >> 1] + (r & 1), j);
    int t0 = n;
    for (int work = 0; work < 32 * 136 * tail / 100;) work += 4 * (p.items[--t0] & 15) + 3;
    for (int i = t0 + 1; i < n; i++)
        for (int j = i; j > t0 && (p.items[j] & 15) > (p.items[j - 1] & 15); j--) { const uint16_t t = p.items[j]; p.items[j] = p.items[j - 1]; p.items[j - 1] = t; }
    for (int r = early - 1; r >= 0; r--) {
        const uint16_t t = p.items[n - 32 + early - 1];
        for (int j = n - 32 + early - 1; j > n - epos; j--) p.items[j] = p.items[j - 1];
        p.items[n - epos] = t;
    }
    for (int moved = 0; moved < 2 && late >= 0; moved++)
        for (int i = a0; i < n; i++)
            if (p.items[i] == (T_ATTN << 13 | (2 * order[15] + moved) << 4 | late)) {
                for (int j = i; j + 1 < n; j++) p.items[j] = p.items[j + 1];
                p.items[n - 1] = (uint16_t)(T_ATTN << 13 | (2 * order[15] + moved) << 4 | late);
                break;
            }
    for (int s = 0, lo = 0, hi = WIDE - 1; s < 80; s++) {
        const int r = s / 2, g = r < 8 ? 32 + r : 2 * order[r / 2 - 4] + (r & 1);
        p.ostep[s >= WIDE ? s : r & 1 ? hi-- : lo++] = (uint8_t)(2 * g + (s & 1));
    }
}

void build_params(Params& p, void* const* d_in, void* d_out) {
    void* fnp = nullptr;
    cudaDriverEntryPointQueryResult qr;
    cudaGetDriverEntryPoint("cuTensorMapEncodeTiled", &fnp, cudaEnableDefault, &qr);
    EncodeFn fn = (EncodeFn)fnp;
    void* scr = nullptr;
    cudaGetSymbolAddress(&scr, g_scr);
    map_act(fn, &p.m[M_X], d_in[0], SEQ, 1024, 128);
    map_act(fn, &p.m[M_C], d_in[1], SEQ, 512, 128);
    map_wgt(fn, &p.m[M_WQ], d_in[2], 1024, 4096);
    map_wgt(fn, &p.m[M_WUK], d_in[3], 512, 4096);
    map_wgt(fn, &p.m[M_WUV], d_in[4], 512, 4096);
    map_wgt(fn, &p.m[M_WO], d_in[5], 4096, 1024);
    map_wgt(fn, &p.m[M_WQKV], d_in[7], 1024, 3072);
    map_wgt(fn, &p.m[M_WOB], d_in[8], 1024, 1024);
    encode3(fn, &p.m[M_SCR_LD], scr, 128, SEQ, G_TOTAL, 256, (uint64_t)SEQ * 256, 64, 128, 1);
    encode3(fn, &p.m[M_SCR_LOC], scr, 256, SEQ / 2, G_TOTAL, 512, (uint64_t)SEQ * 256, 64, 72, 1);
    encode3(fn, &p.m[M_SCR_LOQ], scr, 256, SEQ / 2, G_TOTAL, 512, (uint64_t)SEQ * 256, 64, 64, 1);
    encode3(fn, &p.m[M_SCR_ST], scr, 128, SEQ, G_TOTAL, 256, (uint64_t)SEQ * 256, 64, 64, 1);
    map_act(fn, &p.m[M_OUT], d_out, SEQ, 1024, 64);
    p.x = (const __nv_bfloat16*)d_in[0];
    p.gate_w = (const __nv_bfloat16*)d_in[9];
    p.zero = 0;
    p.wo = (const char*)d_in[5];
    p.out = (__nv_bfloat16*)d_out;
    build_schedule(p);
}

}

extern "C" void kernel_launch(void* const* d_in, const int* in_sizes, int n_in, void* d_out, int out_size) {
    (void)in_sizes; (void)n_in; (void)out_size;
    Params p;
    build_params(p, d_in, d_out);
    cudaFuncSetAttribute(fused_kernel, cudaFuncAttributeMaxDynamicSharedMemorySize, SM_TOTAL);
    fused_kernel<<<NCTA, 384, SM_TOTAL>>>(p);
}
```

```cpp
#include <cuda_runtime.h>
#include <cuda_bf16.h>
#include <cuda.h>
#include <stddef.h>
#include <stdint.h>
#include <type_traits>

namespace {

constexpr int SEQ = 2048;
constexpr int G_Q = 0, G_K = 32, G_V = 64, G_B = 96, G_CTX = G_Q, G_LOC = G_B, G_TOTAL = 120;

__device__ __align__(1024) __nv_bfloat16 g_scr[(size_t)G_TOTAL * SEQ * 128];
__device__ __align__(128) float g_gate[SEQ];

__device__ __forceinline__ uint32_t smem_u32(const void* p) { return (uint32_t)__cvta_generic_to_shared(p); }
__device__ __forceinline__ bool elect_one() {
    uint32_t p;
    asm volatile("{\n.reg .pred P;\nelect.sync _|P, 0xffffffff;\nselp.u32 %0, 1, 0, P;\n}\n" : "=r"(p));
    return p != 0;
}
__device__ __forceinline__ void mbar_init(uint32_t bar, uint32_t count) {
    asm volatile("mbarrier.init.shared::cta.b64 [%0], %1;" :: "r"(bar), "r"(count) : "memory");
}
__device__ __forceinline__ uint32_t cluster_rank() { uint32_t r; asm("mov.u32 %0, %%cluster_ctarank;" : "=r"(r)); return r; }
__device__ __forceinline__ uint32_t map_cta(uint32_t addr, uint32_t cta) {
    uint32_t r; asm("mapa.shared::cluster.u32 %0, %1, %2;" : "=r"(r) : "r"(addr), "r"(cta)); return r;
}
__device__ __forceinline__ void mbar_arrive_cluster_if(bool pred, uint32_t cluster_bar) {
    asm volatile("{\n.reg .pred P;\nsetp.ne.u32 P, %1, 0;\n@P mbarrier.arrive.shared::cluster.b64 _, [%0];\n}\n"
                 :: "r"(cluster_bar), "r"((uint32_t)pred) : "memory");
}
__device__ __forceinline__ void mbar_arrive_cluster_n_if(bool pred, uint32_t cluster_bar, uint32_t count) {
    asm volatile("{\n.reg .pred P;\nsetp.ne.u32 P, %1, 0;\n@P mbarrier.arrive.shared::cluster.b64 _, [%0], %2;\n}\n"
                 :: "r"(cluster_bar), "r"((uint32_t)pred), "r"(count) : "memory");
}
__device__ __forceinline__ void mbar_arrive_if(bool pred, uint32_t bar) {
    asm volatile("{\n.reg .pred P;\nsetp.ne.u32 P, %1, 0;\n@P mbarrier.arrive.shared::cta.b64 _, [%0];\n}\n"
                 :: "r"(bar), "r"((uint32_t)pred) : "memory");
}
__device__ __forceinline__ bool mbar_test(uint32_t bar, uint32_t parity) {
    uint32_t ok;
    asm volatile("{\n.reg .pred P;\nmbarrier.test_wait.parity.shared::cta.b64 P, [%1], %2;\nselp.u32 %0, 1, 0, P;\n}\n"
                 : "=r"(ok) : "r"(bar), "r"(parity) : "memory");
    return ok != 0;
}
__device__ __forceinline__ void mbar_wait(uint32_t bar, uint32_t parity) {
    asm volatile("{\n.reg .pred P;\n.reg .u32 c;\n"
                 "mov.u32 c, 0;\n"
                 "SPIN:\n"
                 "mbarrier.try_wait.parity.shared::cta.b64 P, [%0], %1;\n"
                 "@P bra DONE;\n"
                 "add.u32 c, c, 1;\n"
                 "setp.lt.u32 P, c, 4194304;\n"
                 "@P bra SPIN;\n"
                 "trap;\n"
                 "DONE:\n}\n" :: "r"(bar), "r"(parity) : "memory");
}
__device__ __forceinline__ void mbar_spin(uint32_t bar, uint32_t parity) {
    asm volatile("{\n.reg .pred P;\n"
                 "SPIN:\n"
                 "mbarrier.try_wait.parity.shared::cta.b64 P, [%0], %1;\n"
                 "@!P bra SPIN;\n}\n" :: "r"(bar), "r"(parity) : "memory");
}
__device__ __forceinline__ void bar_sync(int id, int n) { asm volatile("bar.sync %0, %1;" :: "r"(id), "r"(n) : "memory"); }
__device__ __forceinline__ void bar_arrive(int id, int n) { asm volatile("bar.arrive %0, %1;" :: "r"(id), "r"(n) : "memory"); }
__device__ __forceinline__ void fence_proxy_async_smem() { asm volatile("fence.proxy.async.shared::cta;" ::: "memory"); }
__device__ __forceinline__ void warp_expect_tx(uint32_t bar, uint32_t bytes) {
    asm volatile("{\n.reg .pred P;\nelect.sync _|P, 0xffffffff;\n@P mbarrier.arrive.expect_tx.shared::cta.b64 _, [%0], %1;\n}\n"
                 :: "r"(bar), "r"(bytes) : "memory");
}
constexpr uint64_t EVICT_FIRST = 0x12F0000000000000ull;
__device__ __forceinline__ void warp_tma_load(uint32_t dst, const CUtensorMap* map, uint32_t bar, int c0, int c1, int c2, bool stream) {
    if (stream)
        asm volatile("{\n.reg .pred P;\nelect.sync _|P, 0xffffffff;\n"
                     "@P cp.async.bulk.tensor.3d.shared::cluster.global.mbarrier::complete_tx::bytes.L2::cache_hint"
                     " [%0], [%1, {%3, %4, %5}], [%2], %6;\n}\n"
                     :: "r"(dst), "l"(map), "r"(bar), "r"(c0), "r"(c1), "r"(c2), "l"(EVICT_FIRST) : "memory");
    else
        asm volatile("{\n.reg .pred P;\nelect.sync _|P, 0xffffffff;\n"
                     "@P cp.async.bulk.tensor.3d.shared::cluster.global.mbarrier::complete_tx::bytes [%0], [%1, {%3, %4, %5}], [%2];\n}\n"
                     :: "r"(dst), "l"(map), "r"(bar), "r"(c0), "r"(c1), "r"(c2) : "memory");
}
__device__ __forceinline__ void warp_tma_load_pair(uint32_t dst, const CUtensorMap* map, uint32_t bar, int c0, int c1, int c2, bool stream) {
    if (stream)
        asm volatile("{\n.reg .pred P;\nelect.sync _|P, 0xffffffff;\n"
                     "@P cp.async.bulk.tensor.3d.shared::cluster.global.mbarrier::complete_tx::bytes.multicast::cluster.L2::cache_hint"
                     " [%0], [%1, {%3, %4, %5}], [%2], %6, %7;\n}\n"
                     :: "r"(dst), "l"(map), "r"(bar), "r"(c0), "r"(c1), "r"(c2), "h"((uint16_t)3), "l"(EVICT_FIRST) : "memory");
    else
        asm volatile("{\n.reg .pred P;\nelect.sync _|P, 0xffffffff;\n"
                     "@P cp.async.bulk.tensor.3d.shared::cluster.global.mbarrier::complete_tx::bytes.multicast::cluster"
                     " [%0], [%1, {%3, %4, %5}], [%2], %6;\n}\n"
                     :: "r"(dst), "l"(map), "r"(bar), "r"(c0), "r"(c1), "r"(c2), "h"((uint16_t)3) : "memory");
}
__device__ __forceinline__ void warp_bulk_load(uint32_t dst, const void* src, uint32_t bytes, uint32_t bar) {
    asm volatile("{\n.reg .pred P;\nelect.sync _|P, 0xffffffff;\n"
                 "@P cp.async.bulk.shared::cluster.global.mbarrier::complete_tx::bytes [%0], [%1], %2, [%3];\n}\n"
                 :: "r"(dst), "l"(src), "r"(bytes), "r"(bar) : "memory");
}
__device__ __forceinline__ void warp_tma_store(const CUtensorMap* map, uint32_t src, int c0, int c1, int c2, bool stream) {
    if (stream)
        asm volatile("{\n.reg .pred P;\nelect.sync _|P, 0xffffffff;\n"
                     "@P cp.async.bulk.tensor.3d.global.shared::cta.bulk_group.L2::cache_hint [%0, {%2, %3, %4}], [%1], %5;\n}\n"
                     :: "l"(map), "r"(src), "r"(c0), "r"(c1), "r"(c2), "l"(EVICT_FIRST) : "memory");
    else
        asm volatile("{\n.reg .pred P;\nelect.sync _|P, 0xffffffff;\n"
                     "@P cp.async.bulk.tensor.3d.global.shared::cta.bulk_group [%0, {%2, %3, %4}], [%1];\n}\n"
                     :: "l"(map), "r"(src), "r"(c0), "r"(c1), "r"(c2) : "memory");
}
__device__ __forceinline__ void warp_tma_add(const CUtensorMap* map, uint32_t src, int c0, int c1, int c2) {
    asm volatile("{\n.reg .pred P;\nelect.sync _|P, 0xffffffff;\n"
                 "@P cp.reduce.async.bulk.tensor.3d.global.shared::cta.add.tile.bulk_group [%0, {%2, %3, %4}], [%1];\n}\n"
                 :: "l"(map), "r"(src), "r"(c0), "r"(c1), "r"(c2) : "memory");
}
__device__ __forceinline__ void warp_bulk_store(void* dst, uint32_t src, uint32_t bytes) {
    asm volatile("{\n.reg .pred P;\nelect.sync _|P, 0xffffffff;\n"
                 "@P cp.async.bulk.global.shared::cta.bulk_group [%0], [%1], %2;\n}\n" :: "l"(dst), "r"(src), "r"(bytes) : "memory");
}
__device__ __forceinline__ void warp_prefetch(const void* src, uint32_t bytes) {
    asm volatile("{\n.reg .pred P;\nelect.sync _|P, 0xffffffff;\n@P cp.async.bulk.prefetch.L2.global [%0], %1;\n}\n" :: "l"(src), "r"(bytes) : "memory");
}
__device__ __forceinline__ void bulk_commit() { asm volatile("cp.async.bulk.commit_group;" ::: "memory"); }
template <int N> __device__ __forceinline__ void bulk_wait_read() { asm volatile("cp.async.bulk.wait_group.read %0;" :: "n"(N) : "memory"); }
template <int N> __device__ __forceinline__ void bulk_wait() { asm volatile("cp.async.bulk.wait_group %0;" :: "n"(N) : "memory"); }
__device__ __forceinline__ void wgmma_fence() { asm volatile("wgmma.fence.sync.aligned;" ::: "memory"); }
__device__ __forceinline__ void wgmma_commit() { asm volatile("wgmma.commit_group.sync.aligned;" ::: "memory"); }
template <int N> __device__ __forceinline__ void wgmma_wait() { asm volatile("wgmma.wait_group.sync.aligned %0;" :: "n"(N) : "memory"); }
template <int N> __device__ __forceinline__ void fence_regs(float (&d)[N]) {
#pragma unroll
    for (int i = 0; i < N; i++) asm volatile("" : "+f"(d[i]) :: "memory");
}
template <int N> __device__ __forceinline__ void fence_regs(uint32_t (&d)[N]) {
#pragma unroll
    for (int i = 0; i < N; i++) asm volatile("" : "+r"(d[i]) :: "memory");
}
template <int N> __device__ __forceinline__ void reg_dec() { asm volatile("setmaxnreg.dec.sync.aligned.u32 %0;" :: "n"(N)); }
template <int N> __device__ __forceinline__ void reg_inc() { asm volatile("setmaxnreg.inc.sync.aligned.u32 %0;" :: "n"(N)); }
__device__ __forceinline__ uint32_t pack_bf16(float lo, float hi) {
    uint32_t r; asm("cvt.rn.bf16x2.f32 %0, %1, %2;" : "=r"(r) : "f"(hi), "f"(lo)); return r;
}
__device__ __forceinline__ void stmatrix_x4(uint32_t addr, uint32_t r0, uint32_t r1, uint32_t r2, uint32_t r3) {
    asm volatile("stmatrix.sync.aligned.m8n8.x4.shared.b16 [%0], {%1, %2, %3, %4};"
                 :: "r"(addr), "r"(r0), "r"(r1), "r"(r2), "r"(r3) : "memory");
}
__device__ __forceinline__ float ex2(float x) { float y; asm("ex2.approx.ftz.f32 %0, %1;" : "=f"(y) : "f"(x)); return y; }

constexpr uint32_t DESC_HI = (1024 >> 4) | (1u << 30);
__device__ __forceinline__ uint32_t make_desc(uint32_t addr, uint32_t lbo) {
    uint32_t lo = ((addr & 0x3FFFF) >> 4) | ((lbo >> 4) << 16);
    asm volatile("" : "+r"(lo));
    return lo;
}
__device__ __forceinline__ uint64_t full_desc(uint32_t lo) {
    uint64_t d; asm("mov.b64 %0, {%1, %2};" : "=l"(d) : "r"(lo), "r"(DESC_HI)); return d;
}

__device__ __forceinline__ void wgmma_ss_n256_tb_init(float (&d)[128], uint64_t da, uint64_t db) {
    asm volatile("{\n.reg .pred p;\n"
        "setp.ne.b32 p, 0, 0;\n"
        "wgmma.mma_async.sync.aligned.m64n256k16.f32.bf16.bf16 "
        "{%0, %1, %2, %3, %4, %5, %6, %7, %8, %9, %10, %11, %12, %13, %14, %15, %16, %17, %18, %19, %20, "
        "%21, %22, %23, %24, %25, %26, %27, %28, %29, %30, %31, %32, %33, %34, %35, %36, %37, %38, %39, %40, "
        "%41, %42, %43, %44, %45, %46, %47, %48, %49, %50, %51, %52, %53, %54, %55, %56, %57, %58, %59, %60, "
        "%61, %62, %63, %64, %65, %66, %67, %68, %69, %70, %71, %72, %73, %74, %75, %76, %77, %78, %79, %80, "
        "%81, %82, %83, %84, %85, %86, %87, %88, %89, %90, %91, %92, %93, %94, %95, %96, %97, %98, %99, "
        "%100, %101, %102, %103, %104, %105, %106, %107, %108, %109, %110, %111, %112, %113, %114, %115, "
        "%116, %117, %118, %119, %120, %121, %122, %123, %124, %125, %126, %127},"
        " %128, %129, p, 1, 1, 0, 1;\n}\n"
        : "=f"(d[0]), "=f"(d[1]), "=f"(d[2]), "=f"(d[3]), "=f"(d[4]), "=f"(d[5]), "=f"(d[6]), "=f"(d[7]),
        "=f"(d[8]), "=f"(d[9]), "=f"(d[10]), "=f"(d[11]), "=f"(d[12]), "=f"(d[13]), "=f"(d[14]), "=f"(d[15]),
        "=f"(d[16]), "=f"(d[17]), "=f"(d[18]), "=f"(d[19]), "=f"(d[20]), "=f"(d[21]), "=f"(d[22]),
        "=f"(d[23]), "=f"(d[24]), "=f"(d[25]), "=f"(d[26]), "=f"(d[27]), "=f"(d[28]), "=f"(d[29]),
        "=f"(d[30]), "=f"(d[31]), "=f"(d[32]), "=f"(d[33]), "=f"(d[34]), "=f"(d[35]), "=f"(d[36]),
        "=f"(d[37]), "=f"(d[38]), "=f"(d[39]), "=f"(d[40]), "=f"(d[41]), "=f"(d[42]), "=f"(d[43]),
        "=f"(d[44]), "=f"(d[45]), "=f"(d[46]), "=f"(d[47]), "=f"(d[48]), "=f"(d[49]), "=f"(d[50]),
        "=f"(d[51]), "=f"(d[52]), "=f"(d[53]), "=f"(d[54]), "=f"(d[55]), "=f"(d[56]), "=f"(d[57]),
        "=f"(d[58]), "=f"(d[59]), "=f"(d[60]), "=f"(d[61]), "=f"(d[62]), "=f"(d[63]), "=f"(d[64]),
        "=f"(d[65]), "=f"(d[66]), "=f"(d[67]), "=f"(d[68]), "=f"(d[69]), "=f"(d[70]), "=f"(d[71]),
        "=f"(d[72]), "=f"(d[73]), "=f"(d[74]), "=f"(d[75]), "=f"(d[76]), "=f"(d[77]), "=f"(d[78]),
        "=f"(d[79]), "=f"(d[80]), "=f"(d[81]), "=f"(d[82]), "=f"(d[83]), "=f"(d[84]), "=f"(d[85]),
        "=f"(d[86]), "=f"(d[87]), "=f"(d[88]), "=f"(d[89]), "=f"(d[90]), "=f"(d[91]), "=f"(d[92]),
        "=f"(d[93]), "=f"(d[94]), "=f"(d[95]), "=f"(d[96]), "=f"(d[97]), "=f"(d[98]), "=f"(d[99]),
        "=f"(d[100]), "=f"(d[101]), "=f"(d[102]), "=f"(d[103]), "=f"(d[104]), "=f"(d[105]), "=f"(d[106]),
        "=f"(d[107]), "=f"(d[108]), "=f"(d[109]), "=f"(d[110]), "=f"(d[111]), "=f"(d[112]), "=f"(d[113]),
        "=f"(d[114]), "=f"(d[115]), "=f"(d[116]), "=f"(d[117]), "=f"(d[118]), "=f"(d[119]), "=f"(d[120]),
        "=f"(d[121]), "=f"(d[122]), "=f"(d[123]), "=f"(d[124]), "=f"(d[125]), "=f"(d[126]), "=f"(d[127])
        : "l"(da), "l"(db));
}
__device__ __forceinline__ void wgmma_ss_n256_tb(float (&d)[128], uint64_t da, uint64_t db, int scale_d) {
    asm volatile("{\n.reg .pred p;\n"
        "setp.ne.b32 p, %130, 0;\n"
        "wgmma.mma_async.sync.aligned.m64n256k16.f32.bf16.bf16 "
        "{%0, %1, %2, %3, %4, %5, %6, %7, %8, %9, %10, %11, %12, %13, %14, %15, %16, %17, %18, %19, %20, "
        "%21, %22, %23, %24, %25, %26, %27, %28, %29, %30, %31, %32, %33, %34, %35, %36, %37, %38, %39, %40, "
        "%41, %42, %43, %44, %45, %46, %47, %48, %49, %50, %51, %52, %53, %54, %55, %56, %57, %58, %59, %60, "
        "%61, %62, %63, %64, %65, %66, %67, %68, %69, %70, %71, %72, %73, %74, %75, %76, %77, %78, %79, %80, "
        "%81, %82, %83, %84, %85, %86, %87, %88, %89, %90, %91, %92, %93, %94, %95, %96, %97, %98, %99, "
        "%100, %101, %102, %103, %104, %105, %106, %107, %108, %109, %110, %111, %112, %113, %114, %115, "
        "%116, %117, %118, %119, %120, %121, %122, %123, %124, %125, %126, %127},"
        " %128, %129, p, 1, 1, 0, 1;\n}\n"
        : "+f"(d[0]), "+f"(d[1]), "+f"(d[2]), "+f"(d[3]), "+f"(d[4]), "+f"(d[5]), "+f"(d[6]), "+f"(d[7]),
        "+f"(d[8]), "+f"(d[9]), "+f"(d[10]), "+f"(d[11]), "+f"(d[12]), "+f"(d[13]), "+f"(d[14]), "+f"(d[15]),
        "+f"(d[16]), "+f"(d[17]), "+f"(d[18]), "+f"(d[19]), "+f"(d[20]), "+f"(d[21]), "+f"(d[22]),
        "+f"(d[23]), "+f"(d[24]), "+f"(d[25]), "+f"(d[26]), "+f"(d[27]), "+f"(d[28]), "+f"(d[29]),
        "+f"(d[30]), "+f"(d[31]), "+f"(d[32]), "+f"(d[33]), "+f"(d[34]), "+f"(d[35]), "+f"(d[36]),
        "+f"(d[37]), "+f"(d[38]), "+f"(d[39]), "+f"(d[40]), "+f"(d[41]), "+f"(d[42]), "+f"(d[43]),
        "+f"(d[44]), "+f"(d[45]), "+f"(d[46]), "+f"(d[47]), "+f"(d[48]), "+f"(d[49]), "+f"(d[50]),
        "+f"(d[51]), "+f"(d[52]), "+f"(d[53]), "+f"(d[54]), "+f"(d[55]), "+f"(d[56]), "+f"(d[57]),
        "+f"(d[58]), "+f"(d[59]), "+f"(d[60]), "+f"(d[61]), "+f"(d[62]), "+f"(d[63]), "+f"(d[64]),
        "+f"(d[65]), "+f"(d[66]), "+f"(d[67]), "+f"(d[68]), "+f"(d[69]), "+f"(d[70]), "+f"(d[71]),
        "+f"(d[72]), "+f"(d[73]), "+f"(d[74]), "+f"(d[75]), "+f"(d[76]), "+f"(d[77]), "+f"(d[78]),
        "+f"(d[79]), "+f"(d[80]), "+f"(d[81]), "+f"(d[82]), "+f"(d[83]), "+f"(d[84]), "+f"(d[85]),
        "+f"(d[86]), "+f"(d[87]), "+f"(d[88]), "+f"(d[89]), "+f"(d[90]), "+f"(d[91]), "+f"(d[92]),
        "+f"(d[93]), "+f"(d[94]), "+f"(d[95]), "+f"(d[96]), "+f"(d[97]), "+f"(d[98]), "+f"(d[99]),
        "+f"(d[100]), "+f"(d[101]), "+f"(d[102]), "+f"(d[103]), "+f"(d[104]), "+f"(d[105]), "+f"(d[106]),
        "+f"(d[107]), "+f"(d[108]), "+f"(d[109]), "+f"(d[110]), "+f"(d[111]), "+f"(d[112]), "+f"(d[113]),
        "+f"(d[114]), "+f"(d[115]), "+f"(d[116]), "+f"(d[117]), "+f"(d[118]), "+f"(d[119]), "+f"(d[120]),
        "+f"(d[121]), "+f"(d[122]), "+f"(d[123]), "+f"(d[124]), "+f"(d[125]), "+f"(d[126]), "+f"(d[127])
        : "l"(da), "l"(db), "r"(scale_d));
}
__device__ __forceinline__ void wgmma_ss_n128_init(float (&d)[64], uint64_t da, uint64_t db) {
    asm volatile("{\n.reg .pred p;\n"
        "setp.ne.b32 p, 0, 0;\n"
        "wgmma.mma_async.sync.aligned.m64n128k16.f32.bf16.bf16 "
        "{%0, %1, %2, %3, %4, %5, %6, %7, %8, %9, %10, %11, %12, %13, %14, %15, %16, %17, %18, %19, %20, "
        "%21, %22, %23, %24, %25, %26, %27, %28, %29, %30, %31, %32, %33, %34, %35, %36, %37, %38, %39, %40, "
        "%41, %42, %43, %44, %45, %46, %47, %48, %49, %50, %51, %52, %53, %54, %55, %56, %57, %58, %59, %60, "
        "%61, %62, %63},"
        " %64, %65, p, 1, 1, 0, 0;\n}\n"
        : "=f"(d[0]), "=f"(d[1]), "=f"(d[2]), "=f"(d[3]), "=f"(d[4]), "=f"(d[5]), "=f"(d[6]), "=f"(d[7]),
        "=f"(d[8]), "=f"(d[9]), "=f"(d[10]), "=f"(d[11]), "=f"(d[12]), "=f"(d[13]), "=f"(d[14]), "=f"(d[15]),
        "=f"(d[16]), "=f"(d[17]), "=f"(d[18]), "=f"(d[19]), "=f"(d[20]), "=f"(d[21]), "=f"(d[22]),
        "=f"(d[23]), "=f"(d[24]), "=f"(d[25]), "=f"(d[26]), "=f"(d[27]), "=f"(d[28]), "=f"(d[29]),
        "=f"(d[30]), "=f"(d[31]), "=f"(d[32]), "=f"(d[33]), "=f"(d[34]), "=f"(d[35]), "=f"(d[36]),
        "=f"(d[37]), "=f"(d[38]), "=f"(d[39]), "=f"(d[40]), "=f"(d[41]), "=f"(d[42]), "=f"(d[43]),
        "=f"(d[44]), "=f"(d[45]), "=f"(d[46]), "=f"(d[47]), "=f"(d[48]), "=f"(d[49]), "=f"(d[50]),
        "=f"(d[51]), "=f"(d[52]), "=f"(d[53]), "=f"(d[54]), "=f"(d[55]), "=f"(d[56]), "=f"(d[57]),
        "=f"(d[58]), "=f"(d[59]), "=f"(d[60]), "=f"(d[61]), "=f"(d[62]), "=f"(d[63])
        : "l"(da), "l"(db));
}
__device__ __forceinline__ void wgmma_ss_n128(float (&d)[64], uint64_t da, uint64_t db, int scale_d) {
    asm volatile("{\n.reg .pred p;\n"
        "setp.ne.b32 p, %66, 0;\n"
        "wgmma.mma_async.sync.aligned.m64n128k16.f32.bf16.bf16 "
        "{%0, %1, %2, %3, %4, %5, %6, %7, %8, %9, %10, %11, %12, %13, %14, %15, %16, %17, %18, %19, %20, "
        "%21, %22, %23, %24, %25, %26, %27, %28, %29, %30, %31, %32, %33, %34, %35, %36, %37, %38, %39, %40, "
        "%41, %42, %43, %44, %45, %46, %47, %48, %49, %50, %51, %52, %53, %54, %55, %56, %57, %58, %59, %60, "
        "%61, %62, %63},"
        " %64, %65, p, 1, 1, 0, 0;\n}\n"
        : "+f"(d[0]), "+f"(d[1]), "+f"(d[2]), "+f"(d[3]), "+f"(d[4]), "+f"(d[5]), "+f"(d[6]), "+f"(d[7]),
        "+f"(d[8]), "+f"(d[9]), "+f"(d[10]), "+f"(d[11]), "+f"(d[12]), "+f"(d[13]), "+f"(d[14]), "+f"(d[15]),
        "+f"(d[16]), "+f"(d[17]), "+f"(d[18]), "+f"(d[19]), "+f"(d[20]), "+f"(d[21]), "+f"(d[22]),
        "+f"(d[23]), "+f"(d[24]), "+f"(d[25]), "+f"(d[26]), "+f"(d[27]), "+f"(d[28]), "+f"(d[29]),
        "+f"(d[30]), "+f"(d[31]), "+f"(d[32]), "+f"(d[33]), "+f"(d[34]), "+f"(d[35]), "+f"(d[36]),
        "+f"(d[37]), "+f"(d[38]), "+f"(d[39]), "+f"(d[40]), "+f"(d[41]), "+f"(d[42]), "+f"(d[43]),
        "+f"(d[44]), "+f"(d[45]), "+f"(d[46]), "+f"(d[47]), "+f"(d[48]), "+f"(d[49]), "+f"(d[50]),
        "+f"(d[51]), "+f"(d[52]), "+f"(d[53]), "+f"(d[54]), "+f"(d[55]), "+f"(d[56]), "+f"(d[57]),
        "+f"(d[58]), "+f"(d[59]), "+f"(d[60]), "+f"(d[61]), "+f"(d[62]), "+f"(d[63])
        : "l"(da), "l"(db), "r"(scale_d));
}
__device__ __forceinline__ void wgmma_rs_n128_tb(float (&d)[64], uint32_t a0, uint32_t a1, uint32_t a2, uint32_t a3, uint64_t db, int scale_d) {
    asm volatile("{\n.reg .pred p;\n"
        "setp.ne.b32 p, %69, 0;\n"
        "wgmma.mma_async.sync.aligned.m64n128k16.f32.bf16.bf16 "
        "{%0, %1, %2, %3, %4, %5, %6, %7, %8, %9, %10, %11, %12, %13, %14, %15, %16, %17, %18, %19, %20, "
        "%21, %22, %23, %24, %25, %26, %27, %28, %29, %30, %31, %32, %33, %34, %35, %36, %37, %38, %39, %40, "
        "%41, %42, %43, %44, %45, %46, %47, %48, %49, %50, %51, %52, %53, %54, %55, %56, %57, %58, %59, %60, "
        "%61, %62, %63},"
        " {%64, %65, %66, %67}, %68, p, 1, 1, 1;\n}\n"
        : "+f"(d[0]), "+f"(d[1]), "+f"(d[2]), "+f"(d[3]), "+f"(d[4]), "+f"(d[5]), "+f"(d[6]), "+f"(d[7]),
        "+f"(d[8]), "+f"(d[9]), "+f"(d[10]), "+f"(d[11]), "+f"(d[12]), "+f"(d[13]), "+f"(d[14]), "+f"(d[15]),
        "+f"(d[16]), "+f"(d[17]), "+f"(d[18]), "+f"(d[19]), "+f"(d[20]), "+f"(d[21]), "+f"(d[22]),
        "+f"(d[23]), "+f"(d[24]), "+f"(d[25]), "+f"(d[26]), "+f"(d[27]), "+f"(d[28]), "+f"(d[29]),
        "+f"(d[30]), "+f"(d[31]), "+f"(d[32]), "+f"(d[33]), "+f"(d[34]), "+f"(d[35]), "+f"(d[36]),
        "+f"(d[37]), "+f"(d[38]), "+f"(d[39]), "+f"(d[40]), "+f"(d[41]), "+f"(d[42]), "+f"(d[43]),
        "+f"(d[44]), "+f"(d[45]), "+f"(d[46]), "+f"(d[47]), "+f"(d[48]), "+f"(d[49]), "+f"(d[50]),
        "+f"(d[51]), "+f"(d[52]), "+f"(d[53]), "+f"(d[54]), "+f"(d[55]), "+f"(d[56]), "+f"(d[57]),
        "+f"(d[58]), "+f"(d[59]), "+f"(d[60]), "+f"(d[61]), "+f"(d[62]), "+f"(d[63])
        : "r"(a0), "r"(a1), "r"(a2), "r"(a3), "l"(db), "r"(scale_d));
}
__device__ __forceinline__ void wgmma_ss_n128_tb_init(float (&d)[64], uint64_t da, uint64_t db) {
    asm volatile("{\n.reg .pred p;\n"
        "setp.ne.b32 p, 0, 0;\n"
        "wgmma.mma_async.sync.aligned.m64n128k16.f32.bf16.bf16 "
        "{%0, %1, %2, %3, %4, %5, %6, %7, %8, %9, %10, %11, %12, %13, %14, %15, %16, %17, %18, %19, %20, "
        "%21, %22, %23, %24, %25, %26, %27, %28, %29, %30, %31, %32, %33, %34, %35, %36, %37, %38, %39, %40, "
        "%41, %42, %43, %44, %45, %46, %47, %48, %49, %50, %51, %52, %53, %54, %55, %56, %57, %58, %59, %60, "
        "%61, %62, %63},"
        " %64, %65, p, 1, 1, 0, 1;\n}\n"
        : "=f"(d[0]), "=f"(d[1]), "=f"(d[2]), "=f"(d[3]), "=f"(d[4]), "=f"(d[5]), "=f"(d[6]), "=f"(d[7]),
        "=f"(d[8]), "=f"(d[9]), "=f"(d[10]), "=f"(d[11]), "=f"(d[12]), "=f"(d[13]), "=f"(d[14]), "=f"(d[15]),
        "=f"(d[16]), "=f"(d[17]), "=f"(d[18]), "=f"(d[19]), "=f"(d[20]), "=f"(d[21]), "=f"(d[22]),
        "=f"(d[23]), "=f"(d[24]), "=f"(d[25]), "=f"(d[26]), "=f"(d[27]), "=f"(d[28]), "=f"(d[29]),
        "=f"(d[30]), "=f"(d[31]), "=f"(d[32]), "=f"(d[33]), "=f"(d[34]), "=f"(d[35]), "=f"(d[36]),
        "=f"(d[37]), "=f"(d[38]), "=f"(d[39]), "=f"(d[40]), "=f"(d[41]), "=f"(d[42]), "=f"(d[43]),
        "=f"(d[44]), "=f"(d[45]), "=f"(d[46]), "=f"(d[47]), "=f"(d[48]), "=f"(d[49]), "=f"(d[50]),
        "=f"(d[51]), "=f"(d[52]), "=f"(d[53]), "=f"(d[54]), "=f"(d[55]), "=f"(d[56]), "=f"(d[57]),
        "=f"(d[58]), "=f"(d[59]), "=f"(d[60]), "=f"(d[61]), "=f"(d[62]), "=f"(d[63])
        : "l"(da), "l"(db));
}
__device__ __forceinline__ void wgmma_ss_n128_tb(float (&d)[64], uint64_t da, uint64_t db, int scale_d) {
    asm volatile("{\n.reg .pred p;\n"
        "setp.ne.b32 p, %66, 0;\n"
        "wgmma.mma_async.sync.aligned.m64n128k16.f32.bf16.bf16 "
        "{%0, %1, %2, %3, %4, %5, %6, %7, %8, %9, %10, %11, %12, %13, %14, %15, %16, %17, %18, %19, %20, "
        "%21, %22, %23, %24, %25, %26, %27, %28, %29, %30, %31, %32, %33, %34, %35, %36, %37, %38, %39, %40, "
        "%41, %42, %43, %44, %45, %46, %47, %48, %49, %50, %51, %52, %53, %54, %55, %56, %57, %58, %59, %60, "
        "%61, %62, %63},"
        " %64, %65, p, 1, 1, 0, 1;\n}\n"
        : "+f"(d[0]), "+f"(d[1]), "+f"(d[2]), "+f"(d[3]), "+f"(d[4]), "+f"(d[5]), "+f"(d[6]), "+f"(d[7]),
        "+f"(d[8]), "+f"(d[9]), "+f"(d[10]), "+f"(d[11]), "+f"(d[12]), "+f"(d[13]), "+f"(d[14]), "+f"(d[15]),
        "+f"(d[16]), "+f"(d[17]), "+f"(d[18]), "+f"(d[19]), "+f"(d[20]), "+f"(d[21]), "+f"(d[22]),
        "+f"(d[23]), "+f"(d[24]), "+f"(d[25]), "+f"(d[26]), "+f"(d[27]), "+f"(d[28]), "+f"(d[29]),
        "+f"(d[30]), "+f"(d[31]), "+f"(d[32]), "+f"(d[33]), "+f"(d[34]), "+f"(d[35]), "+f"(d[36]),
        "+f"(d[37]), "+f"(d[38]), "+f"(d[39]), "+f"(d[40]), "+f"(d[41]), "+f"(d[42]), "+f"(d[43]),
        "+f"(d[44]), "+f"(d[45]), "+f"(d[46]), "+f"(d[47]), "+f"(d[48]), "+f"(d[49]), "+f"(d[50]),
        "+f"(d[51]), "+f"(d[52]), "+f"(d[53]), "+f"(d[54]), "+f"(d[55]), "+f"(d[56]), "+f"(d[57]),
        "+f"(d[58]), "+f"(d[59]), "+f"(d[60]), "+f"(d[61]), "+f"(d[62]), "+f"(d[63])
        : "l"(da), "l"(db), "r"(scale_d));
}

enum { M_X = 0, M_C, M_WQ, M_WUK, M_WUV, M_WQKV, M_WO, M_WOB, M_SCR_LD, M_SCR_LOC, M_SCR_LOQ, M_SCR_ST, M_OUT, M_COUNT };
enum { T_Q = 0, T_K, T_V, T_B, T_OUT, T_LOCAL, T_ATTN, T_END };
constexpr int NCTA = 132;
constexpr int NITEMS = 256;
constexpr int TRIPLES = 2, WIDE = 80 - 3 * TRIPLES;
struct Params {
    CUtensorMap m[M_COUNT];
    const __nv_bfloat16* x;
    const __nv_bfloat16* gate_w;
    const char* wo;
    __nv_bfloat16* out;
    uint32_t zero;
    uint16_t plan[10][16];
    uint16_t items[NITEMS];
    uint8_t ostep[80];
    uint8_t kgroup[16];
};
__device__ __forceinline__ int item_type(int it) { return it >> 13; }
__device__ __forceinline__ int item_row(int it) { return it & 15; }
__device__ __forceinline__ int item_col(int it) { return (it >> 4) & 31; }
__device__ __forceinline__ int item_asc(int it) { return (it >> 9) & 1; }
constexpr int ITEM_READY = 1 << 10;

struct __align__(128) Sync {
    unsigned long long count[4];
    __align__(128) unsigned long long ctx[16];
    unsigned next, next_out, done;
    unsigned used;
    __align__(128) unsigned step[32][2];
    unsigned split[32];
};
__device__ Sync g_sync;

constexpr uint32_t GST_BYTES = 49152, SM_KV = 65536, SM_STAGING = 196608, SM_BARS = SM_STAGING + 32768;
constexpr uint32_t B_GFULL = 0, B_GEMPTY = 32, B_AFULL = 64, B_AEMPTY = 112, B_SFULL = 160, B_SEMPTY = 192,
                   B_IFULL = 224, B_IEMPTY = 288, B_XFREE = 352, B_WANT = 384, B_MEET = 392, B_HALF = 416,
                   SM_ORDY = 448, SM_QUEUE = 456, B_ALT = 488, B_QFREE = 504, SM_GATE = 512, SM_TOTAL = SM_BARS + 1536;
constexpr int QDEPTH = 8;
constexpr int FIRST_PAIR = 6;
constexpr int K_MEET = 16, K_SPLIT = 30;
constexpr int K_FETCH = 20;
constexpr uint32_t LOC_PLANE = 72 * 128;
constexpr float LOC_SCALE = 0.17677669529663687f * 1.4426950408889634f;
constexpr float SUM_LIMIT = 1180591620717411303424.f;
constexpr float REF_RANGE = 60.f;

__device__ __forceinline__ unsigned ld_acquire(const unsigned* p) {
    unsigned v; asm volatile("ld.acquire.gpu.global.u32 %0, [%1];" : "=r"(v) : "l"(p) : "memory"); return v;
}
__device__ __forceinline__ unsigned long long ld_acquire(const unsigned long long* p) {
    unsigned long long v; asm volatile("ld.acquire.gpu.global.u64 %0, [%1];" : "=l"(v) : "l"(p) : "memory"); return v;
}
__device__ __forceinline__ void spin_guard(unsigned& n) {
    asm volatile("{\n.reg .pred P;\nadd.u32 %0, %0, 1;\nsetp.gt.u32 P, %0, 16777216;\n@P trap;\n}\n" : "+r"(n));
    if (n > 1) __nanosleep(100);
}
__device__ __forceinline__ void red_add(unsigned long long* p, unsigned long long v) {
    asm volatile("red.release.gpu.global.add.u64 [%0], %1;" :: "l"(p), "l"(v) : "memory");
}
__device__ __forceinline__ float rcp(float x) { float y; asm("rcp.approx.ftz.f32 %0, %1;" : "=f"(y) : "f"(x)); return y; }
__device__ __forceinline__ float lds_f32(uint32_t addr) {
    float v; asm volatile("ld.shared.f32 %0, [%1];" : "=f"(v) : "r"(addr) : "memory"); return v;
}
__device__ __forceinline__ void ldsm_x4(uint32_t (&r)[4], uint32_t addr) {
    asm volatile("ldmatrix.sync.aligned.m8n8.x4.shared.b16 {%0, %1, %2, %3}, [%4];"
                 : "=r"(r[0]), "=r"(r[1]), "=r"(r[2]), "=r"(r[3]) : "r"(addr) : "memory");
}
__device__ __forceinline__ void ldsm_x4_t(uint32_t (&r)[4], uint32_t addr) {
    asm volatile("ldmatrix.sync.aligned.m8n8.x4.trans.shared.b16 {%0, %1, %2, %3}, [%4];"
                 : "=r"(r[0]), "=r"(r[1]), "=r"(r[2]), "=r"(r[3]) : "r"(addr) : "memory");
}
__device__ __forceinline__ void mma_k16(float (&d)[4], const uint32_t (&a)[4], uint32_t b0, uint32_t b1) {
    asm("mma.sync.aligned.m16n8k16.row.col.f32.bf16.bf16.f32 {%0,%1,%2,%3}, {%4,%5,%6,%7}, {%8,%9}, {%0,%1,%2,%3};"
        : "+f"(d[0]), "+f"(d[1]), "+f"(d[2]), "+f"(d[3]) : "r"(a[0]), "r"(a[1]), "r"(a[2]), "r"(a[3]), "r"(b0), "r"(b1));
}
__device__ __forceinline__ void mma_k16_init(float (&d)[4], const uint32_t (&a)[4], uint32_t b0, uint32_t b1) {
    asm("{\n.reg .f32 z;\nmov.f32 z, 0f00000000;\n"
        "mma.sync.aligned.m16n8k16.row.col.f32.bf16.bf16.f32 {%0,%1,%2,%3}, {%4,%5,%6,%7}, {%8,%9}, {z,z,z,z};\n}\n"
        : "=f"(d[0]), "=f"(d[1]), "=f"(d[2]), "=f"(d[3]) : "r"(a[0]), "r"(a[1]), "r"(a[2]), "r"(a[3]), "r"(b0), "r"(b1));
}
__device__ __forceinline__ void mma_k8(float (&d)[4], uint32_t a0, uint32_t a1, uint32_t b0) {
    asm("mma.sync.aligned.m16n8k8.row.col.f32.bf16.bf16.f32 {%0,%1,%2,%3}, {%4,%5}, {%6}, {%0,%1,%2,%3};"
        : "+f"(d[0]), "+f"(d[1]), "+f"(d[2]), "+f"(d[3]) : "r"(a0), "r"(a1), "r"(b0));
}
template <typename T, int N> __device__ __forceinline__ void zero_regs(T (&d)[N]) {
#pragma unroll
    for (int i = 0; i < N; i++) d[i] = 0;
}
__device__ __forceinline__ float quad_max(float v) {
    v = fmaxf(v, __shfl_xor_sync(0xffffffffu, v, 1));
    return fmaxf(v, __shfl_xor_sync(0xffffffffu, v, 2));
}
__device__ __forceinline__ float quad_sum(float v) {
    v += __shfl_xor_sync(0xffffffffu, v, 1);
    return v + __shfl_xor_sync(0xffffffffu, v, 2);
}

__device__ __forceinline__ void qk_gemm(float (&s)[64], uint32_t q_lo, uint32_t k_lo) {
    const uint64_t dq = full_desc(q_lo), dk = full_desc(k_lo);
    wgmma_fence();
    wgmma_ss_n128_init(s, dq, dk);
#pragma unroll
    for (int kk = 1; kk < 8; kk++) {
        const uint32_t o = (kk >> 2) * 1024 + (kk & 3) * 2;
        wgmma_ss_n128(s, dq + o, dk + o, 1);
    }
    wgmma_commit();
}
__device__ __forceinline__ void pv_gemm(float (&o)[64], uint32_t (&p)[32], uint32_t v_lo, int accumulate) {
    const uint64_t dv = full_desc(v_lo);
    fence_regs(o);
    fence_regs(p);
    wgmma_fence();
#pragma unroll
    for (int kk = 0; kk < 8; kk++)
        wgmma_rs_n128_tb(o, p[4 * kk], p[4 * kk + 1], p[4 * kk + 2], p[4 * kk + 3], dv + kk * 128, kk != 0 || accumulate);
    wgmma_commit();
}
__device__ __forceinline__ void row_max(const float (&s)[64], float& x0, float& x1) {
    float z0 = fmaxf(s[0], s[1]), z1 = fmaxf(s[2], s[3]);
    x0 = fmaxf(s[4], s[5]); x1 = fmaxf(s[6], s[7]);
#pragma unroll
    for (int j = 2; j < 16; j += 2) {
        z0 = fmaxf(z0, fmaxf(s[4 * j], s[4 * j + 1]));
        z1 = fmaxf(z1, fmaxf(s[4 * j + 2], s[4 * j + 3]));
        x0 = fmaxf(x0, fmaxf(s[4 * j + 4], s[4 * j + 5]));
        x1 = fmaxf(x1, fmaxf(s[4 * j + 6], s[4 * j + 7]));
    }
    x0 = quad_max(fmaxf(x0, z0)); x1 = quad_max(fmaxf(x1, z1));
}
__device__ __forceinline__ void exp_pack(uint32_t (&p)[32], const float (&s)[64], float& r0, float& r1) {
#pragma unroll
    for (int j = 0; j < 16; j++) {
        const float e0 = ex2(s[4 * j]), e1 = ex2(s[4 * j + 1]), e2 = ex2(s[4 * j + 2]), e3 = ex2(s[4 * j + 3]);
        if (j == 0) { r0 = e0 + e1; r1 = e2 + e3; }
        else { r0 += e0 + e1; r1 += e2 + e3; }
        p[2 * j] = pack_bf16(e0, e1);
        p[2 * j + 1] = pack_bf16(e2, e3);
    }
}
__device__ __forceinline__ void shift_rows(float (&s)[64], float d0, float d1) {
#pragma unroll
    for (int j = 0; j < 16; j++) { s[4 * j] -= d0; s[4 * j + 1] -= d0; s[4 * j + 2] -= d1; s[4 * j + 3] -= d1; }
}
constexpr float MASKED = -3e38f;
template <int J0>
__device__ __forceinline__ void mask_triangle(float (&s)[64], float thr) {
#pragma unroll
    for (int j = 0; j < 16; j++) {
        const float m = __saturatef((float)(8 * (j >> 1) + (j & 1)) - thr);
        const int i = 4 * (J0 + (j >> 1)) + (j & 1);
        s[i] = fmaf(m, MASKED, s[i]);
        if (j < 14) s[i + 6] = fmaf(m, MASKED, s[i + 6]);
    }
}
__device__ __forceinline__ void causal_mask(float (&s)[64], float thr, int wg) {
    asm volatile("" : "+f"(thr));
    if (wg == 0) {
        mask_triangle<0>(s, thr);
#pragma unroll
        for (int j = 32; j < 64; j++) s[j] += MASKED;
    } else {
        mask_triangle<8>(s, thr);
    }
}

__global__ void __cluster_dims__(2, 1, 1) __launch_bounds__(384, 1) fused_kernel(const __grid_constant__ Params prm) {
    extern __shared__ __align__(1024) uint8_t smem[];
    const uint32_t sb = smem_u32(smem), bars = sb + SM_BARS;
    const int warp = __shfl_sync(0xffffffffu, threadIdx.x >> 5, 0), lane = threadIdx.x & 31;

    const uint32_t rank = cluster_rank();
    const uint32_t bars0 = map_cta(bars, 0), bars_peer = map_cta(bars, rank ^ 1);

    auto plan_index = [&]() -> uint32_t {
        uint32_t p = blockIdx.x >> 1;
        asm volatile("" : "+r"(p));
        const uint32_t r = (p - 36) * 37 >> 8;
        return p < 4 ? 4 + p : p < 36 ? (p - 4 & 7) * 8 + (p - 4 >> 3) : p < 64 ? (p - 35 - 7 * r) * 8 + 4 + r : p;
    };
    auto first_item = [&]() -> int {
        const uint32_t pair = plan_index();
        const uint32_t slot = pair & 7, c = slot * 11 >> 5;
        return pair < 64 ? T_B << 13 | (4 * slot - 11 * c) << 4 | (2 * (pair >> 3) + rank) : T_K << 13 | (8 * slot + rank);
    };
    if (warp == 0) {
        if (elect_one())
            for (int k = 0; k < 4; k++) mbar_init(bars + B_GFULL + 8 * k, 1);
        const int first_it = __shfl_sync(0xffffffffu, first_item(), 0);
        asm volatile("fence.mbarrier_init.release.cluster;" ::: "memory");
        fence_proxy_async_smem();
        __syncwarp();
        asm volatile("barrier.cluster.arrive.relaxed.aligned;" ::: "memory");
        const CUtensorMap* ma = &prm.m[item_type(first_it) == T_K ? M_C : M_X];
        const CUtensorMap* mb = &prm.m[M_WQ + item_type(first_it)];
#pragma unroll
        for (int k = 0; k < 2; k++) {
            const uint32_t dst = sb + k * GST_BYTES, fb = bars + B_GFULL + 8 * k;
            warp_expect_tx(fb, GST_BYTES);
            warp_tma_load(dst + 16384, mb, fb, 0, k * 64, item_col(first_it) * 4, true);
            warp_tma_load(dst, ma, fb, k * 64, item_row(first_it) * 128, 0, false);
            warp_tma_load(dst + 32768, mb, fb, 0, k * 64, item_col(first_it) * 4 + 2, true);
        }
    }
    if (threadIdx.x == 32) {
        for (int i = 0; i < 4; i++) mbar_init(bars + B_GEMPTY + 8 * i, 16);
        for (int i = 0; i < 6; i++) { mbar_init(bars + B_AFULL + 8 * i, 1); mbar_init(bars + B_AEMPTY + 8 * i, i < 2 ? 8 : 16); }
        for (int i = 0; i < 4; i++) { mbar_init(bars + B_SFULL + 8 * i, 4); mbar_init(bars + B_SEMPTY + 8 * i, 1); }
        for (int i = 0; i < QDEPTH; i++) { mbar_init(bars + B_IFULL + 8 * i, 1); mbar_init(bars + B_IEMPTY + 8 * i, 23); }
        mbar_init(bars + B_WANT, 2); mbar_init(bars + B_MEET, 1); mbar_init(bars + B_XFREE, 1);
        for (int i = 0; i < 4; i++) mbar_init(bars + B_HALF + 8 * i, 1);
        mbar_init(bars + B_ALT, 4); mbar_init(bars + B_ALT + 8, 4); mbar_init(bars + B_QFREE, 2);
        asm volatile("st.shared.u64 [%0], 0;" :: "r"(bars + SM_ORDY) : "memory");
        asm volatile("fence.mbarrier_init.release.cluster;\nfence.acq_rel.cta;" ::: "memory");
    }
    __syncwarp();
    if (warp != 0) asm volatile("barrier.cluster.arrive.relaxed.aligned;" ::: "memory");
    asm volatile("barrier.cluster.wait.acquire.aligned;" ::: "memory");

    uint32_t qn = 0;
    auto next_item = [&](bool releaser, bool bounded = true) -> int {
        const uint32_t slot = qn % QDEPTH;
        if (bounded) mbar_wait(bars + B_IFULL + 8 * slot, (qn / QDEPTH) & 1);
        else mbar_spin(bars + B_IFULL + 8 * slot, (qn / QDEPTH) & 1);
        uint32_t it;
        asm volatile("ld.shared.u32 %0, [%1];" : "=r"(it) : "r"(bars + SM_QUEUE + 4 * slot) : "memory");
        mbar_arrive_cluster_if(releaser, bars0 + B_IEMPTY + 8 * slot);
        qn++;
        return it;
    };

    if (warp < 4) {
        reg_dec<40>();
        if (warp == 0) {
            {
                uint32_t gph = 1;
                const uint32_t prank = __shfl_sync(0xffffffffu, rank, 0);
                auto request = [&]() { mbar_arrive_cluster_if(lane == 0, bars0 + B_WANT); };
                auto take_item = [&]() -> int { return __shfl_sync(0xffffffffu, next_item(lane == 0), 0); };
                auto inputs_seen = [&](uint32_t word, unsigned& n) -> uint32_t {
                    uint32_t v;
                    spin_guard(n);
                    asm volatile("ld.acquire.cta.shared.u32 %0, [%1];" : "=r"(v) : "r"(bars + SM_ORDY + 4 * word) : "memory");
                    return __shfl_sync(0xffffffffu, v, 0);
                };
                uint32_t oneed = 0;
                auto wait_inputs = [&](int it) {
                    if (it & ITEM_READY) return;
                    oneed += 256;
                    for (unsigned n = 0; inputs_seen(1, n) < oneed;) {}
                };
                int nxt = first_item(), ring = -1, rot = 0;
                for (int k0 = 2; item_type(nxt) <= T_LOCAL; k0 = 0) {
                    const int type = item_type(nxt), m = item_row(nxt), c = item_col(nxt);
                    if (type == T_LOCAL) {
                        wait_inputs(nxt);
                        request();
#pragma unroll 1
                        for (uint32_t st = 0; st < 4; st++) {
                            mbar_wait(bars + B_GEMPTY + 8 * st, gph);
                            const uint32_t dst = sb + st * GST_BYTES, fb = bars + B_GFULL + 8 * st;
                            warp_expect_tx(fb, st == 0 ? 32768 + 512 : st == 3 ? 0 : 4 * LOC_PLANE);
                            if (st == 3) break;
                            if (st == 0) warp_bulk_load(dst + 4 * LOC_PLANE, &g_gate[m * 128], 512, fb);
#pragma unroll 1
                            for (int i = 0; i < 4; i++)
                                warp_tma_load(dst + i * LOC_PLANE, &prm.m[st ? M_SCR_LOC : M_SCR_LOQ], fb, i * 64, m * 64 - (st ? 8 : 0), G_B + 8 * st + c, false);
                        }
                        gph ^= 1;
                        ring = -1;
                    } else {
                        const int nk = type == T_K || type == T_V ? 8 : 16, kept = ring == m + 16 * nk ? 4 : 0;
                        ring = m + 16 * nk;
                        rot = kept ? rot - 4 : 0;
                        const CUtensorMap* ma = &prm.m[nk == 8 ? M_C : M_X];
                        const CUtensorMap* mb = &prm.m[M_WQ + type];
#pragma unroll 1
                        for (int k = k0; k < nk; k++) {
                            if (k == nk - 3) request();
                            const uint32_t st = k & 3, dst = sb + st * GST_BYTES, fb = bars + B_GFULL + 8 * st;
                            const int kc = ((k + rot) & (nk - 1)) * 64;
                            mbar_wait(bars + B_GEMPTY + 8 * st, gph);
                            warp_expect_tx(fb, k < kept ? 32768 : GST_BYTES);
                            if (k >= kept) warp_tma_load(dst, ma, fb, kc, m * 128, 0, c == 15 && type != T_K);
                            warp_tma_load_pair(dst + 16384 + prank * 16384, mb, fb, 0, kc, c * 4 + 2 * prank, blockIdx.x < 128 || (m & 6) == 6);
                            if (st == 3) gph ^= 1;
                        }
                    }
                    nxt = take_item();
                }
                uint32_t kv = 0, kvph = 1;
                uint32_t qc = 0;
                auto a_parity = [&](uint32_t b) { return b < 2 ? (((qc + 1 - b) >> 1) & 1) ^ 1 : kvph ^ (b - 2 < kv); };
                const CUtensorMap* tile_map = &prm.m[M_SCR_LD];
                asm volatile("" : "+l"(tile_map));
                {
                    bool need_g = true, more = true;
                    int pv_grp = -1, pv_row = 0;
                    int pv_shared = 0;
                    bool peer_longer = false;
                    int m = 0, kg = 0, vg = 0, asc = 0, nu = 0, uend = 0, ureq = -1, ufetch = 0;
#pragma unroll 1
                    for (int u = 0;; u++) {
                        if (u == ufetch) {
                            if (qc) nxt = take_item();
                            if (item_type(nxt) == T_ATTN) {
                                wait_inputs(nxt);
                                const uint32_t b = qc & 1, dst = sb + b * 32768, fb = bars + B_AFULL + 8 * b, row = item_row(nxt) * 128;
                                mbar_wait(bars + (qc == 0 ? B_GEMPTY : qc == 1 ? B_QFREE : B_AEMPTY + 8 * b), qc == 0 ? gph : qc == 1 ? 0 : a_parity(b));
                                warp_expect_tx(fb, 32768 + 512);
                                warp_tma_load(dst, tile_map, fb, 0, row, G_Q + item_col(nxt), false);
                                warp_tma_load(dst + 16384, tile_map, fb, 64, row, G_Q + item_col(nxt), false);
                                warp_bulk_load(bars + SM_GATE + b * 512, &g_gate[row], 512, fb);
                                qc++;
                            }
                        }
                        if (u == uend) {
                            if (!more) break;
                            more = item_type(nxt) == T_ATTN;
                            m = item_row(nxt); asc = item_asc(nxt);
                            kg = prm.kgroup[item_col(nxt) >> 1] + (item_col(nxt) & 1); vg = kg + (kg < G_V ? 32 : 8);
                            nu = more ? 2 * m + 2 : 0;
                            uend = nu + ((more ? m < 2 : pv_grp >= 0) ? 3 : 0);
                            ureq = 2 * max(m - 2 - (asc & m), 0);
                            ufetch = !more ? -1 : m ? 2 * m : uend;
                            u = -1;
                            continue;
                        }
                        int grp = pv_grp, row = pv_row;
                        int shared = pv_shared;
                        if (u >= nu) {
                            if (u == nu + 1) pv_grp = -1;
                            else if (peer_longer) { grp = -1; shared = 0; }
                            else continue;
                        } else {
                            const int j = asc ? u >> 1 : m - (u >> 1);
                            if (u & 1) {
                                pv_grp = vg; pv_row = j * 128; pv_shared = (m | 1) - j;
                                peer_longer = asc & ~m & 1;
                                if (u == nu - 1 && (m & 1) && item_type(nxt) == T_END) mbar_arrive_cluster_n_if(lane == 0, bars0 + B_WANT, 2);
                                if (grp < 0) continue;
                            } else {
                                if (u == ureq) request();
                                grp = kg; row = j * 128; shared = (m | 1) - j;
                            }
                        }
                        uint32_t fb = bars + B_AFULL + 16 + 8 * kv, mine = sb + SM_KV + kv * 32768 + prank * 16384;
                        int c_mine = prank * 64;
                        asm volatile("" : "+r"(mine), "+r"(fb), "+r"(row), "+r"(grp), "+r"(c_mine));
                        mbar_wait(need_g ? bars + B_GEMPTY + 8 + 8 * kv : fb + B_AEMPTY - B_AFULL, need_g ? gph : kvph);
                        warp_expect_tx(fb, grp < 0 ? 0 : 32768);
                        if (shared) {
                            warp_tma_load_pair(mine, tile_map, fb, c_mine, row, grp, shared == 1);
                        } else if (grp >= 0) {
                            warp_tma_load(mine, tile_map, fb, c_mine, row, grp, true);
                            warp_tma_load(mine + 16384 - prank * 32768, tile_map, fb, 64 - c_mine, row, grp, true);
                        } else {
                            mbar_arrive_cluster_n_if(lane < 2, map_cta(fb, lane & 1) + B_AEMPTY - B_AFULL, 8);
                        }
                        if (kv == 2) need_g = false;
                        if (++kv == 4) { kv = 0; kvph ^= 1; }
                    }
                }
                if (!qc) request();
                const int it = take_item();
                int nk = 0;
                if (item_type(it) == T_OUT) {
                    const int m = item_row(it), c = item_col(it), half = c & 1;
                    nk = 80;
                    for (unsigned n = 0; (inputs_seen(1, n) & 255) != 255;) {}
                    mbar_wait(bars + B_GEMPTY + 24, gph);
                    mbar_wait(bars + B_QFREE, 0);
                    mbar_wait(bars + B_AEMPTY + 8 * (qc & 1), a_parity(qc & 1));
#pragma unroll 1
                    for (uint32_t k = 0; k < 4; k++) {
                        const uint32_t sa = prm.ostep[half ? WIDE - 1 - k : k], dst = sb + k * GST_BYTES, fb = bars + B_GFULL + 8 * k;
                        const uint32_t b0 = k ? 1 + k : ~qc & 1, b1 = 2 + k - (k == 1);
                        mbar_wait(bars + B_AEMPTY + 8 * b0, a_parity(b0));
                        mbar_arrive_cluster_if(lane == 0 && !k, bars_peer + B_XFREE);
                        warp_expect_tx(fb, GST_BYTES);
                        warp_tma_load(dst, tile_map, fb, (sa & 1) * 64, m * 128, G_LOC - 32 + (sa >> 1), true);
                        mbar_wait(bars + (k ? B_AEMPTY + 8 * b1 : B_XFREE), k ? kvph ^ (b1 - 2 < kv) : 0);
                        warp_tma_load_pair(dst + 16384 + prank * 16384, &prm.m[M_WOB], fb, 0, (sa & 63) * 64, (c >> 1) * 4 + 2 * (half ^ prank), false);
                    }
                    gph ^= 1;
                    uint32_t seen = 0;
                    for (int k = 4; k < nk; k++) {
                        if (k == K_SPLIT) nk = 2 * TRIPLES + (take_item() & 127);
                        const int kn = k + 2 * TRIPLES - nk, first = kn >= 0 && !(kn & 1);
                        const int s = kn >= 0 ? WIDE + (3 * kn + 1) / 2 : half ? WIDE - 1 - k : k;
                        const uint32_t sa = prm.ostep[s], sa2 = prm.ostep[s + first], sw = prm.ostep[s - (kn >= 0 && !first ? prank : 0)];
                        const uint32_t need = 1u << (sa >> 1 & 31) | 1u << (sa2 >> 1 & 31);
                        for (unsigned n = 0; sa < 64 && (need & ~seen);) seen = inputs_seen(0, n);
                        const uint32_t st = k & 3;
                        uint32_t dst = sb + st * GST_BYTES, fb = bars + B_GFULL + 8 * st;
                        uint32_t dstb = dst + 16384 + (first ? 0 : prank * 16384), skipb = first && (kn >> 1 & 1) != prank;
                        int a0 = (sa & 1) * 64, a1 = m * 128, a2 = (sa >> 1) + (sa < 64 ? G_CTX : G_LOC - 32);
                        int b1 = (sw & 63) * 64, b2 = (c >> 1) * 4 + 2 * (kn >= 0 ? half : half ^ prank);
                        const CUtensorMap* mb = &prm.m[sw >= 64 ? M_WOB : M_WO];
                        asm volatile("" : "+r"(dst), "+r"(fb), "+r"(dstb), "+r"(skipb), "+r"(a0), "+r"(a1), "+r"(a2), "+r"(b1), "+r"(b2), "+l"(mb));
                        mbar_wait(bars + B_GEMPTY + 8 * st, gph);
                        warp_expect_tx(fb, GST_BYTES);
                        warp_tma_load(dst, tile_map, fb, a0, a1, a2, true);
                        if (!skipb) warp_tma_load_pair(dstb, mb, fb, 0, b1, b2, false);
                        if (first) warp_tma_load(dst + 32768, tile_map, fb, (sa2 & 1) * 64, a1, G_CTX + (sa2 >> 1), true);
                        if (k < K_SPLIT && lane == 0 && !prank)
                            asm volatile("st.relaxed.gpu.global.u32 [%0], %1;" :: "l"(&g_sync.step[0][0] + m * 4 + c), "r"(k) : "memory");
                        mbar_arrive_if(k == K_MEET && lane == 0, bars + B_MEET);
                        if ((uint32_t)(k - K_FETCH) < (3 * TRIPLES + 1) / 2) {
                            const uint32_t g = prm.ostep[79 - 2 * (k - K_FETCH)] >> 1;
                            warp_prefetch((const char*)g_scr + (uint32_t)((G_CTX + g) * (SEQ * 256) + m * 32768 + c * 4096), 4096);
                            warp_prefetch(prm.wo + (uint32_t)(g * 262144 + (m * 8 + c) * 2048), 2048);
                        }
                        if (st == 3) gph ^= 1;
                    }
                    for (unsigned n = 0; ~inputs_seen(0, n);) {}
                }
#pragma unroll 1
                for (uint32_t st = 0; st < 4; st++) { mbar_wait(bars + B_GEMPTY + 8 * st, gph ^ (st < (nk & 3))); mbar_wait(bars + B_AEMPTY + 16 + 8 * st, a_parity(2 + st)); }
                unsigned left = 0;
                if (lane == 0) asm volatile("atom.relaxed.gpu.global.add.u32 %0, [%1], 1;" : "=r"(left) : "l"(&g_sync.done) : "memory");
                if (__shfl_sync(0xffffffffu, left, 0) == NCTA - 1)
#pragma unroll 1
                    for (uint32_t i = lane * 8; i < sizeof(Sync); i += 256) *(unsigned long long*)((char*)&g_sync + i) = 0;
            }
        } else if (warp <= 2) {
            if (blockIdx.x < SEQ / 16) {
                const uint32_t r0 = 16 * blockIdx.x + 8 * (warp - 1), gbuf = bars + SM_GATE + 4 * (r0 & 15);
                float z[4];
                mbar_wait(bars + B_GFULL + 24, 0);
#pragma unroll 1
                for (uint32_t i = 0; i < 8; i++) {
                    const uint32_t off = (i & 3) * 512 + lane * 16;
                    const uint4* xp = (const uint4*)((const char*)prm.x + ((r0 + (i & 4)) * 2048 + off));
                    const uint4 wv = __ldg((const uint4*)((const char*)prm.gate_w + off));
                    uint4 xv[4];
#pragma unroll
                    for (int r = 0; r < 4; r++) { xv[r] = __ldg(xp + r * 128); if (!(i & 3)) z[r] = 0.f; }
                    const uint32_t ws[4] = {wv.x, wv.y, wv.z, wv.w};
#pragma unroll
                    for (int e = 0; e < 4; e++)
#pragma unroll
                        for (int r = 0; r < 4; r++) {
                            const uint32_t xs = e == 0 ? xv[r].x : e == 1 ? xv[r].y : e == 2 ? xv[r].z : xv[r].w;
                            z[r] = fmaf(__uint_as_float(xs << 16), __uint_as_float(ws[e] << 16), z[r]);
                            z[r] = fmaf(__uint_as_float(xs & 0xffff0000u), __uint_as_float(ws[e] & 0xffff0000u), z[r]);
                        }
                    if ((i & 3) == 3) {
#pragma unroll
                        for (int o = 16; o > 0; o >>= 1)
#pragma unroll
                            for (int r = 0; r < 4; r++) z[r] += __shfl_xor_sync(0xffffffffu, z[r], o);
                        const float zr = lane & 2 ? (lane & 1 ? z[3] : z[2]) : (lane & 1 ? z[1] : z[0]);
                        asm volatile("st.shared.f32 [%0], %1;" :: "r"(gbuf + 4 * ((i & 4) + (lane & 3))), "f"(1.f / (1.f + __expf(-zr))) : "memory");
                    }
                }
                fence_proxy_async_smem();
                __syncwarp();
                warp_bulk_store((char*)g_gate + 4 * r0, gbuf, 32);
                bulk_commit();
                bulk_wait<0>();
                __syncwarp();
                if (lane == 0) red_add(&g_sync.count[3], 1);
            }
            __syncwarp();
            {
                const int w = warp - 1;
                uint32_t sph = 0, nann = 0;
                int unsent = 0, nunsent = 0;
                bool urgent = false;
                auto announce = [&]() {
                    if (!urgent) return;
                    bulk_wait<0>();
                    __syncwarp();
                    const uint32_t hb = bars + B_HALF + 8 * (nann & 3);
                    if (w == 0) {
                        mbar_arrive_if(lane == 0, hb);
                    } else {
                        mbar_wait(hb, (nann >> 2) & 1);
                        const uint32_t type = item_type(unsent), m = item_row(unsent), c = item_col(unsent);
                        const uint32_t word = type < T_B ? c >> 3 : type == T_B ? 2 : offsetof(Sync, ctx) / 8 + m;
                        const uint32_t bit = type < T_B ? 8 * (c & 7) : type == T_B ? 8 * (c & 3) : type == T_LOCAL ? 32 + c : c;
                        if (lane < nunsent) red_add((unsigned long long*)((char*)&g_sync + 8 * word), 1ull << bit);
                        __syncwarp();
                    }
                    nann++;
                    nunsent = 0; urgent = false;
                };
                int held = first_item(), it;
                do {
                    if (!__all_sync(0xffffffffu, mbar_test(bars + B_IFULL + 8 * (qn % QDEPTH), (qn / QDEPTH) & 1))) announce();
                    it = __shfl_sync(0xffffffffu, next_item(lane == 0), 0);
                    const int itype = item_type(it);
                    const bool keep_held = itype == T_LOCAL;
#pragma unroll 1
                    for (int pass = held < 0 || keep_held; pass < 2; pass++) {
                        if (pass && (itype < T_OUT || itype == T_END)) break;
                        const int cur = pass ? it : held, type = item_type(cur), m = item_row(cur), c = item_col(cur);
                        const bool local = type == T_LOCAL;
                        int grp = pass ? (local ? G_LOC : G_CTX) + c : type * 32 + 2 * c;
                        if ((type == T_K || type == T_V) && prm.kgroup[c] > G_B) {
                            grp = prm.kgroup[c] + (type == T_V ? 8 : 0);
                            for (unsigned n = 0; !__all_sync(0xffffffffu, (ld_acquire(&g_sync.used) >> (4 * (grp & 6)) & 255) == 32);) { announce(); spin_guard(n); }
                        }
#pragma unroll 1
                        for (int i = 0; i < 4 - 2 * pass; i++) {
                            const int b = i & 1;
                            const bool alt = i >= 2 && itype >= T_ATTN;
                            const uint32_t full = bars + (alt ? B_ALT + 8 * w : B_SFULL + 16 * w + 8 * b), par = alt ? 0 : sph;
                            if (i == 3 - 2 * pass || !__all_sync(0xffffffffu, mbar_test(full, par))) announce();
                            mbar_wait(full, par);
                            if (local && w + b == 2 && lane == 0) asm volatile("red.relaxed.gpu.global.add.u32 [%0], %1;" :: "l"(&g_sync.used), "r"(1 << (4 * (c & 6))) : "memory");
                            fence_proxy_async_smem();
                            warp_tma_store(&prm.m[local ? M_SCR_LOQ : M_SCR_ST], sb + (alt ? 32768 : SM_STAGING) + w * 16384 + b * 8192,
                                         local ? b * 128 + w * 64 : b * 64, local ? m * 64 : m * 128 + w * 64, grp + (i >> 1), local || (type < T_B && c < FIRST_PAIR));
                            bulk_commit();
                            if (pass > b) continue;
                            bulk_wait_read<0>();
                            __syncwarp();
                            mbar_arrive_if(lane <= pass && !alt, bars + B_SEMPTY + 16 * w + 8 * (b - lane));
                            sph ^= b & !alt;
                        }
                        mbar_arrive_if(lane == 0 && !pass && itype >= T_ATTN, bars + B_QFREE);
                        if (lane == nunsent) unsent = cur;
                        nunsent++;
                        urgent = !local;
                    }
                    if (!keep_held) held = itype < T_OUT ? it : -1;
                } while (item_type(it) != T_END);
                announce();
                it = __shfl_sync(0xffffffffu, next_item(lane == 0), 0);
                if (item_type(it) == T_OUT) {
                    if (w) {
                        mbar_wait(bars + B_MEET, 0);
                        asm volatile("fence.proxy.async.global;\nfence.acq_rel.gpu;" ::: "memory");
                        mbar_arrive_cluster_if(lane == 0, bars0 + B_WANT);
                    }
                    next_item(lane == 0);
#pragma unroll 1
                    for (int i = 0; i < 4; i++) {
                        const int b = i & 1;
                        mbar_wait(bars + B_SFULL + 16 * w + 8 * b, sph ^ (i >> 1));
                        fence_proxy_async_smem();
                        warp_tma_add(&prm.m[M_OUT], sb + SM_STAGING + w * 16384 + b * 8192, (item_col(it) ^ (i < 2)) * 128 + b * 64, item_row(it) * 128 + w * 64, 0);
                        bulk_commit();
                        if (b) {
                            bulk_wait_read<0>();
                            __syncwarp();
                            mbar_arrive_if(lane < 2, bars + B_SEMPTY + 16 * w + 8 * lane);
                        }
                    }
                }
            }
        } else {
            if (elect_one()) {
                uint32_t ordy = 0;
                unsigned long long cnt_lo = 0, cnt_hi = 0;
                int late = 0;
                auto refresh = [&]() {
                    if (!late && cnt_lo == 0x30303030 && cnt_hi == SEQ / 8) late = 1;
                    asm volatile("ld.acquire.gpu.global.v2.u64 {%0, %1}, [%2];" : "=l"(cnt_lo), "=l"(cnt_hi) : "l"(late ? &g_sync.count[0] : &g_sync.count[2]) : "memory");
                };
                auto inputs_ready = [&](int it) -> bool {
                    const int c = item_col(it);
                    if (item_type(it) == T_ATTN) return late && ((c < 16 ? cnt_lo : cnt_hi) >> (4 * (c & 14)) & 255) == 48;
                    return late || (cnt_hi == SEQ / 8 && (cnt_lo >> (4 * (c & 6)) & 255) == 48);
                };
                auto publish = [&](int it, int step) {
                    const uint32_t slot = qn % QDEPTH;
                    mbar_wait(bars + B_IEMPTY + 8 * slot, ((qn / QDEPTH) & 1) ^ 1);
                    for (uint32_t r = 0; r < 2; r++) {
                        const uint32_t rb = map_cta(bars, r);
                        asm volatile("mbarrier.arrive.expect_tx.shared::cluster.b64 _, [%0], 4;" :: "r"(rb + B_IFULL + 8 * slot) : "memory");
                        asm volatile("st.async.shared::cluster.mbarrier::complete_tx::bytes.u32 [%0], %1, [%2];"
                                     :: "r"(rb + SM_QUEUE + 4 * slot), "r"(it + r * step), "r"(rb + B_IFULL + 8 * slot) : "memory");
                    }
                    qn++;
                };
                int asc = 1;
                int it;
                do {
                    if (rank == 0) {
                        mbar_wait(bars + B_WANT, qn & 1);
                        const uint32_t pair = plan_index();
                        int pit = prm.plan[pair < 64 ? pair & 7 : pair - 56][min(qn + 1, 15u)];
                        unsigned i;
                        const bool planned = item_type(pit) != T_END;
                        if (!planned) asm volatile("atom.relaxed.gpu.global.add.u32 %0, [%1], 1;" : "=r"(i) : "l"(&g_sync.next) : "memory");
                        if (cnt_lo != 0x3030303030303030ull || cnt_hi != cnt_lo) refresh();
                        if (planned) pit += (pair >> 3 & 7) << (item_type(pit) == T_LOCAL);
                        else if (i < NITEMS) pit = prm.items[i];
                        const int type = item_type(pit);
                        int step = type == T_LOCAL ? 16 : 1;
                        it = pit + (pit & (step == 1 ? 15 : 0x1f0));
                        if (type == T_ATTN) {
                            if (!asc) { it += 1; step = -1; }
                            it |= asc << 9;
                        }
                        asc = type != T_ATTN || item_row(pit) == 0 || !asc;
                        if (inputs_ready(it)) it |= ITEM_READY;
                        publish(it, step);
                    } else {
                        it = next_item(true);
                    }
                    if ((item_type(it) == T_ATTN || item_type(it) == T_LOCAL) && !(it & ITEM_READY)) {
                        unsigned n = 0;
                        while (!inputs_ready(it)) { refresh(); spin_guard(n); }
                        asm volatile("st.release.cta.shared.u32 [%0], %1;" :: "r"(bars + SM_ORDY + 4), "r"(ordy += 256) : "memory");
                    }
                } while (item_type(it) != T_END);
                if (rank == 0) {
                    mbar_wait(bars + B_WANT, qn & 1);
                    const unsigned i = atomicAdd(&g_sync.next_out, 1u), t = i < 32 ? 31 - i : i - 32;
                    it = i < 64 ? T_OUT << 13 | ((t & 3) * 2 + (i >> 5)) << 4 | (t >> 2) * 2 : T_END << 13;
                    publish(it, 1);
                } else {
                    it = next_item(true);
                }
                if (item_type(it) == T_OUT) {
                    const uint32_t m = item_row(it), half = item_col(it) & 1, tile = m * 2 + (item_col(it) >> 1);
                    unsigned* split = (unsigned*)((char*)g_sync.split + 4 * tile);
                    unsigned long long rdy = 0;
                    int state = rank ? 2 : 0;
                    for (unsigned n = 0; rdy != 0xffffffffffull || state < 2; spin_guard(n)) {
                        if (rdy != 0xffffffffffull) {
                            rdy = ld_acquire((const unsigned long long*)((char*)g_sync.ctx + 8 * m));
                            asm volatile("st.release.cta.shared.u64 [%0], %1;" :: "r"(bars + SM_ORDY), "l"(rdy) : "memory");
                        }
                        unsigned steps = 0;
                        if (state == 1) {
                            steps = ld_acquire(split);
                        } else if (state == 0 && mbar_test(bars + B_WANT, qn & 1)) {
                            state = 1;
                            unsigned seen;
                            asm volatile("atom.acq_rel.gpu.global.exch.b32 %0, [%1], 1;" : "=r"(seen) : "l"(split) : "memory");
                            if (seen) {
                                const unsigned long long v = ld_acquire((const unsigned long long*)((char*)g_sync.step + 8 * tile));
                                const int d = (int)(v >> 32) - (int)v;
                                steps = (WIDE + min(max(half ? d : -d, -12), 12)) >> 1;
                                atomicExch(split, WIDE - steps);
                            }
                        }
                        if (steps > 1) { publish(T_END << 13 | steps, 0); state = 2; }
                    }
                    if (rank) next_item(true);
                }
#pragma unroll 1
                for (uint32_t n = qn; n < qn + QDEPTH && rank == 0; n++) mbar_wait(bars + B_IEMPTY + 8 * (n % QDEPTH), ((n / QDEPTH) & 1) ^ 1);
            }
        }
    } else {
        reg_inc<232>();
        const int wg = (warp >> 2) - 1, wq = warp & 3;
        uint32_t gph = 0;
        uint32_t kvn = 0;
        const uint32_t dA = make_desc(sb + wg * 8192, 16);
        uint32_t ti = 0;
        uint32_t sph = 1;
        const uint32_t stg = sb + SM_STAGING + wg * 16384;
        const uint32_t stg_lane = stg + (wq * 16 + (lane & 15)) * 128 + (((lane >> 4) ^ (lane & 7)) << 4);
        auto write_blocks = [&](auto n, uint32_t off, const uint32_t* v) {
            uint32_t a = stg_lane;
            asm volatile("" : "+r"(a));
            a += off;
#pragma unroll
            for (int j = 0; j < decltype(n)::value; j++)
                stmatrix_x4((a ^ (32 * (j & 3))) + (j >> 2) * 8192, v[4 * j], v[4 * j + 1], v[4 * j + 2], v[4 * j + 3]);
        };
        auto release = [&](uint32_t bar) { mbar_arrive_if(lane == 0, bars + bar); };
        const uint32_t bars_lane = map_cta(bars, lane & 1);
        auto release_stage = [&](uint32_t st) { mbar_arrive_cluster_if(lane < 2, bars_lane + B_GEMPTY + 8 * st); };
        auto take_item = [&]() -> int {
            return __shfl_sync(0xffffffffu, next_item(lane == 0, false), 0);
        };
        auto stage_acquire = [&](int b) { mbar_spin(bars + B_SEMPTY + 16 * wg + 8 * b, sph); };
        auto stage_publish = [&](int b) {
            __syncwarp();
            release(B_SFULL + 16 * wg + 8 * b);
        };
        auto stage_chunk = [&](int b, const uint32_t* v) {
            stage_acquire(b);
            write_blocks(std::integral_constant<int, 4>(), b * 8192, v);
            stage_publish(b);
            if (b) sph ^= 1;
        };
        auto publish_pair = [&]() {
            __syncwarp();
            mbar_arrive_if(lane < 2, bars + B_SFULL + 16 * wg + 8 * lane);
            sph ^= 1;
        };
        auto gemm_step = [&](float (&acc)[128], uint32_t dB, int& k, bool order) {
            const uint32_t st = k & 3;
            wgmma_wait<0>();
            release_stage((k - 1) & 3);
            mbar_spin(bars + B_GFULL + 8 * st, gph);
            const uint64_t da = full_desc(dA + st * (GST_BYTES >> 4)), db = full_desc(dB + st * (GST_BYTES >> 4));
            if (order && wg) bar_sync(3, 256);
            wgmma_fence();
#pragma unroll
            for (int kk = 0; kk < 4; kk++) wgmma_ss_n256_tb(acc, da + 2 * kk, db + 128 * kk, 1);
            wgmma_commit();
            if (order && !wg) bar_arrive(3, 256);
            gph ^= st == 3;
            k++;
        };
        if (wg == 1) bar_arrive(1, 256);
        int it = first_item();
        float s[64];
        const uint32_t dK = make_desc(sb + SM_KV, 16);
        auto kv_wait = [&](uint32_t n) { mbar_spin(bars + B_AFULL + 16 + 8 * (n & 3), (n >> 2) & 1); };
        auto first_scores = [&](bool valid) {
            if (valid) { mbar_spin(bars + B_AFULL + 8 * (ti & 1), (ti >> 1) & 1); kv_wait(kvn); }
            bar_sync(1 + wg, 256);
            qk_gemm(s, dA + (ti & 1) * 2048, dK + (kvn & 3) * 2048);
        };
        bool issued;
        {
            {
                float acc[128];
                uint32_t pk[64];
                bool pending = false;
                int held = T_END;
                auto scale_q = [&](int j0) {
                    if (held != T_Q) return;
#pragma unroll
                    for (int j = j0; j < j0 + 16; j++)
                        asm("{\n.reg .b32 t;\nmul.rn.bf16x2 t, %0, %2;\nfma.rn.bf16x2 %0, %0, %1, t;\n}\n" : "+r"(pk[j]) : "r"(0x3e033e03u), "r"(0xb9d8b9d8u));
                };
                zero_regs(pk);
                const uint32_t dB = make_desc(sb + 16384, 8192);
                do {
                    if (item_type(it) == T_LOCAL) {
                        int ln = lane;
                        asm volatile("" : "+r"(ln));
                        const int g = ln >> 2, t = ln & 3, par = wq & 1;
                        const uint32_t hc = (wq >> 1) * 4, pl = sb + (par * 2 + wg) * LOC_PLANE;
                        const uint32_t a16 = (ln & 15) * 128 + (((hc + (ln >> 4)) ^ (ln & 7)) << 4), a8 = (ln & 7) * 128 + (((hc + (ln >> 3)) ^ (ln & 7)) << 4);
                        const bool first0 = 2 * t > g, first1 = 2 * t + 1 > g;
                        const uint32_t fmask = (first0 ? 0xffffu : 0u) | (first1 ? 0xffff0000u : 0u);
                        const bool edge = item_row(it) == 0;
                        uint32_t q[4][2][4], kf[9][4], vf[9][4];
                        float w[8];
                        mbar_spin(bars + B_GFULL, gph);
#pragma unroll
                        for (int u = 0; u < 4; u++) { ldsm_x4(q[u][0], pl + u * 2048 + a16); ldsm_x4(q[u][1], pl + u * 2048 + (a16 ^ 32)); }
#pragma unroll
                        for (int j = 0; j < 8; j++) w[j] = lds_f32(sb + 4 * LOC_PLANE + 4 * (2 * g + par) + 64 * j);
                        __syncwarp();
                        release_stage(0);
                        mbar_spin(bars + B_GFULL + 8, gph);
#pragma unroll
                        for (int n = 0; n < 9; n++) ldsm_x4(kf[n], pl + GST_BYTES + n * 1024 + a8);
                        __syncwarp();
                        release_stage(1);
                        float s[8][2];
#pragma unroll
                        for (int u = 0; u < 4; u++) {
                            float d[3][4];
#pragma unroll
                            for (int nt = 0; nt < 3; nt++) {
                                mma_k16_init(d[nt], q[u][0], kf[2 * u + nt][0], kf[2 * u + nt][1]);
                                mma_k16(d[nt], q[u][1], kf[2 * u + nt][2], kf[2 * u + nt][3]);
                            }
                            if (u == 0 && edge) { d[0][0] = -INFINITY; d[0][1] = -INFINITY; }
                            s[2 * u][0] = first0 ? d[0][0] : d[1][0]; s[2 * u][1] = first1 ? d[0][1] : d[1][1];
                            s[2 * u + 1][0] = first0 ? d[1][2] : d[2][2]; s[2 * u + 1][1] = first1 ? d[1][3] : d[2][3];
                        }
                        mbar_spin(bars + B_GFULL + 16, gph);
#pragma unroll
                        for (int u = 0; u < 4; u++) { ldsm_x4_t(vf[2 * u], pl + 2 * GST_BYTES + u * 2048 + a16); ldsm_x4_t(vf[2 * u + 1], pl + 2 * GST_BYTES + u * 2048 + (a16 ^ 32)); }
                        ldsm_x4_t(vf[8], pl + 2 * GST_BYTES + 8192 + a8);
                        __syncwarp();
                        release_stage(2);
                        float x[8];
#pragma unroll
                        for (int j = 0; j < 8; j++) x[j] = fmaxf(s[j][0], s[j][1]);
#pragma unroll
                        for (int o = 1; o < 4; o *= 2)
#pragma unroll
                            for (int j = 0; j < 8; j++) x[j] = fmaxf(x[j], __shfl_xor_sync(0xffffffffu, x[j], o));
#pragma unroll
                        for (int j = 0; j < 8; j++) {
                            const float n = x[j] * -LOC_SCALE;
                            s[j][0] = ex2(fmaf(s[j][0], LOC_SCALE, n)); s[j][1] = ex2(fmaf(s[j][1], LOC_SCALE, n));
                            x[j] = s[j][0] + s[j][1];
                        }
#pragma unroll
                        for (int o = 1; o < 4; o *= 2)
#pragma unroll
                            for (int j = 0; j < 8; j++) x[j] += __shfl_xor_sync(0xffffffffu, x[j], o);
                        mbar_spin(bars + B_GFULL + 24, gph);
                        release_stage(3);
                        it = take_item();
                        uint32_t ob[4][8];
#pragma unroll
                        for (int u = 0; u < 4; u++) {
                            const float r0 = rcp(x[2 * u]), r1 = rcp(x[2 * u + 1]), f0 = fmaf(-w[2 * u], r0, r0), f1 = fmaf(-w[2 * u + 1], r1, r1);
                            const uint32_t p0 = pack_bf16(s[2 * u][0] * f0, s[2 * u][1] * f0), p1 = pack_bf16(s[2 * u + 1][0] * f1, s[2 * u + 1][1] * f1);
                            const uint32_t pa[4] = {p0 & fmask, 0, p0 & ~fmask, p1 & fmask};
#pragma unroll
                            for (int c = 0; c < 4; c++) {
                                float ol[4];
                                mma_k16_init(ol, pa, vf[2 * u + (c >> 1)][2 * (c & 1)], vf[2 * u + (c >> 1)][2 * (c & 1) + 1]);
                                mma_k8(ol, 0, p1 & ~fmask, u < 3 ? vf[2 * u + 2 + (c >> 1)][2 * (c & 1)] : vf[8][c]);
                                ob[u][2 * c] = pack_bf16(ol[0], ol[1]);
                                ob[u][2 * c + 1] = pack_bf16(ol[2], ol[3]);
                            }
                        }
                        stage_acquire(0); stage_acquire(1);
#pragma unroll
                        for (int u = 0; u < 4; u++) {
                            stmatrix_x4(stg + par * 8192 + u * 2048 + a16, ob[u][0], ob[u][1], ob[u][2], ob[u][3]);
                            stmatrix_x4(stg + par * 8192 + u * 2048 + (a16 ^ 32), ob[u][4], ob[u][5], ob[u][6], ob[u][7]);
                        }
                        publish_pair();
                        bar_sync(4, 256);
                        gph ^= 1;
                        continue;
                    }
                    mbar_spin(bars + B_GFULL, gph);
                    bool more;
                    do {
                        wgmma_fence();
                        wgmma_ss_n256_tb_init(acc, full_desc(dA), full_desc(dB));
#pragma unroll
                        for (int kk = 1; kk < 4; kk++) wgmma_ss_n256_tb(acc, full_desc(dA) + 2 * kk, full_desc(dB) + 128 * kk, 1);
                        wgmma_commit();
                        const int type = item_type(it), nk = type == T_K || type == T_V ? 8 : 16;
                        int k = 1;
                        do {
                            if (pending) {
                                if (k == 1) { scale_q(0); stage_chunk(0, pk); }
                                else if (k == 3) { scale_q(16); stage_chunk(1, pk + 16); }
                                else if (k == 5) { scale_q(32); stage_chunk(0, pk + 32); }
                                else if (k == 6) { scale_q(48); stage_chunk(1, pk + 48); }
                            }
                            if (k == nk - 1) it = take_item();
                            gemm_step(acc, dB, k, item_type(it) > T_LOCAL);
                        } while (k < nk);
                        held = type;
                        more = item_type(it) < T_LOCAL;
                        if (more) mbar_spin(bars + B_GFULL, gph);
                        wgmma_wait<0>();
                        fence_regs(acc);
                        release_stage(3);
#pragma unroll
                        for (int j = 0; j < 64; j++) pk[j] = pack_bf16(acc[2 * j], acc[2 * j + 1]);
                        pending = true;
                    } while (more);
                } while (item_type(it) <= T_LOCAL);
                issued = item_type(it) == T_ATTN && (it & ITEM_READY);
                first_scores(issued);
                stage_acquire(0); stage_acquire(1);
                mbar_spin(bars + B_GEMPTY + 8, gph ^ 1);
                write_blocks(std::integral_constant<int, 8>(), 0, pk);
                write_blocks(std::integral_constant<int, 8>(), 32768 - SM_STAGING, pk + 32);
                publish_pair();
                release(B_ALT + 8 * wg);
                bar_arrive(2 - wg, 256);
                wgmma_wait<0>();
                fence_regs(s);
                if (item_type(it) == T_END) it = take_item();
            }
            while (item_type(it) == T_ATTN) {
                if (!issued) { first_scores(true); bar_arrive(2 - wg, 256); wgmma_wait<0>(); fence_regs(s); }
                issued = false;
                float o[64];
                uint32_t pa[32], pb[32];
                float n0 = 0.f, n1 = 0.f;
                int shifted = 0;
                float l0 = 0.f, l1 = 0.f, f0 = 0.f, f1 = 0.f, g0, g1;
                uint32_t has_pv = 0;
                int first = 0;
                int pending = 0;
                const uint32_t dV = make_desc(sb + SM_KV, 16384);
                const uint32_t lane_off = bars_lane - bars + B_AEMPTY - B_AFULL;
                int cur = it;
                uint32_t qoff = (ti & 1) * 2048;
                const int row = wg * 64 + wq * 16 + (lane >> 2);
                const float thr = (row & 63) - (lane & 3) * 2;
                int diag = item_row(cur) == 0 || !item_asc(cur);
                int peek = -1;
                auto kv_release = [&](uint32_t n) { mbar_arrive_cluster_if(lane < 2, bars_lane + B_AEMPTY + 16 + 8 * (n & 3)); };
                struct Slot { uint32_t bar, par, off; } slot[4];
#pragma unroll
                for (uint32_t i = 0; i < 4; i++) {
                    const uint32_t n = kvn + 1 + (i ^ 2);
                    slot[i].bar = bars + B_AFULL + 16 + 8 * (n & 3); slot[i].par = (n >> 2) & 1; slot[i].off = (n & 3) * 2048;
                }
                kvn++;
                auto next_gate = [&]() {
                    g0 = lds_f32(bars + SM_GATE + (ti & 1) * 512 + 4 * row); g1 = lds_f32(bars + SM_GATE + (ti & 1) * 512 + 4 * row + 32);
                    ti++;
                };
                next_gate();
                auto scale_o = [&]() {
#pragma unroll
                    for (int j = 0; j < 16; j++) { o[4 * j] *= f0; o[4 * j + 1] *= f0; o[4 * j + 2] *= f1; o[4 * j + 3] *= f1; }
                };
                auto pack_o = [&](uint32_t (&v)[32]) {
#pragma unroll
                    for (int j = 0; j < 32; j++) v[j] = pack_bf16(o[2 * j], o[2 * j + 1]);
                };
                auto scales = [&]() { f0 = g0 * rcp(quad_sum(l0)); f1 = g1 * rcp(quad_sum(l1)); };
                auto issue = [&](auto even, uint32_t (&pin)[32], uint32_t (&pout)[32], bool fresh, bool last) {
                    constexpr bool EVEN = decltype(even)::value;
                    Slot& sk = slot[EVEN ? 0 : 2];
                    Slot& sv = slot[EVEN ? 1 : 3];
                    kvn += 2;
                    mbar_spin(sk.bar, sk.par);
                    bar_sync(1 + wg, 256);
                    qk_gemm(s, dA + qoff, dK + sk.off);
                    if (EVEN && fresh) {
                        scales();
                        next_gate();
                        n0 = 0.f; n1 = 0.f; l0 = 0.f; l1 = 0.f;
                        shifted = 0;
                        stage_acquire(0); stage_acquire(1);
                    }
                    if (!EVEN && pending) {
                        pack_o(pout);
                        write_blocks(std::integral_constant<int, 4>(), 0, pout);
                    }
                    if (last)
                        asm volatile("{\n.reg .pred P, Q;\n"
                                     "mbarrier.test_wait.parity.shared::cta.b64 Q, [%1], %2;\n"
                                     "mbarrier.test_wait.parity.shared::cta.b64 P, [%3], %4;\n"
                                     "ld.shared.u32 %0, [%5];\n"
                                     "@!Q or.b32 %0, %0, 0x10000;\n"
                                     "@!P mov.u32 %0, -1;\n}\n"
                                     : "=r"(peek) : "r"(bars + B_AFULL + 8 * (ti & 1)), "r"((ti >> 1) & 1), "r"(bars + B_IFULL + 8 * (qn % QDEPTH)),
                                       "r"((qn / QDEPTH) & 1), "r"(bars + SM_QUEUE + 4 * (qn % QDEPTH)) : "memory");
                    diag = item_asc(cur) ? last : fresh;
                    asm volatile("" : "+r"(diag));
                    mbar_spin(sv.bar, sv.par);
                    pv_gemm(o, pin, dV + sv.off, EVEN || !first);
                    bar_arrive(2 - wg, 256);
                    if (!EVEN && pending) {
                        write_blocks(std::integral_constant<int, 4>(), 8192, pout + 16);
                        publish_pair();
                    }
                    sk.par ^= 1; sv.par ^= 1;
                    wgmma_wait<1>();
                    fence_regs(s);
                    mbar_arrive_cluster_if(lane < 2, sk.bar + lane_off);
                    mbar_arrive_if(lane == 0 && last, bars + B_AEMPTY + 8 * ((ti - 1) & 1));
                };
                auto softmax = [&](auto even, uint32_t (&pin)[32], uint32_t (&pout)[32], bool fresh) {
                    constexpr bool EVEN = decltype(even)::value;
                    Slot& sv = slot[EVEN ? 1 : 3];
                    float r0, r1, x0 = n0, x1 = n1;
#pragma unroll 1
                    for (int mask = diag, redone = 0;; mask = 0, redone = 1) {
                        if (mask | shifted) {
                            if (mask) causal_mask(s, thr, wg);
                            if (shifted) shift_rows(s, x0, x1);
                        }
                        exp_pack(pout, s, r0, r1);
                        if (!__any_sync(0xffffffffu, fmaxf(r0, r1) >= SUM_LIMIT || (EVEN && fresh && !(lane & 3) && !(fminf(s[0], s[2]) >= -REF_RANGE))) || redone) break;
                        row_max(s, x0, x1);
                        if (!(EVEN && fresh)) { x0 = fmaxf(x0, 0.f); x1 = fmaxf(x1, 0.f); }
                        float a0 = ex2(-x0), a1 = ex2(-x1);
                        n0 += x0; n1 += x1;
                        shifted = 1;
                        if (EVEN && fresh) { a0 = 1.f; a1 = 1.f; }
                        l0 *= a0; l1 *= a1;
                        wgmma_wait<0>();
                        fence_regs(o);
#pragma unroll
                        for (int q = 0; q < 16; q++) { o[4 * q] *= a0; o[4 * q + 1] *= a0; o[4 * q + 2] *= a1; o[4 * q + 3] *= a1; }
                    }
                    l0 += r0; l1 += r1;
                    wgmma_wait<0>();
                    fence_regs(o);
                    fence_regs(pin);
                    mbar_arrive_cluster_if(lane < 2, sv.bar + lane_off);
                };
                auto copy_p = [&]() {
#pragma unroll
                    for (int j = 0; j < 32; j++) pa[j] = __float_as_uint(__uint_as_float(pb[j]) + __uint_as_float(prm.zero));
                };
                int rem = 0;
                mbar_arrive_if(lane == 0 && item_row(cur) == 0, bars + B_AEMPTY + 8 * ((ti - 1) & 1));
                zero_regs(pa);
                wgmma_fence();
                wgmma_ss_n128_init(o, full_desc(dA), full_desc(dK));
                wgmma_commit();
                while (true) {
                    const bool fresh = rem == 0;
                    softmax(std::true_type(), pa, pb, fresh);
                    first = fresh;
                    if (fresh) {
                        pending = has_pv; has_pv = 1;
                        if (pending) scale_o();
                        rem = item_row(cur) + 1;
                    }
                    if (--rem == 0) {
                        copy_p();
                        const Slot t0 = slot[0], t1 = slot[1];
                        slot[0] = slot[2]; slot[1] = slot[3]; slot[2] = t0; slot[3] = t1;
                    } else {
                        issue(std::false_type(), pb, pa, false, rem == 1);
                        softmax(std::false_type(), pb, pa, false);
                        pending = 0; first = 0;
                        rem--;
                    }
                    if (rem == 0) {
                        const int seen = peek;
                        if (seen >= 0) {
                            mbar_arrive_cluster_if(lane == 0, bars0 + B_IEMPTY + 8 * (qn % QDEPTH));
                            qn++;
                            it = seen & 0xffff;
                        } else {
                            it = take_item();
                        }
                        if (item_row(cur) < 2 || item_type(it) != T_ATTN) break;
                        if (seen & 0x10000) mbar_spin(bars + B_AFULL + 8 * (ti & 1), (ti >> 1) & 1);
                        cur = it;
                        qoff = (ti & 1) * 2048;
                    }
                    issue(std::true_type(), pa, pb, rem == 0, rem ? rem == 1 : item_row(cur) == 0);
                }
                const uint32_t skip = item_asc(cur) & ~item_row(cur) & 1;
                kvn += skip;
                const bool end = item_type(it) == T_END;
#pragma unroll 1
                for (int pass = pending ? 0 : 1; pass < 2; pass++) {
                    if (pass) {
                        kv_wait(kvn);
                        pv_gemm(o, pa, dV + (kvn & 3) * 2048, !first);
                        scales();
                        stage_acquire(0); stage_acquire(1);
                        if (end) it = take_item();
                        wgmma_wait<0>();
                        fence_regs(o);
                        kv_release(kvn);
                        kvn += 1 + skip;
                        scale_o();
                    }
                    pack_o(pb);
                    write_blocks(std::integral_constant<int, 8>(), 0, pb);
                    publish_pair();
                }
            }
        }
        if (item_type(it) == T_OUT) {
            float acc[128];
            const uint32_t dB = make_desc(sb + 16384, 8192);
            mbar_spin(bars + B_GFULL, gph);
            wgmma_fence();
            wgmma_ss_n256_tb_init(acc, full_desc(dA), full_desc(dB));
#pragma unroll
            for (int kk = 1; kk < 4; kk++) wgmma_ss_n256_tb(acc, full_desc(dA) + 2 * kk, full_desc(dB) + 128 * kk, 1);
            wgmma_commit();
            uint32_t ln;
            asm volatile("mov.u32 %0, %%laneid;" : "=r"(ln));
            char* const mine = (char*)prm.out + (uint32_t)((item_row(it) * 128 + wg * 64 + wq * 16 + (ln >> 4)) * 2048 + item_col(it) * 256 + (ln & 15) * 16);
            int k = 1, nk = 80;
            do {
                if ((uint32_t)(k - (K_MEET - 12)) < 8) *(uint4*)(mine + (uint32_t)(k - (K_MEET - 12)) * 4096) = make_uint4(0, 0, 0, 0);
                __syncwarp();
                if (k == K_SPLIT) nk = take_item() & 127;
                gemm_step(acc, dB, k, false);
            } while (k < nk);
            float lo[64];
            auto triple = [&](auto first) {
                const uint32_t s0 = k & 3, s1 = (k + 1) & 3, o0 = s0 * (GST_BYTES >> 4), o1 = s1 * (GST_BYTES >> 4);
                wgmma_wait<0>();
                mbar_arrive_cluster_if(ln < (decltype(first)::value ? 2 : 4), bars_lane + B_GEMPTY + 8 * ((k - 1 - (ln >> 1)) & 3));
                mbar_spin(bars + B_GFULL + 8 * s0, gph);
                gph ^= s0 == 3;
                wgmma_fence();
#pragma unroll
                for (int kk = 0; kk < 4; kk++) {
                    if (decltype(first)::value && kk == 0) wgmma_ss_n128_tb_init(lo, full_desc(dA + o0), full_desc(dB + o0));
                    else wgmma_ss_n128_tb(lo, full_desc(dA + o0) + 2 * kk, full_desc(dB + o0) + 128 * kk, 1);
                }
                mbar_spin(bars + B_GFULL + 8 * s1, gph);
                gph ^= s1 == 3;
                wgmma_fence();
#pragma unroll
                for (int kk = 0; kk < 4; kk++) wgmma_ss_n128_tb(lo, full_desc(dA + o0 + 2048) + 2 * kk, full_desc(dB + o1 + 1024) + 128 * kk, 1);
#pragma unroll
                for (int kk = 0; kk < 4; kk++) wgmma_ss_n128_tb(lo, full_desc(dA + o1) + 2 * kk, full_desc(dB + o1) + 128 * kk, 1);
                wgmma_commit();
                k += 2;
            };
            triple(std::true_type());
            fence_regs(acc);
            uint32_t pk[32];
#pragma unroll
            for (int j = 0; j < 32; j++) pk[j] = pack_bf16(acc[64 + 2 * j], acc[65 + 2 * j]);
            stage_acquire(0); stage_acquire(1);
            write_blocks(std::integral_constant<int, 8>(), 0, pk);
            publish_pair();
            triple(std::false_type());
            stage_acquire(0); stage_acquire(1);
            wgmma_wait<0>();
            fence_regs(lo);
            mbar_arrive_cluster_if(ln < 4, bars_lane + B_GEMPTY + 8 * ((k - 1 - (ln >> 1)) & 3));
#pragma unroll
            for (int b = 0; b < 2; b++) {
#pragma unroll
                for (int j = 16 * b; j < 16 * b + 16; j++) pk[j] = pack_bf16(acc[2 * j] + lo[2 * j], acc[2 * j + 1] + lo[2 * j + 1]);
                write_blocks(std::integral_constant<int, 4>(), b * 8192, pk + 16 * b);
                stage_publish(b);
            }
        }
    }
}

typedef CUresult (*EncodeFn)(CUtensorMap*, CUtensorMapDataType, cuuint32_t, void*, const cuuint64_t*, const cuuint64_t*,
                             const cuuint32_t*, const cuuint32_t*, CUtensorMapInterleave, CUtensorMapSwizzle,
                             CUtensorMapL2promotion, CUtensorMapFloatOOBfill);

void encode3(EncodeFn fn, CUtensorMap* m, const void* ptr, uint64_t d0, uint64_t d1, uint64_t d2, uint64_t s1, uint64_t s2,
             uint32_t b0, uint32_t b1, uint32_t b2) {
    cuuint64_t dims[3] = {d0, d1, d2};
    cuuint64_t strides[2] = {s1, s2};
    cuuint32_t box[3] = {b0, b1, b2};
    cuuint32_t es[3] = {1, 1, 1};
    fn(m, CU_TENSOR_MAP_DATA_TYPE_BFLOAT16, 3, const_cast<void*>(ptr), dims, strides, box, es, CU_TENSOR_MAP_INTERLEAVE_NONE,
       CU_TENSOR_MAP_SWIZZLE_128B, b2 > 1 ? CU_TENSOR_MAP_L2_PROMOTION_L2_256B : CU_TENSOR_MAP_L2_PROMOTION_NONE, CU_TENSOR_MAP_FLOAT_OOB_FILL_NONE);
}
void map_act(EncodeFn fn, CUtensorMap* m, const void* p, int rows, int cols, int box_rows) {
    encode3(fn, m, p, cols, rows, 1, (uint64_t)cols * 2, (uint64_t)cols * rows * 2, 64, box_rows, 1);
}
void map_wgt(EncodeFn fn, CUtensorMap* m, const void* p, int K, int N) {
    encode3(fn, m, p, 64, K, N / 64, (uint64_t)N * 2, 128, 64, 64, 2);
}

void build_schedule(Params& p) {
    int n = 0;
    auto add = [&](int type, int col, int row) { p.items[n++] = (uint16_t)(type << 13 | col << 4 | row); };
    int beta = 32, tail = 32, late = 6, early = 4, epos = 60;
    int order[16] = {6, 7, 8, 9, 10, 11, 12, 13, 14, 15, 5, 4, 3, 2, 1, 0};
    const char* plans = "xxxxxc,xxlcccccc,xxxxxc,xxlcccccc,xxllcclxxc,xxxllxxc,xxxlccccc,xxcccccc";
    const char* pos[8];
    int len[8] = {}, start[8] = {};
    for (int s = 0; s < 8; s++) { pos[s] = plans; while (*plans && *plans++ != ',') {} }
    for (int i = 0; i < 160; i++) p.plan[i / 16][i % 16] = T_END << 13;
    int lend[4] = {}, nset = 0, margin = 12;
    for (int c = 0; c < 16; c++) p.kgroup[c] = (uint8_t)(G_K + 2 * c);
    for (int nx = 0, nc = 3, nl = 0; nx + nc + nl < 28 + 32 + 8;) {
        int s = -1;
        for (int i = 0; i < 8; i++) if (*pos[i] > ',' && (s < 0 || start[i] < start[s])) s = i;
        const char kind = *pos[s]++;
        int it;
        if (kind == 'x') { it = nx < 12 ? T_B << 13 | (nx % 3 * 4 + nx / 3) << 4 : T_Q << 13 | (nx - 12) << 4; nx++; }
        else if (kind == 'c') { it = (T_K + (nc & 1)) << 13 | nc / 2 << 4; nc++; }
        else { it = T_LOCAL << 13 | nl / 2 << 4 | (nl & 1); nl++; }
        p.plan[s][len[s]++] = (uint16_t)it;
        start[s] += kind == 'x' ? 48 : kind == 'c' ? 24 : 8;
        if (kind == 'l') lend[(nl - 1) / 2] = start[s];
        if (kind == 'c' && (nc & 1) && nset < nl / 2 && start[s] >= lend[nset] + margin) p.kgroup[nc / 2] = (uint8_t)(G_B + 8 + 2 * nset++);
    }
    for (int i = 0; i < 24; i++) p.plan[8 + i / 12][i % 12] = (uint16_t)((T_K + (i % 3 & 1)) << 13 | i % 3 / 2 << 4 | i / 3);
    const int a0 = n;
    for (int key = 0; key < 4000; key++)
        for (int r = 0; r < 32; r++)
            for (int j = 7; j >= 0; j--)
                if ((j ? (7 - j) * 40 + r * beta : 3999) == key) add(T_ATTN, 2 * order[r >> 1] + (r & 1), j);
    int t0 = n;
    for (int work = 0; work < 32 * 136 * tail / 100;) work += 4 * (p.items[--t0] & 15) + 3;
    for (int i = t0 + 1; i < n; i++)
        for (int j = i; j > t0 && (p.items[j] & 15) > (p.items[j - 1] & 15); j--) { const uint16_t t = p.items[j]; p.items[j] = p.items[j - 1]; p.items[j - 1] = t; }
    for (int r = early - 1; r >= 0; r--) {
        const uint16_t t = p.items[n - 32 + early - 1];
        for (int j = n - 32 + early - 1; j > n - epos; j--) p.items[j] = p.items[j - 1];
        p.items[n - epos] = t;
    }
    for (int moved = 0; moved < 2 && late >= 0; moved++)
        for (int i = a0; i < n; i++)
            if (p.items[i] == (T_ATTN << 13 | (2 * order[15] + moved) << 4 | late)) {
                for (int j = i; j + 1 < n; j++) p.items[j] = p.items[j + 1];
                p.items[n - 1] = (uint16_t)(T_ATTN << 13 | (2 * order[15] + moved) << 4 | late);
                break;
            }
    for (int s = 0, lo = 0, hi = WIDE - 1; s < 80; s++) {
        const int r = s / 2, g = r < 8 ? 32 + r : 2 * order[r / 2 - 4] + (r & 1);
        p.ostep[s >= WIDE ? s : r & 1 ? hi-- : lo++] = (uint8_t)(2 * g + (s & 1));
    }
}

void build_params(Params& p, void* const* d_in, void* d_out) {
    void* fnp = nullptr;
    cudaDriverEntryPointQueryResult qr;
    cudaGetDriverEntryPoint("cuTensorMapEncodeTiled", &fnp, cudaEnableDefault, &qr);
    EncodeFn fn = (EncodeFn)fnp;
    void* scr = nullptr;
    cudaGetSymbolAddress(&scr, g_scr);
    map_act(fn, &p.m[M_X], d_in[0], SEQ, 1024, 128);
    map_act(fn, &p.m[M_C], d_in[1], SEQ, 512, 128);
    map_wgt(fn, &p.m[M_WQ], d_in[2], 1024, 4096);
    map_wgt(fn, &p.m[M_WUK], d_in[3], 512, 4096);
    map_wgt(fn, &p.m[M_WUV], d_in[4], 512, 4096);
    map_wgt(fn, &p.m[M_WO], d_in[5], 4096, 1024);
    map_wgt(fn, &p.m[M_WQKV], d_in[7], 1024, 3072);
    map_wgt(fn, &p.m[M_WOB], d_in[8], 1024, 1024);
    encode3(fn, &p.m[M_SCR_LD], scr, 128, SEQ, G_TOTAL, 256, (uint64_t)SEQ * 256, 64, 128, 1);
    encode3(fn, &p.m[M_SCR_LOC], scr, 256, SEQ / 2, G_TOTAL, 512, (uint64_t)SEQ * 256, 64, 72, 1);
    encode3(fn, &p.m[M_SCR_LOQ], scr, 256, SEQ / 2, G_TOTAL, 512, (uint64_t)SEQ * 256, 64, 64, 1);
    encode3(fn, &p.m[M_SCR_ST], scr, 128, SEQ, G_TOTAL, 256, (uint64_t)SEQ * 256, 64, 64, 1);
    map_act(fn, &p.m[M_OUT], d_out, SEQ, 1024, 64);
    p.x = (const __nv_bfloat16*)d_in[0];
    p.gate_w = (const __nv_bfloat16*)d_in[9];
    p.zero = 0;
    p.wo = (const char*)d_in[5];
    p.out = (__nv_bfloat16*)d_out;
    build_schedule(p);
}

}

extern "C" void kernel_launch(void* const* d_in, const int* in_sizes, int n_in, void* d_out, int out_size) {
    (void)in_sizes; (void)n_in; (void)out_size;
    Params p;
    build_params(p, d_in, d_out);
    cudaFuncSetAttribute(fused_kernel, cudaFuncAttributeMaxDynamicSharedMemorySize, SM_TOTAL);
    fused_kernel<<<NCTA, 384, SM_TOTAL>>>(p);
}
```

```cpp
#include <cuda_runtime.h>
#include <cuda_bf16.h>
#include <cuda.h>
#include <stddef.h>
#include <stdint.h>
#include <type_traits>

namespace {

constexpr int SEQ = 2048;
constexpr int G_Q = 0, G_K = 32, G_V = 64, G_B = 96, G_CTX = G_Q, G_LOC = G_B, G_TOTAL = 120;

__device__ __align__(1024) __nv_bfloat16 g_scr[(size_t)G_TOTAL * SEQ * 128];
__device__ __align__(128) float g_gate[SEQ];

__device__ __forceinline__ uint32_t smem_u32(const void* p) { return (uint32_t)__cvta_generic_to_shared(p); }
__device__ __forceinline__ bool elect_one() {
    uint32_t p;
    asm volatile("{\n.reg .pred P;\nelect.sync _|P, 0xffffffff;\nselp.u32 %0, 1, 0, P;\n}\n" : "=r"(p));
    return p != 0;
}
__device__ __forceinline__ void mbar_init(uint32_t bar, uint32_t count) {
    asm volatile("mbarrier.init.shared::cta.b64 [%0], %1;" :: "r"(bar), "r"(count) : "memory");
}
__device__ __forceinline__ uint32_t cluster_rank() { uint32_t r; asm("mov.u32 %0, %%cluster_ctarank;" : "=r"(r)); return r; }
__device__ __forceinline__ uint32_t map_cta(uint32_t addr, uint32_t cta) {
    uint32_t r; asm("mapa.shared::cluster.u32 %0, %1, %2;" : "=r"(r) : "r"(addr), "r"(cta)); return r;
}
__device__ __forceinline__ void mbar_arrive_cluster_if(bool pred, uint32_t cluster_bar) {
    asm volatile("{\n.reg .pred P;\nsetp.ne.u32 P, %1, 0;\n@P mbarrier.arrive.shared::cluster.b64 _, [%0];\n}\n"
                 :: "r"(cluster_bar), "r"((uint32_t)pred) : "memory");
}
__device__ __forceinline__ void mbar_arrive_cluster_n_if(bool pred, uint32_t cluster_bar, uint32_t count) {
    asm volatile("{\n.reg .pred P;\nsetp.ne.u32 P, %1, 0;\n@P mbarrier.arrive.shared::cluster.b64 _, [%0], %2;\n}\n"
                 :: "r"(cluster_bar), "r"((uint32_t)pred), "r"(count) : "memory");
}
__device__ __forceinline__ void mbar_arrive_if(bool pred, uint32_t bar) {
    asm volatile("{\n.reg .pred P;\nsetp.ne.u32 P, %1, 0;\n@P mbarrier.arrive.shared::cta.b64 _, [%0];\n}\n"
                 :: "r"(bar), "r"((uint32_t)pred) : "memory");
}
__device__ __forceinline__ bool mbar_test(uint32_t bar, uint32_t parity) {
    uint32_t ok;
    asm volatile("{\n.reg .pred P;\nmbarrier.test_wait.parity.shared::cta.b64 P, [%1], %2;\nselp.u32 %0, 1, 0, P;\n}\n"
                 : "=r"(ok) : "r"(bar), "r"(parity) : "memory");
    return ok != 0;
}
__device__ __forceinline__ void mbar_wait(uint32_t bar, uint32_t parity) {
    asm volatile("{\n.reg .pred P;\n.reg .u32 c;\n"
                 "mov.u32 c, 0;\n"
                 "SPIN:\n"
                 "mbarrier.try_wait.parity.shared::cta.b64 P, [%0], %1;\n"
                 "@P bra DONE;\n"
                 "add.u32 c, c, 1;\n"
                 "setp.lt.u32 P, c, 4194304;\n"
                 "@P bra SPIN;\n"
                 "trap;\n"
                 "DONE:\n}\n" :: "r"(bar), "r"(parity) : "memory");
}
__device__ __forceinline__ void mbar_spin(uint32_t bar, uint32_t parity) {
    asm volatile("{\n.reg .pred P;\n"
                 "SPIN:\n"
                 "mbarrier.try_wait.parity.shared::cta.b64 P, [%0], %1;\n"
                 "@!P bra SPIN;\n}\n" :: "r"(bar), "r"(parity) : "memory");
}
__device__ __forceinline__ void bar_sync(int id, int n) { asm volatile("bar.sync %0, %1;" :: "r"(id), "r"(n) : "memory"); }
__device__ __forceinline__ void bar_arrive(int id, int n) { asm volatile("bar.arrive %0, %1;" :: "r"(id), "r"(n) : "memory"); }
__device__ __forceinline__ void fence_proxy_async_smem() { asm volatile("fence.proxy.async.shared::cta;" ::: "memory"); }
__device__ __forceinline__ void warp_expect_tx(uint32_t bar, uint32_t bytes) {
    asm volatile("{\n.reg .pred P;\nelect.sync _|P, 0xffffffff;\n@P mbarrier.arrive.expect_tx.shared::cta.b64 _, [%0], %1;\n}\n"
                 :: "r"(bar), "r"(bytes) : "memory");
}
constexpr uint64_t EVICT_FIRST = 0x12F0000000000000ull;
__device__ __forceinline__ void warp_tma_load(uint32_t dst, const CUtensorMap* map, uint32_t bar, int c0, int c1, int c2, bool stream) {
    if (stream)
        asm volatile("{\n.reg .pred P;\nelect.sync _|P, 0xffffffff;\n"
                     "@P cp.async.bulk.tensor.3d.shared::cluster.global.mbarrier::complete_tx::bytes.L2::cache_hint"
                     " [%0], [%1, {%3, %4, %5}], [%2], %6;\n}\n"
                     :: "r"(dst), "l"(map), "r"(bar), "r"(c0), "r"(c1), "r"(c2), "l"(EVICT_FIRST) : "memory");
    else
        asm volatile("{\n.reg .pred P;\nelect.sync _|P, 0xffffffff;\n"
                     "@P cp.async.bulk.tensor.3d.shared::cluster.global.mbarrier::complete_tx::bytes [%0], [%1, {%3, %4, %5}], [%2];\n}\n"
                     :: "r"(dst), "l"(map), "r"(bar), "r"(c0), "r"(c1), "r"(c2) : "memory");
}
__device__ __forceinline__ void warp_tma_load_pair(uint32_t dst, const CUtensorMap* map, uint32_t bar, int c0, int c1, int c2, bool stream) {
    if (stream)
        asm volatile("{\n.reg .pred P;\nelect.sync _|P, 0xffffffff;\n"
                     "@P cp.async.bulk.tensor.3d.shared::cluster.global.mbarrier::complete_tx::bytes.multicast::cluster.L2::cache_hint"
                     " [%0], [%1, {%3, %4, %5}], [%2], %6, %7;\n}\n"
                     :: "r"(dst), "l"(map), "r"(bar), "r"(c0), "r"(c1), "r"(c2), "h"((uint16_t)3), "l"(EVICT_FIRST) : "memory");
    else
        asm volatile("{\n.reg .pred P;\nelect.sync _|P, 0xffffffff;\n"
                     "@P cp.async.bulk.tensor.3d.shared::cluster.global.mbarrier::complete_tx::bytes.multicast::cluster"
                     " [%0], [%1, {%3, %4, %5}], [%2], %6;\n}\n"
                     :: "r"(dst), "l"(map), "r"(bar), "r"(c0), "r"(c1), "r"(c2), "h"((uint16_t)3) : "memory");
}
__device__ __forceinline__ void warp_bulk_load(uint32_t dst, const void* src, uint32_t bytes, uint32_t bar) {
    asm volatile("{\n.reg .pred P;\nelect.sync _|P, 0xffffffff;\n"
                 "@P cp.async.bulk.shared::cluster.global.mbarrier::complete_tx::bytes [%0], [%1], %2, [%3];\n}\n"
                 :: "r"(dst), "l"(src), "r"(bytes), "r"(bar) : "memory");
}
__device__ __forceinline__ void warp_tma_store(const CUtensorMap* map, uint32_t src, int c0, int c1, int c2, bool stream) {
    if (stream)
        asm volatile("{\n.reg .pred P;\nelect.sync _|P, 0xffffffff;\n"
                     "@P cp.async.bulk.tensor.3d.global.shared::cta.bulk_group.L2::cache_hint [%0, {%2, %3, %4}], [%1], %5;\n}\n"
                     :: "l"(map), "r"(src), "r"(c0), "r"(c1), "r"(c2), "l"(EVICT_FIRST) : "memory");
    else
        asm volatile("{\n.reg .pred P;\nelect.sync _|P, 0xffffffff;\n"
                     "@P cp.async.bulk.tensor.3d.global.shared::cta.bulk_group [%0, {%2, %3, %4}], [%1];\n}\n"
                     :: "l"(map), "r"(src), "r"(c0), "r"(c1), "r"(c2) : "memory");
}
__device__ __forceinline__ void warp_tma_add(const CUtensorMap* map, uint32_t src, int c0, int c1, int c2) {
    asm volatile("{\n.reg .pred P;\nelect.sync _|P, 0xffffffff;\n"
                 "@P cp.reduce.async.bulk.tensor.3d.global.shared::cta.add.tile.bulk_group [%0, {%2, %3, %4}], [%1];\n}\n"
                 :: "l"(map), "r"(src), "r"(c0), "r"(c1), "r"(c2) : "memory");
}
__device__ __forceinline__ void warp_bulk_store(void* dst, uint32_t src, uint32_t bytes) {
    asm volatile("{\n.reg .pred P;\nelect.sync _|P, 0xffffffff;\n"
                 "@P cp.async.bulk.global.shared::cta.bulk_group [%0], [%1], %2;\n}\n" :: "l"(dst), "r"(src), "r"(bytes) : "memory");
}
__device__ __forceinline__ void warp_prefetch(const void* src, uint32_t bytes) {
    asm volatile("{\n.reg .pred P;\nelect.sync _|P, 0xffffffff;\n@P cp.async.bulk.prefetch.L2.global [%0], %1;\n}\n" :: "l"(src), "r"(bytes) : "memory");
}
__device__ __forceinline__ void bulk_commit() { asm volatile("cp.async.bulk.commit_group;" ::: "memory"); }
template <int N> __device__ __forceinline__ void bulk_wait_read() { asm volatile("cp.async.bulk.wait_group.read %0;" :: "n"(N) : "memory"); }
template <int N> __device__ __forceinline__ void bulk_wait() { asm volatile("cp.async.bulk.wait_group %0;" :: "n"(N) : "memory"); }
__device__ __forceinline__ void wgmma_fence() { asm volatile("wgmma.fence.sync.aligned;" ::: "memory"); }
__device__ __forceinline__ void wgmma_commit() { asm volatile("wgmma.commit_group.sync.aligned;" ::: "memory"); }
template <int N> __device__ __forceinline__ void wgmma_wait() { asm volatile("wgmma.wait_group.sync.aligned %0;" :: "n"(N) : "memory"); }
template <int N> __device__ __forceinline__ void fence_regs(float (&d)[N]) {
#pragma unroll
    for (int i = 0; i < N; i++) asm volatile("" : "+f"(d[i]) :: "memory");
}
template <int N> __device__ __forceinline__ void fence_regs(uint32_t (&d)[N]) {
#pragma unroll
    for (int i = 0; i < N; i++) asm volatile("" : "+r"(d[i]) :: "memory");
}
template <int N> __device__ __forceinline__ void reg_dec() { asm volatile("setmaxnreg.dec.sync.aligned.u32 %0;" :: "n"(N)); }
template <int N> __device__ __forceinline__ void reg_inc() { asm volatile("setmaxnreg.inc.sync.aligned.u32 %0;" :: "n"(N)); }
__device__ __forceinline__ uint32_t pack_bf16(float lo, float hi) {
    uint32_t r; asm("cvt.rn.bf16x2.f32 %0, %1, %2;" : "=r"(r) : "f"(hi), "f"(lo)); return r;
}
__device__ __forceinline__ void stmatrix_x4(uint32_t addr, uint32_t r0, uint32_t r1, uint32_t r2, uint32_t r3) {
    asm volatile("stmatrix.sync.aligned.m8n8.x4.shared.b16 [%0], {%1, %2, %3, %4};"
                 :: "r"(addr), "r"(r0), "r"(r1), "r"(r2), "r"(r3) : "memory");
}
__device__ __forceinline__ float ex2(float x) { float y; asm("ex2.approx.ftz.f32 %0, %1;" : "=f"(y) : "f"(x)); return y; }

constexpr uint32_t DESC_HI = (1024 >> 4) | (1u << 30);
__device__ __forceinline__ uint32_t make_desc(uint32_t addr, uint32_t lbo) {
    uint32_t lo = ((addr & 0x3FFFF) >> 4) | ((lbo >> 4) << 16);
    asm volatile("" : "+r"(lo));
    return lo;
}
__device__ __forceinline__ uint64_t full_desc(uint32_t lo) {
    uint64_t d; asm("mov.b64 %0, {%1, %2};" : "=l"(d) : "r"(lo), "r"(DESC_HI)); return d;
}

__device__ __forceinline__ void wgmma_ss_n256_tb_init(float (&d)[128], uint64_t da, uint64_t db) {
    asm volatile("{\n.reg .pred p;\n"
        "setp.ne.b32 p, 0, 0;\n"
        "wgmma.mma_async.sync.aligned.m64n256k16.f32.bf16.bf16 "
        "{%0, %1, %2, %3, %4, %5, %6, %7, %8, %9, %10, %11, %12, %13, %14, %15, %16, %17, %18, %19, %20, "
        "%21, %22, %23, %24, %25, %26, %27, %28, %29, %30, %31, %32, %33, %34, %35, %36, %37, %38, %39, %40, "
        "%41, %42, %43, %44, %45, %46, %47, %48, %49, %50, %51, %52, %53, %54, %55, %56, %57, %58, %59, %60, "
        "%61, %62, %63, %64, %65, %66, %67, %68, %69, %70, %71, %72, %73, %74, %75, %76, %77, %78, %79, %80, "
        "%81, %82, %83, %84, %85, %86, %87, %88, %89, %90, %91, %92, %93, %94, %95, %96, %97, %98, %99, "
        "%100, %101, %102, %103, %104, %105, %106, %107, %108, %109, %110, %111, %112, %113, %114, %115, "
        "%116, %117, %118, %119, %120, %121, %122, %123, %124, %125, %126, %127},"
        " %128, %129, p, 1, 1, 0, 1;\n}\n"
        : "=f"(d[0]), "=f"(d[1]), "=f"(d[2]), "=f"(d[3]), "=f"(d[4]), "=f"(d[5]), "=f"(d[6]), "=f"(d[7]),
        "=f"(d[8]), "=f"(d[9]), "=f"(d[10]), "=f"(d[11]), "=f"(d[12]), "=f"(d[13]), "=f"(d[14]), "=f"(d[15]),
        "=f"(d[16]), "=f"(d[17]), "=f"(d[18]), "=f"(d[19]), "=f"(d[20]), "=f"(d[21]), "=f"(d[22]),
        "=f"(d[23]), "=f"(d[24]), "=f"(d[25]), "=f"(d[26]), "=f"(d[27]), "=f"(d[28]), "=f"(d[29]),
        "=f"(d[30]), "=f"(d[31]), "=f"(d[32]), "=f"(d[33]), "=f"(d[34]), "=f"(d[35]), "=f"(d[36]),
        "=f"(d[37]), "=f"(d[38]), "=f"(d[39]), "=f"(d[40]), "=f"(d[41]), "=f"(d[42]), "=f"(d[43]),
        "=f"(d[44]), "=f"(d[45]), "=f"(d[46]), "=f"(d[47]), "=f"(d[48]), "=f"(d[49]), "=f"(d[50]),
        "=f"(d[51]), "=f"(d[52]), "=f"(d[53]), "=f"(d[54]), "=f"(d[55]), "=f"(d[56]), "=f"(d[57]),
        "=f"(d[58]), "=f"(d[59]), "=f"(d[60]), "=f"(d[61]), "=f"(d[62]), "=f"(d[63]), "=f"(d[64]),
        "=f"(d[65]), "=f"(d[66]), "=f"(d[67]), "=f"(d[68]), "=f"(d[69]), "=f"(d[70]), "=f"(d[71]),
        "=f"(d[72]), "=f"(d[73]), "=f"(d[74]), "=f"(d[75]), "=f"(d[76]), "=f"(d[77]), "=f"(d[78]),
        "=f"(d[79]), "=f"(d[80]), "=f"(d[81]), "=f"(d[82]), "=f"(d[83]), "=f"(d[84]), "=f"(d[85]),
        "=f"(d[86]), "=f"(d[87]), "=f"(d[88]), "=f"(d[89]), "=f"(d[90]), "=f"(d[91]), "=f"(d[92]),
        "=f"(d[93]), "=f"(d[94]), "=f"(d[95]), "=f"(d[96]), "=f"(d[97]), "=f"(d[98]), "=f"(d[99]),
        "=f"(d[100]), "=f"(d[101]), "=f"(d[102]), "=f"(d[103]), "=f"(d[104]), "=f"(d[105]), "=f"(d[106]),
        "=f"(d[107]), "=f"(d[108]), "=f"(d[109]), "=f"(d[110]), "=f"(d[111]), "=f"(d[112]), "=f"(d[113]),
        "=f"(d[114]), "=f"(d[115]), "=f"(d[116]), "=f"(d[117]), "=f"(d[118]), "=f"(d[119]), "=f"(d[120]),
        "=f"(d[121]), "=f"(d[122]), "=f"(d[123]), "=f"(d[124]), "=f"(d[125]), "=f"(d[126]), "=f"(d[127])
        : "l"(da), "l"(db));
}
__device__ __forceinline__ void wgmma_ss_n256_tb(float (&d)[128], uint64_t da, uint64_t db, int scale_d) {
    asm volatile("{\n.reg .pred p;\n"
        "setp.ne.b32 p, %130, 0;\n"
        "wgmma.mma_async.sync.aligned.m64n256k16.f32.bf16.bf16 "
        "{%0, %1, %2, %3, %4, %5, %6, %7, %8, %9, %10, %11, %12, %13, %14, %15, %16, %17, %18, %19, %20, "
        "%21, %22, %23, %24, %25, %26, %27, %28, %29, %30, %31, %32, %33, %34, %35, %36, %37, %38, %39, %40, "
        "%41, %42, %43, %44, %45, %46, %47, %48, %49, %50, %51, %52, %53, %54, %55, %56, %57, %58, %59, %60, "
        "%61, %62, %63, %64, %65, %66, %67, %68, %69, %70, %71, %72, %73, %74, %75, %76, %77, %78, %79, %80, "
        "%81, %82, %83, %84, %85, %86, %87, %88, %89, %90, %91, %92, %93, %94, %95, %96, %97, %98, %99, "
        "%100, %101, %102, %103, %104, %105, %106, %107, %108, %109, %110, %111, %112, %113, %114, %115, "
        "%116, %117, %118, %119, %120, %121, %122, %123, %124, %125, %126, %127},"
        " %128, %129, p, 1, 1, 0, 1;\n}\n"
        : "+f"(d[0]), "+f"(d[1]), "+f"(d[2]), "+f"(d[3]), "+f"(d[4]), "+f"(d[5]), "+f"(d[6]), "+f"(d[7]),
        "+f"(d[8]), "+f"(d[9]), "+f"(d[10]), "+f"(d[11]), "+f"(d[12]), "+f"(d[13]), "+f"(d[14]), "+f"(d[15]),
        "+f"(d[16]), "+f"(d[17]), "+f"(d[18]), "+f"(d[19]), "+f"(d[20]), "+f"(d[21]), "+f"(d[22]),
        "+f"(d[23]), "+f"(d[24]), "+f"(d[25]), "+f"(d[26]), "+f"(d[27]), "+f"(d[28]), "+f"(d[29]),
        "+f"(d[30]), "+f"(d[31]), "+f"(d[32]), "+f"(d[33]), "+f"(d[34]), "+f"(d[35]), "+f"(d[36]),
        "+f"(d[37]), "+f"(d[38]), "+f"(d[39]), "+f"(d[40]), "+f"(d[41]), "+f"(d[42]), "+f"(d[43]),
        "+f"(d[44]), "+f"(d[45]), "+f"(d[46]), "+f"(d[47]), "+f"(d[48]), "+f"(d[49]), "+f"(d[50]),
        "+f"(d[51]), "+f"(d[52]), "+f"(d[53]), "+f"(d[54]), "+f"(d[55]), "+f"(d[56]), "+f"(d[57]),
        "+f"(d[58]), "+f"(d[59]), "+f"(d[60]), "+f"(d[61]), "+f"(d[62]), "+f"(d[63]), "+f"(d[64]),
        "+f"(d[65]), "+f"(d[66]), "+f"(d[67]), "+f"(d[68]), "+f"(d[69]), "+f"(d[70]), "+f"(d[71]),
        "+f"(d[72]), "+f"(d[73]), "+f"(d[74]), "+f"(d[75]), "+f"(d[76]), "+f"(d[77]), "+f"(d[78]),
        "+f"(d[79]), "+f"(d[80]), "+f"(d[81]), "+f"(d[82]), "+f"(d[83]), "+f"(d[84]), "+f"(d[85]),
        "+f"(d[86]), "+f"(d[87]), "+f"(d[88]), "+f"(d[89]), "+f"(d[90]), "+f"(d[91]), "+f"(d[92]),
        "+f"(d[93]), "+f"(d[94]), "+f"(d[95]), "+f"(d[96]), "+f"(d[97]), "+f"(d[98]), "+f"(d[99]),
        "+f"(d[100]), "+f"(d[101]), "+f"(d[102]), "+f"(d[103]), "+f"(d[104]), "+f"(d[105]), "+f"(d[106]),
        "+f"(d[107]), "+f"(d[108]), "+f"(d[109]), "+f"(d[110]), "+f"(d[111]), "+f"(d[112]), "+f"(d[113]),
        "+f"(d[114]), "+f"(d[115]), "+f"(d[116]), "+f"(d[117]), "+f"(d[118]), "+f"(d[119]), "+f"(d[120]),
        "+f"(d[121]), "+f"(d[122]), "+f"(d[123]), "+f"(d[124]), "+f"(d[125]), "+f"(d[126]), "+f"(d[127])
        : "l"(da), "l"(db), "r"(scale_d));
}
__device__ __forceinline__ void wgmma_ss_n128_init(float (&d)[64], uint64_t da, uint64_t db) {
    asm volatile("{\n.reg .pred p;\n"
        "setp.ne.b32 p, 0, 0;\n"
        "wgmma.mma_async.sync.aligned.m64n128k16.f32.bf16.bf16 "
        "{%0, %1, %2, %3, %4, %5, %6, %7, %8, %9, %10, %11, %12, %13, %14, %15, %16, %17, %18, %19, %20, "
        "%21, %22, %23, %24, %25, %26, %27, %28, %29, %30, %31, %32, %33, %34, %35, %36, %37, %38, %39, %40, "
        "%41, %42, %43, %44, %45, %46, %47, %48, %49, %50, %51, %52, %53, %54, %55, %56, %57, %58, %59, %60, "
        "%61, %62, %63},"
        " %64, %65, p, 1, 1, 0, 0;\n}\n"
        : "=f"(d[0]), "=f"(d[1]), "=f"(d[2]), "=f"(d[3]), "=f"(d[4]), "=f"(d[5]), "=f"(d[6]), "=f"(d[7]),
        "=f"(d[8]), "=f"(d[9]), "=f"(d[10]), "=f"(d[11]), "=f"(d[12]), "=f"(d[13]), "=f"(d[14]), "=f"(d[15]),
        "=f"(d[16]), "=f"(d[17]), "=f"(d[18]), "=f"(d[19]), "=f"(d[20]), "=f"(d[21]), "=f"(d[22]),
        "=f"(d[23]), "=f"(d[24]), "=f"(d[25]), "=f"(d[26]), "=f"(d[27]), "=f"(d[28]), "=f"(d[29]),
        "=f"(d[30]), "=f"(d[31]), "=f"(d[32]), "=f"(d[33]), "=f"(d[34]), "=f"(d[35]), "=f"(d[36]),
        "=f"(d[37]), "=f"(d[38]), "=f"(d[39]), "=f"(d[40]), "=f"(d[41]), "=f"(d[42]), "=f"(d[43]),
        "=f"(d[44]), "=f"(d[45]), "=f"(d[46]), "=f"(d[47]), "=f"(d[48]), "=f"(d[49]), "=f"(d[50]),
        "=f"(d[51]), "=f"(d[52]), "=f"(d[53]), "=f"(d[54]), "=f"(d[55]), "=f"(d[56]), "=f"(d[57]),
        "=f"(d[58]), "=f"(d[59]), "=f"(d[60]), "=f"(d[61]), "=f"(d[62]), "=f"(d[63])
        : "l"(da), "l"(db));
}
__device__ __forceinline__ void wgmma_ss_n128(float (&d)[64], uint64_t da, uint64_t db, int scale_d) {
    asm volatile("{\n.reg .pred p;\n"
        "setp.ne.b32 p, %66, 0;\n"
        "wgmma.mma_async.sync.aligned.m64n128k16.f32.bf16.bf16 "
        "{%0, %1, %2, %3, %4, %5, %6, %7, %8, %9, %10, %11, %12, %13, %14, %15, %16, %17, %18, %19, %20, "
        "%21, %22, %23, %24, %25, %26, %27, %28, %29, %30, %31, %32, %33, %34, %35, %36, %37, %38, %39, %40, "
        "%41, %42, %43, %44, %45, %46, %47, %48, %49, %50, %51, %52, %53, %54, %55, %56, %57, %58, %59, %60, "
        "%61, %62, %63},"
        " %64, %65, p, 1, 1, 0, 0;\n}\n"
        : "+f"(d[0]), "+f"(d[1]), "+f"(d[2]), "+f"(d[3]), "+f"(d[4]), "+f"(d[5]), "+f"(d[6]), "+f"(d[7]),
        "+f"(d[8]), "+f"(d[9]), "+f"(d[10]), "+f"(d[11]), "+f"(d[12]), "+f"(d[13]), "+f"(d[14]), "+f"(d[15]),
        "+f"(d[16]), "+f"(d[17]), "+f"(d[18]), "+f"(d[19]), "+f"(d[20]), "+f"(d[21]), "+f"(d[22]),
        "+f"(d[23]), "+f"(d[24]), "+f"(d[25]), "+f"(d[26]), "+f"(d[27]), "+f"(d[28]), "+f"(d[29]),
        "+f"(d[30]), "+f"(d[31]), "+f"(d[32]), "+f"(d[33]), "+f"(d[34]), "+f"(d[35]), "+f"(d[36]),
        "+f"(d[37]), "+f"(d[38]), "+f"(d[39]), "+f"(d[40]), "+f"(d[41]), "+f"(d[42]), "+f"(d[43]),
        "+f"(d[44]), "+f"(d[45]), "+f"(d[46]), "+f"(d[47]), "+f"(d[48]), "+f"(d[49]), "+f"(d[50]),
        "+f"(d[51]), "+f"(d[52]), "+f"(d[53]), "+f"(d[54]), "+f"(d[55]), "+f"(d[56]), "+f"(d[57]),
        "+f"(d[58]), "+f"(d[59]), "+f"(d[60]), "+f"(d[61]), "+f"(d[62]), "+f"(d[63])
        : "l"(da), "l"(db), "r"(scale_d));
}
__device__ __forceinline__ void wgmma_rs_n128_tb(float (&d)[64], uint32_t a0, uint32_t a1, uint32_t a2, uint32_t a3, uint64_t db, int scale_d) {
    asm volatile("{\n.reg .pred p;\n"
        "setp.ne.b32 p, %69, 0;\n"
        "wgmma.mma_async.sync.aligned.m64n128k16.f32.bf16.bf16 "
        "{%0, %1, %2, %3, %4, %5, %6, %7, %8, %9, %10, %11, %12, %13, %14, %15, %16, %17, %18, %19, %20, "
        "%21, %22, %23, %24, %25, %26, %27, %28, %29, %30, %31, %32, %33, %34, %35, %36, %37, %38, %39, %40, "
        "%41, %42, %43, %44, %45, %46, %47, %48, %49, %50, %51, %52, %53, %54, %55, %56, %57, %58, %59, %60, "
        "%61, %62, %63},"
        " {%64, %65, %66, %67}, %68, p, 1, 1, 1;\n}\n"
        : "+f"(d[0]), "+f"(d[1]), "+f"(d[2]), "+f"(d[3]), "+f"(d[4]), "+f"(d[5]), "+f"(d[6]), "+f"(d[7]),
        "+f"(d[8]), "+f"(d[9]), "+f"(d[10]), "+f"(d[11]), "+f"(d[12]), "+f"(d[13]), "+f"(d[14]), "+f"(d[15]),
        "+f"(d[16]), "+f"(d[17]), "+f"(d[18]), "+f"(d[19]), "+f"(d[20]), "+f"(d[21]), "+f"(d[22]),
        "+f"(d[23]), "+f"(d[24]), "+f"(d[25]), "+f"(d[26]), "+f"(d[27]), "+f"(d[28]), "+f"(d[29]),
        "+f"(d[30]), "+f"(d[31]), "+f"(d[32]), "+f"(d[33]), "+f"(d[34]), "+f"(d[35]), "+f"(d[36]),
        "+f"(d[37]), "+f"(d[38]), "+f"(d[39]), "+f"(d[40]), "+f"(d[41]), "+f"(d[42]), "+f"(d[43]),
        "+f"(d[44]), "+f"(d[45]), "+f"(d[46]), "+f"(d[47]), "+f"(d[48]), "+f"(d[49]), "+f"(d[50]),
        "+f"(d[51]), "+f"(d[52]), "+f"(d[53]), "+f"(d[54]), "+f"(d[55]), "+f"(d[56]), "+f"(d[57]),
        "+f"(d[58]), "+f"(d[59]), "+f"(d[60]), "+f"(d[61]), "+f"(d[62]), "+f"(d[63])
        : "r"(a0), "r"(a1), "r"(a2), "r"(a3), "l"(db), "r"(scale_d));
}
__device__ __forceinline__ void wgmma_ss_n128_tb_init(float (&d)[64], uint64_t da, uint64_t db) {
    asm volatile("{\n.reg .pred p;\n"
        "setp.ne.b32 p, 0, 0;\n"
        "wgmma.mma_async.sync.aligned.m64n128k16.f32.bf16.bf16 "
        "{%0, %1, %2, %3, %4, %5, %6, %7, %8, %9, %10, %11, %12, %13, %14, %15, %16, %17, %18, %19, %20, "
        "%21, %22, %23, %24, %25, %26, %27, %28, %29, %30, %31, %32, %33, %34, %35, %36, %37, %38, %39, %40, "
        "%41, %42, %43, %44, %45, %46, %47, %48, %49, %50, %51, %52, %53, %54, %55, %56, %57, %58, %59, %60, "
        "%61, %62, %63},"
        " %64, %65, p, 1, 1, 0, 1;\n}\n"
        : "=f"(d[0]), "=f"(d[1]), "=f"(d[2]), "=f"(d[3]), "=f"(d[4]), "=f"(d[5]), "=f"(d[6]), "=f"(d[7]),
        "=f"(d[8]), "=f"(d[9]), "=f"(d[10]), "=f"(d[11]), "=f"(d[12]), "=f"(d[13]), "=f"(d[14]), "=f"(d[15]),
        "=f"(d[16]), "=f"(d[17]), "=f"(d[18]), "=f"(d[19]), "=f"(d[20]), "=f"(d[21]), "=f"(d[22]),
        "=f"(d[23]), "=f"(d[24]), "=f"(d[25]), "=f"(d[26]), "=f"(d[27]), "=f"(d[28]), "=f"(d[29]),
        "=f"(d[30]), "=f"(d[31]), "=f"(d[32]), "=f"(d[33]), "=f"(d[34]), "=f"(d[35]), "=f"(d[36]),
        "=f"(d[37]), "=f"(d[38]), "=f"(d[39]), "=f"(d[40]), "=f"(d[41]), "=f"(d[42]), "=f"(d[43]),
        "=f"(d[44]), "=f"(d[45]), "=f"(d[46]), "=f"(d[47]), "=f"(d[48]), "=f"(d[49]), "=f"(d[50]),
        "=f"(d[51]), "=f"(d[52]), "=f"(d[53]), "=f"(d[54]), "=f"(d[55]), "=f"(d[56]), "=f"(d[57]),
        "=f"(d[58]), "=f"(d[59]), "=f"(d[60]), "=f"(d[61]), "=f"(d[62]), "=f"(d[63])
        : "l"(da), "l"(db));
}
__device__ __forceinline__ void wgmma_ss_n128_tb(float (&d)[64], uint64_t da, uint64_t db, int scale_d) {
    asm volatile("{\n.reg .pred p;\n"
        "setp.ne.b32 p, %66, 0;\n"
        "wgmma.mma_async.sync.aligned.m64n128k16.f32.bf16.bf16 "
        "{%0, %1, %2, %3, %4, %5, %6, %7, %8, %9, %10, %11, %12, %13, %14, %15, %16, %17, %18, %19, %20, "
        "%21, %22, %23, %24, %25, %26, %27, %28, %29, %30, %31, %32, %33, %34, %35, %36, %37, %38, %39, %40, "
        "%41, %42, %43, %44, %45, %46, %47, %48, %49, %50, %51, %52, %53, %54, %55, %56, %57, %58, %59, %60, "
        "%61, %62, %63},"
        " %64, %65, p, 1, 1, 0, 1;\n}\n"
        : "+f"(d[0]), "+f"(d[1]), "+f"(d[2]), "+f"(d[3]), "+f"(d[4]), "+f"(d[5]), "+f"(d[6]), "+f"(d[7]),
        "+f"(d[8]), "+f"(d[9]), "+f"(d[10]), "+f"(d[11]), "+f"(d[12]), "+f"(d[13]), "+f"(d[14]), "+f"(d[15]),
        "+f"(d[16]), "+f"(d[17]), "+f"(d[18]), "+f"(d[19]), "+f"(d[20]), "+f"(d[21]), "+f"(d[22]),
        "+f"(d[23]), "+f"(d[24]), "+f"(d[25]), "+f"(d[26]), "+f"(d[27]), "+f"(d[28]), "+f"(d[29]),
        "+f"(d[30]), "+f"(d[31]), "+f"(d[32]), "+f"(d[33]), "+f"(d[34]), "+f"(d[35]), "+f"(d[36]),
        "+f"(d[37]), "+f"(d[38]), "+f"(d[39]), "+f"(d[40]), "+f"(d[41]), "+f"(d[42]), "+f"(d[43]),
        "+f"(d[44]), "+f"(d[45]), "+f"(d[46]), "+f"(d[47]), "+f"(d[48]), "+f"(d[49]), "+f"(d[50]),
        "+f"(d[51]), "+f"(d[52]), "+f"(d[53]), "+f"(d[54]), "+f"(d[55]), "+f"(d[56]), "+f"(d[57]),
        "+f"(d[58]), "+f"(d[59]), "+f"(d[60]), "+f"(d[61]), "+f"(d[62]), "+f"(d[63])
        : "l"(da), "l"(db), "r"(scale_d));
}
__device__ __forceinline__ void wgmma_ss_n64_lo(float (&d)[64], uint64_t da, uint64_t db, int scale_d) {
    asm volatile("{\n.reg .pred p;\n"
        "setp.ne.b32 p, %34, 0;\n"
        "wgmma.mma_async.sync.aligned.m64n64k16.f32.bf16.bf16 "
        "{%0, %1, %2, %3, %4, %5, %6, %7, %8, %9, %10, %11, %12, %13, %14, %15, %16, %17, %18, %19, %20, "
        "%21, %22, %23, %24, %25, %26, %27, %28, %29, %30, %31},"
        " %32, %33, p, 1, 1, 0, 0;\n}\n"
        : "+f"(d[0]), "+f"(d[1]), "+f"(d[2]), "+f"(d[3]), "+f"(d[4]), "+f"(d[5]), "+f"(d[6]), "+f"(d[7]),
        "+f"(d[8]), "+f"(d[9]), "+f"(d[10]), "+f"(d[11]), "+f"(d[12]), "+f"(d[13]), "+f"(d[14]), "+f"(d[15]),
        "+f"(d[16]), "+f"(d[17]), "+f"(d[18]), "+f"(d[19]), "+f"(d[20]), "+f"(d[21]), "+f"(d[22]),
        "+f"(d[23]), "+f"(d[24]), "+f"(d[25]), "+f"(d[26]), "+f"(d[27]), "+f"(d[28]), "+f"(d[29]),
        "+f"(d[30]), "+f"(d[31])
        : "l"(da), "l"(db), "r"(scale_d));
}

enum { M_X = 0, M_C, M_WQ, M_WUK, M_WUV, M_WQKV, M_WO, M_WOB, M_SCR_LD, M_SCR_LOC, M_SCR_LOQ, M_SCR_ST, M_OUT, M_COUNT };
enum { T_Q = 0, T_K, T_V, T_B, T_OUT, T_LOCAL, T_ATTN, T_END };
constexpr int NCTA = 132;
constexpr int NITEMS = 256;
constexpr int TRIPLES = 2, WIDE = 80 - 3 * TRIPLES;
struct Params {
    CUtensorMap m[M_COUNT];
    const __nv_bfloat16* x;
    const __nv_bfloat16* gate_w;
    const char* wo;
    __nv_bfloat16* out;
    uint32_t zero;
    uint16_t plan[10][16];
    uint16_t items[NITEMS];
    uint8_t ostep[80];
    uint8_t kgroup[16];
};
__device__ __forceinline__ int item_type(int it) { return it >> 13; }
__device__ __forceinline__ int item_row(int it) { return it & 15; }
__device__ __forceinline__ int item_col(int it) { return (it >> 4) & 31; }
__device__ __forceinline__ int item_asc(int it) { return (it >> 9) & 1; }
constexpr int ITEM_READY = 1 << 10;

struct __align__(128) Sync {
    unsigned long long count[4];
    __align__(128) unsigned long long ctx[16];
    unsigned next, next_out, done;
    unsigned used;
    __align__(128) unsigned step[32][2];
    unsigned split[32];
};
__device__ Sync g_sync;

constexpr uint32_t GST_BYTES = 49152, SM_KV = 65536, SM_STAGING = 196608, SM_BARS = SM_STAGING + 32768;
constexpr uint32_t B_GFULL = 0, B_GEMPTY = 32, B_AFULL = 64, B_AEMPTY = 112, B_SFULL = 160, B_SEMPTY = 192,
                   B_IFULL = 224, B_IEMPTY = 288, B_XFREE = 352, B_WANT = 384, B_MEET = 392, B_HALF = 416,
                   SM_ORDY = 448, SM_QUEUE = 456, B_ALT = 488, B_QFREE = 504, SM_GATE = 512, SM_TOTAL = SM_BARS + 1536;
constexpr int QDEPTH = 8;
constexpr int FIRST_PAIR = 6;
constexpr int K_MEET = 16, K_SPLIT = 30;
constexpr int K_FETCH = 20;
constexpr uint32_t LOC_PLANE = 72 * 128;
constexpr float LOC_SCALE = 0.17677669529663687f * 1.4426950408889634f;
constexpr float SUM_LIMIT = 1180591620717411303424.f;
constexpr float REF_RANGE = 60.f;

__device__ __forceinline__ unsigned ld_acquire(const unsigned* p) {
    unsigned v; asm volatile("ld.acquire.gpu.global.u32 %0, [%1];" : "=r"(v) : "l"(p) : "memory"); return v;
}
__device__ __forceinline__ unsigned long long ld_acquire(const unsigned long long* p) {
    unsigned long long v; asm volatile("ld.acquire.gpu.global.u64 %0, [%1];" : "=l"(v) : "l"(p) : "memory"); return v;
}
__device__ __forceinline__ void spin_guard(unsigned& n) {
    asm volatile("{\n.reg .pred P;\nadd.u32 %0, %0, 1;\nsetp.gt.u32 P, %0, 16777216;\n@P trap;\n}\n" : "+r"(n));
    if (n > 1) __nanosleep(100);
}
__device__ __forceinline__ void red_add(unsigned long long* p, unsigned long long v) {
    asm volatile("red.release.gpu.global.add.u64 [%0], %1;" :: "l"(p), "l"(v) : "memory");
}
__device__ __forceinline__ float rcp(float x) { float y; asm("rcp.approx.ftz.f32 %0, %1;" : "=f"(y) : "f"(x)); return y; }
__device__ __forceinline__ float lds_f32(uint32_t addr) {
    float v; asm volatile("ld.shared.f32 %0, [%1];" : "=f"(v) : "r"(addr) : "memory"); return v;
}
__device__ __forceinline__ void ldsm_x4(uint32_t (&r)[4], uint32_t addr) {
    asm volatile("ldmatrix.sync.aligned.m8n8.x4.shared.b16 {%0, %1, %2, %3}, [%4];"
                 : "=r"(r[0]), "=r"(r[1]), "=r"(r[2]), "=r"(r[3]) : "r"(addr) : "memory");
}
__device__ __forceinline__ void ldsm_x4_t(uint32_t (&r)[4], uint32_t addr) {
    asm volatile("ldmatrix.sync.aligned.m8n8.x4.trans.shared.b16 {%0, %1, %2, %3}, [%4];"
                 : "=r"(r[0]), "=r"(r[1]), "=r"(r[2]), "=r"(r[3]) : "r"(addr) : "memory");
}
__device__ __forceinline__ void mma_k16(float (&d)[4], const uint32_t (&a)[4], uint32_t b0, uint32_t b1) {
    asm("mma.sync.aligned.m16n8k16.row.col.f32.bf16.bf16.f32 {%0,%1,%2,%3}, {%4,%5,%6,%7}, {%8,%9}, {%0,%1,%2,%3};"
        : "+f"(d[0]), "+f"(d[1]), "+f"(d[2]), "+f"(d[3]) : "r"(a[0]), "r"(a[1]), "r"(a[2]), "r"(a[3]), "r"(b0), "r"(b1));
}
__device__ __forceinline__ void mma_k16_init(float (&d)[4], const uint32_t (&a)[4], uint32_t b0, uint32_t b1) {
    asm("{\n.reg .f32 z;\nmov.f32 z, 0f00000000;\n"
        "mma.sync.aligned.m16n8k16.row.col.f32.bf16.bf16.f32 {%0,%1,%2,%3}, {%4,%5,%6,%7}, {%8,%9}, {z,z,z,z};\n}\n"
        : "=f"(d[0]), "=f"(d[1]), "=f"(d[2]), "=f"(d[3]) : "r"(a[0]), "r"(a[1]), "r"(a[2]), "r"(a[3]), "r"(b0), "r"(b1));
}
__device__ __forceinline__ void mma_k8(float (&d)[4], uint32_t a0, uint32_t a1, uint32_t b0) {
    asm("mma.sync.aligned.m16n8k8.row.col.f32.bf16.bf16.f32 {%0,%1,%2,%3}, {%4,%5}, {%6}, {%0,%1,%2,%3};"
        : "+f"(d[0]), "+f"(d[1]), "+f"(d[2]), "+f"(d[3]) : "r"(a0), "r"(a1), "r"(b0));
}
template <typename T, int N> __device__ __forceinline__ void zero_regs(T (&d)[N]) {
#pragma unroll
    for (int i = 0; i < N; i++) d[i] = 0;
}
__device__ __forceinline__ float quad_max(float v) {
    v = fmaxf(v, __shfl_xor_sync(0xffffffffu, v, 1));
    return fmaxf(v, __shfl_xor_sync(0xffffffffu, v, 2));
}
__device__ __forceinline__ float quad_sum(float v) {
    v += __shfl_xor_sync(0xffffffffu, v, 1);
    return v + __shfl_xor_sync(0xffffffffu, v, 2);
}

template <bool HALF>
__device__ __forceinline__ void qk_steps(float (&s)[64], uint32_t q_lo, uint32_t k_lo) {
    const uint64_t dq = full_desc(q_lo), dk = full_desc(k_lo);
    wgmma_fence();
    wgmma_ss_n128_init(s, dq, dk);
#pragma unroll
    for (int kk = 1; kk < 8; kk++) {
        const uint32_t o = (kk >> 2) * 1024 + (kk & 3) * 2;
        if (HALF) wgmma_ss_n64_lo(s, dq + o, dk + o, 1);
        else wgmma_ss_n128(s, dq + o, dk + o, 1);
    }
    wgmma_commit();
}
__device__ __forceinline__ void qk_gemm(float (&s)[64], uint32_t q_lo, uint32_t k_lo, bool half) {
    if (half) qk_steps<true>(s, q_lo, k_lo);
    else qk_steps<false>(s, q_lo, k_lo);
}
template <int NK>
__device__ __forceinline__ void pv_steps(float (&o)[64], uint32_t (&p)[32], uint32_t v_lo, int accumulate) {
    const uint64_t dv = full_desc(v_lo);
    fence_regs(o);
    fence_regs(p);
    wgmma_fence();
#pragma unroll
    for (int kk = 0; kk < NK; kk++)
        wgmma_rs_n128_tb(o, p[4 * kk], p[4 * kk + 1], p[4 * kk + 2], p[4 * kk + 3], dv + kk * 128, kk != 0 || accumulate);
    wgmma_commit();
}
__device__ __forceinline__ void pv_gemm(float (&o)[64], uint32_t (&p)[32], uint32_t v_lo, int accumulate, bool half) {
    if (half) pv_steps<4>(o, p, v_lo, accumulate);
    else pv_steps<8>(o, p, v_lo, accumulate);
}
__device__ __forceinline__ void row_max(const float (&s)[64], float& x0, float& x1) {
    float z0 = fmaxf(s[0], s[1]), z1 = fmaxf(s[2], s[3]);
    x0 = fmaxf(s[4], s[5]); x1 = fmaxf(s[6], s[7]);
#pragma unroll
    for (int j = 2; j < 16; j += 2) {
        z0 = fmaxf(z0, fmaxf(s[4 * j], s[4 * j + 1]));
        z1 = fmaxf(z1, fmaxf(s[4 * j + 2], s[4 * j + 3]));
        x0 = fmaxf(x0, fmaxf(s[4 * j + 4], s[4 * j + 5]));
        x1 = fmaxf(x1, fmaxf(s[4 * j + 6], s[4 * j + 7]));
    }
    x0 = quad_max(fmaxf(x0, z0)); x1 = quad_max(fmaxf(x1, z1));
}
template <int NJ>
__device__ __forceinline__ void exp_pack(uint32_t (&p)[32], const float (&s)[64], float& r0, float& r1) {
#pragma unroll
    for (int j = 2 * NJ; j < 32; j++) p[j] = 0;
#pragma unroll
    for (int j = 0; j < NJ; j++) {
        const float e0 = ex2(s[4 * j]), e1 = ex2(s[4 * j + 1]), e2 = ex2(s[4 * j + 2]), e3 = ex2(s[4 * j + 3]);
        if (j == 0) { r0 = e0 + e1; r1 = e2 + e3; }
        else { r0 += e0 + e1; r1 += e2 + e3; }
        p[2 * j] = pack_bf16(e0, e1);
        p[2 * j + 1] = pack_bf16(e2, e3);
    }
}
__device__ __forceinline__ void shift_rows(float (&s)[64], float d0, float d1) {
#pragma unroll
    for (int j = 0; j < 16; j++) { s[4 * j] -= d0; s[4 * j + 1] -= d0; s[4 * j + 2] -= d1; s[4 * j + 3] -= d1; }
}
constexpr float MASKED = -3e38f;
template <int J0>
__device__ __forceinline__ void mask_triangle(float (&s)[64], float thr) {
#pragma unroll
    for (int j = 0; j < 16; j++) {
        const float m = __saturatef((float)(8 * (j >> 1) + (j & 1)) - thr);
        const int i = 4 * (J0 + (j >> 1)) + (j & 1);
        s[i] = fmaf(m, MASKED, s[i]);
        if (j < 14) s[i + 6] = fmaf(m, MASKED, s[i + 6]);
    }
}
__device__ __forceinline__ void causal_mask(float (&s)[64], float thr, int wg) {
    asm volatile("" : "+f"(thr));
    if (wg == 0) mask_triangle<0>(s, thr);
    else mask_triangle<8>(s, thr);
}

__global__ void __cluster_dims__(2, 1, 1) __launch_bounds__(384, 1) fused_kernel(const __grid_constant__ Params prm) {
    extern __shared__ __align__(1024) uint8_t smem[];
    const uint32_t sb = smem_u32(smem), bars = sb + SM_BARS;
    const int warp = __shfl_sync(0xffffffffu, threadIdx.x >> 5, 0), lane = threadIdx.x & 31;

    const uint32_t rank = cluster_rank();
    const uint32_t bars0 = map_cta(bars, 0), bars_peer = map_cta(bars, rank ^ 1);

    auto plan_index = [&]() -> uint32_t {
        uint32_t p = blockIdx.x >> 1;
        asm volatile("" : "+r"(p));
        const uint32_t r = (p - 36) * 37 >> 8;
        return p < 4 ? 4 + p : p < 36 ? (p - 4 & 7) * 8 + (p - 4 >> 3) : p < 64 ? (p - 35 - 7 * r) * 8 + 4 + r : p;
    };
    auto first_item = [&]() -> int {
        const uint32_t pair = plan_index();
        const uint32_t slot = pair & 7, c = slot * 11 >> 5;
        return pair < 64 ? T_B << 13 | (4 * slot - 11 * c) << 4 | (2 * (pair >> 3) + rank) : T_K << 13 | (8 * slot + rank);
    };
    if (warp == 0) {
        if (elect_one())
            for (int k = 0; k < 4; k++) mbar_init(bars + B_GFULL + 8 * k, 1);
        const int first_it = __shfl_sync(0xffffffffu, first_item(), 0);
        asm volatile("fence.mbarrier_init.release.cluster;" ::: "memory");
        fence_proxy_async_smem();
        __syncwarp();
        asm volatile("barrier.cluster.arrive.relaxed.aligned;" ::: "memory");
        const CUtensorMap* ma = &prm.m[item_type(first_it) == T_K ? M_C : M_X];
        const CUtensorMap* mb = &prm.m[M_WQ + item_type(first_it)];
#pragma unroll
        for (int k = 0; k < 2; k++) {
            const uint32_t dst = sb + k * GST_BYTES, fb = bars + B_GFULL + 8 * k;
            warp_expect_tx(fb, GST_BYTES);
            warp_tma_load(dst + 16384, mb, fb, 0, k * 64, item_col(first_it) * 4, true);
            warp_tma_load(dst, ma, fb, k * 64, item_row(first_it) * 128, 0, false);
            warp_tma_load(dst + 32768, mb, fb, 0, k * 64, item_col(first_it) * 4 + 2, true);
        }
    }
    if (threadIdx.x == 32) {
        for (int i = 0; i < 4; i++) mbar_init(bars + B_GEMPTY + 8 * i, 16);
        for (int i = 0; i < 6; i++) { mbar_init(bars + B_AFULL + 8 * i, 1); mbar_init(bars + B_AEMPTY + 8 * i, i < 2 ? 8 : 16); }
        for (int i = 0; i < 4; i++) { mbar_init(bars + B_SFULL + 8 * i, 4); mbar_init(bars + B_SEMPTY + 8 * i, 1); }
        for (int i = 0; i < QDEPTH; i++) { mbar_init(bars + B_IFULL + 8 * i, 1); mbar_init(bars + B_IEMPTY + 8 * i, 23); }
        mbar_init(bars + B_WANT, 2); mbar_init(bars + B_MEET, 1); mbar_init(bars + B_XFREE, 1);
        for (int i = 0; i < 4; i++) mbar_init(bars + B_HALF + 8 * i, 1);
        mbar_init(bars + B_ALT, 4); mbar_init(bars + B_ALT + 8, 4); mbar_init(bars + B_QFREE, 2);
        asm volatile("st.shared.u64 [%0], 0;" :: "r"(bars + SM_ORDY) : "memory");
        asm volatile("fence.mbarrier_init.release.cluster;\nfence.acq_rel.cta;" ::: "memory");
    }
    __syncwarp();
    if (warp != 0) asm volatile("barrier.cluster.arrive.relaxed.aligned;" ::: "memory");
    asm volatile("barrier.cluster.wait.acquire.aligned;" ::: "memory");

    uint32_t qn = 0;
    auto next_item = [&](bool releaser, bool bounded = true) -> int {
        const uint32_t slot = qn % QDEPTH;
        if (bounded) mbar_wait(bars + B_IFULL + 8 * slot, (qn / QDEPTH) & 1);
        else mbar_spin(bars + B_IFULL + 8 * slot, (qn / QDEPTH) & 1);
        uint32_t it;
        asm volatile("ld.shared.u32 %0, [%1];" : "=r"(it) : "r"(bars + SM_QUEUE + 4 * slot) : "memory");
        mbar_arrive_cluster_if(releaser, bars0 + B_IEMPTY + 8 * slot);
        qn++;
        return it;
    };

    if (warp < 4) {
        reg_dec<40>();
        if (warp == 0) {
            {
                uint32_t gph = 1;
                const uint32_t prank = __shfl_sync(0xffffffffu, rank, 0);
                auto request = [&]() { mbar_arrive_cluster_if(lane == 0, bars0 + B_WANT); };
                auto take_item = [&]() -> int { return __shfl_sync(0xffffffffu, next_item(lane == 0), 0); };
                auto inputs_seen = [&](uint32_t word, unsigned& n) -> uint32_t {
                    uint32_t v;
                    spin_guard(n);
                    asm volatile("ld.acquire.cta.shared.u32 %0, [%1];" : "=r"(v) : "r"(bars + SM_ORDY + 4 * word) : "memory");
                    return __shfl_sync(0xffffffffu, v, 0);
                };
                uint32_t oneed = 0;
                auto wait_inputs = [&](int it) {
                    if (it & ITEM_READY) return;
                    oneed += 256;
                    for (unsigned n = 0; inputs_seen(1, n) < oneed;) {}
                };
                int nxt = first_item(), ring = -1, rot = 0;
                for (int k0 = 2; item_type(nxt) <= T_LOCAL; k0 = 0) {
                    const int type = item_type(nxt), m = item_row(nxt), c = item_col(nxt);
                    if (type == T_LOCAL) {
                        wait_inputs(nxt);
                        request();
#pragma unroll 1
                        for (uint32_t st = 0; st < 4; st++) {
                            mbar_wait(bars + B_GEMPTY + 8 * st, gph);
                            const uint32_t dst = sb + st * GST_BYTES, fb = bars + B_GFULL + 8 * st;
                            warp_expect_tx(fb, st == 0 ? 32768 + 512 : st == 3 ? 0 : 4 * LOC_PLANE);
                            if (st == 3) break;
                            if (st == 0) warp_bulk_load(dst + 4 * LOC_PLANE, &g_gate[m * 128], 512, fb);
#pragma unroll 1
                            for (int i = 0; i < 4; i++)
                                warp_tma_load(dst + i * LOC_PLANE, &prm.m[st ? M_SCR_LOC : M_SCR_LOQ], fb, i * 64, m * 64 - (st ? 8 : 0), G_B + 8 * st + c, false);
                        }
                        gph ^= 1;
                        ring = -1;
                    } else {
                        const int nk = type == T_K || type == T_V ? 8 : 16, kept = ring == m + 16 * nk ? 4 : 0;
                        ring = m + 16 * nk;
                        rot = kept ? rot - 4 : 0;
                        const CUtensorMap* ma = &prm.m[nk == 8 ? M_C : M_X];
                        const CUtensorMap* mb = &prm.m[M_WQ + type];
#pragma unroll 1
                        for (int k = k0; k < nk; k++) {
                            if (k == nk - 3) request();
                            const uint32_t st = k & 3, dst = sb + st * GST_BYTES, fb = bars + B_GFULL + 8 * st;
                            const int kc = ((k + rot) & (nk - 1)) * 64;
                            mbar_wait(bars + B_GEMPTY + 8 * st, gph);
                            warp_expect_tx(fb, k < kept ? 32768 : GST_BYTES);
                            if (k >= kept) warp_tma_load(dst, ma, fb, kc, m * 128, 0, c == 15 && type != T_K);
                            warp_tma_load_pair(dst + 16384 + prank * 16384, mb, fb, 0, kc, c * 4 + 2 * prank, blockIdx.x < 128 || (m & 6) == 6);
                            if (st == 3) gph ^= 1;
                        }
                    }
                    nxt = take_item();
                }
                uint32_t kv = 0, kvph = 1;
                uint32_t qc = 0;
                auto a_parity = [&](uint32_t b) { return b < 2 ? (((qc + 1 - b) >> 1) & 1) ^ 1 : kvph ^ (b - 2 < kv); };
                const CUtensorMap* tile_map = &prm.m[M_SCR_LD];
                asm volatile("" : "+l"(tile_map));
                {
                    bool need_g = true, more = true;
                    int pv_grp = -1, pv_row = 0;
                    int pv_shared = 0;
                    bool peer_longer = false;
                    int m = 0, kg = 0, vg = 0, asc = 0, nu = 0, uend = 0, ureq = -1, ufetch = 0;
#pragma unroll 1
                    for (int u = 0;; u++) {
                        if (u == ufetch) {
                            if (qc) nxt = take_item();
                            if (item_type(nxt) == T_ATTN) {
                                wait_inputs(nxt);
                                const uint32_t b = qc & 1, dst = sb + b * 32768, fb = bars + B_AFULL + 8 * b, row = item_row(nxt) * 128;
                                mbar_wait(bars + (qc == 0 ? B_GEMPTY : qc == 1 ? B_QFREE : B_AEMPTY + 8 * b), qc == 0 ? gph : qc == 1 ? 0 : a_parity(b));
                                warp_expect_tx(fb, 32768 + 512);
                                warp_tma_load(dst, tile_map, fb, 0, row, G_Q + item_col(nxt), false);
                                warp_tma_load(dst + 16384, tile_map, fb, 64, row, G_Q + item_col(nxt), false);
                                warp_bulk_load(bars + SM_GATE + b * 512, &g_gate[row], 512, fb);
                                qc++;
                            }
                        }
                        if (u == uend) {
                            if (!more) break;
                            more = item_type(nxt) == T_ATTN;
                            m = item_row(nxt); asc = item_asc(nxt);
                            kg = prm.kgroup[item_col(nxt) >> 1] + (item_col(nxt) & 1); vg = kg + (kg < G_V ? 32 : 8);
                            nu = more ? 2 * m + 2 : 0;
                            uend = nu + ((more ? m < 2 : pv_grp >= 0) ? 3 : 0);
                            ureq = 2 * max(m - 2 - (asc & m), 0);
                            ufetch = !more ? -1 : m ? 2 * m : uend;
                            u = -1;
                            continue;
                        }
                        int grp = pv_grp, row = pv_row;
                        int shared = pv_shared;
                        if (u >= nu) {
                            if (u == nu + 1) pv_grp = -1;
                            else if (peer_longer) { grp = -1; shared = 0; }
                            else continue;
                        } else {
                            const int j = asc ? u >> 1 : m - (u >> 1);
                            if (u & 1) {
                                pv_grp = vg; pv_row = j * 128; pv_shared = (m | 1) - j;
                                peer_longer = asc & ~m & 1;
                                if (u == nu - 1 && (m & 1) && item_type(nxt) == T_END) mbar_arrive_cluster_n_if(lane == 0, bars0 + B_WANT, 2);
                                if (grp < 0) continue;
                            } else {
                                if (u == ureq) request();
                                grp = kg; row = j * 128; shared = (m | 1) - j;
                            }
                        }
                        uint32_t fb = bars + B_AFULL + 16 + 8 * kv, mine = sb + SM_KV + kv * 32768 + prank * 16384;
                        int c_mine = prank * 64;
                        asm volatile("" : "+r"(mine), "+r"(fb), "+r"(row), "+r"(grp), "+r"(c_mine));
                        mbar_wait(need_g ? bars + B_GEMPTY + 8 + 8 * kv : fb + B_AEMPTY - B_AFULL, need_g ? gph : kvph);
                        warp_expect_tx(fb, grp < 0 ? 0 : 32768);
                        if (shared) {
                            warp_tma_load_pair(mine, tile_map, fb, c_mine, row, grp, shared == 1);
                        } else if (grp >= 0) {
                            warp_tma_load(mine, tile_map, fb, c_mine, row, grp, true);
                            warp_tma_load(mine + 16384 - prank * 32768, tile_map, fb, 64 - c_mine, row, grp, true);
                        } else {
                            mbar_arrive_cluster_n_if(lane < 2, map_cta(fb, lane & 1) + B_AEMPTY - B_AFULL, 8);
                        }
                        if (kv == 2) need_g = false;
                        if (++kv == 4) { kv = 0; kvph ^= 1; }
                    }
                }
                if (!qc) request();
                const int it = take_item();
                int nk = 0;
                if (item_type(it) == T_OUT) {
                    const int m = item_row(it), c = item_col(it), half = c & 1;
                    nk = 80;
                    for (unsigned n = 0; (inputs_seen(1, n) & 255) != 255;) {}
                    mbar_wait(bars + B_GEMPTY + 24, gph);
                    mbar_wait(bars + B_QFREE, 0);
                    mbar_wait(bars + B_AEMPTY + 8 * (qc & 1), a_parity(qc & 1));
#pragma unroll 1
                    for (uint32_t k = 0; k < 4; k++) {
                        const uint32_t sa = prm.ostep[half ? WIDE - 1 - k : k], dst = sb + k * GST_BYTES, fb = bars + B_GFULL + 8 * k;
                        const uint32_t b0 = k ? 1 + k : ~qc & 1, b1 = 2 + k - (k == 1);
                        mbar_wait(bars + B_AEMPTY + 8 * b0, a_parity(b0));
                        mbar_arrive_cluster_if(lane == 0 && !k, bars_peer + B_XFREE);
                        warp_expect_tx(fb, GST_BYTES);
                        warp_tma_load(dst, tile_map, fb, (sa & 1) * 64, m * 128, G_LOC - 32 + (sa >> 1), true);
                        mbar_wait(bars + (k ? B_AEMPTY + 8 * b1 : B_XFREE), k ? kvph ^ (b1 - 2 < kv) : 0);
                        warp_tma_load_pair(dst + 16384 + prank * 16384, &prm.m[M_WOB], fb, 0, (sa & 63) * 64, (c >> 1) * 4 + 2 * (half ^ prank), false);
                    }
                    gph ^= 1;
                    uint32_t seen = 0;
                    for (int k = 4; k < nk; k++) {
                        if (k == K_SPLIT) nk = 2 * TRIPLES + (take_item() & 127);
                        const int kn = k + 2 * TRIPLES - nk, first = kn >= 0 && !(kn & 1);
                        const int s = kn >= 0 ? WIDE + (3 * kn + 1) / 2 : half ? WIDE - 1 - k : k;
                        const uint32_t sa = prm.ostep[s], sa2 = prm.ostep[s + first], sw = prm.ostep[s - (kn >= 0 && !first ? prank : 0)];
                        const uint32_t need = 1u << (sa >> 1 & 31) | 1u << (sa2 >> 1 & 31);
                        for (unsigned n = 0; sa < 64 && (need & ~seen);) seen = inputs_seen(0, n);
                        const uint32_t st = k & 3;
                        uint32_t dst = sb + st * GST_BYTES, fb = bars + B_GFULL + 8 * st;
                        uint32_t dstb = dst + 16384 + (first ? 0 : prank * 16384), skipb = first && (kn >> 1 & 1) != prank;
                        int a0 = (sa & 1) * 64, a1 = m * 128, a2 = (sa >> 1) + (sa < 64 ? G_CTX : G_LOC - 32);
                        int b1 = (sw & 63) * 64, b2 = (c >> 1) * 4 + 2 * (kn >= 0 ? half : half ^ prank);
                        const CUtensorMap* mb = &prm.m[sw >= 64 ? M_WOB : M_WO];
                        asm volatile("" : "+r"(dst), "+r"(fb), "+r"(dstb), "+r"(skipb), "+r"(a0), "+r"(a1), "+r"(a2), "+r"(b1), "+r"(b2), "+l"(mb));
                        mbar_wait(bars + B_GEMPTY + 8 * st, gph);
                        warp_expect_tx(fb, GST_BYTES);
                        warp_tma_load(dst, tile_map, fb, a0, a1, a2, true);
                        if (!skipb) warp_tma_load_pair(dstb, mb, fb, 0, b1, b2, false);
                        if (first) warp_tma_load(dst + 32768, tile_map, fb, (sa2 & 1) * 64, a1, G_CTX + (sa2 >> 1), true);
                        if (k < K_SPLIT && lane == 0 && !prank)
                            asm volatile("st.relaxed.gpu.global.u32 [%0], %1;" :: "l"(&g_sync.step[0][0] + m * 4 + c), "r"(k) : "memory");
                        mbar_arrive_if(k == K_MEET && lane == 0, bars + B_MEET);
                        if ((uint32_t)(k - K_FETCH) < (3 * TRIPLES + 1) / 2) {
                            const uint32_t g = prm.ostep[79 - 2 * (k - K_FETCH)] >> 1;
                            warp_prefetch((const char*)g_scr + (uint32_t)((G_CTX + g) * (SEQ * 256) + m * 32768 + c * 4096), 4096);
                            warp_prefetch(prm.wo + (uint32_t)(g * 262144 + (m * 8 + c) * 2048), 2048);
                        }
                        if (st == 3) gph ^= 1;
                    }
                    for (unsigned n = 0; ~inputs_seen(0, n);) {}
                }
#pragma unroll 1
                for (uint32_t st = 0; st < 4; st++) { mbar_wait(bars + B_GEMPTY + 8 * st, gph ^ (st < (nk & 3))); mbar_wait(bars + B_AEMPTY + 16 + 8 * st, a_parity(2 + st)); }
                unsigned left = 0;
                if (lane == 0) asm volatile("atom.relaxed.gpu.global.add.u32 %0, [%1], 1;" : "=r"(left) : "l"(&g_sync.done) : "memory");
                if (__shfl_sync(0xffffffffu, left, 0) == NCTA - 1)
#pragma unroll 1
                    for (uint32_t i = lane * 8; i < sizeof(Sync); i += 256) *(unsigned long long*)((char*)&g_sync + i) = 0;
            }
        } else if (warp <= 2) {
            if (blockIdx.x < SEQ / 16) {
                const uint32_t r0 = 16 * blockIdx.x + 8 * (warp - 1), gbuf = bars + SM_GATE + 4 * (r0 & 15);
                float z[4];
                mbar_wait(bars + B_GFULL + 24, 0);
#pragma unroll 1
                for (uint32_t i = 0; i < 8; i++) {
                    const uint32_t off = (i & 3) * 512 + lane * 16;
                    const uint4* xp = (const uint4*)((const char*)prm.x + ((r0 + (i & 4)) * 2048 + off));
                    const uint4 wv = __ldg((const uint4*)((const char*)prm.gate_w + off));
                    uint4 xv[4];
#pragma unroll
                    for (int r = 0; r < 4; r++) { xv[r] = __ldg(xp + r * 128); if (!(i & 3)) z[r] = 0.f; }
                    const uint32_t ws[4] = {wv.x, wv.y, wv.z, wv.w};
#pragma unroll
                    for (int e = 0; e < 4; e++)
#pragma unroll
                        for (int r = 0; r < 4; r++) {
                            const uint32_t xs = e == 0 ? xv[r].x : e == 1 ? xv[r].y : e == 2 ? xv[r].z : xv[r].w;
                            z[r] = fmaf(__uint_as_float(xs << 16), __uint_as_float(ws[e] << 16), z[r]);
                            z[r] = fmaf(__uint_as_float(xs & 0xffff0000u), __uint_as_float(ws[e] & 0xffff0000u), z[r]);
                        }
                    if ((i & 3) == 3) {
#pragma unroll
                        for (int o = 16; o > 0; o >>= 1)
#pragma unroll
                            for (int r = 0; r < 4; r++) z[r] += __shfl_xor_sync(0xffffffffu, z[r], o);
                        const float zr = lane & 2 ? (lane & 1 ? z[3] : z[2]) : (lane & 1 ? z[1] : z[0]);
                        asm volatile("st.shared.f32 [%0], %1;" :: "r"(gbuf + 4 * ((i & 4) + (lane & 3))), "f"(1.f / (1.f + __expf(-zr))) : "memory");
                    }
                }
                fence_proxy_async_smem();
                __syncwarp();
                warp_bulk_store((char*)g_gate + 4 * r0, gbuf, 32);
                bulk_commit();
                bulk_wait<0>();
                __syncwarp();
                if (lane == 0) red_add(&g_sync.count[3], 1);
            }
            __syncwarp();
            {
                const int w = warp - 1;
                uint32_t sph = 0, nann = 0;
                int unsent = 0, nunsent = 0;
                bool urgent = false;
                auto announce = [&]() {
                    if (!urgent) return;
                    bulk_wait<0>();
                    __syncwarp();
                    const uint32_t hb = bars + B_HALF + 8 * (nann & 3);
                    if (w == 0) {
                        mbar_arrive_if(lane == 0, hb);
                    } else {
                        mbar_wait(hb, (nann >> 2) & 1);
                        const uint32_t type = item_type(unsent), m = item_row(unsent), c = item_col(unsent);
                        const uint32_t word = type < T_B ? c >> 3 : type == T_B ? 2 : offsetof(Sync, ctx) / 8 + m;
                        const uint32_t bit = type < T_B ? 8 * (c & 7) : type == T_B ? 8 * (c & 3) : type == T_LOCAL ? 32 + c : c;
                        if (lane < nunsent) red_add((unsigned long long*)((char*)&g_sync + 8 * word), 1ull << bit);
                        __syncwarp();
                    }
                    nann++;
                    nunsent = 0; urgent = false;
                };
                int held = first_item(), it;
                do {
                    if (!__all_sync(0xffffffffu, mbar_test(bars + B_IFULL + 8 * (qn % QDEPTH), (qn / QDEPTH) & 1))) announce();
                    it = __shfl_sync(0xffffffffu, next_item(lane == 0), 0);
                    const int itype = item_type(it);
                    const bool keep_held = itype == T_LOCAL;
#pragma unroll 1
                    for (int pass = held < 0 || keep_held; pass < 2; pass++) {
                        if (pass && (itype < T_OUT || itype == T_END)) break;
                        const int cur = pass ? it : held, type = item_type(cur), m = item_row(cur), c = item_col(cur);
                        const bool local = type == T_LOCAL;
                        int grp = pass ? (local ? G_LOC : G_CTX) + c : type * 32 + 2 * c;
                        if ((type == T_K || type == T_V) && prm.kgroup[c] > G_B) {
                            grp = prm.kgroup[c] + (type == T_V ? 8 : 0);
                            for (unsigned n = 0; !__all_sync(0xffffffffu, (ld_acquire(&g_sync.used) >> (4 * (grp & 6)) & 255) == 32);) { announce(); spin_guard(n); }
                        }
#pragma unroll 1
                        for (int i = 0; i < 4 - 2 * pass; i++) {
                            const int b = i & 1;
                            const bool alt = i >= 2 && itype >= T_ATTN;
                            const uint32_t full = bars + (alt ? B_ALT + 8 * w : B_SFULL + 16 * w + 8 * b), par = alt ? 0 : sph;
                            if (i == 3 - 2 * pass || !__all_sync(0xffffffffu, mbar_test(full, par))) announce();
                            mbar_wait(full, par);
                            if (local && w + b == 2 && lane == 0) asm volatile("red.relaxed.gpu.global.add.u32 [%0], %1;" :: "l"(&g_sync.used), "r"(1 << (4 * (c & 6))) : "memory");
                            fence_proxy_async_smem();
                            warp_tma_store(&prm.m[local ? M_SCR_LOQ : M_SCR_ST], sb + (alt ? 32768 : SM_STAGING) + w * 16384 + b * 8192,
                                         local ? b * 128 + w * 64 : b * 64, local ? m * 64 : m * 128 + w * 64, grp + (i >> 1), local || (type < T_B && c < FIRST_PAIR));
                            bulk_commit();
                            if (pass > b) continue;
                            bulk_wait_read<0>();
                            __syncwarp();
                            mbar_arrive_if(lane <= pass && !alt, bars + B_SEMPTY + 16 * w + 8 * (b - lane));
                            sph ^= b & !alt;
                        }
                        mbar_arrive_if(lane == 0 && !pass && itype >= T_ATTN, bars + B_QFREE);
                        if (lane == nunsent) unsent = cur;
                        nunsent++;
                        urgent = !local;
                    }
                    if (!keep_held) held = itype < T_OUT ? it : -1;
                } while (item_type(it) != T_END);
                announce();
                it = __shfl_sync(0xffffffffu, next_item(lane == 0), 0);
                if (item_type(it) == T_OUT) {
                    if (w) {
                        mbar_wait(bars + B_MEET, 0);
                        asm volatile("fence.proxy.async.global;\nfence.acq_rel.gpu;" ::: "memory");
                        mbar_arrive_cluster_if(lane == 0, bars0 + B_WANT);
                    }
                    next_item(lane == 0);
#pragma unroll 1
                    for (int i = 0; i < 4; i++) {
                        const int b = i & 1;
                        mbar_wait(bars + B_SFULL + 16 * w + 8 * b, sph ^ (i >> 1));
                        fence_proxy_async_smem();
                        warp_tma_add(&prm.m[M_OUT], sb + SM_STAGING + w * 16384 + b * 8192, (item_col(it) ^ (i < 2)) * 128 + b * 64, item_row(it) * 128 + w * 64, 0);
                        bulk_commit();
                        if (b) {
                            bulk_wait_read<0>();
                            __syncwarp();
                            mbar_arrive_if(lane < 2, bars + B_SEMPTY + 16 * w + 8 * lane);
                        }
                    }
                }
            }
        } else {
            if (elect_one()) {
                uint32_t ordy = 0;
                unsigned long long cnt_lo = 0, cnt_hi = 0;
                int late = 0;
                auto refresh = [&]() {
                    if (!late && cnt_lo == 0x30303030 && cnt_hi == SEQ / 8) late = 1;
                    asm volatile("ld.acquire.gpu.global.v2.u64 {%0, %1}, [%2];" : "=l"(cnt_lo), "=l"(cnt_hi) : "l"(late ? &g_sync.count[0] : &g_sync.count[2]) : "memory");
                };
                auto inputs_ready = [&](int it) -> bool {
                    const int c = item_col(it);
                    if (item_type(it) == T_ATTN) return late && ((c < 16 ? cnt_lo : cnt_hi) >> (4 * (c & 14)) & 255) == 48;
                    return late || (cnt_hi == SEQ / 8 && (cnt_lo >> (4 * (c & 6)) & 255) == 48);
                };
                auto publish = [&](int it, int step) {
                    const uint32_t slot = qn % QDEPTH;
                    mbar_wait(bars + B_IEMPTY + 8 * slot, ((qn / QDEPTH) & 1) ^ 1);
                    for (uint32_t r = 0; r < 2; r++) {
                        const uint32_t rb = map_cta(bars, r);
                        asm volatile("mbarrier.arrive.expect_tx.shared::cluster.b64 _, [%0], 4;" :: "r"(rb + B_IFULL + 8 * slot) : "memory");
                        asm volatile("st.async.shared::cluster.mbarrier::complete_tx::bytes.u32 [%0], %1, [%2];"
                                     :: "r"(rb + SM_QUEUE + 4 * slot), "r"(it + r * step), "r"(rb + B_IFULL + 8 * slot) : "memory");
                    }
                    qn++;
                };
                int asc = 1;
                int it;
                do {
                    if (rank == 0) {
                        mbar_wait(bars + B_WANT, qn & 1);
                        const uint32_t pair = plan_index();
                        int pit = prm.plan[pair < 64 ? pair & 7 : pair - 56][min(qn + 1, 15u)];
                        unsigned i;
                        const bool planned = item_type(pit) != T_END;
                        if (!planned) asm volatile("atom.relaxed.gpu.global.add.u32 %0, [%1], 1;" : "=r"(i) : "l"(&g_sync.next) : "memory");
                        if (cnt_lo != 0x3030303030303030ull || cnt_hi != cnt_lo) refresh();
                        if (planned) pit += (pair >> 3 & 7) << (item_type(pit) == T_LOCAL);
                        else if (i < NITEMS) pit = prm.items[i];
                        const int type = item_type(pit);
                        int step = type == T_LOCAL ? 16 : 1;
                        it = pit + (pit & (step == 1 ? 15 : 0x1f0));
                        if (type == T_ATTN) {
                            if (!asc) { it += 1; step = -1; }
                            it |= asc << 9;
                        }
                        asc = type != T_ATTN || item_row(pit) == 0 || !asc;
                        if (inputs_ready(it)) it |= ITEM_READY;
                        publish(it, step);
                    } else {
                        it = next_item(true);
                    }
                    if ((item_type(it) == T_ATTN || item_type(it) == T_LOCAL) && !(it & ITEM_READY)) {
                        unsigned n = 0;
                        while (!inputs_ready(it)) { refresh(); spin_guard(n); }
                        asm volatile("st.release.cta.shared.u32 [%0], %1;" :: "r"(bars + SM_ORDY + 4), "r"(ordy += 256) : "memory");
                    }
                } while (item_type(it) != T_END);
                if (rank == 0) {
                    mbar_wait(bars + B_WANT, qn & 1);
                    const unsigned i = atomicAdd(&g_sync.next_out, 1u), t = i < 32 ? 31 - i : i - 32;
                    it = i < 64 ? T_OUT << 13 | ((t & 3) * 2 + (i >> 5)) << 4 | (t >> 2) * 2 : T_END << 13;
                    publish(it, 1);
                } else {
                    it = next_item(true);
                }
                if (item_type(it) == T_OUT) {
                    const uint32_t m = item_row(it), half = item_col(it) & 1, tile = m * 2 + (item_col(it) >> 1);
                    unsigned* split = (unsigned*)((char*)g_sync.split + 4 * tile);
                    unsigned long long rdy = 0;
                    int state = rank ? 2 : 0;
                    for (unsigned n = 0; rdy != 0xffffffffffull || state < 2; spin_guard(n)) {
                        if (rdy != 0xffffffffffull) {
                            rdy = ld_acquire((const unsigned long long*)((char*)g_sync.ctx + 8 * m));
                            asm volatile("st.release.cta.shared.u64 [%0], %1;" :: "r"(bars + SM_ORDY), "l"(rdy) : "memory");
                        }
                        unsigned steps = 0;
                        if (state == 1) {
                            steps = ld_acquire(split);
                        } else if (state == 0 && mbar_test(bars + B_WANT, qn & 1)) {
                            state = 1;
                            unsigned seen;
                            asm volatile("atom.acq_rel.gpu.global.exch.b32 %0, [%1], 1;" : "=r"(seen) : "l"(split) : "memory");
                            if (seen) {
                                const unsigned long long v = ld_acquire((const unsigned long long*)((char*)g_sync.step + 8 * tile));
                                const int d = (int)(v >> 32) - (int)v;
                                steps = (WIDE + min(max(half ? d : -d, -12), 12)) >> 1;
                                atomicExch(split, WIDE - steps);
                            }
                        }
                        if (steps > 1) { publish(T_END << 13 | steps, 0); state = 2; }
                    }
                    if (rank) next_item(true);
                }
#pragma unroll 1
                for (uint32_t n = qn; n < qn + QDEPTH && rank == 0; n++) mbar_wait(bars + B_IEMPTY + 8 * (n % QDEPTH), ((n / QDEPTH) & 1) ^ 1);
            }
        }
    } else {
        reg_inc<232>();
        const int wg = (warp >> 2) - 1, wq = warp & 3;
        uint32_t gph = 0;
        uint32_t kvn = 0;
        const uint32_t dA = make_desc(sb + wg * 8192, 16);
        uint32_t ti = 0;
        uint32_t sph = 1;
        const uint32_t stg = sb + SM_STAGING + wg * 16384;
        const uint32_t stg_lane = stg + (wq * 16 + (lane & 15)) * 128 + (((lane >> 4) ^ (lane & 7)) << 4);
        auto write_blocks = [&](auto n, uint32_t off, const uint32_t* v) {
            uint32_t a = stg_lane;
            asm volatile("" : "+r"(a));
            a += off;
#pragma unroll
            for (int j = 0; j < decltype(n)::value; j++)
                stmatrix_x4((a ^ (32 * (j & 3))) + (j >> 2) * 8192, v[4 * j], v[4 * j + 1], v[4 * j + 2], v[4 * j + 3]);
        };
        auto release = [&](uint32_t bar) { mbar_arrive_if(lane == 0, bars + bar); };
        const uint32_t bars_lane = map_cta(bars, lane & 1);
        auto release_stage = [&](uint32_t st) { mbar_arrive_cluster_if(lane < 2, bars_lane + B_GEMPTY + 8 * st); };
        auto take_item = [&]() -> int {
            return __shfl_sync(0xffffffffu, next_item(lane == 0, false), 0);
        };
        auto stage_acquire = [&](int b) { mbar_spin(bars + B_SEMPTY + 16 * wg + 8 * b, sph); };
        auto stage_publish = [&](int b) {
            __syncwarp();
            release(B_SFULL + 16 * wg + 8 * b);
        };
        auto stage_chunk = [&](int b, const uint32_t* v) {
            stage_acquire(b);
            write_blocks(std::integral_constant<int, 4>(), b * 8192, v);
            stage_publish(b);
            if (b) sph ^= 1;
        };
        auto publish_pair = [&]() {
            __syncwarp();
            mbar_arrive_if(lane < 2, bars + B_SFULL + 16 * wg + 8 * lane);
            sph ^= 1;
        };
        auto gemm_step = [&](float (&acc)[128], uint32_t dB, int& k, bool order) {
            const uint32_t st = k & 3;
            wgmma_wait<0>();
            release_stage((k - 1) & 3);
            mbar_spin(bars + B_GFULL + 8 * st, gph);
            const uint64_t da = full_desc(dA + st * (GST_BYTES >> 4)), db = full_desc(dB + st * (GST_BYTES >> 4));
            if (order && wg) bar_sync(3, 256);
            wgmma_fence();
#pragma unroll
            for (int kk = 0; kk < 4; kk++) wgmma_ss_n256_tb(acc, da + 2 * kk, db + 128 * kk, 1);
            wgmma_commit();
            if (order && !wg) bar_arrive(3, 256);
            gph ^= st == 3;
            k++;
        };
        if (wg == 1) bar_arrive(1, 256);
        int it = first_item();
        float s[64];
        const uint32_t dK = make_desc(sb + SM_KV, 16);
        auto kv_wait = [&](uint32_t n) { mbar_spin(bars + B_AFULL + 16 + 8 * (n & 3), (n >> 2) & 1); };
        auto first_scores = [&](bool valid) {
            if (valid) { mbar_spin(bars + B_AFULL + 8 * (ti & 1), (ti >> 1) & 1); kv_wait(kvn); }
            bar_sync(1 + wg, 256);
            qk_gemm(s, dA + (ti & 1) * 2048, dK + (kvn & 3) * 2048, false);
        };
        bool issued;
        {
            {
                float acc[128];
                uint32_t pk[64];
                bool pending = false;
                int held = T_END;
                auto scale_q = [&](int j0) {
                    if (held != T_Q) return;
#pragma unroll
                    for (int j = j0; j < j0 + 16; j++)
                        asm("{\n.reg .b32 t;\nmul.rn.bf16x2 t, %0, %2;\nfma.rn.bf16x2 %0, %0, %1, t;\n}\n" : "+r"(pk[j]) : "r"(0x3e033e03u), "r"(0xb9d8b9d8u));
                };
                zero_regs(pk);
                const uint32_t dB = make_desc(sb + 16384, 8192);
                do {
                    if (item_type(it) == T_LOCAL) {
                        int ln = lane;
                        asm volatile("" : "+r"(ln));
                        const int g = ln >> 2, t = ln & 3, par = wq & 1;
                        const uint32_t hc = (wq >> 1) * 4, pl = sb + (par * 2 + wg) * LOC_PLANE;
                        const uint32_t a16 = (ln & 15) * 128 + (((hc + (ln >> 4)) ^ (ln & 7)) << 4), a8 = (ln & 7) * 128 + (((hc + (ln >> 3)) ^ (ln & 7)) << 4);
                        const bool first0 = 2 * t > g, first1 = 2 * t + 1 > g;
                        const uint32_t fmask = (first0 ? 0xffffu : 0u) | (first1 ? 0xffff0000u : 0u);
                        const bool edge = item_row(it) == 0;
                        uint32_t q[4][2][4], kf[9][4], vf[9][4];
                        float w[8];
                        mbar_spin(bars + B_GFULL, gph);
#pragma unroll
                        for (int u = 0; u < 4; u++) { ldsm_x4(q[u][0], pl + u * 2048 + a16); ldsm_x4(q[u][1], pl + u * 2048 + (a16 ^ 32)); }
#pragma unroll
                        for (int j = 0; j < 8; j++) w[j] = lds_f32(sb + 4 * LOC_PLANE + 4 * (2 * g + par) + 64 * j);
                        __syncwarp();
                        release_stage(0);
                        mbar_spin(bars + B_GFULL + 8, gph);
#pragma unroll
                        for (int n = 0; n < 9; n++) ldsm_x4(kf[n], pl + GST_BYTES + n * 1024 + a8);
                        __syncwarp();
                        release_stage(1);
                        float s[8][2];
#pragma unroll
                        for (int u = 0; u < 4; u++) {
                            float d[3][4];
#pragma unroll
                            for (int nt = 0; nt < 3; nt++) {
                                mma_k16_init(d[nt], q[u][0], kf[2 * u + nt][0], kf[2 * u + nt][1]);
                                mma_k16(d[nt], q[u][1], kf[2 * u + nt][2], kf[2 * u + nt][3]);
                            }
                            if (u == 0 && edge) { d[0][0] = -INFINITY; d[0][1] = -INFINITY; }
                            s[2 * u][0] = first0 ? d[0][0] : d[1][0]; s[2 * u][1] = first1 ? d[0][1] : d[1][1];
                            s[2 * u + 1][0] = first0 ? d[1][2] : d[2][2]; s[2 * u + 1][1] = first1 ? d[1][3] : d[2][3];
                        }
                        mbar_spin(bars + B_GFULL + 16, gph);
#pragma unroll
                        for (int u = 0; u < 4; u++) { ldsm_x4_t(vf[2 * u], pl + 2 * GST_BYTES + u * 2048 + a16); ldsm_x4_t(vf[2 * u + 1], pl + 2 * GST_BYTES + u * 2048 + (a16 ^ 32)); }
                        ldsm_x4_t(vf[8], pl + 2 * GST_BYTES + 8192 + a8);
                        __syncwarp();
                        release_stage(2);
                        float x[8];
#pragma unroll
                        for (int j = 0; j < 8; j++) x[j] = fmaxf(s[j][0], s[j][1]);
#pragma unroll
                        for (int o = 1; o < 4; o *= 2)
#pragma unroll
                            for (int j = 0; j < 8; j++) x[j] = fmaxf(x[j], __shfl_xor_sync(0xffffffffu, x[j], o));
#pragma unroll
                        for (int j = 0; j < 8; j++) {
                            const float n = x[j] * -LOC_SCALE;
                            s[j][0] = ex2(fmaf(s[j][0], LOC_SCALE, n)); s[j][1] = ex2(fmaf(s[j][1], LOC_SCALE, n));
                            x[j] = s[j][0] + s[j][1];
                        }
#pragma unroll
                        for (int o = 1; o < 4; o *= 2)
#pragma unroll
                            for (int j = 0; j < 8; j++) x[j] += __shfl_xor_sync(0xffffffffu, x[j], o);
                        mbar_spin(bars + B_GFULL + 24, gph);
                        release_stage(3);
                        it = take_item();
                        uint32_t ob[4][8];
#pragma unroll
                        for (int u = 0; u < 4; u++) {
                            const float r0 = rcp(x[2 * u]), r1 = rcp(x[2 * u + 1]), f0 = fmaf(-w[2 * u], r0, r0), f1 = fmaf(-w[2 * u + 1], r1, r1);
                            const uint32_t p0 = pack_bf16(s[2 * u][0] * f0, s[2 * u][1] * f0), p1 = pack_bf16(s[2 * u + 1][0] * f1, s[2 * u + 1][1] * f1);
                            const uint32_t pa[4] = {p0 & fmask, 0, p0 & ~fmask, p1 & fmask};
#pragma unroll
                            for (int c = 0; c < 4; c++) {
                                float ol[4];
                                mma_k16_init(ol, pa, vf[2 * u + (c >> 1)][2 * (c & 1)], vf[2 * u + (c >> 1)][2 * (c & 1) + 1]);
                                mma_k8(ol, 0, p1 & ~fmask, u < 3 ? vf[2 * u + 2 + (c >> 1)][2 * (c & 1)] : vf[8][c]);
                                ob[u][2 * c] = pack_bf16(ol[0], ol[1]);
                                ob[u][2 * c + 1] = pack_bf16(ol[2], ol[3]);
                            }
                        }
                        stage_acquire(0); stage_acquire(1);
#pragma unroll
                        for (int u = 0; u < 4; u++) {
                            stmatrix_x4(stg + par * 8192 + u * 2048 + a16, ob[u][0], ob[u][1], ob[u][2], ob[u][3]);
                            stmatrix_x4(stg + par * 8192 + u * 2048 + (a16 ^ 32), ob[u][4], ob[u][5], ob[u][6], ob[u][7]);
                        }
                        publish_pair();
                        bar_sync(4, 256);
                        gph ^= 1;
                        continue;
                    }
                    mbar_spin(bars + B_GFULL, gph);
                    bool more;
                    do {
                        wgmma_fence();
                        wgmma_ss_n256_tb_init(acc, full_desc(dA), full_desc(dB));
#pragma unroll
                        for (int kk = 1; kk < 4; kk++) wgmma_ss_n256_tb(acc, full_desc(dA) + 2 * kk, full_desc(dB) + 128 * kk, 1);
                        wgmma_commit();
                        const int type = item_type(it), nk = type == T_K || type == T_V ? 8 : 16;
                        int k = 1;
                        do {
                            if (pending) {
                                if (k == 1) { scale_q(0); stage_chunk(0, pk); }
                                else if (k == 3) { scale_q(16); stage_chunk(1, pk + 16); }
                                else if (k == 5) { scale_q(32); stage_chunk(0, pk + 32); }
                                else if (k == 6) { scale_q(48); stage_chunk(1, pk + 48); }
                            }
                            if (k == nk - 1) it = take_item();
                            gemm_step(acc, dB, k, item_type(it) > T_LOCAL);
                        } while (k < nk);
                        held = type;
                        more = item_type(it) < T_LOCAL;
                        if (more) mbar_spin(bars + B_GFULL, gph);
                        wgmma_wait<0>();
                        fence_regs(acc);
                        release_stage(3);
#pragma unroll
                        for (int j = 0; j < 64; j++) pk[j] = pack_bf16(acc[2 * j], acc[2 * j + 1]);
                        pending = true;
                    } while (more);
                } while (item_type(it) <= T_LOCAL);
                issued = item_type(it) == T_ATTN && (it & ITEM_READY);
                first_scores(issued);
                stage_acquire(0); stage_acquire(1);
                mbar_spin(bars + B_GEMPTY + 8, gph ^ 1);
                write_blocks(std::integral_constant<int, 8>(), 0, pk);
                write_blocks(std::integral_constant<int, 8>(), 32768 - SM_STAGING, pk + 32);
                publish_pair();
                release(B_ALT + 8 * wg);
                bar_arrive(2 - wg, 256);
                wgmma_wait<0>();
                fence_regs(s);
                if (item_type(it) == T_END) it = take_item();
            }
            while (item_type(it) == T_ATTN) {
                if (!issued) { first_scores(true); bar_arrive(2 - wg, 256); wgmma_wait<0>(); fence_regs(s); }
                issued = false;
                float o[64];
                uint32_t pa[32], pb[32];
                float n0 = 0.f, n1 = 0.f;
                int shifted = 0;
                float l0 = 0.f, l1 = 0.f, f0 = 0.f, f1 = 0.f, g0, g1;
                uint32_t has_pv = 0;
                int first = 0;
                int pending = 0;
                const uint32_t dV = make_desc(sb + SM_KV, 16384);
                const uint32_t lane_off = bars_lane - bars + B_AEMPTY - B_AFULL;
                int cur = it;
                uint32_t dQ = dA + (ti & 1) * 2048;
                const int row = wq * 16 + (lane >> 2);
                const float thr = row - (lane & 3) * 2;
                int diag = item_row(cur) == 0 || !item_asc(cur);
                int short_row = diag && wg == 0;
                int peek = -1;
                auto kv_release = [&](uint32_t n) { mbar_arrive_cluster_if(lane < 2, bars_lane + B_AEMPTY + 16 + 8 * (n & 3)); };
                struct Slot { uint32_t bar, par, off; } slot[4];
#pragma unroll
                for (uint32_t i = 0; i < 4; i++) {
                    const uint32_t n = kvn + 1 + (i ^ 2);
                    slot[i].bar = bars + B_AFULL + 16 + 8 * (n & 3); slot[i].par = (n >> 2) & 1; slot[i].off = (n & 3) * 2048;
                }
                kvn++;
                auto next_gate = [&]() {
                    const uint32_t a = bars + SM_GATE + (ti & 1) * 512 + wg * 256 + 4 * row;
                    g0 = lds_f32(a); g1 = lds_f32(a + 32);
                    ti++;
                };
                next_gate();
                auto scale_o = [&]() {
#pragma unroll
                    for (int j = 0; j < 16; j++) { o[4 * j] *= f0; o[4 * j + 1] *= f0; o[4 * j + 2] *= f1; o[4 * j + 3] *= f1; }
                };
                auto pack_o = [&](uint32_t (&v)[32]) {
#pragma unroll
                    for (int j = 0; j < 32; j++) v[j] = pack_bf16(o[2 * j], o[2 * j + 1]);
                };
                auto scales = [&]() { f0 = g0 * rcp(quad_sum(l0)); f1 = g1 * rcp(quad_sum(l1)); };
                auto issue = [&](auto even, uint32_t (&pin)[32], uint32_t (&pout)[32], bool fresh, bool last) {
                    constexpr bool EVEN = decltype(even)::value;
                    Slot& sk = slot[EVEN ? 0 : 2];
                    Slot& sv = slot[EVEN ? 1 : 3];
                    kvn += 2;
                    mbar_spin(sk.bar, sk.par);
                    bar_sync(1 + wg, 256);
                    qk_gemm(s, dQ, dK + sk.off, wg == 0 && (item_asc(cur) ? last : fresh));
                    if (EVEN && fresh) {
                        scales();
                        next_gate();
                        n0 = 0.f; n1 = 0.f; l0 = 0.f; l1 = 0.f;
                        shifted = 0;
                        stage_acquire(0); stage_acquire(1);
                    }
                    if (!EVEN && pending) {
                        pack_o(pout);
                        write_blocks(std::integral_constant<int, 4>(), 0, pout);
                    }
                    if (last)
                        asm volatile("{\n.reg .pred P, Q;\n"
                                     "mbarrier.test_wait.parity.shared::cta.b64 Q, [%1], %2;\n"
                                     "mbarrier.test_wait.parity.shared::cta.b64 P, [%3], %4;\n"
                                     "ld.shared.u32 %0, [%5];\n"
                                     "@!Q or.b32 %0, %0, 0x10000;\n"
                                     "@!P mov.u32 %0, -1;\n}\n"
                                     : "=r"(peek) : "r"(bars + B_AFULL + 8 * (ti & 1)), "r"((ti >> 1) & 1), "r"(bars + B_IFULL + 8 * (qn % QDEPTH)),
                                       "r"((qn / QDEPTH) & 1), "r"(bars + SM_QUEUE + 4 * (qn % QDEPTH)) : "memory");
                    const bool half = short_row;
                    diag = item_asc(cur) ? last : fresh;
                    short_row = diag && wg == 0;
                    asm volatile("" : "+r"(diag));
                    mbar_spin(sv.bar, sv.par);
                    pv_gemm(o, pin, dV + sv.off, EVEN || !first, half);
                    bar_arrive(2 - wg, 256);
                    if (!EVEN && pending) {
                        write_blocks(std::integral_constant<int, 4>(), 8192, pout + 16);
                        publish_pair();
                    }
                    sk.par ^= 1; sv.par ^= 1;
                    wgmma_wait<1>();
                    fence_regs(s);
                    mbar_arrive_cluster_if(lane < 2, sk.bar + lane_off);
                    mbar_arrive_if(lane == 0 && last, bars + B_AEMPTY + 8 * ((ti - 1) & 1));
                };
                auto softmax = [&](auto even, uint32_t (&pin)[32], uint32_t (&pout)[32], bool fresh) {
                    constexpr bool EVEN = decltype(even)::value;
                    Slot& sv = slot[EVEN ? 1 : 3];
                    float r0, r1, x0 = n0, x1 = n1;
#pragma unroll 1
                    for (int mask = diag, redone = 0;; mask = 0, redone = 1) {
                        if (mask | shifted) {
                            if (mask) causal_mask(s, thr, wg);
                            if (shifted) shift_rows(s, x0, x1);
                            if (short_row) { exp_pack<8>(pout, s, r0, r1); goto check; }
                        }
                        exp_pack<16>(pout, s, r0, r1);
                    check:
                        if (!__any_sync(0xffffffffu, fmaxf(r0, r1) >= SUM_LIMIT || (EVEN && fresh && !(lane & 3) && !(fminf(s[0], s[2]) >= -REF_RANGE))) || redone) break;
                        if (short_row) {
#pragma unroll
                            for (int j = 32; j < 64; j++) s[j] = MASKED;
                        }
                        row_max(s, x0, x1);
                        if (!(EVEN && fresh)) { x0 = fmaxf(x0, 0.f); x1 = fmaxf(x1, 0.f); }
                        float a0 = ex2(-x0), a1 = ex2(-x1);
                        n0 += x0; n1 += x1;
                        shifted = 1;
                        if (EVEN && fresh) { a0 = 1.f; a1 = 1.f; }
                        l0 *= a0; l1 *= a1;
                        wgmma_wait<0>();
                        fence_regs(o);
#pragma unroll
                        for (int q = 0; q < 16; q++) { o[4 * q] *= a0; o[4 * q + 1] *= a0; o[4 * q + 2] *= a1; o[4 * q + 3] *= a1; }
                    }
                    l0 += r0; l1 += r1;
                    wgmma_wait<0>();
                    fence_regs(o);
                    fence_regs(pin);
                    mbar_arrive_cluster_if(lane < 2, sv.bar + lane_off);
                };
                auto copy_p = [&]() {
#pragma unroll
                    for (int j = 0; j < 32; j++) pa[j] = __float_as_uint(__uint_as_float(pb[j]) + __uint_as_float(prm.zero));
                };
                int rem = 0;
                mbar_arrive_if(lane == 0 && item_row(cur) == 0, bars + B_AEMPTY + 8 * ((ti - 1) & 1));
                zero_regs(pa);
                wgmma_fence();
                wgmma_ss_n128_init(o, full_desc(dA), full_desc(dK));
                wgmma_commit();
                while (true) {
                    const bool fresh = rem == 0;
                    softmax(std::true_type(), pa, pb, fresh);
                    first = fresh;
                    if (fresh) {
                        pending = has_pv; has_pv = 1;
                        if (pending) scale_o();
                        rem = item_row(cur) + 1;
                    }
                    if (--rem == 0) {
                        copy_p();
                        const Slot t0 = slot[0], t1 = slot[1];
                        slot[0] = slot[2]; slot[1] = slot[3]; slot[2] = t0; slot[3] = t1;
                    } else {
                        issue(std::false_type(), pb, pa, false, rem == 1);
                        softmax(std::false_type(), pb, pa, false);
                        pending = 0; first = 0;
                        rem--;
                    }
                    if (rem == 0) {
                        const int seen = peek;
                        if (seen >= 0) {
                            mbar_arrive_cluster_if(lane == 0, bars0 + B_IEMPTY + 8 * (qn % QDEPTH));
                            qn++;
                            it = seen & 0xffff;
                        } else {
                            it = take_item();
                        }
                        if (item_row(cur) < 2 || item_type(it) != T_ATTN) break;
                        if (seen & 0x10000) mbar_spin(bars + B_AFULL + 8 * (ti & 1), (ti >> 1) & 1);
                        cur = it;
                        dQ = dA + (ti & 1) * 2048;
                    }
                    issue(std::true_type(), pa, pb, rem == 0, rem ? rem == 1 : item_row(cur) == 0);
                }
                const uint32_t skip = item_asc(cur) & ~item_row(cur) & 1;
                kvn += skip;
                const bool end = item_type(it) == T_END;
#pragma unroll 1
                for (int pass = pending ? 0 : 1; pass < 2; pass++) {
                    if (pass) {
                        kv_wait(kvn);
                        pv_gemm(o, pa, dV + (kvn & 3) * 2048, !first, short_row);
                        scales();
                        stage_acquire(0); stage_acquire(1);
                        if (end) it = take_item();
                        wgmma_wait<0>();
                        fence_regs(o);
                        kv_release(kvn);
                        kvn += 1 + skip;
                        scale_o();
                    }
                    pack_o(pb);
                    write_blocks(std::integral_constant<int, 8>(), 0, pb);
                    publish_pair();
                }
            }
        }
        if (item_type(it) == T_OUT) {
            float acc[128];
            const uint32_t dB = make_desc(sb + 16384, 8192);
            mbar_spin(bars + B_GFULL, gph);
            wgmma_fence();
            wgmma_ss_n256_tb_init(acc, full_desc(dA), full_desc(dB));
#pragma unroll
            for (int kk = 1; kk < 4; kk++) wgmma_ss_n256_tb(acc, full_desc(dA) + 2 * kk, full_desc(dB) + 128 * kk, 1);
            wgmma_commit();
            uint32_t ln;
            asm volatile("mov.u32 %0, %%laneid;" : "=r"(ln));
            char* const mine = (char*)prm.out + (uint32_t)((item_row(it) * 128 + wg * 64 + wq * 16 + (ln >> 4)) * 2048 + item_col(it) * 256 + (ln & 15) * 16);
            int k = 1, nk = 80;
            do {
                if ((uint32_t)(k - (K_MEET - 12)) < 8) *(uint4*)(mine + (uint32_t)(k - (K_MEET - 12)) * 4096) = make_uint4(0, 0, 0, 0);
                __syncwarp();
                if (k == K_SPLIT) nk = take_item() & 127;
                gemm_step(acc, dB, k, false);
            } while (k < nk);
            float lo[64];
            auto triple = [&](auto first) {
                const uint32_t s0 = k & 3, s1 = (k + 1) & 3, o0 = s0 * (GST_BYTES >> 4), o1 = s1 * (GST_BYTES >> 4);
                wgmma_wait<0>();
                mbar_arrive_cluster_if(ln < (decltype(first)::value ? 2 : 4), bars_lane + B_GEMPTY + 8 * ((k - 1 - (ln >> 1)) & 3));
                mbar_spin(bars + B_GFULL + 8 * s0, gph);
                gph ^= s0 == 3;
                wgmma_fence();
#pragma unroll
                for (int kk = 0; kk < 4; kk++) {
                    if (decltype(first)::value && kk == 0) wgmma_ss_n128_tb_init(lo, full_desc(dA + o0), full_desc(dB + o0));
                    else wgmma_ss_n128_tb(lo, full_desc(dA + o0) + 2 * kk, full_desc(dB + o0) + 128 * kk, 1);
                }
                mbar_spin(bars + B_GFULL + 8 * s1, gph);
                gph ^= s1 == 3;
                wgmma_fence();
#pragma unroll
                for (int kk = 0; kk < 4; kk++) wgmma_ss_n128_tb(lo, full_desc(dA + o0 + 2048) + 2 * kk, full_desc(dB + o1 + 1024) + 128 * kk, 1);
#pragma unroll
                for (int kk = 0; kk < 4; kk++) wgmma_ss_n128_tb(lo, full_desc(dA + o1) + 2 * kk, full_desc(dB + o1) + 128 * kk, 1);
                wgmma_commit();
                k += 2;
            };
            triple(std::true_type());
            fence_regs(acc);
            uint32_t pk[32];
#pragma unroll
            for (int j = 0; j < 32; j++) pk[j] = pack_bf16(acc[64 + 2 * j], acc[65 + 2 * j]);
            stage_acquire(0); stage_acquire(1);
            write_blocks(std::integral_constant<int, 8>(), 0, pk);
            publish_pair();
            triple(std::false_type());
            stage_acquire(0); stage_acquire(1);
            wgmma_wait<0>();
            fence_regs(lo);
            mbar_arrive_cluster_if(ln < 4, bars_lane + B_GEMPTY + 8 * ((k - 1 - (ln >> 1)) & 3));
#pragma unroll
            for (int b = 0; b < 2; b++) {
#pragma unroll
                for (int j = 16 * b; j < 16 * b + 16; j++) pk[j] = pack_bf16(acc[2 * j] + lo[2 * j], acc[2 * j + 1] + lo[2 * j + 1]);
                write_blocks(std::integral_constant<int, 4>(), b * 8192, pk + 16 * b);
                stage_publish(b);
            }
        }
    }
}

typedef CUresult (*EncodeFn)(CUtensorMap*, CUtensorMapDataType, cuuint32_t, void*, const cuuint64_t*, const cuuint64_t*,
                             const cuuint32_t*, const cuuint32_t*, CUtensorMapInterleave, CUtensorMapSwizzle,
                             CUtensorMapL2promotion, CUtensorMapFloatOOBfill);

void encode3(EncodeFn fn, CUtensorMap* m, const void* ptr, uint64_t d0, uint64_t d1, uint64_t d2, uint64_t s1, uint64_t s2,
             uint32_t b0, uint32_t b1, uint32_t b2) {
    cuuint64_t dims[3] = {d0, d1, d2};
    cuuint64_t strides[2] = {s1, s2};
    cuuint32_t box[3] = {b0, b1, b2};
    cuuint32_t es[3] = {1, 1, 1};
    fn(m, CU_TENSOR_MAP_DATA_TYPE_BFLOAT16, 3, const_cast<void*>(ptr), dims, strides, box, es, CU_TENSOR_MAP_INTERLEAVE_NONE,
       CU_TENSOR_MAP_SWIZZLE_128B, b2 > 1 ? CU_TENSOR_MAP_L2_PROMOTION_L2_256B : CU_TENSOR_MAP_L2_PROMOTION_NONE, CU_TENSOR_MAP_FLOAT_OOB_FILL_NONE);
}
void map_act(EncodeFn fn, CUtensorMap* m, const void* p, int rows, int cols, int box_rows) {
    encode3(fn, m, p, cols, rows, 1, (uint64_t)cols * 2, (uint64_t)cols * rows * 2, 64, box_rows, 1);
}
void map_wgt(EncodeFn fn, CUtensorMap* m, const void* p, int K, int N) {
    encode3(fn, m, p, 64, K, N / 64, (uint64_t)N * 2, 128, 64, 64, 2);
}

void build_schedule(Params& p) {
    int n = 0;
    auto add = [&](int type, int col, int row) { p.items[n++] = (uint16_t)(type << 13 | col << 4 | row); };
    int beta = 32, tail = 32, late = 6, early = 4, epos = 60;
    int order[16] = {6, 7, 8, 9, 10, 11, 12, 13, 14, 15, 5, 4, 3, 2, 1, 0};
    const char* plans = "xxxxxc,xxlcccccc,xxxxxc,xxlcccccc,xxllcclxxc,xxxllxxc,xxxlccccc,xxcccccc";
    const char* pos[8];
    int len[8] = {}, start[8] = {};
    for (int s = 0; s < 8; s++) { pos[s] = plans; while (*plans && *plans++ != ',') {} }
    for (int i = 0; i < 160; i++) p.plan[i / 16][i % 16] = T_END << 13;
    int lend[4] = {}, nset = 0, margin = 12;
    for (int c = 0; c < 16; c++) p.kgroup[c] = (uint8_t)(G_K + 2 * c);
    for (int nx = 0, nc = 3, nl = 0; nx + nc + nl < 28 + 32 + 8;) {
        int s = -1;
        for (int i = 0; i < 8; i++) if (*pos[i] > ',' && (s < 0 || start[i] < start[s])) s = i;
        const char kind = *pos[s]++;
        int it;
        if (kind == 'x') { it = nx < 12 ? T_B << 13 | (nx % 3 * 4 + nx / 3) << 4 : T_Q << 13 | (nx - 12) << 4; nx++; }
        else if (kind == 'c') { it = (T_K + (nc & 1)) << 13 | nc / 2 << 4; nc++; }
        else { it = T_LOCAL << 13 | nl / 2 << 4 | (nl & 1); nl++; }
        p.plan[s][len[s]++] = (uint16_t)it;
        start[s] += kind == 'x' ? 48 : kind == 'c' ? 24 : 8;
        if (kind == 'l') lend[(nl - 1) / 2] = start[s];
        if (kind == 'c' && (nc & 1) && nset < nl / 2 && start[s] >= lend[nset] + margin) p.kgroup[nc / 2] = (uint8_t)(G_B + 8 + 2 * nset++);
    }
    for (int i = 0; i < 24; i++) p.plan[8 + i / 12][i % 12] = (uint16_t)((T_K + (i % 3 & 1)) << 13 | i % 3 / 2 << 4 | i / 3);
    const int a0 = n;
    for (int key = 0; key < 4000; key++)
        for (int r = 0; r < 32; r++)
            for (int j = 7; j >= 0; j--)
                if ((j ? (7 - j) * 40 + r * beta : 3999) == key) add(T_ATTN, 2 * order[r >> 1] + (r & 1), j);
    int t0 = n;
    for (int work = 0; work < 32 * 136 * tail / 100;) work += 4 * (p.items[--t0] & 15) + 3;
    for (int i = t0 + 1; i < n; i++)
        for (int j = i; j > t0 && (p.items[j] & 15) > (p.items[j - 1] & 15); j--) { const uint16_t t = p.items[j]; p.items[j] = p.items[j - 1]; p.items[j - 1] = t; }
    for (int r = early - 1; r >= 0; r--) {
        const uint16_t t = p.items[n - 32 + early - 1];
        for (int j = n - 32 + early - 1; j > n - epos; j--) p.items[j] = p.items[j - 1];
        p.items[n - epos] = t;
    }
    for (int moved = 0; moved < 2 && late >= 0; moved++)
        for (int i = a0; i < n; i++)
            if (p.items[i] == (T_ATTN << 13 | (2 * order[15] + moved) << 4 | late)) {
                for (int j = i; j + 1 < n; j++) p.items[j] = p.items[j + 1];
                p.items[n - 1] = (uint16_t)(T_ATTN << 13 | (2 * order[15] + moved) << 4 | late);
                break;
            }
    for (int s = 0, lo = 0, hi = WIDE - 1; s < 80; s++) {
        const int r = s / 2, g = r < 8 ? 32 + r : 2 * order[r / 2 - 4] + (r & 1);
        p.ostep[s >= WIDE ? s : r & 1 ? hi-- : lo++] = (uint8_t)(2 * g + (s & 1));
    }
}

void build_params(Params& p, void* const* d_in, void* d_out) {
    void* fnp = nullptr;
    cudaDriverEntryPointQueryResult qr;
    cudaGetDriverEntryPoint("cuTensorMapEncodeTiled", &fnp, cudaEnableDefault, &qr);
    EncodeFn fn = (EncodeFn)fnp;
    void* scr = nullptr;
    cudaGetSymbolAddress(&scr, g_scr);
    map_act(fn, &p.m[M_X], d_in[0], SEQ, 1024, 128);
    map_act(fn, &p.m[M_C], d_in[1], SEQ, 512, 128);
    map_wgt(fn, &p.m[M_WQ], d_in[2], 1024, 4096);
    map_wgt(fn, &p.m[M_WUK], d_in[3], 512, 4096);
    map_wgt(fn, &p.m[M_WUV], d_in[4], 512, 4096);
    map_wgt(fn, &p.m[M_WO], d_in[5], 4096, 1024);
    map_wgt(fn, &p.m[M_WQKV], d_in[7], 1024, 3072);
    map_wgt(fn, &p.m[M_WOB], d_in[8], 1024, 1024);
    encode3(fn, &p.m[M_SCR_LD], scr, 128, SEQ, G_TOTAL, 256, (uint64_t)SEQ * 256, 64, 128, 1);
    encode3(fn, &p.m[M_SCR_LOC], scr, 256, SEQ / 2, G_TOTAL, 512, (uint64_t)SEQ * 256, 64, 72, 1);
    encode3(fn, &p.m[M_SCR_LOQ], scr, 256, SEQ / 2, G_TOTAL, 512, (uint64_t)SEQ * 256, 64, 64, 1);
    encode3(fn, &p.m[M_SCR_ST], scr, 128, SEQ, G_TOTAL, 256, (uint64_t)SEQ * 256, 64, 64, 1);
    map_act(fn, &p.m[M_OUT], d_out, SEQ, 1024, 64);
    p.x = (const __nv_bfloat16*)d_in[0];
    p.gate_w = (const __nv_bfloat16*)d_in[9];
    p.zero = 0;
    p.wo = (const char*)d_in[5];
    p.out = (__nv_bfloat16*)d_out;
    build_schedule(p);
}

}

extern "C" void kernel_launch(void* const* d_in, const int* in_sizes, int n_in, void* d_out, int out_size) {
    (void)in_sizes; (void)n_in; (void)out_size;
    Params p;
    build_params(p, d_in, d_out);
    cudaFuncSetAttribute(fused_kernel, cudaFuncAttributeMaxDynamicSharedMemorySize, SM_TOTAL);
    fused_kernel<<<NCTA, 384, SM_TOTAL>>>(p);
}
```

```cpp
#include <cuda_runtime.h>
#include <cuda_bf16.h>
#include <cuda.h>
#include <stddef.h>
#include <stdint.h>
#include <type_traits>

namespace {

constexpr int SEQ = 2048;
constexpr int G_Q = 0, G_K = 32, G_V = 64, G_B = 96, G_CTX = G_Q, G_LOC = G_B, G_TOTAL = 120;

__device__ __align__(1024) __nv_bfloat16 g_scr[(size_t)G_TOTAL * SEQ * 128];
__device__ __align__(128) float g_gate[SEQ];

__device__ __forceinline__ uint32_t smem_u32(const void* p) { return (uint32_t)__cvta_generic_to_shared(p); }
__device__ __forceinline__ bool elect_one() {
    uint32_t p;
    asm volatile("{\n.reg .pred P;\nelect.sync _|P, 0xffffffff;\nselp.u32 %0, 1, 0, P;\n}\n" : "=r"(p));
    return p != 0;
}
__device__ __forceinline__ void mbar_init(uint32_t bar, uint32_t count) {
    asm volatile("mbarrier.init.shared::cta.b64 [%0], %1;" :: "r"(bar), "r"(count) : "memory");
}
__device__ __forceinline__ uint32_t cluster_rank() { uint32_t r; asm("mov.u32 %0, %%cluster_ctarank;" : "=r"(r)); return r; }
__device__ __forceinline__ uint32_t map_cta(uint32_t addr, uint32_t cta) {
    uint32_t r; asm("mapa.shared::cluster.u32 %0, %1, %2;" : "=r"(r) : "r"(addr), "r"(cta)); return r;
}
__device__ __forceinline__ void mbar_arrive_cluster_if(bool pred, uint32_t cluster_bar) {
    asm volatile("{\n.reg .pred P;\nsetp.ne.u32 P, %1, 0;\n@P mbarrier.arrive.shared::cluster.b64 _, [%0];\n}\n"
                 :: "r"(cluster_bar), "r"((uint32_t)pred) : "memory");
}
__device__ __forceinline__ void mbar_arrive_cluster_n_if(bool pred, uint32_t cluster_bar, uint32_t count) {
    asm volatile("{\n.reg .pred P;\nsetp.ne.u32 P, %1, 0;\n@P mbarrier.arrive.shared::cluster.b64 _, [%0], %2;\n}\n"
                 :: "r"(cluster_bar), "r"((uint32_t)pred), "r"(count) : "memory");
}
__device__ __forceinline__ void mbar_arrive_if(bool pred, uint32_t bar) {
    asm volatile("{\n.reg .pred P;\nsetp.ne.u32 P, %1, 0;\n@P mbarrier.arrive.shared::cta.b64 _, [%0];\n}\n"
                 :: "r"(bar), "r"((uint32_t)pred) : "memory");
}
__device__ __forceinline__ bool mbar_test(uint32_t bar, uint32_t parity) {
    uint32_t ok;
    asm volatile("{\n.reg .pred P;\nmbarrier.test_wait.parity.shared::cta.b64 P, [%1], %2;\nselp.u32 %0, 1, 0, P;\n}\n"
                 : "=r"(ok) : "r"(bar), "r"(parity) : "memory");
    return ok != 0;
}
__device__ __forceinline__ void mbar_wait(uint32_t bar, uint32_t parity) {
    asm volatile("{\n.reg .pred P;\n.reg .u32 c;\n"
                 "mov.u32 c, 0;\n"
                 "SPIN:\n"
                 "mbarrier.try_wait.parity.shared::cta.b64 P, [%0], %1;\n"
                 "@P bra DONE;\n"
                 "add.u32 c, c, 1;\n"
                 "setp.lt.u32 P, c, 4194304;\n"
                 "@P bra SPIN;\n"
                 "trap;\n"
                 "DONE:\n}\n" :: "r"(bar), "r"(parity) : "memory");
}
__device__ __forceinline__ void mbar_spin(uint32_t bar, uint32_t parity) {
    asm volatile("{\n.reg .pred P;\n"
                 "SPIN:\n"
                 "mbarrier.try_wait.parity.shared::cta.b64 P, [%0], %1;\n"
                 "@!P bra SPIN;\n}\n" :: "r"(bar), "r"(parity) : "memory");
}
__device__ __forceinline__ void bar_sync(int id, int n) { asm volatile("bar.sync %0, %1;" :: "r"(id), "r"(n) : "memory"); }
__device__ __forceinline__ void bar_arrive(int id, int n) { asm volatile("bar.arrive %0, %1;" :: "r"(id), "r"(n) : "memory"); }
__device__ __forceinline__ void fence_proxy_async_smem() { asm volatile("fence.proxy.async.shared::cta;" ::: "memory"); }
__device__ __forceinline__ void warp_expect_tx(uint32_t bar, uint32_t bytes) {
    asm volatile("{\n.reg .pred P;\nelect.sync _|P, 0xffffffff;\n@P mbarrier.arrive.expect_tx.shared::cta.b64 _, [%0], %1;\n}\n"
                 :: "r"(bar), "r"(bytes) : "memory");
}
constexpr uint64_t EVICT_FIRST = 0x12F0000000000000ull;
__device__ __forceinline__ void warp_tma_load(uint32_t dst, const CUtensorMap* map, uint32_t bar, int c0, int c1, int c2, bool stream) {
    if (stream)
        asm volatile("{\n.reg .pred P;\nelect.sync _|P, 0xffffffff;\n"
                     "@P cp.async.bulk.tensor.3d.shared::cluster.global.mbarrier::complete_tx::bytes.L2::cache_hint"
                     " [%0], [%1, {%3, %4, %5}], [%2], %6;\n}\n"
                     :: "r"(dst), "l"(map), "r"(bar), "r"(c0), "r"(c1), "r"(c2), "l"(EVICT_FIRST) : "memory");
    else
        asm volatile("{\n.reg .pred P;\nelect.sync _|P, 0xffffffff;\n"
                     "@P cp.async.bulk.tensor.3d.shared::cluster.global.mbarrier::complete_tx::bytes [%0], [%1, {%3, %4, %5}], [%2];\n}\n"
                     :: "r"(dst), "l"(map), "r"(bar), "r"(c0), "r"(c1), "r"(c2) : "memory");
}
__device__ __forceinline__ void warp_tma_load_pair(uint32_t dst, const CUtensorMap* map, uint32_t bar, int c0, int c1, int c2, bool stream) {
    if (stream)
        asm volatile("{\n.reg .pred P;\nelect.sync _|P, 0xffffffff;\n"
                     "@P cp.async.bulk.tensor.3d.shared::cluster.global.mbarrier::complete_tx::bytes.multicast::cluster.L2::cache_hint"
                     " [%0], [%1, {%3, %4, %5}], [%2], %6, %7;\n}\n"
                     :: "r"(dst), "l"(map), "r"(bar), "r"(c0), "r"(c1), "r"(c2), "h"((uint16_t)3), "l"(EVICT_FIRST) : "memory");
    else
        asm volatile("{\n.reg .pred P;\nelect.sync _|P, 0xffffffff;\n"
                     "@P cp.async.bulk.tensor.3d.shared::cluster.global.mbarrier::complete_tx::bytes.multicast::cluster"
                     " [%0], [%1, {%3, %4, %5}], [%2], %6;\n}\n"
                     :: "r"(dst), "l"(map), "r"(bar), "r"(c0), "r"(c1), "r"(c2), "h"((uint16_t)3) : "memory");
}
__device__ __forceinline__ void warp_bulk_load(uint32_t dst, const void* src, uint32_t bytes, uint32_t bar) {
    asm volatile("{\n.reg .pred P;\nelect.sync _|P, 0xffffffff;\n"
                 "@P cp.async.bulk.shared::cluster.global.mbarrier::complete_tx::bytes [%0], [%1], %2, [%3];\n}\n"
                 :: "r"(dst), "l"(src), "r"(bytes), "r"(bar) : "memory");
}
__device__ __forceinline__ void warp_tma_store(const CUtensorMap* map, uint32_t src, int c0, int c1, int c2, bool stream) {
    if (stream)
        asm volatile("{\n.reg .pred P;\nelect.sync _|P, 0xffffffff;\n"
                     "@P cp.async.bulk.tensor.3d.global.shared::cta.bulk_group.L2::cache_hint [%0, {%2, %3, %4}], [%1], %5;\n}\n"
                     :: "l"(map), "r"(src), "r"(c0), "r"(c1), "r"(c2), "l"(EVICT_FIRST) : "memory");
    else
        asm volatile("{\n.reg .pred P;\nelect.sync _|P, 0xffffffff;\n"
                     "@P cp.async.bulk.tensor.3d.global.shared::cta.bulk_group [%0, {%2, %3, %4}], [%1];\n}\n"
                     :: "l"(map), "r"(src), "r"(c0), "r"(c1), "r"(c2) : "memory");
}
__device__ __forceinline__ void warp_tma_add(const CUtensorMap* map, uint32_t src, int c0, int c1, int c2) {
    asm volatile("{\n.reg .pred P;\nelect.sync _|P, 0xffffffff;\n"
                 "@P cp.reduce.async.bulk.tensor.3d.global.shared::cta.add.tile.bulk_group [%0, {%2, %3, %4}], [%1];\n}\n"
                 :: "l"(map), "r"(src), "r"(c0), "r"(c1), "r"(c2) : "memory");
}
__device__ __forceinline__ void warp_bulk_store(void* dst, uint32_t src, uint32_t bytes) {
    asm volatile("{\n.reg .pred P;\nelect.sync _|P, 0xffffffff;\n"
                 "@P cp.async.bulk.global.shared::cta.bulk_group [%0], [%1], %2;\n}\n" :: "l"(dst), "r"(src), "r"(bytes) : "memory");
}
__device__ __forceinline__ void warp_prefetch(const void* src, uint32_t bytes) {
    asm volatile("{\n.reg .pred P;\nelect.sync _|P, 0xffffffff;\n@P cp.async.bulk.prefetch.L2.global [%0], %1;\n}\n" :: "l"(src), "r"(bytes) : "memory");
}
__device__ __forceinline__ void bulk_commit() { asm volatile("cp.async.bulk.commit_group;" ::: "memory"); }
template <int N> __device__ __forceinline__ void bulk_wait_read() { asm volatile("cp.async.bulk.wait_group.read %0;" :: "n"(N) : "memory"); }
template <int N> __device__ __forceinline__ void bulk_wait() { asm volatile("cp.async.bulk.wait_group %0;" :: "n"(N) : "memory"); }
__device__ __forceinline__ void wgmma_fence() { asm volatile("wgmma.fence.sync.aligned;" ::: "memory"); }
__device__ __forceinline__ void wgmma_commit() { asm volatile("wgmma.commit_group.sync.aligned;" ::: "memory"); }
template <int N> __device__ __forceinline__ void wgmma_wait() { asm volatile("wgmma.wait_group.sync.aligned %0;" :: "n"(N) : "memory"); }
template <int N> __device__ __forceinline__ void fence_regs(float (&d)[N]) {
#pragma unroll
    for (int i = 0; i < N; i++) asm volatile("" : "+f"(d[i]) :: "memory");
}
template <int N> __device__ __forceinline__ void fence_regs(uint32_t (&d)[N]) {
#pragma unroll
    for (int i = 0; i < N; i++) asm volatile("" : "+r"(d[i]) :: "memory");
}
template <int N> __device__ __forceinline__ void reg_dec() { asm volatile("setmaxnreg.dec.sync.aligned.u32 %0;" :: "n"(N)); }
template <int N> __device__ __forceinline__ void reg_inc() { asm volatile("setmaxnreg.inc.sync.aligned.u32 %0;" :: "n"(N)); }
__device__ __forceinline__ uint32_t pack_bf16(float lo, float hi) {
    uint32_t r; asm("cvt.rn.bf16x2.f32 %0, %1, %2;" : "=r"(r) : "f"(hi), "f"(lo)); return r;
}
__device__ __forceinline__ void stmatrix_x4(uint32_t addr, uint32_t r0, uint32_t r1, uint32_t r2, uint32_t r3) {
    asm volatile("stmatrix.sync.aligned.m8n8.x4.shared.b16 [%0], {%1, %2, %3, %4};"
                 :: "r"(addr), "r"(r0), "r"(r1), "r"(r2), "r"(r3) : "memory");
}
__device__ __forceinline__ float ex2(float x) { float y; asm("ex2.approx.ftz.f32 %0, %1;" : "=f"(y) : "f"(x)); return y; }

constexpr uint32_t DESC_HI = (1024 >> 4) | (1u << 30);
__device__ __forceinline__ uint32_t make_desc(uint32_t addr, uint32_t lbo) {
    uint32_t lo = ((addr & 0x3FFFF) >> 4) | ((lbo >> 4) << 16);
    asm volatile("" : "+r"(lo));
    return lo;
}
__device__ __forceinline__ uint64_t full_desc(uint32_t lo) {
    uint64_t d; asm("mov.b64 %0, {%1, %2};" : "=l"(d) : "r"(lo), "r"(DESC_HI)); return d;
}

__device__ __forceinline__ void wgmma_ss_n256_tb_init(float (&d)[128], uint64_t da, uint64_t db) {
    asm volatile("{\n.reg .pred p;\n"
        "setp.ne.b32 p, 0, 0;\n"
        "wgmma.mma_async.sync.aligned.m64n256k16.f32.bf16.bf16 "
        "{%0, %1, %2, %3, %4, %5, %6, %7, %8, %9, %10, %11, %12, %13, %14, %15, %16, %17, %18, %19, %20, "
        "%21, %22, %23, %24, %25, %26, %27, %28, %29, %30, %31, %32, %33, %34, %35, %36, %37, %38, %39, %40, "
        "%41, %42, %43, %44, %45, %46, %47, %48, %49, %50, %51, %52, %53, %54, %55, %56, %57, %58, %59, %60, "
        "%61, %62, %63, %64, %65, %66, %67, %68, %69, %70, %71, %72, %73, %74, %75, %76, %77, %78, %79, %80, "
        "%81, %82, %83, %84, %85, %86, %87, %88, %89, %90, %91, %92, %93, %94, %95, %96, %97, %98, %99, "
        "%100, %101, %102, %103, %104, %105, %106, %107, %108, %109, %110, %111, %112, %113, %114, %115, "
        "%116, %117, %118, %119, %120, %121, %122, %123, %124, %125, %126, %127},"
        " %128, %129, p, 1, 1, 0, 1;\n}\n"
        : "=f"(d[0]), "=f"(d[1]), "=f"(d[2]), "=f"(d[3]), "=f"(d[4]), "=f"(d[5]), "=f"(d[6]), "=f"(d[7]),
        "=f"(d[8]), "=f"(d[9]), "=f"(d[10]), "=f"(d[11]), "=f"(d[12]), "=f"(d[13]), "=f"(d[14]), "=f"(d[15]),
        "=f"(d[16]), "=f"(d[17]), "=f"(d[18]), "=f"(d[19]), "=f"(d[20]), "=f"(d[21]), "=f"(d[22]),
        "=f"(d[23]), "=f"(d[24]), "=f"(d[25]), "=f"(d[26]), "=f"(d[27]), "=f"(d[28]), "=f"(d[29]),
        "=f"(d[30]), "=f"(d[31]), "=f"(d[32]), "=f"(d[33]), "=f"(d[34]), "=f"(d[35]), "=f"(d[36]),
        "=f"(d[37]), "=f"(d[38]), "=f"(d[39]), "=f"(d[40]), "=f"(d[41]), "=f"(d[42]), "=f"(d[43]),
        "=f"(d[44]), "=f"(d[45]), "=f"(d[46]), "=f"(d[47]), "=f"(d[48]), "=f"(d[49]), "=f"(d[50]),
        "=f"(d[51]), "=f"(d[52]), "=f"(d[53]), "=f"(d[54]), "=f"(d[55]), "=f"(d[56]), "=f"(d[57]),
        "=f"(d[58]), "=f"(d[59]), "=f"(d[60]), "=f"(d[61]), "=f"(d[62]), "=f"(d[63]), "=f"(d[64]),
        "=f"(d[65]), "=f"(d[66]), "=f"(d[67]), "=f"(d[68]), "=f"(d[69]), "=f"(d[70]), "=f"(d[71]),
        "=f"(d[72]), "=f"(d[73]), "=f"(d[74]), "=f"(d[75]), "=f"(d[76]), "=f"(d[77]), "=f"(d[78]),
        "=f"(d[79]), "=f"(d[80]), "=f"(d[81]), "=f"(d[82]), "=f"(d[83]), "=f"(d[84]), "=f"(d[85]),
        "=f"(d[86]), "=f"(d[87]), "=f"(d[88]), "=f"(d[89]), "=f"(d[90]), "=f"(d[91]), "=f"(d[92]),
        "=f"(d[93]), "=f"(d[94]), "=f"(d[95]), "=f"(d[96]), "=f"(d[97]), "=f"(d[98]), "=f"(d[99]),
        "=f"(d[100]), "=f"(d[101]), "=f"(d[102]), "=f"(d[103]), "=f"(d[104]), "=f"(d[105]), "=f"(d[106]),
        "=f"(d[107]), "=f"(d[108]), "=f"(d[109]), "=f"(d[110]), "=f"(d[111]), "=f"(d[112]), "=f"(d[113]),
        "=f"(d[114]), "=f"(d[115]), "=f"(d[116]), "=f"(d[117]), "=f"(d[118]), "=f"(d[119]), "=f"(d[120]),
        "=f"(d[121]), "=f"(d[122]), "=f"(d[123]), "=f"(d[124]), "=f"(d[125]), "=f"(d[126]), "=f"(d[127])
        : "l"(da), "l"(db));
}
__device__ __forceinline__ void wgmma_ss_n256_tb(float (&d)[128], uint64_t da, uint64_t db, int scale_d) {
    asm volatile("{\n.reg .pred p;\n"
        "setp.ne.b32 p, %130, 0;\n"
        "wgmma.mma_async.sync.aligned.m64n256k16.f32.bf16.bf16 "
        "{%0, %1, %2, %3, %4, %5, %6, %7, %8, %9, %10, %11, %12, %13, %14, %15, %16, %17, %18, %19, %20, "
        "%21, %22, %23, %24, %25, %26, %27, %28, %29, %30, %31, %32, %33, %34, %35, %36, %37, %38, %39, %40, "
        "%41, %42, %43, %44, %45, %46, %47, %48, %49, %50, %51, %52, %53, %54, %55, %56, %57, %58, %59, %60, "
        "%61, %62, %63, %64, %65, %66, %67, %68, %69, %70, %71, %72, %73, %74, %75, %76, %77, %78, %79, %80, "
        "%81, %82, %83, %84, %85, %86, %87, %88, %89, %90, %91, %92, %93, %94, %95, %96, %97, %98, %99, "
        "%100, %101, %102, %103, %104, %105, %106, %107, %108, %109, %110, %111, %112, %113, %114, %115, "
        "%116, %117, %118, %119, %120, %121, %122, %123, %124, %125, %126, %127},"
        " %128, %129, p, 1, 1, 0, 1;\n}\n"
        : "+f"(d[0]), "+f"(d[1]), "+f"(d[2]), "+f"(d[3]), "+f"(d[4]), "+f"(d[5]), "+f"(d[6]), "+f"(d[7]),
        "+f"(d[8]), "+f"(d[9]), "+f"(d[10]), "+f"(d[11]), "+f"(d[12]), "+f"(d[13]), "+f"(d[14]), "+f"(d[15]),
        "+f"(d[16]), "+f"(d[17]), "+f"(d[18]), "+f"(d[19]), "+f"(d[20]), "+f"(d[21]), "+f"(d[22]),
        "+f"(d[23]), "+f"(d[24]), "+f"(d[25]), "+f"(d[26]), "+f"(d[27]), "+f"(d[28]), "+f"(d[29]),
        "+f"(d[30]), "+f"(d[31]), "+f"(d[32]), "+f"(d[33]), "+f"(d[34]), "+f"(d[35]), "+f"(d[36]),
        "+f"(d[37]), "+f"(d[38]), "+f"(d[39]), "+f"(d[40]), "+f"(d[41]), "+f"(d[42]), "+f"(d[43]),
        "+f"(d[44]), "+f"(d[45]), "+f"(d[46]), "+f"(d[47]), "+f"(d[48]), "+f"(d[49]), "+f"(d[50]),
        "+f"(d[51]), "+f"(d[52]), "+f"(d[53]), "+f"(d[54]), "+f"(d[55]), "+f"(d[56]), "+f"(d[57]),
        "+f"(d[58]), "+f"(d[59]), "+f"(d[60]), "+f"(d[61]), "+f"(d[62]), "+f"(d[63]), "+f"(d[64]),
        "+f"(d[65]), "+f"(d[66]), "+f"(d[67]), "+f"(d[68]), "+f"(d[69]), "+f"(d[70]), "+f"(d[71]),
        "+f"(d[72]), "+f"(d[73]), "+f"(d[74]), "+f"(d[75]), "+f"(d[76]), "+f"(d[77]), "+f"(d[78]),
        "+f"(d[79]), "+f"(d[80]), "+f"(d[81]), "+f"(d[82]), "+f"(d[83]), "+f"(d[84]), "+f"(d[85]),
        "+f"(d[86]), "+f"(d[87]), "+f"(d[88]), "+f"(d[89]), "+f"(d[90]), "+f"(d[91]), "+f"(d[92]),
        "+f"(d[93]), "+f"(d[94]), "+f"(d[95]), "+f"(d[96]), "+f"(d[97]), "+f"(d[98]), "+f"(d[99]),
        "+f"(d[100]), "+f"(d[101]), "+f"(d[102]), "+f"(d[103]), "+f"(d[104]), "+f"(d[105]), "+f"(d[106]),
        "+f"(d[107]), "+f"(d[108]), "+f"(d[109]), "+f"(d[110]), "+f"(d[111]), "+f"(d[112]), "+f"(d[113]),
        "+f"(d[114]), "+f"(d[115]), "+f"(d[116]), "+f"(d[117]), "+f"(d[118]), "+f"(d[119]), "+f"(d[120]),
        "+f"(d[121]), "+f"(d[122]), "+f"(d[123]), "+f"(d[124]), "+f"(d[125]), "+f"(d[126]), "+f"(d[127])
        : "l"(da), "l"(db), "r"(scale_d));
}
__device__ __forceinline__ void wgmma_ss_n128_init(float (&d)[64], uint64_t da, uint64_t db) {
    asm volatile("{\n.reg .pred p;\n"
        "setp.ne.b32 p, 0, 0;\n"
        "wgmma.mma_async.sync.aligned.m64n128k16.f32.bf16.bf16 "
        "{%0, %1, %2, %3, %4, %5, %6, %7, %8, %9, %10, %11, %12, %13, %14, %15, %16, %17, %18, %19, %20, "
        "%21, %22, %23, %24, %25, %26, %27, %28, %29, %30, %31, %32, %33, %34, %35, %36, %37, %38, %39, %40, "
        "%41, %42, %43, %44, %45, %46, %47, %48, %49, %50, %51, %52, %53, %54, %55, %56, %57, %58, %59, %60, "
        "%61, %62, %63},"
        " %64, %65, p, 1, 1, 0, 0;\n}\n"
        : "=f"(d[0]), "=f"(d[1]), "=f"(d[2]), "=f"(d[3]), "=f"(d[4]), "=f"(d[5]), "=f"(d[6]), "=f"(d[7]),
        "=f"(d[8]), "=f"(d[9]), "=f"(d[10]), "=f"(d[11]), "=f"(d[12]), "=f"(d[13]), "=f"(d[14]), "=f"(d[15]),
        "=f"(d[16]), "=f"(d[17]), "=f"(d[18]), "=f"(d[19]), "=f"(d[20]), "=f"(d[21]), "=f"(d[22]),
        "=f"(d[23]), "=f"(d[24]), "=f"(d[25]), "=f"(d[26]), "=f"(d[27]), "=f"(d[28]), "=f"(d[29]),
        "=f"(d[30]), "=f"(d[31]), "=f"(d[32]), "=f"(d[33]), "=f"(d[34]), "=f"(d[35]), "=f"(d[36]),
        "=f"(d[37]), "=f"(d[38]), "=f"(d[39]), "=f"(d[40]), "=f"(d[41]), "=f"(d[42]), "=f"(d[43]),
        "=f"(d[44]), "=f"(d[45]), "=f"(d[46]), "=f"(d[47]), "=f"(d[48]), "=f"(d[49]), "=f"(d[50]),
        "=f"(d[51]), "=f"(d[52]), "=f"(d[53]), "=f"(d[54]), "=f"(d[55]), "=f"(d[56]), "=f"(d[57]),
        "=f"(d[58]), "=f"(d[59]), "=f"(d[60]), "=f"(d[61]), "=f"(d[62]), "=f"(d[63])
        : "l"(da), "l"(db));
}
__device__ __forceinline__ void wgmma_ss_n128(float (&d)[64], uint64_t da, uint64_t db, int scale_d) {
    asm volatile("{\n.reg .pred p;\n"
        "setp.ne.b32 p, %66, 0;\n"
        "wgmma.mma_async.sync.aligned.m64n128k16.f32.bf16.bf16 "
        "{%0, %1, %2, %3, %4, %5, %6, %7, %8, %9, %10, %11, %12, %13, %14, %15, %16, %17, %18, %19, %20, "
        "%21, %22, %23, %24, %25, %26, %27, %28, %29, %30, %31, %32, %33, %34, %35, %36, %37, %38, %39, %40, "
        "%41, %42, %43, %44, %45, %46, %47, %48, %49, %50, %51, %52, %53, %54, %55, %56, %57, %58, %59, %60, "
        "%61, %62, %63},"
        " %64, %65, p, 1, 1, 0, 0;\n}\n"
        : "+f"(d[0]), "+f"(d[1]), "+f"(d[2]), "+f"(d[3]), "+f"(d[4]), "+f"(d[5]), "+f"(d[6]), "+f"(d[7]),
        "+f"(d[8]), "+f"(d[9]), "+f"(d[10]), "+f"(d[11]), "+f"(d[12]), "+f"(d[13]), "+f"(d[14]), "+f"(d[15]),
        "+f"(d[16]), "+f"(d[17]), "+f"(d[18]), "+f"(d[19]), "+f"(d[20]), "+f"(d[21]), "+f"(d[22]),
        "+f"(d[23]), "+f"(d[24]), "+f"(d[25]), "+f"(d[26]), "+f"(d[27]), "+f"(d[28]), "+f"(d[29]),
        "+f"(d[30]), "+f"(d[31]), "+f"(d[32]), "+f"(d[33]), "+f"(d[34]), "+f"(d[35]), "+f"(d[36]),
        "+f"(d[37]), "+f"(d[38]), "+f"(d[39]), "+f"(d[40]), "+f"(d[41]), "+f"(d[42]), "+f"(d[43]),
        "+f"(d[44]), "+f"(d[45]), "+f"(d[46]), "+f"(d[47]), "+f"(d[48]), "+f"(d[49]), "+f"(d[50]),
        "+f"(d[51]), "+f"(d[52]), "+f"(d[53]), "+f"(d[54]), "+f"(d[55]), "+f"(d[56]), "+f"(d[57]),
        "+f"(d[58]), "+f"(d[59]), "+f"(d[60]), "+f"(d[61]), "+f"(d[62]), "+f"(d[63])
        : "l"(da), "l"(db), "r"(scale_d));
}
__device__ __forceinline__ void wgmma_rs_n128_tb(float (&d)[64], uint32_t a0, uint32_t a1, uint32_t a2, uint32_t a3, uint64_t db, int scale_d) {
    asm volatile("{\n.reg .pred p;\n"
        "setp.ne.b32 p, %69, 0;\n"
        "wgmma.mma_async.sync.aligned.m64n128k16.f32.bf16.bf16 "
        "{%0, %1, %2, %3, %4, %5, %6, %7, %8, %9, %10, %11, %12, %13, %14, %15, %16, %17, %18, %19, %20, "
        "%21, %22, %23, %24, %25, %26, %27, %28, %29, %30, %31, %32, %33, %34, %35, %36, %37, %38, %39, %40, "
        "%41, %42, %43, %44, %45, %46, %47, %48, %49, %50, %51, %52, %53, %54, %55, %56, %57, %58, %59, %60, "
        "%61, %62, %63},"
        " {%64, %65, %66, %67}, %68, p, 1, 1, 1;\n}\n"
        : "+f"(d[0]), "+f"(d[1]), "+f"(d[2]), "+f"(d[3]), "+f"(d[4]), "+f"(d[5]), "+f"(d[6]), "+f"(d[7]),
        "+f"(d[8]), "+f"(d[9]), "+f"(d[10]), "+f"(d[11]), "+f"(d[12]), "+f"(d[13]), "+f"(d[14]), "+f"(d[15]),
        "+f"(d[16]), "+f"(d[17]), "+f"(d[18]), "+f"(d[19]), "+f"(d[20]), "+f"(d[21]), "+f"(d[22]),
        "+f"(d[23]), "+f"(d[24]), "+f"(d[25]), "+f"(d[26]), "+f"(d[27]), "+f"(d[28]), "+f"(d[29]),
        "+f"(d[30]), "+f"(d[31]), "+f"(d[32]), "+f"(d[33]), "+f"(d[34]), "+f"(d[35]), "+f"(d[36]),
        "+f"(d[37]), "+f"(d[38]), "+f"(d[39]), "+f"(d[40]), "+f"(d[41]), "+f"(d[42]), "+f"(d[43]),
        "+f"(d[44]), "+f"(d[45]), "+f"(d[46]), "+f"(d[47]), "+f"(d[48]), "+f"(d[49]), "+f"(d[50]),
        "+f"(d[51]), "+f"(d[52]), "+f"(d[53]), "+f"(d[54]), "+f"(d[55]), "+f"(d[56]), "+f"(d[57]),
        "+f"(d[58]), "+f"(d[59]), "+f"(d[60]), "+f"(d[61]), "+f"(d[62]), "+f"(d[63])
        : "r"(a0), "r"(a1), "r"(a2), "r"(a3), "l"(db), "r"(scale_d));
}
__device__ __forceinline__ void wgmma_ss_n128_tb_init(float (&d)[64], uint64_t da, uint64_t db) {
    asm volatile("{\n.reg .pred p;\n"
        "setp.ne.b32 p, 0, 0;\n"
        "wgmma.mma_async.sync.aligned.m64n128k16.f32.bf16.bf16 "
        "{%0, %1, %2, %3, %4, %5, %6, %7, %8, %9, %10, %11, %12, %13, %14, %15, %16, %17, %18, %19, %20, "
        "%21, %22, %23, %24, %25, %26, %27, %28, %29, %30, %31, %32, %33, %34, %35, %36, %37, %38, %39, %40, "
        "%41, %42, %43, %44, %45, %46, %47, %48, %49, %50, %51, %52, %53, %54, %55, %56, %57, %58, %59, %60, "
        "%61, %62, %63},"
        " %64, %65, p, 1, 1, 0, 1;\n}\n"
        : "=f"(d[0]), "=f"(d[1]), "=f"(d[2]), "=f"(d[3]), "=f"(d[4]), "=f"(d[5]), "=f"(d[6]), "=f"(d[7]),
        "=f"(d[8]), "=f"(d[9]), "=f"(d[10]), "=f"(d[11]), "=f"(d[12]), "=f"(d[13]), "=f"(d[14]), "=f"(d[15]),
        "=f"(d[16]), "=f"(d[17]), "=f"(d[18]), "=f"(d[19]), "=f"(d[20]), "=f"(d[21]), "=f"(d[22]),
        "=f"(d[23]), "=f"(d[24]), "=f"(d[25]), "=f"(d[26]), "=f"(d[27]), "=f"(d[28]), "=f"(d[29]),
        "=f"(d[30]), "=f"(d[31]), "=f"(d[32]), "=f"(d[33]), "=f"(d[34]), "=f"(d[35]), "=f"(d[36]),
        "=f"(d[37]), "=f"(d[38]), "=f"(d[39]), "=f"(d[40]), "=f"(d[41]), "=f"(d[42]), "=f"(d[43]),
        "=f"(d[44]), "=f"(d[45]), "=f"(d[46]), "=f"(d[47]), "=f"(d[48]), "=f"(d[49]), "=f"(d[50]),
        "=f"(d[51]), "=f"(d[52]), "=f"(d[53]), "=f"(d[54]), "=f"(d[55]), "=f"(d[56]), "=f"(d[57]),
        "=f"(d[58]), "=f"(d[59]), "=f"(d[60]), "=f"(d[61]), "=f"(d[62]), "=f"(d[63])
        : "l"(da), "l"(db));
}
__device__ __forceinline__ void wgmma_ss_n128_tb(float (&d)[64], uint64_t da, uint64_t db, int scale_d) {
    asm volatile("{\n.reg .pred p;\n"
        "setp.ne.b32 p, %66, 0;\n"
        "wgmma.mma_async.sync.aligned.m64n128k16.f32.bf16.bf16 "
        "{%0, %1, %2, %3, %4, %5, %6, %7, %8, %9, %10, %11, %12, %13, %14, %15, %16, %17, %18, %19, %20, "
        "%21, %22, %23, %24, %25, %26, %27, %28, %29, %30, %31, %32, %33, %34, %35, %36, %37, %38, %39, %40, "
        "%41, %42, %43, %44, %45, %46, %47, %48, %49, %50, %51, %52, %53, %54, %55, %56, %57, %58, %59, %60, "
        "%61, %62, %63},"
        " %64, %65, p, 1, 1, 0, 1;\n}\n"
        : "+f"(d[0]), "+f"(d[1]), "+f"(d[2]), "+f"(d[3]), "+f"(d[4]), "+f"(d[5]), "+f"(d[6]), "+f"(d[7]),
        "+f"(d[8]), "+f"(d[9]), "+f"(d[10]), "+f"(d[11]), "+f"(d[12]), "+f"(d[13]), "+f"(d[14]), "+f"(d[15]),
        "+f"(d[16]), "+f"(d[17]), "+f"(d[18]), "+f"(d[19]), "+f"(d[20]), "+f"(d[21]), "+f"(d[22]),
        "+f"(d[23]), "+f"(d[24]), "+f"(d[25]), "+f"(d[26]), "+f"(d[27]), "+f"(d[28]), "+f"(d[29]),
        "+f"(d[30]), "+f"(d[31]), "+f"(d[32]), "+f"(d[33]), "+f"(d[34]), "+f"(d[35]), "+f"(d[36]),
        "+f"(d[37]), "+f"(d[38]), "+f"(d[39]), "+f"(d[40]), "+f"(d[41]), "+f"(d[42]), "+f"(d[43]),
        "+f"(d[44]), "+f"(d[45]), "+f"(d[46]), "+f"(d[47]), "+f"(d[48]), "+f"(d[49]), "+f"(d[50]),
        "+f"(d[51]), "+f"(d[52]), "+f"(d[53]), "+f"(d[54]), "+f"(d[55]), "+f"(d[56]), "+f"(d[57]),
        "+f"(d[58]), "+f"(d[59]), "+f"(d[60]), "+f"(d[61]), "+f"(d[62]), "+f"(d[63])
        : "l"(da), "l"(db), "r"(scale_d));
}
__device__ __forceinline__ void wgmma_ss_n64_lo(float (&d)[64], uint64_t da, uint64_t db, int scale_d) {
    asm volatile("{\n.reg .pred p;\n"
        "setp.ne.b32 p, %34, 0;\n"
        "wgmma.mma_async.sync.aligned.m64n64k16.f32.bf16.bf16 "
        "{%0, %1, %2, %3, %4, %5, %6, %7, %8, %9, %10, %11, %12, %13, %14, %15, %16, %17, %18, %19, %20, "
        "%21, %22, %23, %24, %25, %26, %27, %28, %29, %30, %31},"
        " %32, %33, p, 1, 1, 0, 0;\n}\n"
        : "+f"(d[0]), "+f"(d[1]), "+f"(d[2]), "+f"(d[3]), "+f"(d[4]), "+f"(d[5]), "+f"(d[6]), "+f"(d[7]),
        "+f"(d[8]), "+f"(d[9]), "+f"(d[10]), "+f"(d[11]), "+f"(d[12]), "+f"(d[13]), "+f"(d[14]), "+f"(d[15]),
        "+f"(d[16]), "+f"(d[17]), "+f"(d[18]), "+f"(d[19]), "+f"(d[20]), "+f"(d[21]), "+f"(d[22]),
        "+f"(d[23]), "+f"(d[24]), "+f"(d[25]), "+f"(d[26]), "+f"(d[27]), "+f"(d[28]), "+f"(d[29]),
        "+f"(d[30]), "+f"(d[31])
        : "l"(da), "l"(db), "r"(scale_d));
}

enum { M_X = 0, M_C, M_WQ, M_WUK, M_WUV, M_WQKV, M_WO, M_WOB, M_SCR_LD, M_SCR_LOC, M_SCR_LOQ, M_SCR_ST, M_OUT, M_COUNT };
enum { T_Q = 0, T_K, T_V, T_B, T_OUT, T_LOCAL, T_ATTN, T_END };
constexpr int NCTA = 132;
constexpr int NITEMS = 256;
constexpr int TRIPLES = 2, WIDE = 80 - 3 * TRIPLES;
struct Params {
    CUtensorMap m[M_COUNT];
    const __nv_bfloat16* x;
    const __nv_bfloat16* gate_w;
    const char* wo;
    __nv_bfloat16* out;
    uint32_t zero;
    uint16_t plan[10][16];
    uint16_t items[NITEMS];
    uint8_t ostep[80];
    uint8_t kgroup[16];
};
__device__ __forceinline__ int item_type(int it) { return it >> 13; }
__device__ __forceinline__ int item_row(int it) { return it & 15; }
__device__ __forceinline__ int item_col(int it) { return (it >> 4) & 31; }
__device__ __forceinline__ int item_asc(int it) { return (it >> 9) & 1; }
constexpr int ITEM_READY = 1 << 10;

struct __align__(128) Sync {
    unsigned long long count[4];
    __align__(128) unsigned long long ctx[16];
    unsigned next, next_out, done;
    unsigned used;
    __align__(128) unsigned step[32][2];
    unsigned split[32];
};
__device__ Sync g_sync;

constexpr uint32_t GST_BYTES = 49152, SM_KV = 65536, SM_STAGING = 196608, SM_BARS = SM_STAGING + 32768;
constexpr uint32_t B_GFULL = 0, B_GEMPTY = 32, B_AFULL = 64, B_AEMPTY = 112, B_SFULL = 160, B_SEMPTY = 192,
                   B_IFULL = 224, B_IEMPTY = 288, B_XFREE = 352, B_WANT = 384, B_MEET = 392, B_HALF = 416,
                   SM_ORDY = 448, SM_QUEUE = 456, B_ALT = 488, B_QFREE = 504, SM_GATE = 512, SM_TOTAL = SM_BARS + 1536;
constexpr int QDEPTH = 8;
constexpr int FIRST_PAIR = 6;
constexpr int K_MEET = 16, K_SPLIT = 30;
constexpr int K_FETCH = 20;
constexpr uint32_t LOC_PLANE = 72 * 128;
constexpr float LOC_SCALE = 0.17677669529663687f * 1.4426950408889634f;
constexpr float SUM_LIMIT = 1180591620717411303424.f;
constexpr float REF_RANGE = 60.f;

__device__ __forceinline__ unsigned ld_acquire(const unsigned* p) {
    unsigned v; asm volatile("ld.acquire.gpu.global.u32 %0, [%1];" : "=r"(v) : "l"(p) : "memory"); return v;
}
__device__ __forceinline__ unsigned long long ld_acquire(const unsigned long long* p) {
    unsigned long long v; asm volatile("ld.acquire.gpu.global.u64 %0, [%1];" : "=l"(v) : "l"(p) : "memory"); return v;
}
__device__ __forceinline__ void spin_guard(unsigned& n) {
    asm volatile("{\n.reg .pred P;\nadd.u32 %0, %0, 1;\nsetp.gt.u32 P, %0, 16777216;\n@P trap;\n}\n" : "+r"(n));
    if (n > 1) __nanosleep(100);
}
__device__ __forceinline__ void red_add(unsigned long long* p, unsigned long long v) {
    asm volatile("red.release.gpu.global.add.u64 [%0], %1;" :: "l"(p), "l"(v) : "memory");
}
__device__ __forceinline__ float rcp(float x) { float y; asm("rcp.approx.ftz.f32 %0, %1;" : "=f"(y) : "f"(x)); return y; }
__device__ __forceinline__ float lds_f32(uint32_t addr) {
    float v; asm volatile("ld.shared.f32 %0, [%1];" : "=f"(v) : "r"(addr) : "memory"); return v;
}
__device__ __forceinline__ void ldsm_x4(uint32_t (&r)[4], uint32_t addr) {
    asm volatile("ldmatrix.sync.aligned.m8n8.x4.shared.b16 {%0, %1, %2, %3}, [%4];"
                 : "=r"(r[0]), "=r"(r[1]), "=r"(r[2]), "=r"(r[3]) : "r"(addr) : "memory");
}
__device__ __forceinline__ void ldsm_x4_t(uint32_t (&r)[4], uint32_t addr) {
    asm volatile("ldmatrix.sync.aligned.m8n8.x4.trans.shared.b16 {%0, %1, %2, %3}, [%4];"
                 : "=r"(r[0]), "=r"(r[1]), "=r"(r[2]), "=r"(r[3]) : "r"(addr) : "memory");
}
__device__ __forceinline__ void mma_k16(float (&d)[4], const uint32_t (&a)[4], uint32_t b0, uint32_t b1) {
    asm("mma.sync.aligned.m16n8k16.row.col.f32.bf16.bf16.f32 {%0,%1,%2,%3}, {%4,%5,%6,%7}, {%8,%9}, {%0,%1,%2,%3};"
        : "+f"(d[0]), "+f"(d[1]), "+f"(d[2]), "+f"(d[3]) : "r"(a[0]), "r"(a[1]), "r"(a[2]), "r"(a[3]), "r"(b0), "r"(b1));
}
__device__ __forceinline__ void mma_k16_init(float (&d)[4], const uint32_t (&a)[4], uint32_t b0, uint32_t b1) {
    asm("{\n.reg .f32 z;\nmov.f32 z, 0f00000000;\n"
        "mma.sync.aligned.m16n8k16.row.col.f32.bf16.bf16.f32 {%0,%1,%2,%3}, {%4,%5,%6,%7}, {%8,%9}, {z,z,z,z};\n}\n"
        : "=f"(d[0]), "=f"(d[1]), "=f"(d[2]), "=f"(d[3]) : "r"(a[0]), "r"(a[1]), "r"(a[2]), "r"(a[3]), "r"(b0), "r"(b1));
}
__device__ __forceinline__ void mma_k8(float (&d)[4], uint32_t a0, uint32_t a1, uint32_t b0) {
    asm("mma.sync.aligned.m16n8k8.row.col.f32.bf16.bf16.f32 {%0,%1,%2,%3}, {%4,%5}, {%6}, {%0,%1,%2,%3};"
        : "+f"(d[0]), "+f"(d[1]), "+f"(d[2]), "+f"(d[3]) : "r"(a0), "r"(a1), "r"(b0));
}
template <typename T, int N> __device__ __forceinline__ void zero_regs(T (&d)[N]) {
#pragma unroll
    for (int i = 0; i < N; i++) d[i] = 0;
}
__device__ __forceinline__ float quad_max(float v) {
    v = fmaxf(v, __shfl_xor_sync(0xffffffffu, v, 1));
    return fmaxf(v, __shfl_xor_sync(0xffffffffu, v, 2));
}
__device__ __forceinline__ float quad_sum(float v) {
    v += __shfl_xor_sync(0xffffffffu, v, 1);
    return v + __shfl_xor_sync(0xffffffffu, v, 2);
}

template <bool HALF>
__device__ __forceinline__ void qk_steps(float (&s)[64], uint32_t q_lo, uint32_t k_lo) {
    const uint64_t dq = full_desc(q_lo), dk = full_desc(k_lo);
    wgmma_fence();
    wgmma_ss_n128_init(s, dq, dk);
#pragma unroll
    for (int kk = 1; kk < 8; kk++) {
        const uint32_t o = (kk >> 2) * 1024 + (kk & 3) * 2;
        if (HALF) wgmma_ss_n64_lo(s, dq + o, dk + o, 1);
        else wgmma_ss_n128(s, dq + o, dk + o, 1);
    }
    wgmma_commit();
}
__device__ __forceinline__ void qk_gemm(float (&s)[64], uint32_t q_lo, uint32_t k_lo, bool half) {
    if (half) qk_steps<true>(s, q_lo, k_lo);
    else qk_steps<false>(s, q_lo, k_lo);
}
template <int NK>
__device__ __forceinline__ void pv_steps(float (&o)[64], uint32_t (&p)[32], uint32_t v_lo, int accumulate) {
    const uint64_t dv = full_desc(v_lo);
    fence_regs(o);
    fence_regs(p);
    wgmma_fence();
#pragma unroll
    for (int kk = 0; kk < NK; kk++)
        wgmma_rs_n128_tb(o, p[4 * kk], p[4 * kk + 1], p[4 * kk + 2], p[4 * kk + 3], dv + kk * 128, kk != 0 || accumulate);
    wgmma_commit();
}
__device__ __forceinline__ void pv_gemm(float (&o)[64], uint32_t (&p)[32], uint32_t v_lo, int accumulate, bool half) {
    if (half) pv_steps<4>(o, p, v_lo, accumulate);
    else pv_steps<8>(o, p, v_lo, accumulate);
}
__device__ __forceinline__ void row_max(const float (&s)[64], float& x0, float& x1) {
    float z0 = fmaxf(s[0], s[1]), z1 = fmaxf(s[2], s[3]);
    x0 = fmaxf(s[4], s[5]); x1 = fmaxf(s[6], s[7]);
#pragma unroll
    for (int j = 2; j < 16; j += 2) {
        z0 = fmaxf(z0, fmaxf(s[4 * j], s[4 * j + 1]));
        z1 = fmaxf(z1, fmaxf(s[4 * j + 2], s[4 * j + 3]));
        x0 = fmaxf(x0, fmaxf(s[4 * j + 4], s[4 * j + 5]));
        x1 = fmaxf(x1, fmaxf(s[4 * j + 6], s[4 * j + 7]));
    }
    x0 = quad_max(fmaxf(x0, z0)); x1 = quad_max(fmaxf(x1, z1));
}
template <int NJ>
__device__ __forceinline__ void exp_pack(uint32_t (&p)[32], const float (&s)[64], float& r0, float& r1) {
#pragma unroll
    for (int j = 2 * NJ; j < 32; j++) p[j] = 0;
#pragma unroll
    for (int j = 0; j < NJ; j++) {
        const float e0 = ex2(s[4 * j]), e1 = ex2(s[4 * j + 1]), e2 = ex2(s[4 * j + 2]), e3 = ex2(s[4 * j + 3]);
        if (j == 0) { r0 = e0 + e1; r1 = e2 + e3; }
        else { r0 += e0 + e1; r1 += e2 + e3; }
        p[2 * j] = pack_bf16(e0, e1);
        p[2 * j + 1] = pack_bf16(e2, e3);
    }
}
__device__ __forceinline__ void shift_rows(float (&s)[64], float d0, float d1) {
#pragma unroll
    for (int j = 0; j < 16; j++) { s[4 * j] -= d0; s[4 * j + 1] -= d0; s[4 * j + 2] -= d1; s[4 * j + 3] -= d1; }
}
constexpr float MASKED = -3e38f;
template <int J0>
__device__ __forceinline__ void mask_triangle(float (&s)[64], float thr) {
#pragma unroll
    for (int j = 0; j < 16; j++) {
        const float m = __saturatef((float)(8 * (j >> 1) + (j & 1)) - thr);
        const int i = 4 * (J0 + (j >> 1)) + (j & 1);
        s[i] = fmaf(m, MASKED, s[i]);
        if (j < 14) s[i + 6] = fmaf(m, MASKED, s[i + 6]);
    }
}
__device__ __forceinline__ void causal_mask(float (&s)[64], float thr, int wg) {
    asm volatile("" : "+f"(thr));
    if (wg == 0) mask_triangle<0>(s, thr);
    else mask_triangle<8>(s, thr);
}

__global__ void __cluster_dims__(2, 1, 1) __launch_bounds__(384, 1) fused_kernel(const __grid_constant__ Params prm) {
    extern __shared__ __align__(1024) uint8_t smem[];
    const uint32_t sb = smem_u32(smem), bars = sb + SM_BARS;
    const int warp = __shfl_sync(0xffffffffu, threadIdx.x >> 5, 0), lane = threadIdx.x & 31;

    const uint32_t rank = cluster_rank();
    const uint32_t bars0 = map_cta(bars, 0), bars_peer = map_cta(bars, rank ^ 1);

    const uint32_t cl = blockIdx.x >> 1, round7 = (cl - 36) * 37 >> 8;
    const uint32_t pair = cl < 4 ? 4 + cl : cl < 36 ? (cl - 4 & 7) * 8 + (cl - 4 >> 3) : cl < 64 ? (cl - 35 - 7 * round7) * 8 + 4 + round7 : cl;
    const int first_it = pair < 64 ? T_B << 13 | (4 * (pair & 7) - 11 * ((pair & 7) * 11 >> 5)) << 4 | (2 * (pair >> 3) + rank)
                                   : T_K << 13 | (8 * (pair & 7) + rank);
    if (warp == 0) {
        if (elect_one())
            for (int k = 0; k < 4; k++) mbar_init(bars + B_GFULL + 8 * k, 1);
        asm volatile("fence.mbarrier_init.release.cluster;" ::: "memory");
        fence_proxy_async_smem();
        __syncwarp();
        asm volatile("barrier.cluster.arrive.relaxed.aligned;" ::: "memory");
        const CUtensorMap* ma = &prm.m[item_type(first_it) == T_K ? M_C : M_X];
        const CUtensorMap* mb = &prm.m[M_WQ + item_type(first_it)];
#pragma unroll
        for (int k = 0; k < 2; k++) {
            const uint32_t dst = sb + k * GST_BYTES, fb = bars + B_GFULL + 8 * k;
            warp_expect_tx(fb, GST_BYTES);
            warp_tma_load(dst + 16384, mb, fb, 0, k * 64, item_col(first_it) * 4, true);
            warp_tma_load(dst, ma, fb, k * 64, item_row(first_it) * 128, 0, false);
            warp_tma_load(dst + 32768, mb, fb, 0, k * 64, item_col(first_it) * 4 + 2, true);
        }
    }
    if (threadIdx.x == 32) {
        for (int i = 0; i < 4; i++) mbar_init(bars + B_GEMPTY + 8 * i, 16);
        for (int i = 0; i < 6; i++) { mbar_init(bars + B_AFULL + 8 * i, 1); mbar_init(bars + B_AEMPTY + 8 * i, i < 2 ? 8 : 16); }
        for (int i = 0; i < 4; i++) { mbar_init(bars + B_SFULL + 8 * i, 4); mbar_init(bars + B_SEMPTY + 8 * i, 1); }
        for (int i = 0; i < QDEPTH; i++) { mbar_init(bars + B_IFULL + 8 * i, 1); mbar_init(bars + B_IEMPTY + 8 * i, 23); }
        mbar_init(bars + B_WANT, 2); mbar_init(bars + B_MEET, 1); mbar_init(bars + B_XFREE, 1);
        for (int i = 0; i < 4; i++) mbar_init(bars + B_HALF + 8 * i, 1);
        mbar_init(bars + B_ALT, 4); mbar_init(bars + B_ALT + 8, 4); mbar_init(bars + B_QFREE, 2);
        asm volatile("st.shared.u64 [%0], 0;" :: "r"(bars + SM_ORDY) : "memory");
        asm volatile("fence.mbarrier_init.release.cluster;\nfence.acq_rel.cta;" ::: "memory");
    }
    __syncwarp();
    if (warp != 0) asm volatile("barrier.cluster.arrive.relaxed.aligned;" ::: "memory");
    asm volatile("barrier.cluster.wait.acquire.aligned;" ::: "memory");

    uint32_t qn = 0;
    auto next_item = [&](bool releaser, bool bounded = true) -> int {
        const uint32_t slot = qn % QDEPTH;
        if (bounded) mbar_wait(bars + B_IFULL + 8 * slot, (qn / QDEPTH) & 1);
        else mbar_spin(bars + B_IFULL + 8 * slot, (qn / QDEPTH) & 1);
        uint32_t it;
        asm volatile("ld.shared.u32 %0, [%1];" : "=r"(it) : "r"(bars + SM_QUEUE + 4 * slot) : "memory");
        mbar_arrive_cluster_if(releaser, bars0 + B_IEMPTY + 8 * slot);
        qn++;
        return it;
    };

    if (warp < 4) {
        reg_dec<40>();
        if (warp == 0) {
            {
                uint32_t gph = 1;
                const uint32_t prank = __shfl_sync(0xffffffffu, rank, 0);
                auto request = [&]() { mbar_arrive_cluster_if(lane == 0, bars0 + B_WANT); };
                auto take_item = [&]() -> int { return __shfl_sync(0xffffffffu, next_item(lane == 0), 0); };
                auto inputs_seen = [&](uint32_t word, unsigned& n) -> uint32_t {
                    uint32_t v;
                    spin_guard(n);
                    asm volatile("ld.acquire.cta.shared.u32 %0, [%1];" : "=r"(v) : "r"(bars + SM_ORDY + 4 * word) : "memory");
                    return __shfl_sync(0xffffffffu, v, 0);
                };
                uint32_t oneed = 0;
                auto wait_inputs = [&](int it) {
                    if (it & ITEM_READY) return;
                    oneed += 256;
                    for (unsigned n = 0; inputs_seen(1, n) < oneed;) {}
                };
                int nxt = first_it, ring = -1, rot = 0;
                for (int k0 = 2; item_type(nxt) <= T_LOCAL; k0 = 0) {
                    const int type = item_type(nxt), m = item_row(nxt), c = item_col(nxt);
                    if (type == T_LOCAL) {
                        wait_inputs(nxt);
                        request();
#pragma unroll 1
                        for (uint32_t st = 0; st < 4; st++) {
                            mbar_wait(bars + B_GEMPTY + 8 * st, gph);
                            const uint32_t dst = sb + st * GST_BYTES, fb = bars + B_GFULL + 8 * st;
                            warp_expect_tx(fb, st == 0 ? 32768 + 512 : st == 3 ? 0 : 4 * LOC_PLANE);
                            if (st == 3) break;
                            if (st == 0) warp_bulk_load(dst + 4 * LOC_PLANE, &g_gate[m * 128], 512, fb);
#pragma unroll 1
                            for (int i = 0; i < 4; i++)
                                warp_tma_load(dst + i * LOC_PLANE, &prm.m[st ? M_SCR_LOC : M_SCR_LOQ], fb, i * 64, m * 64 - (st ? 8 : 0), G_B + 8 * st + c, false);
                        }
                        gph ^= 1;
                        ring = -1;
                    } else {
                        const int nk = type == T_K || type == T_V ? 8 : 16, kept = ring == m + 16 * nk ? 4 : 0;
                        ring = m + 16 * nk;
                        rot = kept ? rot - 4 : 0;
                        const CUtensorMap* ma = &prm.m[nk == 8 ? M_C : M_X];
                        const CUtensorMap* mb = &prm.m[M_WQ + type];
#pragma unroll 1
                        for (int k = k0; k < nk; k++) {
                            if (k == nk - 3) request();
                            const uint32_t st = k & 3, dst = sb + st * GST_BYTES, fb = bars + B_GFULL + 8 * st;
                            const int kc = ((k + rot) & (nk - 1)) * 64;
                            mbar_wait(bars + B_GEMPTY + 8 * st, gph);
                            warp_expect_tx(fb, k < kept ? 32768 : GST_BYTES);
                            if (k >= kept) warp_tma_load(dst, ma, fb, kc, m * 128, 0, c == 15 && type != T_K);
                            warp_tma_load_pair(dst + 16384 + prank * 16384, mb, fb, 0, kc, c * 4 + 2 * prank, blockIdx.x < 128 || (m & 6) == 6);
                            if (st == 3) gph ^= 1;
                        }
                    }
                    nxt = take_item();
                }
                uint32_t kv = 0, kvph = 1;
                uint32_t qc = 0;
                auto a_parity = [&](uint32_t b) { return b < 2 ? (((qc + 1 - b) >> 1) & 1) ^ 1 : kvph ^ (b - 2 < kv); };
                const CUtensorMap* tile_map = &prm.m[M_SCR_LD];
                asm volatile("" : "+l"(tile_map));
                {
                    bool need_g = true, more = true;
                    int pv_grp = -1, pv_row = 0;
                    int pv_shared = 0;
                    bool peer_longer = false;
                    int m = 0, kg = 0, vg = 0, asc = 0, nu = 0, uend = 0, ureq = -1, ufetch = 0;
#pragma unroll 1
                    for (int u = 0;; u++) {
                        if (u == ufetch) {
                            if (qc) nxt = take_item();
                            if (item_type(nxt) == T_ATTN) {
                                wait_inputs(nxt);
                                const uint32_t b = qc & 1, dst = sb + b * 32768, fb = bars + B_AFULL + 8 * b, row = item_row(nxt) * 128;
                                mbar_wait(bars + (qc == 0 ? B_GEMPTY : qc == 1 ? B_QFREE : B_AEMPTY + 8 * b), qc == 0 ? gph : qc == 1 ? 0 : a_parity(b));
                                warp_expect_tx(fb, 32768 + 512);
                                warp_tma_load(dst, tile_map, fb, 0, row, G_Q + item_col(nxt), false);
                                warp_tma_load(dst + 16384, tile_map, fb, 64, row, G_Q + item_col(nxt), false);
                                warp_bulk_load(bars + SM_GATE + b * 512, &g_gate[row], 512, fb);
                                qc++;
                            }
                        }
                        if (u == uend) {
                            if (!more) break;
                            more = item_type(nxt) == T_ATTN;
                            m = item_row(nxt); asc = item_asc(nxt);
                            kg = prm.kgroup[item_col(nxt) >> 1] + (item_col(nxt) & 1); vg = kg + (kg < G_V ? 32 : 8);
                            nu = more ? 2 * m + 2 : 0;
                            uend = nu + ((more ? m < 2 : pv_grp >= 0) ? 3 : 0);
                            ureq = 2 * max(m - 2 - (asc & m), 0);
                            ufetch = !more ? -1 : m ? 2 * m : uend;
                            u = -1;
                            continue;
                        }
                        int grp = pv_grp, row = pv_row;
                        int shared = pv_shared;
                        if (u >= nu) {
                            if (u == nu + 1) pv_grp = -1;
                            else if (peer_longer) { grp = -1; shared = 0; }
                            else continue;
                        } else {
                            const int j = asc ? u >> 1 : m - (u >> 1);
                            if (u & 1) {
                                pv_grp = vg; pv_row = j * 128; pv_shared = (m | 1) - j;
                                peer_longer = asc & ~m & 1;
                                if (u == nu - 1 && (m & 1) && item_type(nxt) == T_END) mbar_arrive_cluster_n_if(lane == 0, bars0 + B_WANT, 2);
                                if (grp < 0) continue;
                            } else {
                                if (u == ureq) request();
                                grp = kg; row = j * 128; shared = (m | 1) - j;
                            }
                        }
                        uint32_t fb = bars + B_AFULL + 16 + 8 * kv, mine = sb + SM_KV + kv * 32768 + prank * 16384;
                        int c_mine = prank * 64;
                        asm volatile("" : "+r"(mine), "+r"(fb), "+r"(row), "+r"(grp), "+r"(c_mine));
                        mbar_wait(need_g ? bars + B_GEMPTY + 8 + 8 * kv : fb + B_AEMPTY - B_AFULL, need_g ? gph : kvph);
                        warp_expect_tx(fb, grp < 0 ? 0 : 32768);
                        if (shared) {
                            warp_tma_load_pair(mine, tile_map, fb, c_mine, row, grp, shared == 1);
                        } else if (grp >= 0) {
                            warp_tma_load(mine, tile_map, fb, c_mine, row, grp, true);
                            warp_tma_load(mine + 16384 - prank * 32768, tile_map, fb, 64 - c_mine, row, grp, true);
                        } else {
                            mbar_arrive_cluster_n_if(lane < 2, map_cta(fb, lane & 1) + B_AEMPTY - B_AFULL, 8);
                        }
                        if (kv == 2) need_g = false;
                        if (++kv == 4) { kv = 0; kvph ^= 1; }
                    }
                }
                if (!qc) request();
                const int it = take_item();
                int nk = 0;
                if (item_type(it) == T_OUT) {
                    const int m = item_row(it), c = item_col(it), half = c & 1;
                    nk = 80;
                    for (unsigned n = 0; (inputs_seen(1, n) & 255) != 255;) {}
                    mbar_wait(bars + B_GEMPTY + 24, gph);
                    mbar_wait(bars + B_QFREE, 0);
                    mbar_wait(bars + B_AEMPTY + 8 * (qc & 1), a_parity(qc & 1));
#pragma unroll 1
                    for (uint32_t k = 0; k < 4; k++) {
                        const uint32_t sa = prm.ostep[half ? WIDE - 1 - k : k], dst = sb + k * GST_BYTES, fb = bars + B_GFULL + 8 * k;
                        const uint32_t b0 = k ? 1 + k : ~qc & 1, b1 = 2 + k - (k == 1);
                        mbar_wait(bars + B_AEMPTY + 8 * b0, a_parity(b0));
                        mbar_arrive_cluster_if(lane == 0 && !k, bars_peer + B_XFREE);
                        warp_expect_tx(fb, GST_BYTES);
                        warp_tma_load(dst, tile_map, fb, (sa & 1) * 64, m * 128, G_LOC - 32 + (sa >> 1), true);
                        mbar_wait(bars + (k ? B_AEMPTY + 8 * b1 : B_XFREE), k ? kvph ^ (b1 - 2 < kv) : 0);
                        warp_tma_load_pair(dst + 16384 + prank * 16384, &prm.m[M_WOB], fb, 0, (sa & 63) * 64, (c >> 1) * 4 + 2 * (half ^ prank), false);
                    }
                    gph ^= 1;
                    uint32_t seen = 0;
                    for (int k = 4; k < nk; k++) {
                        if (k == K_SPLIT) nk = 2 * TRIPLES + (take_item() & 127);
                        const int kn = k + 2 * TRIPLES - nk, first = kn >= 0 && !(kn & 1);
                        const int s = kn >= 0 ? WIDE + (3 * kn + 1) / 2 : half ? WIDE - 1 - k : k;
                        const uint32_t sa = prm.ostep[s], sa2 = prm.ostep[s + first], sw = prm.ostep[s - (kn >= 0 && !first ? prank : 0)];
                        const uint32_t need = 1u << (sa >> 1 & 31) | 1u << (sa2 >> 1 & 31);
                        for (unsigned n = 0; sa < 64 && (need & ~seen);) seen = inputs_seen(0, n);
                        const uint32_t st = k & 3;
                        uint32_t dst = sb + st * GST_BYTES, fb = bars + B_GFULL + 8 * st;
                        uint32_t dstb = dst + 16384 + (first ? 0 : prank * 16384), skipb = first && (kn >> 1 & 1) != prank;
                        int a0 = (sa & 1) * 64, a1 = m * 128, a2 = (sa >> 1) + (sa < 64 ? G_CTX : G_LOC - 32);
                        int b1 = (sw & 63) * 64, b2 = (c >> 1) * 4 + 2 * (kn >= 0 ? half : half ^ prank);
                        const CUtensorMap* mb = &prm.m[sw >= 64 ? M_WOB : M_WO];
                        asm volatile("" : "+r"(dst), "+r"(fb), "+r"(dstb), "+r"(skipb), "+r"(a0), "+r"(a1), "+r"(a2), "+r"(b1), "+r"(b2), "+l"(mb));
                        mbar_wait(bars + B_GEMPTY + 8 * st, gph);
                        warp_expect_tx(fb, GST_BYTES);
                        warp_tma_load(dst, tile_map, fb, a0, a1, a2, true);
                        if (!skipb) warp_tma_load_pair(dstb, mb, fb, 0, b1, b2, false);
                        if (first) warp_tma_load(dst + 32768, tile_map, fb, (sa2 & 1) * 64, a1, G_CTX + (sa2 >> 1), true);
                        if (k < K_SPLIT && lane == 0 && !prank)
                            asm volatile("st.relaxed.gpu.global.u32 [%0], %1;" :: "l"(&g_sync.step[0][0] + m * 4 + c), "r"(k) : "memory");
                        mbar_arrive_if(k == K_MEET && lane == 0, bars + B_MEET);
                        if ((uint32_t)(k - K_FETCH) < (3 * TRIPLES + 1) / 2) {
                            const uint32_t g = prm.ostep[79 - 2 * (k - K_FETCH)] >> 1;
                            warp_prefetch((const char*)g_scr + (uint32_t)((G_CTX + g) * (SEQ * 256) + m * 32768 + c * 4096), 4096);
                            warp_prefetch(prm.wo + (uint32_t)(g * 262144 + (m * 8 + c) * 2048), 2048);
                        }
                        if (st == 3) gph ^= 1;
                    }
                    for (unsigned n = 0; ~inputs_seen(0, n);) {}
                }
#pragma unroll 1
                for (uint32_t st = 0; st < 4; st++) { mbar_wait(bars + B_GEMPTY + 8 * st, gph ^ (st < (nk & 3))); mbar_wait(bars + B_AEMPTY + 16 + 8 * st, a_parity(2 + st)); }
                unsigned left = 0;
                if (lane == 0) asm volatile("atom.relaxed.gpu.global.add.u32 %0, [%1], 1;" : "=r"(left) : "l"(&g_sync.done) : "memory");
                if (__shfl_sync(0xffffffffu, left, 0) == NCTA - 1)
#pragma unroll 1
                    for (uint32_t i = lane * 8; i < sizeof(Sync); i += 256) *(unsigned long long*)((char*)&g_sync + i) = 0;
            }
        } else if (warp <= 2) {
            if (blockIdx.x < SEQ / 16) {
                const uint32_t r0 = 16 * blockIdx.x + 8 * (warp - 1), gbuf = bars + SM_GATE + 4 * (r0 & 15);
                float z[4];
                mbar_wait(bars + B_GFULL + 24, 0);
#pragma unroll 1
                for (uint32_t i = 0; i < 8; i++) {
                    const uint32_t off = (i & 3) * 512 + lane * 16;
                    const uint4* xp = (const uint4*)((const char*)prm.x + ((r0 + (i & 4)) * 2048 + off));
                    const uint4 wv = __ldg((const uint4*)((const char*)prm.gate_w + off));
                    uint4 xv[4];
#pragma unroll
                    for (int r = 0; r < 4; r++) { xv[r] = __ldg(xp + r * 128); if (!(i & 3)) z[r] = 0.f; }
                    const uint32_t ws[4] = {wv.x, wv.y, wv.z, wv.w};
#pragma unroll
                    for (int e = 0; e < 4; e++)
#pragma unroll
                        for (int r = 0; r < 4; r++) {
                            const uint32_t xs = e == 0 ? xv[r].x : e == 1 ? xv[r].y : e == 2 ? xv[r].z : xv[r].w;
                            z[r] = fmaf(__uint_as_float(xs << 16), __uint_as_float(ws[e] << 16), z[r]);
                            z[r] = fmaf(__uint_as_float(xs & 0xffff0000u), __uint_as_float(ws[e] & 0xffff0000u), z[r]);
                        }
                    if ((i & 3) == 3) {
#pragma unroll
                        for (int o = 16; o > 0; o >>= 1)
#pragma unroll
                            for (int r = 0; r < 4; r++) z[r] += __shfl_xor_sync(0xffffffffu, z[r], o);
                        const float zr = lane & 2 ? (lane & 1 ? z[3] : z[2]) : (lane & 1 ? z[1] : z[0]);
                        asm volatile("st.shared.f32 [%0], %1;" :: "r"(gbuf + 4 * ((i & 4) + (lane & 3))), "f"(rcp(1.f + ex2(zr * -1.4426950408889634f))) : "memory");
                    }
                }
                fence_proxy_async_smem();
                __syncwarp();
                warp_bulk_store((char*)g_gate + 4 * r0, gbuf, 32);
                bulk_commit();
                bulk_wait<0>();
                __syncwarp();
                if (lane == 0) red_add(&g_sync.count[3], 1);
            }
            __syncwarp();
            {
                const int w = warp - 1;
                uint32_t sph = 0, nann = 0;
                int unsent = 0, nunsent = 0;
                bool urgent = false;
                auto announce = [&]() {
                    if (!urgent) return;
                    bulk_wait<0>();
                    __syncwarp();
                    const uint32_t hb = bars + B_HALF + 8 * (nann & 3);
                    if (w == 0) {
                        mbar_arrive_if(lane == 0, hb);
                    } else {
                        mbar_wait(hb, (nann >> 2) & 1);
                        const uint32_t type = item_type(unsent), m = item_row(unsent), c = item_col(unsent);
                        const uint32_t word = type < T_B ? c >> 3 : type == T_B ? 2 : offsetof(Sync, ctx) / 8 + m;
                        const uint32_t bit = type < T_B ? 8 * (c & 7) : type == T_B ? 8 * (c & 3) : type == T_LOCAL ? 32 + c : c;
                        if (lane < nunsent) red_add((unsigned long long*)((char*)&g_sync + 8 * word), 1ull << bit);
                        __syncwarp();
                    }
                    nann++;
                    nunsent = 0; urgent = false;
                };
                int held = first_it, it;
                for (bool ended = false;; ended = item_type(it) == T_END) {
                    if (ended || !__all_sync(0xffffffffu, mbar_test(bars + B_IFULL + 8 * (qn % QDEPTH), (qn / QDEPTH) & 1))) announce();
                    it = __shfl_sync(0xffffffffu, next_item(lane == 0), 0);
                    if (ended) break;
                    const int itype = item_type(it);
                    const bool keep_held = itype == T_LOCAL;
#pragma unroll 1
                    for (int pass = held < 0 || keep_held; pass < 2; pass++) {
                        if (pass && (itype < T_OUT || itype == T_END)) break;
                        const int cur = pass ? it : held, type = item_type(cur), m = item_row(cur), c = item_col(cur);
                        const bool local = type == T_LOCAL;
                        int grp = pass ? (local ? G_LOC : G_CTX) + c : type * 32 + 2 * c;
                        const bool replaces = (type == T_K || type == T_V) && prm.kgroup[c] > G_B;
                        if (replaces) grp = prm.kgroup[c] + (type == T_V ? 8 : 0);
#pragma unroll 1
                        for (int i = 0; i < 4 - 2 * pass; i++) {
                            const int b = i & 1;
                            const bool alt = i >= 2 && itype >= T_ATTN;
                            const uint32_t full = bars + (alt ? B_ALT + 8 * w : B_SFULL + 16 * w + 8 * b), par = alt ? 0 : sph;
                            if (i == 3 - 2 * pass || replaces || !__all_sync(0xffffffffu, mbar_test(full, par))) announce();
                            if (replaces && !i)
                                for (unsigned n = 0; !__all_sync(0xffffffffu, (ld_acquire(&g_sync.used) >> (4 * (grp & 6)) & 255) == 32);) spin_guard(n);
                            mbar_wait(full, par);
                            if (local && w + b == 2 && lane == 0) asm volatile("red.relaxed.gpu.global.add.u32 [%0], %1;" :: "l"(&g_sync.used), "r"(1 << (4 * (c & 6))) : "memory");
                            fence_proxy_async_smem();
                            warp_tma_store(&prm.m[local ? M_SCR_LOQ : M_SCR_ST], sb + (alt ? 32768 : SM_STAGING) + w * 16384 + b * 8192,
                                         local ? b * 128 + w * 64 : b * 64, local ? m * 64 : m * 128 + w * 64, grp + (i >> 1), local || (type < T_B && c < FIRST_PAIR));
                            bulk_commit();
                            if (pass > b) continue;
                            bulk_wait_read<0>();
                            __syncwarp();
                            mbar_arrive_if(lane <= pass && !alt, bars + B_SEMPTY + 16 * w + 8 * (b - lane));
                            sph ^= b & !alt;
                        }
                        mbar_arrive_if(lane == 0 && !pass && itype >= T_ATTN, bars + B_QFREE);
                        if (lane == nunsent) unsent = cur;
                        nunsent++;
                        urgent = !local;
                    }
                    if (!keep_held) held = itype < T_OUT ? it : -1;
                }
                if (item_type(it) == T_OUT) {
                    if (w) {
                        mbar_wait(bars + B_MEET, 0);
                        asm volatile("fence.proxy.async.global;\nfence.acq_rel.gpu;" ::: "memory");
                        mbar_arrive_cluster_if(lane == 0, bars0 + B_WANT);
                    }
                    next_item(lane == 0);
#pragma unroll 1
                    for (int i = 0; i < 4; i++) {
                        const int b = i & 1;
                        mbar_wait(bars + B_SFULL + 16 * w + 8 * b, sph ^ (i >> 1));
                        fence_proxy_async_smem();
                        warp_tma_add(&prm.m[M_OUT], sb + SM_STAGING + w * 16384 + b * 8192, (item_col(it) ^ (i < 2)) * 128 + b * 64, item_row(it) * 128 + w * 64, 0);
                        bulk_commit();
                        if (b) {
                            bulk_wait_read<0>();
                            __syncwarp();
                            mbar_arrive_if(lane < 2, bars + B_SEMPTY + 16 * w + 8 * lane);
                        }
                    }
                }
            }
        } else {
            if (elect_one()) {
                uint32_t ordy = 0;
                unsigned long long cnt_lo = 0, cnt_hi = 0;
                int late = 0;
                auto refresh = [&]() {
                    if (!late && cnt_lo == 0x30303030 && cnt_hi == SEQ / 8) late = 1;
                    asm volatile("ld.acquire.gpu.global.v2.u64 {%0, %1}, [%2];" : "=l"(cnt_lo), "=l"(cnt_hi) : "l"(late ? &g_sync.count[0] : &g_sync.count[2]) : "memory");
                };
                auto inputs_ready = [&](int it) -> bool {
                    const int c = item_col(it);
                    if (item_type(it) == T_ATTN) return late && ((c < 16 ? cnt_lo : cnt_hi) >> (4 * (c & 14)) & 255) == 48;
                    return late || (cnt_hi == SEQ / 8 && (cnt_lo >> (4 * (c & 6)) & 255) == 48);
                };
                auto publish = [&](int it, int step) {
                    const uint32_t slot = qn % QDEPTH;
                    mbar_wait(bars + B_IEMPTY + 8 * slot, ((qn / QDEPTH) & 1) ^ 1);
                    for (uint32_t r = 0; r < 2; r++) {
                        const uint32_t rb = map_cta(bars, r);
                        asm volatile("mbarrier.arrive.expect_tx.shared::cluster.b64 _, [%0], 4;" :: "r"(rb + B_IFULL + 8 * slot) : "memory");
                        asm volatile("st.async.shared::cluster.mbarrier::complete_tx::bytes.u32 [%0], %1, [%2];"
                                     :: "r"(rb + SM_QUEUE + 4 * slot), "r"(it + r * step), "r"(rb + B_IFULL + 8 * slot) : "memory");
                    }
                    qn++;
                };
                int asc = 1;
                int it;
                do {
                    if (rank == 0) {
                        mbar_wait(bars + B_WANT, qn & 1);
                        int pit = prm.plan[pair < 64 ? pair & 7 : pair - 56][min(qn + 1, 15u)];
                        unsigned i;
                        const bool planned = item_type(pit) != T_END;
                        if (!planned) asm volatile("atom.relaxed.gpu.global.add.u32 %0, [%1], 1;" : "=r"(i) : "l"(&g_sync.next) : "memory");
                        if (cnt_lo != 0x3030303030303030ull || cnt_hi != cnt_lo) refresh();
                        if (planned) pit += (pair >> 3 & 7) << (item_type(pit) == T_LOCAL);
                        else if (i < NITEMS) pit = prm.items[i];
                        const int type = item_type(pit);
                        int step = type == T_LOCAL ? 16 : 1;
                        it = pit + (pit & (step == 1 ? 15 : 0x1f0));
                        if (type == T_ATTN) {
                            if (!asc) { it += 1; step = -1; }
                            it |= asc << 9;
                        }
                        asc = type != T_ATTN || item_row(pit) == 0 || !asc;
                        if (inputs_ready(it)) it |= ITEM_READY;
                        publish(it, step);
                    } else {
                        it = next_item(true);
                    }
                    if ((item_type(it) == T_ATTN || item_type(it) == T_LOCAL) && !(it & ITEM_READY)) {
                        unsigned n = 0;
                        while (!inputs_ready(it)) { refresh(); spin_guard(n); }
                        asm volatile("st.release.cta.shared.u32 [%0], %1;" :: "r"(bars + SM_ORDY + 4), "r"(ordy += 256) : "memory");
                    }
                } while (item_type(it) != T_END);
                if (rank == 0) {
                    mbar_wait(bars + B_WANT, qn & 1);
                    const unsigned i = atomicAdd(&g_sync.next_out, 1u), t = i < 32 ? 31 - i : i - 32;
                    it = i < 64 ? T_OUT << 13 | ((t & 3) * 2 + (i >> 5)) << 4 | (t >> 2) * 2 : T_END << 13;
                    publish(it, 1);
                } else {
                    it = next_item(true);
                }
                if (item_type(it) == T_OUT) {
                    const uint32_t m = item_row(it), half = item_col(it) & 1, tile = m * 2 + (item_col(it) >> 1);
                    unsigned* split = (unsigned*)((char*)g_sync.split + 4 * tile);
                    unsigned long long rdy = 0;
                    int state = rank ? 2 : 0;
                    for (unsigned n = 0; rdy != 0xffffffffffull || state < 2; spin_guard(n)) {
                        if (rdy != 0xffffffffffull) {
                            rdy = ld_acquire((const unsigned long long*)((char*)g_sync.ctx + 8 * m));
                            asm volatile("st.release.cta.shared.u64 [%0], %1;" :: "r"(bars + SM_ORDY), "l"(rdy) : "memory");
                        }
                        unsigned steps = 0;
                        if (state == 1) {
                            steps = ld_acquire(split);
                        } else if (state == 0 && mbar_test(bars + B_WANT, qn & 1)) {
                            state = 1;
                            unsigned seen;
                            asm volatile("atom.acq_rel.gpu.global.exch.b32 %0, [%1], 1;" : "=r"(seen) : "l"(split) : "memory");
                            if (seen) {
                                const unsigned long long v = ld_acquire((const unsigned long long*)((char*)g_sync.step + 8 * tile));
                                const int d = (int)(v >> 32) - (int)v;
                                steps = (WIDE + min(max(half ? d : -d, -12), 12)) >> 1;
                                atomicExch(split, WIDE - steps);
                            }
                        }
                        if (steps > 1) { publish(T_END << 13 | steps, 0); state = 2; }
                    }
                    if (rank) next_item(true);
                }
#pragma unroll 1
                for (uint32_t n = qn; n < qn + QDEPTH && rank == 0; n++) mbar_wait(bars + B_IEMPTY + 8 * (n % QDEPTH), ((n / QDEPTH) & 1) ^ 1);
            }
        }
    } else {
        reg_inc<232>();
        const int wg = (warp >> 2) - 1, wq = warp & 3;
        uint32_t gph = 0;
        uint32_t kvn = 0;
        const uint32_t dA = make_desc(sb + wg * 8192, 16);
        uint32_t ti = 0;
        uint32_t sph = 1;
        const uint32_t stg = sb + SM_STAGING + wg * 16384;
        const uint32_t stg_lane = stg + (wq * 16 + (lane & 15)) * 128 + (((lane >> 4) ^ (lane & 7)) << 4);
        auto write_blocks = [&](auto n, uint32_t off, const uint32_t* v) {
            uint32_t a = stg_lane;
            asm volatile("" : "+r"(a));
            a += off;
#pragma unroll
            for (int j = 0; j < decltype(n)::value; j++)
                stmatrix_x4((a ^ (32 * (j & 3))) + (j >> 2) * 8192, v[4 * j], v[4 * j + 1], v[4 * j + 2], v[4 * j + 3]);
        };
        auto release = [&](uint32_t bar) { mbar_arrive_if(lane == 0, bars + bar); };
        const uint32_t bars_lane = map_cta(bars, lane & 1);
        auto release_stage = [&](uint32_t st) { mbar_arrive_cluster_if(lane < 2, bars_lane + B_GEMPTY + 8 * st); };
        auto take_item = [&]() -> int {
            return __shfl_sync(0xffffffffu, next_item(lane == 0, false), 0);
        };
        auto stage_acquire = [&](int b) { mbar_spin(bars + B_SEMPTY + 16 * wg + 8 * b, sph); };
        auto stage_publish = [&](int b) {
            __syncwarp();
            release(B_SFULL + 16 * wg + 8 * b);
        };
        auto stage_chunk = [&](int b, const uint32_t* v) {
            stage_acquire(b);
            write_blocks(std::integral_constant<int, 4>(), b * 8192, v);
            stage_publish(b);
            if (b) sph ^= 1;
        };
        auto publish_pair = [&]() {
            __syncwarp();
            mbar_arrive_if(lane < 2, bars + B_SFULL + 16 * wg + 8 * lane);
            sph ^= 1;
        };
        auto gemm_step = [&](float (&acc)[128], uint32_t dB, int& k, bool order) {
            const uint32_t st = k & 3;
            wgmma_wait<0>();
            release_stage((k - 1) & 3);
            mbar_spin(bars + B_GFULL + 8 * st, gph);
            const uint64_t da = full_desc(dA + st * (GST_BYTES >> 4)), db = full_desc(dB + st * (GST_BYTES >> 4));
            if (order && wg) bar_sync(3, 256);
            wgmma_fence();
#pragma unroll
            for (int kk = 0; kk < 4; kk++) wgmma_ss_n256_tb(acc, da + 2 * kk, db + 128 * kk, 1);
            wgmma_commit();
            if (order && !wg) bar_arrive(3, 256);
            gph ^= st == 3;
            k++;
        };
        if (wg == 1) bar_arrive(1, 256);
        int it = first_it;
        float s[64];
        const uint32_t dK = make_desc(sb + SM_KV, 16);
        auto kv_wait = [&](uint32_t n) { mbar_spin(bars + B_AFULL + 16 + 8 * (n & 3), (n >> 2) & 1); };
        auto first_scores = [&](bool valid) {
            if (valid) { mbar_spin(bars + B_AFULL + 8 * (ti & 1), (ti >> 1) & 1); kv_wait(kvn); }
            bar_sync(1 + wg, 256);
            qk_gemm(s, dA + (ti & 1) * 2048, dK + (kvn & 3) * 2048, false);
        };
        bool issued;
        {
            {
                float acc[128];
                uint32_t pk[64];
                bool pending = false;
                int held = T_END;
                auto scale_q = [&](int j0) {
                    if (held != T_Q) return;
#pragma unroll
                    for (int j = j0; j < j0 + 16; j++)
                        asm("{\n.reg .b32 t;\nmul.rn.bf16x2 t, %0, %2;\nfma.rn.bf16x2 %0, %0, %1, t;\n}\n" : "+r"(pk[j]) : "r"(0x3e033e03u), "r"(0xb9d8b9d8u));
                };
                zero_regs(pk);
                const uint32_t dB = make_desc(sb + 16384, 8192);
                do {
                    if (item_type(it) == T_LOCAL) {
                        int ln = lane;
                        asm volatile("" : "+r"(ln));
                        const int g = ln >> 2, t = ln & 3, par = wq & 1;
                        const uint32_t hc = (wq >> 1) * 4, pl = sb + (par * 2 + wg) * LOC_PLANE;
                        const uint32_t a16 = (ln & 15) * 128 + (((hc + (ln >> 4)) ^ (ln & 7)) << 4), a8 = (ln & 7) * 128 + (((hc + (ln >> 3)) ^ (ln & 7)) << 4);
                        const bool first0 = 2 * t > g, first1 = 2 * t + 1 > g;
                        const uint32_t fmask = (first0 ? 0xffffu : 0u) | (first1 ? 0xffff0000u : 0u);
                        const bool edge = item_row(it) == 0;
                        uint32_t q[4][2][4], kf[9][4], vf[9][4];
                        float w[8];
                        mbar_spin(bars + B_GFULL, gph);
#pragma unroll
                        for (int u = 0; u < 4; u++) { ldsm_x4(q[u][0], pl + u * 2048 + a16); ldsm_x4(q[u][1], pl + u * 2048 + (a16 ^ 32)); }
#pragma unroll
                        for (int j = 0; j < 8; j++) w[j] = lds_f32(sb + 4 * LOC_PLANE + 4 * (2 * g + par) + 64 * j);
                        __syncwarp();
                        release_stage(0);
                        mbar_spin(bars + B_GFULL + 8, gph);
#pragma unroll
                        for (int n = 0; n < 9; n++) ldsm_x4(kf[n], pl + GST_BYTES + n * 1024 + a8);
                        __syncwarp();
                        release_stage(1);
                        float s[8][2];
#pragma unroll
                        for (int u = 0; u < 4; u++) {
                            float d[3][4];
#pragma unroll
                            for (int nt = 0; nt < 3; nt++) {
                                mma_k16_init(d[nt], q[u][0], kf[2 * u + nt][0], kf[2 * u + nt][1]);
                                mma_k16(d[nt], q[u][1], kf[2 * u + nt][2], kf[2 * u + nt][3]);
                            }
                            if (u == 0 && edge) { d[0][0] = -INFINITY; d[0][1] = -INFINITY; }
                            s[2 * u][0] = first0 ? d[0][0] : d[1][0]; s[2 * u][1] = first1 ? d[0][1] : d[1][1];
                            s[2 * u + 1][0] = first0 ? d[1][2] : d[2][2]; s[2 * u + 1][1] = first1 ? d[1][3] : d[2][3];
                        }
                        mbar_spin(bars + B_GFULL + 16, gph);
#pragma unroll
                        for (int u = 0; u < 4; u++) { ldsm_x4_t(vf[2 * u], pl + 2 * GST_BYTES + u * 2048 + a16); ldsm_x4_t(vf[2 * u + 1], pl + 2 * GST_BYTES + u * 2048 + (a16 ^ 32)); }
                        ldsm_x4_t(vf[8], pl + 2 * GST_BYTES + 8192 + a8);
                        __syncwarp();
                        release_stage(2);
                        float x[8];
#pragma unroll
                        for (int j = 0; j < 8; j++) x[j] = fmaxf(s[j][0], s[j][1]);
#pragma unroll
                        for (int o = 1; o < 4; o *= 2)
#pragma unroll
                            for (int j = 0; j < 8; j++) x[j] = fmaxf(x[j], __shfl_xor_sync(0xffffffffu, x[j], o));
#pragma unroll
                        for (int j = 0; j < 8; j++) {
                            const float n = x[j] * -LOC_SCALE;
                            s[j][0] = ex2(fmaf(s[j][0], LOC_SCALE, n)); s[j][1] = ex2(fmaf(s[j][1], LOC_SCALE, n));
                            x[j] = s[j][0] + s[j][1];
                        }
#pragma unroll
                        for (int o = 1; o < 4; o *= 2)
#pragma unroll
                            for (int j = 0; j < 8; j++) x[j] += __shfl_xor_sync(0xffffffffu, x[j], o);
                        mbar_spin(bars + B_GFULL + 24, gph);
                        release_stage(3);
                        it = take_item();
                        uint32_t ob[4][8];
#pragma unroll
                        for (int u = 0; u < 4; u++) {
                            const float r0 = rcp(x[2 * u]), r1 = rcp(x[2 * u + 1]), f0 = fmaf(-w[2 * u], r0, r0), f1 = fmaf(-w[2 * u + 1], r1, r1);
                            const uint32_t p0 = pack_bf16(s[2 * u][0] * f0, s[2 * u][1] * f0), p1 = pack_bf16(s[2 * u + 1][0] * f1, s[2 * u + 1][1] * f1);
                            const uint32_t pa[4] = {p0 & fmask, 0, p0 & ~fmask, p1 & fmask};
#pragma unroll
                            for (int c = 0; c < 4; c++) {
                                float ol[4];
                                mma_k16_init(ol, pa, vf[2 * u + (c >> 1)][2 * (c & 1)], vf[2 * u + (c >> 1)][2 * (c & 1) + 1]);
                                mma_k8(ol, 0, p1 & ~fmask, u < 3 ? vf[2 * u + 2 + (c >> 1)][2 * (c & 1)] : vf[8][c]);
                                ob[u][2 * c] = pack_bf16(ol[0], ol[1]);
                                ob[u][2 * c + 1] = pack_bf16(ol[2], ol[3]);
                            }
                        }
                        stage_acquire(0); stage_acquire(1);
#pragma unroll
                        for (int u = 0; u < 4; u++) {
                            stmatrix_x4(stg + par * 8192 + u * 2048 + a16, ob[u][0], ob[u][1], ob[u][2], ob[u][3]);
                            stmatrix_x4(stg + par * 8192 + u * 2048 + (a16 ^ 32), ob[u][4], ob[u][5], ob[u][6], ob[u][7]);
                        }
                        publish_pair();
                        bar_sync(4, 256);
                        gph ^= 1;
                        continue;
                    }
                    mbar_spin(bars + B_GFULL, gph);
                    bool more;
                    do {
                        wgmma_fence();
                        wgmma_ss_n256_tb_init(acc, full_desc(dA), full_desc(dB));
#pragma unroll
                        for (int kk = 1; kk < 4; kk++) wgmma_ss_n256_tb(acc, full_desc(dA) + 2 * kk, full_desc(dB) + 128 * kk, 1);
                        wgmma_commit();
                        const int type = item_type(it), nk = type == T_K || type == T_V ? 8 : 16;
                        int k = 1;
                        do {
                            if (pending) {
                                if (k == 1) { scale_q(0); stage_chunk(0, pk); }
                                else if (k == 3) { scale_q(16); stage_chunk(1, pk + 16); }
                                else if (k == 5) { scale_q(32); stage_chunk(0, pk + 32); }
                                else if (k == 6) { scale_q(48); stage_chunk(1, pk + 48); }
                            }
                            if (k == nk - 1) it = take_item();
                            gemm_step(acc, dB, k, item_type(it) > T_LOCAL);
                        } while (k < nk);
                        held = type;
                        more = item_type(it) < T_LOCAL;
                        if (more) mbar_spin(bars + B_GFULL, gph);
                        wgmma_wait<0>();
                        fence_regs(acc);
                        release_stage(3);
#pragma unroll
                        for (int j = 0; j < 64; j++) pk[j] = pack_bf16(acc[2 * j], acc[2 * j + 1]);
                        pending = true;
                    } while (more);
                } while (item_type(it) <= T_LOCAL);
                issued = item_type(it) == T_ATTN && (it & ITEM_READY);
                first_scores(issued);
                stage_acquire(0); stage_acquire(1);
                mbar_spin(bars + B_GEMPTY + 8, gph ^ 1);
                write_blocks(std::integral_constant<int, 8>(), 0, pk);
                write_blocks(std::integral_constant<int, 8>(), 32768 - SM_STAGING, pk + 32);
                publish_pair();
                release(B_ALT + 8 * wg);
                bar_arrive(2 - wg, 256);
                wgmma_wait<0>();
                fence_regs(s);
                if (item_type(it) == T_END) it = take_item();
            }
            while (item_type(it) == T_ATTN) {
                if (!issued) { first_scores(true); bar_arrive(2 - wg, 256); wgmma_wait<0>(); fence_regs(s); }
                issued = false;
                float o[64];
                uint32_t pa[32], pb[32];
                float n0 = 0.f, n1 = 0.f;
                int shifted = 0;
                float l0 = 0.f, l1 = 0.f, f0 = 0.f, f1 = 0.f, g0, g1;
                uint32_t has_pv = 0;
                int first = 0;
                int pending = 0;
                const uint32_t dV = make_desc(sb + SM_KV, 16384);
                const uint32_t lane_off = bars_lane - bars + B_AEMPTY - B_AFULL;
                int cur = it;
                uint32_t dQ = dA + (ti & 1) * 2048;
                const int row = wq * 16 + (lane >> 2);
                const float thr = row - (lane & 3) * 2;
                int diag = item_row(cur) == 0 || !item_asc(cur);
                int short_row = diag && wg == 0;
                int peek = -1;
                auto kv_release = [&](uint32_t n) { mbar_arrive_cluster_if(lane < 2, bars_lane + B_AEMPTY + 16 + 8 * (n & 3)); };
                struct Slot { uint32_t bar, par, off; } slot[4];
#pragma unroll
                for (uint32_t i = 0; i < 4; i++) {
                    const uint32_t n = kvn + 1 + (i ^ 2);
                    slot[i].bar = bars + B_AFULL + 16 + 8 * (n & 3); slot[i].par = (n >> 2) & 1; slot[i].off = (n & 3) * 2048;
                }
                kvn++;
                auto next_gate = [&]() {
                    const uint32_t a = bars + SM_GATE + (ti & 1) * 512 + wg * 256 + 4 * row;
                    g0 = lds_f32(a); g1 = lds_f32(a + 32);
                    ti++;
                };
                next_gate();
                auto scale_o = [&]() {
#pragma unroll
                    for (int j = 0; j < 16; j++) { o[4 * j] *= f0; o[4 * j + 1] *= f0; o[4 * j + 2] *= f1; o[4 * j + 3] *= f1; }
                };
                auto pack_o = [&](uint32_t (&v)[32]) {
#pragma unroll
                    for (int j = 0; j < 32; j++) v[j] = pack_bf16(o[2 * j], o[2 * j + 1]);
                };
                auto scales = [&]() { f0 = g0 * rcp(quad_sum(l0)); f1 = g1 * rcp(quad_sum(l1)); };
                auto issue = [&](auto even, uint32_t (&pin)[32], uint32_t (&pout)[32], bool fresh, bool last) {
                    constexpr bool EVEN = decltype(even)::value;
                    Slot& sk = slot[EVEN ? 0 : 2];
                    Slot& sv = slot[EVEN ? 1 : 3];
                    kvn += 2;
                    mbar_spin(sk.bar, sk.par);
                    bar_sync(1 + wg, 256);
                    qk_gemm(s, dQ, dK + sk.off, wg == 0 && (item_asc(cur) ? last : fresh));
                    if (EVEN && fresh) {
                        scales();
                        next_gate();
                        n0 = 0.f; n1 = 0.f; l0 = 0.f; l1 = 0.f;
                        shifted = 0;
                        stage_acquire(0); stage_acquire(1);
                    }
                    if (!EVEN && pending) {
                        pack_o(pout);
                        write_blocks(std::integral_constant<int, 4>(), 0, pout);
                    }
                    if (last)
                        asm volatile("{\n.reg .pred P, Q;\n"
                                     "mbarrier.test_wait.parity.shared::cta.b64 Q, [%1], %2;\n"
                                     "mbarrier.test_wait.parity.shared::cta.b64 P, [%3], %4;\n"
                                     "ld.shared.u32 %0, [%5];\n"
                                     "@!Q or.b32 %0, %0, 0x10000;\n"
                                     "@!P mov.u32 %0, -1;\n}\n"
                                     : "=r"(peek) : "r"(bars + B_AFULL + 8 * (ti & 1)), "r"((ti >> 1) & 1), "r"(bars + B_IFULL + 8 * (qn % QDEPTH)),
                                       "r"((qn / QDEPTH) & 1), "r"(bars + SM_QUEUE + 4 * (qn % QDEPTH)) : "memory");
                    const bool half = short_row;
                    diag = item_asc(cur) ? last : fresh;
                    short_row = diag && wg == 0;
                    asm volatile("" : "+r"(diag));
                    mbar_spin(sv.bar, sv.par);
                    pv_gemm(o, pin, dV + sv.off, EVEN || !first, half);
                    bar_arrive(2 - wg, 256);
                    if (!EVEN && pending) {
                        write_blocks(std::integral_constant<int, 4>(), 8192, pout + 16);
                        publish_pair();
                    }
                    sk.par ^= 1; sv.par ^= 1;
                    wgmma_wait<1>();
                    fence_regs(s);
                    mbar_arrive_cluster_if(lane < 2, sk.bar + lane_off);
                    mbar_arrive_if(lane == 0 && last, bars + B_AEMPTY + 8 * ((ti - 1) & 1));
                };
                auto softmax = [&](auto even, uint32_t (&pin)[32], uint32_t (&pout)[32], bool fresh) {
                    constexpr bool EVEN = decltype(even)::value;
                    Slot& sv = slot[EVEN ? 1 : 3];
                    float r0, r1, x0 = n0, x1 = n1;
#pragma unroll 1
                    for (int mask = diag, redone = 0;; mask = 0, redone = 1) {
                        if (mask | shifted) {
                            if (mask) causal_mask(s, thr, wg);
                            if (shifted) shift_rows(s, x0, x1);
                            if (short_row) { exp_pack<8>(pout, s, r0, r1); goto check; }
                        }
                        exp_pack<16>(pout, s, r0, r1);
                    check:
                        if (!__any_sync(0xffffffffu, fmaxf(r0, r1) >= SUM_LIMIT || (EVEN && fresh && !(lane & 3) && !(fminf(s[0], s[2]) >= -REF_RANGE))) || redone) break;
                        if (short_row) {
#pragma unroll
                            for (int j = 32; j < 64; j++) s[j] = MASKED;
                        }
                        row_max(s, x0, x1);
                        if (!(EVEN && fresh)) { x0 = fmaxf(x0, 0.f); x1 = fmaxf(x1, 0.f); }
                        float a0 = ex2(-x0), a1 = ex2(-x1);
                        n0 += x0; n1 += x1;
                        shifted = 1;
                        if (EVEN && fresh) { a0 = 1.f; a1 = 1.f; }
                        l0 *= a0; l1 *= a1;
                        wgmma_wait<0>();
                        fence_regs(o);
#pragma unroll
                        for (int q = 0; q < 16; q++) { o[4 * q] *= a0; o[4 * q + 1] *= a0; o[4 * q + 2] *= a1; o[4 * q + 3] *= a1; }
                    }
                    l0 += r0; l1 += r1;
                    wgmma_wait<0>();
                    fence_regs(o);
                    fence_regs(pin);
                    mbar_arrive_cluster_if(lane < 2, sv.bar + lane_off);
                };
                auto copy_p = [&]() {
#pragma unroll
                    for (int j = 0; j < 32; j++) pa[j] = __float_as_uint(__uint_as_float(pb[j]) + __uint_as_float(prm.zero));
                };
                int rem = 0;
                mbar_arrive_if(lane == 0 && item_row(cur) == 0, bars + B_AEMPTY + 8 * ((ti - 1) & 1));
                zero_regs(pa);
                wgmma_fence();
                wgmma_ss_n128_init(o, full_desc(dA), full_desc(dK));
                wgmma_commit();
                while (true) {
                    const bool fresh = rem == 0;
                    softmax(std::true_type(), pa, pb, fresh);
                    first = fresh;
                    if (fresh) {
                        pending = has_pv; has_pv = 1;
                        if (pending) scale_o();
                        rem = item_row(cur) + 1;
                    }
                    if (--rem == 0) {
                        copy_p();
                        const Slot t0 = slot[0], t1 = slot[1];
                        slot[0] = slot[2]; slot[1] = slot[3]; slot[2] = t0; slot[3] = t1;
                    } else {
                        issue(std::false_type(), pb, pa, false, rem == 1);
                        softmax(std::false_type(), pb, pa, false);
                        pending = 0; first = 0;
                        rem--;
                    }
                    if (rem == 0) {
                        const int seen = peek;
                        if (seen >= 0) {
                            mbar_arrive_cluster_if(lane == 0, bars0 + B_IEMPTY + 8 * (qn % QDEPTH));
                            qn++;
                            it = seen & 0xffff;
                        } else {
                            it = take_item();
                        }
                        if (item_row(cur) < 2 || item_type(it) != T_ATTN) break;
                        if (seen & 0x10000) mbar_spin(bars + B_AFULL + 8 * (ti & 1), (ti >> 1) & 1);
                        cur = it;
                        dQ = dA + (ti & 1) * 2048;
                    }
                    issue(std::true_type(), pa, pb, rem == 0, rem ? rem == 1 : item_row(cur) == 0);
                }
                const uint32_t skip = item_asc(cur) & ~item_row(cur) & 1;
                kvn += skip;
                const bool end = item_type(it) == T_END;
#pragma unroll 1
                for (int pass = pending ? 0 : 1; pass < 2; pass++) {
                    if (pass) {
                        kv_wait(kvn);
                        pv_gemm(o, pa, dV + (kvn & 3) * 2048, !first, short_row);
                        scales();
                        stage_acquire(0); stage_acquire(1);
                        if (end) it = take_item();
                        wgmma_wait<0>();
                        fence_regs(o);
                        kv_release(kvn);
                        kvn += 1 + skip;
                        scale_o();
                    }
                    pack_o(pb);
                    write_blocks(std::integral_constant<int, 8>(), 0, pb);
                    publish_pair();
                }
            }
        }
        if (item_type(it) == T_OUT) {
            float acc[128];
            const uint32_t dB = make_desc(sb + 16384, 8192);
            mbar_spin(bars + B_GFULL, gph);
            wgmma_fence();
            wgmma_ss_n256_tb_init(acc, full_desc(dA), full_desc(dB));
#pragma unroll
            for (int kk = 1; kk < 4; kk++) wgmma_ss_n256_tb(acc, full_desc(dA) + 2 * kk, full_desc(dB) + 128 * kk, 1);
            wgmma_commit();
            uint32_t ln;
            asm volatile("mov.u32 %0, %%laneid;" : "=r"(ln));
            char* const mine = (char*)prm.out + (uint32_t)((item_row(it) * 128 + wg * 64 + wq * 16 + (ln >> 4)) * 2048 + item_col(it) * 256 + (ln & 15) * 16);
            int k = 1, nk = 80;
            do {
                if ((uint32_t)(k - (K_MEET - 12)) < 8) *(uint4*)(mine + (uint32_t)(k - (K_MEET - 12)) * 4096) = make_uint4(0, 0, 0, 0);
                __syncwarp();
                if (k == K_SPLIT) nk = take_item() & 127;
                gemm_step(acc, dB, k, false);
            } while (k < nk);
            float lo[64];
            auto triple = [&](auto first) {
                const uint32_t s0 = k & 3, s1 = (k + 1) & 3, o0 = s0 * (GST_BYTES >> 4), o1 = s1 * (GST_BYTES >> 4);
                wgmma_wait<0>();
                mbar_arrive_cluster_if(ln < (decltype(first)::value ? 2 : 4), bars_lane + B_GEMPTY + 8 * ((k - 1 - (ln >> 1)) & 3));
                mbar_spin(bars + B_GFULL + 8 * s0, gph);
                gph ^= s0 == 3;
                wgmma_fence();
#pragma unroll
                for (int kk = 0; kk < 4; kk++) {
                    if (decltype(first)::value && kk == 0) wgmma_ss_n128_tb_init(lo, full_desc(dA + o0), full_desc(dB + o0));
                    else wgmma_ss_n128_tb(lo, full_desc(dA + o0) + 2 * kk, full_desc(dB + o0) + 128 * kk, 1);
                }
                mbar_spin(bars + B_GFULL + 8 * s1, gph);
                gph ^= s1 == 3;
                wgmma_fence();
#pragma unroll
                for (int kk = 0; kk < 4; kk++) wgmma_ss_n128_tb(lo, full_desc(dA + o0 + 2048) + 2 * kk, full_desc(dB + o1 + 1024) + 128 * kk, 1);
#pragma unroll
                for (int kk = 0; kk < 4; kk++) wgmma_ss_n128_tb(lo, full_desc(dA + o1) + 2 * kk, full_desc(dB + o1) + 128 * kk, 1);
                wgmma_commit();
                k += 2;
            };
            triple(std::true_type());
            fence_regs(acc);
            uint32_t pk[32];
#pragma unroll
            for (int j = 0; j < 32; j++) pk[j] = pack_bf16(acc[64 + 2 * j], acc[65 + 2 * j]);
            stage_acquire(0); stage_acquire(1);
            write_blocks(std::integral_constant<int, 8>(), 0, pk);
            publish_pair();
            triple(std::false_type());
            stage_acquire(0); stage_acquire(1);
            wgmma_wait<0>();
            fence_regs(lo);
            mbar_arrive_cluster_if(ln < 4, bars_lane + B_GEMPTY + 8 * ((k - 1 - (ln >> 1)) & 3));
#pragma unroll
            for (int b = 0; b < 2; b++) {
#pragma unroll
                for (int j = 16 * b; j < 16 * b + 16; j++) pk[j] = pack_bf16(acc[2 * j] + lo[2 * j], acc[2 * j + 1] + lo[2 * j + 1]);
                write_blocks(std::integral_constant<int, 4>(), b * 8192, pk + 16 * b);
                stage_publish(b);
            }
        }
    }
}

typedef CUresult (*EncodeFn)(CUtensorMap*, CUtensorMapDataType, cuuint32_t, void*, const cuuint64_t*, const cuuint64_t*,
                             const cuuint32_t*, const cuuint32_t*, CUtensorMapInterleave, CUtensorMapSwizzle,
                             CUtensorMapL2promotion, CUtensorMapFloatOOBfill);

void encode3(EncodeFn fn, CUtensorMap* m, const void* ptr, uint64_t d0, uint64_t d1, uint64_t d2, uint64_t s1, uint64_t s2,
             uint32_t b0, uint32_t b1, uint32_t b2) {
    cuuint64_t dims[3] = {d0, d1, d2};
    cuuint64_t strides[2] = {s1, s2};
    cuuint32_t box[3] = {b0, b1, b2};
    cuuint32_t es[3] = {1, 1, 1};
    fn(m, CU_TENSOR_MAP_DATA_TYPE_BFLOAT16, 3, const_cast<void*>(ptr), dims, strides, box, es, CU_TENSOR_MAP_INTERLEAVE_NONE,
       CU_TENSOR_MAP_SWIZZLE_128B, b2 > 1 ? CU_TENSOR_MAP_L2_PROMOTION_L2_256B : CU_TENSOR_MAP_L2_PROMOTION_NONE, CU_TENSOR_MAP_FLOAT_OOB_FILL_NONE);
}
void map_act(EncodeFn fn, CUtensorMap* m, const void* p, int rows, int cols, int box_rows) {
    encode3(fn, m, p, cols, rows, 1, (uint64_t)cols * 2, (uint64_t)cols * rows * 2, 64, box_rows, 1);
}
void map_wgt(EncodeFn fn, CUtensorMap* m, const void* p, int K, int N) {
    encode3(fn, m, p, 64, K, N / 64, (uint64_t)N * 2, 128, 64, 64, 2);
}

void build_schedule(Params& p) {
    int n = 0;
    auto add = [&](int type, int col, int row) { p.items[n++] = (uint16_t)(type << 13 | col << 4 | row); };
    int beta = 32, tail = 32, late = 6, early = 4, epos = 60;
    int order[16] = {6, 7, 8, 9, 10, 11, 12, 13, 14, 15, 5, 4, 3, 2, 1, 0};
    const char* plans = "xxxxxc,xxlcccccc,xxxxxc,xxlcccccc,xxllcclxxc,xxxllxxc,xxxlccccc,xxcccccc";
    const char* pos[8];
    int len[8] = {}, start[8] = {};
    for (int s = 0; s < 8; s++) { pos[s] = plans; while (*plans && *plans++ != ',') {} }
    for (int i = 0; i < 160; i++) p.plan[i / 16][i % 16] = T_END << 13;
    int lend[4] = {}, nset = 0, margin = 12;
    for (int c = 0; c < 16; c++) p.kgroup[c] = (uint8_t)(G_K + 2 * c);
    for (int nx = 0, nc = 3, nl = 0; nx + nc + nl < 28 + 32 + 8;) {
        int s = -1;
        for (int i = 0; i < 8; i++) if (*pos[i] > ',' && (s < 0 || start[i] < start[s])) s = i;
        const char kind = *pos[s]++;
        int it;
        if (kind == 'x') { it = nx < 12 ? T_B << 13 | (nx % 3 * 4 + nx / 3) << 4 : T_Q << 13 | (nx - 12) << 4; nx++; }
        else if (kind == 'c') { it = (T_K + (nc & 1)) << 13 | nc / 2 << 4; nc++; }
        else { it = T_LOCAL << 13 | nl / 2 << 4 | (nl & 1); nl++; }
        p.plan[s][len[s]++] = (uint16_t)it;
        start[s] += kind == 'x' ? 48 : kind == 'c' ? 24 : 8;
        if (kind == 'l') lend[(nl - 1) / 2] = start[s];
        if (kind == 'c' && (nc & 1) && nset < nl / 2 && start[s] >= lend[nset] + margin) p.kgroup[nc / 2] = (uint8_t)(G_B + 8 + 2 * nset++);
    }
    for (int i = 0; i < 24; i++) p.plan[8 + i / 12][i % 12] = (uint16_t)((T_K + (i % 3 & 1)) << 13 | i % 3 / 2 << 4 | i / 3);
    const int a0 = n;
    for (int key = 0; key < 4000; key++)
        for (int r = 0; r < 32; r++)
            for (int j = 7; j >= 0; j--)
                if ((j ? (7 - j) * 40 + r * beta : 3999) == key) add(T_ATTN, 2 * order[r >> 1] + (r & 1), j);
    int t0 = n;
    for (int work = 0; work < 32 * 136 * tail / 100;) work += 4 * (p.items[--t0] & 15) + 3;
    for (int i = t0 + 1; i < n; i++)
        for (int j = i; j > t0 && (p.items[j] & 15) > (p.items[j - 1] & 15); j--) { const uint16_t t = p.items[j]; p.items[j] = p.items[j - 1]; p.items[j - 1] = t; }
    for (int r = early - 1; r >= 0; r--) {
        const uint16_t t = p.items[n - 32 + early - 1];
        for (int j = n - 32 + early - 1; j > n - epos; j--) p.items[j] = p.items[j - 1];
        p.items[n - epos] = t;
    }
    for (int moved = 0; moved < 2 && late >= 0; moved++)
        for (int i = a0; i < n; i++)
            if (p.items[i] == (T_ATTN << 13 | (2 * order[15] + moved) << 4 | late)) {
                for (int j = i; j + 1 < n; j++) p.items[j] = p.items[j + 1];
                p.items[n - 1] = (uint16_t)(T_ATTN << 13 | (2 * order[15] + moved) << 4 | late);
                break;
            }
    for (int s = 0, lo = 0, hi = WIDE - 1; s < 80; s++) {
        const int r = s / 2, g = r < 8 ? 32 + r : 2 * order[r / 2 - 4] + (r & 1);
        p.ostep[s >= WIDE ? s : r & 1 ? hi-- : lo++] = (uint8_t)(2 * g + (s & 1));
    }
}

void build_params(Params& p, void* const* d_in, void* d_out) {
    void* fnp = nullptr;
    cudaDriverEntryPointQueryResult qr;
    cudaGetDriverEntryPoint("cuTensorMapEncodeTiled", &fnp, cudaEnableDefault, &qr);
    EncodeFn fn = (EncodeFn)fnp;
    void* scr = nullptr;
    cudaGetSymbolAddress(&scr, g_scr);
    map_act(fn, &p.m[M_X], d_in[0], SEQ, 1024, 128);
    map_act(fn, &p.m[M_C], d_in[1], SEQ, 512, 128);
    map_wgt(fn, &p.m[M_WQ], d_in[2], 1024, 4096);
    map_wgt(fn, &p.m[M_WUK], d_in[3], 512, 4096);
    map_wgt(fn, &p.m[M_WUV], d_in[4], 512, 4096);
    map_wgt(fn, &p.m[M_WO], d_in[5], 4096, 1024);
    map_wgt(fn, &p.m[M_WQKV], d_in[7], 1024, 3072);
    map_wgt(fn, &p.m[M_WOB], d_in[8], 1024, 1024);
    encode3(fn, &p.m[M_SCR_LD], scr, 128, SEQ, G_TOTAL, 256, (uint64_t)SEQ * 256, 64, 128, 1);
    encode3(fn, &p.m[M_SCR_LOC], scr, 256, SEQ / 2, G_TOTAL, 512, (uint64_t)SEQ * 256, 64, 72, 1);
    encode3(fn, &p.m[M_SCR_LOQ], scr, 256, SEQ / 2, G_TOTAL, 512, (uint64_t)SEQ * 256, 64, 64, 1);
    encode3(fn, &p.m[M_SCR_ST], scr, 128, SEQ, G_TOTAL, 256, (uint64_t)SEQ * 256, 64, 64, 1);
    map_act(fn, &p.m[M_OUT], d_out, SEQ, 1024, 64);
    p.x = (const __nv_bfloat16*)d_in[0];
    p.gate_w = (const __nv_bfloat16*)d_in[9];
    p.zero = 0;
    p.wo = (const char*)d_in[5];
    p.out = (__nv_bfloat16*)d_out;
    build_schedule(p);
}

}

extern "C" void kernel_launch(void* const* d_in, const int* in_sizes, int n_in, void* d_out, int out_size) {
    (void)in_sizes; (void)n_in; (void)out_size;
    Params p;
    build_params(p, d_in, d_out);
    cudaFuncSetAttribute(fused_kernel, cudaFuncAttributeMaxDynamicSharedMemorySize, SM_TOTAL);
    fused_kernel<<<NCTA, 384, SM_TOTAL>>>(p);
}
```
